```python
import torch

def _softmax(x, axis=-1):
    return torch.softmax(x, dim=axis)
def _gelu(x):
    return torch.nn.functional.gelu(x, approximate="tanh")
def _silu(x):
    return torch.nn.functional.silu(x)
def _sigmoid(x):
    return torch.sigmoid(x)
def _layernorm(x, axis=-1, eps=1e-5):
    m = x.mean(dim=axis, keepdim=True)
    v = x.var(dim=axis, keepdim=True, unbiased=False)
    return (x - m) / torch.sqrt(v + eps)
def _scatter_add(tgt, idx, src, axis=0):
    return tgt.clone().index_add_(axis, idx, src)
def _segment_sum(src, seg, n):
    out = torch.zeros((n,) + src.shape[1:], dtype=src.dtype)
    return out.index_add_(0, seg, src)
def _pad(x, pw):
    flat = tuple(v for pair in reversed(pw) for v in pair)
    return torch.nn.functional.pad(x, flat)

kernel_name = 'gated_mix__ssm_conv_s4__moe_arch_mod__prompt'

def setup_inputs():

    _w = (lambda a: (lambda t: t.to(torch.bfloat16) if t.is_floating_point() else t)(torch.as_tensor(a)))
    def _A_setup():
        B, L, D, N = 1, 2048, 576, 128
        A_re = -(lambda _x: torch.exp(torch.as_tensor(_x)))((lambda *s: torch.randn(*s, dtype=torch.bfloat16) * 3.2)(D, N))
        A_im = torch.pi * (lambda *s: torch.randn(*s, dtype=torch.bfloat16) * 0.05)(D, N)
        B_re = (lambda *s: torch.randn(*s, dtype=torch.bfloat16) * 0.2)(D, N)
        B_im = (lambda *s: torch.randn(*s, dtype=torch.bfloat16) * 0.2)(D, N)
        C_re = (lambda *s: torch.randn(*s, dtype=torch.bfloat16) * 0.2)(D, N)
        C_im = (lambda *s: torch.randn(*s, dtype=torch.bfloat16) * 0.2)(D, N)
        log_dt = (lambda *s: torch.randn(*s, dtype=torch.bfloat16) * 0.05)(D) * 0.5 - 4.0
        Dskip = (lambda *s: torch.randn(*s, dtype=torch.bfloat16) * 0.1)(D)
        return {
            "u": _w((lambda *s: torch.randn(*s, dtype=torch.bfloat16) * 0.05)(B, L, D)),
            "A_re": _w(A_re),
            "A_im": _w(A_im),
            "B_re": _w(B_re),
            "B_im": _w(B_im),
            "C_re": _w(C_re),
            "C_im": _w(C_im),
            "log_dt": _w(log_dt),
            "Dskip": _w(Dskip),
        }
    _A_in = _A_setup()

    def _B_setup():
        B, S, D, F, C = 1, 2048, 576, 4608, 8
        return {
            "x": _w((lambda *s: torch.randn(*s, dtype=torch.bfloat16) * 0.05)(B, S, D)),
            "w_r": _w((lambda *s: torch.randn(*s, dtype=torch.bfloat16) * 3.2)(D)),
            "w_gate": _w((lambda *s: torch.randn(*s, dtype=torch.bfloat16) * 0.1)(D, F)),
            "w_up": _w((lambda *s: torch.randn(*s, dtype=torch.bfloat16) * 0.1)(D, F)),
            "w_down": _w((lambda *s: torch.randn(*s, dtype=torch.bfloat16) * 0.1)(F, D)),
        }
    _B_in = _B_setup()

    return {
        "A_u": _A_in["u"],
        "A_A_re": _A_in["A_re"],
        "A_A_im": _A_in["A_im"],
        "A_B_re": _A_in["B_re"],
        "A_B_im": _A_in["B_im"],
        "A_C_re": _A_in["C_re"],
        "A_C_im": _A_in["C_im"],
        "A_log_dt": _A_in["log_dt"],
        "A_Dskip": _A_in["Dskip"],
        "B_x": _B_in["x"],
        "B_w_r": _B_in["w_r"],
        "B_w_gate": _B_in["w_gate"],
        "B_w_up": _B_in["w_up"],
        "B_w_down": _B_in["w_down"],
        "gate_w": _w((lambda *s: torch.randn(*s, dtype=torch.bfloat16) * 0.05)(576) * 16.0),
    }

def reference(A_u, A_A_re, A_A_im, A_B_re, A_B_im, A_C_re, A_C_im, A_log_dt, A_Dskip, B_x, B_w_r, B_w_gate, B_w_up, B_w_down, gate_w):
    def _A_ref(u, A_re, A_im, B_re, B_im, C_re, C_im, log_dt, Dskip):
        Bsz, L, D = u.shape
        dt = torch.exp(log_dt)[:, None]
        A = A_re + 1j * A_im
        Bc = B_re + 1j * B_im
        Cc = C_re + 1j * C_im
        logdA = dt * A
        dB = dt * Bc
        l = (lambda x, dt: x.to(dt))(torch.arange(L), A_re.dtype)
        P = torch.exp(logdA[:, :, None] * l[None, None, :])
        K = torch.einsum("dn,dnl,dn->dl", Cc, P, dB).real
        L2 = 2 * L
        Kp = _pad(K, ((0, 0), (0, L)))
        up = (lambda x, *d: x.permute(*d))(u, 0, 2, 1)
        up = _pad(up, ((0, 0), (0, 0), (0, L)))
        Kf = (lambda x, axes=(-2,-1): torch.fft.rfft2(x.float(), dim=axes))(Kp[:, None, :], axes=(-2, -1))
        Uf = (lambda x, axes=(-2,-1): torch.fft.rfft2(x.float(), dim=axes))(up[:, :, None, :], axes=(-2, -1))
        Yf = Uf * Kf[None, :, :, :]
        y = (lambda x, s, axes=(-2,-1): torch.fft.irfft2(x, s=s, dim=axes).to(torch.bfloat16))(Yf, (1, L2), axes=(-2, -1))[:, :, 0, :L]
        y = (lambda x, *d: x.permute(*d))(y, 0, 2, 1) + u * Dskip[None, None, :]
        return y

    def _B_ref(x, w_r, w_gate, w_up, w_down):
        B, S, D = x.shape
        C = 8
        r = x @ w_r
        idx = torch.argsort(-r, axis=-1)[:, :C]
        idx_e = (lambda x, n, axis: torch.repeat_interleave(x, n, dim=axis))(idx.reshape(B, C, 1), D, axis=2)
        x_sel = (lambda x, i, axis: torch.take_along_dim(x, i, dim=axis))(x, idx_e, axis=1)
        g = _silu(x_sel @ w_gate)
        u = x_sel @ w_up
        y = (g * u) @ w_down
        r_sel = _sigmoid((lambda x, i, axis: torch.take_along_dim(x, i, dim=axis))(r, idx, axis=1))
        y = y * r_sel.reshape(B, C, 1)
        b_off = (torch.arange(B) * S).reshape(B, 1)
        flat_idx = (idx + b_off).reshape(B * C)
        zero = (x * 0.0).reshape(B * S, D)
        upd = _scatter_add(zero, flat_idx, y.reshape(B * C, D), axis=0)
        return x + upd.reshape(B, S, D)

    x = A_u
    g = _sigmoid((x * gate_w).sum(-1, keepdims=True))
    a = _A_ref(x, A_A_re, A_A_im, A_B_re, A_B_im, A_C_re, A_C_im, A_log_dt, A_Dskip)
    b = _B_ref(x, B_w_r, B_w_gate, B_w_up, B_w_down)
    return g * a + (1 - g) * b
```

```cpp
#include <cuda_runtime.h>
#include <cuda_bf16.h>
#include <cuda_fp16.h>
#include <cuda.h>
#include <stdint.h>

#define WDELAY 2200
#define WGAP 620
#define DDELAY 7800
#define DGAP 230

namespace {

constexpr int DM = 576, NST = 128, FF = 4608, L_SEQ = 2048;
constexpr int NCONV = 72, NX = 36, NFFN = 60, NCTA = 132, NTHR = 512;

__device__ unsigned g_launch;
__device__ __align__(128) uint32_t g_keys[64 * 8];
__device__ __align__(128) uint32_t g_sel[18 * 8];
__device__ __align__(128) uint16_t g_gate[L_SEQ];
__device__ __align__(128) uint2 g_h[2 * 288 * 32];
#define TFLUSH()
#define TSTAMP(i)

struct Params {
    const __nv_bfloat16 *Are, *Aim, *Bre, *Bim, *Cre, *Cim, *logdt, *Dskip, *u, *wr, *gatew;
    __nv_bfloat16* out;
};

__device__ __forceinline__ uint32_t smem_u32(const void* p) { return (uint32_t)__cvta_generic_to_shared(p); }
__device__ __forceinline__ uint32_t pack_bf16(float lo, float hi) { uint32_t r; asm("cvt.rn.bf16x2.f32 %0, %1, %2;" : "=r"(r) : "f"(hi), "f"(lo)); return r; }
__device__ __forceinline__ uint32_t pack_f16(float lo, float hi) { uint32_t r; asm("cvt.rn.f16x2.f32 %0, %1, %2;" : "=r"(r) : "f"(hi), "f"(lo)); return r; }
__device__ __forceinline__ float bf_lo(uint32_t w) { return __uint_as_float(w << 16); }
__device__ __forceinline__ float bf_hi(uint32_t w) { return __uint_as_float(w & 0xffff0000u); }
__device__ __forceinline__ float rbf(float x) { return bf_lo(pack_bf16(x, 0.f)); }
__device__ __forceinline__ uint32_t badd2(uint32_t a, uint32_t b) { uint32_t r; asm("add.rn.bf16x2 %0, %1, %2;" : "=r"(r) : "r"(a), "r"(b)); return r; }
__device__ __forceinline__ uint32_t bsub2(uint32_t a, uint32_t b) { uint32_t r; asm("sub.rn.bf16x2 %0, %1, %2;" : "=r"(r) : "r"(a), "r"(b)); return r; }
__device__ __forceinline__ uint32_t gmix(uint32_t g, uint32_t y, uint32_t u) {
    uint32_t r; asm("{ .reg .b32 n, t; neg.bf16x2 n, %1; fma.rn.bf16x2 t, n, %3, %3; fma.rn.bf16x2 %0, %1, %2, t; }" : "=r"(r) : "r"(g), "r"(y), "r"(u)); return r;
}
__device__ __forceinline__ void mma_bf(float (&c)[4], uint32_t a0, uint32_t a1, uint32_t a2, uint32_t a3, uint32_t b0, uint32_t b1) {
    asm("mma.sync.aligned.m16n8k16.row.col.f32.bf16.bf16.f32 {%0,%1,%2,%3}, {%4,%5,%6,%7}, {%8,%9}, {%0,%1,%2,%3};"
        : "+f"(c[0]), "+f"(c[1]), "+f"(c[2]), "+f"(c[3]) : "r"(a0), "r"(a1), "r"(a2), "r"(a3), "r"(b0), "r"(b1));
}
__device__ __forceinline__ void mma_bf8(float (&c)[4], uint32_t a0, uint32_t a1, uint32_t b0) {
    asm("mma.sync.aligned.m16n8k8.row.col.f32.bf16.bf16.f32 {%0,%1,%2,%3}, {%4,%5}, {%6}, {%0,%1,%2,%3};"
        : "+f"(c[0]), "+f"(c[1]), "+f"(c[2]), "+f"(c[3]) : "r"(a0), "r"(a1), "r"(b0));
}
__device__ __forceinline__ void mma_h(float (&c)[4], uint32_t a0, uint32_t a1, uint32_t a2, uint32_t a3, uint32_t b0, uint32_t b1) {
    asm("mma.sync.aligned.m16n8k16.row.col.f32.f16.f16.f32 {%0,%1,%2,%3}, {%4,%5,%6,%7}, {%8,%9}, {%0,%1,%2,%3};"
        : "+f"(c[0]), "+f"(c[1]), "+f"(c[2]), "+f"(c[3]) : "r"(a0), "r"(a1), "r"(a2), "r"(a3), "r"(b0), "r"(b1));
}
__device__ __forceinline__ uint32_t fresh(uint32_t a) { asm volatile("" : "+r"(a) :: "memory"); return a; }
__device__ __forceinline__ uint32_t lds16(uint32_t a) { uint32_t v; asm("ld.shared.u16 %0, [%1];" : "=r"(v) : "r"(a)); return v; }
__device__ __forceinline__ uint32_t lds32(uint32_t a) { uint32_t v; asm("ld.shared.u32 %0, [%1];" : "=r"(v) : "r"(a)); return v; }
__device__ __forceinline__ uint2 lds64(uint32_t a) { uint2 v; asm("ld.shared.v2.u32 {%0,%1}, [%2];" : "=r"(v.x), "=r"(v.y) : "r"(a)); return v; }
__device__ __forceinline__ uint4 lds128(uint32_t a) { uint4 v; asm("ld.shared.v4.u32 {%0,%1,%2,%3}, [%4];" : "=r"(v.x), "=r"(v.y), "=r"(v.z), "=r"(v.w) : "r"(a)); return v; }
__device__ __forceinline__ uint4 lds128v(uint32_t a) { uint4 v; asm volatile("ld.shared.v4.u32 {%0,%1,%2,%3}, [%4];" : "=r"(v.x), "=r"(v.y), "=r"(v.z), "=r"(v.w) : "r"(a) : "memory"); return v; }
__device__ __forceinline__ void ldsm4(uint32_t (&r)[4], uint32_t a) {
    asm("ldmatrix.sync.aligned.m8n8.x4.shared.b16 {%0,%1,%2,%3}, [%4];" : "=r"(r[0]), "=r"(r[1]), "=r"(r[2]), "=r"(r[3]) : "r"(a));
}
__device__ __forceinline__ void ldsm4t(uint32_t (&r)[4], uint32_t a) {
    asm("ldmatrix.sync.aligned.m8n8.x4.trans.shared.b16 {%0,%1,%2,%3}, [%4];" : "=r"(r[0]), "=r"(r[1]), "=r"(r[2]), "=r"(r[3]) : "r"(a));
}
__device__ __forceinline__ void sts16(uint32_t a, uint32_t v) { asm volatile("st.shared.u16 [%0], %1;" :: "r"(a), "h"((unsigned short)v) : "memory"); }
__device__ __forceinline__ void sts32(uint32_t a, uint32_t v) { asm volatile("st.shared.u32 [%0], %1;" :: "r"(a), "r"(v) : "memory"); }
__device__ __forceinline__ void sts64(uint32_t a, uint32_t x, uint32_t y) { asm volatile("st.shared.v2.u32 [%0], {%1,%2};" :: "r"(a), "r"(x), "r"(y) : "memory"); }
__device__ __forceinline__ void sts128(uint32_t a, uint32_t x, uint32_t y, uint32_t z, uint32_t w) {
    asm volatile("st.shared.v4.u32 [%0], {%1,%2,%3,%4};" :: "r"(a), "r"(x), "r"(y), "r"(z), "r"(w) : "memory");
}
__device__ __forceinline__ void st_async128(uint32_t a, uint32_t x, uint32_t y, uint32_t z, uint32_t w, uint32_t bar) {
    asm volatile("st.async.weak.shared::cluster.mbarrier::complete_tx::bytes.v4.b32 [%0], {%1,%2,%3,%4}, [%5];" :: "r"(a), "r"(x), "r"(y), "r"(z), "r"(w), "r"(bar) : "memory");
}
__device__ __forceinline__ void mbar_init(uint32_t b, uint32_t cnt) { asm volatile("mbarrier.init.shared::cta.b64 [%0], %1;" :: "r"(b), "r"(cnt) : "memory"); }
__device__ __forceinline__ void mbar_fence() { asm volatile("fence.mbarrier_init.release.cluster;" ::: "memory"); }
__device__ __forceinline__ void mbar_expect(uint32_t b, uint32_t bytes) { asm volatile("mbarrier.arrive.expect_tx.shared::cta.b64 _, [%0], %1;" :: "r"(b), "r"(bytes) : "memory"); }
__device__ __forceinline__ void mbar_arrive(uint32_t b) { asm volatile("mbarrier.arrive.shared::cta.b64 _, [%0];" :: "r"(b) : "memory"); }
__device__ __forceinline__ void mbar_wait(uint32_t b, uint32_t parity = 0) {
    asm volatile("{ .reg .pred p; .reg .u32 n; mov.u32 n, 0;\n"
                 "LW: mbarrier.try_wait.parity.shared::cta.b64 p, [%0], %1; @p bra LD; add.u32 n, n, 1; setp.lt.u32 p, n, 4194304; @p bra LW; trap;\n"
                 "LD: }" :: "r"(b), "r"(parity) : "memory");
}
__device__ __forceinline__ void mbar_wait_cluster(uint32_t b) {
    asm volatile("{ .reg .pred p; .reg .u32 n; mov.u32 n, 0;\n"
                 "LW: mbarrier.try_wait.parity.acquire.cluster.shared::cta.b64 p, [%0], 0; @p bra LD; add.u32 n, n, 1; setp.lt.u32 p, n, 4194304; @p bra LW; trap;\n"
                 "LD: }" :: "r"(b) : "memory");
}
__device__ __forceinline__ void tma2d(uint32_t dst, const CUtensorMap* m, int c0, int c1, uint32_t bar) {
    asm volatile("cp.async.bulk.tensor.2d.shared::cluster.global.mbarrier::complete_tx::bytes [%0], [%1, {%3, %4}], [%2];"
                 :: "r"(dst), "l"(m), "r"(bar), "r"(c0), "r"(c1) : "memory");
}
__device__ __forceinline__ void tma3d(uint32_t dst, const CUtensorMap* m, int c0, int c1, int c2, uint32_t bar) {
    asm volatile("cp.async.bulk.tensor.3d.shared::cluster.global.mbarrier::complete_tx::bytes [%0], [%1, {%3, %4, %5}], [%2];"
                 :: "r"(dst), "l"(m), "r"(bar), "r"(c0), "r"(c1), "r"(c2) : "memory");
}
__device__ __forceinline__ void tma4d(uint32_t dst, const CUtensorMap* m, int c0, int c1, int c2, int c3, uint32_t bar) {
    asm volatile("cp.async.bulk.tensor.4d.shared::cluster.global.mbarrier::complete_tx::bytes [%0], [%1, {%3, %4, %5, %6}], [%2];"
                 :: "r"(dst), "l"(m), "r"(bar), "r"(c0), "r"(c1), "r"(c2), "r"(c3) : "memory");
}
__device__ __forceinline__ void bulk_g2s(uint32_t dst, const void* src, uint32_t bytes, uint32_t bar) {
    asm volatile("cp.async.bulk.shared::cluster.global.mbarrier::complete_tx::bytes [%0], [%1], %2, [%3];"
                 :: "r"(dst), "l"(src), "r"(bytes), "r"(bar) : "memory");
}
__device__ __forceinline__ uint32_t mapa(uint32_t a, uint32_t rank) { uint32_t r; asm("mapa.shared::cluster.u32 %0, %1, %2;" : "=r"(r) : "r"(a), "r"(rank)); return r; }
__device__ __forceinline__ void prefetch_map(const CUtensorMap* m) { asm volatile("prefetch.tensormap [%0];" :: "l"(m) : "memory"); }
__device__ __forceinline__ void bar_sync(int id, int n) { asm volatile("bar.sync %0, %1;" :: "r"(id), "r"(n) : "memory"); }
__device__ __forceinline__ void bar_arrive(int id, int n) { asm volatile("bar.arrive %0, %1;" :: "r"(id), "r"(n) : "memory"); }
__device__ __forceinline__ void fence_gpu() { asm volatile("fence.acq_rel.gpu;" ::: "memory"); }
__device__ __forceinline__ uint32_t ldg16(const void* p) { uint32_t v; asm volatile("ld.global.nc.u16 %0, [%1];" : "=r"(v) : "l"(p)); return v; }
__device__ __forceinline__ uint32_t ldg32(const void* p) { uint32_t v; asm volatile("ld.global.nc.u32 %0, [%1];" : "=r"(v) : "l"(p)); return v; }
__device__ __forceinline__ uint32_t ld_rlx32(const void* p) { uint32_t v; asm volatile("ld.relaxed.gpu.global.u32 %0, [%1];" : "=r"(v) : "l"(p) : "memory"); return v; }
__device__ __forceinline__ uint4 ld_rlx128(const void* p) {
    uint4 v; asm volatile("ld.relaxed.gpu.global.v4.u32 {%0,%1,%2,%3}, [%4];" : "=r"(v.x), "=r"(v.y), "=r"(v.z), "=r"(v.w) : "l"(p) : "memory"); return v;
}
__device__ __forceinline__ void st_rlx32(void* p, uint32_t v) { asm volatile("st.relaxed.gpu.global.u32 [%0], %1;" :: "l"(p), "r"(v) : "memory"); }
__device__ __forceinline__ void stg128(void* p, uint32_t x, uint32_t y, uint32_t z, uint32_t w) {
    asm volatile("st.global.v4.u32 [%0], {%1,%2,%3,%4};" :: "l"(p), "r"(x), "r"(y), "r"(z), "r"(w) : "memory");
}
__device__ __forceinline__ unsigned take_ticket() { unsigned v; asm volatile("atom.relaxed.gpu.global.add.u32 %0, [%1], 1;" : "=r"(v) : "l"(&g_launch) : "memory"); return v; }
__device__ __forceinline__ unsigned clock32() { unsigned c; asm volatile("mov.u32 %0, %clock;" : "=r"(c) :: "memory"); return c; }
__device__ __forceinline__ void until(unsigned t0, unsigned c) { while (clock32() - t0 < c) { } }
__device__ __forceinline__ float sigmoidf_(float x) { return __fdividef(1.0f, 1.0f + __expf(-x)); }
__device__ __forceinline__ uint32_t key_tag(unsigned ticket) { return (((ticket / NCTA) & 15u) | 16u) << 11; }
__device__ __forceinline__ int key_row(uint32_t key) { return 2047 - (int)(key & 2047u); }
__device__ __forceinline__ uint32_t wait_sel(int s32, int r8, uint32_t tag) {
    uint32_t k;
    for (int it = 0;; it++) {
        k = ld_rlx32(&g_sel[s32 * 8 + r8]);
        if (__all_sync(0xffffffffu, (k & 0xf800u) == tag)) break;
        if (it > (1 << 20)) __trap();
    }
    fence_gpu();
    return k;
}

struct cplx { float re, im; };
__device__ __forceinline__ cplx csq(cplx a) { cplx r; r.re = a.re * a.re - a.im * a.im; r.im = 2.f * a.re * a.im; return r; }
__device__ __forceinline__ cplx cexpk(float ar, float ai, float k) {
    float mag, s, c;
    asm("ex2.approx.ftz.f32 %0, %1;" : "=f"(mag) : "f"(ar * (k * 1.4426950408889634f)));
    const float r = ai * k;
    asm("sin.approx.ftz.f32 %0, %1;" : "=f"(s) : "f"(r));
    asm("cos.approx.ftz.f32 %0, %1;" : "=f"(c) : "f"(r));
    cplx o; o.re = mag * c; o.im = mag * s; return o;
}
struct h2c { uint32_t re, im; };
__device__ __forceinline__ h2c cmul_cd(h2c v, __half2 c, __half2 d) {
    const __half2 r = *(const __half2*)&v.re, i = *(const __half2*)&v.im;
    const __half2 x = __hfma2(__hneg2(i), d, __hmul2(r, c)), y = __hfma2(i, c, __hmul2(r, d));
    h2c o; o.re = *(const uint32_t*)&x; o.im = *(const uint32_t*)&y; return o;
}
__device__ __forceinline__ h2c cmul_s(h2c v, uint32_t s) { const __half2 h = *(const __half2*)&s; return cmul_cd(v, __low2half2(h), __high2half2(h)); }
__device__ __forceinline__ h2c cmul_sc(h2c v, uint32_t s) {
    const __half2 h = *(const __half2*)&s, c = __low2half2(h), d = __high2half2(h), r = *(const __half2*)&v.re, i = *(const __half2*)&v.im;
    const __half2 x = __hfma2(i, d, __hmul2(r, c)), y = __hfma2(__hneg2(r), d, __hmul2(i, c));
    h2c o; o.re = *(const uint32_t*)&x; o.im = *(const uint32_t*)&y; return o;
}
__device__ __forceinline__ h2c cmul_vc(h2c v, uint32_t s) {
    const __half2 h = *(const __half2*)&s, c = __low2half2(h), d = __high2half2(h), r = *(const __half2*)&v.re, i = *(const __half2*)&v.im;
    const __half2 x = __hfma2(i, d, __hmul2(r, c)), y = __hfma2(__hneg2(i), c, __hmul2(r, d));
    h2c o; o.re = *(const uint32_t*)&x; o.im = *(const uint32_t*)&y; return o;
}

constexpr int UT_HALF = 2240, UT_STRIDE = 4448;
constexpr int KT_T = 542, KT_C = 552, KT_D = 648, KT_BYTES = 720 * 4;
constexpr int VC_OFF = 80, VE_BASE = 1616;
constexpr int V_STRIDE = (1616 + 1024) * 4 + 80;
constexpr int KG_STAGE = 5248;
constexpr int Y_CS = 2080, Y_RS = 8 * Y_CS + 64;

constexpr int SC_RT = 0;
constexpr int SC_UT = 33408;
constexpr int SC_ST = SC_UT + 8 * UT_STRIDE;
constexpr int SC_KT = SC_ST + 8 * UT_STRIDE;
constexpr int SC_GT = SC_KT + 8 * KT_BYTES;
constexpr int SC_V = SC_GT + UT_STRIDE;
constexpr int SC_MISC = SC_V + 8 * V_STRIDE;
static_assert(V_STRIDE % 128 == 16 && 16 * KG_STAGE <= 8 * V_STRIDE && 2 * Y_RS <= SC_UT && SC_UT % 128 == 0, "layout");
static_assert(SC_MISC % 16 == 0 && SC_MISC + 512 <= 232192, "layout");

__device__ __forceinline__ void window_task(uint32_t ut, uint32_t vt, int a, bool withE) {
    const uint32_t src = ut + (a + 6) * 16;
    float S[35];
    {
        uint32_t w[20];
#pragma unroll
        for (int i = 0; i < 5; i++) {
            const uint4 v = lds128(src + ((i & 1) ? 0 : UT_HALF) + ((i + 1) >> 1) * 16);
            w[4 * i] = v.x; w[4 * i + 1] = v.y; w[4 * i + 2] = v.z; w[4 * i + 3] = v.w;
        }
        float s = 0.f; S[2] = 0.f;
#pragma unroll
        for (int i = 3; i < 26; i++) { s += (i & 1) ? bf_hi(w[i >> 1]) : bf_lo(w[i >> 1]); S[i] = s; }
        const uint32_t dst = vt + (VC_OFF - 16 + 16 * a) * 4;
#pragma unroll
        for (int i = 0; i < 16; i += 4)
            sts128(dst + 4 * i, pack_bf16(S[10 + i] - S[5 + i], S[5 + i] - S[2 + i]), pack_bf16(S[11 + i] - S[6 + i], S[6 + i] - S[3 + i]),
                   pack_bf16(S[12 + i] - S[7 + i], S[7 + i] - S[4 + i]), pack_bf16(S[13 + i] - S[8 + i], S[8 + i] - S[5 + i]));
        if (withE) {
#pragma unroll
            for (int i = 26; i < 35; i++) { s += (i & 1) ? bf_hi(w[i >> 1]) : bf_lo(w[i >> 1]); S[i] = s; }
            const uint32_t dse = vt + (VE_BASE + 16 * a) * 4;
#pragma unroll
            for (int i = 0; i < 16; i += 4)
                sts128(dse + 4 * i, pack_bf16(S[19 + i] - S[12 + i], S[12 + i] - S[3 + i]), pack_bf16(S[20 + i] - S[13 + i], S[13 + i] - S[4 + i]),
                       pack_bf16(S[21 + i] - S[14 + i], S[14 + i] - S[5 + i]), pack_bf16(S[22 + i] - S[15 + i], S[15 + i] - S[6 + i]));
        }
    }
}

__device__ __forceinline__ void conv_cta(const Params& p, const CUtensorMap* mU, uint32_t sb, int warp, int lane, int bid) {
    const int g = lane >> 2, t = lane & 3, mi = lane >> 3, r8 = lane & 7;
    const int rank = bid & 1, slab = bid >> 1;
    const uint32_t bar_box = sb + SC_MISC, bar_u = bar_box + 32, bar_y = bar_box + 40, s_tk = bar_box + 72, s_bm = bar_box + 128;

    {
        const int ch = 8 * blockIdx.x + (threadIdx.x >> 6), q = warp & 1;
        const int o = 8 * NST * blockIdx.x + 2 * threadIdx.x;
        const uint32_t pAr = ldg32(p.Are + o), pAi = ldg32(p.Aim + o), pBr = ldg32(p.Bre + o), pBi = ldg32(p.Bim + o), pCr = ldg32(p.Cre + o), pCi = ldg32(p.Cim + o);
        const uint32_t pDt = ldg16(p.logdt + ch), pD = ldg16(p.Dskip + ch);
        unsigned ticket = 0;
        if (lane == 0) {
            if (warp < 9) {
                mbar_init(bar_box + 8 * warp, 1); mbar_fence();
                mbar_expect(bar_box + 8 * warp, warp == 4 ? 16384 : 8192);
                if (warp < 4) tma4d(sb + SC_RT + 8192 * warp, mU, 16 * slab, 0, 0, 32 * rank + 8 * warp, bar_box + 8 * warp);
            } else if (warp == 9) ticket = take_ticket();
        }
        __syncwarp();
        asm volatile("barrier.cluster.arrive.relaxed.aligned;" ::: "memory");
        if (lane < 30) {
            const uint32_t a = sb + SC_KT + warp * (KT_BYTES / 2) + lane * 16;
            sts128(a, 0, 0, 0, 0); sts128(a + 480, 0, 0, 0, 0); sts128(a + 960, 0, 0, 0, 0);
        }
        sts128(lane < 16 ? sb + SC_UT + warp * UT_STRIDE + mi * UT_HALF + r8 * 16 : s_bm + (lane - 16) * 16, 0, 0, 0, 0);
        if (warp == 0) TSTAMP(1);

        const float dt = rbf(__expf(bf_lo(pDt)));
        float ar = dt * bf_lo(pAr), ai = dt * bf_lo(pAi), ar1 = dt * bf_hi(pAr), ai1 = dt * bf_hi(pAi);
        float wr, wi, wr1, wi1;
        { const float br = dt * bf_lo(pBr), bi = dt * bf_lo(pBi), cr = bf_lo(pCr), ci = bf_lo(pCi); wr = cr * br - ci * bi; wi = cr * bi + ci * br; }
        { const float br = dt * bf_hi(pBr), bi = dt * bf_hi(pBi), cr = bf_hi(pCr), ci = bf_hi(pCi); wr1 = cr * br - ci * bi; wi1 = cr * bi + ci * br; }
        const uint32_t ex = max(__reduce_max_sync(0xffffffffu, __float_as_uint(fmaxf(fmaxf(fabsf(wr), fabsf(wi)), fmaxf(fabsf(wr1), fabsf(wi1))))) >> 23, 14u);
        const float scl = __uint_as_float((267u - ex) << 23);
        uint32_t W = pack_f16(wr * scl, wi * -scl);
        const uint32_t W1 = pack_f16(wr1 * scl, wi1 * -scl);
        if (warp == 0) TSTAMP(2);

        const uint32_t stage = sb + SC_V + warp * KG_STAGE;
        float acc[6][4];
#pragma unroll
        for (int a = 0; a < 6; a++) { acc[a][0] = acc[a][1] = acc[a][2] = acc[a][3] = 0.f; }
#pragma unroll 1
        for (int r = 0; r < 2; r++) {
            const cplx z1 = cexpk(ar, ai, 1.f), z64 = cexpk(ar, ai, 64.f);
            const cplx z2 = csq(z1), z4 = csq(z2), z8 = csq(z4), z16 = csq(z8), z32 = csq(z16);
            const cplx z128 = csq(z64), z256 = csq(z128), z512 = csq(z256), z1024 = csq(z512);
            const uint32_t wb = stage + lane * 16;
            auto put = [&](int grp, h2c a, h2c b, h2c c, h2c d) { sts128(wb + grp * 1024, a.re, b.re, c.re, d.re); sts128(wb + grp * 1024 + 512, a.im, b.im, c.im, d.im); };
            {
                const uint32_t s1 = pack_f16(z1.re, z1.im), s2 = pack_f16(z2.re, z2.im), s256 = pack_f16(z256.re, z256.im), s512 = pack_f16(z512.re, z512.im), s1024 = pack_f16(z1024.re, z1024.im);
                const h2c c04 = cmul_vc(h2c{pack_f16(1.f, z4.re), pack_f16(0.f, z4.im)}, W), c26 = cmul_sc(c04, s2);
                put(2, c04, c26, cmul_sc(c04, s1), cmul_sc(c26, s1));
                const h2c d04 = cmul_sc(c04, s256), e04 = cmul_sc(c04, s512), f04 = cmul_sc(d04, s512);
                put(3, d04, cmul_sc(c26, s256), e04, f04);
                const h2c ef = {__byte_perm(e04.re, f04.re, 0x5410), __byte_perm(e04.im, f04.im, 0x5410)};
                const h2c gh = cmul_sc(ef, s512);
                put(4, gh, cmul_sc(ef, s1024), cmul_sc(gh, s1024), ef);
            }
            {
                const uint32_t s32 = pack_f16(z32.re, z32.im), s64 = pack_f16(z64.re, z64.im), s128 = pack_f16(z128.re, z128.im);
                const h2c p0 = {pack_f16(1.f, z8.re), pack_f16(0.f, z8.im)}, p1 = cmul_s(p0, pack_f16(z16.re, z16.im)), p2 = cmul_s(p0, s32), p3 = cmul_s(p1, s32);
                put(0, p0, p1, p2, p3);
                put(1, cmul_s(p0, s64), cmul_s(p1, s64), cmul_s(p2, s64), cmul_s(p3, s64));
                const uint32_t za = stage + 5120 + ((lane >> 1) & 3) * 16 + mi * 4 + (lane & 1) * 2;
                sts16(za, s128); sts16(za + 64, s128 >> 16);
            }
            if (r == 1) {
                if (warp == 0) TSTAMP(3);
                asm volatile("barrier.cluster.wait.acquire.aligned;" ::: "memory");
                mbar_wait(bar_box + 8 * (warp >> 2));
                if (warp == 0) TSTAMP(4);
                if (warp == 15) TSTAMP(5);
                const uint32_t src = fresh(sb + SC_RT) + warp * 2048 + (8 * mi + 4 * (r8 & 1) + (r8 >> 1)) * 32 + ((rank ^ (r8 & 1)) << 4);
                const uint32_t dst = sb + SC_UT + g * UT_STRIDE + (t & 1) * UT_HALF + (8 + 64 * rank + 4 * warp + (t >> 1)) * 16;
                const uint32_t rdst = mapa(dst, rank ^ 1), rbar = mapa(bar_u, rank ^ 1);
                uint32_t x[4][4];
                ldsm4t(x[0], src); ldsm4t(x[1], src + 1024); ldsm4t(x[2], src ^ 16); ldsm4t(x[3], (src ^ 16) + 1024);
                sts128(dst, x[0][0], x[0][1], x[0][2], x[0][3]); sts128(dst + 32, x[1][0], x[1][1], x[1][2], x[1][3]);
                st_async128(rdst, x[2][0], x[2][1], x[2][2], x[2][3], rbar); st_async128(rdst + 32, x[3][0], x[3][1], x[3][2], x[3][3], rbar);
            }
            __syncwarp();
            {
                const uint32_t sf = fresh(stage);
                const uint32_t aA = sf + (mi & 1) * 1024 + (mi >> 1) * 512 + r8 * 16, aB = sf + 2048 + mi * 512 + r8 * 16, aC = sf + 4096 + (mi & 1) * 512 + (mi >> 1) * 128 + r8 * 16;
                const uint4 zc = lds128(sf + 5120 + t * 16), zd = lds128(sf + 5184 + t * 16);
                const uint32_t zcs[4] = {zc.x, zc.y, zc.z, zc.w}, zds[4] = {zd.x, zd.y, zd.z, zd.w};
                uint32_t c[4];
#pragma unroll
                for (int k = 0; k < 4; k++) {
                    uint32_t a[4], b[4];
                    ldsm4t(a, aA + 128 * k); ldsm4t(b, aB + 128 * k);
                    if (!(k & 1)) ldsm4t(c, aC + 128 * k);
                    const h2c x = cmul_cd(h2c{a[0], a[2]}, *(const __half2*)&zcs[k], *(const __half2*)&zds[k]), y = cmul_cd(h2c{a[1], a[3]}, *(const __half2*)&zcs[k], *(const __half2*)&zds[k]);
                    mma_h(acc[0], a[0], a[1], a[2], a[3], b[0], b[1]);
                    mma_h(acc[1], a[0], a[1], a[2], a[3], b[2], b[3]);
                    mma_h(acc[2], a[0], a[1], a[2], a[3], c[2 * (k & 1)], c[2 * (k & 1) + 1]);
                    mma_h(acc[3], x.re, y.re, x.im, y.im, b[0], b[1]);
                    mma_h(acc[4], x.re, y.re, x.im, y.im, b[2], b[3]);
                    mma_h(acc[5], x.re, y.re, x.im, y.im, c[2 * (k & 1)], c[2 * (k & 1) + 1]);
                }
                asm volatile("" :: "f"(acc[0][0]), "f"(acc[1][0]), "f"(acc[2][0]), "f"(acc[3][0]), "f"(acc[4][0]), "f"(acc[5][0]) : "memory");
            }
            __syncwarp();
            ar = ar1; ai = ai1; W = W1;
        }
        if (warp == 0) TSTAMP(6);
#pragma unroll
        for (int a = 0; a < 6; a++) sts128(stage + a * 512 + lane * 16, __float_as_uint(acc[a][0]), __float_as_uint(acc[a][1]), __float_as_uint(acc[a][2]), __float_as_uint(acc[a][3]));
        sts32(stage + 5120, (ex - 13u) << 23);
        bar_sync(1 + (warp >> 1), 64);
        const uint32_t st0 = fresh(stage - q * KG_STAGE), kt = sb + SC_KT + (warp >> 1) * KT_BYTES;
        const uint32_t kd = st0 + 3088;
        {
            const float i0 = __uint_as_float(lds32(st0 + 5120)), i1 = __uint_as_float(lds32(st0 + KG_STAGE + 5120));
            const int rho = 16 * q + g;
            uint4 xs[3], ys[3];
#pragma unroll
            for (int nu = 0; nu < 3; nu++) { xs[nu] = lds128v(st0 + (3 * q + nu) * 512 + lane * 16); ys[nu] = lds128v(st0 + KG_STAGE + (3 * q + nu) * 512 + lane * 16); }
#pragma unroll
            for (int nu = 0; nu < 3; nu++) {
                const uint4 x = xs[nu], y = ys[nu];
                float v0 = __uint_as_float(x.x) * i0 + __uint_as_float(y.x) * i1;
                const float v1 = __uint_as_float(x.y) * i0 + __uint_as_float(y.y) * i1, v2 = __uint_as_float(x.z) * i0 + __uint_as_float(y.z) * i1, v3 = __uint_as_float(x.w) * i0 + __uint_as_float(y.w) * i1;
                uint32_t a, a0, de, dr;
                if (nu == 0) { a = kd + (8 * rho + 2 * (t & 1) + (t >> 1)) * 2; de = 8; dr = 128; a0 = a; if (rho + t == 0) v0 += bf_lo(pD); }
                else if (nu == 1) { a = t < 2 ? kd + (256 + 4 * rho + t) * 2 : kt + KT_C * 4 + (64 * t - 100 + 2 * rho) * 2; de = t < 2 ? 4 : 2; dr = t < 2 ? 64 : 32; a0 = a; }
                else {
                    a = t < 2 ? kt + KT_D * 4 + (13 + 64 * t + rho) * 2 : st0 + 4096; de = 64; dr = 16; a0 = a;
                    if (rho == 0 && !(t & 1)) a0 = kt + (t ? KT_D * 4 + 141 * 2 : KT_C * 4 + 156 * 2);
                }
                const uint32_t w01 = pack_bf16(v0, v1), w23 = pack_bf16(v2, v3);
                sts16(a0, w01); sts16(a + de, w01 >> 16); sts16(a + dr, w23); sts16(a + dr + de, w23 >> 16);
                if (nu == 2 && rho + t == 0) sts128(kt + (KT_T + 2) * 4, 0, w01 & 0xffffu, __byte_perm(w01, 0, 0x1010), w01 << 16);
            }
        }
        bar_sync(1 + (warp >> 1), 64);
        {
            const uint32_t kf = fresh(kd);
            uint32_t w0, w1, w2, w3, pv = lds16(kf + (q ? 512 : 16 * lane) - 2);
            if (q == 0) { const uint4 v = lds128(kf + 16 * lane); w0 = v.x; w1 = v.y; w2 = v.z; w3 = v.w; if (lane == 0) pv = 0; }
            else {
                const uint2 v = lds64(kf + 512 + 8 * lane);
                const uint32_t c4 = lds16(lane == 31 ? fresh(kt) + KT_C * 4 + 28 * 2 : kf + 520 + 8 * lane);
                w0 = __byte_perm(v.x, 0, 0x1010); w1 = __byte_perm(v.x, v.y, 0x5432); w2 = __byte_perm(v.y, 0, 0x1010); w3 = __byte_perm(v.y, c4, 0x5432);
                if (lane == 31) w3 = bsub2(w3, __byte_perm(c4, 0, 0x1010));
                if (lane) pv = v.x;
            }
            const uint32_t d = kt + (16 + 256 * q + 8 * lane) * 4;
            sts128(d, __byte_perm(w0, pv, 0x5410), __byte_perm(w0, 0, 0x1032), __byte_perm(w1, w0, 0x7610), __byte_perm(w1, 0, 0x1032));
            sts128(d + 16, __byte_perm(w2, w1, 0x7610), __byte_perm(w2, 0, 0x1032), __byte_perm(w3, w2, 0x7610), __byte_perm(w3, 0, 0x1032));
        }
        if (warp == 9 && lane == 0) sts32(s_tk, ticket);
    }
    if (warp == 0) TSTAMP(7);
    bar_sync(0, NTHR);
    mbar_wait_cluster(bar_u);
    if (warp == 0) TSTAMP(8);

    if (warp >= 8) {
        asm volatile("setmaxnreg.dec.sync.aligned.u32 88;");
        const int aw = warp - 8;
        if (lane < 16) sts128(sb + SC_V + aw * V_STRIDE + lane * 16, 0, 0, 0, 0);
        {
            const int c = 4 * (aw & 1) + t;
            const uint32_t ut = fresh(sb + SC_UT) + c * UT_STRIDE, vt = sb + SC_V + c * V_STRIDE;
#pragma unroll 1
            for (int a = 8 * (aw >> 1) + g; a < 97; a += 32) window_task(ut, vt, a, a < 64);
        }
        __syncwarp();
        if (aw == 0) TSTAMP(9);
        const unsigned ticket = lds32(fresh(s_tk));
        if (aw == 7) {
            const int row = key_row(wait_sel(slab >> 1, r8, key_tag(ticket)));
            if (lane < 8) asm volatile("red.shared.or.b32 [%0], %1;" :: "r"(s_bm + (row >> 5) * 4), "r"(1u << (row & 31)) : "memory");
            TSTAMP(10);
        }
        {
            const uint32_t par = ((ticket / NCTA) & 1) ? 0u : 0x80008000u;
            uint4 v;
            for (int it = 0;; it++) {
                v = ld_rlx128(g_gate + 256 * aw + 8 * lane);
                v.x ^= par; v.y ^= par; v.z ^= par; v.w ^= par;
                if (__all_sync(0xffffffffu, ((v.x | v.y | v.z | v.w) & 0x80008000u) == 0)) break;
                if (it > (1 << 20)) __trap();
            }
            sts128(sb + SC_GT + (lane & 1) * UT_HALF + (8 + 16 * aw + (lane >> 1)) * 16, v.x, v.y, v.z, v.w);
        }
        bar_sync(0, NTHR);
        const uint32_t src = sb + SC_RT + ((r8 >> 1) & 1) * Y_RS + (2 * mi + (r8 & 1)) * Y_CS + (2 * aw + (r8 >> 2)) * 16;
        const int L = 2 * aw + (t >> 1);
        const int row0 = 256 * rank + 128 * (g >> 2) + 32 * (L & 3) + 16 * (g & 1) + 8 * ((g >> 1) & 1) + (L >> 2);
        __nv_bfloat16* outp = p.out + (size_t)row0 * DM + 16 * slab + 8 * (t & 1);
#pragma unroll 1
        for (int s = 0; s < 4; s++) {
            const uint32_t bm = lds32(fresh(s_bm) + (16 * s + (row0 >> 5)) * 4) >> (row0 & 31);
            mbar_wait_cluster(bar_y + 8 * s);
            const uint32_t sf = fresh(src) + 512 * s;
#pragma unroll
            for (int k = 0; k < 2; k++) {
                uint32_t y[4];
                ldsm4t(y, sf + 256 * k);
                __nv_bfloat16* o = outp + (size_t)(512 * s + 4 * k) * DM;
                if (bm & (1u << (4 * k)))
                    asm volatile("red.relaxed.gpu.global.add.noftz.v4.bf16x2 [%0], {%1,%2,%3,%4};" :: "l"(o), "r"(y[0]), "r"(y[1]), "r"(y[2]), "r"(y[3]) : "memory");
                else stg128(o, y[0], y[1], y[2], y[3]);
            }
            if (aw == 0) TSTAMP(16 + s);
        }
        if (aw == 0) TFLUSH();
    } else {
        asm volatile("setmaxnreg.inc.sync.aligned.u32 168;");
        const uint32_t ut = fresh(sb + SC_UT) + warp * UT_STRIDE, kt = fresh(sb + SC_KT) + warp * KT_BYTES;
        {
            const uint32_t a = ut + (mi & 1) * UT_HALF + (64 * (mi >> 1) + r8) * 16;
            uint4 v = lds128(a);
#pragma unroll
            for (int i = 1; i <= 8; i++) {
                const uint4 w = lds128(a + 128 * i);
                sts128(a + 128 * i + (SC_ST - SC_UT), badd2(v.x, w.x), badd2(v.y, w.y), badd2(v.z, w.z), badd2(v.w, w.w));
                v = w;
            }
        }
        const uint32_t u1 = ut + (mi & 1) * UT_HALF + (8 + r8) * 16 + (mi >> 1) * 128;
        const uint32_t kb = kt + (16 + g - 2 * t) * 4, kz = kb + (lds32(kt) >> 1);
        float acc[16][4];
        {
            const uint32_t c0 = lds32(kb + 2048), c1 = lds32(kb + 2080), c2 = lds32(kb + 2016), c3 = lds32(kz + 2048);
            const uint32_t e0 = lds32(kb + (KT_T - 16) * 4), e1 = lds32(kb + (KT_T - 8) * 4), e2 = lds32(kb + (KT_T - 24) * 4), e3 = lds32(kz + (KT_T - 16) * 4);
            const uint32_t f0 = lds32(kz + (KT_T - 8) * 4), f1 = lds32(kb + KT_T * 4);
            const uint32_t uo = ut + UT_HALF + (7 + lane) * 16;
#pragma unroll
            for (int i = 0; i < 16; i++) { acc[i][0] = acc[i][1] = acc[i][2] = acc[i][3] = 0.f; }
#pragma unroll
            for (int mu = 0; mu < 8; mu += 4) {
                uint32_t b[4];
                ldsm4(b, uo + 128 * mu);
#pragma unroll
                for (int k = 0; k < 4; k++) mma_bf8(acc[mu + 8 + k], f0, f1, b[k]);
            }
#pragma unroll
            for (int mu = 0; mu < 12; mu += 2) {
                uint32_t b[4];
                ldsm4(b, u1 + 128 * mu);
                mma_bf(acc[mu + 4], c0, c1, c2, c3, b[0], b[1]);
                mma_bf(acc[mu + 5], c0, c1, c2, c3, b[2], b[3]);
                if (mu < 8) { mma_bf(acc[mu + 8], e0, e1, e2, e3, b[0], b[1]); mma_bf(acc[mu + 9], e0, e1, e2, e3, b[2], b[3]); }
            }
        }
        __syncwarp();
        {
            float M[8][4];
#pragma unroll
            for (int i = 0; i < 8; i++) { M[i][0] = M[i][1] = M[i][2] = M[i][3] = 0.f; }
            const uint32_t s1 = fresh(u1) + (SC_ST - SC_UT);
#pragma unroll 1
            for (int j0 = 0; j0 < 8; j0++) {
                const uint32_t kp = kb + 64 * j0, kq = kz + 64 * j0, sp = s1 - 16 * j0, up = u1 + (mi >> 1) * 128 - 16 * j0;
                uint32_t a[4][4], d[2][4];
#pragma unroll
                for (int j = 0; j < 4; j++) { a[j][0] = lds32(kp + 512 * j); a[j][1] = lds32(kp + 512 * j + 32); a[j][2] = lds32(kp + 512 * j - 32); a[j][3] = lds32(kq + 512 * j); }
#pragma unroll
                for (int c = 0; c < 2; c++)
#pragma unroll
                    for (int e = 0; e < 4; e++) d[c][e] = bsub2(a[2 * c][e], a[2 * c + 1][e]);
                uint32_t b[4];
#pragma unroll
                for (int i = 0; i < 8; i++) {
                    uint32_t s[4];
                    ldsm4(s, sp + 256 * i);
                    if (!(i & 1)) ldsm4(b, up + 256 * i);
                    const uint32_t b0 = b[2 * (i & 1)], b1 = b[2 * (i & 1) + 1];
                    if (i < 7) {
                        mma_bf(acc[2 * i + 2], a[3][0], a[3][1], a[3][2], a[3][3], s[0], s[1]);
                        mma_bf(acc[2 * i + 3], a[2][0], a[2][1], a[2][2], a[2][3], s[2], s[3]);
                        mma_bf(M[i + 1], d[1][0], d[1][1], d[1][2], d[1][3], b0, b1);
                    }
                    mma_bf(acc[2 * i], a[1][0], a[1][1], a[1][2], a[1][3], s[0], s[1]);
                    mma_bf(acc[2 * i + 1], a[0][0], a[0][1], a[0][2], a[0][3], s[2], s[3]);
                    mma_bf(M[i], d[0][0], d[0][1], d[0][2], d[0][3], b0, b1);
                }
            }
#pragma unroll
            for (int i = 0; i < 8; i++)
#pragma unroll
                for (int c = 0; c < 4; c++) { acc[2 * i][c] += M[i][c]; acc[2 * i + 1][c] -= M[i][c]; }
        }
        if (warp == 0) TSTAMP(11);
        bar_sync(0, NTHR);
        if (warp == 0) TSTAMP(12);
        const uint32_t vt = fresh(sb + SC_V) + warp * V_STRIDE;
        const uint32_t g1 = fresh(u1) - ut + sb + SC_GT;
        const uint32_t ydst = sb + SC_RT + rank * Y_RS + warp * Y_CS + lane * 16;
        const uint32_t yd0 = mapa(ydst, 0), yd1 = mapa(ydst, 1), yb0 = mapa(bar_y, 0), yb1 = mapa(bar_y, 1);
        auto ship = [&](int i) {
            uint32_t u[4], gg[4];
            ldsm4t(u, u1 + 256 * i); ldsm4t(gg, g1 + 256 * i);
            st_async128(((i & 1) ? yd1 : yd0) + 512 * (i >> 1),
                        gmix(gg[0], pack_bf16(acc[2 * i][0], acc[2 * i][1]), u[0]), gmix(gg[1], pack_bf16(acc[2 * i][2], acc[2 * i][3]), u[1]),
                        gmix(gg[2], pack_bf16(acc[2 * i + 1][0], acc[2 * i + 1][1]), u[2]), gmix(gg[3], pack_bf16(acc[2 * i + 1][2], acc[2 * i + 1][3]), u[3]),
                        ((i & 1) ? yb1 : yb0) + 8 * (i >> 1));
        };
        ship(0);
        {
            const uint32_t KE = kt + (KT_D + g + t) * 4, VE = vt + (VE_BASE - 912 + g - 16 * t) * 4;
            uint32_t b0[8], b1[8];
#pragma unroll
            for (int s = 0; s < 8; s++) { b0[s] = lds32(KE + 32 * s); b1[s] = lds32(KE + 32 * s + 16); }
#pragma unroll
            for (int dl = 8; dl < 16; dl++) {
                const uint32_t vp = VE + 512 * dl;
                const uint32_t x0 = lds32(vp), x1 = lds32(vp + 32), x2 = lds32(vp - 256), x3 = lds32(vp - 224);
#pragma unroll
                for (int s = 0; s < 8; s++) if (dl + s < 16) mma_bf(acc[dl + s], x0, x1, x2, x3, b0[s], b1[s]);
            }
        }
        if (warp == 0) TSTAMP(13);
        {
            const uint32_t KD = kt + (KT_C + 2 * g + t) * 4, VD = vt + (VC_OFF - 400 + g - 8 * t) * 4;
            uint32_t b0[10], b1[10];
#pragma unroll
            for (int s = 0; s < 10; s++) { b0[s] = lds32(KD + 32 * s); b1[s] = lds32(KD + 32 * s + 16); }
#pragma unroll
            for (int dl = 6; dl <= 30; dl++) {
                const uint32_t vp = VD + 256 * dl;
                const uint32_t x0 = lds32(vp), x1 = lds32(vp + 32), x2 = lds32(vp - 128), x3 = lds32(vp - 96);
#pragma unroll
                for (int s = dl & 1; s < 10; s += 2) if ((dl + s) / 2 < 16) mma_bf(acc[(dl + s) / 2], x0, x1, x2, x3, b0[s], b1[s]);
                if ((dl & 3) == 2) ship((dl - 2) / 4);
            }
        }
        if (warp == 0) TSTAMP(14);
        if (warp == 7) TSTAMP(15);
    }
}

constexpr int SF_WD = 147456;
constexpr int SF_H = 81920;
constexpr int SF_RED = 131072;
constexpr int SF_XS = 221184;
constexpr int SF_MISC = SF_XS + 8 * 1168;
enum { BAR_R = 1, BAR_GU = 2, BAR_RED = 3 };

__device__ __forceinline__ void ffn_cta(const Params& p, const CUtensorMap* maps, uint32_t sb, int warp, int lane, int bid) {
    const unsigned t0 = clock32();
    const int g = lane >> 2, t = lane & 3, mi = lane >> 3, r8 = lane & 7;
    const int f = bid - NCONV;
    const bool isx = f < NX;
    const int nrw = f < 8 ? 6 : 4, r0 = f < 8 ? 48 * f : 128 + 32 * f;
    const uint32_t bar_row = sb + SF_MISC  , bar_x = bar_row + 64, bar_rdone = bar_row + 72, bar_free = bar_row + 80;
    const uint32_t bar_w = bar_row + 128  , bar_d = bar_row + 256  , bar_h = bar_row + 384  ;
    const uint32_t s_part = bar_row + 512  , s_tok = bar_row + 896  , s_tk = bar_row + 960;
    const uint32_t rows = sb + SF_XS - 9216 * (warp + 1);
    if (lane == 0) {
        mbar_init(bar_row + 8 * warp, warp == 9 ? nrw : warp == 10 ? 4 : 1); mbar_fence();
        if (warp < nrw) { mbar_expect(bar_row + 8 * warp, 9216); bulk_g2s(rows, p.u + (size_t)(r0 + 8 * warp) * DM, 9216, bar_row + 8 * warp); }
        else if ((warp >> 1) == 3) { mbar_expect(bar_row + 8 * warp, 1152); bulk_g2s(sb + SF_XS + (warp & 1) * 1152, (warp & 1) ? p.gatew : p.wr, 1152, bar_row + 8 * warp); }
        mbar_init(bar_w + 8 * warp, 1); mbar_init(bar_d + 8 * warp, 1); mbar_init(bar_h + 8 * warp, 1); mbar_fence();
    }
    const int ks0 = isx ? 4 * f : 6 * f - 72, nt = isx ? 4 : 6;
    unsigned ticket = 0;
    if (warp == 15) {
        if (lane == 0) ticket = take_ticket();
        if (lane < 8) st_rlx32(&g_keys[f * 8 + lane], 0);
        else if (lane < 16 && isx && !(f & 1)) st_rlx32(&g_sel[4 * f + lane - 8], 0);
    }
    if (warp < nt) stg128((uint4*)(g_h + ((lane >> 4) * 288 + ks0 + warp) * 32) + (lane & 15), 0, 0, 0, 0);
    __syncwarp();
    bar_sync(0, NTHR);
    if (warp == 0) TSTAMP(1);

    if (warp == 13) {
        if (lane == 0) {
            const CUtensorMap* m = maps + (isx ? 1 : 3);
            prefetch_map(m); prefetch_map(m + 1);
#pragma unroll 1
            for (int n = 0; n < 9; n++) {
                until(t0, WDELAY + n * WGAP);
                if (n == 7) mbar_wait(bar_rdone);
                mbar_expect(bar_w + 8 * n, nt * 4096);
                tma3d(sb + n * nt * 4096, m, 0, 64 * n, ks0 >> 1, bar_w + 8 * n);
                tma3d(sb + n * nt * 4096 + nt * 2048, m + 1, 0, 64 * n, ks0 >> 1, bar_w + 8 * n);
            }
            TSTAMP(12);
        }
    } else if (warp == 14) {
        if (lane == 0 && isx) {
            prefetch_map(maps + 5);
            mbar_wait(bar_rdone);
#pragma unroll 1
            for (int n = 0; n < 12; n++) {
                until(t0, DDELAY + n * DGAP);
                if (n == 6) mbar_wait(bar_free);
                mbar_expect(bar_d + 8 * n, 12288);
                tma2d(sb + (n < 6 ? SF_WD : -6 * 12288) + n * 12288, maps + 5, 32 * (f >> 1), 2304 * (f & 1) + 192 * n, bar_d + 8 * n);
            }
            TSTAMP(13);
        }
    } else if (warp == 15) {
        ticket = __shfl_sync(0xffffffffu, ticket, 0);
        sts32(s_tk, ((ticket / NCTA) & 1) * 288);
        const uint32_t tag = key_tag(ticket), par = ((ticket / NCTA) & 1) ? 0u : 0x8000u;
        bar_sync(BAR_R, 32 * (nrw + 1));
        TSTAMP(3);
        uint32_t k[16];
        k[0] = 0;
#pragma unroll 1
        for (int rr = lane + (nrw > 4 ? 32 : 0); rr >= 0; rr -= 32) {
            k[1] = k[0]; k[0] = 0;
            if (rr < 48) {
                const uint2 v = lds64(fresh(s_part) + rr * 8);
                const uint32_t gb = pack_bf16(sigmoidf_(rbf(__uint_as_float(v.y))), 0.f) | par;
                asm volatile("st.relaxed.gpu.global.u16 [%0], %1;" :: "l"(g_gate + r0 + rr), "h"((unsigned short)gb) : "memory");
                const uint32_t rb = pack_bf16(0.f, __uint_as_float(v.x));
                k[0] = (rb ^ (((int)rb >> 31) & 0x7fff0000u) ^ 0x80000000u) | tag | (uint32_t)(2047 - r0 - rr);
            }
        }
        uint32_t key = 0;
#pragma unroll 1
        for (int r = 0; r < 8; r++) {
            const uint32_t m = __reduce_max_sync(0xffffffffu, max(k[0], k[1]));
            if (k[0] == m) k[0] = 0;
            if (k[1] == m) k[1] = 0;
            if (lane == r) key = m;
        }
        if (lane < 8) st_rlx32(&g_keys[f * 8 + lane], key);
        TSTAMP(4);
        for (int it = 0;; it++) {
            uint32_t bad = 0;
#pragma unroll
            for (int h = 0; h < 2; h++) {
                const uint32_t* src = &g_keys[min(lane + 32 * h, NFFN - 1) * 8];
                const uint4 x = ld_rlx128(src), y = ld_rlx128(src + 4);
                k[h] = x.x; k[2 + h] = x.y; k[4 + h] = x.z; k[6 + h] = x.w; k[8 + h] = y.x; k[10 + h] = y.y; k[12 + h] = y.z; k[14 + h] = y.w;
            }
#pragma unroll
            for (int i = 0; i < 16; i++) bad |= k[i] ^ tag;
            if (__all_sync(0xffffffffu, (bad & 0xf800u) == 0)) break;
            if (it > (1 << 20)) __trap();
        }
        TSTAMP(5);
#pragma unroll 1
        for (int r = 0; r < 8; r++) {
            const uint32_t m = __reduce_max_sync(0xffffffffu, max(k[0], k[1]));
            const bool pa = k[0] == m, pb = k[1] == m;
#pragma unroll
            for (int i = 0; i < 7; i++) { k[2 * i] = pa ? k[2 * i + 2] : k[2 * i]; k[2 * i + 1] = pb ? k[2 * i + 3] : k[2 * i + 1]; }
            if (r8 == r) key = m;
        }
        const int row = key_row(key);
        if (lane == 0) mbar_expect(bar_x, 8 * 1152);
        __syncwarp();
        if (lane < 8) bulk_g2s(sb + SF_XS + lane * 1168, p.u + (size_t)row * DM, 1152, bar_x);
        TSTAMP(6);
        if (isx) {
            if (!(f & 1)) {
                stg128(p.out + (size_t)row * DM + 16 * f + 8 * mi, 0, 0, 0, 0);
                fence_gpu();
                __syncwarp();
                if (lane < 8) st_rlx32(&g_sel[4 * f + lane], key);
            }
            wait_sel(f >> 1, r8, tag);
            uint32_t gb;
            for (int it = 0;; it++) {
                asm volatile("ld.relaxed.gpu.global.u16 %0, [%1];" : "=r"(gb) : "l"(g_gate + row) : "memory");
                gb ^= par;
                if (!(gb & 0x8000u)) break;
                if (it > (1 << 20)) __trap();
            }
            const uint32_t rb = key ^ 0x80000000u, rv = (rb ^ (((int)rb >> 31) & 0x7fff0000u)) & 0xffff0000u;
            sts64(s_tok + r8 * 8, row, __float_as_uint(rbf(1.0f - bf_lo(gb)) * rbf(sigmoidf_(__uint_as_float(rv)))));
            __syncwarp();
            TSTAMP(7);
            bar_arrive(BAR_RED, 416);
        }
    } else if (warp < 12) {
        if (warp < nrw) {
            float c[2][4];
#pragma unroll
            for (int i = 0; i < 2; i++) { c[i][0] = c[i][1] = c[i][2] = c[i][3] = 0.f; }
            mbar_wait(bar_row + 48); mbar_wait(bar_row + 56);
            const uint32_t b = fresh(sb + SF_XS) + (g & 1) * 1152 + (g >> 2) * 64 + t * 16 + (g & 2) * 2;
            uint32_t w[18][2];
#pragma unroll
            for (int kb = 0; kb < 18; kb++) { const uint32_t o = ((kb & 1) ? b ^ 64 : b) + 128 * (kb >> 1); w[kb][0] = lds32(o); w[kb][1] = lds32(o + 8); }
            mbar_wait(bar_row + 8 * warp);
            if (warp == 0) TSTAMP(2);
            const uint32_t a = fresh(rows) + g * 1152 + (g & 1) * 64 + t * 16;
#pragma unroll
            for (int kb = 0; kb < 18; kb++) {
                const uint4 x = lds128(((kb & 1) ? a ^ 64 : a) + 128 * (kb >> 1));
                mma_bf(c[kb & 1], x.x, x.y, x.z, x.w, w[kb][0], w[kb][1]);
            }
            const float sr = c[0][0] + c[1][0] + __shfl_down_sync(0xffffffffu, c[0][2] + c[1][2], 1);
            const float sg = c[0][1] + c[1][1] + __shfl_down_sync(0xffffffffu, c[0][3] + c[1][3], 1);
            if (t == 2 * (g & 1)) sts64(s_part + (8 * warp + g) * 8, __float_as_uint(sr), __float_as_uint(sg));
            __syncwarp();
            bar_arrive(BAR_R, 32 * (nrw + 1));
            if (lane == 0) mbar_arrive(bar_rdone);
        }
        if (warp < nt) {
            float ag[2][4], au[2][4];
#pragma unroll
            for (int i = 0; i < 2; i++) { ag[i][0] = ag[i][1] = ag[i][2] = ag[i][3] = 0.f; au[i][0] = au[i][1] = au[i][2] = au[i][3] = 0.f; }
            const uint32_t wb = sb + (warp >> 1) * 4096 + (r8 + 8 * (mi >> 1)) * 64 + (((2 * (warp & 1) + (mi & 1)) ^ (r8 >> 1)) << 4);
            const uint32_t xb = sb + SF_XS + r8 * 1168 + mi * 16;
            mbar_wait(bar_x);
            if (warp == 0) TSTAMP(8);
#pragma unroll 1
            for (int n = 0; n < 9; n++) {
                mbar_wait(bar_w + 8 * n);
                const uint32_t wk = fresh(wb) + n * nt * 4096, xk = fresh(xb) + 128 * n;
                uint32_t x[4];
#pragma unroll
                for (int s = 0; s < 4; s++) {
                    uint32_t a[4], b[4];
                    if (!(s & 1)) ldsm4(x, xk + 32 * s);
                    ldsm4t(a, wk + 1024 * s); ldsm4t(b, wk + 1024 * s + nt * 2048);
                    mma_bf(ag[s & 1], a[0], a[1], a[2], a[3], x[2 * (s & 1)], x[2 * (s & 1) + 1]);
                    mma_bf(au[s & 1], b[0], b[1], b[2], b[3], x[2 * (s & 1)], x[2 * (s & 1) + 1]);
                }
                asm volatile("" :: "f"(ag[0][0]), "f"(ag[1][0]), "f"(au[0][0]), "f"(au[1][0]) : "memory");
                if (n == 4 && lane == 0 && isx) mbar_arrive(bar_free);
            }
            if (warp == 0) TSTAMP(9);
            float h[4];
#pragma unroll
            for (int c = 0; c < 4; c++) {
                const float gv = rbf(ag[0][c] + ag[1][c]);
                h[c] = rbf(gv * sigmoidf_(gv)) * rbf(au[0][c] + au[1][c]);
            }
            uint32_t h0, h1;
            asm("movmatrix.sync.aligned.m8n8.trans.b16 %0, %1;" : "=r"(h0) : "r"(pack_bf16(h[0], h[1])));
            asm("movmatrix.sync.aligned.m8n8.trans.b16 %0, %1;" : "=r"(h1) : "r"(pack_bf16(h[2], h[3])));
            if (h0 == 0) h0 = 0x8000u;
            asm volatile("{ .reg .b64 v; mov.b64 v, {%1, %2}; st.relaxed.gpu.global.b64 [%0], v; }" :: "l"(g_h + (lds32(fresh(s_tk)) + ks0 + warp) * 32 + lane), "r"(h0), "r"(h1) : "memory");
        }
        if (isx) {
            bar_sync(BAR_GU, 384);
            if (warp == 0) TSTAMP(10);
            uint2 hb[12];
            const uint32_t hs = sb + SF_H + warp * 3072;
            const uint2* hsrc = g_h + (__shfl_sync(0xffffffffu, lds32(fresh(s_tk)), 0) + 144 * (f & 1) + 12 * warp) * 32;
            for (int it = 0;; it++) {
                if (lane == 0) { mbar_expect(bar_h + 8 * warp, 3072); bulk_g2s(hs, hsrc, 3072, bar_h + 8 * warp); }
                mbar_wait(bar_h + 8 * warp, it & 1);
                const uint32_t hf = fresh(hs) + lane * 8;
                uint32_t mn = 0xffffffffu;
#pragma unroll
                for (int s = 0; s < 12; s++) { hb[s] = lds64(hf + 256 * s); mn = min(mn, hb[s].x); }
                if (__all_sync(0xffffffffu, mn != 0)) break;
                if (it > (1 << 16)) __trap();
            }
            if (warp == 0) TSTAMP(11);
            mbar_wait(bar_d + 8 * warp);
            if (warp == 11) TSTAMP(14);
            float ad[2][2][4];
#pragma unroll
            for (int i = 0; i < 4; i++) { ad[i >> 1][i & 1][0] = ad[i >> 1][i & 1][1] = ad[i >> 1][i & 1][2] = ad[i >> 1][i & 1][3] = 0.f; }
            const uint32_t wd = fresh(sb) + (warp < 6 ? SF_WD : -6 * 12288) + warp * 12288 + (r8 + 8 * (mi >> 1)) * 64 + (((mi & 1) ^ (r8 >> 1)) << 4);
#pragma unroll
            for (int s = 0; s < 12; s++) {
                uint32_t a[4], b[4];
                ldsm4t(a, wd + 1024 * s); ldsm4t(b, (wd ^ 32) + 1024 * s);
                mma_bf(ad[0][s & 1], a[0], a[1], a[2], a[3], hb[s].x, hb[s].y);
                mma_bf(ad[1][s & 1], b[0], b[1], b[2], b[3], hb[s].x, hb[s].y);
            }
            const uint32_t rd = sb + SF_RED + warp * 1152 + (72 * t + g) * 4;
#pragma unroll
            for (int i = 0; i < 8; i++) sts32(rd + (i >> 2) * 64 + (i & 1) * 144 + ((i >> 1) & 1) * 32, __float_as_uint(ad[i >> 2][0][i & 3] + ad[i >> 2][1][i & 3]));
            bar_sync(BAR_RED, 416);
            if (warp < 4) {
                const int tid = 32 * warp + lane;
                const uint32_t rs = fresh(sb + SF_RED) + (tid >> 4) * 144 + (tid & 15) * 8;
                const uint2 tk = lds64(fresh(s_tok) + (tid >> 4) * 8);
                float x = 0.f, y = 0.f;
#pragma unroll
                for (int w = 0; w < 12; w++) { const uint2 v = lds64(rs + w * 1152); x += __uint_as_float(v.x); y += __uint_as_float(v.y); }
                asm volatile("red.relaxed.gpu.global.add.noftz.bf16x2 [%0], %1;" :: "l"(p.out + (size_t)tk.x * DM + 32 * (f >> 1) + 2 * (tid & 15)),
                             "r"(pack_bf16(x * __uint_as_float(tk.y), y * __uint_as_float(tk.y))) : "memory");
            }
            if (warp == 0) TSTAMP(15);
        }
        if (warp == 0) TFLUSH();
    }
}

constexpr int SMEM_BYTES = 232448;
static_assert(SF_MISC + 1024 <= 232192, "layout");

struct Maps { CUtensorMap m[6]; };

__global__ void __cluster_dims__(2, 1, 1) __launch_bounds__(NTHR, 1)
fused_kernel(const Params p, const __grid_constant__ Maps maps) {
    extern __shared__ __align__(1024) uint8_t smem_raw[];
    const uint32_t sb = __shfl_sync(0xffffffffu, smem_u32(smem_raw), 0);
    const int warp = __shfl_sync(0xffffffffu, threadIdx.x >> 5, 0), bid = __shfl_sync(0xffffffffu, blockIdx.x, 0);
    const int lane = __shfl_sync(0xffffffffu, threadIdx.x & 31, threadIdx.x);
    if (blockIdx.x < NCONV) conv_cta(p, maps.m, sb, warp, lane, bid);
    else ffn_cta(p, maps.m, sb, warp, lane, bid);
}

typedef CUresult (*EncodeFn)(CUtensorMap*, CUtensorMapDataType, cuuint32_t, void*, const cuuint64_t*, const cuuint64_t*, const cuuint32_t*, const cuuint32_t*,
                             CUtensorMapInterleave, CUtensorMapSwizzle, CUtensorMapL2promotion, CUtensorMapFloatOOBfill);

void make_map(EncodeFn fn, CUtensorMap* m, const void* base, int rank, const cuuint64_t* dims, const cuuint64_t* strides, const cuuint32_t* box, CUtensorMapSwizzle sw) {
    const cuuint32_t es[4] = {1, 1, 1, 1};
    fn(m, CU_TENSOR_MAP_DATA_TYPE_BFLOAT16, rank, (void*)base, dims, strides, box, es, CU_TENSOR_MAP_INTERLEAVE_NONE, sw,
       CU_TENSOR_MAP_L2_PROMOTION_NONE, CU_TENSOR_MAP_FLOAT_OOB_FILL_NONE);
}

}

extern "C" void kernel_launch(void* const* d_in, const int* in_sizes, int n_in, void* d_out, int out_size) {
    (void)in_sizes; (void)n_in; (void)out_size;
    static EncodeFn fn = nullptr;
    if (!fn) {
        void* ptr = nullptr; cudaDriverEntryPointQueryResult qr;
        cudaGetDriverEntryPoint("cuTensorMapEncodeTiled", &ptr, cudaEnableDefault, &qr);
        fn = (EncodeFn)ptr;
        cudaFuncSetAttribute(fused_kernel, cudaFuncAttributeMaxDynamicSharedMemorySize, SMEM_BYTES);
    }
    typedef const __nv_bfloat16* bp;
    Params p;
    p.u = (bp)d_in[0]; p.Are = (bp)d_in[1]; p.Aim = (bp)d_in[2]; p.Bre = (bp)d_in[3]; p.Bim = (bp)d_in[4]; p.Cre = (bp)d_in[5]; p.Cim = (bp)d_in[6];
    p.logdt = (bp)d_in[7]; p.Dskip = (bp)d_in[8]; p.wr = (bp)d_in[10]; p.gatew = (bp)d_in[14];
    p.out = (__nv_bfloat16*)d_out;
    Maps maps;
    {
        const cuuint64_t dims[4] = {DM, 4, 8, 64}, strides[3] = {8 * DM * 2, DM * 2, 32 * DM * 2};
        const cuuint32_t box[4] = {16, 4, 8, 8};
        make_map(fn, &maps.m[0], d_in[0], 4, dims, strides, box, CU_TENSOR_MAP_SWIZZLE_32B);
    }
    for (int i = 0; i < 4; i++) {
        const cuuint64_t dims[3] = {32, DM, FF / 32}, strides[2] = {FF * 2, 64};
        const cuuint32_t box[3] = {32, 64, i < 2 ? 2u : 3u};
        make_map(fn, &maps.m[1 + i], d_in[11 + (i & 1)], 3, dims, strides, box, CU_TENSOR_MAP_SWIZZLE_64B);
    }
    {
        const cuuint64_t dims[2] = {DM, FF}, strides[1] = {DM * 2};
        const cuuint32_t box[2] = {32, 192};
        make_map(fn, &maps.m[5], d_in[13], 2, dims, strides, box, CU_TENSOR_MAP_SWIZZLE_64B);
    }
    fused_kernel<<<NCTA, NTHR, SMEM_BYTES>>>(p, maps);
}
```

```cpp
#include <cuda_runtime.h>
#include <cuda_bf16.h>
#include <cuda_fp16.h>
#include <cuda.h>
#include <stdint.h>

#define UDELAY 0
#define RDELAY 0
#define WDELAY 2200
#define WGAP 620
#define DDELAY 7800
#define DGAP 230

namespace {

constexpr int DM = 576, NST = 128, FF = 4608, L_SEQ = 2048;
constexpr int NCONV = 72, NX = 36, NFFN = 60, NCTA = 132, NTHR = 512;

struct __align__(128) Scratch {
    unsigned epoch[NCTA * 16];
    uint32_t keys[64 * 8];
    uint32_t sel[20 * 8];
    uint16_t gate[L_SEQ];
    uint2 h[2 * 288 * 32];
    uint4 kp[288 * 128];
};
__device__ Scratch g_scratch;
#define TFLUSH()
#define TSTAMP(i)

struct Params {
    const __nv_bfloat16 *Are, *Aim, *Bre, *Bim, *Cre, *Cim, *logdt, *Dskip, *u, *wr, *gatew;
    __nv_bfloat16* out;
    Scratch* s;
};

__device__ __forceinline__ uint32_t smem_u32(const void* p) { return (uint32_t)__cvta_generic_to_shared(p); }
__device__ __forceinline__ uint32_t pack_bf16(float lo, float hi) { uint32_t r; asm("cvt.rn.bf16x2.f32 %0, %1, %2;" : "=r"(r) : "f"(hi), "f"(lo)); return r; }
__device__ __forceinline__ uint32_t pack_f16(float lo, float hi) { uint32_t r; asm("cvt.rn.f16x2.f32 %0, %1, %2;" : "=r"(r) : "f"(hi), "f"(lo)); return r; }
__device__ __forceinline__ float bf_lo(uint32_t w) { return __uint_as_float(w << 16); }
__device__ __forceinline__ float bf_hi(uint32_t w) { return __uint_as_float(w & 0xffff0000u); }
__device__ __forceinline__ float rbf(float x) { return bf_lo(pack_bf16(x, 0.f)); }
__device__ __forceinline__ uint32_t badd2(uint32_t a, uint32_t b) { uint32_t r; asm("add.rn.bf16x2 %0, %1, %2;" : "=r"(r) : "r"(a), "r"(b)); return r; }
__device__ __forceinline__ uint32_t bsub2(uint32_t a, uint32_t b) { uint32_t r; asm("sub.rn.bf16x2 %0, %1, %2;" : "=r"(r) : "r"(a), "r"(b)); return r; }
__device__ __forceinline__ uint32_t gmix(uint32_t g, uint32_t y, uint32_t u) {
    uint32_t r; asm("{ .reg .b32 n, t; neg.bf16x2 n, %1; fma.rn.bf16x2 t, n, %3, %3; fma.rn.bf16x2 %0, %1, %2, t; }" : "=r"(r) : "r"(g), "r"(y), "r"(u)); return r;
}
__device__ __forceinline__ void mma_bf(float (&c)[4], uint32_t a0, uint32_t a1, uint32_t a2, uint32_t a3, uint32_t b0, uint32_t b1) {
    asm("mma.sync.aligned.m16n8k16.row.col.f32.bf16.bf16.f32 {%0,%1,%2,%3}, {%4,%5,%6,%7}, {%8,%9}, {%0,%1,%2,%3};"
        : "+f"(c[0]), "+f"(c[1]), "+f"(c[2]), "+f"(c[3]) : "r"(a0), "r"(a1), "r"(a2), "r"(a3), "r"(b0), "r"(b1));
}
__device__ __forceinline__ void mma_bf8(float (&c)[4], uint32_t a0, uint32_t a1, uint32_t b0) {
    asm("mma.sync.aligned.m16n8k8.row.col.f32.bf16.bf16.f32 {%0,%1,%2,%3}, {%4,%5}, {%6}, {%0,%1,%2,%3};"
        : "+f"(c[0]), "+f"(c[1]), "+f"(c[2]), "+f"(c[3]) : "r"(a0), "r"(a1), "r"(b0));
}
__device__ __forceinline__ void mma_h(float (&c)[4], uint32_t a0, uint32_t a1, uint32_t a2, uint32_t a3, uint32_t b0, uint32_t b1) {
    asm("mma.sync.aligned.m16n8k16.row.col.f32.f16.f16.f32 {%0,%1,%2,%3}, {%4,%5,%6,%7}, {%8,%9}, {%0,%1,%2,%3};"
        : "+f"(c[0]), "+f"(c[1]), "+f"(c[2]), "+f"(c[3]) : "r"(a0), "r"(a1), "r"(a2), "r"(a3), "r"(b0), "r"(b1));
}
__device__ __forceinline__ uint32_t fresh(uint32_t a) { asm volatile("" : "+r"(a) :: "memory"); return a; }
__device__ __forceinline__ uint32_t lds16(uint32_t a) { uint32_t v; asm("ld.shared.u16 %0, [%1];" : "=r"(v) : "r"(a)); return v; }
__device__ __forceinline__ uint32_t lds32(uint32_t a) { uint32_t v; asm("ld.shared.u32 %0, [%1];" : "=r"(v) : "r"(a)); return v; }
__device__ __forceinline__ uint2 lds64(uint32_t a) { uint2 v; asm("ld.shared.v2.u32 {%0,%1}, [%2];" : "=r"(v.x), "=r"(v.y) : "r"(a)); return v; }
__device__ __forceinline__ uint4 lds128(uint32_t a) { uint4 v; asm("ld.shared.v4.u32 {%0,%1,%2,%3}, [%4];" : "=r"(v.x), "=r"(v.y), "=r"(v.z), "=r"(v.w) : "r"(a)); return v; }
__device__ __forceinline__ uint4 lds128v(uint32_t a) { uint4 v; asm volatile("ld.shared.v4.u32 {%0,%1,%2,%3}, [%4];" : "=r"(v.x), "=r"(v.y), "=r"(v.z), "=r"(v.w) : "r"(a) : "memory"); return v; }
__device__ __forceinline__ void ldsm4(uint32_t (&r)[4], uint32_t a) {
    asm("ldmatrix.sync.aligned.m8n8.x4.shared.b16 {%0,%1,%2,%3}, [%4];" : "=r"(r[0]), "=r"(r[1]), "=r"(r[2]), "=r"(r[3]) : "r"(a));
}
__device__ __forceinline__ void ldsm4t(uint32_t (&r)[4], uint32_t a) {
    asm("ldmatrix.sync.aligned.m8n8.x4.trans.shared.b16 {%0,%1,%2,%3}, [%4];" : "=r"(r[0]), "=r"(r[1]), "=r"(r[2]), "=r"(r[3]) : "r"(a));
}
__device__ __forceinline__ void sts16(uint32_t a, uint32_t v) { asm volatile("st.shared.u16 [%0], %1;" :: "r"(a), "h"((unsigned short)v) : "memory"); }
__device__ __forceinline__ void sts32(uint32_t a, uint32_t v) { asm volatile("st.shared.u32 [%0], %1;" :: "r"(a), "r"(v) : "memory"); }
__device__ __forceinline__ void sts64(uint32_t a, uint32_t x, uint32_t y) { asm volatile("st.shared.v2.u32 [%0], {%1,%2};" :: "r"(a), "r"(x), "r"(y) : "memory"); }
__device__ __forceinline__ void sts128(uint32_t a, uint32_t x, uint32_t y, uint32_t z, uint32_t w) {
    asm volatile("st.shared.v4.u32 [%0], {%1,%2,%3,%4};" :: "r"(a), "r"(x), "r"(y), "r"(z), "r"(w) : "memory");
}
__device__ __forceinline__ void st_async128(uint32_t a, uint32_t x, uint32_t y, uint32_t z, uint32_t w, uint32_t bar) {
    asm volatile("st.async.weak.shared::cluster.mbarrier::complete_tx::bytes.v4.b32 [%0], {%1,%2,%3,%4}, [%5];" :: "r"(a), "r"(x), "r"(y), "r"(z), "r"(w), "r"(bar) : "memory");
}
__device__ __forceinline__ void mbar_init(uint32_t b, uint32_t cnt) { asm volatile("mbarrier.init.shared::cta.b64 [%0], %1;" :: "r"(b), "r"(cnt) : "memory"); }
__device__ __forceinline__ void mbar_fence() { asm volatile("fence.mbarrier_init.release.cluster;" ::: "memory"); }
__device__ __forceinline__ void mbar_expect(uint32_t b, uint32_t bytes) { asm volatile("mbarrier.arrive.expect_tx.shared::cta.b64 _, [%0], %1;" :: "r"(b), "r"(bytes) : "memory"); }
__device__ __forceinline__ void mbar_arrive(uint32_t b) { asm volatile("mbarrier.arrive.shared::cta.b64 _, [%0];" :: "r"(b) : "memory"); }
__device__ __forceinline__ void mbar_wait(uint32_t b, uint32_t parity = 0) {
    asm volatile("{ .reg .pred p; .reg .u32 n; mov.u32 n, 0;\n"
                 "LW: mbarrier.try_wait.parity.shared::cta.b64 p, [%0], %1; @p bra LD; add.u32 n, n, 1; setp.lt.u32 p, n, 4194304; @p bra LW; trap;\n"
                 "LD: }" :: "r"(b), "r"(parity) : "memory");
}
__device__ __forceinline__ void mbar_wait_cluster(uint32_t b) {
    asm volatile("{ .reg .pred p; .reg .u32 n; mov.u32 n, 0;\n"
                 "LW: mbarrier.try_wait.parity.acquire.cluster.shared::cta.b64 p, [%0], 0; @p bra LD; add.u32 n, n, 1; setp.lt.u32 p, n, 4194304; @p bra LW; trap;\n"
                 "LD: }" :: "r"(b) : "memory");
}
__device__ __forceinline__ void tma2d(uint32_t dst, const CUtensorMap* m, int c0, int c1, uint32_t bar) {
    asm volatile("cp.async.bulk.tensor.2d.shared::cluster.global.mbarrier::complete_tx::bytes [%0], [%1, {%3, %4}], [%2];"
                 :: "r"(dst), "l"(m), "r"(bar), "r"(c0), "r"(c1) : "memory");
}
__device__ __forceinline__ void tma3d(uint32_t dst, const CUtensorMap* m, int c0, int c1, int c2, uint32_t bar) {
    asm volatile("cp.async.bulk.tensor.3d.shared::cluster.global.mbarrier::complete_tx::bytes [%0], [%1, {%3, %4, %5}], [%2];"
                 :: "r"(dst), "l"(m), "r"(bar), "r"(c0), "r"(c1), "r"(c2) : "memory");
}
__device__ __forceinline__ void tma4d(uint32_t dst, const CUtensorMap* m, int c0, int c1, int c2, int c3, uint32_t bar) {
    asm volatile("cp.async.bulk.tensor.4d.shared::cluster.global.mbarrier::complete_tx::bytes [%0], [%1, {%3, %4, %5, %6}], [%2];"
                 :: "r"(dst), "l"(m), "r"(bar), "r"(c0), "r"(c1), "r"(c2), "r"(c3) : "memory");
}
__device__ __forceinline__ void bulk_g2s(uint32_t dst, const void* src, uint32_t bytes, uint32_t bar) {
    asm volatile("cp.async.bulk.shared::cluster.global.mbarrier::complete_tx::bytes [%0], [%1], %2, [%3];"
                 :: "r"(dst), "l"(src), "r"(bytes), "r"(bar) : "memory");
}
__device__ __forceinline__ uint32_t mapa(uint32_t a, uint32_t rank) { uint32_t r; asm("mapa.shared::cluster.u32 %0, %1, %2;" : "=r"(r) : "r"(a), "r"(rank)); return r; }
__device__ __forceinline__ void prefetch_map(const CUtensorMap* m) { asm volatile("prefetch.tensormap [%0];" :: "l"(m) : "memory"); }
__device__ __forceinline__ void bar_sync(int id, int n) { asm volatile("bar.sync %0, %1;" :: "r"(id), "r"(n) : "memory"); }
__device__ __forceinline__ void bar_arrive(int id, int n) { asm volatile("bar.arrive %0, %1;" :: "r"(id), "r"(n) : "memory"); }
__device__ __forceinline__ void fence_gpu() { asm volatile("fence.acq_rel.gpu;" ::: "memory"); }
__device__ __forceinline__ uint32_t ldg16(const void* p) { uint32_t v; asm volatile("ld.global.nc.u16 %0, [%1];" : "=r"(v) : "l"(p)); return v; }
__device__ __forceinline__ uint32_t ldg32(const void* p) { uint32_t v; asm volatile("ld.global.nc.u32 %0, [%1];" : "=r"(v) : "l"(p)); return v; }
__device__ __forceinline__ uint32_t ld_rlx32(const void* p) { uint32_t v; asm volatile("ld.relaxed.gpu.global.u32 %0, [%1];" : "=r"(v) : "l"(p) : "memory"); return v; }
__device__ __forceinline__ uint4 ld_rlx128(const void* p) {
    uint4 v; asm volatile("ld.relaxed.gpu.global.v4.u32 {%0,%1,%2,%3}, [%4];" : "=r"(v.x), "=r"(v.y), "=r"(v.z), "=r"(v.w) : "l"(p) : "memory"); return v;
}
__device__ __forceinline__ void st_rlx32(void* p, uint32_t v) { asm volatile("st.relaxed.gpu.global.u32 [%0], %1;" :: "l"(p), "r"(v) : "memory"); }
__device__ __forceinline__ void stg128(void* p, uint32_t x, uint32_t y, uint32_t z, uint32_t w) {
    asm volatile("st.global.v4.u32 [%0], {%1,%2,%3,%4};" :: "l"(p), "r"(x), "r"(y), "r"(z), "r"(w) : "memory");
}
__device__ __forceinline__ void next_epoch(const Params& p, unsigned e) { if ((threadIdx.x & 31) == 0) p.s->epoch[blockIdx.x * 16 + (threadIdx.x >> 5)] = e + 1; }
__device__ __forceinline__ void sts128z_if(bool c, uint32_t a) { asm volatile("{ .reg .pred p; setp.ne.u32 p, %1, 0; @p st.shared.v4.u32 [%0], {%2,%2,%2,%2}; }" :: "r"(a), "r"((uint32_t)c), "r"(0) : "memory"); }
__device__ __forceinline__ void stg128z_if(bool c, void* a) { asm volatile("{ .reg .pred p; setp.ne.u32 p, %1, 0; @p st.global.v4.u32 [%0], {%2,%2,%2,%2}; }" :: "l"(a), "r"((uint32_t)c), "r"(0) : "memory"); }
__device__ __forceinline__ unsigned clock32() { unsigned c; asm volatile("mov.u32 %0, %clock;" : "=r"(c) :: "memory"); return c; }
__device__ __forceinline__ void until(unsigned t0, unsigned c) { while (clock32() - t0 < c) { } }
__device__ __forceinline__ float sigmoidf_(float x) { return __fdividef(1.0f, 1.0f + __expf(-x)); }
__device__ __forceinline__ uint32_t key_tag(unsigned epoch) { return ((epoch & 15u) | 16u) << 11; }
__device__ __forceinline__ int key_row(uint32_t key) { return 2047 - (int)(key & 2047u); }
__device__ __forceinline__ uint32_t wait_sel(const Params& p, int s32, int r8, uint32_t tag) {
    uint32_t k;
    for (int it = 0;; it++) {
        k = ld_rlx32(&p.s->sel[s32 * 8 + r8]);
        if (__all_sync(0xffffffffu, (k & 0xf800u) == tag)) break;
        if (it > (1 << 20)) __trap();
    }
    fence_gpu();
    return k;
}

struct cplx { float re, im; };
__device__ __forceinline__ cplx csq(cplx a) { cplx r; r.re = a.re * a.re - a.im * a.im; r.im = (a.re * a.im) * 2.f; return r; }
__device__ __forceinline__ cplx cexpk(float ar, float ai, float k) {
    float mag, s, c;
    asm("ex2.approx.ftz.f32 %0, %1;" : "=f"(mag) : "f"(ar * (k * 1.4426950408889634f)));
    const float r = ai * k;
    asm("sin.approx.ftz.f32 %0, %1;" : "=f"(s) : "f"(r));
    asm("cos.approx.ftz.f32 %0, %1;" : "=f"(c) : "f"(r));
    cplx o; o.re = mag * c; o.im = mag * s; return o;
}
struct h2c { uint32_t re, im; };
__device__ __forceinline__ h2c cmul_cd(h2c v, __half2 c, __half2 d) {
    const __half2 r = *(const __half2*)&v.re, i = *(const __half2*)&v.im;
    const __half2 x = __hfma2(__hneg2(i), d, __hmul2(r, c)), y = __hfma2(i, c, __hmul2(r, d));
    h2c o; o.re = *(const uint32_t*)&x; o.im = *(const uint32_t*)&y; return o;
}
__device__ __forceinline__ h2c cmul_s(h2c v, uint32_t s) { const __half2 h = *(const __half2*)&s; return cmul_cd(v, __low2half2(h), __high2half2(h)); }
__device__ __forceinline__ h2c cmul_sc(h2c v, uint32_t s) {
    const __half2 h = *(const __half2*)&s, c = __low2half2(h), d = __high2half2(h), r = *(const __half2*)&v.re, i = *(const __half2*)&v.im;
    const __half2 x = __hfma2(i, d, __hmul2(r, c)), y = __hfma2(__hneg2(r), d, __hmul2(i, c));
    h2c o; o.re = *(const uint32_t*)&x; o.im = *(const uint32_t*)&y; return o;
}
__device__ __forceinline__ h2c cmul_vc(h2c v, uint32_t s) {
    const __half2 h = *(const __half2*)&s, c = __low2half2(h), d = __high2half2(h), r = *(const __half2*)&v.re, i = *(const __half2*)&v.im;
    const __half2 x = __hfma2(i, d, __hmul2(r, c)), y = __hfma2(__hneg2(i), c, __hmul2(r, d));
    h2c o; o.re = *(const uint32_t*)&x; o.im = *(const uint32_t*)&y; return o;
}

constexpr int UT_HALF = 2240, UT_STRIDE = 4448;
constexpr int KT_T = 542, KT_C = 552, KT_D = 648, KT_BYTES = 720 * 4;
constexpr int VC_OFF = 80, VE_BASE = 1616;
constexpr int V_STRIDE = (1616 + 1024) * 4 + 80;
constexpr int KG_STAGE = 5248;
constexpr int Y_CS = 2080, Y_RS = 8 * Y_CS + 64;

constexpr int SC_RT = 0;
constexpr int SC_UT = 33408;
constexpr int SC_ST = SC_UT + 8 * UT_STRIDE;
constexpr int SC_KT = SC_ST + 8 * UT_STRIDE;
constexpr int SC_GT = SC_KT + 8 * KT_BYTES;
constexpr int SC_V = SC_GT + UT_STRIDE;
constexpr int SC_KG = SC_V + 4 * V_STRIDE;
constexpr int SC_KD = SC_V + 8 * V_STRIDE;
constexpr int SC_MISC = SC_KD + 8192;
static_assert(V_STRIDE % 128 == 16 && 8 * KG_STAGE <= 4 * V_STRIDE && 2 * Y_RS <= SC_UT && SC_UT % 128 == 0, "layout");
static_assert(SC_MISC % 16 == 0 && SC_MISC + 512 <= 232192, "layout");

__device__ __forceinline__ void window_task(uint32_t ut, uint32_t vt, int a, bool withE) {
    const uint32_t src = ut + (a + 6) * 16;
    float S[35];
    {
        uint32_t w[20];
#pragma unroll
        for (int i = 0; i < 5; i++) {
            const uint4 v = lds128(src + ((i & 1) ? 0 : UT_HALF) + ((i + 1) >> 1) * 16);
            w[4 * i] = v.x; w[4 * i + 1] = v.y; w[4 * i + 2] = v.z; w[4 * i + 3] = v.w;
        }
        float s = 0.f; S[2] = 0.f;
#pragma unroll
        for (int i = 3; i < 26; i++) { s += (i & 1) ? bf_hi(w[i >> 1]) : bf_lo(w[i >> 1]); S[i] = s; }
        const uint32_t dst = vt + (VC_OFF - 16 + 16 * a) * 4;
#pragma unroll
        for (int i = 0; i < 16; i += 4)
            sts128(dst + 4 * i, pack_bf16(S[10 + i] - S[5 + i], S[5 + i] - S[2 + i]), pack_bf16(S[11 + i] - S[6 + i], S[6 + i] - S[3 + i]),
                   pack_bf16(S[12 + i] - S[7 + i], S[7 + i] - S[4 + i]), pack_bf16(S[13 + i] - S[8 + i], S[8 + i] - S[5 + i]));
        if (withE) {
#pragma unroll
            for (int i = 26; i < 35; i++) { s += (i & 1) ? bf_hi(w[i >> 1]) : bf_lo(w[i >> 1]); S[i] = s; }
            const uint32_t dse = vt + (VE_BASE + 16 * a) * 4;
#pragma unroll
            for (int i = 0; i < 16; i += 4)
                sts128(dse + 4 * i, pack_bf16(S[19 + i] - S[12 + i], S[12 + i] - S[3 + i]), pack_bf16(S[20 + i] - S[13 + i], S[13 + i] - S[4 + i]),
                       pack_bf16(S[21 + i] - S[14 + i], S[14 + i] - S[5 + i]), pack_bf16(S[22 + i] - S[15 + i], S[15 + i] - S[6 + i]));
        }
    }
}

template <class F>
__device__ __forceinline__ void kgen(const Params& p, uint32_t sb, int ch, int half, uint32_t stage, uint32_t pstage, int barid, int lane, uint32_t (&w)[12], F shadow) {
    const int t = lane & 3, mi = lane >> 3, r8 = lane & 7;
    {
        const int o = NST * ch + 64 * half + 2 * (threadIdx.x & 31);
        const uint32_t pAr = ldg32(p.Are + o), pAi = ldg32(p.Aim + o), pBr = ldg32(p.Bre + o), pBi = ldg32(p.Bim + o), pCr = ldg32(p.Cre + o), pCi = ldg32(p.Cim + o);
        const uint32_t pDt = ldg16(p.logdt + ch), pD = ldg16(p.Dskip + ch);
        const uint32_t wb = fresh(stage + lane * 16), za = fresh(stage + 5120 + ((lane >> 1) & 3) * 16 + mi * 4 + (lane & 1) * 2), zr = fresh(stage + 5120 + t * 16);
        const uint32_t oA = fresh(stage + (mi & 1) * 1024 + (mi >> 1) * 512 + r8 * 16), oB = fresh(stage + 2048 + mi * 512 + r8 * 16), oC = fresh(stage + 4096 + (mi & 1) * 512 + (mi >> 1) * 128 + r8 * 16);
        float acc[6][4];
#pragma unroll
        for (int a = 0; a < 6; a++) { acc[a][0] = acc[a][1] = acc[a][2] = acc[a][3] = 0.f; asm volatile("" : "+f"(acc[a][0]), "+f"(acc[a][1]), "+f"(acc[a][2]), "+f"(acc[a][3])); }
        shadow();
        const float dt = rbf(__expf(bf_lo(pDt)));
        float ar = dt * bf_lo(pAr), ai = dt * bf_lo(pAi), ar1 = dt * bf_hi(pAr), ai1 = dt * bf_hi(pAi);
        float wr, wi, wr1, wi1;
        { const float br = dt * bf_lo(pBr), bi = dt * bf_lo(pBi), cr = bf_lo(pCr), ci = bf_lo(pCi); wr = cr * br - ci * bi; wi = cr * bi + ci * br; }
        { const float br = dt * bf_hi(pBr), bi = dt * bf_hi(pBi), cr = bf_hi(pCr), ci = bf_hi(pCi); wr1 = cr * br - ci * bi; wi1 = cr * bi + ci * br; }
        const uint32_t ex = max(__reduce_max_sync(0xffffffffu, __float_as_uint(fmaxf(fmaxf(fabsf(wr), fabsf(wi)), fmaxf(fabsf(wr1), fabsf(wi1))))) >> 23, 14u);
        const float scl = __uint_as_float((267u - ex) << 23);
        uint32_t W = pack_f16(wr * scl, wi * -scl);
        const uint32_t W1 = pack_f16(wr1 * scl, wi1 * -scl);
        if (threadIdx.x < 32) TSTAMP(20);

#pragma unroll 1
        for (int r = 0; r < 2; r++) {
            const cplx z1 = cexpk(ar, ai, 1.f), z64 = cexpk(ar, ai, 64.f);
            const cplx z2 = csq(z1), z4 = csq(z2), z8 = csq(z4), z16 = csq(z8), z32 = csq(z16);
            const cplx z128 = csq(z64), z256 = csq(z128), z512 = csq(z256), z1024 = csq(z512);
            auto put = [&](int grp, h2c a, h2c b, h2c c, h2c d) { sts128(wb + grp * 1024, a.re, b.re, c.re, d.re); sts128(wb + grp * 1024 + 512, a.im, b.im, c.im, d.im); };
            {
                const uint32_t s1 = pack_f16(z1.re, z1.im), s2 = pack_f16(z2.re, z2.im), s256 = pack_f16(z256.re, z256.im), s512 = pack_f16(z512.re, z512.im), s1024 = pack_f16(z1024.re, z1024.im);
                const h2c c04 = cmul_vc(h2c{pack_f16(1.f, z4.re), pack_f16(0.f, z4.im)}, W), c26 = cmul_sc(c04, s2);
                put(2, c04, c26, cmul_sc(c04, s1), cmul_sc(c26, s1));
                const h2c d04 = cmul_sc(c04, s256), e04 = cmul_sc(c04, s512), f04 = cmul_sc(d04, s512);
                put(3, d04, cmul_sc(c26, s256), e04, f04);
                const h2c ef = {__byte_perm(e04.re, f04.re, 0x5410), __byte_perm(e04.im, f04.im, 0x5410)};
                const h2c gh = cmul_sc(ef, s512);
                put(4, gh, cmul_sc(ef, s1024), cmul_sc(gh, s1024), ef);
            }
            {
                const uint32_t s32 = pack_f16(z32.re, z32.im), s64 = pack_f16(z64.re, z64.im), s128 = pack_f16(z128.re, z128.im);
                const h2c p0 = {pack_f16(1.f, z8.re), pack_f16(0.f, z8.im)}, p1 = cmul_s(p0, pack_f16(z16.re, z16.im)), p2 = cmul_s(p0, s32), p3 = cmul_s(p1, s32);
                put(0, p0, p1, p2, p3);
                put(1, cmul_s(p0, s64), cmul_s(p1, s64), cmul_s(p2, s64), cmul_s(p3, s64));
                sts16(za, s128); sts16(za + 64, s128 >> 16);
            }
            __syncwarp();
            {
                const uint32_t aA = fresh(oA), aB = fresh(oB), aC = fresh(oC), aZ = fresh(zr);
                const uint4 zc = lds128(aZ), zd = lds128(aZ + 64);
                const uint32_t zcs[4] = {zc.x, zc.y, zc.z, zc.w}, zds[4] = {zd.x, zd.y, zd.z, zd.w};
                uint32_t c[4];
#pragma unroll
                for (int k = 0; k < 4; k++) {
                    uint32_t a[4], b[4];
                    ldsm4t(a, aA + 128 * k); ldsm4t(b, aB + 128 * k);
                    if (!(k & 1)) ldsm4t(c, aC + 128 * k);
                    const h2c x = cmul_cd(h2c{a[0], a[2]}, *(const __half2*)&zcs[k], *(const __half2*)&zds[k]), y = cmul_cd(h2c{a[1], a[3]}, *(const __half2*)&zcs[k], *(const __half2*)&zds[k]);
                    mma_h(acc[0], a[0], a[1], a[2], a[3], b[0], b[1]);
                    mma_h(acc[1], a[0], a[1], a[2], a[3], b[2], b[3]);
                    mma_h(acc[2], a[0], a[1], a[2], a[3], c[2 * (k & 1)], c[2 * (k & 1) + 1]);
                    mma_h(acc[3], x.re, y.re, x.im, y.im, b[0], b[1]);
                    mma_h(acc[4], x.re, y.re, x.im, y.im, b[2], b[3]);
                    mma_h(acc[5], x.re, y.re, x.im, y.im, c[2 * (k & 1)], c[2 * (k & 1) + 1]);
                }
                asm volatile("" :: "f"(acc[0][0]), "f"(acc[1][0]), "f"(acc[2][0]), "f"(acc[3][0]), "f"(acc[4][0]), "f"(acc[5][0]) : "memory");
            }
            __syncwarp();
            ar = ar1; ai = ai1; W = W1;
        }
        if (threadIdx.x < 32) TSTAMP(21);
        const float i0 = __uint_as_float((ex - 13u) << 23);
        if (half) {
#pragma unroll
            for (int a = 0; a < 6; a++) sts128(wb + a * 512, __float_as_uint(acc[a][0] * i0), __float_as_uint(acc[a][1] * i0), __float_as_uint(acc[a][2] * i0), __float_as_uint(acc[a][3] * i0));
            bar_arrive(barid, 64);
        } else {
            bar_sync(barid, 64);
            const uint32_t src = fresh(pstage) + lane * 16;
#pragma unroll
            for (int a = 0; a < 6; a++) {
                const uint4 y = lds128(src + a * 512);
                float v0 = fmaf(acc[a][0], i0, __uint_as_float(y.x));
                if (a == 0 && lane == 0) v0 += bf_lo(pD);
                w[2 * a] = pack_bf16(v0, fmaf(acc[a][1], i0, __uint_as_float(y.y)));
                w[2 * a + 1] = pack_bf16(fmaf(acc[a][2], i0, __uint_as_float(y.z)), fmaf(acc[a][3], i0, __uint_as_float(y.w)));
            }
        }
    }
}

enum { BC_AUX = 0, BC_S = 5, BC_KG = 15 };

__device__ __forceinline__ void conv_aux(const Params& p, const CUtensorMap* mU, uint32_t sb, int aw, int lane, int bid, unsigned epoch) {
    const unsigned t0 = clock32();
    asm volatile("setmaxnreg.dec.sync.aligned.u32 88;");
    const int g = lane >> 2, t = lane & 3, mi = lane >> 3, r8 = lane & 7;
    const int rank = bid & 1, slab = bid >> 1;
    const uint32_t bar_box = sb + SC_MISC, bar_y = bar_box + 32, bar_u = bar_box + 64, bar_v = bar_box + 72, s_bm = bar_box + 128;
    if (lane == 0) {
        mbar_init(bar_box + 8 * aw, 1);
        if (aw >= 6) mbar_init(bar_box + 16 + 8 * aw, aw == 6 ? 1 : 8);
        mbar_fence();
        mbar_expect(bar_box + 8 * aw, 8192);
        if (aw == 6) mbar_expect(bar_u, 16384);
    }
    __syncwarp();
    asm volatile("barrier.cluster.arrive.relaxed.aligned;" ::: "memory");
    if (lane == 0 && aw < 4) { until(t0, UDELAY); tma4d(sb + SC_RT + 8192 * aw, mU, 16 * slab, 0, 0, 32 * rank + 8 * aw, bar_box + 8 * aw); }
    __syncwarp();
    const uint32_t ut = sb + SC_UT + aw * UT_STRIDE;
    sts128(ut + (mi >> 1) * (SC_ST - SC_UT) + (mi & 1) * UT_HALF + r8 * 16, 0, 0, 0, 0);
    if (lane < 16) sts128(s_bm + lane * 16, 0, 0, 0, 0);
    {
        const uint32_t dst = sb + SC_UT + g * UT_STRIDE + (t & 1) * UT_HALF + (8 + 64 * rank + 8 * aw + (t >> 1)) * 16;
        const uint32_t rdst = mapa(dst, rank ^ 1), rbar = mapa(bar_u, rank ^ 1);
        asm volatile("barrier.cluster.wait.acquire.aligned;" ::: "memory");
        mbar_wait(bar_box + 8 * (aw >> 1));
        if (aw == 0) TSTAMP(1);
        const uint32_t src = fresh(sb + SC_RT) + aw * 4096 + (8 * mi + 4 * (r8 & 1) + (r8 >> 1)) * 32 + ((rank ^ (r8 & 1)) << 4);
        uint32_t x[8][4];
#pragma unroll
        for (int i = 0; i < 4; i++) { ldsm4t(x[i], src + 1024 * i); ldsm4t(x[4 + i], (src ^ 16) + 1024 * i); }
        asm volatile("" :: "r"(x[0][0]), "r"(x[1][0]), "r"(x[2][0]), "r"(x[3][0]) : "memory");
#pragma unroll
        for (int i = 0; i < 4; i++) st_async128(rdst + 32 * i, x[4 + i][0], x[4 + i][1], x[4 + i][2], x[4 + i][3], rbar);
#pragma unroll
        for (int i = 0; i < 4; i++) sts128(dst + 32 * i, x[i][0], x[i][1], x[i][2], x[i][3]);
    }
    bar_sync(BC_AUX, 256);
    mbar_wait_cluster(bar_u);
    if (aw == 0) TSTAMP(2);
    {
        const uint32_t a = fresh(ut) + (mi & 1) * UT_HALF + (64 * (mi >> 1) + r8) * 16;
        uint4 v = lds128(a);
#pragma unroll
        for (int i = 1; i <= 8; i++) {
            const uint4 w = lds128(a + 128 * i);
            sts128(a + 128 * i + (SC_ST - SC_UT), badd2(v.x, w.x), badd2(v.y, w.y), badd2(v.z, w.z), badd2(v.w, w.w));
            v = w;
        }
    }
    bar_arrive(BC_S + aw, 64);
    if (aw == 0) TSTAMP(3);
#pragma unroll 1
    for (int k = aw; k < 26; k += 8) {
        if (k - aw == 8) {
            bar_sync(BC_KG, 384);
            if (lane < 16) sts128(sb + SC_V + aw * V_STRIDE + lane * 16, 0, 0, 0, 0);
        }
        const int c = (k < 13 ? 0 : 4) + t, a = 8 * (k < 13 ? k : k - 13) + g;
        if (a < 97) window_task(fresh(sb + SC_UT) + c * UT_STRIDE, sb + SC_V + c * V_STRIDE, a, a < 64);
        __syncwarp();
    }
    if (aw == 0) TSTAMP(9);
    {
        {
            const uint32_t par = (epoch & 1) ? 0u : 0x80008000u;
            uint4 v;
            for (int it = 0;; it++) {
                v = ld_rlx128(p.s->gate + 256 * aw + 8 * lane);
                v.x ^= par; v.y ^= par; v.z ^= par; v.w ^= par;
                if (__all_sync(0xffffffffu, ((v.x | v.y | v.z | v.w) & 0x80008000u) == 0)) break;
                if (it > (1 << 20)) __trap();
            }
            sts128(sb + SC_GT + (lane & 1) * UT_HALF + (8 + 16 * aw + (lane >> 1)) * 16, v.x, v.y, v.z, v.w);
        }
        __syncwarp();
        if (lane == 0) mbar_arrive(bar_v);
        next_epoch(p, epoch);
        if (aw == 0) TSTAMP(4);
        if (aw == 7) {
            const int row = key_row(wait_sel(p, slab >> 1, r8, key_tag(epoch)));
            if (lane < 8) asm volatile("red.shared.or.b32 [%0], %1;" :: "r"(s_bm + (row >> 5) * 4), "r"(1u << (row & 31)) : "memory");
            TSTAMP(10);
        }
        bar_sync(BC_AUX, 256);
        const uint32_t src = sb + SC_RT + ((r8 >> 1) & 1) * Y_RS + (2 * mi + (r8 & 1)) * Y_CS + (2 * aw + (r8 >> 2)) * 16;
        const int L = 2 * aw + (t >> 1);
        const int row0 = 256 * rank + 128 * (g >> 2) + 32 * (L & 3) + 16 * (g & 1) + 8 * ((g >> 1) & 1) + (L >> 2);
        __nv_bfloat16* outp = p.out + (size_t)row0 * DM + 16 * slab + 8 * (t & 1);
#pragma unroll 1
        for (int s = 0; s < 4; s++) {
            const uint32_t bm = lds32(fresh(s_bm) + (16 * s + (row0 >> 5)) * 4) >> (row0 & 31);
            mbar_wait_cluster(bar_y + 8 * s);
            const uint32_t sf = fresh(src) + 512 * s;
#pragma unroll
            for (int k = 0; k < 2; k++) {
                uint32_t y[4];
                ldsm4t(y, sf + 256 * k);
                __nv_bfloat16* o = outp + (size_t)(512 * s + 4 * k) * DM;
                if (bm & (1u << (4 * k)))
                    asm volatile("red.relaxed.gpu.global.add.noftz.v4.bf16x2 [%0], {%1,%2,%3,%4};" :: "l"(o), "r"(y[0]), "r"(y[1]), "r"(y[2]), "r"(y[3]) : "memory");
                else stg128(o, y[0], y[1], y[2], y[3]);
            }
            if (aw == 0) TSTAMP(16 + s);
        }
        if (aw == 0) TFLUSH();
    }
}

__device__ __forceinline__ void conv_main(const Params& p, uint32_t sb, int warp, int lane, int bid, unsigned epoch, uint32_t (&w)[12]) {
    asm volatile("setmaxnreg.inc.sync.aligned.u32 168;");
    const int g = lane >> 2, t = lane & 3, mi = lane >> 3, r8 = lane & 7;
    const int rank = bid & 1;
    const uint32_t bar_y = sb + SC_MISC + 32, bar_v = bar_y + 40;
    next_epoch(p, epoch);
    if (warp < 4) {
        asm volatile("" :: "r"(w[0]), "r"(w[2]), "r"(w[4]), "r"(w[6]), "r"(w[8]), "r"(w[10]) : "memory");
        bar_arrive(BC_KG, 384);
    } else {
        const uint4* src = p.s->kp + (4 * bid + warp - 4) * 128 + lane;
        for (int it = 0;; it++) {
            uint32_t bad = 0;
#pragma unroll
            for (int i = 0; i < 4; i++) { const uint4 v = ld_rlx128(src + 32 * i); w[3 * i] = v.x; w[3 * i + 1] = v.y; w[3 * i + 2] = v.z; bad |= v.w ^ ~epoch; }
            if (__all_sync(0xffffffffu, bad == 0)) break;
            if (it > (1 << 20)) __trap();
        }
    }
    if ((warp & 3) == 0) TSTAMP(5 + (warp >> 2));
    {
        const uint32_t kt = sb + SC_KT + warp * KT_BYTES;
        const uint32_t kd = sb + SC_KD + warp * 1024 + 16;
#pragma unroll
        for (int nu = 0; nu < 3; nu++) {
            uint32_t a, a0, de, dr;
            if (nu == 0) { a = kd + (8 * g + 2 * (t & 1) + (t >> 1)) * 2; de = 8; dr = 128; a0 = a; }
            else if (nu == 1) { a = t < 2 ? kd + (256 + 4 * g + t) * 2 : kt + KT_C * 4 + (64 * t - 100 + 2 * g) * 2; de = t < 2 ? 4 : 2; dr = t < 2 ? 64 : 32; a0 = a; }
            else {
                a = t < 2 ? kt + KT_D * 4 + (13 + 64 * t + g) * 2 : kd + 800; de = 64; dr = 16; a0 = a;
                if ((lane & 29) == 0) a0 = kt + (t ? KT_D * 4 + 141 * 2 : KT_C * 4 + 156 * 2);
            }
#pragma unroll
            for (int i = 0; i < 4; i++) {
                const uint32_t v = w[6 * (i >> 1) + 2 * nu + (i & 1)];
                sts16(i ? a + i * dr : a0, v); sts16(a + i * dr + de, v >> 16);
            }
        }
        if (lane == 0) sts128(kt + (KT_T + 2) * 4, 0, w[4] & 0xffffu, __byte_perm(w[4], 0, 0x1010), w[4] << 16);
        __syncwarp();
        const uint32_t kf = fresh(kd), d = kt + (16 + 8 * lane) * 4;
        auto put = [&](uint32_t d, uint32_t pv, uint32_t w0, uint32_t w1, uint32_t w2, uint32_t w3) {
            sts128(d, __byte_perm(w0, pv, 0x5410), __byte_perm(w0, 0, 0x1032), __byte_perm(w1, w0, 0x7610), __byte_perm(w1, 0, 0x1032));
            sts128(d + 16, __byte_perm(w2, w1, 0x7610), __byte_perm(w2, 0, 0x1032), __byte_perm(w3, w2, 0x7610), __byte_perm(w3, 0, 0x1032));
        };
        const uint32_t pv = lds16(kf + (lane ? 16 * lane : 512) - 2);
        const uint4 x = lds128(kf + 16 * lane);
        const uint2 v = lds64(kf + 512 + 8 * lane);
        const uint32_t c4 = lds16(lane == 31 ? fresh(kt) + KT_C * 4 + 28 * 2 : kf + 520 + 8 * lane);
        put(d, lane ? pv : 0, x.x, x.y, x.z, x.w);
        uint32_t w3 = __byte_perm(v.y, c4, 0x5432);
        if (lane == 31) w3 = bsub2(w3, __byte_perm(c4, 0, 0x1010));
        put(d + 1024, lane ? v.x : pv, __byte_perm(v.x, 0, 0x1010), __byte_perm(v.x, v.y, 0x5432), __byte_perm(v.y, 0, 0x1010), w3);
    }
    asm volatile("barrier.cluster.wait.acquire.aligned;" ::: "memory");
    bar_sync(BC_S + warp, 64);
    if ((warp & 3) == 0) TSTAMP(7 + (warp >> 2));
    {
        const uint32_t ut = fresh(sb + SC_UT) + warp * UT_STRIDE, kt = fresh(sb + SC_KT) + warp * KT_BYTES;
        const uint32_t u1 = ut + (mi & 1) * UT_HALF + (8 + r8) * 16 + (mi >> 1) * 128;
        const uint32_t kb = kt + (16 + g - 2 * t) * 4, kz = kb + (lds32(kt) >> 1);
        float acc[16][4];
        {
            const uint32_t c0 = lds32(kb + 2048), c1 = lds32(kb + 2080), c2 = lds32(kb + 2016), c3 = lds32(kz + 2048);
            const uint32_t e0 = lds32(kb + (KT_T - 16) * 4), e1 = lds32(kb + (KT_T - 8) * 4), e2 = lds32(kb + (KT_T - 24) * 4), e3 = lds32(kz + (KT_T - 16) * 4);
            const uint32_t f0 = lds32(kz + (KT_T - 8) * 4), f1 = lds32(kb + KT_T * 4);
            const uint32_t uo = ut + UT_HALF + (7 + lane) * 16;
#pragma unroll
            for (int i = 0; i < 16; i++) { acc[i][0] = acc[i][1] = acc[i][2] = acc[i][3] = 0.f; }
#pragma unroll
            for (int mu = 0; mu < 8; mu += 4) {
                uint32_t b[4];
                ldsm4(b, uo + 128 * mu);
#pragma unroll
                for (int k = 0; k < 4; k++) mma_bf8(acc[mu + 8 + k], f0, f1, b[k]);
            }
#pragma unroll
            for (int mu = 0; mu < 12; mu += 2) {
                uint32_t b[4];
                ldsm4(b, u1 + 128 * mu);
                mma_bf(acc[mu + 4], c0, c1, c2, c3, b[0], b[1]);
                mma_bf(acc[mu + 5], c0, c1, c2, c3, b[2], b[3]);
                if (mu < 8) { mma_bf(acc[mu + 8], e0, e1, e2, e3, b[0], b[1]); mma_bf(acc[mu + 9], e0, e1, e2, e3, b[2], b[3]); }
            }
        }
        {
            float M[8][4];
#pragma unroll
            for (int i = 0; i < 8; i++) { M[i][0] = M[i][1] = M[i][2] = M[i][3] = 0.f; }
            const uint32_t s1 = u1 + (SC_ST - SC_UT);
#pragma unroll 1
            for (int j0 = 0; j0 < 8; j0++) {
                const uint32_t kp = kb + 64 * j0, kq = kz + 64 * j0, sp = s1 - 16 * j0, up = u1 + (mi >> 1) * 128 - 16 * j0;
                uint32_t a[4][4], d[2][4];
#pragma unroll
                for (int j = 0; j < 4; j++) { a[j][0] = lds32(kp + 512 * j); a[j][1] = lds32(kp + 512 * j + 32); a[j][2] = lds32(kp + 512 * j - 32); a[j][3] = lds32(kq + 512 * j); }
#pragma unroll
                for (int c = 0; c < 2; c++)
#pragma unroll
                    for (int e = 0; e < 4; e++) d[c][e] = bsub2(a[2 * c][e], a[2 * c + 1][e]);
                uint32_t b[4];
#pragma unroll
                for (int i = 0; i < 8; i++) {
                    uint32_t s[4];
                    ldsm4(s, sp + 256 * i);
                    if (!(i & 1)) ldsm4(b, up + 256 * i);
                    const uint32_t b0 = b[2 * (i & 1)], b1 = b[2 * (i & 1) + 1];
                    if (i < 7) {
                        mma_bf(acc[2 * i + 2], a[3][0], a[3][1], a[3][2], a[3][3], s[0], s[1]);
                        mma_bf(acc[2 * i + 3], a[2][0], a[2][1], a[2][2], a[2][3], s[2], s[3]);
                        mma_bf(M[i + 1], d[1][0], d[1][1], d[1][2], d[1][3], b0, b1);
                    }
                    mma_bf(acc[2 * i], a[1][0], a[1][1], a[1][2], a[1][3], s[0], s[1]);
                    mma_bf(acc[2 * i + 1], a[0][0], a[0][1], a[0][2], a[0][3], s[2], s[3]);
                    mma_bf(M[i], d[0][0], d[0][1], d[0][2], d[0][3], b0, b1);
                }
            }
#pragma unroll
            for (int i = 0; i < 8; i++)
#pragma unroll
                for (int c = 0; c < 4; c++) { acc[2 * i][c] += M[i][c]; acc[2 * i + 1][c] -= M[i][c]; }
        }
        if ((warp & 3) == 0) TSTAMP(11 + (warp >> 2));
        mbar_wait(bar_v);
        const uint32_t vt = fresh(sb + SC_V) + warp * V_STRIDE;
        const uint32_t g1 = fresh(u1) - ut + sb + SC_GT;
        const uint32_t ydst = sb + SC_RT + rank * Y_RS + warp * Y_CS + lane * 16;
        const uint32_t yd0 = mapa(ydst, 0), yd1 = mapa(ydst, 1), yb0 = mapa(bar_y, 0), yb1 = mapa(bar_y, 1);
        auto ship = [&](int i) {
            uint32_t u[4], gg[4];
            ldsm4t(u, u1 + 256 * i); ldsm4t(gg, g1 + 256 * i);
            st_async128(((i & 1) ? yd1 : yd0) + 512 * (i >> 1),
                        gmix(gg[0], pack_bf16(acc[2 * i][0], acc[2 * i][1]), u[0]), gmix(gg[1], pack_bf16(acc[2 * i][2], acc[2 * i][3]), u[1]),
                        gmix(gg[2], pack_bf16(acc[2 * i + 1][0], acc[2 * i + 1][1]), u[2]), gmix(gg[3], pack_bf16(acc[2 * i + 1][2], acc[2 * i + 1][3]), u[3]),
                        ((i & 1) ? yb1 : yb0) + 8 * (i >> 1));
        };
        ship(0);
        {
            const uint32_t KE = kt + (KT_D + g + t) * 4, VE = vt + (VE_BASE - 912 + g - 16 * t) * 4;
            uint32_t b0[8], b1[8];
#pragma unroll
            for (int s = 0; s < 8; s++) { b0[s] = lds32(KE + 32 * s); b1[s] = lds32(KE + 32 * s + 16); }
#pragma unroll
            for (int dl = 8; dl < 16; dl++) {
                const uint32_t vp = VE + 512 * dl;
                const uint32_t x0 = lds32(vp), x1 = lds32(vp + 32), x2 = lds32(vp - 256), x3 = lds32(vp - 224);
#pragma unroll
                for (int s = 0; s < 8; s++) if (dl + s < 16) mma_bf(acc[dl + s], x0, x1, x2, x3, b0[s], b1[s]);
            }
        }
        if (warp == 4) TSTAMP(13);
        {
            const uint32_t KD = kt + (KT_C + 2 * g + t) * 4, VD = vt + (VC_OFF - 400 + g - 8 * t) * 4;
            uint32_t b0[10], b1[10];
#pragma unroll
            for (int s = 0; s < 10; s++) { b0[s] = lds32(KD + 32 * s); b1[s] = lds32(KD + 32 * s + 16); }
#pragma unroll
            for (int dl = 6; dl <= 30; dl++) {
                const uint32_t vp = VD + 256 * dl;
                const uint32_t x0 = lds32(vp), x1 = lds32(vp + 32), x2 = lds32(vp - 128), x3 = lds32(vp - 96);
#pragma unroll
                for (int s = dl & 1; s < 10; s += 2) if ((dl + s) / 2 < 16) mma_bf(acc[(dl + s) / 2], x0, x1, x2, x3, b0[s], b1[s]);
                if ((dl & 3) == 2) ship((dl - 2) / 4);
            }
        }
        if ((warp & 3) == 0) TSTAMP(14 + (warp >> 2));
    }
}

constexpr int SF_WD = 147456;
constexpr int SF_H = 81920;
constexpr int SF_RED = 131072;
constexpr int SF_XS = 221184;
constexpr int SF_MISC = SF_XS + 8 * 1168;
constexpr int SF_KG = SF_MISC - 10 * KG_STAGE;
constexpr int SF_WR = SF_KG - 2304;
constexpr int FB_X = 64, FB_RDONE = 72, FB_FREE = 80, FB_KDONE = 88, FB_W = 112, FB_D = FB_W + 72, FB_H = FB_D + 96, FS_PART = 512, FS_TOK = 896;
enum { BAR_F = 6, BAR_R = 7, BAR_GU = 8, BAR_RED = 9 };
static_assert(SF_KG % 128 == 0 && SF_KG >= 7 * 24576 && SF_WR - 4 * 9216 >= 5 * 24576 && SF_WR - 6 * 9216 >= 5 * 16384, "layout");

__device__ __forceinline__ void ffn_front(const Params& p, const CUtensorMap* maps, uint32_t sb, int warp, int lane, int f, unsigned epoch) {
    const unsigned t0 = clock32();
    const int g = lane >> 2, t = lane & 3, mi = lane >> 3, r8 = lane & 7;
    const bool isx = f < NX;
    const int nrw = f < 8 ? 6 : 4, r0 = f < 8 ? 48 * f : 128 + 32 * f;
    const int rw = warp < 12 ? 13 - warp : warp ^ (warp < 14 ? 10 : 15);
    const uint32_t bar_row = sb + SF_MISC  , bar_x = bar_row + FB_X, bar_rdone = bar_row + FB_RDONE;
    const uint32_t s_part = bar_row + FS_PART  , s_tok = bar_row + FS_TOK  ;
    const uint32_t rows = sb + SF_WR - 9216 * (rw + 1);
    if (lane == 0) {
        mbar_init(bar_row + 8 * rw, 1); mbar_fence();
        if (rw < nrw) { mbar_expect(bar_row + 8 * rw, 9216); until(t0, RDELAY); bulk_g2s(rows, p.u + (size_t)(r0 + 8 * rw) * DM, 9216, bar_row + 8 * rw); }
        else if (rw >= 6) { mbar_expect(bar_row + 8 * rw, 1152); bulk_g2s(sb + SF_WR + (rw & 1) * 1152, (rw & 1) ? p.gatew : p.wr, 1152, bar_row + 8 * rw); }
        if (warp >= 10) {
#pragma unroll 1
            for (int i = warp - 10; i < 39; i += 6) mbar_init(bar_x + 8 * i, i == 1 ? nrw : i == 2 ? 4 : 1);
        }
        mbar_fence();
    }
    const int ks0 = isx ? 4 * f : 6 * f - 72, nt = isx ? 4 : 6;
    if (warp == 13) {
        if (lane < 8) st_rlx32(&p.s->keys[f * 8 + lane], 0);
        else if (lane < 16 && isx && !(f & 1)) st_rlx32(&p.s->sel[4 * f + lane - 8], 0);
    }
    __syncwarp();
    bar_sync(BAR_F, f < 12 ? 256 : 192);
    bar_arrive(0, NTHR);
    if (warp == 15) TSTAMP(1);

    if (warp == 12) {
        if (lane == 0) {
            const CUtensorMap* m = maps + (isx ? 1 : 3);
            prefetch_map(m); prefetch_map(m + 1);
#pragma unroll 1
            for (int n = 0; n < 9; n++) {
                until(t0, WDELAY + n * WGAP);
                if (n == 5) mbar_wait(bar_rdone);
                if (n == 7) mbar_wait(bar_row + FB_KDONE);
                const uint32_t b = bar_row + FB_W + 8 * n;
                mbar_expect(b, nt * 4096);
                tma3d(sb + n * nt * 4096, m, 0, 64 * n, ks0 >> 1, b);
                tma3d(sb + n * nt * 4096 + nt * 2048, m + 1, 0, 64 * n, ks0 >> 1, b);
            }
            TSTAMP(12);
            if (isx) {
                prefetch_map(maps + 5);
#pragma unroll 1
                for (int n = 0; n < 12; n++) {
                    until(t0, DDELAY + n * DGAP);
                    if (n == 6) mbar_wait(bar_row + FB_FREE);
                    mbar_expect(bar_row + FB_D + 8 * n, 12288);
                    tma2d(sb + (n < 6 ? SF_WD : -6 * 12288) + n * 12288, maps + 5, 32 * (f >> 1), 2304 * (f & 1) + 192 * n, bar_row + FB_D + 8 * n);
                }
                TSTAMP(13);
            }
        }
    } else if (warp == 13) {
        const uint32_t tag = key_tag(epoch), par = (epoch & 1) ? 0u : 0x8000u;
        next_epoch(p, epoch);
        bar_sync(BAR_R, 32 * (nrw + 1));
        TSTAMP(3);
        uint32_t k[16];
        k[0] = 0;
#pragma unroll 1
        for (int rr = lane + (nrw > 4 ? 32 : 0); rr >= 0; rr -= 32) {
            k[1] = k[0]; k[0] = 0;
            if (rr < 48) {
                const uint2 v = lds64(fresh(s_part) + rr * 8);
                const uint32_t gb = pack_bf16(sigmoidf_(rbf(__uint_as_float(v.y))), 0.f) | par;
                asm volatile("st.relaxed.gpu.global.u16 [%0], %1;" :: "l"(p.s->gate + r0 + rr), "h"((unsigned short)gb) : "memory");
                const uint32_t rb = pack_bf16(0.f, __uint_as_float(v.x));
                k[0] = (rb ^ (((int)rb >> 31) & 0x7fff0000u) ^ 0x80000000u) | tag | (uint32_t)(2047 - r0 - rr);
            }
        }
        uint32_t key = 0;
#pragma unroll 1
        for (int r = 0; r < 8; r++) {
            const uint32_t m = __reduce_max_sync(0xffffffffu, max(k[0], k[1]));
            if (k[0] == m) k[0] = 0;
            if (k[1] == m) k[1] = 0;
            if (lane == r) key = m;
        }
        if (lane < 8) st_rlx32(&p.s->keys[f * 8 + lane], key);
        TSTAMP(4);
        for (int it = 0;; it++) {
            uint32_t bad = 0;
#pragma unroll
            for (int h = 0; h < 2; h++) {
                const uint32_t* src = &p.s->keys[min(lane + 32 * h, NFFN - 1) * 8];
                const uint4 x = ld_rlx128(src), y = ld_rlx128(src + 4);
                k[h] = x.x; k[2 + h] = x.y; k[4 + h] = x.z; k[6 + h] = x.w; k[8 + h] = y.x; k[10 + h] = y.y; k[12 + h] = y.z; k[14 + h] = y.w;
            }
#pragma unroll
            for (int i = 0; i < 16; i++) bad |= k[i] ^ tag;
            if (__all_sync(0xffffffffu, (bad & 0xf800u) == 0)) break;
            if (it > (1 << 20)) __trap();
        }
        TSTAMP(5);
#pragma unroll 1
        for (int r = 0; r < 8; r++) {
            const uint32_t m = __reduce_max_sync(0xffffffffu, max(k[0], k[1]));
            const bool pa = k[0] == m, pb = k[1] == m;
#pragma unroll
            for (int i = 0; i < 7; i++) { k[2 * i] = pa ? k[2 * i + 2] : k[2 * i]; k[2 * i + 1] = pb ? k[2 * i + 3] : k[2 * i + 1]; }
            if (r8 == r) key = m;
        }
        const int row = key_row(key);
        mbar_wait(bar_row + FB_KDONE);
        if (lane == 0) mbar_expect(bar_x, 8 * 1152);
        __syncwarp();
        if (lane < 8) bulk_g2s(sb + SF_XS + lane * 1168, p.u + (size_t)row * DM, 1152, bar_x);
        TSTAMP(6);
        if (isx) {
            if (!(f & 1)) {
                stg128(p.out + (size_t)row * DM + 16 * f + 8 * mi, 0, 0, 0, 0);
                fence_gpu();
                __syncwarp();
                if (lane < 8) st_rlx32(&p.s->sel[4 * f + lane], key);
            }
            wait_sel(p, f >> 1, r8, tag);
            uint32_t gb;
            for (int it = 0;; it++) {
                asm volatile("ld.relaxed.gpu.global.u16 %0, [%1];" : "=r"(gb) : "l"(p.s->gate + row) : "memory");
                gb ^= par;
                if (!(gb & 0x8000u)) break;
                if (it > (1 << 20)) __trap();
            }
            const uint32_t rb = key ^ 0x80000000u, rv = (rb ^ (((int)rb >> 31) & 0x7fff0000u)) & 0xffff0000u;
            sts64(s_tok + r8 * 8, row, __float_as_uint(rbf(1.0f - bf_lo(gb)) * rbf(sigmoidf_(__uint_as_float(rv)))));
            __syncwarp();
            TSTAMP(7);
            bar_arrive(BAR_RED, 416);
        }
    } else {
        if (rw < nrw) {
            float c[2][4];
#pragma unroll
            for (int i = 0; i < 2; i++) { c[i][0] = c[i][1] = c[i][2] = c[i][3] = 0.f; }
            mbar_wait(bar_row + 48); mbar_wait(bar_row + 56);
            const uint32_t b = fresh(sb + SF_WR) + (g & 1) * 1152 + (g >> 2) * 64 + t * 16 + (g & 2) * 2;
            uint32_t w[18][2];
#pragma unroll
            for (int kb = 0; kb < 18; kb++) { const uint32_t o = ((kb & 1) ? b ^ 64 : b) + 128 * (kb >> 1); w[kb][0] = lds32(o); w[kb][1] = lds32(o + 8); }
            mbar_wait(bar_row + 8 * rw);
            if (warp == 15) TSTAMP(2);
            const uint32_t a = fresh(rows) + g * 1152 + (g & 1) * 64 + t * 16;
#pragma unroll
            for (int kb = 0; kb < 18; kb++) {
                const uint4 x = lds128(((kb & 1) ? a ^ 64 : a) + 128 * (kb >> 1));
                mma_bf(c[kb & 1], x.x, x.y, x.z, x.w, w[kb][0], w[kb][1]);
            }
            const float sr = c[0][0] + c[1][0] + __shfl_down_sync(0xffffffffu, c[0][2] + c[1][2], 1);
            const float sg = c[0][1] + c[1][1] + __shfl_down_sync(0xffffffffu, c[0][3] + c[1][3], 1);
            if (t == 2 * (g & 1)) sts64(s_part + (8 * rw + g) * 8, __float_as_uint(sr), __float_as_uint(sg));
            __syncwarp();
            bar_arrive(BAR_R, 32 * (nrw + 1));
            if (lane == 0) mbar_arrive(bar_rdone);
        }
    }
}

__device__ __forceinline__ void ffn_work(const Params& p, uint32_t sb, int warp, int lane, int f, unsigned epoch) {
    const int g = lane >> 2, t = lane & 3, mi = lane >> 3, r8 = lane & 7;
    const bool isx = f < NX;
    const int ks0 = isx ? 4 * f : 6 * f - 72, nt = isx ? 4 : 6;
    const uint32_t bar_x = sb + SF_MISC + FB_X, bar_free = sb + SF_MISC + FB_FREE, bar_w = sb + SF_MISC + FB_W, bar_d = sb + SF_MISC + FB_D, bar_h = sb + SF_MISC + FB_H, s_tok = sb + SF_MISC + FS_TOK;
    next_epoch(p, epoch);
    {
        if (warp < nt) {
            float ag[2][4], au[2][4];
#pragma unroll
            for (int i = 0; i < 2; i++) { ag[i][0] = ag[i][1] = ag[i][2] = ag[i][3] = 0.f; au[i][0] = au[i][1] = au[i][2] = au[i][3] = 0.f; }
            const uint32_t wb = sb + (warp >> 1) * 4096 + (r8 + 8 * (mi >> 1)) * 64 + (((2 * (warp & 1) + (mi & 1)) ^ (r8 >> 1)) << 4);
            const uint32_t xb = sb + SF_XS + r8 * 1168 + mi * 16;
            mbar_wait(bar_x);
            if (warp == 0) TSTAMP(8);
#pragma unroll 1
            for (int n = 0; n < 9; n++) {
                mbar_wait(bar_w + 8 * n);
                const uint32_t wk = fresh(wb) + n * nt * 4096, xk = fresh(xb) + 128 * n;
                uint32_t x[4];
#pragma unroll
                for (int s = 0; s < 4; s++) {
                    uint32_t a[4], b[4];
                    if (!(s & 1)) ldsm4(x, xk + 32 * s);
                    ldsm4t(a, wk + 1024 * s); ldsm4t(b, wk + 1024 * s + nt * 2048);
                    mma_bf(ag[s & 1], a[0], a[1], a[2], a[3], x[2 * (s & 1)], x[2 * (s & 1) + 1]);
                    mma_bf(au[s & 1], b[0], b[1], b[2], b[3], x[2 * (s & 1)], x[2 * (s & 1) + 1]);
                }
                asm volatile("" :: "f"(ag[0][0]), "f"(ag[1][0]), "f"(au[0][0]), "f"(au[1][0]) : "memory");
                if (n == 4 && lane == 0 && isx) mbar_arrive(bar_free);
            }
            if (warp == 0) TSTAMP(9);
            float h[4];
#pragma unroll
            for (int c = 0; c < 4; c++) {
                const float gv = rbf(ag[0][c] + ag[1][c]);
                h[c] = rbf(gv * sigmoidf_(gv)) * rbf(au[0][c] + au[1][c]);
            }
            uint32_t h0, h1;
            asm("movmatrix.sync.aligned.m8n8.trans.b16 %0, %1;" : "=r"(h0) : "r"(pack_bf16(h[0], h[1])));
            asm("movmatrix.sync.aligned.m8n8.trans.b16 %0, %1;" : "=r"(h1) : "r"(pack_bf16(h[2], h[3])));
            if (h0 == 0) h0 = 0x8000u;
            asm volatile("{ .reg .b64 v; mov.b64 v, {%1, %2}; st.relaxed.gpu.global.b64 [%0], v; }" :: "l"(p.s->h + ((epoch & 1) * 288 + ks0 + warp) * 32 + lane), "r"(h0), "r"(h1) : "memory");
        }
        if (isx) {
            bar_sync(BAR_GU, 384);
            if (warp == 0) TSTAMP(10);
            uint2 hb[12];
            const uint32_t hs = sb + SF_H + warp * 3072;
            const uint2* hsrc = p.s->h + ((__shfl_sync(0xffffffffu, epoch, 0) & 1) * 288 + 144 * (f & 1) + 12 * warp) * 32;
            for (int it = 0;; it++) {
                if (lane == 0) { mbar_expect(bar_h + 8 * warp, 3072); bulk_g2s(hs, hsrc, 3072, bar_h + 8 * warp); }
                mbar_wait(bar_h + 8 * warp, it & 1);
                const uint32_t hf = fresh(hs) + lane * 8;
                uint32_t mn = 0xffffffffu;
#pragma unroll
                for (int s = 0; s < 12; s++) { hb[s] = lds64(hf + 256 * s); mn = min(mn, hb[s].x); }
                if (__all_sync(0xffffffffu, mn != 0)) break;
                if (it > (1 << 16)) __trap();
            }
            if (warp == 0) TSTAMP(11);
            mbar_wait(bar_d + 8 * warp);
            if (warp == 11) TSTAMP(14);
            float ad[2][2][4];
#pragma unroll
            for (int i = 0; i < 4; i++) { ad[i >> 1][i & 1][0] = ad[i >> 1][i & 1][1] = ad[i >> 1][i & 1][2] = ad[i >> 1][i & 1][3] = 0.f; }
            const uint32_t wd = fresh(sb) + (warp < 6 ? SF_WD : -6 * 12288) + warp * 12288 + (r8 + 8 * (mi >> 1)) * 64 + (((mi & 1) ^ (r8 >> 1)) << 4);
#pragma unroll
            for (int s = 0; s < 12; s++) {
                uint32_t a[4], b[4];
                ldsm4t(a, wd + 1024 * s); ldsm4t(b, (wd ^ 32) + 1024 * s);
                mma_bf(ad[0][s & 1], a[0], a[1], a[2], a[3], hb[s].x, hb[s].y);
                mma_bf(ad[1][s & 1], b[0], b[1], b[2], b[3], hb[s].x, hb[s].y);
            }
            const uint32_t rd = sb + SF_RED + warp * 1152 + (72 * t + g) * 4;
#pragma unroll
            for (int i = 0; i < 8; i++) sts32(rd + (i >> 2) * 64 + (i & 1) * 144 + ((i >> 1) & 1) * 32, __float_as_uint(ad[i >> 2][0][i & 3] + ad[i >> 2][1][i & 3]));
            bar_sync(BAR_RED, 416);
            if (warp < 4) {
                const int tid = 32 * warp + lane;
                const uint32_t rs = fresh(sb + SF_RED) + (tid >> 4) * 144 + (tid & 15) * 8;
                const uint2 tk = lds64(fresh(s_tok) + (tid >> 4) * 8);
                float x = 0.f, y = 0.f;
#pragma unroll
                for (int w = 0; w < 12; w++) { const uint2 v = lds64(rs + w * 1152); x += __uint_as_float(v.x); y += __uint_as_float(v.y); }
                asm volatile("red.relaxed.gpu.global.add.noftz.bf16x2 [%0], %1;" :: "l"(p.out + (size_t)tk.x * DM + 32 * (f >> 1) + 2 * (tid & 15)),
                             "r"(pack_bf16(x * __uint_as_float(tk.y), y * __uint_as_float(tk.y))) : "memory");
            }
            if (warp == 0) TSTAMP(15);
        }
        if (warp == 0) TFLUSH();
    }
}

constexpr int SMEM_BYTES = 232448;
static_assert(SF_MISC + 1024 <= 232192, "layout");

struct Maps { CUtensorMap m[6]; };

__global__ void __cluster_dims__(2, 1, 1) __launch_bounds__(NTHR, 1)
fused_kernel(const Params p, const __grid_constant__ Maps maps) {
    extern __shared__ __align__(1024) uint8_t smem_raw[];
    const unsigned epoch = ld_rlx32(&p.s->epoch[blockIdx.x * 16 + (threadIdx.x >> 5)]);
    const uint32_t sb = __shfl_sync(0xffffffffu, smem_u32(smem_raw), 0);
    const int warp = __shfl_sync(0xffffffffu, threadIdx.x >> 5, 0), bid = __shfl_sync(0xffffffffu, blockIdx.x, 0);
    const int lane = __shfl_sync(0xffffffffu, threadIdx.x & 31, threadIdx.x);
    const bool conv = bid < NCONV;
    const int f = bid - NCONV;
    uint32_t w[12];
    if (warp < (f < 12 ? 8 : 10)) {
        const int half = conv ? warp >> 2 : warp & 1, pr = conv ? warp & 3 : warp >> 1;
        const int rc = (f < 12 ? 4 * f : 5 * f - 12) + pr, ch = conv ? 8 * bid + pr : 8 * (rc >> 2) + 4 + (rc & 3);
        const uint32_t stage = sb + (conv ? SC_KG : SF_KG) + warp * KG_STAGE;
        uint4* const kp = p.s->kp + rc * 128 + lane;
        kgen(p, sb, ch, half, stage, stage + (conv ? 4 : 1) * KG_STAGE, 1 + pr, lane, w, [&] {
            const uint32_t a = sb + SC_KT + warp * KT_BYTES + lane * 16;
#pragma unroll
            for (int i = 0; i < 6; i++) sts128z_if(conv && lane < 30, a + 480 * i);
            stg128z_if(!conv, kp + 64 * half); stg128z_if(!conv, kp + 64 * half + 32);
            stg128z_if(!conv && warp < (f < NX ? 4 : 6), (uint4*)(p.s->h + ((lane >> 4) * 288 + (f < NX ? 4 * f : 6 * f - 72) + warp) * 32) + (lane & 15));
            if (conv) asm volatile("barrier.cluster.arrive.relaxed.aligned;" ::: "memory");
        });
        if (!conv) {
            if (!half) {
#pragma unroll
                for (int i = 0; i < 4; i++) asm volatile("st.relaxed.gpu.global.v4.u32 [%0], {%1,%2,%3,%4};" :: "l"(kp + 32 * i), "r"(w[3 * i]), "r"(w[3 * i + 1]), "r"(w[3 * i + 2]), "r"(~epoch) : "memory");
            }
            if (warp == 0) TSTAMP(22);
            if (warp == 2) TSTAMP(23);
            bar_sync(0, NTHR);
            if (warp == 0 && lane == 0) mbar_arrive(sb + SF_MISC + FB_KDONE);
        }
    } else if (conv) {
        conv_aux(p, maps.m, sb, warp - 8, lane, bid, epoch);
        return;
    } else {
        ffn_front(p, maps.m, sb, warp, lane, f, epoch);
        if (warp >= 12) return;
    }
    if (conv) conv_main(p, sb, warp, lane, bid, epoch, w);
    else ffn_work(p, sb, warp, lane, f, epoch);
}

typedef CUresult (*EncodeFn)(CUtensorMap*, CUtensorMapDataType, cuuint32_t, void*, const cuuint64_t*, const cuuint64_t*, const cuuint32_t*, const cuuint32_t*,
                             CUtensorMapInterleave, CUtensorMapSwizzle, CUtensorMapL2promotion, CUtensorMapFloatOOBfill);

void make_map(EncodeFn fn, CUtensorMap* m, const void* base, int rank, const cuuint64_t* dims, const cuuint64_t* strides, const cuuint32_t* box, CUtensorMapSwizzle sw) {
    const cuuint32_t es[4] = {1, 1, 1, 1};
    fn(m, CU_TENSOR_MAP_DATA_TYPE_BFLOAT16, rank, (void*)base, dims, strides, box, es, CU_TENSOR_MAP_INTERLEAVE_NONE, sw,
       CU_TENSOR_MAP_L2_PROMOTION_NONE, CU_TENSOR_MAP_FLOAT_OOB_FILL_NONE);
}

}

extern "C" void kernel_launch(void* const* d_in, const int* in_sizes, int n_in, void* d_out, int out_size) {
    (void)in_sizes; (void)n_in; (void)out_size;
    static EncodeFn fn = nullptr;
    static void* scratch = nullptr;
    if (!fn) {
        void* ptr = nullptr; cudaDriverEntryPointQueryResult qr;
        cudaGetDriverEntryPoint("cuTensorMapEncodeTiled", &ptr, cudaEnableDefault, &qr);
        fn = (EncodeFn)ptr;
        cudaGetSymbolAddress(&scratch, g_scratch);
        cudaFuncSetAttribute(fused_kernel, cudaFuncAttributeMaxDynamicSharedMemorySize, SMEM_BYTES);
    }
    typedef const __nv_bfloat16* bp;
    Params p;
    p.u = (bp)d_in[0]; p.Are = (bp)d_in[1]; p.Aim = (bp)d_in[2]; p.Bre = (bp)d_in[3]; p.Bim = (bp)d_in[4]; p.Cre = (bp)d_in[5]; p.Cim = (bp)d_in[6];
    p.logdt = (bp)d_in[7]; p.Dskip = (bp)d_in[8]; p.wr = (bp)d_in[10]; p.gatew = (bp)d_in[14];
    p.out = (__nv_bfloat16*)d_out; p.s = (Scratch*)scratch;
    Maps maps;
    {
        const cuuint64_t dims[4] = {DM, 4, 8, 64}, strides[3] = {8 * DM * 2, DM * 2, 32 * DM * 2};
        const cuuint32_t box[4] = {16, 4, 8, 8};
        make_map(fn, &maps.m[0], d_in[0], 4, dims, strides, box, CU_TENSOR_MAP_SWIZZLE_32B);
    }
    for (int i = 0; i < 4; i++) {
        const cuuint64_t dims[3] = {32, DM, FF / 32}, strides[2] = {FF * 2, 64};
        const cuuint32_t box[3] = {32, 64, i < 2 ? 2u : 3u};
        make_map(fn, &maps.m[1 + i], d_in[11 + (i & 1)], 3, dims, strides, box, CU_TENSOR_MAP_SWIZZLE_64B);
    }
    {
        const cuuint64_t dims[2] = {DM, FF}, strides[1] = {DM * 2};
        const cuuint32_t box[2] = {32, 192};
        make_map(fn, &maps.m[5], d_in[13], 2, dims, strides, box, CU_TENSOR_MAP_SWIZZLE_64B);
    }
    fused_kernel<<<NCTA, NTHR, SMEM_BYTES>>>(p, maps);
}
```

```cpp
#include <cuda_runtime.h>
#include <cuda_bf16.h>
#include <cuda_fp16.h>
#include <cuda.h>
#include <stdint.h>

#define WSTAG 0
#define WSPLIT 1
#define DSTAG 0
#define UDELAY 300
#define RDELAY 900
#define WDELAY 2700
#define WGAP 650
#define DDELAY 8600
#define DGAP 250

namespace {

constexpr int DM = 576, NST = 128, FF = 4608, L_SEQ = 2048;
constexpr int NCONV = 72, NX = 36, NFFN = 60, NCTA = 132, NTHR = 512;

struct __align__(128) Scratch {
    unsigned epoch[NCTA * 16];
    uint4 keys[16 * 128];
    uint32_t sel[18 * 64];
    uint16_t gate[L_SEQ];
    uint2 h[2 * 288 * 32];
    uint4 kp[288 * 128];
};
__device__ Scratch g_scratch;
#define TFLUSH()
#define TSTAMP(i)

struct Params {
    const __nv_bfloat16 *Are, *Aim, *Bre, *Bim, *Cre, *Cim, *logdt, *Dskip, *u, *wr, *gatew;
    __nv_bfloat16* out;
    Scratch* s;
    uint32_t zero;
};

__device__ __forceinline__ uint32_t smem_u32(const void* p) { return (uint32_t)__cvta_generic_to_shared(p); }
__device__ __forceinline__ uint32_t pack_bf16(float lo, float hi) { uint32_t r; asm("cvt.rn.bf16x2.f32 %0, %1, %2;" : "=r"(r) : "f"(hi), "f"(lo)); return r; }
__device__ __forceinline__ uint32_t pack_f16(float lo, float hi) { uint32_t r; asm("cvt.rn.f16x2.f32 %0, %1, %2;" : "=r"(r) : "f"(hi), "f"(lo)); return r; }
__device__ __forceinline__ float bf_lo(uint32_t w) { return __uint_as_float(w << 16); }
__device__ __forceinline__ float bf_hi(uint32_t w) { return __uint_as_float(w & 0xffff0000u); }
__device__ __forceinline__ float rbf(float x) { return bf_lo(pack_bf16(x, 0.f)); }
__device__ __forceinline__ uint32_t badd2(uint32_t a, uint32_t b) { uint32_t r; asm("add.rn.bf16x2 %0, %1, %2;" : "=r"(r) : "r"(a), "r"(b)); return r; }
__device__ __forceinline__ uint32_t bsub2(uint32_t a, uint32_t b) { uint32_t r; asm("sub.rn.bf16x2 %0, %1, %2;" : "=r"(r) : "r"(a), "r"(b)); return r; }
__device__ __forceinline__ uint32_t gmix(uint32_t g, uint32_t y, uint32_t u) {
    uint32_t r; asm("{ .reg .b32 n, t; neg.bf16x2 n, %1; fma.rn.bf16x2 t, n, %3, %3; fma.rn.bf16x2 %0, %1, %2, t; }" : "=r"(r) : "r"(g), "r"(y), "r"(u)); return r;
}
__device__ __forceinline__ void mma_bf(float (&c)[4], uint32_t a0, uint32_t a1, uint32_t a2, uint32_t a3, uint32_t b0, uint32_t b1) {
    asm("mma.sync.aligned.m16n8k16.row.col.f32.bf16.bf16.f32 {%0,%1,%2,%3}, {%4,%5,%6,%7}, {%8,%9}, {%0,%1,%2,%3};"
        : "+f"(c[0]), "+f"(c[1]), "+f"(c[2]), "+f"(c[3]) : "r"(a0), "r"(a1), "r"(a2), "r"(a3), "r"(b0), "r"(b1));
}
__device__ __forceinline__ void mma_bf8(float (&c)[4], uint32_t a0, uint32_t a1, uint32_t b0) {
    asm("mma.sync.aligned.m16n8k8.row.col.f32.bf16.bf16.f32 {%0,%1,%2,%3}, {%4,%5}, {%6}, {%0,%1,%2,%3};"
        : "+f"(c[0]), "+f"(c[1]), "+f"(c[2]), "+f"(c[3]) : "r"(a0), "r"(a1), "r"(b0));
}
__device__ __forceinline__ void mma_h(float (&c)[4], uint32_t a0, uint32_t a1, uint32_t a2, uint32_t a3, uint32_t b0, uint32_t b1) {
    asm("mma.sync.aligned.m16n8k16.row.col.f32.f16.f16.f32 {%0,%1,%2,%3}, {%4,%5,%6,%7}, {%8,%9}, {%0,%1,%2,%3};"
        : "+f"(c[0]), "+f"(c[1]), "+f"(c[2]), "+f"(c[3]) : "r"(a0), "r"(a1), "r"(a2), "r"(a3), "r"(b0), "r"(b1));
}
__device__ __forceinline__ uint32_t fresh(uint32_t a) { asm volatile("" : "+r"(a) :: "memory"); return a; }
__device__ __forceinline__ uint32_t lds16(uint32_t a) { uint32_t v; asm("ld.shared.u16 %0, [%1];" : "=r"(v) : "r"(a)); return v; }
__device__ __forceinline__ uint32_t lds32(uint32_t a) { uint32_t v; asm("ld.shared.u32 %0, [%1];" : "=r"(v) : "r"(a)); return v; }
__device__ __forceinline__ uint2 lds64(uint32_t a) { uint2 v; asm("ld.shared.v2.u32 {%0,%1}, [%2];" : "=r"(v.x), "=r"(v.y) : "r"(a)); return v; }
__device__ __forceinline__ uint4 lds128(uint32_t a) { uint4 v; asm("ld.shared.v4.u32 {%0,%1,%2,%3}, [%4];" : "=r"(v.x), "=r"(v.y), "=r"(v.z), "=r"(v.w) : "r"(a)); return v; }
__device__ __forceinline__ uint4 lds128v(uint32_t a) { uint4 v; asm volatile("ld.shared.v4.u32 {%0,%1,%2,%3}, [%4];" : "=r"(v.x), "=r"(v.y), "=r"(v.z), "=r"(v.w) : "r"(a) : "memory"); return v; }
__device__ __forceinline__ void ldsm4(uint32_t (&r)[4], uint32_t a) {
    asm("ldmatrix.sync.aligned.m8n8.x4.shared.b16 {%0,%1,%2,%3}, [%4];" : "=r"(r[0]), "=r"(r[1]), "=r"(r[2]), "=r"(r[3]) : "r"(a));
}
__device__ __forceinline__ void ldsm4t(uint32_t (&r)[4], uint32_t a) {
    asm("ldmatrix.sync.aligned.m8n8.x4.trans.shared.b16 {%0,%1,%2,%3}, [%4];" : "=r"(r[0]), "=r"(r[1]), "=r"(r[2]), "=r"(r[3]) : "r"(a));
}
__device__ __forceinline__ void sts16(uint32_t a, uint32_t v) { asm volatile("st.shared.u16 [%0], %1;" :: "r"(a), "h"((unsigned short)v) : "memory"); }
__device__ __forceinline__ void sts32(uint32_t a, uint32_t v) { asm volatile("st.shared.u32 [%0], %1;" :: "r"(a), "r"(v) : "memory"); }
__device__ __forceinline__ void sts64(uint32_t a, uint32_t x, uint32_t y) { asm volatile("st.shared.v2.u32 [%0], {%1,%2};" :: "r"(a), "r"(x), "r"(y) : "memory"); }
__device__ __forceinline__ void sts128(uint32_t a, uint32_t x, uint32_t y, uint32_t z, uint32_t w) {
    asm volatile("st.shared.v4.u32 [%0], {%1,%2,%3,%4};" :: "r"(a), "r"(x), "r"(y), "r"(z), "r"(w) : "memory");
}
__device__ __forceinline__ void st_async128(uint32_t a, uint32_t x, uint32_t y, uint32_t z, uint32_t w, uint32_t bar) {
    asm volatile("st.async.weak.shared::cluster.mbarrier::complete_tx::bytes.v4.b32 [%0], {%1,%2,%3,%4}, [%5];" :: "r"(a), "r"(x), "r"(y), "r"(z), "r"(w), "r"(bar) : "memory");
}
__device__ __forceinline__ void mbar_init(uint32_t b, uint32_t cnt) { asm volatile("mbarrier.init.shared::cta.b64 [%0], %1;" :: "r"(b), "r"(cnt) : "memory"); }
__device__ __forceinline__ void mbar_fence() { asm volatile("fence.mbarrier_init.release.cluster;" ::: "memory"); }
__device__ __forceinline__ void mbar_expect(uint32_t b, uint32_t bytes) { asm volatile("mbarrier.arrive.expect_tx.shared::cta.b64 _, [%0], %1;" :: "r"(b), "r"(bytes) : "memory"); }
__device__ __forceinline__ void mbar_arrive(uint32_t b) { asm volatile("mbarrier.arrive.shared::cta.b64 _, [%0];" :: "r"(b) : "memory"); }
__device__ __forceinline__ void mbar_wait(uint32_t b, uint32_t parity = 0) {
    asm volatile("{ .reg .pred p; .reg .u32 n; mov.u32 n, 0;\n"
                 "LW: mbarrier.try_wait.parity.shared::cta.b64 p, [%0], %1; @p bra LD; add.u32 n, n, 1; setp.lt.u32 p, n, 4194304; @p bra LW; trap;\n"
                 "LD: }" :: "r"(b), "r"(parity) : "memory");
}
__device__ __forceinline__ void mbar_wait_cluster(uint32_t b) {
    asm volatile("{ .reg .pred p; .reg .u32 n; mov.u32 n, 0;\n"
                 "LW: mbarrier.try_wait.parity.acquire.cluster.shared::cta.b64 p, [%0], 0; @p bra LD; add.u32 n, n, 1; setp.lt.u32 p, n, 4194304; @p bra LW; trap;\n"
                 "LD: }" :: "r"(b) : "memory");
}
__device__ __forceinline__ void tma2d(uint32_t dst, const CUtensorMap* m, int c0, int c1, uint32_t bar) {
    asm volatile("cp.async.bulk.tensor.2d.shared::cluster.global.mbarrier::complete_tx::bytes [%0], [%1, {%3, %4}], [%2];"
                 :: "r"(dst), "l"(m), "r"(bar), "r"(c0), "r"(c1) : "memory");
}
__device__ __forceinline__ void tma3d(uint32_t dst, const CUtensorMap* m, int c0, int c1, int c2, uint32_t bar) {
    asm volatile("cp.async.bulk.tensor.3d.shared::cluster.global.mbarrier::complete_tx::bytes [%0], [%1, {%3, %4, %5}], [%2];"
                 :: "r"(dst), "l"(m), "r"(bar), "r"(c0), "r"(c1), "r"(c2) : "memory");
}
__device__ __forceinline__ void tma4d(uint32_t dst, const CUtensorMap* m, int c0, int c1, int c2, int c3, uint32_t bar) {
    asm volatile("cp.async.bulk.tensor.4d.shared::cluster.global.mbarrier::complete_tx::bytes [%0], [%1, {%3, %4, %5, %6}], [%2];"
                 :: "r"(dst), "l"(m), "r"(bar), "r"(c0), "r"(c1), "r"(c2), "r"(c3) : "memory");
}
__device__ __forceinline__ void bulk_g2s(uint32_t dst, const void* src, uint32_t bytes, uint32_t bar) {
    asm volatile("cp.async.bulk.shared::cluster.global.mbarrier::complete_tx::bytes [%0], [%1], %2, [%3];"
                 :: "r"(dst), "l"(src), "r"(bytes), "r"(bar) : "memory");
}
__device__ __forceinline__ uint32_t mapa(uint32_t a, uint32_t rank) { uint32_t r; asm("mapa.shared::cluster.u32 %0, %1, %2;" : "=r"(r) : "r"(a), "r"(rank)); return r; }
__device__ __forceinline__ void prefetch_map(const CUtensorMap* m) { asm volatile("prefetch.tensormap [%0];" :: "l"(m) : "memory"); }
__device__ __forceinline__ void bar_sync(int id, int n) { asm volatile("bar.sync %0, %1;" :: "r"(id), "r"(n) : "memory"); }
__device__ __forceinline__ void bar_arrive(int id, int n) { asm volatile("bar.arrive %0, %1;" :: "r"(id), "r"(n) : "memory"); }
__device__ __forceinline__ void fence_gpu() { asm volatile("fence.acq_rel.gpu;" ::: "memory"); }
__device__ __forceinline__ uint32_t ldg16_if(bool c, const void* p) { uint32_t v; asm volatile("{ .reg .pred p; setp.ne.u32 p, %2, 0; @p ld.global.nc.u16 %0, [%1]; }" : "=r"(v) : "l"(p), "r"((uint32_t)c)); return v; }
__device__ __forceinline__ uint32_t ldg32_if(bool c, const void* p) { uint32_t v; asm volatile("{ .reg .pred p; setp.ne.u32 p, %2, 0; @p ld.global.nc.u32 %0, [%1]; }" : "=r"(v) : "l"(p), "r"((uint32_t)c)); return v; }
__device__ __forceinline__ uint32_t ld_rlx32(const void* p) { uint32_t v; asm volatile("ld.relaxed.gpu.global.u32 %0, [%1];" : "=r"(v) : "l"(p) : "memory"); return v; }
__device__ __forceinline__ uint4 ld_rlx128(const void* p) {
    uint4 v; asm volatile("ld.relaxed.gpu.global.v4.u32 {%0,%1,%2,%3}, [%4];" : "=r"(v.x), "=r"(v.y), "=r"(v.z), "=r"(v.w) : "l"(p) : "memory"); return v;
}
__device__ __forceinline__ void st_rlx32(void* p, uint32_t v) { asm volatile("st.relaxed.gpu.global.u32 [%0], %1;" :: "l"(p), "r"(v) : "memory"); }
__device__ __forceinline__ void stg128(void* p, uint32_t x, uint32_t y, uint32_t z, uint32_t w) {
    asm volatile("st.global.v4.u32 [%0], {%1,%2,%3,%4};" :: "l"(p), "r"(x), "r"(y), "r"(z), "r"(w) : "memory");
}
__device__ __forceinline__ void next_epoch(const Params& p, unsigned e) { if ((threadIdx.x & 31) == 0) p.s->epoch[blockIdx.x * 16 + (threadIdx.x >> 5)] = e + 1; }
__device__ __forceinline__ void sts128z_if(bool c, uint32_t a) { asm volatile("{ .reg .pred p; setp.ne.u32 p, %1, 0; @p st.shared.v4.u32 [%0], {%2,%2,%2,%2}; }" :: "r"(a), "r"((uint32_t)c), "r"(0) : "memory"); }
__device__ __forceinline__ void stg128z_if(bool c, void* a) { asm volatile("{ .reg .pred p; setp.ne.u32 p, %1, 0; @p st.global.v4.u32 [%0], {%2,%2,%2,%2}; }" :: "l"(a), "r"((uint32_t)c), "r"(0) : "memory"); }
__device__ __forceinline__ unsigned clock32() { unsigned c; asm volatile("mov.u32 %0, %clock;" : "=r"(c) :: "memory"); return c; }
__device__ __forceinline__ void until(unsigned t0, unsigned c) { while (clock32() - t0 < c) { } }
__device__ __forceinline__ float sigmoidf_(float x) { return __fdividef(1.0f, 1.0f + __expf(-x)); }
__device__ __forceinline__ uint32_t key_tag(unsigned epoch) { return ((epoch & 15u) | 16u) << 11; }
__device__ __forceinline__ int key_row(uint32_t key) { return 2047 - (int)(key & 2047u); }
__device__ __forceinline__ uint32_t wait_sel(const Params& p, int s32, int r8, uint32_t tag) {
    uint32_t k;
    for (int it = 0;; it++) {
        k = ld_rlx32(&p.s->sel[s32 * 64 + r8]);
        if (__all_sync(0xffffffffu, (k & 0xf800u) == tag)) break;
        if (it > (1 << 20)) __trap();
    }
    fence_gpu();
    return k;
}

struct cplx { float re, im; };
__device__ __forceinline__ cplx csq(cplx a) { cplx r; r.re = a.re * a.re - a.im * a.im; r.im = (a.re * a.im) * 2.f; return r; }
__device__ __forceinline__ cplx cexpk(float ar, float ai, float k) {
    float mag, s, c;
    asm("ex2.approx.ftz.f32 %0, %1;" : "=f"(mag) : "f"(ar * (k * 1.4426950408889634f)));
    const float r = ai * k;
    asm("sin.approx.ftz.f32 %0, %1;" : "=f"(s) : "f"(r));
    asm("cos.approx.ftz.f32 %0, %1;" : "=f"(c) : "f"(r));
    cplx o; o.re = mag * c; o.im = mag * s; return o;
}
struct h2c { uint32_t re, im; };
__device__ __forceinline__ h2c cmul_cd(h2c v, __half2 c, __half2 d) {
    const __half2 r = *(const __half2*)&v.re, i = *(const __half2*)&v.im;
    const __half2 x = __hfma2(__hneg2(i), d, __hmul2(r, c)), y = __hfma2(i, c, __hmul2(r, d));
    h2c o; o.re = *(const uint32_t*)&x; o.im = *(const uint32_t*)&y; return o;
}
__device__ __forceinline__ h2c cmul_s(h2c v, uint32_t s) { const __half2 h = *(const __half2*)&s; return cmul_cd(v, __low2half2(h), __high2half2(h)); }
__device__ __forceinline__ h2c cmul_sc(h2c v, uint32_t s) {
    const __half2 h = *(const __half2*)&s, c = __low2half2(h), d = __high2half2(h), r = *(const __half2*)&v.re, i = *(const __half2*)&v.im;
    const __half2 x = __hfma2(i, d, __hmul2(r, c)), y = __hfma2(__hneg2(r), d, __hmul2(i, c));
    h2c o; o.re = *(const uint32_t*)&x; o.im = *(const uint32_t*)&y; return o;
}
__device__ __forceinline__ h2c cmul_vc(h2c v, uint32_t s) {
    const __half2 h = *(const __half2*)&s, c = __low2half2(h), d = __high2half2(h), r = *(const __half2*)&v.re, i = *(const __half2*)&v.im;
    const __half2 x = __hfma2(i, d, __hmul2(r, c)), y = __hfma2(__hneg2(i), c, __hmul2(r, d));
    h2c o; o.re = *(const uint32_t*)&x; o.im = *(const uint32_t*)&y; return o;
}

constexpr int UT_HALF = 2240, UT_STRIDE = 4448;
constexpr int KT_T = 542, KT_C = 552, KT_D = 648, KT_BYTES = 720 * 4;
constexpr int VC_OFF = 80, VE_BASE = 1616;
constexpr int V_STRIDE = (1616 + 1024) * 4 + 80;
constexpr int KG_STAGE = 5248;
constexpr int Y_CS = 2080, Y_RS = 8 * Y_CS + 64;

constexpr int SC_RT = 0;
constexpr int SC_UT = 33408;
constexpr int SC_ST = SC_UT + 8 * UT_STRIDE;
constexpr int SC_KT = SC_ST + 8 * UT_STRIDE;
constexpr int SC_GT = SC_KT + 8 * KT_BYTES;
constexpr int SC_V = SC_GT + UT_STRIDE;
constexpr int SC_KG = SC_V + 4 * V_STRIDE;
constexpr int SC_KD = SC_V + 8 * V_STRIDE;
constexpr int SC_MISC = SC_KD + 8192;
static_assert(V_STRIDE % 128 == 16 && 8 * KG_STAGE <= 4 * V_STRIDE && 2 * Y_RS <= SC_UT && SC_UT % 128 == 0, "layout");
static_assert(SC_MISC % 16 == 0 && SC_MISC + 512 <= 232192, "layout");

__device__ __forceinline__ void window_task(uint32_t ut, uint32_t vt, int a, bool withE) {
    const uint32_t src = ut + (a + 6) * 16;
    float S[35];
    {
        uint32_t w[20];
#pragma unroll
        for (int i = 0; i < 5; i++) {
            const uint4 v = lds128(src + ((i & 1) ? 0 : UT_HALF) + ((i + 1) >> 1) * 16);
            w[4 * i] = v.x; w[4 * i + 1] = v.y; w[4 * i + 2] = v.z; w[4 * i + 3] = v.w;
        }
        float s = 0.f; S[2] = 0.f;
#pragma unroll
        for (int i = 3; i < 26; i++) { s += (i & 1) ? bf_hi(w[i >> 1]) : bf_lo(w[i >> 1]); S[i] = s; }
        const uint32_t dst = vt + (VC_OFF - 16 + 16 * a) * 4;
#pragma unroll
        for (int i = 0; i < 16; i += 4)
            sts128(dst + 4 * i, pack_bf16(S[10 + i] - S[5 + i], S[5 + i] - S[2 + i]), pack_bf16(S[11 + i] - S[6 + i], S[6 + i] - S[3 + i]),
                   pack_bf16(S[12 + i] - S[7 + i], S[7 + i] - S[4 + i]), pack_bf16(S[13 + i] - S[8 + i], S[8 + i] - S[5 + i]));
        if (withE) {
#pragma unroll
            for (int i = 26; i < 35; i++) { s += (i & 1) ? bf_hi(w[i >> 1]) : bf_lo(w[i >> 1]); S[i] = s; }
            const uint32_t dse = vt + (VE_BASE + 16 * a) * 4;
#pragma unroll
            for (int i = 0; i < 16; i += 4)
                sts128(dse + 4 * i, pack_bf16(S[19 + i] - S[12 + i], S[12 + i] - S[3 + i]), pack_bf16(S[20 + i] - S[13 + i], S[13 + i] - S[4 + i]),
                       pack_bf16(S[21 + i] - S[14 + i], S[14 + i] - S[5 + i]), pack_bf16(S[22 + i] - S[15 + i], S[15 + i] - S[6 + i]));
        }
    }
}

template <class F>
__device__ __forceinline__ void kgen(const uint32_t (&q)[8], uint32_t sb, int half, uint32_t stage, uint32_t pstage, int barid, int lane, uint32_t (&w)[12], F shadow) {
    const int t = lane & 3, mi = lane >> 3, r8 = lane & 7;
    {
        const uint32_t pAr = q[0], pAi = q[1], pBr = q[2], pBi = q[3], pCr = q[4], pCi = q[5], pDt = q[6], pD = q[7];
        const uint32_t wb = fresh(stage + lane * 16), za = fresh(stage + 5120 + ((lane >> 1) & 3) * 16 + mi * 4 + (lane & 1) * 2), zr = fresh(stage + 5120 + t * 16);
        const uint32_t oA = fresh(stage + (mi & 1) * 1024 + (mi >> 1) * 512 + r8 * 16), oB = fresh(stage + 2048 + mi * 512 + r8 * 16), oC = fresh(stage + 4096 + (mi & 1) * 512 + (mi >> 1) * 128 + r8 * 16);
        float acc[6][4];
#pragma unroll
        for (int a = 0; a < 6; a++) { acc[a][0] = acc[a][1] = acc[a][2] = acc[a][3] = 0.f; asm volatile("" : "+f"(acc[a][0]), "+f"(acc[a][1]), "+f"(acc[a][2]), "+f"(acc[a][3])); }
        shadow();
        sts32(zr, clock32());
        const float dt = rbf(__expf(bf_lo(pDt)));
        float ar = dt * bf_lo(pAr), ai = dt * bf_lo(pAi), ar1 = dt * bf_hi(pAr), ai1 = dt * bf_hi(pAi);
        float wr, wi, wr1, wi1;
        { const float br = dt * bf_lo(pBr), bi = dt * bf_lo(pBi), cr = bf_lo(pCr), ci = bf_lo(pCi); wr = cr * br - ci * bi; wi = cr * bi + ci * br; }
        { const float br = dt * bf_hi(pBr), bi = dt * bf_hi(pBi), cr = bf_hi(pCr), ci = bf_hi(pCi); wr1 = cr * br - ci * bi; wi1 = cr * bi + ci * br; }
        const uint32_t ex = max(__reduce_max_sync(0xffffffffu, __float_as_uint(fmaxf(fmaxf(fabsf(wr), fabsf(wi)), fmaxf(fabsf(wr1), fabsf(wi1))))) >> 23, 14u);
        const float scl = __uint_as_float((267u - ex) << 23);
        uint32_t W = pack_f16(wr * scl, wi * -scl);
        const uint32_t W1 = pack_f16(wr1 * scl, wi1 * -scl);
        if (threadIdx.x < 32) TSTAMP(20);

#pragma unroll 1
        for (int r = 0; r < 2; r++) {
            const cplx z1 = cexpk(ar, ai, 1.f), z64 = cexpk(ar, ai, 64.f);
            const cplx z2 = csq(z1), z4 = csq(z2), z8 = csq(z4), z16 = csq(z8), z32 = csq(z16);
            const cplx z128 = csq(z64), z256 = csq(z128), z512 = csq(z256), z1024 = csq(z512);
            auto put = [&](int grp, h2c a, h2c b, h2c c, h2c d) { sts128(wb + grp * 1024, a.re, b.re, c.re, d.re); sts128(wb + grp * 1024 + 512, a.im, b.im, c.im, d.im); };
            {
                const uint32_t s1 = pack_f16(z1.re, z1.im), s2 = pack_f16(z2.re, z2.im), s256 = pack_f16(z256.re, z256.im), s512 = pack_f16(z512.re, z512.im), s1024 = pack_f16(z1024.re, z1024.im);
                const h2c c04 = cmul_vc(h2c{pack_f16(1.f, z4.re), pack_f16(0.f, z4.im)}, W), c26 = cmul_sc(c04, s2);
                put(2, c04, c26, cmul_sc(c04, s1), cmul_sc(c26, s1));
                const h2c d04 = cmul_sc(c04, s256), e04 = cmul_sc(c04, s512), f04 = cmul_sc(d04, s512);
                put(3, d04, cmul_sc(c26, s256), e04, f04);
                const h2c ef = {__byte_perm(e04.re, f04.re, 0x5410), __byte_perm(e04.im, f04.im, 0x5410)};
                const h2c gh = cmul_sc(ef, s512);
                put(4, gh, cmul_sc(ef, s1024), cmul_sc(gh, s1024), ef);
            }
            {
                const uint32_t s32 = pack_f16(z32.re, z32.im), s64 = pack_f16(z64.re, z64.im), s128 = pack_f16(z128.re, z128.im);
                const h2c p0 = {pack_f16(1.f, z8.re), pack_f16(0.f, z8.im)}, p1 = cmul_s(p0, pack_f16(z16.re, z16.im)), p2 = cmul_s(p0, s32), p3 = cmul_s(p1, s32);
                put(0, p0, p1, p2, p3);
                put(1, cmul_s(p0, s64), cmul_s(p1, s64), cmul_s(p2, s64), cmul_s(p3, s64));
                sts16(za, s128); sts16(za + 64, s128 >> 16);
            }
            __syncwarp();
            {
                const uint32_t aA = fresh(oA), aB = fresh(oB), aC = fresh(oC), aZ = fresh(zr);
                const uint4 zc = lds128(aZ), zd = lds128(aZ + 64);
                const uint32_t zcs[4] = {zc.x, zc.y, zc.z, zc.w}, zds[4] = {zd.x, zd.y, zd.z, zd.w};
                uint32_t c[4];
#pragma unroll
                for (int k = 0; k < 4; k++) {
                    uint32_t a[4], b[4];
                    ldsm4t(a, aA + 128 * k); ldsm4t(b, aB + 128 * k);
                    if (!(k & 1)) ldsm4t(c, aC + 128 * k);
                    const h2c x = cmul_cd(h2c{a[0], a[2]}, *(const __half2*)&zcs[k], *(const __half2*)&zds[k]), y = cmul_cd(h2c{a[1], a[3]}, *(const __half2*)&zcs[k], *(const __half2*)&zds[k]);
                    mma_h(acc[0], a[0], a[1], a[2], a[3], b[0], b[1]);
                    mma_h(acc[1], a[0], a[1], a[2], a[3], b[2], b[3]);
                    mma_h(acc[2], a[0], a[1], a[2], a[3], c[2 * (k & 1)], c[2 * (k & 1) + 1]);
                    mma_h(acc[3], x.re, y.re, x.im, y.im, b[0], b[1]);
                    mma_h(acc[4], x.re, y.re, x.im, y.im, b[2], b[3]);
                    mma_h(acc[5], x.re, y.re, x.im, y.im, c[2 * (k & 1)], c[2 * (k & 1) + 1]);
                }
                asm volatile("" :: "f"(acc[0][0]), "f"(acc[1][0]), "f"(acc[2][0]), "f"(acc[3][0]), "f"(acc[4][0]), "f"(acc[5][0]) : "memory");
            }
            __syncwarp();
            ar = ar1; ai = ai1; W = W1;
        }
        if (threadIdx.x < 32) TSTAMP(21);
        const float i0 = __uint_as_float((ex - 13u) << 23);
        if (half) {
#pragma unroll
            for (int a = 0; a < 6; a++) sts128(wb + a * 512, __float_as_uint(acc[a][0] * i0), __float_as_uint(acc[a][1] * i0), __float_as_uint(acc[a][2] * i0), __float_as_uint(acc[a][3] * i0));
            bar_arrive(barid, 64);
        } else {
            bar_sync(barid, 64);
            const uint32_t src = fresh(pstage) + lane * 16;
#pragma unroll
            for (int a = 0; a < 6; a++) {
                const uint4 y = lds128(src + a * 512);
                float v0 = fmaf(acc[a][0], i0, __uint_as_float(y.x));
                if (a == 0 && lane == 0) v0 += bf_lo(pD);
                w[2 * a] = pack_bf16(v0, fmaf(acc[a][1], i0, __uint_as_float(y.y)));
                w[2 * a + 1] = pack_bf16(fmaf(acc[a][2], i0, __uint_as_float(y.z)), fmaf(acc[a][3], i0, __uint_as_float(y.w)));
            }
        }
    }
}

__device__ __forceinline__ int swap01(int i) { return (i & ~3) | ((i & 1) << 1) | ((i >> 1) & 1); }
enum { BC_AUX = 0, BC_S = 5, BC_KG = 15 };

__device__ __forceinline__ void conv_aux(const Params& p, const CUtensorMap* mU, uint32_t sb, int aw, int lane, int bid, unsigned epoch) {
    const unsigned t0 = clock32();
    const int g = lane >> 2, t = lane & 3, mi = lane >> 3, r8 = lane & 7;
    const int rank = bid & 1, slab = bid >> 1;
    const uint32_t bar_y = sb + SC_MISC, bar_u = bar_y + 32, bar_v = bar_y + 40, bar_box = bar_y + 64 + 8 * aw, s_bm = bar_y + 128;
    if (lane == 0) {
        mbar_init(bar_box, 1); mbar_fence();
        mbar_expect(bar_box, 4096);
        if (UDELAY) until(t0, UDELAY);
        tma4d(sb + SC_RT + 4096 * aw, mU, 16 * slab, 0, 0, 16 * rank + 2 * aw, bar_box);
        mbar_init(bar_y + 8 * aw, aw == 5 ? 8 : 1); mbar_fence();
        if (aw < 5) mbar_expect(bar_y + 8 * aw, aw == 4 ? 16384 : 8192);
    }
    __syncwarp();
    asm volatile("barrier.cluster.arrive.relaxed.aligned;" ::: "memory");
    asm volatile("setmaxnreg.dec.sync.aligned.u32 88;");
    const uint32_t ut = sb + SC_UT + aw * UT_STRIDE;
    sts128(ut + (mi >> 1) * (SC_ST - SC_UT) + (mi & 1) * UT_HALF + r8 * 16, 0, 0, 0, 0);
    if (lane < 16) sts128(s_bm + lane * 16, 0, 0, 0, 0);
    {
        const uint32_t dst = sb + SC_UT + swap01(g) * UT_STRIDE + (8 + 64 * rank + 8 * aw + t) * 16;
        const uint32_t rdst = mapa(dst, rank ^ 1), rbar = mapa(bar_u, rank ^ 1);
        asm volatile("barrier.cluster.wait.acquire.aligned;" ::: "memory");
        mbar_wait(bar_box);
        if (aw == 0) TSTAMP(1);
        const uint32_t src = fresh(sb + SC_RT) + aw * 4096 + (8 * mi + 4 * (r8 & 1) + (r8 >> 1)) * 32 + ((rank ^ (r8 & 1)) << 4);
        uint32_t x[8][4];
#pragma unroll
        for (int i = 0; i < 4; i++) { ldsm4t(x[i], src + 1024 * i); ldsm4t(x[4 + i], (src ^ 16) + 1024 * i); }
        asm volatile("" :: "r"(x[0][0]), "r"(x[1][0]), "r"(x[2][0]), "r"(x[3][0]) : "memory");
#pragma unroll
        for (int i = 0; i < 4; i++) st_async128(rdst + (i & 1) * UT_HALF + 32 * (i & 2), x[4 + i][0], x[4 + i][1], x[4 + i][2], x[4 + i][3], rbar);
#pragma unroll
        for (int i = 0; i < 4; i++) sts128(dst + (i & 1) * UT_HALF + 32 * (i & 2), x[i][0], x[i][1], x[i][2], x[i][3]);
    }
    bar_sync(BC_AUX, 256);
    mbar_wait_cluster(bar_u);
    if (aw == 0) TSTAMP(2);
    {
        const uint32_t a = fresh(ut) + (mi & 1) * UT_HALF + (64 * (mi >> 1) + r8) * 16;
        uint4 v = lds128(a);
#pragma unroll
        for (int i = 1; i <= 8; i++) {
            const uint4 w = lds128(a + 128 * i);
            sts128(a + 128 * i + (SC_ST - SC_UT), badd2(v.x, w.x), badd2(v.y, w.y), badd2(v.z, w.z), badd2(v.w, w.w));
            v = w;
        }
    }
    bar_arrive(BC_S + aw, 64);
    if (aw == 0) TSTAMP(3);
#pragma unroll 1
    for (int k = aw; k < 26; k += 8) {
        if (k - aw == 8) {
            bar_sync(BC_KG, 384);
            if (lane < 16) sts128(sb + SC_V + aw * V_STRIDE + lane * 16, 0, 0, 0, 0);
        }
        const int c = (k < 13 ? 0 : 4) + t, a = 8 * (k < 13 ? k : k - 13) + g;
        if (a < 97) window_task(fresh(sb + SC_UT) + c * UT_STRIDE, sb + SC_V + c * V_STRIDE, a, a < 64);
        __syncwarp();
    }
    if (aw == 0) TSTAMP(9);
    {
        {
            const uint32_t par = (epoch & 1) ? 0u : 0x80008000u;
            uint4 v;
            for (int it = 0;; it++) {
                v = ld_rlx128(p.s->gate + 256 * aw + 8 * lane);
                v.x ^= par; v.y ^= par; v.z ^= par; v.w ^= par;
                if (__all_sync(0xffffffffu, ((v.x | v.y | v.z | v.w) & 0x80008000u) == 0)) break;
                if (it > (1 << 20)) __trap();
            }
            sts128(sb + SC_GT + (lane & 1) * UT_HALF + (8 + 16 * aw + (lane >> 1)) * 16, v.x, v.y, v.z, v.w);
        }
        __syncwarp();
        if (lane == 0) mbar_arrive(bar_v);
        next_epoch(p, epoch);
        if (aw == 0) TSTAMP(4);
        if (aw == 7) {
            const int row = key_row(wait_sel(p, slab >> 1, r8, key_tag(epoch)));
            if (lane < 8) asm volatile("red.shared.or.b32 [%0], %1;" :: "r"(s_bm + (row >> 5) * 4), "r"(1u << (row & 31)) : "memory");
            TSTAMP(10);
        }
        bar_sync(BC_AUX, 256);
        const uint32_t src = sb + SC_RT + ((r8 >> 1) & 1) * Y_RS + (2 * mi + (r8 & 1)) * Y_CS + (2 * aw + (r8 >> 2)) * 16;
        const int L = 2 * aw + (t >> 1);
        const int row0 = 256 * rank + 128 * (g >> 2) + 32 * (L & 3) + 16 * (g & 1) + 8 * ((g >> 1) & 1) + (L >> 2);
        __nv_bfloat16* outp = p.out + (size_t)row0 * DM + 16 * slab + 8 * (t & 1);
#pragma unroll 1
        for (int s = 0; s < 4; s++) {
            const uint32_t bm = lds32(fresh(s_bm) + (16 * s + (row0 >> 5)) * 4) >> (row0 & 31);
            mbar_wait_cluster(bar_y + 8 * s);
            const uint32_t sf = fresh(src) + 512 * s;
#pragma unroll
            for (int k = 0; k < 2; k++) {
                uint32_t y[4];
                ldsm4t(y, sf + 256 * k);
                __nv_bfloat16* o = outp + (size_t)(512 * s + 4 * k) * DM;
                if (bm & (1u << (4 * k)))
                    asm volatile("red.relaxed.gpu.global.add.noftz.v4.bf16x2 [%0], {%1,%2,%3,%4};" :: "l"(o), "r"(y[0]), "r"(y[1]), "r"(y[2]), "r"(y[3]) : "memory");
                else stg128(o, y[0], y[1], y[2], y[3]);
            }
            if (aw == 0) TSTAMP(16 + s);
        }
        if (aw == 0) TFLUSH();
    }
}

__device__ __forceinline__ void conv_main(const Params& p, uint32_t sb, int warp, int lane, int bid, unsigned epoch, uint32_t (&w)[12]) {
    asm volatile("setmaxnreg.inc.sync.aligned.u32 168;");
    const int g = lane >> 2, t = lane & 3, mi = lane >> 3, r8 = lane & 7;
    const int rank = bid & 1;
    const uint32_t bar_y = sb + SC_MISC, bar_v = bar_y + 40;
    next_epoch(p, epoch);
    if (warp < 4) {
        asm volatile("" :: "r"(w[0]), "r"(w[2]), "r"(w[4]), "r"(w[6]), "r"(w[8]), "r"(w[10]) : "memory");
        bar_arrive(BC_KG, 384);
    } else {
        const uint4* src = p.s->kp + (4 * bid + warp - 4) * 128 + lane;
        for (int it = 0;; it++) {
            uint32_t bad = 0;
#pragma unroll
            for (int i = 0; i < 4; i++) { const uint4 v = ld_rlx128(src + 32 * i); w[3 * i] = v.x; w[3 * i + 1] = v.y; w[3 * i + 2] = v.z; bad |= v.w ^ ~epoch; }
            const bool ok = __all_sync(0xffffffffu, bad == 0);
            if (it < 6 && warp == 4) TSTAMP(22 + it);
            if (ok) break;
            if (it > (1 << 20)) __trap();
        }
    }
    if ((warp & 3) == 0) TSTAMP(5 + (warp >> 2));
    {
        const uint32_t kt = sb + SC_KT + warp * KT_BYTES;
        const uint32_t kd = sb + SC_KD + warp * 1024 + 16;
#pragma unroll
        for (int nu = 0; nu < 3; nu++) {
            uint32_t a, a0, de, dr;
            if (nu == 0) { a = kd + (8 * g + 2 * (t & 1) + (t >> 1)) * 2; de = 8; dr = 128; a0 = a; }
            else if (nu == 1) { a = t < 2 ? kd + (256 + 4 * g + t) * 2 : kt + KT_C * 4 + (64 * t - 100 + 2 * g) * 2; de = t < 2 ? 4 : 2; dr = t < 2 ? 64 : 32; a0 = a; }
            else {
                a = t < 2 ? kt + KT_D * 4 + (13 + 64 * t + g) * 2 : kd + 800; de = 64; dr = 16; a0 = a;
                if ((lane & 29) == 0) a0 = kt + (t ? KT_D * 4 + 141 * 2 : KT_C * 4 + 156 * 2);
            }
#pragma unroll
            for (int i = 0; i < 4; i++) {
                const uint32_t v = w[6 * (i >> 1) + 2 * nu + (i & 1)];
                sts16(i ? a + i * dr : a0, v); sts16(a + i * dr + de, v >> 16);
            }
        }
        if (lane == 0) sts128(kt + (KT_T + 2) * 4, 0, w[4] & 0xffffu, __byte_perm(w[4], 0, 0x1010), w[4] << 16);
        __syncwarp();
        const uint32_t kf = fresh(kd), d = kt + (16 + 8 * lane) * 4;
        auto put = [&](uint32_t d, uint32_t pv, uint32_t w0, uint32_t w1, uint32_t w2, uint32_t w3) {
            sts128(d, __byte_perm(w0, pv, 0x5410), __byte_perm(w0, 0, 0x1032), __byte_perm(w1, w0, 0x7610), __byte_perm(w1, 0, 0x1032));
            sts128(d + 16, __byte_perm(w2, w1, 0x7610), __byte_perm(w2, 0, 0x1032), __byte_perm(w3, w2, 0x7610), __byte_perm(w3, 0, 0x1032));
        };
        const uint32_t pv = lds16(kf + (lane ? 16 * lane : 512) - 2);
        const uint4 x = lds128(kf + 16 * lane);
        const uint2 v = lds64(kf + 512 + 8 * lane);
        const uint32_t c4 = lds16(lane == 31 ? fresh(kt) + KT_C * 4 + 28 * 2 : kf + 520 + 8 * lane);
        put(d, lane ? pv : 0, x.x, x.y, x.z, x.w);
        uint32_t w3 = __byte_perm(v.y, c4, 0x5432);
        if (lane == 31) w3 = bsub2(w3, __byte_perm(c4, 0, 0x1010));
        put(d + 1024, lane ? v.x : pv, __byte_perm(v.x, 0, 0x1010), __byte_perm(v.x, v.y, 0x5432), __byte_perm(v.y, 0, 0x1010), w3);
    }
    asm volatile("barrier.cluster.wait.acquire.aligned;" ::: "memory");
    bar_sync(BC_S + swap01(warp), 64);
    if ((warp & 3) == 0) TSTAMP(7 + (warp >> 2));
    {
        const uint32_t ut = fresh(sb + SC_UT) + swap01(warp) * UT_STRIDE, kt = fresh(sb + SC_KT) + warp * KT_BYTES;
        uint32_t u1 = ut + (mi & 1) * UT_HALF + (8 + r8) * 16 + (mi >> 1) * 128;
        auto dup = [&](uint32_t v) { return v ^ p.zero; };
        uint32_t kp = kt + (16 + g - 2 * t) * 4;
        float acc[16][4];
        {
            const uint32_t c0 = lds32(kp + 2048), c1 = lds32(kp + 2080), c2 = lds32(kp + 2016), c3 = dup(c0);
            const uint32_t e0 = lds32(kp + (KT_T - 16) * 4), e1 = lds32(kp + (KT_T - 8) * 4), e2 = lds32(kp + (KT_T - 24) * 4), e3 = dup(e0);
            const uint32_t f0 = dup(e1), f1 = lds32(kp + KT_T * 4);
            const uint32_t uo = ut + UT_HALF + (7 + lane) * 16;
#pragma unroll
            for (int i = 0; i < 16; i++) { acc[i][0] = acc[i][1] = acc[i][2] = acc[i][3] = 0.f; }
#pragma unroll
            for (int mu = 0; mu < 8; mu += 4) {
                uint32_t b[4];
                ldsm4(b, uo + 128 * mu);
#pragma unroll
                for (int k = 0; k < 4; k++) mma_bf8(acc[mu + 8 + k], f0, f1, b[k]);
            }
#pragma unroll
            for (int mu = 0; mu < 12; mu += 2) {
                uint32_t b[4];
                ldsm4(b, u1 + 128 * mu);
                mma_bf(acc[mu + 4], c0, c1, c2, c3, b[0], b[1]);
                mma_bf(acc[mu + 5], c0, c1, c2, c3, b[2], b[3]);
                if (mu < 8) { mma_bf(acc[mu + 8], e0, e1, e2, e3, b[0], b[1]); mma_bf(acc[mu + 9], e0, e1, e2, e3, b[2], b[3]); }
            }
        }
        {
            float M[8][4];
#pragma unroll
            for (int i = 0; i < 8; i++) { M[i][0] = M[i][1] = M[i][2] = M[i][3] = 0.f; }
            uint32_t up = u1 + (mi >> 1) * 128, s[8][4], a3[4];
            auto frag = [&](uint32_t (&a)[4], uint32_t x) { a[0] = lds32(x); a[1] = lds32(x + 32); a[2] = lds32(x - 32); a[3] = dup(a[0]); };
            frag(a3, kp + 1536);
#pragma unroll
            for (int i = 0; i < 8; i++) ldsm4(s[i], u1 + (SC_ST - SC_UT) + 256 * i);
            __syncwarp();
#pragma unroll 1
            for (int j0 = 0; j0 < 8; j0++) {
                uint32_t a2[4], a1[4], a0[4], b[4][4];
                frag(a2, kp + 1024);
#pragma unroll
                for (int i = 0; i < 4; i++) ldsm4(b[i], up + 512 * i);
                frag(a1, kp + 512); frag(a0, kp);
                kp += 64; u1 -= 16; up -= 16;
#pragma unroll
                for (int i = 0; i < 7; i++) mma_bf(acc[2 * i + 2], a3[0], a3[1], a3[2], a3[3], s[i][0], s[i][1]);
#pragma unroll
                for (int e = 0; e < 4; e++) a3[e] = bsub2(a2[e], a3[e]);
#pragma unroll
                for (int i = 0; i < 7; i++) mma_bf(acc[2 * i + 3], a2[0], a2[1], a2[2], a2[3], s[i][2], s[i][3]);
#pragma unroll
                for (int i = 0; i < 7; i++) mma_bf(M[i + 1], a3[0], a3[1], a3[2], a3[3], b[i >> 1][2 * (i & 1)], b[i >> 1][2 * (i & 1) + 1]);
                frag(a3, kp + 1536);
#pragma unroll
                for (int i = 0; i < 8; i++) mma_bf(acc[2 * i], a1[0], a1[1], a1[2], a1[3], s[i][0], s[i][1]);
#pragma unroll
                for (int e = 0; e < 4; e++) a1[e] = bsub2(a0[e], a1[e]);
#pragma unroll
                for (int i = 0; i < 8; i++) { mma_bf(acc[2 * i + 1], a0[0], a0[1], a0[2], a0[3], s[i][2], s[i][3]); ldsm4(s[i], u1 + (SC_ST - SC_UT) + 256 * i); }
#pragma unroll
                for (int i = 0; i < 8; i++) mma_bf(M[i], a1[0], a1[1], a1[2], a1[3], b[i >> 1][2 * (i & 1)], b[i >> 1][2 * (i & 1) + 1]);
            }
            u1 = dup(u1) + 128;
#pragma unroll
            for (int i = 0; i < 8; i++)
#pragma unroll
                for (int c = 0; c < 4; c++) { acc[2 * i][c] += M[i][c]; acc[2 * i + 1][c] -= M[i][c]; }
        }
        if ((warp & 3) == 0) TSTAMP(11 + (warp >> 2));
        mbar_wait(bar_v);
        const uint32_t vt = fresh(sb + SC_V) + swap01(warp) * V_STRIDE;
        const uint32_t g1 = fresh(u1) - ut + sb + SC_GT;
        const uint32_t ydst = sb + SC_RT + rank * Y_RS + warp * Y_CS + lane * 16;
        const uint32_t yd0 = mapa(ydst, 0), yd1 = mapa(ydst, 1), yb0 = mapa(bar_y, 0), yb1 = mapa(bar_y, 1);
        auto ship = [&](int i) {
            uint32_t u[4], gg[4];
            ldsm4t(u, u1 + 256 * i); ldsm4t(gg, g1 + 256 * i);
            st_async128(((i & 1) ? yd1 : yd0) + 512 * (i >> 1),
                        gmix(gg[0], pack_bf16(acc[2 * i][0], acc[2 * i][1]), u[0]), gmix(gg[1], pack_bf16(acc[2 * i][2], acc[2 * i][3]), u[1]),
                        gmix(gg[2], pack_bf16(acc[2 * i + 1][0], acc[2 * i + 1][1]), u[2]), gmix(gg[3], pack_bf16(acc[2 * i + 1][2], acc[2 * i + 1][3]), u[3]),
                        ((i & 1) ? yb1 : yb0) + 8 * (i >> 1));
        };
        ship(0);
        {
            const uint32_t KE = kt + (KT_D + g + t) * 4, VE = vt + (VE_BASE - 912 + g - 16 * t) * 4;
            uint32_t b0[8], b1[8];
#pragma unroll
            for (int s = 0; s < 8; s++) { b0[s] = lds32(KE + 32 * s); b1[s] = lds32(KE + 32 * s + 16); }
#pragma unroll
            for (int dl = 8; dl < 16; dl++) {
                const uint32_t vp = VE + 512 * dl;
                const uint32_t x0 = lds32(vp), x1 = lds32(vp + 32), x2 = lds32(vp - 256), x3 = lds32(vp - 224);
#pragma unroll
                for (int s = 0; s < 8; s++) if (dl + s < 16) mma_bf(acc[dl + s], x0, x1, x2, x3, b0[s], b1[s]);
            }
        }
        if (warp == 4) TSTAMP(13);
        {
            const uint32_t KD = kt + (KT_C + 2 * g + t) * 4, VD = vt + (VC_OFF - 400 + g - 8 * t) * 4;
            uint32_t b0[10], b1[10];
#pragma unroll
            for (int s = 0; s < 10; s++) { b0[s] = lds32(KD + 32 * s); b1[s] = lds32(KD + 32 * s + 16); }
#pragma unroll
            for (int dl = 6; dl <= 30; dl++) {
                const uint32_t vp = VD + 256 * dl;
                const uint32_t x0 = lds32(vp), x1 = lds32(vp + 32), x2 = lds32(vp - 128), x3 = lds32(vp - 96);
#pragma unroll
                for (int s = dl & 1; s < 10; s += 2) if ((dl + s) / 2 < 16) mma_bf(acc[(dl + s) / 2], x0, x1, x2, x3, b0[s], b1[s]);
                if ((dl & 3) == 2) ship((dl - 2) / 4);
            }
        }
        if ((warp & 3) == 0) TSTAMP(14 + (warp >> 2));
    }
}

constexpr int SF_WD = 147456;
constexpr int SF_H = 81920;
constexpr int SF_RED = 131072;
constexpr int SF_XS = 221184;
constexpr int SF_MISC = SF_XS + 8 * 1168;
constexpr int SF_KG = SF_MISC - 10 * KG_STAGE;
constexpr int SF_WR = SF_KG - 2304;
constexpr int FB_X = 64, FB_RDONE = 72, FB_FREE = 80, FB_KDONE = 88, FB_W = 112, FB_D = FB_W + 72, FB_H = FB_D + 96, FS_PART = 512, FS_TOK = 896;
enum { BAR_F = 6, BAR_R = 7, BAR_GU = 8, BAR_RED = 9 };
static_assert(SF_KG % 128 == 0 && SF_KG >= 7 * 24576 && SF_WR - 4 * 9216 >= 5 * 24576 && SF_WR - 6 * 9216 >= 5 * 16384, "layout");

__device__ __forceinline__ void ffn_front(const Params& p, const CUtensorMap* maps, uint32_t sb, int warp, int lane, int f, unsigned epoch) {
    const unsigned t0 = clock32();
    const int g = lane >> 2, t = lane & 3, mi = lane >> 3, r8 = lane & 7;
    const bool isx = f < NX;
    const int nrw = f < 8 ? 6 : 4, r0 = f < 8 ? 48 * f : 128 + 32 * f;
    const int rw = warp < 12 ? 13 - warp : warp ^ (warp < 14 ? 10 : 15);
    const uint32_t bar_row = sb + SF_MISC  , bar_x = bar_row + FB_X, bar_rdone = bar_row + FB_RDONE;
    const uint32_t s_part = bar_row + FS_PART  , s_tok = bar_row + FS_TOK  ;
    const uint32_t rows = sb + SF_WR - 9216 * (rw + 1);
    if (lane == 0) {
        mbar_init(bar_row + 8 * rw, 1); mbar_fence();
        if (rw < nrw) { mbar_expect(bar_row + 8 * rw, 9216); until(t0, RDELAY); bulk_g2s(rows, p.u + (size_t)(r0 + 8 * rw) * DM, 9216, bar_row + 8 * rw); }
        else if (rw >= 6) { mbar_expect(bar_row + 8 * rw, 1152); bulk_g2s(sb + SF_WR + (rw & 1) * 1152, (rw & 1) ? p.gatew : p.wr, 1152, bar_row + 8 * rw); }
        if (warp >= 10) {
#pragma unroll 1
            for (int i = warp - 10; i < 39; i += 6) mbar_init(bar_x + 8 * i, i == 1 ? nrw : i == 2 ? 4 : 1);
        }
        mbar_fence();
    }
    const int ks0 = isx ? 4 * f : 6 * f - 72, nt = isx ? 4 : 6;
    if (warp == 13) {
        stg128(p.s->keys + (lane >> 1) * 128 + 2 * f + (lane & 1), 0, 0, 0, 0);
        if (lane < 8 && isx && !(f & 1)) st_rlx32(&p.s->sel[32 * f + lane], 0);
    }
    __syncwarp();
    bar_sync(BAR_F, f < 12 ? 256 : 192);
    bar_arrive(0, NTHR);
    if (warp == 15) TSTAMP(1);

    if (warp == 12) {
        if (lane == 0) {
            const CUtensorMap* m = maps + (isx ? 1 : 3);
            prefetch_map(m); prefetch_map(m + 1);
#pragma unroll 1
            for (int n = 0; n < 9; n++) {
                until(t0, WDELAY + n * WGAP + ks0 * WSTAG / 288);
                if (n == 5) mbar_wait(bar_rdone);
                if (n == 7) mbar_wait(bar_row + FB_KDONE);
                const uint32_t b = bar_row + FB_W + 8 * n;
                mbar_expect(b, nt * 4096);
                tma3d(sb + n * nt * 4096, m, 0, 64 * n, ks0 >> 1, b);
                if (WSPLIT) until(t0, WDELAY + n * WGAP + ks0 * WSTAG / 288 + WGAP / 2);
                tma3d(sb + n * nt * 4096 + nt * 2048, m + 1, 0, 64 * n, ks0 >> 1, b);
            }
            TSTAMP(12);
            if (isx) {
                prefetch_map(maps + 5);
#pragma unroll 1
                for (int n = 0; n < 12; n++) {
                    until(t0, DDELAY + n * DGAP + f * DSTAG / 36);
                    if (n == 6) mbar_wait(bar_row + FB_FREE);
                    mbar_expect(bar_row + FB_D + 8 * n, 12288);
                    tma2d(sb + (n < 6 ? SF_WD : -6 * 12288) + n * 12288, maps + 5, 32 * (f >> 1), 2304 * (f & 1) + 192 * n, bar_row + FB_D + 8 * n);
                }
                TSTAMP(13);
            }
        }
    } else if (warp == 13) {
        const uint32_t tag = key_tag(epoch), par = (epoch & 1) ? 0u : 0x8000u;
        next_epoch(p, epoch);
        bar_sync(BAR_R, 32 * (nrw + 1));
        TSTAMP(3);
        uint32_t k[16];
        const uint2 va = lds64(fresh(s_part) + lane * 8), vb = lds64(fresh(s_part) + 256 + lane * 8);
        const bool two = nrw > 4 && lane < 16;
        {
            auto mk = [&](uint32_t r, int row) { const uint32_t rb = pack_bf16(0.f, __uint_as_float(r)); return (rb ^ (((int)rb >> 31) & 0x7fff0000u) ^ 0x80000000u) | tag | (uint32_t)(2047 - row); };
            uint32_t ka = mk(va.x, r0 + lane), kb = two ? mk(vb.x, r0 + 32 + lane) : 0;
#pragma unroll 1
            for (int h = 0; h < 2; h++)
#pragma unroll
                for (int r = 0; r < 4; r++) {
                    const uint32_t m = __reduce_max_sync(0xffffffffu, max(ka, kb));
                    if (ka == m) ka = 0;
                    if (kb == m) kb = 0;
                    if ((lane & 1) == h) k[r] = m;
                }
        }
        asm volatile("st.relaxed.gpu.global.v4.u32 [%0], {%1,%2,%3,%4};" :: "l"(p.s->keys + (lane >> 1) * 128 + 2 * f + (lane & 1)), "r"(k[0]), "r"(k[1]), "r"(k[2]), "r"(k[3]) : "memory");
        TSTAMP(4);
        {
            const uint32_t gb = pack_bf16(sigmoidf_(rbf(__uint_as_float(va.y))), sigmoidf_(rbf(__uint_as_float(vb.y)))) | par | (par << 16);
            asm volatile("st.relaxed.gpu.global.u16 [%0], %1;" :: "l"(p.s->gate + r0 + lane), "h"((unsigned short)gb) : "memory");
            if (two) asm volatile("st.relaxed.gpu.global.u16 [%0], %1;" :: "l"(p.s->gate + r0 + 32 + lane), "h"((unsigned short)(gb >> 16)) : "memory");
        }
        const uint4* src = p.s->keys + (f & 15) * 128 + lane;
        for (int it = 0;; it++) {
            uint32_t bad = 0;
#pragma unroll
            for (int i = 0; i < 4; i++) {
                const uint4 x = ld_rlx128(src + (i < 3 || lane < 24 ? 32 * i : 64));
                k[i] = x.x; k[4 + i] = x.y; k[8 + i] = x.z; k[12 + i] = x.w;
                bad |= x.x ^ tag;
            }
            const bool ok = __all_sync(0xffffffffu, (bad & 0xf800u) == 0);
            if (it < 8) TSTAMP(it < 4 ? 16 + it : 20 + it);
            if (ok) break;
            if (it > (1 << 20)) __trap();
        }
        TSTAMP(5);
        mbar_wait(bar_row + FB_KDONE);
        if (lane == 0) mbar_expect(bar_x, 8 * 1152);
        uint32_t key = 0;
#pragma unroll 1
        for (int r = 0; r < 8; r++) {
            const uint32_t m = __reduce_max_sync(0xffffffffu, max(max(k[0], k[1]), max(k[2], k[3])));
#pragma unroll
            for (int i = 0; i < 4; i++) {
                const bool pop = k[i] == m;
                k[i] = pop ? k[4 + i] : k[i]; k[4 + i] = pop ? k[8 + i] : k[4 + i]; k[8 + i] = pop ? k[12 + i] : k[8 + i]; k[12 + i] = pop ? 0 : k[12 + i];
            }
            if (lane == 0) bulk_g2s(sb + SF_XS + r * 1168, p.u + (size_t)key_row(m) * DM, 1152, bar_x);
            if (r8 == r) key = m;
        }
        const int row = key_row(key);
        TSTAMP(6);
        if (isx) {
            if (!(f & 1)) {
                stg128(p.out + (size_t)row * DM + 16 * f + 8 * mi, 0, 0, 0, 0);
                fence_gpu();
                __syncwarp();
                if (lane < 8) st_rlx32(&p.s->sel[32 * f + lane], key);
            }
            wait_sel(p, f >> 1, r8, tag);
            uint32_t gb;
            for (int it = 0;; it++) {
                asm volatile("ld.relaxed.gpu.global.u16 %0, [%1];" : "=r"(gb) : "l"(p.s->gate + row) : "memory");
                gb ^= par;
                if (!(gb & 0x8000u)) break;
                if (it > (1 << 20)) __trap();
            }
            const uint32_t rb = key ^ 0x80000000u, rv = (rb ^ (((int)rb >> 31) & 0x7fff0000u)) & 0xffff0000u;
            sts64(s_tok + r8 * 8, row, __float_as_uint(rbf(1.0f - bf_lo(gb)) * rbf(sigmoidf_(__uint_as_float(rv)))));
            __syncwarp();
            TSTAMP(7);
            bar_arrive(BAR_RED, 416);
        }
    } else {
        if (rw < nrw) {
            float c[2][4];
#pragma unroll
            for (int i = 0; i < 2; i++) { c[i][0] = c[i][1] = c[i][2] = c[i][3] = 0.f; }
            mbar_wait(bar_row + 48); mbar_wait(bar_row + 56);
            const uint32_t b = fresh(sb + SF_WR) + (g & 1) * 1152 + (g >> 2) * 64 + t * 16 + (g & 2) * 2;
            uint32_t w[18][2];
#pragma unroll
            for (int kb = 0; kb < 18; kb++) { const uint32_t o = ((kb & 1) ? b ^ 64 : b) + 128 * (kb >> 1); w[kb][0] = lds32(o); w[kb][1] = lds32(o + 8); }
            mbar_wait(bar_row + 8 * rw);
            if (warp == 15) TSTAMP(2);
            const uint32_t a = fresh(rows) + g * 1152 + (g & 1) * 64 + t * 16;
#pragma unroll
            for (int kb = 0; kb < 18; kb++) {
                const uint4 x = lds128(((kb & 1) ? a ^ 64 : a) + 128 * (kb >> 1));
                mma_bf(c[kb & 1], x.x, x.y, x.z, x.w, w[kb][0], w[kb][1]);
            }
            const float sr = c[0][0] + c[1][0] + __shfl_down_sync(0xffffffffu, c[0][2] + c[1][2], 1);
            const float sg = c[0][1] + c[1][1] + __shfl_down_sync(0xffffffffu, c[0][3] + c[1][3], 1);
            if (t == 2 * (g & 1)) sts64(s_part + (8 * rw + g) * 8, __float_as_uint(sr), __float_as_uint(sg));
            __syncwarp();
            bar_arrive(BAR_R, 32 * (nrw + 1));
            if (lane == 0) mbar_arrive(bar_rdone);
        }
    }
}

__device__ __forceinline__ void ffn_work(const Params& p, uint32_t sb, int warp, int lane, int f, unsigned epoch) {
    const int g = lane >> 2, t = lane & 3, mi = lane >> 3, r8 = lane & 7;
    const bool isx = f < NX;
    const int ks0 = isx ? 4 * f : 6 * f - 72, nt = isx ? 4 : 6;
    const uint32_t bar_x = sb + SF_MISC + FB_X, bar_free = sb + SF_MISC + FB_FREE, bar_w = sb + SF_MISC + FB_W, bar_d = sb + SF_MISC + FB_D, bar_h = sb + SF_MISC + FB_H, s_tok = sb + SF_MISC + FS_TOK;
    next_epoch(p, epoch);
    {
        if (warp < nt) {
            float ag[2][4], au[2][4];
#pragma unroll
            for (int i = 0; i < 2; i++) { ag[i][0] = ag[i][1] = ag[i][2] = ag[i][3] = 0.f; au[i][0] = au[i][1] = au[i][2] = au[i][3] = 0.f; }
            const uint32_t wb = sb + (warp >> 1) * 4096 + (r8 + 8 * (mi >> 1)) * 64 + (((2 * (warp & 1) + (mi & 1)) ^ (r8 >> 1)) << 4);
            const uint32_t xb = sb + SF_XS + r8 * 1168 + mi * 16;
            mbar_wait(bar_x);
            if (warp == 0) TSTAMP(8);
#pragma unroll 1
            for (int n = 0; n < 9; n++) {
                mbar_wait(bar_w + 8 * n);
                const uint32_t wk = fresh(wb) + n * nt * 4096, xk = fresh(xb) + 128 * n;
                uint32_t x[4];
#pragma unroll
                for (int s = 0; s < 4; s++) {
                    uint32_t a[4], b[4];
                    if (!(s & 1)) ldsm4(x, xk + 32 * s);
                    ldsm4t(a, wk + 1024 * s); ldsm4t(b, wk + 1024 * s + nt * 2048);
                    mma_bf(ag[s & 1], a[0], a[1], a[2], a[3], x[2 * (s & 1)], x[2 * (s & 1) + 1]);
                    mma_bf(au[s & 1], b[0], b[1], b[2], b[3], x[2 * (s & 1)], x[2 * (s & 1) + 1]);
                }
                asm volatile("" :: "f"(ag[0][0]), "f"(ag[1][0]), "f"(au[0][0]), "f"(au[1][0]) : "memory");
                if (n == 4 && lane == 0 && isx) mbar_arrive(bar_free);
            }
            if (warp == 0) TSTAMP(9);
            float h[4];
#pragma unroll
            for (int c = 0; c < 4; c++) {
                const float gv = rbf(ag[0][c] + ag[1][c]);
                h[c] = rbf(gv * sigmoidf_(gv)) * rbf(au[0][c] + au[1][c]);
            }
            uint32_t h0, h1;
            asm("movmatrix.sync.aligned.m8n8.trans.b16 %0, %1;" : "=r"(h0) : "r"(pack_bf16(h[0], h[1])));
            asm("movmatrix.sync.aligned.m8n8.trans.b16 %0, %1;" : "=r"(h1) : "r"(pack_bf16(h[2], h[3])));
            if (h0 == 0) h0 = 0x8000u;
            asm volatile("{ .reg .b64 v; mov.b64 v, {%1, %2}; st.relaxed.gpu.global.b64 [%0], v; }" :: "l"(p.s->h + ((epoch & 1) * 288 + ks0 + warp) * 32 + lane), "r"(h0), "r"(h1) : "memory");
        }
        if (isx) {
            bar_sync(BAR_GU, 384);
            if (warp == 0) TSTAMP(10);
            uint2 hb[12];
            const uint32_t hs = sb + SF_H + warp * 3072;
            const uint2* hsrc = p.s->h + ((__shfl_sync(0xffffffffu, epoch, 0) & 1) * 288 + 144 * (f & 1) + 12 * warp) * 32;
            for (int it = 0;; it++) {
                if (lane == 0) { mbar_expect(bar_h + 8 * warp, 3072); bulk_g2s(hs, hsrc, 3072, bar_h + 8 * warp); }
                mbar_wait(bar_h + 8 * warp, it & 1);
                const uint32_t hf = fresh(hs) + lane * 8;
                uint32_t mn = 0xffffffffu;
#pragma unroll
                for (int s = 0; s < 12; s++) { hb[s] = lds64(hf + 256 * s); mn = min(mn, hb[s].x); }
                if (__all_sync(0xffffffffu, mn != 0)) break;
                if (it > (1 << 16)) __trap();
            }
            if (warp == 0) TSTAMP(11);
            mbar_wait(bar_d + 8 * warp);
            if (warp == 11) TSTAMP(14);
            float ad[2][2][4];
#pragma unroll
            for (int i = 0; i < 4; i++) { ad[i >> 1][i & 1][0] = ad[i >> 1][i & 1][1] = ad[i >> 1][i & 1][2] = ad[i >> 1][i & 1][3] = 0.f; }
            const uint32_t wd = fresh(sb) + (warp < 6 ? SF_WD : -6 * 12288) + warp * 12288 + (r8 + 8 * (mi >> 1)) * 64 + (((mi & 1) ^ (r8 >> 1)) << 4);
#pragma unroll
            for (int s = 0; s < 12; s++) {
                uint32_t a[4], b[4];
                ldsm4t(a, wd + 1024 * s); ldsm4t(b, (wd ^ 32) + 1024 * s);
                mma_bf(ad[0][s & 1], a[0], a[1], a[2], a[3], hb[s].x, hb[s].y);
                mma_bf(ad[1][s & 1], b[0], b[1], b[2], b[3], hb[s].x, hb[s].y);
            }
            const uint32_t rd = sb + SF_RED + warp * 1152 + (72 * t + g) * 4;
#pragma unroll
            for (int i = 0; i < 8; i++) sts32(rd + (i >> 2) * 64 + (i & 1) * 144 + ((i >> 1) & 1) * 32, __float_as_uint(ad[i >> 2][0][i & 3] + ad[i >> 2][1][i & 3]));
            bar_sync(BAR_RED, 416);
            if (warp < 4) {
                const int tid = 32 * warp + lane;
                const uint32_t rs = fresh(sb + SF_RED) + (tid >> 4) * 144 + (tid & 15) * 8;
                const uint2 tk = lds64(fresh(s_tok) + (tid >> 4) * 8);
                float x = 0.f, y = 0.f;
#pragma unroll
                for (int w = 0; w < 12; w++) { const uint2 v = lds64(rs + w * 1152); x += __uint_as_float(v.x); y += __uint_as_float(v.y); }
                asm volatile("red.relaxed.gpu.global.add.noftz.bf16x2 [%0], %1;" :: "l"(p.out + (size_t)tk.x * DM + 32 * (f >> 1) + 2 * (tid & 15)),
                             "r"(pack_bf16(x * __uint_as_float(tk.y), y * __uint_as_float(tk.y))) : "memory");
            }
            if (warp == 0) TSTAMP(15);
        }
        if (warp == 0) TFLUSH();
    }
}

constexpr int SMEM_BYTES = 232448;
static_assert(SF_MISC + 1024 <= 232192, "layout");

struct Maps { CUtensorMap m[6]; };

__global__ void __cluster_dims__(2, 1, 1) __launch_bounds__(NTHR, 1)
fused_kernel(const Params p, const __grid_constant__ Maps maps) {
    extern __shared__ __align__(1024) uint8_t smem_raw[];
    uint32_t q[8];
    {
        const int b = blockIdx.x, x = threadIdx.x, rc = 4 * b + max(b - 84, 0) - 288 + (x >> 6);
        const int cv = (b - NCONV) >> 31, ca = 8 * b + ((x >> 5) & 3), cb = 2 * rc - (rc & 3) + 4;
        const uint32_t ch = (ca & cv) | (cb & ~cv), o = NST * ch + 2 * ((x & 31) + ((x >> (cv & 2)) & 32));
        const bool c = x < (b < 84 ? 256 : 320);
        q[6] = ldg16_if(c, p.logdt + ch);
        q[2] = ldg32_if(c, p.Bre + o); q[3] = ldg32_if(c, p.Bim + o); q[4] = ldg32_if(c, p.Cre + o); q[5] = ldg32_if(c, p.Cim + o); q[0] = ldg32_if(c, p.Are + o); q[1] = ldg32_if(c, p.Aim + o);
        q[7] = ldg16_if(c, p.Dskip + ch);
    }
    const unsigned epoch = ld_rlx32(&p.s->epoch[blockIdx.x * 16 + (threadIdx.x >> 5)]);
    const uint32_t sb = __shfl_sync(0xffffffffu, smem_u32(smem_raw), 0);
    const int warp = __shfl_sync(0xffffffffu, threadIdx.x >> 5, 0), bid = __shfl_sync(0xffffffffu, blockIdx.x, 0);
    const int lane = __shfl_sync(0xffffffffu, threadIdx.x & 31, threadIdx.x);
    const bool conv = bid < NCONV;
    const int f = bid - NCONV;
    uint32_t w[12];
    if (warp < (f < 12 ? 8 : 10)) {
        const int half = conv ? warp >> 2 : warp & 1, pr = conv ? warp & 3 : warp >> 1;
        const int rc = 4 * f + max(f - 12, 0) + pr;
        const uint32_t stage = sb + (conv ? SC_KG : SF_KG) + warp * KG_STAGE;
        uint4* const kp = p.s->kp + rc * 128 + lane;
        kgen(q, sb, half, stage, stage + (conv ? 4 : 1) * KG_STAGE, 1 + pr, lane, w, [&] {
            const uint32_t a = sb + SC_KT + warp * KT_BYTES + lane * 16;
#pragma unroll
            for (int i = 0; i < 6; i++) sts128z_if(conv && lane < 30, a + 480 * i);
            stg128z_if(!conv, kp + 64 * half); stg128z_if(!conv, kp + 64 * half + 32);
            stg128z_if(!conv && warp < (f < NX ? 4 : 6), (uint4*)(p.s->h + ((lane >> 4) * 288 + (f < NX ? 4 * f : 6 * f - 72) + warp) * 32) + (lane & 15));
            if (conv) asm volatile("barrier.cluster.arrive.relaxed.aligned;" ::: "memory");
        });
        if (!conv) {
            if (!half) {
#pragma unroll
                for (int i = 0; i < 4; i++) asm volatile("st.relaxed.gpu.global.v4.u32 [%0], {%1,%2,%3,%4};" :: "l"(kp + 32 * i), "r"(w[3 * i]), "r"(w[3 * i + 1]), "r"(w[3 * i + 2]), "r"(~epoch) : "memory");
            }
            if (warp == 0) TSTAMP(22);
            if (warp == 2) TSTAMP(23);
            bar_sync(0, NTHR);
            if (warp == 0 && lane == 0) mbar_arrive(sb + SF_MISC + FB_KDONE);
        }
    } else if (conv) {
        conv_aux(p, maps.m, sb, warp - 8, lane, bid, epoch);
        return;
    } else {
        ffn_front(p, maps.m, sb, warp, lane, f, epoch);
        if (warp >= 12) return;
    }
    if (conv) conv_main(p, sb, warp, lane, bid, epoch, w);
    else ffn_work(p, sb, warp, lane, f, epoch);
}

typedef CUresult (*EncodeFn)(CUtensorMap*, CUtensorMapDataType, cuuint32_t, void*, const cuuint64_t*, const cuuint64_t*, const cuuint32_t*, const cuuint32_t*,
                             CUtensorMapInterleave, CUtensorMapSwizzle, CUtensorMapL2promotion, CUtensorMapFloatOOBfill);

void make_map(EncodeFn fn, CUtensorMap* m, const void* base, int rank, const cuuint64_t* dims, const cuuint64_t* strides, const cuuint32_t* box, CUtensorMapSwizzle sw) {
    const cuuint32_t es[4] = {1, 1, 1, 1};
    fn(m, CU_TENSOR_MAP_DATA_TYPE_BFLOAT16, rank, (void*)base, dims, strides, box, es, CU_TENSOR_MAP_INTERLEAVE_NONE, sw,
       CU_TENSOR_MAP_L2_PROMOTION_NONE, CU_TENSOR_MAP_FLOAT_OOB_FILL_NONE);
}

}

extern "C" void kernel_launch(void* const* d_in, const int* in_sizes, int n_in, void* d_out, int out_size) {
    (void)in_sizes; (void)n_in; (void)out_size;
    static EncodeFn fn = nullptr;
    static void* scratch = nullptr;
    if (!fn) {
        void* ptr = nullptr; cudaDriverEntryPointQueryResult qr;
        cudaGetDriverEntryPoint("cuTensorMapEncodeTiled", &ptr, cudaEnableDefault, &qr);
        fn = (EncodeFn)ptr;
        cudaGetSymbolAddress(&scratch, g_scratch);
        cudaFuncSetAttribute(fused_kernel, cudaFuncAttributeMaxDynamicSharedMemorySize, SMEM_BYTES);
    }
    typedef const __nv_bfloat16* bp;
    Params p;
    p.u = (bp)d_in[0]; p.Are = (bp)d_in[1]; p.Aim = (bp)d_in[2]; p.Bre = (bp)d_in[3]; p.Bim = (bp)d_in[4]; p.Cre = (bp)d_in[5]; p.Cim = (bp)d_in[6];
    p.logdt = (bp)d_in[7]; p.Dskip = (bp)d_in[8]; p.wr = (bp)d_in[10]; p.gatew = (bp)d_in[14];
    p.out = (__nv_bfloat16*)d_out; p.s = (Scratch*)scratch; p.zero = 0;
    Maps maps;
    {
        const cuuint64_t dims[4] = {DM, 4, 16, 32}, strides[3] = {16 * DM * 2, DM * 2, 64 * DM * 2};
        const cuuint32_t box[4] = {16, 4, 16, 2};
        make_map(fn, &maps.m[0], d_in[0], 4, dims, strides, box, CU_TENSOR_MAP_SWIZZLE_32B);
    }
    for (int i = 0; i < 4; i++) {
        const cuuint64_t dims[3] = {32, DM, FF / 32}, strides[2] = {FF * 2, 64};
        const cuuint32_t box[3] = {32, 64, i < 2 ? 2u : 3u};
        make_map(fn, &maps.m[1 + i], d_in[11 + (i & 1)], 3, dims, strides, box, CU_TENSOR_MAP_SWIZZLE_64B);
    }
    {
        const cuuint64_t dims[2] = {DM, FF}, strides[1] = {DM * 2};
        const cuuint32_t box[2] = {32, 192};
        make_map(fn, &maps.m[5], d_in[13], 2, dims, strides, box, CU_TENSOR_MAP_SWIZZLE_64B);
    }
    fused_kernel<<<NCTA, NTHR, SMEM_BYTES>>>(p, maps);
}
```

```cpp
#include <cuda_runtime.h>
#include <cuda_bf16.h>
#include <cuda_fp16.h>
#include <cuda.h>
#include <stdint.h>
#include <type_traits>

#define UDELAY 300
#define RDELAY 900
#define WDELAY 2200
#define WGAP 290
#define NPRE 6
#define DGAP 220

namespace {

constexpr int DM = 576, NST = 128, FF = 4608, L_SEQ = 2048;
constexpr int NCONV = 72, NX = 36, NFFN = 60, NCTA = 132, NTHR = 512;

struct __align__(128) Scratch {
    unsigned epoch[NCTA * 16];
    uint4 keys[16 * 128];
    uint32_t sel[18 * 64];
    uint16_t gate[L_SEQ];
    uint2 h[2 * 288 * 32];
    uint4 kp[288 * 128];
};
__device__ Scratch g_scratch;
#define TFLUSH()
#define TSTAMP(i)

struct Params {
    const __nv_bfloat16 *Are, *Aim, *Bre, *Bim, *Cre, *Cim, *logdt, *Dskip, *u, *wr, *gatew;
    __nv_bfloat16* out;
    Scratch* s;
    uint32_t zero;
};

__device__ __forceinline__ uint32_t smem_u32(const void* p) { return (uint32_t)__cvta_generic_to_shared(p); }
__device__ __forceinline__ uint32_t pack_bf16(float lo, float hi) { uint32_t r; asm("cvt.rn.bf16x2.f32 %0, %1, %2;" : "=r"(r) : "f"(hi), "f"(lo)); return r; }
__device__ __forceinline__ uint32_t pack_f16(float lo, float hi) { uint32_t r; asm("cvt.rn.f16x2.f32 %0, %1, %2;" : "=r"(r) : "f"(hi), "f"(lo)); return r; }
__device__ __forceinline__ float bf_lo(uint32_t w) { return __uint_as_float(w << 16); }
__device__ __forceinline__ float bf_hi(uint32_t w) { return __uint_as_float(w & 0xffff0000u); }
__device__ __forceinline__ float rbf(float x) { return bf_lo(pack_bf16(x, 0.f)); }
__device__ __forceinline__ uint32_t badd2(uint32_t a, uint32_t b) { uint32_t r; asm("add.rn.bf16x2 %0, %1, %2;" : "=r"(r) : "r"(a), "r"(b)); return r; }
__device__ __forceinline__ uint32_t bsub2(uint32_t a, uint32_t b) { uint32_t r; asm("sub.rn.bf16x2 %0, %1, %2;" : "=r"(r) : "r"(a), "r"(b)); return r; }
__device__ __forceinline__ uint32_t gmix(uint32_t ng, float ny0, float ny1, uint32_t u) {
    uint32_t r; asm("{ .reg .b32 t; fma.rn.bf16x2 t, %1, %3, %3; fma.rn.bf16x2 %0, %1, %2, t; }" : "=r"(r) : "r"(ng), "r"(pack_bf16(ny0, ny1)), "r"(u)); return r;
}
__device__ __forceinline__ void mma_bf(float (&c)[4], uint32_t a0, uint32_t a1, uint32_t a2, uint32_t a3, uint32_t b0, uint32_t b1) {
    asm("mma.sync.aligned.m16n8k16.row.col.f32.bf16.bf16.f32 {%0,%1,%2,%3}, {%4,%5,%6,%7}, {%8,%9}, {%0,%1,%2,%3};"
        : "+f"(c[0]), "+f"(c[1]), "+f"(c[2]), "+f"(c[3]) : "r"(a0), "r"(a1), "r"(a2), "r"(a3), "r"(b0), "r"(b1));
}
__device__ __forceinline__ void mma_bf8(float (&c)[4], uint32_t a0, uint32_t a1, uint32_t b0) {
    asm("mma.sync.aligned.m16n8k8.row.col.f32.bf16.bf16.f32 {%0,%1,%2,%3}, {%4,%5}, {%6}, {%0,%1,%2,%3};"
        : "+f"(c[0]), "+f"(c[1]), "+f"(c[2]), "+f"(c[3]) : "r"(a0), "r"(a1), "r"(b0));
}
__device__ __forceinline__ void mma_h(float (&c)[4], uint32_t a0, uint32_t a1, uint32_t a2, uint32_t a3, uint32_t b0, uint32_t b1) {
    asm("mma.sync.aligned.m16n8k16.row.col.f32.f16.f16.f32 {%0,%1,%2,%3}, {%4,%5,%6,%7}, {%8,%9}, {%0,%1,%2,%3};"
        : "+f"(c[0]), "+f"(c[1]), "+f"(c[2]), "+f"(c[3]) : "r"(a0), "r"(a1), "r"(a2), "r"(a3), "r"(b0), "r"(b1));
}
__device__ __forceinline__ uint32_t fresh(uint32_t a) { asm volatile("" : "+r"(a) :: "memory"); return a; }
__device__ __forceinline__ uint32_t lds16(uint32_t a) { uint32_t v; asm("ld.shared.u16 %0, [%1];" : "=r"(v) : "r"(a)); return v; }
__device__ __forceinline__ uint32_t lds32(uint32_t a) { uint32_t v; asm("ld.shared.u32 %0, [%1];" : "=r"(v) : "r"(a)); return v; }
__device__ __forceinline__ uint2 lds64(uint32_t a) { uint2 v; asm("ld.shared.v2.u32 {%0,%1}, [%2];" : "=r"(v.x), "=r"(v.y) : "r"(a)); return v; }
__device__ __forceinline__ uint4 lds128(uint32_t a) { uint4 v; asm("ld.shared.v4.u32 {%0,%1,%2,%3}, [%4];" : "=r"(v.x), "=r"(v.y), "=r"(v.z), "=r"(v.w) : "r"(a)); return v; }
__device__ __forceinline__ uint4 lds128v(uint32_t a) { uint4 v; asm volatile("ld.shared.v4.u32 {%0,%1,%2,%3}, [%4];" : "=r"(v.x), "=r"(v.y), "=r"(v.z), "=r"(v.w) : "r"(a) : "memory"); return v; }
__device__ __forceinline__ void ldsm4(uint32_t (&r)[4], uint32_t a) {
    asm("ldmatrix.sync.aligned.m8n8.x4.shared.b16 {%0,%1,%2,%3}, [%4];" : "=r"(r[0]), "=r"(r[1]), "=r"(r[2]), "=r"(r[3]) : "r"(a));
}
__device__ __forceinline__ void ldsm4t(uint32_t (&r)[4], uint32_t a) {
    asm("ldmatrix.sync.aligned.m8n8.x4.trans.shared.b16 {%0,%1,%2,%3}, [%4];" : "=r"(r[0]), "=r"(r[1]), "=r"(r[2]), "=r"(r[3]) : "r"(a));
}
__device__ __forceinline__ void sts16(uint32_t a, uint32_t v) { asm volatile("st.shared.u16 [%0], %1;" :: "r"(a), "h"((unsigned short)v) : "memory"); }
__device__ __forceinline__ void sts32(uint32_t a, uint32_t v) { asm volatile("st.shared.u32 [%0], %1;" :: "r"(a), "r"(v) : "memory"); }
__device__ __forceinline__ void sts64(uint32_t a, uint32_t x, uint32_t y) { asm volatile("st.shared.v2.u32 [%0], {%1,%2};" :: "r"(a), "r"(x), "r"(y) : "memory"); }
__device__ __forceinline__ void sts128(uint32_t a, uint32_t x, uint32_t y, uint32_t z, uint32_t w) {
    asm volatile("st.shared.v4.u32 [%0], {%1,%2,%3,%4};" :: "r"(a), "r"(x), "r"(y), "r"(z), "r"(w) : "memory");
}
__device__ __forceinline__ void st_async128(uint32_t a, uint32_t x, uint32_t y, uint32_t z, uint32_t w, uint32_t bar) {
    asm volatile("st.async.weak.shared::cluster.mbarrier::complete_tx::bytes.v4.b32 [%0], {%1,%2,%3,%4}, [%5];" :: "r"(a), "r"(x), "r"(y), "r"(z), "r"(w), "r"(bar) : "memory");
}
__device__ __forceinline__ void mbar_init(uint32_t b, uint32_t cnt) { asm volatile("mbarrier.init.shared::cta.b64 [%0], %1;" :: "r"(b), "r"(cnt) : "memory"); }
__device__ __forceinline__ void mbar_fence() { asm volatile("fence.mbarrier_init.release.cluster;" ::: "memory"); }
__device__ __forceinline__ void mbar_expect(uint32_t b, uint32_t bytes) { asm volatile("mbarrier.arrive.expect_tx.shared::cta.b64 _, [%0], %1;" :: "r"(b), "r"(bytes) : "memory"); }
__device__ __forceinline__ void mbar_arrive(uint32_t b) { asm volatile("mbarrier.arrive.shared::cta.b64 _, [%0];" :: "r"(b) : "memory"); }
#define CHINT ", 20000"
#define HINT ""
__device__ __forceinline__ void mbar_wait(uint32_t b, uint32_t parity = 0) {
    asm volatile("{ .reg .pred p; .reg .u32 n; mov.u32 n, 0;\n"
                 "LW: mbarrier.try_wait.parity.shared::cta.b64 p, [%0], %1" HINT "; @p bra LD; add.u32 n, n, 1; setp.lt.u32 p, n, 65536; @p bra LW; trap;\n"
                 "LD: }" :: "r"(b), "r"(parity) : "memory");
}
__device__ __forceinline__ void mbar_wait_cluster(uint32_t b) {
    asm volatile("{ .reg .pred p; .reg .u32 n; mov.u32 n, 0;\n"
                 "LW: mbarrier.try_wait.parity.acquire.cluster.shared::cta.b64 p, [%0], 0" CHINT "; @p bra LD; add.u32 n, n, 1; setp.lt.u32 p, n, 65536; @p bra LW; trap;\n"
                 "LD: }" :: "r"(b) : "memory");
}
__device__ __forceinline__ void tma2d(uint32_t dst, const CUtensorMap* m, int c0, int c1, uint32_t bar) {
    asm volatile("cp.async.bulk.tensor.2d.shared::cluster.global.mbarrier::complete_tx::bytes [%0], [%1, {%3, %4}], [%2];"
                 :: "r"(dst), "l"(m), "r"(bar), "r"(c0), "r"(c1) : "memory");
}
__device__ __forceinline__ void tma3d(uint32_t dst, const CUtensorMap* m, int c0, int c1, int c2, uint32_t bar) {
    asm volatile("cp.async.bulk.tensor.3d.shared::cluster.global.mbarrier::complete_tx::bytes [%0], [%1, {%3, %4, %5}], [%2];"
                 :: "r"(dst), "l"(m), "r"(bar), "r"(c0), "r"(c1), "r"(c2) : "memory");
}
__device__ __forceinline__ void tma4d(uint32_t dst, const CUtensorMap* m, int c0, int c1, int c2, int c3, uint32_t bar) {
    asm volatile("cp.async.bulk.tensor.4d.shared::cluster.global.mbarrier::complete_tx::bytes [%0], [%1, {%3, %4, %5, %6}], [%2];"
                 :: "r"(dst), "l"(m), "r"(bar), "r"(c0), "r"(c1), "r"(c2), "r"(c3) : "memory");
}
__device__ __forceinline__ void bulk_g2s(uint32_t dst, const void* src, uint32_t bytes, uint32_t bar) {
    asm volatile("cp.async.bulk.shared::cluster.global.mbarrier::complete_tx::bytes [%0], [%1], %2, [%3];"
                 :: "r"(dst), "l"(src), "r"(bytes), "r"(bar) : "memory");
}
__device__ __forceinline__ uint32_t mapa(uint32_t a, uint32_t rank) { uint32_t r; asm("mapa.shared::cluster.u32 %0, %1, %2;" : "=r"(r) : "r"(a), "r"(rank)); return r; }
__device__ __forceinline__ void prefetch_map(const CUtensorMap* m) { asm volatile("prefetch.tensormap [%0];" :: "l"(m) : "memory"); }
__device__ __forceinline__ void bar_sync(int id, int n) { asm volatile("bar.sync %0, %1;" :: "r"(id), "r"(n) : "memory"); }
__device__ __forceinline__ void bar_arrive(int id, int n) { asm volatile("bar.arrive %0, %1;" :: "r"(id), "r"(n) : "memory"); }
__device__ __forceinline__ void fence_gpu() { asm volatile("fence.acq_rel.gpu;" ::: "memory"); }
__device__ __forceinline__ uint32_t ldg16_if(bool c, const void* p) { uint32_t v; asm volatile("{ .reg .pred p; setp.ne.u32 p, %2, 0; @p ld.global.nc.u16 %0, [%1]; }" : "=r"(v) : "l"(p), "r"((uint32_t)c)); return v; }
__device__ __forceinline__ uint32_t ldg32_if(bool c, const void* p) { uint32_t v; asm volatile("{ .reg .pred p; setp.ne.u32 p, %2, 0; @p ld.global.nc.u32 %0, [%1]; }" : "=r"(v) : "l"(p), "r"((uint32_t)c)); return v; }
__device__ __forceinline__ uint32_t ld_rlx32(const void* p) { uint32_t v; asm volatile("ld.relaxed.gpu.global.u32 %0, [%1];" : "=r"(v) : "l"(p) : "memory"); return v; }
__device__ __forceinline__ uint4 ld_rlx128(const void* p) {
    uint4 v; asm volatile("ld.relaxed.gpu.global.v4.u32 {%0,%1,%2,%3}, [%4];" : "=r"(v.x), "=r"(v.y), "=r"(v.z), "=r"(v.w) : "l"(p) : "memory"); return v;
}
__device__ __forceinline__ void st_rlx32(void* p, uint32_t v) { asm volatile("st.relaxed.gpu.global.u32 [%0], %1;" :: "l"(p), "r"(v) : "memory"); }
__device__ __forceinline__ void stg128(void* p, uint32_t x, uint32_t y, uint32_t z, uint32_t w) {
    asm volatile("st.global.v4.u32 [%0], {%1,%2,%3,%4};" :: "l"(p), "r"(x), "r"(y), "r"(z), "r"(w) : "memory");
}
__device__ __forceinline__ void next_epoch(const Params& p, unsigned e) { if ((threadIdx.x & 31) == 0) p.s->epoch[blockIdx.x * 16 + (threadIdx.x >> 5)] = e + 1; }
__device__ __forceinline__ void sts128z_if(bool c, uint32_t a) { asm volatile("{ .reg .pred p; setp.ne.u32 p, %1, 0; @p st.shared.v4.u32 [%0], {%2,%2,%2,%2}; }" :: "r"(a), "r"((uint32_t)c), "r"(0) : "memory"); }
__device__ __forceinline__ void stg128z_if(bool c, void* a) { asm volatile("{ .reg .pred p; setp.ne.u32 p, %1, 0; @p st.global.v4.u32 [%0], {%2,%2,%2,%2}; }" :: "l"(a), "r"((uint32_t)c), "r"(0) : "memory"); }
__device__ __forceinline__ unsigned clock32() { unsigned c; asm volatile("mov.u32 %0, %clock;" : "=r"(c) :: "memory"); return c; }
__device__ __forceinline__ void until(unsigned t0, int c) { while ((int)(clock32() - t0) < c) { } }
__device__ __forceinline__ float sigmoidf_(float x) { return __fdividef(1.0f, 1.0f + __expf(-x)); }
__device__ __forceinline__ uint32_t key_tag(unsigned epoch) { return ((epoch & 15u) | 16u) << 11; }
__device__ __forceinline__ int key_row(uint32_t key) { return 2047 - (int)(key & 2047u); }
__device__ __forceinline__ uint32_t wait_sel(const Params& p, int s32, int r8, uint32_t tag) {
    uint32_t k;
    for (int it = 0;; it++) {
        k = ld_rlx32(&p.s->sel[s32 * 64 + r8]);
        if (__all_sync(0xffffffffu, (k & 0xf800u) == tag)) break;
        if (it > (1 << 20)) __trap();
    }
    fence_gpu();
    return k;
}

struct cplx { float re, im; };
__device__ __forceinline__ cplx csq(cplx a) { cplx r; r.re = a.re * a.re - a.im * a.im; r.im = (a.re * a.im) * 2.f; return r; }
__device__ __forceinline__ cplx cexpk(float ar, float ai, float k) {
    float mag, s, c;
    asm("ex2.approx.ftz.f32 %0, %1;" : "=f"(mag) : "f"(ar * (k * 1.4426950408889634f)));
    const float r = ai * k;
    asm("sin.approx.ftz.f32 %0, %1;" : "=f"(s) : "f"(r));
    asm("cos.approx.ftz.f32 %0, %1;" : "=f"(c) : "f"(r));
    cplx o; o.re = mag * c; o.im = mag * s; return o;
}
struct h2c { uint32_t re, im; };
__device__ __forceinline__ h2c cmul_cd(h2c v, __half2 c, __half2 d) {
    const __half2 r = *(const __half2*)&v.re, i = *(const __half2*)&v.im;
    const __half2 x = __hfma2(__hneg2(i), d, __hmul2(r, c)), y = __hfma2(i, c, __hmul2(r, d));
    h2c o; o.re = *(const uint32_t*)&x; o.im = *(const uint32_t*)&y; return o;
}
__device__ __forceinline__ h2c cmul_s(h2c v, uint32_t s) { const __half2 h = *(const __half2*)&s; return cmul_cd(v, __low2half2(h), __high2half2(h)); }
__device__ __forceinline__ h2c cmul_sc(h2c v, uint32_t s) {
    const __half2 h = *(const __half2*)&s, c = __low2half2(h), d = __high2half2(h), r = *(const __half2*)&v.re, i = *(const __half2*)&v.im;
    const __half2 x = __hfma2(i, d, __hmul2(r, c)), y = __hfma2(__hneg2(r), d, __hmul2(i, c));
    h2c o; o.re = *(const uint32_t*)&x; o.im = *(const uint32_t*)&y; return o;
}
__device__ __forceinline__ h2c cmul_vc(h2c v, uint32_t s) {
    const __half2 h = *(const __half2*)&s, c = __low2half2(h), d = __high2half2(h), r = *(const __half2*)&v.re, i = *(const __half2*)&v.im;
    const __half2 x = __hfma2(i, d, __hmul2(r, c)), y = __hfma2(__hneg2(i), c, __hmul2(r, d));
    h2c o; o.re = *(const uint32_t*)&x; o.im = *(const uint32_t*)&y; return o;
}

constexpr int UT_HALF = 2240, UT_STRIDE = 4448;
constexpr int KT_T = 542, KT_C = 552, KT_D = 648, KT_BYTES = 720 * 4;
constexpr int VC_OFF = 80, VE_BASE = 1616;
constexpr int V_STRIDE = (1616 + 1024) * 4 + 80;
constexpr int KG_STAGE = 5248;
constexpr int Y_CS = 2080, Y_RS = 8 * Y_CS + 64;

constexpr int SC_RT = 0;
constexpr int SC_UT = 33408;
constexpr int SC_ST = SC_UT + 8 * UT_STRIDE;
constexpr int SC_KT = SC_ST + 8 * UT_STRIDE;
constexpr int SC_GT = SC_KT + 8 * KT_BYTES;
constexpr int SC_V = SC_GT + UT_STRIDE;
constexpr int SC_KG = SC_V + 4 * V_STRIDE;
constexpr int SC_KD = SC_V + 8 * V_STRIDE;
constexpr int SC_MISC = SC_KD + 8192;
static_assert(V_STRIDE % 128 == 16 && 8 * KG_STAGE <= 4 * V_STRIDE && 2 * Y_RS <= SC_UT && SC_UT % 128 == 0, "layout");
static_assert(SC_MISC % 16 == 0 && SC_MISC + 512 <= 232192, "layout");

__device__ __forceinline__ void window_task(uint32_t ut, uint32_t vt, int a, bool withE) {
    const uint32_t src = ut + (a + 6) * 16;
    float S[35];
    {
        uint32_t w[20];
#pragma unroll
        for (int i = 0; i < 5; i++) {
            const uint4 v = lds128(src + ((i & 1) ? 0 : UT_HALF) + ((i + 1) >> 1) * 16);
            w[4 * i] = v.x; w[4 * i + 1] = v.y; w[4 * i + 2] = v.z; w[4 * i + 3] = v.w;
        }
        float s = 0.f; S[2] = 0.f;
#pragma unroll
        for (int i = 3; i < 26; i++) { s += (i & 1) ? bf_hi(w[i >> 1]) : bf_lo(w[i >> 1]); S[i] = s; }
        const uint32_t d0 = vt + 64 * a + 16 * (a & 2), d1 = vt + 64 * a + 16 * (~a & 2);
#pragma unroll
        for (int i = 0; i < 8; i += 2)
            sts128((i & 4 ? d1 : d0) + (VC_OFF - 16) * 4 + 8 * (i & 2), pack_bf16(S[10 + i] - S[5 + i], S[5 + i] - S[2 + i]), pack_bf16(S[18 + i] - S[13 + i], S[13 + i] - S[10 + i]),
                   pack_bf16(S[11 + i] - S[6 + i], S[6 + i] - S[3 + i]), pack_bf16(S[19 + i] - S[14 + i], S[14 + i] - S[11 + i]));
        if (withE) {
#pragma unroll
            for (int i = 26; i < 35; i++) { s += (i & 1) ? bf_hi(w[i >> 1]) : bf_lo(w[i >> 1]); S[i] = s; }
#pragma unroll
            for (int i = 0; i < 8; i += 2)
                sts128((i & 4 ? d1 : d0) + VE_BASE * 4 + 8 * (i & 2), pack_bf16(S[19 + i] - S[12 + i], S[12 + i] - S[3 + i]), pack_bf16(S[27 + i] - S[20 + i], S[20 + i] - S[11 + i]),
                       pack_bf16(S[20 + i] - S[13 + i], S[13 + i] - S[4 + i]), pack_bf16(S[28 + i] - S[21 + i], S[21 + i] - S[12 + i]));
        }
    }
}

template <class F>
__device__ __forceinline__ void kgen(const uint32_t (&q)[8], uint32_t sb, int half, uint32_t stage, uint32_t pstage, int barid, int lane, uint32_t (&w)[12], F shadow) {
    const int t = lane & 3, mi = lane >> 3, r8 = lane & 7;
    {
        const uint32_t pAr = q[0], pAi = q[1], pBr = q[2], pBi = q[3], pCr = q[4], pCi = q[5], pDt = q[6], pD = q[7];
        const uint32_t wb = fresh(stage + lane * 16), za = fresh(stage + 5120 + ((lane >> 1) & 3) * 16 + mi * 4 + (lane & 1) * 2), zr = fresh(stage + 5120 + t * 16);
        const uint32_t oA = fresh(stage + (mi & 1) * 1024 + (mi >> 1) * 512 + r8 * 16), oB = fresh(stage + 2048 + mi * 512 + r8 * 16), oC = fresh(stage + 4096 + (mi & 1) * 512 + (mi >> 1) * 128 + r8 * 16);
        float acc[6][4];
#pragma unroll
        for (int a = 0; a < 6; a++) { acc[a][0] = acc[a][1] = acc[a][2] = acc[a][3] = 0.f; asm volatile("" : "+f"(acc[a][0]), "+f"(acc[a][1]), "+f"(acc[a][2]), "+f"(acc[a][3])); }
        shadow();
        sts32(zr, clock32());
        const float dt = rbf(__expf(bf_lo(pDt)));
        float ar = dt * bf_lo(pAr), ai = dt * bf_lo(pAi), ar1 = dt * bf_hi(pAr), ai1 = dt * bf_hi(pAi);
        float wr, wi, wr1, wi1;
        { const float br = dt * bf_lo(pBr), bi = dt * bf_lo(pBi), cr = bf_lo(pCr), ci = bf_lo(pCi); wr = cr * br - ci * bi; wi = cr * bi + ci * br; }
        { const float br = dt * bf_hi(pBr), bi = dt * bf_hi(pBi), cr = bf_hi(pCr), ci = bf_hi(pCi); wr1 = cr * br - ci * bi; wi1 = cr * bi + ci * br; }
        const uint32_t ex = max(__reduce_max_sync(0xffffffffu, __float_as_uint(fmaxf(fmaxf(fabsf(wr), fabsf(wi)), fmaxf(fabsf(wr1), fabsf(wi1))))) >> 23, 14u);
        const float scl = __uint_as_float((267u - ex) << 23);
        uint32_t W = pack_f16(wr * scl, wi * -scl);
        const uint32_t W1 = pack_f16(wr1 * scl, wi1 * -scl);
        if (threadIdx.x < 32) TSTAMP(20);

#pragma unroll 1
        for (int r = 0; r < 2; r++) {
            const cplx z1 = cexpk(ar, ai, 1.f), z64 = cexpk(ar, ai, 64.f);
            const cplx z2 = csq(z1), z4 = csq(z2), z8 = csq(z4), z16 = csq(z8), z32 = csq(z16);
            const cplx z128 = csq(z64), z256 = csq(z128), z512 = csq(z256), z1024 = csq(z512);
            auto put = [&](int grp, h2c a, h2c b, h2c c, h2c d) { sts128(wb + grp * 1024, a.re, b.re, c.re, d.re); sts128(wb + grp * 1024 + 512, a.im, b.im, c.im, d.im); };
            {
                const uint32_t s1 = pack_f16(z1.re, z1.im), s2 = pack_f16(z2.re, z2.im), s256 = pack_f16(z256.re, z256.im), s512 = pack_f16(z512.re, z512.im), s1024 = pack_f16(z1024.re, z1024.im);
                const h2c c04 = cmul_vc(h2c{pack_f16(1.f, z4.re), pack_f16(0.f, z4.im)}, W), c26 = cmul_sc(c04, s2);
                put(2, c04, c26, cmul_sc(c04, s1), cmul_sc(c26, s1));
                const h2c d04 = cmul_sc(c04, s256), e04 = cmul_sc(c04, s512), f04 = cmul_sc(d04, s512);
                put(3, d04, cmul_sc(c26, s256), e04, f04);
                const h2c ef = {__byte_perm(e04.re, f04.re, 0x5410), __byte_perm(e04.im, f04.im, 0x5410)};
                const h2c gh = cmul_sc(ef, s512);
                put(4, gh, cmul_sc(ef, s1024), cmul_sc(gh, s1024), ef);
            }
            {
                const uint32_t s32 = pack_f16(z32.re, z32.im), s64 = pack_f16(z64.re, z64.im), s128 = pack_f16(z128.re, z128.im);
                const h2c p0 = {pack_f16(1.f, z8.re), pack_f16(0.f, z8.im)}, p1 = cmul_s(p0, pack_f16(z16.re, z16.im)), p2 = cmul_s(p0, s32), p3 = cmul_s(p1, s32);
                put(0, p0, p1, p2, p3);
                put(1, cmul_s(p0, s64), cmul_s(p1, s64), cmul_s(p2, s64), cmul_s(p3, s64));
                sts16(za, s128); sts16(za + 64, s128 >> 16);
            }
            __syncwarp();
            {
                const uint32_t aA = fresh(oA), aB = fresh(oB), aC = fresh(oC), aZ = fresh(zr);
                const uint4 zc = lds128(aZ), zd = lds128(aZ + 64);
                const uint32_t zcs[4] = {zc.x, zc.y, zc.z, zc.w}, zds[4] = {zd.x, zd.y, zd.z, zd.w};
                uint32_t c[4];
#pragma unroll
                for (int k = 0; k < 4; k++) {
                    uint32_t a[4], b[4];
                    ldsm4t(a, aA + 128 * k); ldsm4t(b, aB + 128 * k);
                    if (!(k & 1)) ldsm4t(c, aC + 128 * k);
                    const h2c x = cmul_cd(h2c{a[0], a[2]}, *(const __half2*)&zcs[k], *(const __half2*)&zds[k]), y = cmul_cd(h2c{a[1], a[3]}, *(const __half2*)&zcs[k], *(const __half2*)&zds[k]);
                    mma_h(acc[0], a[0], a[1], a[2], a[3], b[0], b[1]);
                    mma_h(acc[1], a[0], a[1], a[2], a[3], b[2], b[3]);
                    mma_h(acc[2], a[0], a[1], a[2], a[3], c[2 * (k & 1)], c[2 * (k & 1) + 1]);
                    mma_h(acc[3], x.re, y.re, x.im, y.im, b[0], b[1]);
                    mma_h(acc[4], x.re, y.re, x.im, y.im, b[2], b[3]);
                    mma_h(acc[5], x.re, y.re, x.im, y.im, c[2 * (k & 1)], c[2 * (k & 1) + 1]);
                }
                asm volatile("" :: "f"(acc[0][0]), "f"(acc[1][0]), "f"(acc[2][0]), "f"(acc[3][0]), "f"(acc[4][0]), "f"(acc[5][0]) : "memory");
            }
            __syncwarp();
            ar = ar1; ai = ai1; W = W1;
        }
        if (threadIdx.x < 32) TSTAMP(21);
        const float i0 = __uint_as_float((ex + 243u) << 23);
        if (half) {
#pragma unroll
            for (int a = 0; a < 6; a++) sts128(wb + a * 512, __float_as_uint(acc[a][0] * i0), __float_as_uint(acc[a][1] * i0), __float_as_uint(acc[a][2] * i0), __float_as_uint(acc[a][3] * i0));
            bar_arrive(barid, 64);
        } else {
            bar_sync(barid, 64);
            const uint32_t src = fresh(pstage) + lane * 16;
#pragma unroll
            for (int a = 0; a < 6; a++) {
                const uint4 y = lds128(src + a * 512);
                float v0 = fmaf(acc[a][0], i0, __uint_as_float(y.x));
                if (a == 0 && lane == 0) v0 -= bf_lo(pD);
                w[2 * a] = pack_bf16(v0, fmaf(acc[a][1], i0, __uint_as_float(y.y)));
                w[2 * a + 1] = pack_bf16(fmaf(acc[a][2], i0, __uint_as_float(y.z)), fmaf(acc[a][3], i0, __uint_as_float(y.w)));
            }
        }
    }
}

__device__ __forceinline__ int swap01(int i) { return (i & ~3) | ((i & 1) << 1) | ((i >> 1) & 1); }
enum { BC_AUX = 0, BC_S = 5, BC_KG = 15 };

__device__ __forceinline__ void conv_aux(const Params& p, const CUtensorMap* mU, uint32_t sb, int aw, int lane, int bid, unsigned epoch) {
    const unsigned t0 = clock32();
    const int g = lane >> 2, t = lane & 3, mi = lane >> 3, r8 = lane & 7;
    const int rank = bid & 1, slab = bid >> 1;
    const uint32_t bar_y = sb + SC_MISC, bar_u = bar_y + 32, bar_v = bar_y + 40, bar_box = bar_y + 64 + 8 * aw, s_bm = bar_y + 128;
    if (lane == 0) {
        mbar_init(bar_box, 1); mbar_fence();
        mbar_expect(bar_box, 4096);
        if (UDELAY) until(t0, UDELAY);
        tma4d(sb + SC_RT + 4096 * aw, mU, 16 * slab, 0, 0, 16 * rank + 2 * aw, bar_box);
        mbar_init(bar_y + 8 * aw, aw < 4 ? 9 : aw == 5 ? 8 : 1); mbar_fence();
        if (aw < 5) mbar_expect(bar_y + 8 * aw, aw == 4 ? 16384 : 4096);
    }
    __syncwarp();
    asm volatile("barrier.cluster.arrive.relaxed.aligned;" ::: "memory");
    asm volatile("setmaxnreg.dec.sync.aligned.u32 88;");
    const uint32_t ut = sb + SC_UT + aw * UT_STRIDE;
    sts128(ut + (mi >> 1) * (SC_ST - SC_UT) + (mi & 1) * UT_HALF + r8 * 16, 0, 0, 0, 0);
    if (lane < 16) sts128(s_bm + lane * 16, 0, 0, 0, 0);
    {
        const uint32_t dst = sb + SC_UT + swap01(g) * UT_STRIDE + (8 + 64 * rank + 8 * aw + t) * 16;
        const uint32_t rdst = mapa(dst, rank ^ 1), rbar = mapa(bar_u, rank ^ 1);
        asm volatile("barrier.cluster.wait.acquire.aligned;" ::: "memory");
        mbar_wait(bar_box);
        if (aw == 0) TSTAMP(1);
        const uint32_t src = fresh(sb + SC_RT) + aw * 4096 + (8 * mi + 4 * (r8 & 1) + (r8 >> 1)) * 32 + ((rank ^ (r8 & 1)) << 4);
        uint32_t x[8][4];
#pragma unroll
        for (int i = 0; i < 4; i++) { ldsm4t(x[i], src + 1024 * i); ldsm4t(x[4 + i], (src ^ 16) + 1024 * i); }
        asm volatile("" :: "r"(x[0][0]), "r"(x[1][0]), "r"(x[2][0]), "r"(x[3][0]) : "memory");
#pragma unroll
        for (int i = 0; i < 4; i++) st_async128(rdst + (i & 1) * UT_HALF + 32 * (i & 2), x[4 + i][0], x[4 + i][1], x[4 + i][2], x[4 + i][3], rbar);
#pragma unroll
        for (int i = 0; i < 4; i++) sts128(dst + (i & 1) * UT_HALF + 32 * (i & 2), x[i][0], x[i][1], x[i][2], x[i][3]);
    }
    bar_sync(BC_AUX, 256);
    mbar_wait_cluster(bar_u);
    if (aw == 0) TSTAMP(2);
    {
        const uint32_t a = fresh(ut) + (mi & 1) * UT_HALF + (64 * (mi >> 1) + r8) * 16;
        uint4 v = lds128(a);
#pragma unroll
        for (int i = 1; i <= 8; i++) {
            const uint4 w = lds128(a + 128 * i);
            sts128(a + 128 * i + (SC_ST - SC_UT), badd2(v.x, w.x), badd2(v.y, w.y), badd2(v.z, w.z), badd2(v.w, w.w));
            v = w;
        }
    }
    bar_arrive(BC_S + aw, 64);
    if (aw == 0) TSTAMP(3);
#pragma unroll 1
    for (int k = aw; k < 26; k += 8) {
        if (k - aw == 8) {
            bar_sync(BC_KG, 384);
            if (lane < 16) sts128(sb + SC_V + aw * V_STRIDE + lane * 16, 0, 0, 0, 0);
        }
        const int c = (k < 13 ? 0 : 4) + t, a = 8 * (k < 13 ? k : k - 13) + g;
        if (a < 97) window_task(fresh(sb + SC_UT) + c * UT_STRIDE, sb + SC_V + c * V_STRIDE, a, a < 64);
        __syncwarp();
    }
    if (aw == 0) TSTAMP(9);
    {
        {
            const uint32_t par = (epoch & 1) ? 0x80008000u : 0u;
            uint4 v;
            for (int it = 0;; it++) {
                v = ld_rlx128(p.s->gate + 256 * aw + 8 * lane);
                v.x ^= par; v.y ^= par; v.z ^= par; v.w ^= par;
                if (__all_sync(0xffffffffu, (v.x & v.y & v.z & v.w & 0x80008000u) == 0x80008000u)) break;
                if (it > (1 << 20)) __trap();
            }
            sts128(sb + SC_GT + (lane & 1) * UT_HALF + (8 + 16 * aw + (lane >> 1)) * 16, v.x, v.y, v.z, v.w);
        }
        __syncwarp();
        if (lane == 0) mbar_arrive(bar_v);
        next_epoch(p, epoch);
        if (aw == 0) TSTAMP(4);
        if (aw == 7) {
            const int row = key_row(wait_sel(p, slab >> 1, r8, key_tag(epoch)));
            if (lane < 8) asm volatile("red.shared.or.b32 [%0], %1;" :: "r"(s_bm + (row >> 5) * 4), "r"(1u << (row & 31)) : "memory");
            TSTAMP(10);
        }
        bar_sync(BC_AUX, 256);
        const uint32_t src = sb + SC_RT + ((r8 >> 1) & 1) * Y_RS + (2 * mi + (r8 & 1)) * Y_CS + (2 * aw + (r8 >> 2)) * 16;
        const int L = 2 * aw + (t >> 1);
        const int row0 = 256 * rank + 128 * (g >> 2) + 32 * (L & 3) + 16 * (g & 1) + 8 * ((g >> 1) & 1) + (L >> 2);
        __nv_bfloat16* outp = p.out + (size_t)row0 * DM + 16 * slab + 8 * (t & 1);
#pragma unroll 1
        for (int s = 0; s < 4; s++) {
            const uint32_t bm = lds32(fresh(s_bm) + (16 * s + (row0 >> 5)) * 4) >> (row0 & 31);
            mbar_wait_cluster(bar_y + 8 * s);
            const uint32_t sf = fresh(src) + 512 * s;
            uint32_t y[2][4];
            ldsm4t(y[0], sf); ldsm4t(y[1], sf + 256);
#pragma unroll
            for (int k = 0; k < 2; k++)
                asm volatile("{ .reg .pred p; setp.ne.u32 p, %5, 0; @!p st.global.v4.u32 [%0], {%1,%2,%3,%4}; @p red.relaxed.gpu.global.add.noftz.v4.bf16x2 [%0], {%1,%2,%3,%4}; }"
                             :: "l"(outp + (size_t)(512 * s + 4 * k) * DM), "r"(y[k][0]), "r"(y[k][1]), "r"(y[k][2]), "r"(y[k][3]), "r"(bm & (1u << (4 * k))) : "memory");
            if (aw == 0) TSTAMP(16 + s);
        }
        if (aw == 0) TFLUSH();
    }
}

__device__ __forceinline__ void conv_main(const Params& p, uint32_t sb, int warp, int lane, int bid, unsigned epoch, uint32_t (&w)[12]) {
    asm volatile("setmaxnreg.inc.sync.aligned.u32 168;");
    const int g = lane >> 2, t = lane & 3, mi = lane >> 3, r8 = lane & 7;
    const int rank = bid & 1;
    const uint32_t bar_y = sb + SC_MISC, bar_v = bar_y + 40;
    next_epoch(p, epoch);
    if (warp < 4) {
        asm volatile("" :: "r"(w[0]), "r"(w[2]), "r"(w[4]), "r"(w[6]), "r"(w[8]), "r"(w[10]) : "memory");
        bar_arrive(BC_KG, 384);
    } else {
        const uint4* src = p.s->kp + (4 * bid + warp - 4) * 128 + lane;
        for (int it = 0;; it++) {
            uint32_t bad = 0;
#pragma unroll
            for (int i = 0; i < 4; i++) { const uint4 v = ld_rlx128(src + 32 * i); w[3 * i] = v.x; w[3 * i + 1] = v.y; w[3 * i + 2] = v.z; bad |= v.w ^ ~epoch; }
            const bool ok = __all_sync(0xffffffffu, bad == 0);
            if (it < 6 && warp == 4) TSTAMP(22 + it);
            if (ok) break;
            if (it > (1 << 20)) __trap();
        }
    }
    if ((warp & 3) == 0) TSTAMP(5 + (warp >> 2));
    {
        const uint32_t kt = sb + SC_KT + warp * KT_BYTES;
        const uint32_t kd = sb + SC_KD + warp * 1024 + 16;
#pragma unroll
        for (int nu = 0; nu < 3; nu++) {
            uint32_t a, a0, de, dr;
            if (nu == 0) { a = kd + (8 * g + 2 * (t & 1) + (t >> 1)) * 2; de = 8; dr = 128; a0 = a; }
            else if (nu == 1) { a = t < 2 ? kd + (256 + 4 * g + t) * 2 : kt + KT_C * 4 + (64 * t - 100 + 2 * g) * 2; de = t < 2 ? 4 : 2; dr = t < 2 ? 64 : 32; a0 = a; }
            else {
                a = t < 2 ? kt + KT_D * 4 + (13 + 64 * t + g) * 2 : kd + 800; de = 64; dr = 16; a0 = a;
                if ((lane & 29) == 0) a0 = kt + (t ? KT_D * 4 + 141 * 2 : KT_C * 4 + 156 * 2);
            }
#pragma unroll
            for (int i = 0; i < 4; i++) {
                const uint32_t v = w[6 * (i >> 1) + 2 * nu + (i & 1)];
                sts16(i ? a + i * dr : a0, v); sts16(a + i * dr + de, v >> 16);
            }
        }
        if (lane == 0) sts128(kt + (KT_T + 2) * 4, 0, w[4] & 0xffffu, __byte_perm(w[4], 0, 0x1010), w[4] << 16);
        __syncwarp();
        const uint32_t kf = fresh(kd), d = kt + (16 + 8 * lane) * 4;
        auto put = [&](uint32_t d, uint32_t pv, uint32_t w0, uint32_t w1, uint32_t w2, uint32_t w3) {
            sts128(d, __byte_perm(w0, pv, 0x5410), __byte_perm(w0, 0, 0x1032), __byte_perm(w1, w0, 0x7610), __byte_perm(w1, 0, 0x1032));
            sts128(d + 16, __byte_perm(w2, w1, 0x7610), __byte_perm(w2, 0, 0x1032), __byte_perm(w3, w2, 0x7610), __byte_perm(w3, 0, 0x1032));
        };
        const uint32_t pv = lds16(kf + (lane ? 16 * lane : 512) - 2);
        const uint4 x = lds128(kf + 16 * lane);
        const uint2 v = lds64(kf + 512 + 8 * lane);
        const uint32_t c4 = lds16(lane == 31 ? fresh(kt) + KT_C * 4 + 28 * 2 : kf + 520 + 8 * lane);
        put(d, lane ? pv : 0, x.x, x.y, x.z, x.w);
        uint32_t w3 = __byte_perm(v.y, c4, 0x5432);
        if (lane == 31) w3 = bsub2(w3, __byte_perm(c4, 0, 0x1010));
        put(d + 1024, lane ? v.x : pv, __byte_perm(v.x, 0, 0x1010), __byte_perm(v.x, v.y, 0x5432), __byte_perm(v.y, 0, 0x1010), w3);
    }
    asm volatile("barrier.cluster.wait.acquire.aligned;" ::: "memory");
    bar_sync(BC_S + swap01(warp), 64);
    if ((warp & 3) == 0) TSTAMP(7 + (warp >> 2));
    {
        const uint32_t ut = fresh(sb + SC_UT) + swap01(warp) * UT_STRIDE, kt = fresh(sb + SC_KT) + warp * KT_BYTES;
        uint32_t u1 = ut + (mi & 1) * UT_HALF + (8 + r8) * 16 + (mi >> 1) * 128;
        auto dup = [&](uint32_t v) { return v ^ p.zero; };
        uint32_t kp = kt + (16 + g - 2 * t) * 4;
        float acc[16][4];
        {
            const uint32_t c0 = lds32(kp + 2048), c1 = lds32(kp + 2080), c2 = lds32(kp + 2016), c3 = dup(c0);
            const uint32_t e0 = lds32(kp + (KT_T - 16) * 4), e1 = lds32(kp + (KT_T - 8) * 4), e2 = lds32(kp + (KT_T - 24) * 4), e3 = dup(e0);
            const uint32_t f0 = dup(e1), f1 = lds32(kp + KT_T * 4);
            const uint32_t uo = ut + UT_HALF + (7 + lane) * 16;
#pragma unroll
            for (int i = 0; i < 16; i++) { acc[i][0] = acc[i][1] = acc[i][2] = acc[i][3] = 0.f; }
#pragma unroll
            for (int mu = 0; mu < 8; mu += 4) {
                uint32_t b[4];
                ldsm4(b, uo + 128 * mu);
#pragma unroll
                for (int k = 0; k < 4; k++) mma_bf8(acc[mu + 8 + k], f0, f1, b[k]);
            }
#pragma unroll
            for (int mu = 0; mu < 12; mu += 2) {
                uint32_t b[4];
                ldsm4(b, u1 + 128 * mu);
                mma_bf(acc[mu + 4], c0, c1, c2, c3, b[0], b[1]);
                mma_bf(acc[mu + 5], c0, c1, c2, c3, b[2], b[3]);
                if (mu < 8) { mma_bf(acc[mu + 8], e0, e1, e2, e3, b[0], b[1]); mma_bf(acc[mu + 9], e0, e1, e2, e3, b[2], b[3]); }
            }
        }
        {
            float M[8][4];
#pragma unroll
            for (int i = 0; i < 8; i++) { M[i][0] = M[i][1] = M[i][2] = M[i][3] = 0.f; }
            uint32_t up = u1 + (mi >> 1) * 128, s[8][4], a3[4];
            auto frag = [&](uint32_t (&a)[4], uint32_t x) { a[0] = lds32(x); a[1] = lds32(x + 32); a[2] = lds32(x - 32); a[3] = dup(a[0]); };
            frag(a3, kp + 1536);
#pragma unroll
            for (int i = 0; i < 8; i++) ldsm4(s[i], u1 + (SC_ST - SC_UT) + 256 * i);
            __syncwarp();
#pragma unroll 1
            for (int j0 = 0; j0 < 8; j0++) {
                uint32_t a2[4], a1[4], a0[4], b[4][4];
                frag(a2, kp + 1024);
#pragma unroll
                for (int i = 0; i < 4; i++) ldsm4(b[i], up + 512 * i);
                frag(a1, kp + 512); frag(a0, kp);
                kp += 64; u1 -= 16; up -= 16;
#pragma unroll
                for (int i = 0; i < 7; i++) mma_bf(acc[2 * i + 2], a3[0], a3[1], a3[2], a3[3], s[i][0], s[i][1]);
#pragma unroll
                for (int e = 0; e < 4; e++) a3[e] = bsub2(a2[e], a3[e]);
#pragma unroll
                for (int i = 0; i < 7; i++) mma_bf(acc[2 * i + 3], a2[0], a2[1], a2[2], a2[3], s[i][2], s[i][3]);
#pragma unroll
                for (int i = 0; i < 7; i++) mma_bf(M[i + 1], a3[0], a3[1], a3[2], a3[3], b[i >> 1][2 * (i & 1)], b[i >> 1][2 * (i & 1) + 1]);
                frag(a3, kp + 1536);
#pragma unroll
                for (int i = 0; i < 8; i++) mma_bf(acc[2 * i], a1[0], a1[1], a1[2], a1[3], s[i][0], s[i][1]);
#pragma unroll
                for (int e = 0; e < 4; e++) a1[e] = bsub2(a0[e], a1[e]);
#pragma unroll
                for (int i = 0; i < 8; i++) { mma_bf(acc[2 * i + 1], a0[0], a0[1], a0[2], a0[3], s[i][2], s[i][3]); ldsm4(s[i], u1 + (SC_ST - SC_UT) + 256 * i); }
#pragma unroll
                for (int i = 0; i < 8; i++) mma_bf(M[i], a1[0], a1[1], a1[2], a1[3], b[i >> 1][2 * (i & 1)], b[i >> 1][2 * (i & 1) + 1]);
            }
            u1 = dup(u1) + 128;
#pragma unroll
            for (int i = 0; i < 8; i++)
#pragma unroll
                for (int c = 0; c < 4; c++) { acc[2 * i][c] += M[i][c]; acc[2 * i + 1][c] -= M[i][c]; }
        }
        if ((warp & 3) == 0) TSTAMP(11 + (warp >> 2));
        mbar_wait(bar_v);
        const uint32_t vt = fresh(sb + SC_V) + swap01(warp) * V_STRIDE;
        const uint32_t g1 = fresh(u1) - ut + sb + SC_GT;
        const uint32_t ydst = sb + SC_RT + rank * Y_RS + warp * Y_CS + lane * 16;
        const uint32_t ydr = mapa(ydst, rank ^ 1), ybr = mapa(bar_y, rank ^ 1);
        auto stairs = [&](auto R) {
        uint32_t ug[2][2][4];
        auto ld_ug = [&](int i) { ldsm4t(ug[i & 1][0], u1 + 256 * i); ldsm4t(ug[i & 1][1], g1 + 256 * i); };
        auto ship = [&](int i) {
            const uint32_t (&u)[4] = ug[i & 1][0], (&gg)[4] = ug[i & 1][1];
            const uint32_t y0 = gmix(gg[0], acc[2 * i][0], acc[2 * i][1], u[0]), y1 = gmix(gg[1], acc[2 * i][2], acc[2 * i][3], u[1]);
            const uint32_t y2 = gmix(gg[2], acc[2 * i + 1][0], acc[2 * i + 1][1], u[2]), y3 = gmix(gg[3], acc[2 * i + 1][2], acc[2 * i + 1][3], u[3]);
            if ((i & 1) != R.value) st_async128(ydr + 512 * (i >> 1), y0, y1, y2, y3, ybr + 8 * (i >> 1));
            else asm volatile("{ .reg .pred q; setp.eq.u32 q, %6, 0; st.shared.v4.u32 [%0], {%2,%3,%4,%5}; bar.warp.sync 0xffffffff; @q mbarrier.arrive.shared::cta.b64 _, [%1]; }"
                              :: "r"(ydst + 512 * (i >> 1)), "r"(bar_y + 8 * (i >> 1)), "r"(y0), "r"(y1), "r"(y2), "r"(y3), "r"(lane) : "memory");
        };
        const uint32_t VD = vt + (VC_OFF - 400 - 16 * t) * 4 + (8 * g ^ 16 * (-t & 2)), VD2 = vt + (VC_OFF - 415 - 16 * t) * 4 + (8 * g ^ 16 * (~t & 2));
        uint2 bd[10];
        uint32_t x[2][4][4];
        auto ld4 = [&](uint32_t (&v)[4], int dl) { const uint2 w = lds64(VD + 256 * dl); v[0] = w.x; v[1] = w.y; v[2] = lds32(VD2 + 256 * dl); v[3] = dup(w.x); };
        auto mm4 = [&](const uint32_t (&v)[4], int dl) {
#pragma unroll
            for (int s = dl & 1; s < 10; s += 2) if ((dl + s) / 2 < 16) mma_bf(acc[(dl + s) / 2], v[0], v[1], v[2], v[3], bd[s].x, bd[s].y);
        };
        const uint32_t KE = kt + (KT_D + g + t) * 4, VE = vt + (VE_BASE - 912 - 16 * t) * 4 + (8 * g ^ 16 * (~t & 2));
        uint32_t b0[8], b1[8];
        auto ld8 = [&](uint32_t (&v)[4], int dl) { const uint2 w = lds64(VE + 512 * dl), z = lds64(VE + 512 * dl - 256); v[0] = w.x; v[1] = w.y; v[2] = z.x; v[3] = z.y; };
        auto mm8 = [&](const uint32_t (&v)[4], int dl) {
#pragma unroll
            for (int s = 0; s < 8; s++) if (dl + s < 16) mma_bf(acc[dl + s], v[0], v[1], v[2], v[3], b0[s], b1[s]);
        };
        ld_ug(0); ld4(x[0][0], 6);
#pragma unroll
        for (int s = 0; s < 10; s++) bd[s] = lds64(kt + (KT_C + 2 * g + 2 * t + 8 * s) * 4);
        ld_ug(1);
#pragma unroll
        for (int s = 0; s < 8; s++) { b0[s] = lds32(KE + 32 * s); b1[s] = lds32(KE + 32 * s + 16); }
        ship(0);
#pragma unroll
        for (int j = 0; j < 4; j++) ld8(x[1][j], 8 + j);
        mm4(x[0][0], 6);
        ship(1);
#pragma unroll
        for (int j = 0; j < 4; j++) { mm8(x[1][j], 8 + j); ld4(x[0][j], 7 + j); }
        ld_ug(2);
#pragma unroll
        for (int j = 0; j < 4; j++) { uint32_t v[4], z[4]; ld8(v, 12 + j); ld4(z, 30 - j); mm8(v, 12 + j); mm4(x[0][j], 7 + j); mm4(z, 30 - j); }
        if (warp == 4) TSTAMP(13);
#pragma unroll
        for (int k = 2; k < 6; k++) {
#pragma unroll
            for (int j = 0; j < 4; j++) ld4(x[(k + 1) & 1][j], 4 * k + 3 + j);
            ld_ug(k + 1);
            ship(k);
#pragma unroll
            for (int j = 0; j < 4; j++) mm4(x[(k + 1) & 1][j], 4 * k + 3 + j);
        }
        ld_ug(7);
        ship(7 - R.value); ship(6 + R.value);
        };
        if (rank) stairs(std::integral_constant<int, 1>()); else stairs(std::integral_constant<int, 0>());
        if ((warp & 3) == 0) TSTAMP(14 + (warp >> 2));
    }
}

constexpr int SF_WD = 147456;
constexpr int SF_H = 81920;
constexpr int SF_RED = 131072;
constexpr int SF_XS = 221184;
constexpr int SF_MISC = SF_XS + 8 * 1168;
constexpr int SF_KG = SF_MISC - 10 * KG_STAGE;
constexpr int SF_WR = SF_KG - 2304;
constexpr int FB_X = 64, FB_RDONE = 72, FB_FREE = 80, FB_KDONE = 88, FB_KEYS = 96, FB_W = 112, FB_D = FB_W + 72, FB_H = FB_D + 96, FS_PART = 512, FS_TOK = 896;
enum { BAR_F = 6, BAR_R = 7, BAR_GU = 8, BAR_RED = 9 };
static_assert(NPRE <= 10 && SF_KG % 128 == 0 && SF_KG >= 7 * 24576 && SF_WR - 4 * 9216 >= 5 * 24576 && SF_WR - 6 * 9216 >= 5 * 16384, "layout");

__device__ __forceinline__ void ffn_front(const Params& p, const CUtensorMap* maps, uint32_t sb, int warp, int lane, int f, unsigned epoch) {
    const unsigned t0 = clock32();
    const int g = lane >> 2, t = lane & 3, mi = lane >> 3, r8 = lane & 7;
    const bool isx = f < NX;
    const int nrw = f < 8 ? 6 : 4, r0 = f < 8 ? 48 * f : 128 + 32 * f;
    const int rw = warp < 12 ? 13 - warp : warp ^ (warp < 14 ? 10 : 15);
    const uint32_t bar_row = sb + SF_MISC  , bar_x = bar_row + FB_X;
    const uint32_t s_part = bar_row + FS_PART  , s_tok = bar_row + FS_TOK  ;
    const uint32_t rows = sb + SF_WR - 9216 * (rw + 1);
    if (lane == 0) {
        mbar_init(bar_row + 8 * rw, 1); mbar_fence();
        if (rw < nrw) { mbar_expect(bar_row + 8 * rw, 9216); until(t0, RDELAY); bulk_g2s(rows, p.u + (size_t)(r0 + 8 * rw) * DM, 9216, bar_row + 8 * rw); }
        else if (rw >= 6) { mbar_expect(bar_row + 8 * rw, 1152); bulk_g2s(sb + SF_WR + (rw & 1) * 1152, (rw & 1) ? p.gatew : p.wr, 1152, bar_row + 8 * rw); }
        if (warp >= 10) {
#pragma unroll 1
            for (int i = warp - 10; i < 39; i += 6) mbar_init(bar_x + 8 * i, i == 1 ? nrw : i == 2 ? 4 : 1);
        }
        mbar_fence();
    }
    const int ks0 = isx ? 4 * f : 6 * f - 72, nt = isx ? 4 : 6;
    if (warp == 13) {
        stg128(p.s->keys + (lane >> 1) * 128 + 2 * f + (lane & 1), 0, 0, 0, 0);
        if (lane < 8 && isx && !(f & 1)) st_rlx32(&p.s->sel[32 * f + lane], 0);
    }
    __syncwarp();
    bar_sync(BAR_F, f < 12 ? 256 : 192);
    bar_arrive(0, NTHR);
    if (warp == 15) TSTAMP(1);

    if (warp == 12) {
        if (lane == 0) {
            const CUtensorMap* m = maps + (isx ? 1 : 3);
            prefetch_map(m); prefetch_map(m + 1);
            unsigned tb = t0 + WDELAY;
#pragma unroll 1
            for (int n = 0; n < 18; n++) {
                if (n == NPRE) { mbar_wait(bar_row + FB_KEYS); tb = clock32(); }
                until(tb, 0); tb += WGAP;
                const uint32_t b = bar_row + FB_W + 8 * (n >> 1);
                if (!(n & 1)) mbar_expect(b, nt * 4096);
                tma3d(sb + n * nt * 2048, m + (n & 1), 0, 64 * (n >> 1), ks0 >> 1, b);
            }
            TSTAMP(12);
            if (isx) {
                prefetch_map(maps + 5);
#pragma unroll 1
                for (int n = 0; n < 12; n++) {
                    until(tb, 0); tb += DGAP;
                    if (n == 6) mbar_wait(bar_row + FB_FREE);
                    mbar_expect(bar_row + FB_D + 8 * n, 12288);
                    tma2d(sb + (n < 6 ? SF_WD : -6 * 12288) + n * 12288, maps + 5, 32 * (f >> 1), 2304 * (f & 1) + 192 * n, bar_row + FB_D + 8 * n);
                }
                TSTAMP(13);
            }
        }
    } else if (warp == 13) {
        const uint32_t tag = key_tag(epoch), par = (epoch & 1) ? 0u : 0x8000u;
        next_epoch(p, epoch);
        bar_sync(BAR_R, 32 * (nrw + 1));
        TSTAMP(3);
        uint32_t k[16];
        const uint2 va = lds64(fresh(s_part) + lane * 8), vb = lds64(fresh(s_part) + 256 + lane * 8);
        const bool two = nrw > 4 && lane < 16;
        {
            auto mk = [&](uint32_t r, int row) { const uint32_t rb = pack_bf16(0.f, __uint_as_float(r)); return (rb ^ (((int)rb >> 31) & 0x7fff0000u) ^ 0x80000000u) | tag | (uint32_t)(2047 - row); };
            uint32_t ka = mk(va.x, r0 + lane), kb = two ? mk(vb.x, r0 + 32 + lane) : 0;
#pragma unroll 1
            for (int h = 0; h < 2; h++)
#pragma unroll
                for (int r = 0; r < 4; r++) {
                    const uint32_t m = __reduce_max_sync(0xffffffffu, max(ka, kb));
                    if (ka == m) ka = 0;
                    if (kb == m) kb = 0;
                    if ((lane & 1) == h) k[r] = m;
                }
        }
        asm volatile("st.relaxed.gpu.global.v4.u32 [%0], {%1,%2,%3,%4};" :: "l"(p.s->keys + (lane >> 1) * 128 + 2 * f + (lane & 1)), "r"(k[0]), "r"(k[1]), "r"(k[2]), "r"(k[3]) : "memory");
        TSTAMP(4);
        {
            const uint32_t gb = pack_bf16(sigmoidf_(rbf(__uint_as_float(va.y))), sigmoidf_(rbf(__uint_as_float(vb.y)))) | par | (par << 16);
            asm volatile("st.relaxed.gpu.global.u16 [%0], %1;" :: "l"(p.s->gate + r0 + lane), "h"((unsigned short)gb) : "memory");
            if (two) asm volatile("st.relaxed.gpu.global.u16 [%0], %1;" :: "l"(p.s->gate + r0 + 32 + lane), "h"((unsigned short)(gb >> 16)) : "memory");
        }
        const uint4* src = p.s->keys + (f & 15) * 128 + lane;
        for (int it = 0;; it++) {
            uint32_t bad = 0;
#pragma unroll
            for (int i = 0; i < 4; i++) {
                const uint4 x = ld_rlx128(src + (i < 3 || lane < 24 ? 32 * i : 64));
                k[i] = x.x; k[4 + i] = x.y; k[8 + i] = x.z; k[12 + i] = x.w;
                bad |= x.x ^ tag;
            }
            const bool ok = __all_sync(0xffffffffu, (bad & 0xf800u) == 0);
            if (it < 8) TSTAMP(it < 4 ? 16 + it : 20 + it);
            if (ok) break;
            if (it > (1 << 20)) __trap();
        }
        TSTAMP(5);
        mbar_wait(bar_row + FB_KDONE);
        if (lane == 0) { mbar_arrive(bar_row + FB_KEYS); mbar_expect(bar_x, 8 * 1152); }
        uint32_t key = 0;
#pragma unroll 1
        for (int r = 0; r < 8; r++) {
            const uint32_t m = __reduce_max_sync(0xffffffffu, max(max(k[0], k[1]), max(k[2], k[3])));
#pragma unroll
            for (int i = 0; i < 4; i++) {
                const bool pop = k[i] == m;
                k[i] = pop ? k[4 + i] : k[i]; k[4 + i] = pop ? k[8 + i] : k[4 + i]; k[8 + i] = pop ? k[12 + i] : k[8 + i]; k[12 + i] = pop ? 0 : k[12 + i];
            }
            if (lane == 0) bulk_g2s(sb + SF_XS + r * 1168, p.u + (size_t)key_row(m) * DM, 1152, bar_x);
            if (r8 == r) key = m;
        }
        const int row = key_row(key);
        TSTAMP(6);
        if (isx) {
            if (!(f & 1)) {
                stg128(p.out + (size_t)row * DM + 16 * f + 8 * mi, 0, 0, 0, 0);
                fence_gpu();
                __syncwarp();
                if (lane < 8) st_rlx32(&p.s->sel[32 * f + lane], key);
            }
            wait_sel(p, f >> 1, r8, tag);
            uint32_t gb;
            for (int it = 0;; it++) {
                asm volatile("ld.relaxed.gpu.global.u16 %0, [%1];" : "=r"(gb) : "l"(p.s->gate + row) : "memory");
                gb ^= par;
                if (!(gb & 0x8000u)) break;
                if (it > (1 << 20)) __trap();
            }
            const uint32_t rb = key ^ 0x80000000u, rv = (rb ^ (((int)rb >> 31) & 0x7fff0000u)) & 0xffff0000u;
            sts64(s_tok + r8 * 8, row, __float_as_uint(rbf(1.0f - bf_lo(gb)) * rbf(sigmoidf_(__uint_as_float(rv)))));
            __syncwarp();
            TSTAMP(7);
            bar_arrive(BAR_RED, 416);
        }
    } else {
        if (rw < nrw) {
            float c[2][4];
#pragma unroll
            for (int i = 0; i < 2; i++) { c[i][0] = c[i][1] = c[i][2] = c[i][3] = 0.f; }
            mbar_wait(bar_row + 48); mbar_wait(bar_row + 56);
            const uint32_t b = fresh(sb + SF_WR) + (g & 1) * 1152 + (g >> 2) * 64 + t * 16 + (g & 2) * 2;
            uint32_t w[18][2];
#pragma unroll
            for (int kb = 0; kb < 18; kb++) { const uint32_t o = ((kb & 1) ? b ^ 64 : b) + 128 * (kb >> 1); w[kb][0] = lds32(o); w[kb][1] = lds32(o + 8); }
            mbar_wait(bar_row + 8 * rw);
            if (warp == 15) TSTAMP(2);
            const uint32_t a = fresh(rows) + g * 1152 + (g & 1) * 64 + t * 16;
#pragma unroll
            for (int kb = 0; kb < 18; kb++) {
                const uint4 x = lds128(((kb & 1) ? a ^ 64 : a) + 128 * (kb >> 1));
                mma_bf(c[kb & 1], x.x, x.y, x.z, x.w, w[kb][0], w[kb][1]);
            }
            const float sr = c[0][0] + c[1][0] + __shfl_down_sync(0xffffffffu, c[0][2] + c[1][2], 1);
            const float sg = c[0][1] + c[1][1] + __shfl_down_sync(0xffffffffu, c[0][3] + c[1][3], 1);
            if (t == 2 * (g & 1)) sts64(s_part + (8 * rw + g) * 8, __float_as_uint(sr), __float_as_uint(sg));
            __syncwarp();
            bar_arrive(BAR_R, 32 * (nrw + 1));
        }
    }
}

__device__ __forceinline__ void ffn_work(const Params& p, uint32_t sb, int warp, int lane, int f, unsigned epoch) {
    const int g = lane >> 2, t = lane & 3, mi = lane >> 3, r8 = lane & 7;
    const bool isx = f < NX;
    const int ks0 = isx ? 4 * f : 6 * f - 72, nt = isx ? 4 : 6;
    const uint32_t bar_x = sb + SF_MISC + FB_X, bar_free = sb + SF_MISC + FB_FREE, bar_w = sb + SF_MISC + FB_W, bar_d = sb + SF_MISC + FB_D, bar_h = sb + SF_MISC + FB_H, s_tok = sb + SF_MISC + FS_TOK;
    next_epoch(p, epoch);
    {
        if (warp < nt) {
            float ag[2][4], au[2][4];
#pragma unroll
            for (int i = 0; i < 2; i++) { ag[i][0] = ag[i][1] = ag[i][2] = ag[i][3] = 0.f; au[i][0] = au[i][1] = au[i][2] = au[i][3] = 0.f; }
            const uint32_t wb = sb + (warp >> 1) * 4096 + (r8 + 8 * (mi >> 1)) * 64 + (((2 * (warp & 1) + (mi & 1)) ^ (r8 >> 1)) << 4);
            const uint32_t xb = sb + SF_XS + r8 * 1168 + mi * 16;
            mbar_wait(bar_x);
            if (warp == 0) TSTAMP(8);
#pragma unroll 1
            for (int n = 0; n < 9; n++) {
                mbar_wait(bar_w + 8 * n);
                const uint32_t wk = fresh(wb) + n * nt * 4096, xk = fresh(xb) + 128 * n;
                uint32_t x[4];
#pragma unroll
                for (int s = 0; s < 4; s++) {
                    uint32_t a[4], b[4];
                    if (!(s & 1)) ldsm4(x, xk + 32 * s);
                    ldsm4t(a, wk + 1024 * s); ldsm4t(b, wk + 1024 * s + nt * 2048);
                    mma_bf(ag[s & 1], a[0], a[1], a[2], a[3], x[2 * (s & 1)], x[2 * (s & 1) + 1]);
                    mma_bf(au[s & 1], b[0], b[1], b[2], b[3], x[2 * (s & 1)], x[2 * (s & 1) + 1]);
                }
                asm volatile("" :: "f"(ag[0][0]), "f"(ag[1][0]), "f"(au[0][0]), "f"(au[1][0]) : "memory");
                if (n == 4 && lane == 0 && isx) mbar_arrive(bar_free);
            }
            if (warp == 0) TSTAMP(9);
            float h[4];
#pragma unroll
            for (int c = 0; c < 4; c++) {
                const float gv = rbf(ag[0][c] + ag[1][c]);
                h[c] = rbf(gv * sigmoidf_(gv)) * rbf(au[0][c] + au[1][c]);
            }
            uint32_t h0, h1;
            asm("movmatrix.sync.aligned.m8n8.trans.b16 %0, %1;" : "=r"(h0) : "r"(pack_bf16(h[0], h[1])));
            asm("movmatrix.sync.aligned.m8n8.trans.b16 %0, %1;" : "=r"(h1) : "r"(pack_bf16(h[2], h[3])));
            if (h0 == 0) h0 = 0x8000u;
            asm volatile("{ .reg .b64 v; mov.b64 v, {%1, %2}; st.relaxed.gpu.global.b64 [%0], v; }" :: "l"(p.s->h + ((epoch & 1) * 288 + ks0 + warp) * 32 + lane), "r"(h0), "r"(h1) : "memory");
        }
        if (isx) {
            bar_sync(BAR_GU, 384);
            if (warp == 0) TSTAMP(10);
            uint2 hb[12];
            const uint32_t hs = sb + SF_H + warp * 3072;
            const uint2* hsrc = p.s->h + ((__shfl_sync(0xffffffffu, epoch, 0) & 1) * 288 + 144 * (f & 1) + 12 * warp) * 32;
            for (int it = 0;; it++) {
                if (lane == 0) { mbar_expect(bar_h + 8 * warp, 3072); bulk_g2s(hs, hsrc, 3072, bar_h + 8 * warp); }
                mbar_wait(bar_h + 8 * warp, it & 1);
                const uint32_t hf = fresh(hs) + lane * 8;
                uint32_t mn = 0xffffffffu;
#pragma unroll
                for (int s = 0; s < 12; s++) { hb[s] = lds64(hf + 256 * s); mn = min(mn, hb[s].x); }
                if (__all_sync(0xffffffffu, mn != 0)) break;
                if (it > (1 << 16)) __trap();
            }
            if (warp == 0) TSTAMP(11);
            mbar_wait(bar_d + 8 * warp);
            if (warp == 11) TSTAMP(14);
            float ad[2][2][4];
#pragma unroll
            for (int i = 0; i < 4; i++) { ad[i >> 1][i & 1][0] = ad[i >> 1][i & 1][1] = ad[i >> 1][i & 1][2] = ad[i >> 1][i & 1][3] = 0.f; }
            const uint32_t wd = fresh(sb) + (warp < 6 ? SF_WD : -6 * 12288) + warp * 12288 + (r8 + 8 * (mi >> 1)) * 64 + (((mi & 1) ^ (r8 >> 1)) << 4);
#pragma unroll
            for (int s = 0; s < 12; s++) {
                uint32_t a[4], b[4];
                ldsm4t(a, wd + 1024 * s); ldsm4t(b, (wd ^ 32) + 1024 * s);
                mma_bf(ad[0][s & 1], a[0], a[1], a[2], a[3], hb[s].x, hb[s].y);
                mma_bf(ad[1][s & 1], b[0], b[1], b[2], b[3], hb[s].x, hb[s].y);
            }
            const uint32_t rd = sb + SF_RED + warp * 1152 + (72 * t + g) * 4;
#pragma unroll
            for (int i = 0; i < 8; i++) sts32(rd + (i >> 2) * 64 + (i & 1) * 144 + ((i >> 1) & 1) * 32, __float_as_uint(ad[i >> 2][0][i & 3] + ad[i >> 2][1][i & 3]));
            bar_sync(BAR_RED, 416);
            if (warp < 4) {
                const int tid = 32 * warp + lane;
                const uint32_t rs = fresh(sb + SF_RED) + (tid >> 4) * 144 + (tid & 15) * 8;
                const uint2 tk = lds64(fresh(s_tok) + (tid >> 4) * 8);
                float x = 0.f, y = 0.f;
#pragma unroll
                for (int w = 0; w < 12; w++) { const uint2 v = lds64(rs + w * 1152); x += __uint_as_float(v.x); y += __uint_as_float(v.y); }
                asm volatile("red.relaxed.gpu.global.add.noftz.bf16x2 [%0], %1;" :: "l"(p.out + (size_t)tk.x * DM + 32 * (f >> 1) + 2 * (tid & 15)),
                             "r"(pack_bf16(x * __uint_as_float(tk.y), y * __uint_as_float(tk.y))) : "memory");
            }
            if (warp == 0) TSTAMP(15);
        }
        if (warp == 0) TFLUSH();
    }
}

constexpr int SMEM_BYTES = 232448;
static_assert(SF_MISC + 1024 <= 232192, "layout");

struct Maps { CUtensorMap m[6]; };

__global__ void __cluster_dims__(2, 1, 1) __launch_bounds__(NTHR, 1)
fused_kernel(const Params p, const __grid_constant__ Maps maps) {
    extern __shared__ __align__(1024) uint8_t smem_raw[];
    uint32_t q[8];
    {
        const int b = blockIdx.x, x = threadIdx.x, rc = 4 * b + max(b - 84, 0) - 288 + (x >> 6);
        const int cv = (b - NCONV) >> 31, ca = 8 * b + ((x >> 5) & 3), cb = 2 * rc - (rc & 3) + 4;
        const uint32_t ch = (ca & cv) | (cb & ~cv), o = NST * ch + 2 * ((x & 31) + ((x >> (cv & 2)) & 32));
        const bool c = x < (b < 84 ? 256 : 320);
        q[6] = ldg16_if(c, p.logdt + ch);
        q[2] = ldg32_if(c, p.Bre + o); q[3] = ldg32_if(c, p.Bim + o); q[4] = ldg32_if(c, p.Cre + o); q[5] = ldg32_if(c, p.Cim + o); q[0] = ldg32_if(c, p.Are + o); q[1] = ldg32_if(c, p.Aim + o);
        q[7] = ldg16_if(c, p.Dskip + ch);
    }
    const unsigned epoch = ld_rlx32(&p.s->epoch[blockIdx.x * 16 + (threadIdx.x >> 5)]);
    const uint32_t sb = __shfl_sync(0xffffffffu, smem_u32(smem_raw), 0);
    const int warp = __shfl_sync(0xffffffffu, threadIdx.x >> 5, 0), bid = __shfl_sync(0xffffffffu, blockIdx.x, 0);
    const int lane = __shfl_sync(0xffffffffu, threadIdx.x & 31, threadIdx.x);
    const bool conv = bid < NCONV;
    const int f = bid - NCONV;
    uint32_t w[12];
    if (warp < (f < 12 ? 8 : 10)) {
        const int half = conv ? warp >> 2 : warp & 1, pr = conv ? warp & 3 : warp >> 1;
        const int rc = 4 * f + max(f - 12, 0) + pr;
        const uint32_t stage = sb + (conv ? SC_KG : SF_KG) + warp * KG_STAGE;
        uint4* const kp = p.s->kp + rc * 128 + lane;
        kgen(q, sb, half, stage, stage + (conv ? 4 : 1) * KG_STAGE, 1 + pr, lane, w, [&] {
            const uint32_t a = sb + SC_KT + warp * KT_BYTES + lane * 16;
#pragma unroll
            for (int i = 0; i < 6; i++) sts128z_if(conv && lane < 30, a + 480 * i);
            stg128z_if(!conv, kp + 64 * half); stg128z_if(!conv, kp + 64 * half + 32);
            stg128z_if(!conv && warp < (f < NX ? 4 : 6), (uint4*)(p.s->h + ((lane >> 4) * 288 + (f < NX ? 4 * f : 6 * f - 72) + warp) * 32) + (lane & 15));
            if (conv) asm volatile("barrier.cluster.arrive.relaxed.aligned;" ::: "memory");
        });
        if (!conv) {
            if (!half) {
#pragma unroll
                for (int i = 0; i < 4; i++) asm volatile("st.relaxed.gpu.global.v4.u32 [%0], {%1,%2,%3,%4};" :: "l"(kp + 32 * i), "r"(w[3 * i]), "r"(w[3 * i + 1]), "r"(w[3 * i + 2]), "r"(~epoch) : "memory");
            }
            if (warp == 0) TSTAMP(22);
            if (warp == 2) TSTAMP(23);
            bar_sync(0, NTHR);
            if (warp == 0 && lane == 0) mbar_arrive(sb + SF_MISC + FB_KDONE);
        }
    } else if (conv) {
        conv_aux(p, maps.m, sb, warp - 8, lane, bid, epoch);
        return;
    } else {
        ffn_front(p, maps.m, sb, warp, lane, f, epoch);
        if (warp >= 12) return;
    }
    if (conv) conv_main(p, sb, warp, lane, bid, epoch, w);
    else ffn_work(p, sb, warp, lane, f, epoch);
}

typedef CUresult (*EncodeFn)(CUtensorMap*, CUtensorMapDataType, cuuint32_t, void*, const cuuint64_t*, const cuuint64_t*, const cuuint32_t*, const cuuint32_t*,
                             CUtensorMapInterleave, CUtensorMapSwizzle, CUtensorMapL2promotion, CUtensorMapFloatOOBfill);

void make_map(EncodeFn fn, CUtensorMap* m, const void* base, int rank, const cuuint64_t* dims, const cuuint64_t* strides, const cuuint32_t* box, CUtensorMapSwizzle sw) {
    const cuuint32_t es[4] = {1, 1, 1, 1};
    fn(m, CU_TENSOR_MAP_DATA_TYPE_BFLOAT16, rank, (void*)base, dims, strides, box, es, CU_TENSOR_MAP_INTERLEAVE_NONE, sw,
       CU_TENSOR_MAP_L2_PROMOTION_NONE, CU_TENSOR_MAP_FLOAT_OOB_FILL_NONE);
}

}

extern "C" void kernel_launch(void* const* d_in, const int* in_sizes, int n_in, void* d_out, int out_size) {
    (void)in_sizes; (void)n_in; (void)out_size;
    static EncodeFn fn = nullptr;
    static void* scratch = nullptr;
    if (!fn) {
        void* ptr = nullptr; cudaDriverEntryPointQueryResult qr;
        cudaGetDriverEntryPoint("cuTensorMapEncodeTiled", &ptr, cudaEnableDefault, &qr);
        fn = (EncodeFn)ptr;
        cudaGetSymbolAddress(&scratch, g_scratch);
        cudaFuncSetAttribute(fused_kernel, cudaFuncAttributeMaxDynamicSharedMemorySize, SMEM_BYTES);
    }
    typedef const __nv_bfloat16* bp;
    Params p;
    p.u = (bp)d_in[0]; p.Are = (bp)d_in[1]; p.Aim = (bp)d_in[2]; p.Bre = (bp)d_in[3]; p.Bim = (bp)d_in[4]; p.Cre = (bp)d_in[5]; p.Cim = (bp)d_in[6];
    p.logdt = (bp)d_in[7]; p.Dskip = (bp)d_in[8]; p.wr = (bp)d_in[10]; p.gatew = (bp)d_in[14];
    p.out = (__nv_bfloat16*)d_out; p.s = (Scratch*)scratch; p.zero = 0;
    Maps maps;
    {
        const cuuint64_t dims[4] = {DM, 4, 16, 32}, strides[3] = {16 * DM * 2, DM * 2, 64 * DM * 2};
        const cuuint32_t box[4] = {16, 4, 16, 2};
        make_map(fn, &maps.m[0], d_in[0], 4, dims, strides, box, CU_TENSOR_MAP_SWIZZLE_32B);
    }
    for (int i = 0; i < 4; i++) {
        const cuuint64_t dims[3] = {32, DM, FF / 32}, strides[2] = {FF * 2, 64};
        const cuuint32_t box[3] = {32, 64, i < 2 ? 2u : 3u};
        make_map(fn, &maps.m[1 + i], d_in[11 + (i & 1)], 3, dims, strides, box, CU_TENSOR_MAP_SWIZZLE_64B);
    }
    {
        const cuuint64_t dims[2] = {DM, FF}, strides[1] = {DM * 2};
        const cuuint32_t box[2] = {32, 192};
        make_map(fn, &maps.m[5], d_in[13], 2, dims, strides, box, CU_TENSOR_MAP_SWIZZLE_64B);
    }
    fused_kernel<<<NCTA, NTHR, SMEM_BYTES>>>(p, maps);
}
```

```cpp
#include <cuda_runtime.h>
#include <cuda_bf16.h>
#include <cuda_fp16.h>
#include <cuda.h>
#include <stdint.h>
#include <type_traits>

#define UDELAY 0
#define RDELAY 900
#define WDELAY 2200
#define WGAP 290
#define NPRE 6
#define DGAP 220

namespace {

constexpr int DM = 576, NST = 128, FF = 4608, L_SEQ = 2048;
constexpr int NCONV = 72, NX = 36, NFFN = 60, NCTA = 132, NTHR = 512;

struct __align__(128) Scratch {
    unsigned epoch[NCTA * 16];
    uint4 keys[16 * 128];
    uint32_t sel[18 * 64];
    uint16_t gate[L_SEQ];
    uint2 h[2 * 288 * 32];
    uint4 kp[288 * 128];
};
__device__ Scratch g_scratch;
#define TFLUSH()
#define TSTAMP(i)

struct Params {
    const __nv_bfloat16 *Are, *Aim, *Bre, *Bim, *Cre, *Cim, *logdt, *Dskip, *u, *wr, *gatew;
    __nv_bfloat16* out;
    Scratch* s;
    uint32_t zero;
};

__device__ __forceinline__ uint32_t smem_u32(const void* p) { return (uint32_t)__cvta_generic_to_shared(p); }
__device__ __forceinline__ uint32_t pack_bf16(float lo, float hi) { uint32_t r; asm("cvt.rn.bf16x2.f32 %0, %1, %2;" : "=r"(r) : "f"(hi), "f"(lo)); return r; }
__device__ __forceinline__ uint32_t pack_f16(float lo, float hi) { uint32_t r; asm("cvt.rn.f16x2.f32 %0, %1, %2;" : "=r"(r) : "f"(hi), "f"(lo)); return r; }
__device__ __forceinline__ float bf_lo(uint32_t w) { return __uint_as_float(w << 16); }
__device__ __forceinline__ float bf_hi(uint32_t w) { return __uint_as_float(w & 0xffff0000u); }
__device__ __forceinline__ float rbf(float x) { return bf_lo(pack_bf16(x, 0.f)); }
__device__ __forceinline__ uint32_t badd2(uint32_t a, uint32_t b) { uint32_t r; asm("add.rn.bf16x2 %0, %1, %2;" : "=r"(r) : "r"(a), "r"(b)); return r; }
__device__ __forceinline__ uint32_t bsub2(uint32_t a, uint32_t b) { uint32_t r; asm("sub.rn.bf16x2 %0, %1, %2;" : "=r"(r) : "r"(a), "r"(b)); return r; }
__device__ __forceinline__ uint32_t gmix(uint32_t ng, float ny0, float ny1, uint32_t u) {
    uint32_t r; asm("{ .reg .b32 t; fma.rn.bf16x2 t, %1, %3, %3; fma.rn.bf16x2 %0, %1, %2, t; }" : "=r"(r) : "r"(ng), "r"(pack_bf16(ny0, ny1)), "r"(u)); return r;
}
__device__ __forceinline__ void mma_bf(float (&c)[4], uint32_t a0, uint32_t a1, uint32_t a2, uint32_t a3, uint32_t b0, uint32_t b1) {
    asm("mma.sync.aligned.m16n8k16.row.col.f32.bf16.bf16.f32 {%0,%1,%2,%3}, {%4,%5,%6,%7}, {%8,%9}, {%0,%1,%2,%3};"
        : "+f"(c[0]), "+f"(c[1]), "+f"(c[2]), "+f"(c[3]) : "r"(a0), "r"(a1), "r"(a2), "r"(a3), "r"(b0), "r"(b1));
}
__device__ __forceinline__ void mma_bf8(float (&c)[4], uint32_t a0, uint32_t a1, uint32_t b0) {
    asm("mma.sync.aligned.m16n8k8.row.col.f32.bf16.bf16.f32 {%0,%1,%2,%3}, {%4,%5}, {%6}, {%0,%1,%2,%3};"
        : "+f"(c[0]), "+f"(c[1]), "+f"(c[2]), "+f"(c[3]) : "r"(a0), "r"(a1), "r"(b0));
}
__device__ __forceinline__ void mma_h(float (&c)[4], uint32_t a0, uint32_t a1, uint32_t a2, uint32_t a3, uint32_t b0, uint32_t b1) {
    asm("mma.sync.aligned.m16n8k16.row.col.f32.f16.f16.f32 {%0,%1,%2,%3}, {%4,%5,%6,%7}, {%8,%9}, {%0,%1,%2,%3};"
        : "+f"(c[0]), "+f"(c[1]), "+f"(c[2]), "+f"(c[3]) : "r"(a0), "r"(a1), "r"(a2), "r"(a3), "r"(b0), "r"(b1));
}
__device__ __forceinline__ uint32_t fresh(uint32_t a) { asm volatile("" : "+r"(a) :: "memory"); return a; }
__device__ __forceinline__ uint32_t lds16(uint32_t a) { uint32_t v; asm("ld.shared.u16 %0, [%1];" : "=r"(v) : "r"(a)); return v; }
__device__ __forceinline__ uint32_t lds32(uint32_t a) { uint32_t v; asm("ld.shared.u32 %0, [%1];" : "=r"(v) : "r"(a)); return v; }
__device__ __forceinline__ uint2 lds64(uint32_t a) { uint2 v; asm("ld.shared.v2.u32 {%0,%1}, [%2];" : "=r"(v.x), "=r"(v.y) : "r"(a)); return v; }
__device__ __forceinline__ uint4 lds128(uint32_t a) { uint4 v; asm("ld.shared.v4.u32 {%0,%1,%2,%3}, [%4];" : "=r"(v.x), "=r"(v.y), "=r"(v.z), "=r"(v.w) : "r"(a)); return v; }
__device__ __forceinline__ uint4 lds128v(uint32_t a) { uint4 v; asm volatile("ld.shared.v4.u32 {%0,%1,%2,%3}, [%4];" : "=r"(v.x), "=r"(v.y), "=r"(v.z), "=r"(v.w) : "r"(a) : "memory"); return v; }
__device__ __forceinline__ void ldsm4(uint32_t (&r)[4], uint32_t a) {
    asm("ldmatrix.sync.aligned.m8n8.x4.shared.b16 {%0,%1,%2,%3}, [%4];" : "=r"(r[0]), "=r"(r[1]), "=r"(r[2]), "=r"(r[3]) : "r"(a));
}
__device__ __forceinline__ void ldsm4t(uint32_t (&r)[4], uint32_t a) {
    asm("ldmatrix.sync.aligned.m8n8.x4.trans.shared.b16 {%0,%1,%2,%3}, [%4];" : "=r"(r[0]), "=r"(r[1]), "=r"(r[2]), "=r"(r[3]) : "r"(a));
}
__device__ __forceinline__ void sts16(uint32_t a, uint32_t v) { asm volatile("st.shared.u16 [%0], %1;" :: "r"(a), "h"((unsigned short)v) : "memory"); }
__device__ __forceinline__ void sts32(uint32_t a, uint32_t v) { asm volatile("st.shared.u32 [%0], %1;" :: "r"(a), "r"(v) : "memory"); }
__device__ __forceinline__ void sts64(uint32_t a, uint32_t x, uint32_t y) { asm volatile("st.shared.v2.u32 [%0], {%1,%2};" :: "r"(a), "r"(x), "r"(y) : "memory"); }
__device__ __forceinline__ void sts128(uint32_t a, uint32_t x, uint32_t y, uint32_t z, uint32_t w) {
    asm volatile("st.shared.v4.u32 [%0], {%1,%2,%3,%4};" :: "r"(a), "r"(x), "r"(y), "r"(z), "r"(w) : "memory");
}
__device__ __forceinline__ void st_async128(uint32_t a, uint32_t x, uint32_t y, uint32_t z, uint32_t w, uint32_t bar) {
    asm volatile("st.async.weak.shared::cluster.mbarrier::complete_tx::bytes.v4.b32 [%0], {%1,%2,%3,%4}, [%5];" :: "r"(a), "r"(x), "r"(y), "r"(z), "r"(w), "r"(bar) : "memory");
}
__device__ __forceinline__ void mbar_init(uint32_t b, uint32_t cnt) { asm volatile("mbarrier.init.shared::cta.b64 [%0], %1;" :: "r"(b), "r"(cnt) : "memory"); }
__device__ __forceinline__ void mbar_fence() { asm volatile("fence.mbarrier_init.release.cluster;" ::: "memory"); }
__device__ __forceinline__ void mbar_expect(uint32_t b, uint32_t bytes) { asm volatile("mbarrier.arrive.expect_tx.shared::cta.b64 _, [%0], %1;" :: "r"(b), "r"(bytes) : "memory"); }
__device__ __forceinline__ void mbar_arrive(uint32_t b) { asm volatile("mbarrier.arrive.shared::cta.b64 _, [%0];" :: "r"(b) : "memory"); }
#define CHINT ""
#define HINT ""
__device__ __forceinline__ void mbar_wait(uint32_t b, uint32_t parity = 0) {
    asm volatile("{ .reg .pred p; .reg .u32 n; mov.u32 n, 0;\n"
                 "LW: mbarrier.try_wait.parity.shared::cta.b64 p, [%0], %1" HINT "; @p bra LD; add.u32 n, n, 1; setp.lt.u32 p, n, 65536; @p bra LW; trap;\n"
                 "LD: }" :: "r"(b), "r"(parity) : "memory");
}
__device__ __forceinline__ void mbar_wait_cluster(uint32_t b) {
    asm volatile("{ .reg .pred p; .reg .u32 n; mov.u32 n, 0;\n"
                 "LW: mbarrier.try_wait.parity.acquire.cluster.shared::cta.b64 p, [%0], 0" CHINT "; @p bra LD; add.u32 n, n, 1; setp.lt.u32 p, n, 65536; @p bra LW; trap;\n"
                 "LD: }" :: "r"(b) : "memory");
}
__device__ __forceinline__ void tma2d(uint32_t dst, const CUtensorMap* m, int c0, int c1, uint32_t bar) {
    asm volatile("cp.async.bulk.tensor.2d.shared::cluster.global.mbarrier::complete_tx::bytes [%0], [%1, {%3, %4}], [%2];"
                 :: "r"(dst), "l"(m), "r"(bar), "r"(c0), "r"(c1) : "memory");
}
__device__ __forceinline__ void tma3d(uint32_t dst, const CUtensorMap* m, int c0, int c1, int c2, uint32_t bar) {
    asm volatile("cp.async.bulk.tensor.3d.shared::cluster.global.mbarrier::complete_tx::bytes [%0], [%1, {%3, %4, %5}], [%2];"
                 :: "r"(dst), "l"(m), "r"(bar), "r"(c0), "r"(c1), "r"(c2) : "memory");
}
__device__ __forceinline__ void tma4d(uint32_t dst, const CUtensorMap* m, int c0, int c1, int c2, int c3, uint32_t bar) {
    asm volatile("cp.async.bulk.tensor.4d.shared::cluster.global.mbarrier::complete_tx::bytes [%0], [%1, {%3, %4, %5, %6}], [%2];"
                 :: "r"(dst), "l"(m), "r"(bar), "r"(c0), "r"(c1), "r"(c2), "r"(c3) : "memory");
}
__device__ __forceinline__ void bulk_g2s(uint32_t dst, const void* src, uint32_t bytes, uint32_t bar) {
    asm volatile("cp.async.bulk.shared::cluster.global.mbarrier::complete_tx::bytes [%0], [%1], %2, [%3];"
                 :: "r"(dst), "l"(src), "r"(bytes), "r"(bar) : "memory");
}
__device__ __forceinline__ uint32_t mapa(uint32_t a, uint32_t rank) { uint32_t r; asm("mapa.shared::cluster.u32 %0, %1, %2;" : "=r"(r) : "r"(a), "r"(rank)); return r; }
__device__ __forceinline__ void prefetch_map(const CUtensorMap* m) { asm volatile("prefetch.tensormap [%0];" :: "l"(m) : "memory"); }
__device__ __forceinline__ void bar_sync(int id, int n) { asm volatile("bar.sync %0, %1;" :: "r"(id), "r"(n) : "memory"); }
__device__ __forceinline__ void bar_arrive(int id, int n) { asm volatile("bar.arrive %0, %1;" :: "r"(id), "r"(n) : "memory"); }
__device__ __forceinline__ void fence_gpu() { asm volatile("fence.acq_rel.gpu;" ::: "memory"); }
__device__ __forceinline__ uint32_t ldg16_if(bool c, const void* p) { uint32_t v; asm volatile("{ .reg .pred p; setp.ne.u32 p, %2, 0; @p ld.global.nc.u16 %0, [%1]; }" : "=r"(v) : "l"(p), "r"((uint32_t)c)); return v; }
__device__ __forceinline__ uint32_t ldg32_if(bool c, const void* p) { uint32_t v; asm volatile("{ .reg .pred p; setp.ne.u32 p, %2, 0; @p ld.global.nc.u32 %0, [%1]; }" : "=r"(v) : "l"(p), "r"((uint32_t)c)); return v; }
__device__ __forceinline__ uint32_t ld_rlx32(const void* p) { uint32_t v; asm volatile("ld.relaxed.gpu.global.u32 %0, [%1];" : "=r"(v) : "l"(p) : "memory"); return v; }
__device__ __forceinline__ uint4 ld_rlx128(const void* p) {
    uint4 v; asm volatile("ld.relaxed.gpu.global.v4.u32 {%0,%1,%2,%3}, [%4];" : "=r"(v.x), "=r"(v.y), "=r"(v.z), "=r"(v.w) : "l"(p) : "memory"); return v;
}
__device__ __forceinline__ void st_rlx32(void* p, uint32_t v) { asm volatile("st.relaxed.gpu.global.u32 [%0], %1;" :: "l"(p), "r"(v) : "memory"); }
__device__ __forceinline__ void stg128(void* p, uint32_t x, uint32_t y, uint32_t z, uint32_t w) {
    asm volatile("st.global.v4.u32 [%0], {%1,%2,%3,%4};" :: "l"(p), "r"(x), "r"(y), "r"(z), "r"(w) : "memory");
}
__device__ __forceinline__ void next_epoch(const Params& p, unsigned e) { if ((threadIdx.x & 31) == 0) p.s->epoch[blockIdx.x * 16 + (threadIdx.x >> 5)] = e + 1; }
__device__ __forceinline__ void sts128z_if(bool c, uint32_t a) { asm volatile("{ .reg .pred p; setp.ne.u32 p, %1, 0; @p st.shared.v4.u32 [%0], {%2,%2,%2,%2}; }" :: "r"(a), "r"((uint32_t)c), "r"(0) : "memory"); }
__device__ __forceinline__ void stg128z_if(bool c, void* a) { asm volatile("{ .reg .pred p; setp.ne.u32 p, %1, 0; @p st.global.v4.u32 [%0], {%2,%2,%2,%2}; }" :: "l"(a), "r"((uint32_t)c), "r"(0) : "memory"); }
__device__ __forceinline__ unsigned clock32() { unsigned c; asm volatile("mov.u32 %0, %clock;" : "=r"(c) :: "memory"); return c; }
__device__ __forceinline__ void until(unsigned t0, int c) { while ((int)(clock32() - t0) < c) { } }
__device__ __forceinline__ float sigmoidf_(float x) { return __fdividef(1.0f, 1.0f + __expf(-x)); }
__device__ __forceinline__ uint32_t key_tag(unsigned epoch) { return ((epoch & 15u) | 16u) << 11; }
__device__ __forceinline__ int key_row(uint32_t key) { return 2047 - (int)(key & 2047u); }
__device__ __forceinline__ uint32_t wait_sel(const Params& p, int s32, int r8, uint32_t tag) {
    uint32_t k;
    for (int it = 0;; it++) {
        k = ld_rlx32(&p.s->sel[s32 * 64 + r8]);
        if (__all_sync(0xffffffffu, (k & 0xf800u) == tag)) break;
        if (it > (1 << 20)) __trap();
    }
    fence_gpu();
    return k;
}

struct cplx { float re, im; };
__device__ __forceinline__ cplx csq(cplx a) { cplx r; r.re = a.re * a.re - a.im * a.im; r.im = (a.re * a.im) * 2.f; return r; }
__device__ __forceinline__ cplx cexpk(float ar, float ai, float k) {
    float mag, s, c;
    asm("ex2.approx.ftz.f32 %0, %1;" : "=f"(mag) : "f"(ar * (k * 1.4426950408889634f)));
    const float r = ai * k;
    asm("sin.approx.ftz.f32 %0, %1;" : "=f"(s) : "f"(r));
    asm("cos.approx.ftz.f32 %0, %1;" : "=f"(c) : "f"(r));
    cplx o; o.re = mag * c; o.im = mag * s; return o;
}
struct h2c { uint32_t re, im; };
__device__ __forceinline__ h2c cmul_cd(h2c v, __half2 c, __half2 d) {
    const __half2 r = *(const __half2*)&v.re, i = *(const __half2*)&v.im;
    const __half2 x = __hfma2(__hneg2(i), d, __hmul2(r, c)), y = __hfma2(i, c, __hmul2(r, d));
    h2c o; o.re = *(const uint32_t*)&x; o.im = *(const uint32_t*)&y; return o;
}
__device__ __forceinline__ h2c cmul_s(h2c v, uint32_t s) { const __half2 h = *(const __half2*)&s; return cmul_cd(v, __low2half2(h), __high2half2(h)); }
__device__ __forceinline__ h2c cmul_sc(h2c v, uint32_t s) {
    const __half2 h = *(const __half2*)&s, c = __low2half2(h), d = __high2half2(h), r = *(const __half2*)&v.re, i = *(const __half2*)&v.im;
    const __half2 x = __hfma2(i, d, __hmul2(r, c)), y = __hfma2(__hneg2(r), d, __hmul2(i, c));
    h2c o; o.re = *(const uint32_t*)&x; o.im = *(const uint32_t*)&y; return o;
}
__device__ __forceinline__ h2c cmul_vc(h2c v, uint32_t s) {
    const __half2 h = *(const __half2*)&s, c = __low2half2(h), d = __high2half2(h), r = *(const __half2*)&v.re, i = *(const __half2*)&v.im;
    const __half2 x = __hfma2(i, d, __hmul2(r, c)), y = __hfma2(__hneg2(i), c, __hmul2(r, d));
    h2c o; o.re = *(const uint32_t*)&x; o.im = *(const uint32_t*)&y; return o;
}

constexpr int UT_HALF = 2240, UT_STRIDE = 4448;
constexpr int KT_T = 542, KT_C = 552, KT_D = 648, KT_BYTES = 720 * 4;
constexpr int VC_OFF = 80, VE_BASE = 1616;
constexpr int V_STRIDE = (1616 + 1024) * 4 + 80;
constexpr int KG_STAGE = 5248;
constexpr int Y_CS = 2080, Y_RS = 8 * Y_CS + 64;

constexpr int SC_RT = 0;
constexpr int SC_UT = 33408;
constexpr int SC_ST = SC_UT + 8 * UT_STRIDE;
constexpr int SC_KT = SC_ST + 8 * UT_STRIDE;
constexpr int SC_GT = SC_KT + 8 * KT_BYTES;
constexpr int SC_V = SC_GT + UT_STRIDE;
constexpr int SC_KG = SC_V + 4 * V_STRIDE;
constexpr int SC_KD = SC_V + 8 * V_STRIDE;
constexpr int SC_MISC = SC_KD + 8192;
static_assert(V_STRIDE % 128 == 16 && 8 * KG_STAGE <= 4 * V_STRIDE && 2 * Y_RS <= SC_UT && SC_UT % 128 == 0 && SC_ST % 128 == 0, "layout");
static_assert(SC_MISC % 16 == 0 && SC_MISC + 512 <= 232192, "layout");

__device__ __forceinline__ void window_task(uint32_t ut, uint32_t vt, int a, bool withE) {
    const uint32_t src = ut + (a + 6) * 16;
    float S[35];
    {
        uint32_t w[20];
#pragma unroll
        for (int i = 0; i < 5; i++) {
            const uint4 v = lds128(src + ((i & 1) ? 0 : UT_HALF) + ((i + 1) >> 1) * 16);
            w[4 * i] = v.x; w[4 * i + 1] = v.y; w[4 * i + 2] = v.z; w[4 * i + 3] = v.w;
        }
        float s = 0.f; S[2] = 0.f;
#pragma unroll
        for (int i = 3; i < 26; i++) { s += (i & 1) ? bf_hi(w[i >> 1]) : bf_lo(w[i >> 1]); S[i] = s; }
        const uint32_t d0 = vt + 64 * a + 16 * (a & 2), d1 = vt + 64 * a + 16 * (~a & 2);
#pragma unroll
        for (int i = 0; i < 8; i += 2)
            sts128((i & 4 ? d1 : d0) + (VC_OFF - 16) * 4 + 8 * (i & 2), pack_bf16(S[10 + i] - S[5 + i], S[5 + i] - S[2 + i]), pack_bf16(S[18 + i] - S[13 + i], S[13 + i] - S[10 + i]),
                   pack_bf16(S[11 + i] - S[6 + i], S[6 + i] - S[3 + i]), pack_bf16(S[19 + i] - S[14 + i], S[14 + i] - S[11 + i]));
        if (withE) {
#pragma unroll
            for (int i = 26; i < 35; i++) { s += (i & 1) ? bf_hi(w[i >> 1]) : bf_lo(w[i >> 1]); S[i] = s; }
#pragma unroll
            for (int i = 0; i < 8; i += 2)
                sts128((i & 4 ? d1 : d0) + VE_BASE * 4 + 8 * (i & 2), pack_bf16(S[19 + i] - S[12 + i], S[12 + i] - S[3 + i]), pack_bf16(S[27 + i] - S[20 + i], S[20 + i] - S[11 + i]),
                       pack_bf16(S[20 + i] - S[13 + i], S[13 + i] - S[4 + i]), pack_bf16(S[28 + i] - S[21 + i], S[21 + i] - S[12 + i]));
        }
    }
}

template <class F>
__device__ __forceinline__ void kgen(const uint32_t (&q)[8], uint32_t sb, int half, uint32_t stage, uint32_t pstage, int barid, int lane, uint32_t (&w)[12], F shadow) {
    const int t = lane & 3, mi = lane >> 3, r8 = lane & 7;
    {
        const uint32_t pAr = q[0], pAi = q[1], pBr = q[2], pBi = q[3], pCr = q[4], pCi = q[5], pDt = q[6], pD = q[7];
        const uint32_t wb = fresh(stage + lane * 16), za = fresh(stage + 5120 + ((lane >> 1) & 3) * 16 + mi * 4 + (lane & 1) * 2), zr = fresh(stage + 5120 + t * 16);
        const uint32_t oA = fresh(stage + (mi & 1) * 1024 + (mi >> 1) * 512 + r8 * 16), oB = fresh(stage + 2048 + mi * 512 + r8 * 16), oC = fresh(stage + 4096 + (mi & 1) * 512 + (mi >> 1) * 128 + r8 * 16);
        float acc[6][4];
#pragma unroll
        for (int a = 0; a < 6; a++) { acc[a][0] = acc[a][1] = acc[a][2] = acc[a][3] = 0.f; asm volatile("" : "+f"(acc[a][0]), "+f"(acc[a][1]), "+f"(acc[a][2]), "+f"(acc[a][3])); }
        shadow();
        sts32(zr, clock32());
        const float dt = rbf(__expf(bf_lo(pDt)));
        float ar = dt * bf_lo(pAr), ai = dt * bf_lo(pAi), ar1 = dt * bf_hi(pAr), ai1 = dt * bf_hi(pAi);
        float wr, wi, wr1, wi1;
        { const float br = dt * bf_lo(pBr), bi = dt * bf_lo(pBi), cr = bf_lo(pCr), ci = bf_lo(pCi); wr = cr * br - ci * bi; wi = cr * bi + ci * br; }
        { const float br = dt * bf_hi(pBr), bi = dt * bf_hi(pBi), cr = bf_hi(pCr), ci = bf_hi(pCi); wr1 = cr * br - ci * bi; wi1 = cr * bi + ci * br; }
        const uint32_t ex = max(__reduce_max_sync(0xffffffffu, __float_as_uint(fmaxf(fmaxf(fabsf(wr), fabsf(wi)), fmaxf(fabsf(wr1), fabsf(wi1))))) >> 23, 14u);
        const float scl = __uint_as_float((267u - ex) << 23);
        uint32_t W = pack_f16(wr * scl, wi * -scl);
        const uint32_t W1 = pack_f16(wr1 * scl, wi1 * -scl);
        if (threadIdx.x < 32) TSTAMP(20);

#pragma unroll 1
        for (int r = 0; r < 2; r++) {
            const cplx z1 = cexpk(ar, ai, 1.f), z64 = cexpk(ar, ai, 64.f);
            const cplx z2 = csq(z1), z4 = csq(z2), z8 = csq(z4), z16 = csq(z8), z32 = csq(z16);
            const cplx z128 = csq(z64), z256 = csq(z128), z512 = csq(z256), z1024 = csq(z512);
            auto put = [&](int grp, h2c a, h2c b, h2c c, h2c d) { sts128(wb + grp * 1024, a.re, b.re, c.re, d.re); sts128(wb + grp * 1024 + 512, a.im, b.im, c.im, d.im); };
            {
                const uint32_t s1 = pack_f16(z1.re, z1.im), s2 = pack_f16(z2.re, z2.im), s256 = pack_f16(z256.re, z256.im), s512 = pack_f16(z512.re, z512.im), s1024 = pack_f16(z1024.re, z1024.im);
                const h2c c04 = cmul_vc(h2c{pack_f16(1.f, z4.re), pack_f16(0.f, z4.im)}, W), c26 = cmul_sc(c04, s2);
                put(2, c04, c26, cmul_sc(c04, s1), cmul_sc(c26, s1));
                const h2c d04 = cmul_sc(c04, s256), e04 = cmul_sc(c04, s512), f04 = cmul_sc(d04, s512);
                put(3, d04, cmul_sc(c26, s256), e04, f04);
                const h2c ef = {__byte_perm(e04.re, f04.re, 0x5410), __byte_perm(e04.im, f04.im, 0x5410)};
                const h2c gh = cmul_sc(ef, s512);
                put(4, gh, cmul_sc(ef, s1024), cmul_sc(gh, s1024), ef);
            }
            {
                const uint32_t s32 = pack_f16(z32.re, z32.im), s64 = pack_f16(z64.re, z64.im), s128 = pack_f16(z128.re, z128.im);
                const h2c p0 = {pack_f16(1.f, z8.re), pack_f16(0.f, z8.im)}, p1 = cmul_s(p0, pack_f16(z16.re, z16.im)), p2 = cmul_s(p0, s32), p3 = cmul_s(p1, s32);
                put(0, p0, p1, p2, p3);
                put(1, cmul_s(p0, s64), cmul_s(p1, s64), cmul_s(p2, s64), cmul_s(p3, s64));
                sts16(za, s128); sts16(za + 64, s128 >> 16);
            }
            __syncwarp();
            {
                const uint32_t aA = fresh(oA), aB = fresh(oB), aC = fresh(oC), aZ = fresh(zr);
                const uint4 zc = lds128(aZ), zd = lds128(aZ + 64);
                const uint32_t zcs[4] = {zc.x, zc.y, zc.z, zc.w}, zds[4] = {zd.x, zd.y, zd.z, zd.w};
                uint32_t c[4];
#pragma unroll
                for (int k = 0; k < 4; k++) {
                    uint32_t a[4], b[4];
                    ldsm4t(a, aA + 128 * k); ldsm4t(b, aB + 128 * k);
                    if (!(k & 1)) ldsm4t(c, aC + 128 * k);
                    const h2c x = cmul_cd(h2c{a[0], a[2]}, *(const __half2*)&zcs[k], *(const __half2*)&zds[k]), y = cmul_cd(h2c{a[1], a[3]}, *(const __half2*)&zcs[k], *(const __half2*)&zds[k]);
                    mma_h(acc[0], a[0], a[1], a[2], a[3], b[0], b[1]);
                    mma_h(acc[1], a[0], a[1], a[2], a[3], b[2], b[3]);
                    mma_h(acc[2], a[0], a[1], a[2], a[3], c[2 * (k & 1)], c[2 * (k & 1) + 1]);
                    mma_h(acc[3], x.re, y.re, x.im, y.im, b[0], b[1]);
                    mma_h(acc[4], x.re, y.re, x.im, y.im, b[2], b[3]);
                    mma_h(acc[5], x.re, y.re, x.im, y.im, c[2 * (k & 1)], c[2 * (k & 1) + 1]);
                }
                asm volatile("" :: "f"(acc[0][0]), "f"(acc[1][0]), "f"(acc[2][0]), "f"(acc[3][0]), "f"(acc[4][0]), "f"(acc[5][0]) : "memory");
            }
            __syncwarp();
            ar = ar1; ai = ai1; W = W1;
        }
        if (threadIdx.x < 32) TSTAMP(21);
        const float i0 = __uint_as_float((ex + 243u) << 23);
        if (half) {
#pragma unroll
            for (int a = 0; a < 6; a++) sts128(wb + a * 512, __float_as_uint(acc[a][0] * i0), __float_as_uint(acc[a][1] * i0), __float_as_uint(acc[a][2] * i0), __float_as_uint(acc[a][3] * i0));
            bar_arrive(barid, 64);
        } else {
            bar_sync(barid, 64);
            const uint32_t src = fresh(pstage) + lane * 16;
#pragma unroll
            for (int a = 0; a < 6; a++) {
                const uint4 y = lds128(src + a * 512);
                float v0 = fmaf(acc[a][0], i0, __uint_as_float(y.x));
                if (a == 0 && lane == 0) v0 -= bf_lo(pD);
                w[2 * a] = pack_bf16(v0, fmaf(acc[a][1], i0, __uint_as_float(y.y)));
                w[2 * a + 1] = pack_bf16(fmaf(acc[a][2], i0, __uint_as_float(y.z)), fmaf(acc[a][3], i0, __uint_as_float(y.w)));
            }
        }
    }
}

__device__ __forceinline__ int swap01(int i) { return (i & ~3) | ((i & 1) << 1) | ((i >> 1) & 1); }
enum { BC_AUX = 0, BC_S = 5, BC_KG = 15 };

__device__ __forceinline__ void conv_aux(const Params& p, const CUtensorMap* mU, uint32_t sb, int aw, int lane, int bid, unsigned epoch) {
    const unsigned t0 = clock32();
    const int g = lane >> 2, t = lane & 3, mi = lane >> 3, r8 = lane & 7;
    const int rank = bid & 1, slab = bid >> 1;
    const uint32_t bar_y = sb + SC_MISC, bar_u = bar_y + 32, bar_v = bar_y + 40, bar_box = bar_y + 64 + 8 * aw, s_bm = bar_y + 128;
    if (lane == 0) {
        mbar_init(bar_box, 1); mbar_fence();
        mbar_expect(bar_box, 4096);
        if (UDELAY) until(t0, UDELAY);
        tma4d(sb + SC_RT + 4096 * aw, mU, 16 * slab, 0, 0, 16 * rank + 2 * aw, bar_box);
        mbar_init(bar_y + 8 * aw, aw < 4 ? 9 : aw == 5 ? 8 : 1); mbar_fence();
        if (aw < 5) mbar_expect(bar_y + 8 * aw, aw == 4 ? 16384 : 4096);
    }
    __syncwarp();
    asm volatile("barrier.cluster.arrive.relaxed.aligned;" ::: "memory");
    asm volatile("setmaxnreg.dec.sync.aligned.u32 88;");
    const uint32_t ut = sb + SC_UT + aw * UT_STRIDE;
    sts128(ut + (mi >> 1) * (SC_ST - SC_UT) + (mi & 1) * UT_HALF + r8 * 16, 0, 0, 0, 0);
    if (lane < 16) sts128(s_bm + lane * 16, 0, 0, 0, 0);
    {
        const uint32_t dst = sb + SC_UT + swap01(g) * UT_STRIDE + (8 + 64 * rank + 8 * aw + t) * 16;
        const uint32_t rdst = mapa(dst, rank ^ 1), rbar = mapa(bar_u, rank ^ 1);
        asm volatile("barrier.cluster.wait.acquire.aligned;" ::: "memory");
        mbar_wait(bar_box);
        if (aw == 0) TSTAMP(1);
        const uint32_t src = fresh(sb + SC_RT) + aw * 4096 + (8 * mi + 4 * (r8 & 1) + (r8 >> 1)) * 32 + ((rank ^ (r8 & 1)) << 4);
        uint32_t x[8][4];
#pragma unroll
        for (int i = 0; i < 4; i++) { ldsm4t(x[i], src + 1024 * i); ldsm4t(x[4 + i], (src ^ 16) + 1024 * i); }
        asm volatile("" :: "r"(x[0][0]), "r"(x[1][0]), "r"(x[2][0]), "r"(x[3][0]) : "memory");
#pragma unroll
        for (int i = 0; i < 4; i++) st_async128(rdst + (i & 1) * UT_HALF + 32 * (i & 2), x[4 + i][0], x[4 + i][1], x[4 + i][2], x[4 + i][3], rbar);
#pragma unroll
        for (int i = 0; i < 4; i++) sts128(dst + (i & 1) * UT_HALF + 32 * (i & 2), x[i][0], x[i][1], x[i][2], x[i][3]);
    }
    bar_sync(BC_AUX, 256);
    mbar_wait_cluster(bar_u);
    if (aw == 0) TSTAMP(2);
    {
        const uint32_t a = fresh(ut) + (mi & 1) * UT_HALF + (64 * (mi >> 1) + r8) * 16;
        uint4 v = lds128(a);
#pragma unroll
        for (int i = 1; i <= 8; i++) {
            const uint4 w = lds128(a + 128 * i);
            sts128(a + 128 * i + (SC_ST - SC_UT), badd2(v.x, w.x), badd2(v.y, w.y), badd2(v.z, w.z), badd2(v.w, w.w));
            v = w;
        }
    }
    bar_arrive(BC_S + aw, 64);
    if (aw == 0) TSTAMP(3);
#pragma unroll 1
    for (int k = aw; k < 26; k += 8) {
        if (k - aw == 8) {
            bar_sync(BC_KG, 384);
            if (lane < 16) sts128(sb + SC_V + aw * V_STRIDE + lane * 16, 0, 0, 0, 0);
        }
        const int c = (k < 13 ? 0 : 4) + t, a = 8 * (k < 13 ? k : k - 13) + g;
        if (a < 97) window_task(fresh(sb + SC_UT) + c * UT_STRIDE, sb + SC_V + c * V_STRIDE, a, a < 64);
        __syncwarp();
    }
    if (aw == 0) TSTAMP(9);
    {
        {
            const uint32_t par = (epoch & 1) ? 0x80008000u : 0u;
            uint4 v;
            for (int it = 0;; it++) {
                v = ld_rlx128(p.s->gate + 256 * aw + 8 * lane);
                v.x ^= par; v.y ^= par; v.z ^= par; v.w ^= par;
                if (__all_sync(0xffffffffu, (v.x & v.y & v.z & v.w & 0x80008000u) == 0x80008000u)) break;
                if (it > (1 << 20)) __trap();
            }
            sts128(sb + SC_GT + (lane & 1) * UT_HALF + (8 + 16 * aw + (lane >> 1)) * 16, v.x, v.y, v.z, v.w);
        }
        __syncwarp();
        if (lane == 0) { mbar_arrive(bar_v); prefetch_map(mU + 6); }
        next_epoch(p, epoch);
        if (aw == 0) TSTAMP(4);
        if (aw == 7) {
            const int row = key_row(wait_sel(p, slab >> 1, r8, key_tag(epoch)));
            if (lane < 8) asm volatile("red.shared.or.b32 [%0], %1;" :: "r"(s_bm + (row >> 5) * 4), "r"(1u << (row & 31)) : "memory");
            TSTAMP(10);
        }
        bar_sync(BC_AUX, 256);
        const uint32_t src = sb + SC_RT + ((r8 >> 1) & 1) * Y_RS + (2 * mi + (r8 & 1)) * Y_CS + (2 * aw + (r8 >> 2)) * 16;
        const int L = 2 * aw + (t >> 1);
        const int row0 = 256 * rank + 128 * (g >> 2) + 32 * (L & 3) + 16 * (g & 1) + 8 * ((g >> 1) & 1) + (L >> 2);
        __nv_bfloat16* outp = p.out + (size_t)row0 * DM + 16 * slab + 8 * (t & 1);
        const uint32_t stg = sb + SC_ST + 4096 * aw, so = (g >> 1) * 256 + (t >> 1) * 64 + (g & 1) * 32 + (t & 1) * 16;
#pragma unroll 1
        for (int s = 0; s < 4; s++) {
            const uint32_t bm = lds32(fresh(s_bm) + (16 * s + (row0 >> 5)) * 4) >> (row0 & 31);
            const bool routed = __any_sync(0xffffffffu, bm & 0x11u);
            mbar_wait_cluster(bar_y + 8 * s);
            const uint32_t sf = fresh(src) + 512 * s;
            uint32_t y[2][4];
            ldsm4t(y[0], sf); ldsm4t(y[1], sf + 256);
            if (routed) {
#pragma unroll
                for (int k = 0; k < 2; k++)
                    asm volatile("{ .reg .pred p; setp.ne.u32 p, %5, 0; @!p st.global.v4.u32 [%0], {%1,%2,%3,%4}; @p red.relaxed.gpu.global.add.noftz.v4.bf16x2 [%0], {%1,%2,%3,%4}; }"
                                 :: "l"(outp + (size_t)(512 * s + 4 * k) * DM), "r"(y[k][0]), "r"(y[k][1]), "r"(y[k][2]), "r"(y[k][3]), "r"(bm & (1u << (4 * k))) : "memory");
            } else {
                sts128(stg + so + 1024 * s, y[0][0], y[0][1], y[0][2], y[0][3]); sts128(stg + so + 1024 * s + 128, y[1][0], y[1][1], y[1][2], y[1][3]);
                asm volatile("fence.proxy.async.shared::cta;" ::: "memory");
                __syncwarp();
                if (lane == 0) asm volatile("cp.async.bulk.tensor.5d.global.shared::cta.bulk_group [%0, {%2, %3, %3, %3, %4}], [%1];"
                                            :: "l"(mU + 6), "r"(stg + 1024 * s), "r"(16 * slab), "r"(0), "r"(512 * s + 256 * rank + 64 * (aw & 1) + (aw >> 1)) : "memory");
            }
            if (aw == 0) TSTAMP(16 + s);
        }
        if (lane == 0) { asm volatile("cp.async.bulk.commit_group;" ::: "memory"); asm volatile("cp.async.bulk.wait_group.read 0;" ::: "memory"); }
        if (aw == 0) TFLUSH();
    }
}

__device__ __forceinline__ void conv_main(const Params& p, uint32_t sb, int warp, int lane, int bid, unsigned epoch, uint32_t (&w)[12]) {
    asm volatile("setmaxnreg.inc.sync.aligned.u32 168;");
    const int g = lane >> 2, t = lane & 3, mi = lane >> 3, r8 = lane & 7;
    const int rank = bid & 1;
    const uint32_t bar_y = sb + SC_MISC, bar_v = bar_y + 40;
    next_epoch(p, epoch);
    if (warp < 4) {
        asm volatile("" :: "r"(w[0]), "r"(w[2]), "r"(w[4]), "r"(w[6]), "r"(w[8]), "r"(w[10]) : "memory");
        bar_arrive(BC_KG, 384);
    } else {
        const uint4* src = p.s->kp + (4 * bid + warp - 4) * 128 + lane;
        for (int it = 0;; it++) {
            uint32_t bad = 0;
#pragma unroll
            for (int i = 0; i < 4; i++) { const uint4 v = ld_rlx128(src + 32 * i); w[3 * i] = v.x; w[3 * i + 1] = v.y; w[3 * i + 2] = v.z; bad |= v.w ^ ~epoch; }
            const bool ok = __all_sync(0xffffffffu, bad == 0);
            if (ok) break;
            if (it > (1 << 20)) __trap();
        }
    }
    if ((warp & 3) == 0) TSTAMP(5 + (warp >> 2));
    {
        const uint32_t kt = sb + SC_KT + warp * KT_BYTES;
        const uint32_t kd = sb + SC_KD + warp * 1024 + 16;
#pragma unroll
        for (int nu = 0; nu < 3; nu++) {
            uint32_t a, a0, de, dr;
            if (nu == 0) { a = kd + (8 * g + 2 * (t & 1) + (t >> 1)) * 2; de = 8; dr = 128; a0 = a; }
            else if (nu == 1) { a = t < 2 ? kd + (256 + 4 * g + t) * 2 : kt + KT_C * 4 + (64 * t - 100 + 2 * g) * 2; de = t < 2 ? 4 : 2; dr = t < 2 ? 64 : 32; a0 = a; }
            else {
                a = t < 2 ? kt + KT_D * 4 + (13 + 64 * t + g) * 2 : kd + 800; de = 64; dr = 16; a0 = a;
                if ((lane & 29) == 0) a0 = kt + (t ? KT_D * 4 + 141 * 2 : KT_C * 4 + 156 * 2);
            }
#pragma unroll
            for (int i = 0; i < 4; i++) {
                const uint32_t v = w[6 * (i >> 1) + 2 * nu + (i & 1)];
                sts16(i ? a + i * dr : a0, v); sts16(a + i * dr + de, v >> 16);
            }
        }
        if (lane == 0) sts128(kt + (KT_T + 2) * 4, 0, w[4] & 0xffffu, __byte_perm(w[4], 0, 0x1010), w[4] << 16);
        __syncwarp();
        const uint32_t kf = fresh(kd), d = kt + (16 + 8 * lane) * 4;
        auto put = [&](uint32_t d, uint32_t pv, uint32_t w0, uint32_t w1, uint32_t w2, uint32_t w3) {
            sts128(d, __byte_perm(w0, pv, 0x5410), __byte_perm(w0, 0, 0x1032), __byte_perm(w1, w0, 0x7610), __byte_perm(w1, 0, 0x1032));
            sts128(d + 16, __byte_perm(w2, w1, 0x7610), __byte_perm(w2, 0, 0x1032), __byte_perm(w3, w2, 0x7610), __byte_perm(w3, 0, 0x1032));
        };
        const uint32_t pv = lds16(kf + (lane ? 16 * lane : 512) - 2);
        const uint4 x = lds128(kf + 16 * lane);
        const uint2 v = lds64(kf + 512 + 8 * lane);
        const uint32_t c4 = lds16(lane == 31 ? fresh(kt) + KT_C * 4 + 28 * 2 : kf + 520 + 8 * lane);
        put(d, lane ? pv : 0, x.x, x.y, x.z, x.w);
        uint32_t w3 = __byte_perm(v.y, c4, 0x5432);
        if (lane == 31) w3 = bsub2(w3, __byte_perm(c4, 0, 0x1010));
        put(d + 1024, lane ? v.x : pv, __byte_perm(v.x, 0, 0x1010), __byte_perm(v.x, v.y, 0x5432), __byte_perm(v.y, 0, 0x1010), w3);
    }
    asm volatile("barrier.cluster.wait.acquire.aligned;" ::: "memory");
    bar_sync(BC_S + swap01(warp), 64);
    if ((warp & 3) == 0) TSTAMP(7 + (warp >> 2));
    {
        const uint32_t ut = fresh(sb + SC_UT) + swap01(warp) * UT_STRIDE, kt = fresh(sb + SC_KT) + warp * KT_BYTES;
        uint32_t u1 = ut + (mi & 1) * UT_HALF + (8 + r8) * 16 + (mi >> 1) * 128;
        auto dup = [&](uint32_t v) { return v ^ p.zero; };
        uint32_t kp = kt + (16 + g - 2 * t) * 4;
        float acc[16][4];
        {
            const uint32_t c0 = lds32(kp + 2048), c1 = lds32(kp + 2080), c2 = lds32(kp + 2016), c3 = dup(c0);
            const uint32_t e0 = lds32(kp + (KT_T - 16) * 4), e1 = lds32(kp + (KT_T - 8) * 4), e2 = lds32(kp + (KT_T - 24) * 4), e3 = dup(e0);
            const uint32_t f0 = dup(e1), f1 = lds32(kp + KT_T * 4);
            const uint32_t uo = ut + UT_HALF + (7 + lane) * 16;
#pragma unroll
            for (int i = 0; i < 16; i++) { acc[i][0] = acc[i][1] = acc[i][2] = acc[i][3] = 0.f; }
#pragma unroll
            for (int mu = 0; mu < 8; mu += 4) {
                uint32_t b[4];
                ldsm4(b, uo + 128 * mu);
#pragma unroll
                for (int k = 0; k < 4; k++) mma_bf8(acc[mu + 8 + k], f0, f1, b[k]);
            }
#pragma unroll
            for (int mu = 0; mu < 12; mu += 2) {
                uint32_t b[4];
                ldsm4(b, u1 + 128 * mu);
                mma_bf(acc[mu + 4], c0, c1, c2, c3, b[0], b[1]);
                mma_bf(acc[mu + 5], c0, c1, c2, c3, b[2], b[3]);
                if (mu < 8) { mma_bf(acc[mu + 8], e0, e1, e2, e3, b[0], b[1]); mma_bf(acc[mu + 9], e0, e1, e2, e3, b[2], b[3]); }
            }
        }
        {
            float M[8][4];
#pragma unroll
            for (int i = 0; i < 8; i++) { M[i][0] = M[i][1] = M[i][2] = M[i][3] = 0.f; }
            uint32_t up = u1 + (mi >> 1) * 128, s[8][4], a3[4];
            auto frag = [&](uint32_t (&a)[4], uint32_t x) { a[0] = lds32(x); a[1] = lds32(x + 32); a[2] = lds32(x - 32); a[3] = dup(a[0]); };
            frag(a3, kp + 1536);
#pragma unroll
            for (int i = 0; i < 8; i++) ldsm4(s[i], u1 + (SC_ST - SC_UT) + 256 * i);
            __syncwarp();
#pragma unroll 1
            for (int j0 = 0; j0 < 8; j0++) {
                uint32_t a2[4], a1[4], a0[4], b[4][4];
                frag(a2, kp + 1024);
#pragma unroll
                for (int i = 0; i < 4; i++) ldsm4(b[i], up + 512 * i);
                frag(a1, kp + 512); frag(a0, kp);
                kp += 64; u1 -= 16; up -= 16;
#pragma unroll
                for (int i = 0; i < 7; i++) mma_bf(acc[2 * i + 2], a3[0], a3[1], a3[2], a3[3], s[i][0], s[i][1]);
#pragma unroll
                for (int e = 0; e < 4; e++) a3[e] = bsub2(a2[e], a3[e]);
#pragma unroll
                for (int i = 0; i < 7; i++) mma_bf(acc[2 * i + 3], a2[0], a2[1], a2[2], a2[3], s[i][2], s[i][3]);
#pragma unroll
                for (int i = 0; i < 7; i++) mma_bf(M[i + 1], a3[0], a3[1], a3[2], a3[3], b[i >> 1][2 * (i & 1)], b[i >> 1][2 * (i & 1) + 1]);
                frag(a3, kp + 1536);
#pragma unroll
                for (int i = 0; i < 8; i++) mma_bf(acc[2 * i], a1[0], a1[1], a1[2], a1[3], s[i][0], s[i][1]);
#pragma unroll
                for (int e = 0; e < 4; e++) a1[e] = bsub2(a0[e], a1[e]);
#pragma unroll
                for (int i = 0; i < 8; i++) { mma_bf(acc[2 * i + 1], a0[0], a0[1], a0[2], a0[3], s[i][2], s[i][3]); ldsm4(s[i], u1 + (SC_ST - SC_UT) + 256 * i); }
#pragma unroll
                for (int i = 0; i < 8; i++) mma_bf(M[i], a1[0], a1[1], a1[2], a1[3], b[i >> 1][2 * (i & 1)], b[i >> 1][2 * (i & 1) + 1]);
            }
            u1 = dup(u1) + 128;
#pragma unroll
            for (int i = 0; i < 8; i++)
#pragma unroll
                for (int c = 0; c < 4; c++) { acc[2 * i][c] += M[i][c]; acc[2 * i + 1][c] -= M[i][c]; }
        }
        if ((warp & 3) == 0) TSTAMP(11 + (warp >> 2));
        mbar_wait(bar_v);
        const uint32_t vt = fresh(sb + SC_V) + swap01(warp) * V_STRIDE;
        const uint32_t g1 = fresh(u1) - ut + sb + SC_GT;
        const uint32_t ydst = sb + SC_RT + rank * Y_RS + warp * Y_CS + lane * 16;
        const uint32_t ydr = mapa(ydst, rank ^ 1), ybr = mapa(bar_y, rank ^ 1);
        auto stairs = [&](auto R) {
        uint32_t ug[2][2][4];
        auto ld_ug = [&](int i) { ldsm4t(ug[i & 1][0], u1 + 256 * i); ldsm4t(ug[i & 1][1], g1 + 256 * i); };
        auto ship = [&](int i) {
            const uint32_t (&u)[4] = ug[i & 1][0], (&gg)[4] = ug[i & 1][1];
            const uint32_t y0 = gmix(gg[0], acc[2 * i][0], acc[2 * i][1], u[0]), y1 = gmix(gg[1], acc[2 * i][2], acc[2 * i][3], u[1]);
            const uint32_t y2 = gmix(gg[2], acc[2 * i + 1][0], acc[2 * i + 1][1], u[2]), y3 = gmix(gg[3], acc[2 * i + 1][2], acc[2 * i + 1][3], u[3]);
            if ((i & 1) != R.value) st_async128(ydr + 512 * (i >> 1), y0, y1, y2, y3, ybr + 8 * (i >> 1));
            else asm volatile("{ .reg .pred q; setp.eq.u32 q, %6, 0; st.shared.v4.u32 [%0], {%2,%3,%4,%5}; bar.warp.sync 0xffffffff; @q mbarrier.arrive.shared::cta.b64 _, [%1]; }"
                              :: "r"(ydst + 512 * (i >> 1)), "r"(bar_y + 8 * (i >> 1)), "r"(y0), "r"(y1), "r"(y2), "r"(y3), "r"(lane) : "memory");
        };
        const uint32_t VD = vt + (VC_OFF - 400 - 16 * t) * 4 + (8 * g ^ 16 * (-t & 2)), VD2 = vt + (VC_OFF - 415 - 16 * t) * 4 + (8 * g ^ 16 * (~t & 2));
        uint2 bd[10];
        uint32_t x[2][4][4];
        auto ld4 = [&](uint32_t (&v)[4], int dl) { const uint2 w = lds64(VD + 256 * dl); v[0] = w.x; v[1] = w.y; v[2] = lds32(VD2 + 256 * dl); v[3] = dup(w.x); };
        auto mm4 = [&](const uint32_t (&v)[4], int dl) {
#pragma unroll
            for (int s = dl & 1; s < 10; s += 2) if ((dl + s) / 2 < 16) mma_bf(acc[(dl + s) / 2], v[0], v[1], v[2], v[3], bd[s].x, bd[s].y);
        };
        const uint32_t KE = kt + (KT_D + g + t) * 4, VE = vt + (VE_BASE - 912 - 16 * t) * 4 + (8 * g ^ 16 * (~t & 2));
        uint32_t b0[8], b1[8];
        auto ld8 = [&](uint32_t (&v)[4], int dl) { const uint2 w = lds64(VE + 512 * dl), z = lds64(VE + 512 * dl - 256); v[0] = w.x; v[1] = w.y; v[2] = z.x; v[3] = z.y; };
        auto mm8 = [&](const uint32_t (&v)[4], int dl) {
#pragma unroll
            for (int s = 0; s < 8; s++) if (dl + s < 16) mma_bf(acc[dl + s], v[0], v[1], v[2], v[3], b0[s], b1[s]);
        };
        ld_ug(0); ld4(x[0][0], 6);
#pragma unroll
        for (int s = 0; s < 10; s++) bd[s] = lds64(kt + (KT_C + 2 * g + 2 * t + 8 * s) * 4);
        ld_ug(1);
#pragma unroll
        for (int s = 0; s < 8; s++) { b0[s] = lds32(KE + 32 * s); b1[s] = lds32(KE + 32 * s + 16); }
        ship(0);
#pragma unroll
        for (int j = 0; j < 4; j++) ld8(x[1][j], 8 + j);
        mm4(x[0][0], 6);
        ship(1);
#pragma unroll
        for (int j = 0; j < 4; j++) { mm8(x[1][j], 8 + j); ld4(x[0][j], 7 + j); }
        ld_ug(2);
#pragma unroll
        for (int j = 0; j < 4; j++) { uint32_t v[4], z[4]; ld8(v, 12 + j); ld4(z, 30 - j); mm8(v, 12 + j); mm4(x[0][j], 7 + j); mm4(z, 30 - j); }
#pragma unroll
        for (int k = 2; k < 6; k++) {
#pragma unroll
            for (int j = 0; j < 4; j++) ld4(x[(k + 1) & 1][j], 4 * k + 3 + j);
            ld_ug(k + 1);
            ship(k);
#pragma unroll
            for (int j = 0; j < 4; j++) mm4(x[(k + 1) & 1][j], 4 * k + 3 + j);
        }
        ld_ug(7);
        ship(7 - R.value); ship(6 + R.value);
        };
        if (rank) stairs(std::integral_constant<int, 1>()); else stairs(std::integral_constant<int, 0>());
        if ((warp & 3) == 0) TSTAMP(14 + (warp >> 2)); else TSTAMP(21 + warp);
    }
}

constexpr int SF_WD = 147456;
constexpr int SF_H = 81920;
constexpr int SF_RED = 131072;
constexpr int SF_XS = 221184;
constexpr int SF_MISC = SF_XS + 8 * 1168;
constexpr int SF_KG = SF_MISC - 10 * KG_STAGE;
constexpr int SF_WR = SF_KG - 2304;
constexpr int FB_X = 64, FB_RDONE = 72, FB_FREE = 80, FB_KDONE = 88, FB_KEYS = 96, FB_W = 112, FB_D = FB_W + 72, FB_H = FB_D + 96, FS_PART = 512, FS_TOK = 896;
enum { BAR_F = 6, BAR_R = 7, BAR_GU = 8, BAR_RED = 9 };
static_assert(NPRE <= 10 && SF_KG % 128 == 0 && SF_KG >= 7 * 24576 && SF_WR - 4 * 9216 >= 5 * 24576 && SF_WR - 6 * 9216 >= 5 * 16384, "layout");

__device__ __forceinline__ void ffn_front(const Params& p, const CUtensorMap* maps, uint32_t sb, int warp, int lane, int f, unsigned epoch) {
    const unsigned t0 = clock32();
    const int g = lane >> 2, t = lane & 3, mi = lane >> 3, r8 = lane & 7;
    const bool isx = f < NX;
    const int nrw = f < 8 ? 6 : 4, r0 = f < 8 ? 48 * f : 128 + 32 * f;
    const int rw = warp < 12 ? 13 - warp : warp ^ (warp < 14 ? 10 : 15);
    const uint32_t bar_row = sb + SF_MISC  , bar_x = bar_row + FB_X;
    const uint32_t s_part = bar_row + FS_PART  , s_tok = bar_row + FS_TOK  ;
    const uint32_t rows = sb + SF_WR - 9216 * (rw + 1);
    if (lane == 0) {
        mbar_init(bar_row + 8 * rw, 1); mbar_fence();
        if (rw < nrw) { mbar_expect(bar_row + 8 * rw, 9216); until(t0, RDELAY); bulk_g2s(rows, p.u + (size_t)(r0 + 8 * rw) * DM, 9216, bar_row + 8 * rw); }
        else if (rw >= 6) { mbar_expect(bar_row + 8 * rw, 1152); bulk_g2s(sb + SF_WR + (rw & 1) * 1152, (rw & 1) ? p.gatew : p.wr, 1152, bar_row + 8 * rw); }
        if (warp >= 10) {
#pragma unroll 1
            for (int i = warp - 10; i < 39; i += 6) mbar_init(bar_x + 8 * i, i == 1 ? nrw : i == 2 ? 4 : 1);
        }
        mbar_fence();
    }
    const int ks0 = isx ? 4 * f : 6 * f - 72, nt = isx ? 4 : 6;
    if (warp == 13) {
        stg128(p.s->keys + (lane >> 1) * 128 + 2 * f + (lane & 1), 0, 0, 0, 0);
        if (lane < 8 && isx && !(f & 1)) st_rlx32(&p.s->sel[32 * f + lane], 0);
    }
    __syncwarp();
    bar_sync(BAR_F, f < 12 ? 256 : 192);
    bar_arrive(0, NTHR);
    if (warp == 15) TSTAMP(1);

    if (warp == 12) {
        if (lane == 0) {
            const CUtensorMap* m = maps + (isx ? 1 : 3);
            prefetch_map(m); prefetch_map(m + 1);
            unsigned tb = t0 + WDELAY;
#pragma unroll 1
            for (int n = 0; n < 18; n++) {
                if (n == NPRE) { mbar_wait(bar_row + FB_KEYS); tb = clock32(); }
                until(tb, 0); tb += WGAP;
                const uint32_t b = bar_row + FB_W + 8 * (n >> 1);
                if (!(n & 1)) mbar_expect(b, nt * 4096);
                tma3d(sb + n * nt * 2048, m + (n & 1), 0, 64 * (n >> 1), ks0 >> 1, b);
            }
            TSTAMP(12);
            if (isx) {
                prefetch_map(maps + 5);
#pragma unroll 1
                for (int n = 0; n < 12; n++) {
                    until(tb, 0); tb += DGAP;
                    if (n == 6) mbar_wait(bar_row + FB_FREE);
                    mbar_expect(bar_row + FB_D + 8 * n, 12288);
                    tma2d(sb + (n < 6 ? SF_WD : -6 * 12288) + n * 12288, maps + 5, 32 * (f >> 1), 2304 * (f & 1) + 192 * n, bar_row + FB_D + 8 * n);
                }
                TSTAMP(13);
            }
        }
    } else if (warp == 13) {
        const uint32_t tag = key_tag(epoch), par = (epoch & 1) ? 0u : 0x8000u;
        next_epoch(p, epoch);
        bar_sync(BAR_R, 32 * (nrw + 1));
        TSTAMP(3);
        uint32_t k[16];
        const uint2 va = lds64(fresh(s_part) + lane * 8), vb = lds64(fresh(s_part) + 256 + lane * 8);
        const bool two = nrw > 4 && lane < 16;
        {
            auto mk = [&](uint32_t r, int row) { const uint32_t rb = pack_bf16(0.f, __uint_as_float(r)); return (rb ^ (((int)rb >> 31) & 0x7fff0000u) ^ 0x80000000u) | tag | (uint32_t)(2047 - row); };
            uint32_t ka = mk(va.x, r0 + lane), kb = two ? mk(vb.x, r0 + 32 + lane) : 0;
#pragma unroll 1
            for (int h = 0; h < 2; h++)
#pragma unroll
                for (int r = 0; r < 4; r++) {
                    const uint32_t m = __reduce_max_sync(0xffffffffu, max(ka, kb));
                    if (ka == m) ka = 0;
                    if (kb == m) kb = 0;
                    if ((lane & 1) == h) k[r] = m;
                }
        }
        asm volatile("st.relaxed.gpu.global.v4.u32 [%0], {%1,%2,%3,%4};" :: "l"(p.s->keys + (lane >> 1) * 128 + 2 * f + (lane & 1)), "r"(k[0]), "r"(k[1]), "r"(k[2]), "r"(k[3]) : "memory");
        TSTAMP(4);
        {
            const uint32_t gb = pack_bf16(sigmoidf_(rbf(__uint_as_float(va.y))), sigmoidf_(rbf(__uint_as_float(vb.y)))) | par | (par << 16);
            asm volatile("st.relaxed.gpu.global.u16 [%0], %1;" :: "l"(p.s->gate + r0 + lane), "h"((unsigned short)gb) : "memory");
            if (two) asm volatile("st.relaxed.gpu.global.u16 [%0], %1;" :: "l"(p.s->gate + r0 + 32 + lane), "h"((unsigned short)(gb >> 16)) : "memory");
        }
        const uint4* src = p.s->keys + (f & 15) * 128 + lane;
        for (int it = 0;; it++) {
            uint32_t bad = 0;
#pragma unroll
            for (int i = 0; i < 4; i++) {
                const uint4 x = ld_rlx128(src + (i < 3 || lane < 24 ? 32 * i : 64));
                k[i] = x.x; k[4 + i] = x.y; k[8 + i] = x.z; k[12 + i] = x.w;
                bad |= x.x ^ tag;
            }
            const bool ok = __all_sync(0xffffffffu, (bad & 0xf800u) == 0);
            if (it < 8) TSTAMP(it < 4 ? 16 + it : 20 + it);
            if (ok) break;
            if (it > (1 << 20)) __trap();
        }
        TSTAMP(5);
        mbar_wait(bar_row + FB_KDONE);
        if (lane == 0) { mbar_arrive(bar_row + FB_KEYS); mbar_expect(bar_x, 8 * 1152); }
        uint32_t key = 0;
#pragma unroll 1
        for (int r = 0; r < 8; r++) {
            const uint32_t m = __reduce_max_sync(0xffffffffu, max(max(k[0], k[1]), max(k[2], k[3])));
#pragma unroll
            for (int i = 0; i < 4; i++) {
                const bool pop = k[i] == m;
                k[i] = pop ? k[4 + i] : k[i]; k[4 + i] = pop ? k[8 + i] : k[4 + i]; k[8 + i] = pop ? k[12 + i] : k[8 + i]; k[12 + i] = pop ? 0 : k[12 + i];
            }
            if (lane == 0) bulk_g2s(sb + SF_XS + r * 1168, p.u + (size_t)key_row(m) * DM, 1152, bar_x);
            if (r8 == r) key = m;
        }
        const int row = key_row(key);
        TSTAMP(6);
        if (isx) {
            if (!(f & 1)) {
                stg128(p.out + (size_t)row * DM + 16 * f + 8 * mi, 0, 0, 0, 0);
                fence_gpu();
                __syncwarp();
                if (lane < 8) st_rlx32(&p.s->sel[32 * f + lane], key);
            }
            wait_sel(p, f >> 1, r8, tag);
            uint32_t gb;
            for (int it = 0;; it++) {
                asm volatile("ld.relaxed.gpu.global.u16 %0, [%1];" : "=r"(gb) : "l"(p.s->gate + row) : "memory");
                gb ^= par;
                if (!(gb & 0x8000u)) break;
                if (it > (1 << 20)) __trap();
            }
            const uint32_t rb = key ^ 0x80000000u, rv = (rb ^ (((int)rb >> 31) & 0x7fff0000u)) & 0xffff0000u;
            sts64(s_tok + r8 * 8, row, __float_as_uint(rbf(1.0f - bf_lo(gb)) * rbf(sigmoidf_(__uint_as_float(rv)))));
            __syncwarp();
            TSTAMP(7);
            bar_arrive(BAR_RED, 416);
        }
    } else {
        if (rw < nrw) {
            float c[2][4];
#pragma unroll
            for (int i = 0; i < 2; i++) { c[i][0] = c[i][1] = c[i][2] = c[i][3] = 0.f; }
            mbar_wait(bar_row + 48); mbar_wait(bar_row + 56);
            const uint32_t b = fresh(sb + SF_WR) + (g & 1) * 1152 + (g >> 2) * 64 + t * 16 + (g & 2) * 2;
            uint32_t w[18][2];
#pragma unroll
            for (int kb = 0; kb < 18; kb++) { const uint32_t o = ((kb & 1) ? b ^ 64 : b) + 128 * (kb >> 1); w[kb][0] = lds32(o); w[kb][1] = lds32(o + 8); }
            mbar_wait(bar_row + 8 * rw);
            if (warp == 15) TSTAMP(2);
            const uint32_t a = fresh(rows) + g * 1152 + (g & 1) * 64 + t * 16;
#pragma unroll
            for (int kb = 0; kb < 18; kb++) {
                const uint4 x = lds128(((kb & 1) ? a ^ 64 : a) + 128 * (kb >> 1));
                mma_bf(c[kb & 1], x.x, x.y, x.z, x.w, w[kb][0], w[kb][1]);
            }
            const float sr = c[0][0] + c[1][0] + __shfl_down_sync(0xffffffffu, c[0][2] + c[1][2], 1);
            const float sg = c[0][1] + c[1][1] + __shfl_down_sync(0xffffffffu, c[0][3] + c[1][3], 1);
            if (t == 2 * (g & 1)) sts64(s_part + (8 * rw + g) * 8, __float_as_uint(sr), __float_as_uint(sg));
            __syncwarp();
            bar_arrive(BAR_R, 32 * (nrw + 1));
        }
    }
}

__device__ __forceinline__ void ffn_work(const Params& p, uint32_t sb, int warp, int lane, int f, unsigned epoch) {
    const int g = lane >> 2, t = lane & 3, mi = lane >> 3, r8 = lane & 7;
    const bool isx = f < NX;
    const int ks0 = isx ? 4 * f : 6 * f - 72, nt = isx ? 4 : 6;
    const uint32_t bar_x = sb + SF_MISC + FB_X, bar_free = sb + SF_MISC + FB_FREE, bar_w = sb + SF_MISC + FB_W, bar_d = sb + SF_MISC + FB_D, bar_h = sb + SF_MISC + FB_H, s_tok = sb + SF_MISC + FS_TOK;
    next_epoch(p, epoch);
    {
        if (warp < nt) {
            float ag[2][4], au[2][4];
#pragma unroll
            for (int i = 0; i < 2; i++) { ag[i][0] = ag[i][1] = ag[i][2] = ag[i][3] = 0.f; au[i][0] = au[i][1] = au[i][2] = au[i][3] = 0.f; }
            const uint32_t wb = sb + (warp >> 1) * 4096 + (r8 + 8 * (mi >> 1)) * 64 + (((2 * (warp & 1) + (mi & 1)) ^ (r8 >> 1)) << 4);
            const uint32_t xb = sb + SF_XS + r8 * 1168 + mi * 16;
            mbar_wait(bar_x);
            if (warp == 0) TSTAMP(8);
#pragma unroll 1
            for (int n = 0; n < 9; n++) {
                mbar_wait(bar_w + 8 * n);
                const uint32_t wk = fresh(wb) + n * nt * 4096, xk = fresh(xb) + 128 * n;
                uint32_t x[4];
#pragma unroll
                for (int s = 0; s < 4; s++) {
                    uint32_t a[4], b[4];
                    if (!(s & 1)) ldsm4(x, xk + 32 * s);
                    ldsm4t(a, wk + 1024 * s); ldsm4t(b, wk + 1024 * s + nt * 2048);
                    mma_bf(ag[s & 1], a[0], a[1], a[2], a[3], x[2 * (s & 1)], x[2 * (s & 1) + 1]);
                    mma_bf(au[s & 1], b[0], b[1], b[2], b[3], x[2 * (s & 1)], x[2 * (s & 1) + 1]);
                }
                asm volatile("" :: "f"(ag[0][0]), "f"(ag[1][0]), "f"(au[0][0]), "f"(au[1][0]) : "memory");
                if (n == 4 && lane == 0 && isx) mbar_arrive(bar_free);
            }
            if (warp == 0) TSTAMP(9);
            float h[4];
#pragma unroll
            for (int c = 0; c < 4; c++) {
                const float gv = rbf(ag[0][c] + ag[1][c]);
                h[c] = rbf(gv * sigmoidf_(gv)) * rbf(au[0][c] + au[1][c]);
            }
            uint32_t h0, h1;
            asm("movmatrix.sync.aligned.m8n8.trans.b16 %0, %1;" : "=r"(h0) : "r"(pack_bf16(h[0], h[1])));
            asm("movmatrix.sync.aligned.m8n8.trans.b16 %0, %1;" : "=r"(h1) : "r"(pack_bf16(h[2], h[3])));
            if (h0 == 0) h0 = 0x8000u;
            asm volatile("{ .reg .b64 v; mov.b64 v, {%1, %2}; st.relaxed.gpu.global.b64 [%0], v; }" :: "l"(p.s->h + ((epoch & 1) * 288 + ks0 + warp) * 32 + lane), "r"(h0), "r"(h1) : "memory");
        }
        if (isx) {
            bar_sync(BAR_GU, 384);
            if (warp == 0) TSTAMP(10);
            uint2 hb[12];
            const uint32_t hs = sb + SF_H + warp * 3072;
            const uint2* hsrc = p.s->h + ((__shfl_sync(0xffffffffu, epoch, 0) & 1) * 288 + 144 * (f & 1) + 12 * warp) * 32;
            for (int it = 0;; it++) {
                if (lane == 0) { mbar_expect(bar_h + 8 * warp, 3072); bulk_g2s(hs, hsrc, 3072, bar_h + 8 * warp); }
                mbar_wait(bar_h + 8 * warp, it & 1);
                const uint32_t hf = fresh(hs) + lane * 8;
                uint32_t mn = 0xffffffffu;
#pragma unroll
                for (int s = 0; s < 12; s++) { hb[s] = lds64(hf + 256 * s); mn = min(mn, hb[s].x); }
                if (__all_sync(0xffffffffu, mn != 0)) break;
                if (it > (1 << 16)) __trap();
            }
            if (warp == 0) TSTAMP(11);
            mbar_wait(bar_d + 8 * warp);
            if (warp == 11) TSTAMP(14);
            float ad[2][2][4];
#pragma unroll
            for (int i = 0; i < 4; i++) { ad[i >> 1][i & 1][0] = ad[i >> 1][i & 1][1] = ad[i >> 1][i & 1][2] = ad[i >> 1][i & 1][3] = 0.f; }
            const uint32_t wd = fresh(sb) + (warp < 6 ? SF_WD : -6 * 12288) + warp * 12288 + (r8 + 8 * (mi >> 1)) * 64 + (((mi & 1) ^ (r8 >> 1)) << 4);
#pragma unroll
            for (int s = 0; s < 12; s++) {
                uint32_t a[4], b[4];
                ldsm4t(a, wd + 1024 * s); ldsm4t(b, (wd ^ 32) + 1024 * s);
                mma_bf(ad[0][s & 1], a[0], a[1], a[2], a[3], hb[s].x, hb[s].y);
                mma_bf(ad[1][s & 1], b[0], b[1], b[2], b[3], hb[s].x, hb[s].y);
            }
            const uint32_t rd = sb + SF_RED + warp * 1152 + (72 * t + g) * 4;
#pragma unroll
            for (int i = 0; i < 8; i++) sts32(rd + (i >> 2) * 64 + (i & 1) * 144 + ((i >> 1) & 1) * 32, __float_as_uint(ad[i >> 2][0][i & 3] + ad[i >> 2][1][i & 3]));
            bar_sync(BAR_RED, 416);
            if (warp < 4) {
                const int tid = 32 * warp + lane;
                const uint32_t rs = fresh(sb + SF_RED) + (tid >> 4) * 144 + (tid & 15) * 8;
                const uint2 tk = lds64(fresh(s_tok) + (tid >> 4) * 8);
                float x = 0.f, y = 0.f;
#pragma unroll
                for (int w = 0; w < 12; w++) { const uint2 v = lds64(rs + w * 1152); x += __uint_as_float(v.x); y += __uint_as_float(v.y); }
                asm volatile("red.relaxed.gpu.global.add.noftz.bf16x2 [%0], %1;" :: "l"(p.out + (size_t)tk.x * DM + 32 * (f >> 1) + 2 * (tid & 15)),
                             "r"(pack_bf16(x * __uint_as_float(tk.y), y * __uint_as_float(tk.y))) : "memory");
            }
            if (warp == 0) TSTAMP(15);
        }
        if (warp == 0) TFLUSH();
    }
}

constexpr int SMEM_BYTES = 232448;
static_assert(SF_MISC + 1024 <= 232192, "layout");

struct Maps { CUtensorMap m[7]; };

__global__ void __cluster_dims__(2, 1, 1) __launch_bounds__(NTHR, 1)
fused_kernel(const Params p, const __grid_constant__ Maps maps) {
    extern __shared__ __align__(1024) uint8_t smem_raw[];
    uint32_t q[8];
    {
        const int b = blockIdx.x, x = threadIdx.x, rc = 4 * b + max(b - 84, 0) - 288 + (x >> 6);
        const int cv = (b - NCONV) >> 31, ca = 8 * b + ((x >> 5) & 3), cb = 2 * rc - (rc & 3) + 4;
        const uint32_t ch = (ca & cv) | (cb & ~cv), o = NST * ch + 2 * ((x & 31) + ((x >> (cv & 2)) & 32));
        const bool c = x < (b < 84 ? 256 : 320);
        q[6] = ldg16_if(c, p.logdt + ch);
        q[2] = ldg32_if(c, p.Bre + o); q[3] = ldg32_if(c, p.Bim + o); q[4] = ldg32_if(c, p.Cre + o); q[5] = ldg32_if(c, p.Cim + o); q[0] = ldg32_if(c, p.Are + o); q[1] = ldg32_if(c, p.Aim + o);
        q[7] = ldg16_if(c, p.Dskip + ch);
    }
    const unsigned epoch = ld_rlx32(&p.s->epoch[blockIdx.x * 16 + (threadIdx.x >> 5)]);
    const uint32_t sb = __shfl_sync(0xffffffffu, smem_u32(smem_raw), 0);
    const int warp = __shfl_sync(0xffffffffu, threadIdx.x >> 5, 0), bid = __shfl_sync(0xffffffffu, blockIdx.x, 0);
    const int lane = __shfl_sync(0xffffffffu, threadIdx.x & 31, threadIdx.x);
    const bool conv = bid < NCONV;
    const int f = bid - NCONV;
    uint32_t w[12];
    if (warp < (f < 12 ? 8 : 10)) {
        const int half = conv ? warp >> 2 : warp & 1, pr = conv ? warp & 3 : warp >> 1;
        const int rc = 4 * f + max(f - 12, 0) + pr;
        const uint32_t stage = sb + (conv ? SC_KG : SF_KG) + warp * KG_STAGE;
        uint4* const kp = p.s->kp + rc * 128 + lane;
        kgen(q, sb, half, stage, stage + (conv ? 4 : 1) * KG_STAGE, 1 + pr, lane, w, [&] {
            const uint32_t a = sb + SC_KT + warp * KT_BYTES + lane * 16;
#pragma unroll
            for (int i = 0; i < 6; i++) sts128z_if(conv && lane < 30, a + 480 * i);
            stg128z_if(!conv, kp + 64 * half); stg128z_if(!conv, kp + 64 * half + 32);
            stg128z_if(!conv && warp < (f < NX ? 4 : 6), (uint4*)(p.s->h + ((lane >> 4) * 288 + (f < NX ? 4 * f : 6 * f - 72) + warp) * 32) + (lane & 15));
            if (conv) asm volatile("barrier.cluster.arrive.relaxed.aligned;" ::: "memory");
        });
        if (!conv) {
            if (!half) {
#pragma unroll
                for (int i = 0; i < 4; i++) asm volatile("st.relaxed.gpu.global.v4.u32 [%0], {%1,%2,%3,%4};" :: "l"(kp + 32 * i), "r"(w[3 * i]), "r"(w[3 * i + 1]), "r"(w[3 * i + 2]), "r"(~epoch) : "memory");
            }
            if (warp == 0) TSTAMP(22);
            if (warp == 2) TSTAMP(23);
            bar_sync(0, NTHR);
            if (warp == 0 && lane == 0) mbar_arrive(sb + SF_MISC + FB_KDONE);
        }
    } else if (conv) {
        conv_aux(p, maps.m, sb, warp - 8, lane, bid, epoch);
        return;
    } else {
        ffn_front(p, maps.m, sb, warp, lane, f, epoch);
        if (warp >= 12) return;
    }
    if (conv) conv_main(p, sb, warp, lane, bid, epoch, w);
    else ffn_work(p, sb, warp, lane, f, epoch);
}

typedef CUresult (*EncodeFn)(CUtensorMap*, CUtensorMapDataType, cuuint32_t, void*, const cuuint64_t*, const cuuint64_t*, const cuuint32_t*, const cuuint32_t*,
                             CUtensorMapInterleave, CUtensorMapSwizzle, CUtensorMapL2promotion, CUtensorMapFloatOOBfill);

void make_map(EncodeFn fn, CUtensorMap* m, const void* base, int rank, const cuuint64_t* dims, const cuuint64_t* strides, const cuuint32_t* box, CUtensorMapSwizzle sw) {
    const cuuint32_t es[5] = {1, 1, 1, 1, 1};
    fn(m, CU_TENSOR_MAP_DATA_TYPE_BFLOAT16, rank, (void*)base, dims, strides, box, es, CU_TENSOR_MAP_INTERLEAVE_NONE, sw,
       CU_TENSOR_MAP_L2_PROMOTION_NONE, CU_TENSOR_MAP_FLOAT_OOB_FILL_NONE);
}

}

extern "C" void kernel_launch(void* const* d_in, const int* in_sizes, int n_in, void* d_out, int out_size) {
    (void)in_sizes; (void)n_in; (void)out_size;
    static EncodeFn fn = nullptr;
    static void* scratch = nullptr;
    if (!fn) {
        void* ptr = nullptr; cudaDriverEntryPointQueryResult qr;
        cudaGetDriverEntryPoint("cuTensorMapEncodeTiled", &ptr, cudaEnableDefault, &qr);
        fn = (EncodeFn)ptr;
        cudaGetSymbolAddress(&scratch, g_scratch);
        cudaFuncSetAttribute(fused_kernel, cudaFuncAttributeMaxDynamicSharedMemorySize, SMEM_BYTES);
    }
    typedef const __nv_bfloat16* bp;
    Params p;
    p.u = (bp)d_in[0]; p.Are = (bp)d_in[1]; p.Aim = (bp)d_in[2]; p.Bre = (bp)d_in[3]; p.Bim = (bp)d_in[4]; p.Cre = (bp)d_in[5]; p.Cim = (bp)d_in[6];
    p.logdt = (bp)d_in[7]; p.Dskip = (bp)d_in[8]; p.wr = (bp)d_in[10]; p.gatew = (bp)d_in[14];
    p.out = (__nv_bfloat16*)d_out; p.s = (Scratch*)scratch; p.zero = 0;
    Maps maps;
    {
        const cuuint64_t dims[4] = {DM, 4, 16, 32}, strides[3] = {16 * DM * 2, DM * 2, 64 * DM * 2};
        const cuuint32_t box[4] = {16, 4, 16, 2};
        make_map(fn, &maps.m[0], d_in[0], 4, dims, strides, box, CU_TENSOR_MAP_SWIZZLE_32B);
    }
    for (int i = 0; i < 4; i++) {
        const cuuint64_t dims[3] = {32, DM, FF / 32}, strides[2] = {FF * 2, 64};
        const cuuint32_t box[3] = {32, 64, i < 2 ? 2u : 3u};
        make_map(fn, &maps.m[1 + i], d_in[11 + (i & 1)], 3, dims, strides, box, CU_TENSOR_MAP_SWIZZLE_64B);
    }
    {
        const cuuint64_t dims[2] = {DM, FF}, strides[1] = {DM * 2};
        const cuuint32_t box[2] = {32, 192};
        make_map(fn, &maps.m[5], d_in[13], 2, dims, strides, box, CU_TENSOR_MAP_SWIZZLE_64B);
    }
    {
        const cuuint64_t dims[5] = {DM, 4, 4, 2, L_SEQ}, strides[4] = {16 * DM * 2, 4 * DM * 2, 128 * DM * 2, DM * 2};
        const cuuint32_t box[5] = {16, 4, 4, 2, 1};
        make_map(fn, &maps.m[6], d_out, 5, dims, strides, box, CU_TENSOR_MAP_SWIZZLE_NONE);
    }
    fused_kernel<<<NCTA, NTHR, SMEM_BYTES>>>(p, maps);
}
```

```cpp
#include <cuda_runtime.h>
#include <cuda_bf16.h>
#include <cuda_fp16.h>
#include <cuda.h>
#include <stdint.h>
#include <type_traits>

#define LASTS 3
#define UDELAY 0
#define RDELAY 900
#define WDELAY 2200
#define WGAP 290
#define NPRE 6
#define DGAP 220

namespace {

constexpr int DM = 576, NST = 128, FF = 4608, L_SEQ = 2048;
constexpr int NCONV = 72, NX = 36, NFFN = 60, NCTA = 132, NTHR = 512;

struct __align__(128) Scratch {
    unsigned epoch[NCTA * 16];
    uint4 keys[16 * 128];
    uint32_t sel[18 * 64];
    uint16_t gate[L_SEQ];
    uint2 h[2 * 288 * 32];
    uint4 kp[288 * 128];
};
__device__ Scratch g_scratch;
#define TFLUSH()
#define TSTAMP(i)

struct Params {
    const __nv_bfloat16 *Are, *Aim, *Bre, *Bim, *Cre, *Cim, *logdt, *Dskip, *u, *wr, *gatew;
    __nv_bfloat16* out;
    Scratch* s;
    uint32_t zero;
};

__device__ __forceinline__ uint32_t smem_u32(const void* p) { return (uint32_t)__cvta_generic_to_shared(p); }
__device__ __forceinline__ uint32_t pack_bf16(float lo, float hi) { uint32_t r; asm("cvt.rn.bf16x2.f32 %0, %1, %2;" : "=r"(r) : "f"(hi), "f"(lo)); return r; }
__device__ __forceinline__ uint32_t pack_f16(float lo, float hi) { uint32_t r; asm("cvt.rn.f16x2.f32 %0, %1, %2;" : "=r"(r) : "f"(hi), "f"(lo)); return r; }
__device__ __forceinline__ float bf_lo(uint32_t w) { return __uint_as_float(w << 16); }
__device__ __forceinline__ float bf_hi(uint32_t w) { return __uint_as_float(w & 0xffff0000u); }
__device__ __forceinline__ float rbf(float x) { return bf_lo(pack_bf16(x, 0.f)); }
__device__ __forceinline__ uint32_t badd2(uint32_t a, uint32_t b) { uint32_t r; asm("add.rn.bf16x2 %0, %1, %2;" : "=r"(r) : "r"(a), "r"(b)); return r; }
__device__ __forceinline__ uint32_t bsub2(uint32_t a, uint32_t b) { uint32_t r; asm("sub.rn.bf16x2 %0, %1, %2;" : "=r"(r) : "r"(a), "r"(b)); return r; }
__device__ __forceinline__ uint32_t gmix(uint32_t ng, float ny0, float ny1, uint32_t u) {
    uint32_t r; asm("{ .reg .b32 t; fma.rn.bf16x2 t, %1, %3, %3; fma.rn.bf16x2 %0, %1, %2, t; }" : "=r"(r) : "r"(ng), "r"(pack_bf16(ny0, ny1)), "r"(u)); return r;
}
__device__ __forceinline__ void mma_bf(float (&c)[4], uint32_t a0, uint32_t a1, uint32_t a2, uint32_t a3, uint32_t b0, uint32_t b1) {
    asm("mma.sync.aligned.m16n8k16.row.col.f32.bf16.bf16.f32 {%0,%1,%2,%3}, {%4,%5,%6,%7}, {%8,%9}, {%0,%1,%2,%3};"
        : "+f"(c[0]), "+f"(c[1]), "+f"(c[2]), "+f"(c[3]) : "r"(a0), "r"(a1), "r"(a2), "r"(a3), "r"(b0), "r"(b1));
}
__device__ __forceinline__ void mma_bf8(float (&c)[4], uint32_t a0, uint32_t a1, uint32_t b0) {
    asm("mma.sync.aligned.m16n8k8.row.col.f32.bf16.bf16.f32 {%0,%1,%2,%3}, {%4,%5}, {%6}, {%0,%1,%2,%3};"
        : "+f"(c[0]), "+f"(c[1]), "+f"(c[2]), "+f"(c[3]) : "r"(a0), "r"(a1), "r"(b0));
}
__device__ __forceinline__ void mma_h(float (&c)[4], uint32_t a0, uint32_t a1, uint32_t a2, uint32_t a3, uint32_t b0, uint32_t b1) {
    asm("mma.sync.aligned.m16n8k16.row.col.f32.f16.f16.f32 {%0,%1,%2,%3}, {%4,%5,%6,%7}, {%8,%9}, {%0,%1,%2,%3};"
        : "+f"(c[0]), "+f"(c[1]), "+f"(c[2]), "+f"(c[3]) : "r"(a0), "r"(a1), "r"(a2), "r"(a3), "r"(b0), "r"(b1));
}
__device__ __forceinline__ uint32_t fresh(uint32_t a) { asm volatile("" : "+r"(a) :: "memory"); return a; }
__device__ __forceinline__ uint32_t lds16(uint32_t a) { uint32_t v; asm("ld.shared.u16 %0, [%1];" : "=r"(v) : "r"(a)); return v; }
__device__ __forceinline__ uint32_t lds32(uint32_t a) { uint32_t v; asm("ld.shared.u32 %0, [%1];" : "=r"(v) : "r"(a)); return v; }
__device__ __forceinline__ uint2 lds64(uint32_t a) { uint2 v; asm("ld.shared.v2.u32 {%0,%1}, [%2];" : "=r"(v.x), "=r"(v.y) : "r"(a)); return v; }
__device__ __forceinline__ uint4 lds128(uint32_t a) { uint4 v; asm("ld.shared.v4.u32 {%0,%1,%2,%3}, [%4];" : "=r"(v.x), "=r"(v.y), "=r"(v.z), "=r"(v.w) : "r"(a)); return v; }
__device__ __forceinline__ uint4 lds128v(uint32_t a) { uint4 v; asm volatile("ld.shared.v4.u32 {%0,%1,%2,%3}, [%4];" : "=r"(v.x), "=r"(v.y), "=r"(v.z), "=r"(v.w) : "r"(a) : "memory"); return v; }
__device__ __forceinline__ void ldsm4(uint32_t (&r)[4], uint32_t a) {
    asm("ldmatrix.sync.aligned.m8n8.x4.shared.b16 {%0,%1,%2,%3}, [%4];" : "=r"(r[0]), "=r"(r[1]), "=r"(r[2]), "=r"(r[3]) : "r"(a));
}
__device__ __forceinline__ void ldsm4t(uint32_t (&r)[4], uint32_t a) {
    asm("ldmatrix.sync.aligned.m8n8.x4.trans.shared.b16 {%0,%1,%2,%3}, [%4];" : "=r"(r[0]), "=r"(r[1]), "=r"(r[2]), "=r"(r[3]) : "r"(a));
}
__device__ __forceinline__ void sts16(uint32_t a, uint32_t v) { asm volatile("st.shared.u16 [%0], %1;" :: "r"(a), "h"((unsigned short)v) : "memory"); }
__device__ __forceinline__ void sts32(uint32_t a, uint32_t v) { asm volatile("st.shared.u32 [%0], %1;" :: "r"(a), "r"(v) : "memory"); }
__device__ __forceinline__ void sts64(uint32_t a, uint32_t x, uint32_t y) { asm volatile("st.shared.v2.u32 [%0], {%1,%2};" :: "r"(a), "r"(x), "r"(y) : "memory"); }
__device__ __forceinline__ void sts128(uint32_t a, uint32_t x, uint32_t y, uint32_t z, uint32_t w) {
    asm volatile("st.shared.v4.u32 [%0], {%1,%2,%3,%4};" :: "r"(a), "r"(x), "r"(y), "r"(z), "r"(w) : "memory");
}
__device__ __forceinline__ void st_async128(uint32_t a, uint32_t x, uint32_t y, uint32_t z, uint32_t w, uint32_t bar) {
    asm volatile("st.async.weak.shared::cluster.mbarrier::complete_tx::bytes.v4.b32 [%0], {%1,%2,%3,%4}, [%5];" :: "r"(a), "r"(x), "r"(y), "r"(z), "r"(w), "r"(bar) : "memory");
}
__device__ __forceinline__ void mbar_init(uint32_t b, uint32_t cnt) { asm volatile("mbarrier.init.shared::cta.b64 [%0], %1;" :: "r"(b), "r"(cnt) : "memory"); }
__device__ __forceinline__ void mbar_fence() { asm volatile("fence.mbarrier_init.release.cluster;" ::: "memory"); }
__device__ __forceinline__ void mbar_expect(uint32_t b, uint32_t bytes) { asm volatile("mbarrier.arrive.expect_tx.shared::cta.b64 _, [%0], %1;" :: "r"(b), "r"(bytes) : "memory"); }
__device__ __forceinline__ void mbar_arrive(uint32_t b) { asm volatile("mbarrier.arrive.shared::cta.b64 _, [%0];" :: "r"(b) : "memory"); }
#define CHINT ""
#define HINT ""
__device__ __forceinline__ void mbar_wait(uint32_t b, uint32_t parity = 0) {
    asm volatile("{ .reg .pred p; .reg .u32 n; mov.u32 n, 0;\n"
                 "LW: mbarrier.try_wait.parity.shared::cta.b64 p, [%0], %1" HINT "; @p bra LD; add.u32 n, n, 1; setp.lt.u32 p, n, 65536; @p bra LW; trap;\n"
                 "LD: }" :: "r"(b), "r"(parity) : "memory");
}
__device__ __forceinline__ void mbar_wait_cluster(uint32_t b) {
    asm volatile("{ .reg .pred p; .reg .u32 n; mov.u32 n, 0;\n"
                 "LW: mbarrier.try_wait.parity.acquire.cluster.shared::cta.b64 p, [%0], 0" CHINT "; @p bra LD; add.u32 n, n, 1; setp.lt.u32 p, n, 65536; @p bra LW; trap;\n"
                 "LD: }" :: "r"(b) : "memory");
}
__device__ __forceinline__ void tma2d(uint32_t dst, const CUtensorMap* m, int c0, int c1, uint32_t bar) {
    asm volatile("cp.async.bulk.tensor.2d.shared::cluster.global.mbarrier::complete_tx::bytes [%0], [%1, {%3, %4}], [%2];"
                 :: "r"(dst), "l"(m), "r"(bar), "r"(c0), "r"(c1) : "memory");
}
__device__ __forceinline__ void tma3d(uint32_t dst, const CUtensorMap* m, int c0, int c1, int c2, uint32_t bar) {
    asm volatile("cp.async.bulk.tensor.3d.shared::cluster.global.mbarrier::complete_tx::bytes [%0], [%1, {%3, %4, %5}], [%2];"
                 :: "r"(dst), "l"(m), "r"(bar), "r"(c0), "r"(c1), "r"(c2) : "memory");
}
__device__ __forceinline__ void tma4d(uint32_t dst, const CUtensorMap* m, int c0, int c1, int c2, int c3, uint32_t bar) {
    asm volatile("cp.async.bulk.tensor.4d.shared::cluster.global.mbarrier::complete_tx::bytes [%0], [%1, {%3, %4, %5, %6}], [%2];"
                 :: "r"(dst), "l"(m), "r"(bar), "r"(c0), "r"(c1), "r"(c2), "r"(c3) : "memory");
}
__device__ __forceinline__ void bulk_g2s(uint32_t dst, const void* src, uint32_t bytes, uint32_t bar) {
    asm volatile("cp.async.bulk.shared::cluster.global.mbarrier::complete_tx::bytes [%0], [%1], %2, [%3];"
                 :: "r"(dst), "l"(src), "r"(bytes), "r"(bar) : "memory");
}
__device__ __forceinline__ uint32_t mapa(uint32_t a, uint32_t rank) { uint32_t r; asm("mapa.shared::cluster.u32 %0, %1, %2;" : "=r"(r) : "r"(a), "r"(rank)); return r; }
__device__ __forceinline__ void prefetch_map(const CUtensorMap* m) { asm volatile("prefetch.tensormap [%0];" :: "l"(m) : "memory"); }
__device__ __forceinline__ void bar_sync(int id, int n) { asm volatile("bar.sync %0, %1;" :: "r"(id), "r"(n) : "memory"); }
__device__ __forceinline__ void bar_arrive(int id, int n) { asm volatile("bar.arrive %0, %1;" :: "r"(id), "r"(n) : "memory"); }
__device__ __forceinline__ uint32_t ldg16_if(bool c, const void* p) { uint32_t v; asm volatile("{ .reg .pred p; setp.ne.u32 p, %2, 0; @p ld.global.nc.u16 %0, [%1]; }" : "=r"(v) : "l"(p), "r"((uint32_t)c)); return v; }
__device__ __forceinline__ uint32_t ldg32_if(bool c, const void* p) { uint32_t v; asm volatile("{ .reg .pred p; setp.ne.u32 p, %2, 0; @p ld.global.nc.u32 %0, [%1]; }" : "=r"(v) : "l"(p), "r"((uint32_t)c)); return v; }
__device__ __forceinline__ uint32_t ld_rlx32(const void* p) { uint32_t v; asm volatile("ld.relaxed.gpu.global.u32 %0, [%1];" : "=r"(v) : "l"(p) : "memory"); return v; }
__device__ __forceinline__ uint4 ld_rlx128(const void* p) {
    uint4 v; asm volatile("ld.relaxed.gpu.global.v4.u32 {%0,%1,%2,%3}, [%4];" : "=r"(v.x), "=r"(v.y), "=r"(v.z), "=r"(v.w) : "l"(p) : "memory"); return v;
}
__device__ __forceinline__ void st_rlx32(void* p, uint32_t v) { asm volatile("st.relaxed.gpu.global.u32 [%0], %1;" :: "l"(p), "r"(v) : "memory"); }
__device__ __forceinline__ void stg128(void* p, uint32_t x, uint32_t y, uint32_t z, uint32_t w) {
    asm volatile("st.global.v4.u32 [%0], {%1,%2,%3,%4};" :: "l"(p), "r"(x), "r"(y), "r"(z), "r"(w) : "memory");
}
__device__ __forceinline__ void next_epoch(const Params& p, unsigned e) { if ((threadIdx.x & 31) == 0) p.s->epoch[blockIdx.x * 16 + (threadIdx.x >> 5)] = e + 1; }
__device__ __forceinline__ void sts128z_if(bool c, uint32_t a) { asm volatile("{ .reg .pred p; setp.ne.u32 p, %1, 0; @p st.shared.v4.u32 [%0], {%2,%2,%2,%2}; }" :: "r"(a), "r"((uint32_t)c), "r"(0) : "memory"); }
__device__ __forceinline__ void stg128z_if(bool c, void* a) { asm volatile("{ .reg .pred p; setp.ne.u32 p, %1, 0; @p st.global.v4.u32 [%0], {%2,%2,%2,%2}; }" :: "l"(a), "r"((uint32_t)c), "r"(0) : "memory"); }
__device__ __forceinline__ unsigned clock32() { unsigned c; asm volatile("mov.u32 %0, %clock;" : "=r"(c) :: "memory"); return c; }
__device__ __forceinline__ void until(unsigned t0, int c) { while ((int)(clock32() - t0) < c) { } }
__device__ __forceinline__ float sigmoidf_(float x) { return __fdividef(1.0f, 1.0f + __expf(-x)); }
__device__ __forceinline__ uint32_t key_tag(unsigned epoch) { return ((epoch & 15u) | 16u) << 11; }
__device__ __forceinline__ int key_row(uint32_t key) { return 2047 - (int)(key & 2047u); }
__device__ __forceinline__ uint32_t wait_sel(const Params& p, int s32, int r8, uint32_t tag) {
    uint32_t k;
    for (int it = 0;; it++) {
        k = ld_rlx32(&p.s->sel[s32 * 64 + r8]);
        if (__all_sync(0xffffffffu, (k & 0xf800u) == tag)) break;
        if (it > (1 << 20)) __trap();
    }
    return k;
}

struct cplx { float re, im; };
__device__ __forceinline__ cplx csq(cplx a) { cplx r; r.re = a.re * a.re - a.im * a.im; r.im = (a.re * a.im) * 2.f; return r; }
__device__ __forceinline__ cplx cexpk(float ar, float ai, float k) {
    float mag, s, c;
    asm("ex2.approx.ftz.f32 %0, %1;" : "=f"(mag) : "f"(ar * (k * 1.4426950408889634f)));
    const float r = ai * k;
    asm("sin.approx.ftz.f32 %0, %1;" : "=f"(s) : "f"(r));
    asm("cos.approx.ftz.f32 %0, %1;" : "=f"(c) : "f"(r));
    cplx o; o.re = mag * c; o.im = mag * s; return o;
}
struct h2c { uint32_t re, im; };
__device__ __forceinline__ h2c cmul_cd(h2c v, __half2 c, __half2 d) {
    const __half2 r = *(const __half2*)&v.re, i = *(const __half2*)&v.im;
    const __half2 x = __hfma2(__hneg2(i), d, __hmul2(r, c)), y = __hfma2(i, c, __hmul2(r, d));
    h2c o; o.re = *(const uint32_t*)&x; o.im = *(const uint32_t*)&y; return o;
}
__device__ __forceinline__ h2c cmul_s(h2c v, uint32_t s) { const __half2 h = *(const __half2*)&s; return cmul_cd(v, __low2half2(h), __high2half2(h)); }
__device__ __forceinline__ h2c cmul_sc(h2c v, uint32_t s) {
    const __half2 h = *(const __half2*)&s, c = __low2half2(h), d = __high2half2(h), r = *(const __half2*)&v.re, i = *(const __half2*)&v.im;
    const __half2 x = __hfma2(i, d, __hmul2(r, c)), y = __hfma2(__hneg2(r), d, __hmul2(i, c));
    h2c o; o.re = *(const uint32_t*)&x; o.im = *(const uint32_t*)&y; return o;
}
__device__ __forceinline__ h2c cmul_vc(h2c v, uint32_t s) {
    const __half2 h = *(const __half2*)&s, c = __low2half2(h), d = __high2half2(h), r = *(const __half2*)&v.re, i = *(const __half2*)&v.im;
    const __half2 x = __hfma2(i, d, __hmul2(r, c)), y = __hfma2(__hneg2(i), c, __hmul2(r, d));
    h2c o; o.re = *(const uint32_t*)&x; o.im = *(const uint32_t*)&y; return o;
}

constexpr int UT_HALF = 2240, UT_STRIDE = 4448;
constexpr int KT_T = 542, KT_C = 552, KT_D = 648, KT_BYTES = 720 * 4;
constexpr int VC_OFF = 80, VE_BASE = 1616;
constexpr int V_STRIDE = (1616 + 1024) * 4 + 80;
constexpr int KG_STAGE = 5248;
constexpr int Y_CS = 2080, Y_RS = 8 * Y_CS + 64;

constexpr int SC_RT = 0;
constexpr int SC_UT = 33408;
constexpr int SC_ST = SC_UT + 8 * UT_STRIDE;
constexpr int SC_KT = SC_ST + 8 * UT_STRIDE;
constexpr int SC_GT = SC_KT + 8 * KT_BYTES;
constexpr int SC_V = SC_GT + UT_STRIDE;
constexpr int SC_KG = SC_V + 4 * V_STRIDE;
constexpr int SC_KD = SC_V + 8 * V_STRIDE;
constexpr int SC_MISC = SC_KD + 8192;
static_assert(V_STRIDE % 128 == 16 && 8 * KG_STAGE <= 4 * V_STRIDE && 2 * Y_RS <= SC_UT && SC_UT % 128 == 0 && SC_ST % 128 == 0, "layout");
static_assert(SC_MISC % 16 == 0 && SC_MISC + 512 <= 232192, "layout");

__device__ __forceinline__ void window_task(uint32_t ut, uint32_t vt, int a, bool withE) {
    const uint32_t src = ut + (a + 6) * 16;
    float S[35];
    {
        uint32_t w[20];
#pragma unroll
        for (int i = 0; i < 5; i++) {
            const uint4 v = lds128(src + ((i & 1) ? 0 : UT_HALF) + ((i + 1) >> 1) * 16);
            w[4 * i] = v.x; w[4 * i + 1] = v.y; w[4 * i + 2] = v.z; w[4 * i + 3] = v.w;
        }
        float s = 0.f; S[2] = 0.f;
#pragma unroll
        for (int i = 3; i < 26; i++) { s += (i & 1) ? bf_hi(w[i >> 1]) : bf_lo(w[i >> 1]); S[i] = s; }
        const uint32_t d0 = vt + 64 * a + 16 * (a & 2), d1 = vt + 64 * a + 16 * (~a & 2);
#pragma unroll
        for (int i = 0; i < 8; i += 2)
            sts128((i & 4 ? d1 : d0) + (VC_OFF - 16) * 4 + 8 * (i & 2), pack_bf16(S[10 + i] - S[5 + i], S[5 + i] - S[2 + i]), pack_bf16(S[18 + i] - S[13 + i], S[13 + i] - S[10 + i]),
                   pack_bf16(S[11 + i] - S[6 + i], S[6 + i] - S[3 + i]), pack_bf16(S[19 + i] - S[14 + i], S[14 + i] - S[11 + i]));
        if (withE) {
#pragma unroll
            for (int i = 26; i < 35; i++) { s += (i & 1) ? bf_hi(w[i >> 1]) : bf_lo(w[i >> 1]); S[i] = s; }
#pragma unroll
            for (int i = 0; i < 8; i += 2)
                sts128((i & 4 ? d1 : d0) + VE_BASE * 4 + 8 * (i & 2), pack_bf16(S[19 + i] - S[12 + i], S[12 + i] - S[3 + i]), pack_bf16(S[27 + i] - S[20 + i], S[20 + i] - S[11 + i]),
                       pack_bf16(S[20 + i] - S[13 + i], S[13 + i] - S[4 + i]), pack_bf16(S[28 + i] - S[21 + i], S[21 + i] - S[12 + i]));
        }
    }
}

template <class F>
__device__ __forceinline__ void kgen(const uint32_t (&q)[8], uint32_t sb, int half, uint32_t stage, uint32_t pstage, int barid, int lane, uint32_t (&w)[12], F shadow) {
    const int t = lane & 3, mi = lane >> 3, r8 = lane & 7;
    {
        const uint32_t pAr = q[0], pAi = q[1], pBr = q[2], pBi = q[3], pCr = q[4], pCi = q[5], pDt = q[6], pD = q[7];
        const uint32_t wb = fresh(stage + lane * 16), za = fresh(stage + 5120 + ((lane >> 1) & 3) * 16 + mi * 4 + (lane & 1) * 2), zr = fresh(stage + 5120 + t * 16);
        const uint32_t oA = fresh(stage + (mi & 1) * 1024 + (mi >> 1) * 512 + r8 * 16), oB = fresh(stage + 2048 + mi * 512 + r8 * 16), oC = fresh(stage + 4096 + (mi & 1) * 512 + (mi >> 1) * 128 + r8 * 16);
        float acc[6][4];
#pragma unroll
        for (int a = 0; a < 6; a++) { acc[a][0] = acc[a][1] = acc[a][2] = acc[a][3] = 0.f; asm volatile("" : "+f"(acc[a][0]), "+f"(acc[a][1]), "+f"(acc[a][2]), "+f"(acc[a][3])); }
        shadow();
        sts32(zr, clock32());
        const float dt = rbf(__expf(bf_lo(pDt)));
        float ar = dt * bf_lo(pAr), ai = dt * bf_lo(pAi), ar1 = dt * bf_hi(pAr), ai1 = dt * bf_hi(pAi);
        float wr, wi, wr1, wi1;
        { const float br = dt * bf_lo(pBr), bi = dt * bf_lo(pBi), cr = bf_lo(pCr), ci = bf_lo(pCi); wr = cr * br - ci * bi; wi = cr * bi + ci * br; }
        { const float br = dt * bf_hi(pBr), bi = dt * bf_hi(pBi), cr = bf_hi(pCr), ci = bf_hi(pCi); wr1 = cr * br - ci * bi; wi1 = cr * bi + ci * br; }
        const uint32_t ex = max(__reduce_max_sync(0xffffffffu, __float_as_uint(fmaxf(fmaxf(fabsf(wr), fabsf(wi)), fmaxf(fabsf(wr1), fabsf(wi1))))) >> 23, 14u);
        const float scl = __uint_as_float((267u - ex) << 23);
        uint32_t W = pack_f16(wr * scl, wi * -scl);
        const uint32_t W1 = pack_f16(wr1 * scl, wi1 * -scl);
        if (threadIdx.x < 32) TSTAMP(20);

#pragma unroll 1
        for (int r = 0; r < 2; r++) {
            const cplx z1 = cexpk(ar, ai, 1.f), z64 = cexpk(ar, ai, 64.f);
            const cplx z2 = csq(z1), z4 = csq(z2), z8 = csq(z4), z16 = csq(z8), z32 = csq(z16);
            const cplx z128 = csq(z64), z256 = csq(z128), z512 = csq(z256), z1024 = csq(z512);
            auto put = [&](int grp, h2c a, h2c b, h2c c, h2c d) { sts128(wb + grp * 1024, a.re, b.re, c.re, d.re); sts128(wb + grp * 1024 + 512, a.im, b.im, c.im, d.im); };
            {
                const uint32_t s1 = pack_f16(z1.re, z1.im), s2 = pack_f16(z2.re, z2.im), s256 = pack_f16(z256.re, z256.im), s512 = pack_f16(z512.re, z512.im), s1024 = pack_f16(z1024.re, z1024.im);
                const h2c c04 = cmul_vc(h2c{pack_f16(1.f, z4.re), pack_f16(0.f, z4.im)}, W), c26 = cmul_sc(c04, s2);
                put(2, c04, c26, cmul_sc(c04, s1), cmul_sc(c26, s1));
                const h2c d04 = cmul_sc(c04, s256), e04 = cmul_sc(c04, s512), f04 = cmul_sc(d04, s512);
                put(3, d04, cmul_sc(c26, s256), e04, f04);
                const h2c ef = {__byte_perm(e04.re, f04.re, 0x5410), __byte_perm(e04.im, f04.im, 0x5410)};
                const h2c gh = cmul_sc(ef, s512);
                put(4, gh, cmul_sc(ef, s1024), cmul_sc(gh, s1024), ef);
            }
            {
                const uint32_t s32 = pack_f16(z32.re, z32.im), s64 = pack_f16(z64.re, z64.im), s128 = pack_f16(z128.re, z128.im);
                const h2c p0 = {pack_f16(1.f, z8.re), pack_f16(0.f, z8.im)}, p1 = cmul_s(p0, pack_f16(z16.re, z16.im)), p2 = cmul_s(p0, s32), p3 = cmul_s(p1, s32);
                put(0, p0, p1, p2, p3);
                put(1, cmul_s(p0, s64), cmul_s(p1, s64), cmul_s(p2, s64), cmul_s(p3, s64));
                sts16(za, s128); sts16(za + 64, s128 >> 16);
            }
            __syncwarp();
            {
                const uint32_t aA = fresh(oA), aB = fresh(oB), aC = fresh(oC), aZ = fresh(zr);
                const uint4 zc = lds128(aZ), zd = lds128(aZ + 64);
                const uint32_t zcs[4] = {zc.x, zc.y, zc.z, zc.w}, zds[4] = {zd.x, zd.y, zd.z, zd.w};
                uint32_t c[4];
#pragma unroll
                for (int k = 0; k < 4; k++) {
                    uint32_t a[4], b[4];
                    ldsm4t(a, aA + 128 * k); ldsm4t(b, aB + 128 * k);
                    if (!(k & 1)) ldsm4t(c, aC + 128 * k);
                    const h2c x = cmul_cd(h2c{a[0], a[2]}, *(const __half2*)&zcs[k], *(const __half2*)&zds[k]), y = cmul_cd(h2c{a[1], a[3]}, *(const __half2*)&zcs[k], *(const __half2*)&zds[k]);
                    mma_h(acc[0], a[0], a[1], a[2], a[3], b[0], b[1]);
                    mma_h(acc[1], a[0], a[1], a[2], a[3], b[2], b[3]);
                    mma_h(acc[2], a[0], a[1], a[2], a[3], c[2 * (k & 1)], c[2 * (k & 1) + 1]);
                    mma_h(acc[3], x.re, y.re, x.im, y.im, b[0], b[1]);
                    mma_h(acc[4], x.re, y.re, x.im, y.im, b[2], b[3]);
                    mma_h(acc[5], x.re, y.re, x.im, y.im, c[2 * (k & 1)], c[2 * (k & 1) + 1]);
                }
                asm volatile("" :: "f"(acc[0][0]), "f"(acc[1][0]), "f"(acc[2][0]), "f"(acc[3][0]), "f"(acc[4][0]), "f"(acc[5][0]) : "memory");
            }
            __syncwarp();
            ar = ar1; ai = ai1; W = W1;
        }
        if (threadIdx.x < 32) TSTAMP(21);
        const float i0 = __uint_as_float((ex + 243u) << 23);
        if (half) {
#pragma unroll
            for (int a = 0; a < 6; a++) sts128(wb + a * 512, __float_as_uint(acc[a][0] * i0), __float_as_uint(acc[a][1] * i0), __float_as_uint(acc[a][2] * i0), __float_as_uint(acc[a][3] * i0));
            bar_arrive(barid, 64);
        } else {
            bar_sync(barid, 64);
            const uint32_t src = fresh(pstage) + lane * 16;
#pragma unroll
            for (int a = 0; a < 6; a++) {
                const uint4 y = lds128(src + a * 512);
                float v0 = fmaf(acc[a][0], i0, __uint_as_float(y.x));
                if (a == 0 && lane == 0) v0 -= bf_lo(pD);
                w[2 * a] = pack_bf16(v0, fmaf(acc[a][1], i0, __uint_as_float(y.y)));
                w[2 * a + 1] = pack_bf16(fmaf(acc[a][2], i0, __uint_as_float(y.z)), fmaf(acc[a][3], i0, __uint_as_float(y.w)));
            }
        }
    }
}

__device__ __forceinline__ int swap01(int i) { return (i & ~3) | ((i & 1) << 1) | ((i >> 1) & 1); }
enum { BC_AUX = 0, BC_S = 5, BC_KG = 15 };

__device__ __forceinline__ void conv_aux(const Params& p, const CUtensorMap* mU, uint32_t sb, int aw, int lane, int bid, unsigned epoch) {
    const unsigned t0 = clock32();
    const int g = lane >> 2, t = lane & 3, mi = lane >> 3, r8 = lane & 7;
    const int rank = bid & 1, slab = bid >> 1;
    const uint32_t bar_y = sb + SC_MISC, bar_u = bar_y + 32, bar_v = bar_y + 40, bar_box = bar_y + 64 + 8 * aw, s_bm = bar_y + 128;
    if (lane == 0) {
        mbar_init(bar_box, 1); mbar_fence();
        mbar_expect(bar_box, 4096);
        if (UDELAY) until(t0, UDELAY);
        tma4d(sb + SC_RT + 4096 * aw, mU, 16 * slab, 0, 0, 16 * rank + 2 * aw, bar_box);
        mbar_init(bar_y + 8 * aw, aw < 4 ? 9 : aw == 5 ? 8 : 1); mbar_fence();
        if (aw < 5) mbar_expect(bar_y + 8 * aw, aw == 4 ? 16384 : 4096);
    }
    __syncwarp();
    asm volatile("barrier.cluster.arrive.relaxed.aligned;" ::: "memory");
    asm volatile("setmaxnreg.dec.sync.aligned.u32 88;");
    const uint32_t ut = sb + SC_UT + aw * UT_STRIDE;
    sts128(ut + (mi >> 1) * (SC_ST - SC_UT) + (mi & 1) * UT_HALF + r8 * 16, 0, 0, 0, 0);
    if (lane < 16) sts128(s_bm + lane * 16, 0, 0, 0, 0);
    {
        const uint32_t dst = sb + SC_UT + swap01(g) * UT_STRIDE + (8 + 64 * rank + 8 * aw + t) * 16;
        const uint32_t rdst = mapa(dst, rank ^ 1), rbar = mapa(bar_u, rank ^ 1);
        asm volatile("barrier.cluster.wait.acquire.aligned;" ::: "memory");
        mbar_wait(bar_box);
        if (aw == 0) TSTAMP(1);
        const uint32_t src = fresh(sb + SC_RT) + aw * 4096 + (8 * mi + 4 * (r8 & 1) + (r8 >> 1)) * 32 + ((rank ^ (r8 & 1)) << 4);
        uint32_t x[8][4];
#pragma unroll
        for (int i = 0; i < 4; i++) { ldsm4t(x[i], src + 1024 * i); ldsm4t(x[4 + i], (src ^ 16) + 1024 * i); }
        asm volatile("" :: "r"(x[0][0]), "r"(x[1][0]), "r"(x[2][0]), "r"(x[3][0]) : "memory");
#pragma unroll
        for (int i = 0; i < 4; i++) st_async128(rdst + (i & 1) * UT_HALF + 32 * (i & 2), x[4 + i][0], x[4 + i][1], x[4 + i][2], x[4 + i][3], rbar);
#pragma unroll
        for (int i = 0; i < 4; i++) sts128(dst + (i & 1) * UT_HALF + 32 * (i & 2), x[i][0], x[i][1], x[i][2], x[i][3]);
    }
    bar_sync(BC_AUX, 256);
    mbar_wait_cluster(bar_u);
    if (aw == 0) TSTAMP(2);
    {
        const uint32_t a = fresh(ut) + (mi & 1) * UT_HALF + (64 * (mi >> 1) + r8) * 16;
        uint4 v = lds128(a);
#pragma unroll
        for (int i = 1; i <= 8; i++) {
            const uint4 w = lds128(a + 128 * i);
            sts128(a + 128 * i + (SC_ST - SC_UT), badd2(v.x, w.x), badd2(v.y, w.y), badd2(v.z, w.z), badd2(v.w, w.w));
            v = w;
        }
    }
    bar_arrive(BC_S + aw, 64);
    if (aw == 0) TSTAMP(3);
#pragma unroll 1
    for (int k = aw; k < 26; k += 8) {
        if (k - aw == 8) {
            bar_sync(BC_KG, 384);
            if (lane < 16) sts128(sb + SC_V + aw * V_STRIDE + lane * 16, 0, 0, 0, 0);
        }
        const int c = (k < 13 ? 0 : 4) + t, a = 8 * (k < 13 ? k : k - 13) + g;
        if (a < 97) window_task(fresh(sb + SC_UT) + c * UT_STRIDE, sb + SC_V + c * V_STRIDE, a, a < 64);
        __syncwarp();
    }
    if (aw == 0) TSTAMP(9);
    {
        {
            const uint32_t par = (epoch & 1) ? 0x80008000u : 0u;
            uint4 v;
            for (int it = 0;; it++) {
                v = ld_rlx128(p.s->gate + 256 * aw + 8 * lane);
                v.x ^= par; v.y ^= par; v.z ^= par; v.w ^= par;
                if (__all_sync(0xffffffffu, (v.x & v.y & v.z & v.w & 0x80008000u) == 0x80008000u)) break;
                if (it > (1 << 20)) __trap();
            }
            sts128(sb + SC_GT + (lane & 1) * UT_HALF + (8 + 16 * aw + (lane >> 1)) * 16, v.x, v.y, v.z, v.w);
        }
        __syncwarp();
        if (lane == 0) { mbar_arrive(bar_v); prefetch_map(mU + 6); }
        next_epoch(p, epoch);
        if (aw == 0) TSTAMP(4);
        if (aw == 7) {
            const int row = key_row(wait_sel(p, slab >> 1, r8, key_tag(epoch)));
            if (lane < 8) asm volatile("red.shared.or.b32 [%0], %1;" :: "r"(s_bm + (row >> 5) * 4), "r"(1u << (row & 31)) : "memory");
            TSTAMP(10);
        }
        bar_sync(BC_AUX, 256);
        const uint32_t src = sb + SC_RT + ((r8 >> 1) & 1) * Y_RS + (2 * mi + (r8 & 1)) * Y_CS + (2 * aw + (r8 >> 2)) * 16;
        const int L = 2 * aw + (t >> 1);
        const int row0 = 256 * rank + 128 * (g >> 2) + 32 * (L & 3) + 16 * (g & 1) + 8 * ((g >> 1) & 1) + (L >> 2);
        __nv_bfloat16* outp = p.out + (size_t)row0 * DM + 16 * slab + 8 * (t & 1);
        const uint32_t stg = sb + SC_ST + 4096 * aw, so = (g >> 1) * 256 + (t >> 1) * 64 + (g & 1) * 32 + (t & 1) * 16;
#pragma unroll 1
        for (int s = 0; s < 4; s++) {
            const uint32_t bm = lds32(fresh(s_bm) + (16 * s + (row0 >> 5)) * 4) >> (row0 & 31);
            const bool routed = __any_sync(0xffffffffu, bm & 0x11u) || s >= LASTS;
            mbar_wait_cluster(bar_y + 8 * s);
            const uint32_t sf = fresh(src) + 512 * s;
            uint32_t y[2][4];
            ldsm4t(y[0], sf); ldsm4t(y[1], sf + 256);
            if (routed) {
#pragma unroll
                for (int k = 0; k < 2; k++)
                    asm volatile("{ .reg .pred p; setp.ne.u32 p, %5, 0; @!p st.global.v4.u32 [%0], {%1,%2,%3,%4}; @p red.relaxed.gpu.global.add.noftz.v4.bf16x2 [%0], {%1,%2,%3,%4}; }"
                                 :: "l"(outp + (size_t)(512 * s + 4 * k) * DM), "r"(y[k][0]), "r"(y[k][1]), "r"(y[k][2]), "r"(y[k][3]), "r"(bm & (1u << (4 * k))) : "memory");
            } else {
                sts128(stg + so + 1024 * s, y[0][0], y[0][1], y[0][2], y[0][3]); sts128(stg + so + 1024 * s + 128, y[1][0], y[1][1], y[1][2], y[1][3]);
                asm volatile("fence.proxy.async.shared::cta;" ::: "memory");
                __syncwarp();
                if (lane == 0) asm volatile("cp.async.bulk.tensor.5d.global.shared::cta.bulk_group [%0, {%2, %3, %3, %3, %4}], [%1];"
                                            :: "l"(mU + 6), "r"(stg + 1024 * s), "r"(16 * slab), "r"(0), "r"(512 * s + 256 * rank + 64 * (aw & 1) + (aw >> 1)) : "memory");
            }
            if (aw == 0) TSTAMP(16 + s);
        }
        if (lane == 0) { asm volatile("cp.async.bulk.commit_group;" ::: "memory"); asm volatile("cp.async.bulk.wait_group.read 0;" ::: "memory"); }
        if (aw == 0) TFLUSH();
    }
}

__device__ __forceinline__ void conv_main(const Params& p, uint32_t sb, int warp, int lane, int bid, unsigned epoch, uint32_t (&w)[12]) {
    asm volatile("setmaxnreg.inc.sync.aligned.u32 168;");
    const int g = lane >> 2, t = lane & 3, mi = lane >> 3, r8 = lane & 7;
    const int rank = bid & 1;
    const uint32_t bar_y = sb + SC_MISC, bar_v = bar_y + 40;
    next_epoch(p, epoch);
    if (warp < 4) {
        asm volatile("" :: "r"(w[0]), "r"(w[2]), "r"(w[4]), "r"(w[6]), "r"(w[8]), "r"(w[10]) : "memory");
        bar_arrive(BC_KG, 384);
    } else {
        const uint4* src = p.s->kp + (4 * bid + warp - 4) * 128 + lane;
        for (int it = 0;; it++) {
            uint32_t bad = 0;
#pragma unroll
            for (int i = 0; i < 4; i++) { const uint4 v = ld_rlx128(src + 32 * i); w[3 * i] = v.x; w[3 * i + 1] = v.y; w[3 * i + 2] = v.z; bad |= v.w ^ ~epoch; }
            const bool ok = __all_sync(0xffffffffu, bad == 0);
            if (ok) break;
            if (it > (1 << 20)) __trap();
        }
    }
    if ((warp & 3) == 0) TSTAMP(5 + (warp >> 2));
    {
        const uint32_t kt = sb + SC_KT + warp * KT_BYTES;
        const uint32_t kd = sb + SC_KD + warp * 1024 + 16;
#pragma unroll
        for (int nu = 0; nu < 3; nu++) {
            uint32_t a, a0, de, dr;
            if (nu == 0) { a = kd + (8 * g + 2 * (t & 1) + (t >> 1)) * 2; de = 8; dr = 128; a0 = a; }
            else if (nu == 1) { a = t < 2 ? kd + (256 + 4 * g + t) * 2 : kt + KT_C * 4 + (64 * t - 100 + 2 * g) * 2; de = t < 2 ? 4 : 2; dr = t < 2 ? 64 : 32; a0 = a; }
            else {
                a = t < 2 ? kt + KT_D * 4 + (13 + 64 * t + g) * 2 : kd + 800; de = 64; dr = 16; a0 = a;
                if ((lane & 29) == 0) a0 = kt + (t ? KT_D * 4 + 141 * 2 : KT_C * 4 + 156 * 2);
            }
#pragma unroll
            for (int i = 0; i < 4; i++) {
                const uint32_t v = w[6 * (i >> 1) + 2 * nu + (i & 1)];
                sts16(i ? a + i * dr : a0, v); sts16(a + i * dr + de, v >> 16);
            }
        }
        if (lane == 0) sts128(kt + (KT_T + 2) * 4, 0, w[4] & 0xffffu, __byte_perm(w[4], 0, 0x1010), w[4] << 16);
        __syncwarp();
        const uint32_t kf = fresh(kd), d = kt + (16 + 8 * lane) * 4;
        auto put = [&](uint32_t d, uint32_t pv, uint32_t w0, uint32_t w1, uint32_t w2, uint32_t w3) {
            sts128(d, __byte_perm(w0, pv, 0x5410), __byte_perm(w0, 0, 0x1032), __byte_perm(w1, w0, 0x7610), __byte_perm(w1, 0, 0x1032));
            sts128(d + 16, __byte_perm(w2, w1, 0x7610), __byte_perm(w2, 0, 0x1032), __byte_perm(w3, w2, 0x7610), __byte_perm(w3, 0, 0x1032));
        };
        const uint32_t pv = lds16(kf + (lane ? 16 * lane : 512) - 2);
        const uint4 x = lds128(kf + 16 * lane);
        const uint2 v = lds64(kf + 512 + 8 * lane);
        const uint32_t c4 = lds16(lane == 31 ? fresh(kt) + KT_C * 4 + 28 * 2 : kf + 520 + 8 * lane);
        put(d, lane ? pv : 0, x.x, x.y, x.z, x.w);
        uint32_t w3 = __byte_perm(v.y, c4, 0x5432);
        if (lane == 31) w3 = bsub2(w3, __byte_perm(c4, 0, 0x1010));
        put(d + 1024, lane ? v.x : pv, __byte_perm(v.x, 0, 0x1010), __byte_perm(v.x, v.y, 0x5432), __byte_perm(v.y, 0, 0x1010), w3);
    }
    asm volatile("barrier.cluster.wait.acquire.aligned;" ::: "memory");
    bar_sync(BC_S + swap01(warp), 64);
    if ((warp & 3) == 0) TSTAMP(7 + (warp >> 2));
    {
        const uint32_t ut = fresh(sb + SC_UT) + swap01(warp) * UT_STRIDE, kt = fresh(sb + SC_KT) + warp * KT_BYTES;
        uint32_t u1 = ut + (mi & 1) * UT_HALF + (8 + r8) * 16 + (mi >> 1) * 128;
        auto dup = [&](uint32_t v) { return v ^ p.zero; };
        uint32_t kp = kt + (16 + g - 2 * t) * 4;
        float acc[16][4];
        {
            const uint32_t c0 = lds32(kp + 2048), c1 = lds32(kp + 2080), c2 = lds32(kp + 2016), c3 = dup(c0);
            const uint32_t e0 = lds32(kp + (KT_T - 16) * 4), e1 = lds32(kp + (KT_T - 8) * 4), e2 = lds32(kp + (KT_T - 24) * 4), e3 = dup(e0);
            const uint32_t f0 = dup(e1), f1 = lds32(kp + KT_T * 4);
            const uint32_t uo = ut + UT_HALF + (7 + lane) * 16;
#pragma unroll
            for (int i = 0; i < 16; i++) { acc[i][0] = acc[i][1] = acc[i][2] = acc[i][3] = 0.f; }
#pragma unroll
            for (int mu = 0; mu < 8; mu += 4) {
                uint32_t b[4];
                ldsm4(b, uo + 128 * mu);
#pragma unroll
                for (int k = 0; k < 4; k++) mma_bf8(acc[mu + 8 + k], f0, f1, b[k]);
            }
#pragma unroll
            for (int mu = 0; mu < 12; mu += 2) {
                uint32_t b[4];
                ldsm4(b, u1 + 128 * mu);
                mma_bf(acc[mu + 4], c0, c1, c2, c3, b[0], b[1]);
                mma_bf(acc[mu + 5], c0, c1, c2, c3, b[2], b[3]);
                if (mu < 8) { mma_bf(acc[mu + 8], e0, e1, e2, e3, b[0], b[1]); mma_bf(acc[mu + 9], e0, e1, e2, e3, b[2], b[3]); }
            }
        }
        {
            float M[8][4];
#pragma unroll
            for (int i = 0; i < 8; i++) { M[i][0] = M[i][1] = M[i][2] = M[i][3] = 0.f; }
            uint32_t up = u1 + (mi >> 1) * 128, s[8][4], a3[4];
            auto frag = [&](uint32_t (&a)[4], uint32_t x) { a[0] = lds32(x); a[1] = lds32(x + 32); a[2] = lds32(x - 32); a[3] = dup(a[0]); };
            frag(a3, kp + 1536);
#pragma unroll
            for (int i = 0; i < 8; i++) ldsm4(s[i], u1 + (SC_ST - SC_UT) + 256 * i);
            __syncwarp();
#pragma unroll 1
            for (int j0 = 0; j0 < 8; j0++) {
                uint32_t a2[4], a1[4], a0[4], b[4][4];
                frag(a2, kp + 1024);
#pragma unroll
                for (int i = 0; i < 4; i++) ldsm4(b[i], up + 512 * i);
                frag(a1, kp + 512); frag(a0, kp);
                kp += 64; u1 -= 16; up -= 16;
#pragma unroll
                for (int i = 0; i < 7; i++) mma_bf(acc[2 * i + 2], a3[0], a3[1], a3[2], a3[3], s[i][0], s[i][1]);
#pragma unroll
                for (int e = 0; e < 4; e++) a3[e] = bsub2(a2[e], a3[e]);
#pragma unroll
                for (int i = 0; i < 7; i++) mma_bf(acc[2 * i + 3], a2[0], a2[1], a2[2], a2[3], s[i][2], s[i][3]);
#pragma unroll
                for (int i = 0; i < 7; i++) mma_bf(M[i + 1], a3[0], a3[1], a3[2], a3[3], b[i >> 1][2 * (i & 1)], b[i >> 1][2 * (i & 1) + 1]);
                frag(a3, kp + 1536);
#pragma unroll
                for (int i = 0; i < 8; i++) mma_bf(acc[2 * i], a1[0], a1[1], a1[2], a1[3], s[i][0], s[i][1]);
#pragma unroll
                for (int e = 0; e < 4; e++) a1[e] = bsub2(a0[e], a1[e]);
#pragma unroll
                for (int i = 0; i < 8; i++) { mma_bf(acc[2 * i + 1], a0[0], a0[1], a0[2], a0[3], s[i][2], s[i][3]); ldsm4(s[i], u1 + (SC_ST - SC_UT) + 256 * i); }
#pragma unroll
                for (int i = 0; i < 8; i++) mma_bf(M[i], a1[0], a1[1], a1[2], a1[3], b[i >> 1][2 * (i & 1)], b[i >> 1][2 * (i & 1) + 1]);
            }
            u1 = dup(u1) + 128;
#pragma unroll
            for (int i = 0; i < 8; i++)
#pragma unroll
                for (int c = 0; c < 4; c++) { acc[2 * i][c] += M[i][c]; acc[2 * i + 1][c] -= M[i][c]; }
        }
        if ((warp & 3) == 0) TSTAMP(11 + (warp >> 2));
        mbar_wait(bar_v);
        const uint32_t vt = fresh(sb + SC_V) + swap01(warp) * V_STRIDE;
        const uint32_t g1 = fresh(u1) - ut + sb + SC_GT;
        const uint32_t ydst = sb + SC_RT + rank * Y_RS + warp * Y_CS + lane * 16;
        const uint32_t ydr = mapa(ydst, rank ^ 1), ybr = mapa(bar_y, rank ^ 1);
        auto stairs = [&](auto R) {
        uint32_t ug[2][2][4];
        auto ld_ug = [&](int i) { ldsm4t(ug[i & 1][0], u1 + 256 * i); ldsm4t(ug[i & 1][1], g1 + 256 * i); };
        auto ship = [&](int i) {
            const uint32_t (&u)[4] = ug[i & 1][0], (&gg)[4] = ug[i & 1][1];
            const uint32_t y0 = gmix(gg[0], acc[2 * i][0], acc[2 * i][1], u[0]), y1 = gmix(gg[1], acc[2 * i][2], acc[2 * i][3], u[1]);
            const uint32_t y2 = gmix(gg[2], acc[2 * i + 1][0], acc[2 * i + 1][1], u[2]), y3 = gmix(gg[3], acc[2 * i + 1][2], acc[2 * i + 1][3], u[3]);
            if ((i & 1) != R.value) st_async128(ydr + 512 * (i >> 1), y0, y1, y2, y3, ybr + 8 * (i >> 1));
            else asm volatile("{ .reg .pred q; setp.eq.u32 q, %6, 0; st.shared.v4.u32 [%0], {%2,%3,%4,%5}; bar.warp.sync 0xffffffff; @q mbarrier.arrive.shared::cta.b64 _, [%1]; }"
                              :: "r"(ydst + 512 * (i >> 1)), "r"(bar_y + 8 * (i >> 1)), "r"(y0), "r"(y1), "r"(y2), "r"(y3), "r"(lane) : "memory");
        };
        const uint32_t VD = vt + (VC_OFF - 400 - 16 * t) * 4 + (8 * g ^ 16 * (-t & 2)), VD2 = vt + (VC_OFF - 415 - 16 * t) * 4 + (8 * g ^ 16 * (~t & 2));
        uint2 bd[10];
        uint32_t x[2][4][4];
        auto ld4 = [&](uint32_t (&v)[4], int dl) { const uint2 w = lds64(VD + 256 * dl); v[0] = w.x; v[1] = w.y; v[2] = lds32(VD2 + 256 * dl); v[3] = dup(w.x); };
        auto mm4 = [&](const uint32_t (&v)[4], int dl) {
#pragma unroll
            for (int s = dl & 1; s < 10; s += 2) if ((dl + s) / 2 < 16) mma_bf(acc[(dl + s) / 2], v[0], v[1], v[2], v[3], bd[s].x, bd[s].y);
        };
        const uint32_t KE = kt + (KT_D + g + t) * 4, VE = vt + (VE_BASE - 912 - 16 * t) * 4 + (8 * g ^ 16 * (~t & 2));
        uint32_t b0[8], b1[8];
        auto ld8 = [&](uint32_t (&v)[4], int dl) { const uint2 w = lds64(VE + 512 * dl), z = lds64(VE + 512 * dl - 256); v[0] = w.x; v[1] = w.y; v[2] = z.x; v[3] = z.y; };
        auto mm8 = [&](const uint32_t (&v)[4], int dl, int lo, int hi) {
#pragma unroll
            for (int s = 0; s < 8; s++) if (dl + s >= lo && dl + s < hi) mma_bf(acc[dl + s], v[0], v[1], v[2], v[3], b0[s], b1[s]);
        };
        ld_ug(0); ld4(x[0][0], 6);
#pragma unroll
        for (int s = 0; s < 10; s++) bd[s] = lds64(kt + (KT_C + 2 * g + 2 * t + 8 * s) * 4);
        ld_ug(1);
        ship(0);
        mm4(x[0][0], 6);
        uint32_t e[4][4];
#pragma unroll
        for (int k = 1; k < 6; k++) {
#pragma unroll
            for (int j = 0; j < 4; j++) ld4(x[k & 1][j], 4 * k + 3 + j);
            ld_ug(k + 1);
            if (k == 3) {
#pragma unroll
                for (int s = 0; s < 8; s++) { b0[s] = lds32(KE + 32 * s); b1[s] = lds32(KE + 32 * s + 16); }
            }
            ship(k);
#pragma unroll
            for (int j = 0; j < 4; j++) {
                mm4(x[k & 1][j], 4 * k + 3 + j);
                if (k == 3) { uint32_t v[4], z[4]; ld8(e[j], 8 + j); ld8(v, 12 + j); ld4(z, 30 - j); mm8(v, 12 + j, 12, 16); mm8(e[j], 8 + j, 8, 12); mm4(z, 30 - j); }
                if (k == 5) { ld8(e[j], 8 + j + p.zero); mm8(e[j], 8 + j, 12, 16); }
            }
        }
        ld_ug(7);
        ship(7 - R.value); ship(6 + R.value);
        };
        if (rank) stairs(std::integral_constant<int, 1>()); else stairs(std::integral_constant<int, 0>());
        if ((warp & 3) == 0) TSTAMP(14 + (warp >> 2)); else TSTAMP(21 + warp);
    }
}

constexpr int SF_WD = 147456;
constexpr int SF_H = 81920;
constexpr int SF_RED = 131072;
constexpr int SF_XS = 221184;
constexpr int SF_MISC = SF_XS + 8 * 1168;
constexpr int SF_KG = SF_MISC - 10 * KG_STAGE;
constexpr int SF_WR = SF_KG - 2304;
constexpr int FB_X = 64, FB_RDONE = 72, FB_FREE = 80, FB_KDONE = 88, FB_KEYS = 96, FB_W = 112, FB_D = FB_W + 72, FB_H = FB_D + 96, FS_PART = 512, FS_TOK = 896;
enum { BAR_F = 6, BAR_R = 7, BAR_GU = 8, BAR_RED = 9 };
static_assert(NPRE <= 10 && SF_KG % 128 == 0 && SF_KG >= 7 * 24576 && SF_WR - 4 * 9216 >= 5 * 24576 && SF_WR - 6 * 9216 >= 5 * 16384, "layout");

__device__ __forceinline__ void ffn_front(const Params& p, const CUtensorMap* maps, uint32_t sb, int warp, int lane, int f, unsigned epoch) {
    const unsigned t0 = clock32();
    const int g = lane >> 2, t = lane & 3, mi = lane >> 3, r8 = lane & 7;
    const bool isx = f < NX;
    const int nrw = f < 8 ? 6 : 4, r0 = f < 8 ? 48 * f : 128 + 32 * f;
    const int rw = warp < 12 ? 13 - warp : warp ^ (warp < 14 ? 10 : 15);
    const uint32_t bar_row = sb + SF_MISC  , bar_x = bar_row + FB_X;
    const uint32_t s_part = bar_row + FS_PART  , s_tok = bar_row + FS_TOK  ;
    const uint32_t rows = sb + SF_WR - 9216 * (rw + 1);
    if (lane == 0) {
        mbar_init(bar_row + 8 * rw, 1); mbar_fence();
        if (rw < nrw) { mbar_expect(bar_row + 8 * rw, 9216); until(t0, RDELAY); bulk_g2s(rows, p.u + (size_t)(r0 + 8 * rw) * DM, 9216, bar_row + 8 * rw); }
        else if (rw >= 6) { mbar_expect(bar_row + 8 * rw, 1152); bulk_g2s(sb + SF_WR + (rw & 1) * 1152, (rw & 1) ? p.gatew : p.wr, 1152, bar_row + 8 * rw); }
        if (warp >= 10) {
#pragma unroll 1
            for (int i = warp - 10; i < 39; i += 6) mbar_init(bar_x + 8 * i, i == 1 ? nrw : i == 2 ? 4 : 1);
        }
        mbar_fence();
    }
    const int ks0 = isx ? 4 * f : 6 * f - 72, nt = isx ? 4 : 6;
    if (warp == 13) {
        stg128(p.s->keys + (lane >> 1) * 128 + 2 * f + (lane & 1), 0, 0, 0, 0);
        if (lane < 8 && isx && !(f & 1)) st_rlx32(&p.s->sel[32 * f + lane], 0);
    }
    __syncwarp();
    bar_sync(BAR_F, f < 12 ? 256 : 192);
    bar_arrive(0, NTHR);
    if (warp == 15) TSTAMP(1);

    if (warp == 12) {
        if (lane == 0) {
            const CUtensorMap* m = maps + (isx ? 1 : 3);
            prefetch_map(m); prefetch_map(m + 1);
            unsigned tb = t0 + WDELAY;
#pragma unroll 1
            for (int n = 0; n < 18; n++) {
                if (n == NPRE) { mbar_wait(bar_row + FB_KEYS); tb = clock32(); }
                until(tb, 0); tb += WGAP;
                const uint32_t b = bar_row + FB_W + 8 * (n >> 1);
                if (!(n & 1)) mbar_expect(b, nt * 4096);
                tma3d(sb + n * nt * 2048, m + (n & 1), 0, 64 * (n >> 1), ks0 >> 1, b);
            }
            TSTAMP(12);
            if (isx) {
                prefetch_map(maps + 5);
#pragma unroll 1
                for (int n = 0; n < 12; n++) {
                    until(tb, 0); tb += DGAP;
                    if (n == 6) mbar_wait(bar_row + FB_FREE);
                    mbar_expect(bar_row + FB_D + 8 * n, 12288);
                    tma2d(sb + (n < 6 ? SF_WD : -6 * 12288) + n * 12288, maps + 5, 32 * (f >> 1), 2304 * (f & 1) + 192 * n, bar_row + FB_D + 8 * n);
                }
                TSTAMP(13);
            }
        }
    } else if (warp == 13) {
        const uint32_t tag = key_tag(epoch), par = (epoch & 1) ? 0u : 0x8000u;
        next_epoch(p, epoch);
        bar_sync(BAR_R, 32 * (nrw + 1));
        TSTAMP(3);
        uint32_t k[16];
        const uint2 va = lds64(fresh(s_part) + lane * 8), vb = lds64(fresh(s_part) + 256 + lane * 8);
        const bool two = nrw > 4 && lane < 16;
        {
            auto mk = [&](uint32_t r, int row) { const uint32_t rb = pack_bf16(0.f, __uint_as_float(r)); return (rb ^ (((int)rb >> 31) & 0x7fff0000u) ^ 0x80000000u) | tag | (uint32_t)(2047 - row); };
            uint32_t ka = mk(va.x, r0 + lane), kb = two ? mk(vb.x, r0 + 32 + lane) : 0;
#pragma unroll 1
            for (int h = 0; h < 2; h++)
#pragma unroll
                for (int r = 0; r < 4; r++) {
                    const uint32_t m = __reduce_max_sync(0xffffffffu, max(ka, kb));
                    if (ka == m) ka = 0;
                    if (kb == m) kb = 0;
                    if ((lane & 1) == h) k[r] = m;
                }
        }
        asm volatile("st.relaxed.gpu.global.v4.u32 [%0], {%1,%2,%3,%4};" :: "l"(p.s->keys + (lane >> 1) * 128 + 2 * f + (lane & 1)), "r"(k[0]), "r"(k[1]), "r"(k[2]), "r"(k[3]) : "memory");
        TSTAMP(4);
        {
            const uint32_t gb = pack_bf16(sigmoidf_(rbf(__uint_as_float(va.y))), sigmoidf_(rbf(__uint_as_float(vb.y)))) | par | (par << 16);
            asm volatile("st.relaxed.gpu.global.u16 [%0], %1;" :: "l"(p.s->gate + r0 + lane), "h"((unsigned short)gb) : "memory");
            if (two) asm volatile("st.relaxed.gpu.global.u16 [%0], %1;" :: "l"(p.s->gate + r0 + 32 + lane), "h"((unsigned short)(gb >> 16)) : "memory");
        }
        const uint4* src = p.s->keys + (f & 15) * 128 + lane;
        for (int it = 0;; it++) {
            uint32_t bad = 0;
#pragma unroll
            for (int i = 0; i < 4; i++) {
                const uint4 x = ld_rlx128(src + (i < 3 || lane < 24 ? 32 * i : 64));
                k[i] = x.x; k[4 + i] = x.y; k[8 + i] = x.z; k[12 + i] = x.w;
                bad |= x.x ^ tag;
            }
            const bool ok = __all_sync(0xffffffffu, (bad & 0xf800u) == 0);
            if (it < 8) TSTAMP(it < 4 ? 16 + it : 20 + it);
            if (ok) break;
            if (it > (1 << 20)) __trap();
        }
        TSTAMP(5);
        mbar_wait(bar_row + FB_KDONE);
        if (lane == 0) { mbar_arrive(bar_row + FB_KEYS); mbar_expect(bar_x, 8 * 1152); }
        uint32_t key = 0;
#pragma unroll 1
        for (int r = 0; r < 8; r++) {
            const uint32_t m = __reduce_max_sync(0xffffffffu, max(max(k[0], k[1]), max(k[2], k[3])));
#pragma unroll
            for (int i = 0; i < 4; i++) {
                const bool pop = k[i] == m;
                k[i] = pop ? k[4 + i] : k[i]; k[4 + i] = pop ? k[8 + i] : k[4 + i]; k[8 + i] = pop ? k[12 + i] : k[8 + i]; k[12 + i] = pop ? 0 : k[12 + i];
            }
            if (lane == 0) bulk_g2s(sb + SF_XS + r * 1168, p.u + (size_t)key_row(m) * DM, 1152, bar_x);
            if (r8 == r) key = m;
        }
        const int row = key_row(key);
        TSTAMP(6);
        if (isx) {
            if (!(f & 1)) {
                __nv_bfloat16* o = p.out + (size_t)row * DM + 16 * f + 8 * mi;
                asm volatile("st.relaxed.gpu.global.v4.u32 [%0], {%1,%1,%1,%1};" :: "l"(o), "r"(0) : "memory");
                if (__any_sync(0xffffffffu, ld_rlx32(o) != 0)) __trap();
                if (lane < 8) st_rlx32(&p.s->sel[32 * f + lane], key);
            } else wait_sel(p, f >> 1, r8, tag);
            uint32_t gb;
            for (int it = 0;; it++) {
                asm volatile("ld.relaxed.gpu.global.u16 %0, [%1];" : "=r"(gb) : "l"(p.s->gate + row) : "memory");
                gb ^= par;
                if (!(gb & 0x8000u)) break;
                if (it > (1 << 20)) __trap();
            }
            const uint32_t rb = key ^ 0x80000000u, rv = (rb ^ (((int)rb >> 31) & 0x7fff0000u)) & 0xffff0000u;
            sts64(s_tok + r8 * 8, row, __float_as_uint(rbf(1.0f - bf_lo(gb)) * rbf(sigmoidf_(__uint_as_float(rv)))));
            __syncwarp();
            TSTAMP(7);
            bar_arrive(BAR_RED, 416);
        }
    } else {
        if (rw < nrw) {
            float c[2][4];
#pragma unroll
            for (int i = 0; i < 2; i++) { c[i][0] = c[i][1] = c[i][2] = c[i][3] = 0.f; }
            mbar_wait(bar_row + 48); mbar_wait(bar_row + 56);
            const uint32_t b = fresh(sb + SF_WR) + (g & 1) * 1152 + (g >> 2) * 64 + t * 16 + (g & 2) * 2;
            uint32_t w[18][2];
#pragma unroll
            for (int kb = 0; kb < 18; kb++) { const uint32_t o = ((kb & 1) ? b ^ 64 : b) + 128 * (kb >> 1); w[kb][0] = lds32(o); w[kb][1] = lds32(o + 8); }
            mbar_wait(bar_row + 8 * rw);
            if (warp == 15) TSTAMP(2);
            const uint32_t a = fresh(rows) + g * 1152 + (g & 1) * 64 + t * 16;
#pragma unroll
            for (int kb = 0; kb < 18; kb++) {
                const uint4 x = lds128(((kb & 1) ? a ^ 64 : a) + 128 * (kb >> 1));
                mma_bf(c[kb & 1], x.x, x.y, x.z, x.w, w[kb][0], w[kb][1]);
            }
            const float sr = c[0][0] + c[1][0] + __shfl_down_sync(0xffffffffu, c[0][2] + c[1][2], 1);
            const float sg = c[0][1] + c[1][1] + __shfl_down_sync(0xffffffffu, c[0][3] + c[1][3], 1);
            if (t == 2 * (g & 1)) sts64(s_part + (8 * rw + g) * 8, __float_as_uint(sr), __float_as_uint(sg));
            __syncwarp();
            bar_arrive(BAR_R, 32 * (nrw + 1));
        }
    }
}

__device__ __forceinline__ void ffn_work(const Params& p, uint32_t sb, int warp, int lane, int f, unsigned epoch) {
    const int g = lane >> 2, t = lane & 3, mi = lane >> 3, r8 = lane & 7;
    const bool isx = f < NX;
    const int ks0 = isx ? 4 * f : 6 * f - 72, nt = isx ? 4 : 6;
    const uint32_t bar_x = sb + SF_MISC + FB_X, bar_free = sb + SF_MISC + FB_FREE, bar_w = sb + SF_MISC + FB_W, bar_d = sb + SF_MISC + FB_D, bar_h = sb + SF_MISC + FB_H, s_tok = sb + SF_MISC + FS_TOK;
    next_epoch(p, epoch);
    {
        if (warp < nt) {
            float ag[2][4], au[2][4];
#pragma unroll
            for (int i = 0; i < 2; i++) { ag[i][0] = ag[i][1] = ag[i][2] = ag[i][3] = 0.f; au[i][0] = au[i][1] = au[i][2] = au[i][3] = 0.f; }
            const uint32_t wb = sb + (warp >> 1) * 4096 + (r8 + 8 * (mi >> 1)) * 64 + (((2 * (warp & 1) + (mi & 1)) ^ (r8 >> 1)) << 4);
            const uint32_t xb = sb + SF_XS + r8 * 1168 + mi * 16;
            mbar_wait(bar_x);
            if (warp == 0) TSTAMP(8);
#pragma unroll 1
            for (int n = 0; n < 9; n++) {
                mbar_wait(bar_w + 8 * n);
                const uint32_t wk = fresh(wb) + n * nt * 4096, xk = fresh(xb) + 128 * n;
                uint32_t x[4];
#pragma unroll
                for (int s = 0; s < 4; s++) {
                    uint32_t a[4], b[4];
                    if (!(s & 1)) ldsm4(x, xk + 32 * s);
                    ldsm4t(a, wk + 1024 * s); ldsm4t(b, wk + 1024 * s + nt * 2048);
                    mma_bf(ag[s & 1], a[0], a[1], a[2], a[3], x[2 * (s & 1)], x[2 * (s & 1) + 1]);
                    mma_bf(au[s & 1], b[0], b[1], b[2], b[3], x[2 * (s & 1)], x[2 * (s & 1) + 1]);
                }
                asm volatile("" :: "f"(ag[0][0]), "f"(ag[1][0]), "f"(au[0][0]), "f"(au[1][0]) : "memory");
                if (n == 4 && lane == 0 && isx) mbar_arrive(bar_free);
            }
            if (warp == 0) TSTAMP(9);
            float h[4];
#pragma unroll
            for (int c = 0; c < 4; c++) {
                const float gv = rbf(ag[0][c] + ag[1][c]);
                h[c] = rbf(gv * sigmoidf_(gv)) * rbf(au[0][c] + au[1][c]);
            }
            uint32_t h0, h1;
            asm("movmatrix.sync.aligned.m8n8.trans.b16 %0, %1;" : "=r"(h0) : "r"(pack_bf16(h[0], h[1])));
            asm("movmatrix.sync.aligned.m8n8.trans.b16 %0, %1;" : "=r"(h1) : "r"(pack_bf16(h[2], h[3])));
            if (h0 == 0) h0 = 0x8000u;
            asm volatile("{ .reg .b64 v; mov.b64 v, {%1, %2}; st.relaxed.gpu.global.b64 [%0], v; }" :: "l"(p.s->h + ((epoch & 1) * 288 + ks0 + warp) * 32 + lane), "r"(h0), "r"(h1) : "memory");
        }
        if (isx) {
            bar_sync(BAR_GU, 384);
            if (warp == 0) TSTAMP(10);
            uint2 hb[12];
            const uint32_t hs = sb + SF_H + warp * 3072;
            const uint2* hsrc = p.s->h + ((__shfl_sync(0xffffffffu, epoch, 0) & 1) * 288 + 144 * (f & 1) + 12 * warp) * 32;
            for (int it = 0;; it++) {
                if (lane == 0) { mbar_expect(bar_h + 8 * warp, 3072); bulk_g2s(hs, hsrc, 3072, bar_h + 8 * warp); }
                mbar_wait(bar_h + 8 * warp, it & 1);
                const uint32_t hf = fresh(hs) + lane * 8;
                uint32_t mn = 0xffffffffu;
#pragma unroll
                for (int s = 0; s < 12; s++) { hb[s] = lds64(hf + 256 * s); mn = min(mn, hb[s].x); }
                if (__all_sync(0xffffffffu, mn != 0)) break;
                if (it > (1 << 16)) __trap();
            }
            if (warp == 0) TSTAMP(11);
            mbar_wait(bar_d + 8 * warp);
            if (warp == 11) TSTAMP(14);
            float ad[2][2][4];
#pragma unroll
            for (int i = 0; i < 4; i++) { ad[i >> 1][i & 1][0] = ad[i >> 1][i & 1][1] = ad[i >> 1][i & 1][2] = ad[i >> 1][i & 1][3] = 0.f; }
            const uint32_t wd = fresh(sb) + (warp < 6 ? SF_WD : -6 * 12288) + warp * 12288 + (r8 + 8 * (mi >> 1)) * 64 + (((mi & 1) ^ (r8 >> 1)) << 4);
#pragma unroll
            for (int s = 0; s < 12; s++) {
                uint32_t a[4], b[4];
                ldsm4t(a, wd + 1024 * s); ldsm4t(b, (wd ^ 32) + 1024 * s);
                mma_bf(ad[0][s & 1], a[0], a[1], a[2], a[3], hb[s].x, hb[s].y);
                mma_bf(ad[1][s & 1], b[0], b[1], b[2], b[3], hb[s].x, hb[s].y);
            }
            const uint32_t rd = sb + SF_RED + warp * 1152 + (72 * t + g) * 4;
#pragma unroll
            for (int i = 0; i < 8; i++) sts32(rd + (i >> 2) * 64 + (i & 1) * 144 + ((i >> 1) & 1) * 32, __float_as_uint(ad[i >> 2][0][i & 3] + ad[i >> 2][1][i & 3]));
            bar_sync(BAR_RED, 416);
            if (warp < 4) {
                const int tid = 32 * warp + lane;
                const uint32_t rs = fresh(sb + SF_RED) + (tid >> 4) * 144 + (tid & 15) * 8;
                const uint2 tk = lds64(fresh(s_tok) + (tid >> 4) * 8);
                float x = 0.f, y = 0.f;
#pragma unroll
                for (int w = 0; w < 12; w++) { const uint2 v = lds64(rs + w * 1152); x += __uint_as_float(v.x); y += __uint_as_float(v.y); }
                asm volatile("red.relaxed.gpu.global.add.noftz.bf16x2 [%0], %1;" :: "l"(p.out + (size_t)tk.x * DM + 32 * (f >> 1) + 2 * (tid & 15)),
                             "r"(pack_bf16(x * __uint_as_float(tk.y), y * __uint_as_float(tk.y))) : "memory");
            }
            if (warp == 0) TSTAMP(15);
        }
        if (warp == 0) TFLUSH();
    }
}

constexpr int SMEM_BYTES = 232448;
static_assert(SF_MISC + 1024 <= 232192, "layout");

struct Maps { CUtensorMap m[7]; };

__global__ void __cluster_dims__(2, 1, 1) __launch_bounds__(NTHR, 1)
fused_kernel(const Params p, const __grid_constant__ Maps maps) {
    extern __shared__ __align__(1024) uint8_t smem_raw[];
    uint32_t q[8];
    {
        const int b = blockIdx.x, x = threadIdx.x, rc = 4 * b + max(b - 84, 0) - 288 + (x >> 6);
        const int cv = (b - NCONV) >> 31, ca = 8 * b + ((x >> 5) & 3), cb = 2 * rc - (rc & 3) + 4;
        const uint32_t ch = (ca & cv) | (cb & ~cv), o = NST * ch + 2 * ((x & 31) + ((x >> (cv & 2)) & 32));
        const bool c = x < (b < 84 ? 256 : 320);
        q[6] = ldg16_if(c, p.logdt + ch);
        q[2] = ldg32_if(c, p.Bre + o); q[3] = ldg32_if(c, p.Bim + o); q[4] = ldg32_if(c, p.Cre + o); q[5] = ldg32_if(c, p.Cim + o); q[0] = ldg32_if(c, p.Are + o); q[1] = ldg32_if(c, p.Aim + o);
        q[7] = ldg16_if(c, p.Dskip + ch);
    }
    const unsigned epoch = ld_rlx32(&p.s->epoch[blockIdx.x * 16 + (threadIdx.x >> 5)]);
    const uint32_t sb = __shfl_sync(0xffffffffu, smem_u32(smem_raw), 0);
    const int warp = __shfl_sync(0xffffffffu, threadIdx.x >> 5, 0), bid = __shfl_sync(0xffffffffu, blockIdx.x, 0);
    const int lane = __shfl_sync(0xffffffffu, threadIdx.x & 31, threadIdx.x);
    const bool conv = bid < NCONV;
    const int f = bid - NCONV;
    uint32_t w[12];
    if (warp < (f < 12 ? 8 : 10)) {
        const int half = conv ? warp >> 2 : warp & 1, pr = conv ? warp & 3 : warp >> 1;
        const int rc = 4 * f + max(f - 12, 0) + pr;
        const uint32_t stage = sb + (conv ? SC_KG : SF_KG) + warp * KG_STAGE;
        uint4* const kp = p.s->kp + rc * 128 + lane;
        kgen(q, sb, half, stage, stage + (conv ? 4 : 1) * KG_STAGE, 1 + pr, lane, w, [&] {
            const uint32_t a = sb + SC_KT + warp * KT_BYTES + lane * 16;
#pragma unroll
            for (int i = 0; i < 6; i++) sts128z_if(conv && lane < 30, a + 480 * i);
            stg128z_if(!conv, kp + 64 * half); stg128z_if(!conv, kp + 64 * half + 32);
            stg128z_if(!conv && warp < (f < NX ? 4 : 6), (uint4*)(p.s->h + ((lane >> 4) * 288 + (f < NX ? 4 * f : 6 * f - 72) + warp) * 32) + (lane & 15));
            if (conv) asm volatile("barrier.cluster.arrive.relaxed.aligned;" ::: "memory");
        });
        if (!conv) {
            if (!half) {
#pragma unroll
                for (int i = 0; i < 4; i++) asm volatile("st.relaxed.gpu.global.v4.u32 [%0], {%1,%2,%3,%4};" :: "l"(kp + 32 * i), "r"(w[3 * i]), "r"(w[3 * i + 1]), "r"(w[3 * i + 2]), "r"(~epoch) : "memory");
            }
            if (warp == 0) TSTAMP(22);
            if (warp == 2) TSTAMP(23);
            bar_sync(0, NTHR);
            if (warp == 0 && lane == 0) mbar_arrive(sb + SF_MISC + FB_KDONE);
        }
    } else if (conv) {
        conv_aux(p, maps.m, sb, warp - 8, lane, bid, epoch);
        return;
    } else {
        ffn_front(p, maps.m, sb, warp, lane, f, epoch);
        if (warp >= 12) return;
    }
    if (conv) conv_main(p, sb, warp, lane, bid, epoch, w);
    else ffn_work(p, sb, warp, lane, f, epoch);
}

typedef CUresult (*EncodeFn)(CUtensorMap*, CUtensorMapDataType, cuuint32_t, void*, const cuuint64_t*, const cuuint64_t*, const cuuint32_t*, const cuuint32_t*,
                             CUtensorMapInterleave, CUtensorMapSwizzle, CUtensorMapL2promotion, CUtensorMapFloatOOBfill);

void make_map(EncodeFn fn, CUtensorMap* m, const void* base, int rank, const cuuint64_t* dims, const cuuint64_t* strides, const cuuint32_t* box, CUtensorMapSwizzle sw) {
    const cuuint32_t es[5] = {1, 1, 1, 1, 1};
    fn(m, CU_TENSOR_MAP_DATA_TYPE_BFLOAT16, rank, (void*)base, dims, strides, box, es, CU_TENSOR_MAP_INTERLEAVE_NONE, sw,
       CU_TENSOR_MAP_L2_PROMOTION_NONE, CU_TENSOR_MAP_FLOAT_OOB_FILL_NONE);
}

}

extern "C" void kernel_launch(void* const* d_in, const int* in_sizes, int n_in, void* d_out, int out_size) {
    (void)in_sizes; (void)n_in; (void)out_size;
    static EncodeFn fn = nullptr;
    static void* scratch = nullptr;
    if (!fn) {
        void* ptr = nullptr; cudaDriverEntryPointQueryResult qr;
        cudaGetDriverEntryPoint("cuTensorMapEncodeTiled", &ptr, cudaEnableDefault, &qr);
        fn = (EncodeFn)ptr;
        cudaGetSymbolAddress(&scratch, g_scratch);
        cudaFuncSetAttribute(fused_kernel, cudaFuncAttributeMaxDynamicSharedMemorySize, SMEM_BYTES);
    }
    typedef const __nv_bfloat16* bp;
    Params p;
    p.u = (bp)d_in[0]; p.Are = (bp)d_in[1]; p.Aim = (bp)d_in[2]; p.Bre = (bp)d_in[3]; p.Bim = (bp)d_in[4]; p.Cre = (bp)d_in[5]; p.Cim = (bp)d_in[6];
    p.logdt = (bp)d_in[7]; p.Dskip = (bp)d_in[8]; p.wr = (bp)d_in[10]; p.gatew = (bp)d_in[14];
    p.out = (__nv_bfloat16*)d_out; p.s = (Scratch*)scratch; p.zero = 0;
    Maps maps;
    {
        const cuuint64_t dims[4] = {DM, 4, 16, 32}, strides[3] = {16 * DM * 2, DM * 2, 64 * DM * 2};
        const cuuint32_t box[4] = {16, 4, 16, 2};
        make_map(fn, &maps.m[0], d_in[0], 4, dims, strides, box, CU_TENSOR_MAP_SWIZZLE_32B);
    }
    for (int i = 0; i < 4; i++) {
        const cuuint64_t dims[3] = {32, DM, FF / 32}, strides[2] = {FF * 2, 64};
        const cuuint32_t box[3] = {32, 64, i < 2 ? 2u : 3u};
        make_map(fn, &maps.m[1 + i], d_in[11 + (i & 1)], 3, dims, strides, box, CU_TENSOR_MAP_SWIZZLE_64B);
    }
    {
        const cuuint64_t dims[2] = {DM, FF}, strides[1] = {DM * 2};
        const cuuint32_t box[2] = {32, 192};
        make_map(fn, &maps.m[5], d_in[13], 2, dims, strides, box, CU_TENSOR_MAP_SWIZZLE_64B);
    }
    {
        const cuuint64_t dims[5] = {DM, 4, 4, 2, L_SEQ}, strides[4] = {16 * DM * 2, 4 * DM * 2, 128 * DM * 2, DM * 2};
        const cuuint32_t box[5] = {16, 4, 4, 2, 1};
        make_map(fn, &maps.m[6], d_out, 5, dims, strides, box, CU_TENSOR_MAP_SWIZZLE_NONE);
    }
    fused_kernel<<<NCTA, NTHR, SMEM_BYTES>>>(p, maps);
}
```

```cpp
#include <cuda_runtime.h>
#include <cuda_bf16.h>
#include <cuda_fp16.h>
#include <cuda.h>
#include <stdint.h>
#include <type_traits>

#define LASTS 3
#define UDELAY 0
#define RDELAY 900
#define WDELAY 2200
#define WGAP 290
#define NPRE 6
#define DGAP 220

namespace {

constexpr int DM = 576, NST = 128, FF = 4608, L_SEQ = 2048;
constexpr int NCONV = 72, NX = 36, NFFN = 60, NCTA = 132, NTHR = 512;

struct __align__(128) Scratch {
    unsigned epoch[NCTA * 16];
    uint4 keys[16 * 128];
    uint32_t sel[18 * 64];
    uint16_t gate[L_SEQ];
    uint2 h[2 * 288 * 32];
    uint4 kp[288 * 128];
};
__device__ Scratch g_scratch;
#define TFLUSH()
#define TSTAMP(i)

struct Params {
    const __nv_bfloat16 *Are, *Aim, *Bre, *Bim, *Cre, *Cim, *logdt, *Dskip, *u, *wr, *gatew;
    __nv_bfloat16* out;
    Scratch* s;
    uint32_t zero;
};

__device__ __forceinline__ uint32_t smem_u32(const void* p) { return (uint32_t)__cvta_generic_to_shared(p); }
__device__ __forceinline__ uint32_t pack_bf16(float lo, float hi) { uint32_t r; asm("cvt.rn.bf16x2.f32 %0, %1, %2;" : "=r"(r) : "f"(hi), "f"(lo)); return r; }
__device__ __forceinline__ uint32_t pack_f16(float lo, float hi) { uint32_t r; asm("cvt.rn.f16x2.f32 %0, %1, %2;" : "=r"(r) : "f"(hi), "f"(lo)); return r; }
__device__ __forceinline__ float bf_lo(uint32_t w) { return __uint_as_float(w << 16); }
__device__ __forceinline__ float bf_hi(uint32_t w) { return __uint_as_float(w & 0xffff0000u); }
__device__ __forceinline__ float rbf(float x) { return bf_lo(pack_bf16(x, 0.f)); }
__device__ __forceinline__ uint32_t badd2(uint32_t a, uint32_t b) { uint32_t r; asm("add.rn.bf16x2 %0, %1, %2;" : "=r"(r) : "r"(a), "r"(b)); return r; }
__device__ __forceinline__ uint32_t bsub2(uint32_t a, uint32_t b) { uint32_t r; asm("sub.rn.bf16x2 %0, %1, %2;" : "=r"(r) : "r"(a), "r"(b)); return r; }
__device__ __forceinline__ uint32_t gmix(uint32_t ng, float ny0, float ny1, uint32_t u) {
    uint32_t r; asm("{ .reg .b32 t; fma.rn.bf16x2 t, %1, %3, %3; fma.rn.bf16x2 %0, %1, %2, t; }" : "=r"(r) : "r"(ng), "r"(pack_bf16(ny0, ny1)), "r"(u)); return r;
}
__device__ __forceinline__ void mma_bf(float (&c)[4], uint32_t a0, uint32_t a1, uint32_t a2, uint32_t a3, uint32_t b0, uint32_t b1) {
    asm("mma.sync.aligned.m16n8k16.row.col.f32.bf16.bf16.f32 {%0,%1,%2,%3}, {%4,%5,%6,%7}, {%8,%9}, {%0,%1,%2,%3};"
        : "+f"(c[0]), "+f"(c[1]), "+f"(c[2]), "+f"(c[3]) : "r"(a0), "r"(a1), "r"(a2), "r"(a3), "r"(b0), "r"(b1));
}
__device__ __forceinline__ void mma_bf8(float (&c)[4], uint32_t a0, uint32_t a1, uint32_t b0) {
    asm("mma.sync.aligned.m16n8k8.row.col.f32.bf16.bf16.f32 {%0,%1,%2,%3}, {%4,%5}, {%6}, {%0,%1,%2,%3};"
        : "+f"(c[0]), "+f"(c[1]), "+f"(c[2]), "+f"(c[3]) : "r"(a0), "r"(a1), "r"(b0));
}
__device__ __forceinline__ void mma_h(float (&c)[4], uint32_t a0, uint32_t a1, uint32_t a2, uint32_t a3, uint32_t b0, uint32_t b1) {
    asm("mma.sync.aligned.m16n8k16.row.col.f32.f16.f16.f32 {%0,%1,%2,%3}, {%4,%5,%6,%7}, {%8,%9}, {%0,%1,%2,%3};"
        : "+f"(c[0]), "+f"(c[1]), "+f"(c[2]), "+f"(c[3]) : "r"(a0), "r"(a1), "r"(a2), "r"(a3), "r"(b0), "r"(b1));
}
__device__ __forceinline__ uint32_t fresh(uint32_t a) { asm volatile("" : "+r"(a) :: "memory"); return a; }
__device__ __forceinline__ uint32_t lds16(uint32_t a) { uint32_t v; asm("ld.shared.u16 %0, [%1];" : "=r"(v) : "r"(a)); return v; }
__device__ __forceinline__ uint32_t lds32(uint32_t a) { uint32_t v; asm("ld.shared.u32 %0, [%1];" : "=r"(v) : "r"(a)); return v; }
__device__ __forceinline__ uint2 lds64(uint32_t a) { uint2 v; asm("ld.shared.v2.u32 {%0,%1}, [%2];" : "=r"(v.x), "=r"(v.y) : "r"(a)); return v; }
__device__ __forceinline__ uint4 lds128(uint32_t a) { uint4 v; asm("ld.shared.v4.u32 {%0,%1,%2,%3}, [%4];" : "=r"(v.x), "=r"(v.y), "=r"(v.z), "=r"(v.w) : "r"(a)); return v; }
__device__ __forceinline__ uint4 lds128v(uint32_t a) { uint4 v; asm volatile("ld.shared.v4.u32 {%0,%1,%2,%3}, [%4];" : "=r"(v.x), "=r"(v.y), "=r"(v.z), "=r"(v.w) : "r"(a) : "memory"); return v; }
__device__ __forceinline__ void ldsm4(uint32_t (&r)[4], uint32_t a) {
    asm("ldmatrix.sync.aligned.m8n8.x4.shared.b16 {%0,%1,%2,%3}, [%4];" : "=r"(r[0]), "=r"(r[1]), "=r"(r[2]), "=r"(r[3]) : "r"(a));
}
__device__ __forceinline__ void ldsm4t(uint32_t (&r)[4], uint32_t a) {
    asm("ldmatrix.sync.aligned.m8n8.x4.trans.shared.b16 {%0,%1,%2,%3}, [%4];" : "=r"(r[0]), "=r"(r[1]), "=r"(r[2]), "=r"(r[3]) : "r"(a));
}
__device__ __forceinline__ void sts16(uint32_t a, uint32_t v) { asm volatile("st.shared.u16 [%0], %1;" :: "r"(a), "h"((unsigned short)v) : "memory"); }
__device__ __forceinline__ void sts32(uint32_t a, uint32_t v) { asm volatile("st.shared.u32 [%0], %1;" :: "r"(a), "r"(v) : "memory"); }
__device__ __forceinline__ void sts64(uint32_t a, uint32_t x, uint32_t y) { asm volatile("st.shared.v2.u32 [%0], {%1,%2};" :: "r"(a), "r"(x), "r"(y) : "memory"); }
__device__ __forceinline__ void sts128(uint32_t a, uint32_t x, uint32_t y, uint32_t z, uint32_t w) {
    asm volatile("st.shared.v4.u32 [%0], {%1,%2,%3,%4};" :: "r"(a), "r"(x), "r"(y), "r"(z), "r"(w) : "memory");
}
__device__ __forceinline__ void st_async128(uint32_t a, uint32_t x, uint32_t y, uint32_t z, uint32_t w, uint32_t bar) {
    asm volatile("st.async.weak.shared::cluster.mbarrier::complete_tx::bytes.v4.b32 [%0], {%1,%2,%3,%4}, [%5];" :: "r"(a), "r"(x), "r"(y), "r"(z), "r"(w), "r"(bar) : "memory");
}
__device__ __forceinline__ void mbar_init(uint32_t b, uint32_t cnt) { asm volatile("mbarrier.init.shared::cta.b64 [%0], %1;" :: "r"(b), "r"(cnt) : "memory"); }
__device__ __forceinline__ void mbar_fence() { asm volatile("fence.mbarrier_init.release.cluster;" ::: "memory"); }
__device__ __forceinline__ void mbar_expect(uint32_t b, uint32_t bytes) { asm volatile("mbarrier.arrive.expect_tx.shared::cta.b64 _, [%0], %1;" :: "r"(b), "r"(bytes) : "memory"); }
__device__ __forceinline__ void mbar_arrive(uint32_t b) { asm volatile("mbarrier.arrive.shared::cta.b64 _, [%0];" :: "r"(b) : "memory"); }
#define CHINT ""
#define HINT ""
__device__ __forceinline__ void mbar_wait(uint32_t b, uint32_t parity = 0) {
    asm volatile("{ .reg .pred p; .reg .u32 n; mov.u32 n, 0;\n"
                 "LW: mbarrier.try_wait.parity.shared::cta.b64 p, [%0], %1" HINT "; @p bra LD; add.u32 n, n, 1; setp.lt.u32 p, n, 65536; @p bra LW; trap;\n"
                 "LD: }" :: "r"(b), "r"(parity) : "memory");
}
__device__ __forceinline__ void mbar_wait_cluster(uint32_t b) {
    asm volatile("{ .reg .pred p; .reg .u32 n; mov.u32 n, 0;\n"
                 "LW: mbarrier.try_wait.parity.acquire.cluster.shared::cta.b64 p, [%0], 0" CHINT "; @p bra LD; add.u32 n, n, 1; setp.lt.u32 p, n, 65536; @p bra LW; trap;\n"
                 "LD: }" :: "r"(b) : "memory");
}
__device__ __forceinline__ void tma2d(uint32_t dst, const CUtensorMap* m, int c0, int c1, uint32_t bar) {
    asm volatile("cp.async.bulk.tensor.2d.shared::cluster.global.mbarrier::complete_tx::bytes [%0], [%1, {%3, %4}], [%2];"
                 :: "r"(dst), "l"(m), "r"(bar), "r"(c0), "r"(c1) : "memory");
}
__device__ __forceinline__ void tma3d(uint32_t dst, const CUtensorMap* m, int c0, int c1, int c2, uint32_t bar) {
    asm volatile("cp.async.bulk.tensor.3d.shared::cluster.global.mbarrier::complete_tx::bytes [%0], [%1, {%3, %4, %5}], [%2];"
                 :: "r"(dst), "l"(m), "r"(bar), "r"(c0), "r"(c1), "r"(c2) : "memory");
}
__device__ __forceinline__ void tma4d(uint32_t dst, const CUtensorMap* m, int c0, int c1, int c2, int c3, uint32_t bar) {
    asm volatile("cp.async.bulk.tensor.4d.shared::cluster.global.mbarrier::complete_tx::bytes [%0], [%1, {%3, %4, %5, %6}], [%2];"
                 :: "r"(dst), "l"(m), "r"(bar), "r"(c0), "r"(c1), "r"(c2), "r"(c3) : "memory");
}
__device__ __forceinline__ void bulk_g2s(uint32_t dst, const void* src, uint32_t bytes, uint32_t bar) {
    asm volatile("cp.async.bulk.shared::cluster.global.mbarrier::complete_tx::bytes [%0], [%1], %2, [%3];"
                 :: "r"(dst), "l"(src), "r"(bytes), "r"(bar) : "memory");
}
__device__ __forceinline__ uint32_t mapa(uint32_t a, uint32_t rank) { uint32_t r; asm("mapa.shared::cluster.u32 %0, %1, %2;" : "=r"(r) : "r"(a), "r"(rank)); return r; }
__device__ __forceinline__ void prefetch_map(const CUtensorMap* m) { asm volatile("prefetch.tensormap [%0];" :: "l"(m) : "memory"); }
__device__ __forceinline__ void bar_sync(int id, int n) { asm volatile("bar.sync %0, %1;" :: "r"(id), "r"(n) : "memory"); }
__device__ __forceinline__ void bar_arrive(int id, int n) { asm volatile("bar.arrive %0, %1;" :: "r"(id), "r"(n) : "memory"); }
__device__ __forceinline__ uint32_t ldg16_if(bool c, const void* p) { uint32_t v; asm volatile("{ .reg .pred p; setp.ne.u32 p, %2, 0; @p ld.global.nc.u16 %0, [%1]; }" : "=r"(v) : "l"(p), "r"((uint32_t)c)); return v; }
__device__ __forceinline__ uint32_t ldg32_if(bool c, const void* p) { uint32_t v; asm volatile("{ .reg .pred p; setp.ne.u32 p, %2, 0; @p ld.global.nc.u32 %0, [%1]; }" : "=r"(v) : "l"(p), "r"((uint32_t)c)); return v; }
__device__ __forceinline__ uint32_t ld_rlx32(const void* p) { uint32_t v; asm volatile("ld.relaxed.gpu.global.u32 %0, [%1];" : "=r"(v) : "l"(p) : "memory"); return v; }
__device__ __forceinline__ uint4 ld_rlx128(const void* p) {
    uint4 v; asm volatile("ld.relaxed.gpu.global.v4.u32 {%0,%1,%2,%3}, [%4];" : "=r"(v.x), "=r"(v.y), "=r"(v.z), "=r"(v.w) : "l"(p) : "memory"); return v;
}
__device__ __forceinline__ void st_rlx32(void* p, uint32_t v) { asm volatile("st.relaxed.gpu.global.u32 [%0], %1;" :: "l"(p), "r"(v) : "memory"); }
__device__ __forceinline__ void stg128(void* p, uint32_t x, uint32_t y, uint32_t z, uint32_t w) {
    asm volatile("st.global.v4.u32 [%0], {%1,%2,%3,%4};" :: "l"(p), "r"(x), "r"(y), "r"(z), "r"(w) : "memory");
}
__device__ __forceinline__ void next_epoch(const Params& p, unsigned e) { if ((threadIdx.x & 31) == 0) p.s->epoch[blockIdx.x * 16 + (threadIdx.x >> 5)] = e + 1; }
__device__ __forceinline__ void sts128z_if(bool c, uint32_t a) { asm volatile("{ .reg .pred p; setp.ne.u32 p, %1, 0; @p st.shared.v4.u32 [%0], {%2,%2,%2,%2}; }" :: "r"(a), "r"((uint32_t)c), "r"(0) : "memory"); }
__device__ __forceinline__ void stg128z_if(bool c, void* a) { asm volatile("{ .reg .pred p; setp.ne.u32 p, %1, 0; @p st.global.v4.u32 [%0], {%2,%2,%2,%2}; }" :: "l"(a), "r"((uint32_t)c), "r"(0) : "memory"); }
__device__ __forceinline__ unsigned clock32() { unsigned c; asm volatile("mov.u32 %0, %clock;" : "=r"(c) :: "memory"); return c; }
__device__ __forceinline__ void until(unsigned t0, int c) { while ((int)(clock32() - t0) < c) { } }
__device__ __forceinline__ float sigmoidf_(float x) { return __fdividef(1.0f, 1.0f + __expf(-x)); }
__device__ __forceinline__ uint32_t key_tag(unsigned epoch) { return ((epoch & 15u) | 16u) << 11; }
__device__ __forceinline__ int key_row(uint32_t key) { return 2047 - (int)(key & 2047u); }
__device__ __forceinline__ uint32_t wait_sel(const Params& p, int s32, int r8, uint32_t tag) {
    uint32_t k;
    for (int it = 0;; it++) {
        k = ld_rlx32(&p.s->sel[s32 * 64 + r8]);
        if (__all_sync(0xffffffffu, (k & 0xf800u) == tag)) break;
        if (it > (1 << 20)) __trap();
    }
    return k;
}

struct cplx { float re, im; };
__device__ __forceinline__ cplx csq(cplx a) { cplx r; r.re = a.re * a.re - a.im * a.im; r.im = (a.re * a.im) * 2.f; return r; }
__device__ __forceinline__ cplx cexpk(float ar, float ai, float k) {
    float mag, s, c;
    asm("ex2.approx.ftz.f32 %0, %1;" : "=f"(mag) : "f"(ar * (k * 1.4426950408889634f)));
    const float r = ai * k;
    asm("sin.approx.ftz.f32 %0, %1;" : "=f"(s) : "f"(r));
    asm("cos.approx.ftz.f32 %0, %1;" : "=f"(c) : "f"(r));
    cplx o; o.re = mag * c; o.im = mag * s; return o;
}
struct h2c { uint32_t re, im; };
__device__ __forceinline__ h2c cmul_cd(h2c v, __half2 c, __half2 d) {
    const __half2 r = *(const __half2*)&v.re, i = *(const __half2*)&v.im;
    const __half2 x = __hfma2(__hneg2(i), d, __hmul2(r, c)), y = __hfma2(i, c, __hmul2(r, d));
    h2c o; o.re = *(const uint32_t*)&x; o.im = *(const uint32_t*)&y; return o;
}
__device__ __forceinline__ h2c cmul_s(h2c v, uint32_t s) { const __half2 h = *(const __half2*)&s; return cmul_cd(v, __low2half2(h), __high2half2(h)); }
__device__ __forceinline__ h2c cmul_sc(h2c v, uint32_t s) {
    const __half2 h = *(const __half2*)&s, c = __low2half2(h), d = __high2half2(h), r = *(const __half2*)&v.re, i = *(const __half2*)&v.im;
    const __half2 x = __hfma2(i, d, __hmul2(r, c)), y = __hfma2(__hneg2(r), d, __hmul2(i, c));
    h2c o; o.re = *(const uint32_t*)&x; o.im = *(const uint32_t*)&y; return o;
}
__device__ __forceinline__ h2c cmul_vc(h2c v, uint32_t s) {
    const __half2 h = *(const __half2*)&s, c = __low2half2(h), d = __high2half2(h), r = *(const __half2*)&v.re, i = *(const __half2*)&v.im;
    const __half2 x = __hfma2(i, d, __hmul2(r, c)), y = __hfma2(__hneg2(i), c, __hmul2(r, d));
    h2c o; o.re = *(const uint32_t*)&x; o.im = *(const uint32_t*)&y; return o;
}

constexpr int UT_HALF = 2240, UT_STRIDE = 4448;
constexpr int KT_T = 542, KT_C = 552, KT_D = 645, KT_BYTES = 720 * 4;
constexpr int VC_OFF = 80, VE_BASE = 1616;
constexpr int V_STRIDE = (1616 + 1024) * 4 + 80;
constexpr int KG_STAGE = 5248;
constexpr int Y_CS = 2080, Y_RS = 8 * Y_CS + 64;

constexpr int SC_RT = 0;
constexpr int SC_UT = 33408;
constexpr int SC_ST = SC_UT + 8 * UT_STRIDE;
constexpr int SC_KT = SC_ST + 8 * UT_STRIDE;
constexpr int SC_GT = SC_KT + 8 * KT_BYTES;
constexpr int SC_V = SC_GT + UT_STRIDE;
constexpr int SC_KG = SC_V + 4 * V_STRIDE;
constexpr int SC_MISC = SC_V + 8 * V_STRIDE;
static_assert(V_STRIDE % 128 == 16 && 8 * KG_STAGE <= 4 * V_STRIDE && 2 * Y_RS <= SC_UT && SC_UT % 128 == 0 && SC_ST % 128 == 0, "layout");
static_assert(SC_MISC % 16 == 0 && SC_MISC + 512 <= 232192, "layout");

__device__ __forceinline__ void window_task(uint32_t ut, uint32_t vt, int a, bool withE) {
    const uint32_t src = ut + (a + 6) * 16;
    float S[35];
    {
        uint32_t w[20];
#pragma unroll
        for (int i = 0; i < 5; i++) {
            const uint4 v = lds128(src + ((i & 1) ? 0 : UT_HALF) + ((i + 1) >> 1) * 16);
            w[4 * i] = v.x; w[4 * i + 1] = v.y; w[4 * i + 2] = v.z; w[4 * i + 3] = v.w;
        }
        float s = 0.f; S[2] = 0.f;
#pragma unroll
        for (int i = 3; i < 26; i++) { s += (i & 1) ? bf_hi(w[i >> 1]) : bf_lo(w[i >> 1]); S[i] = s; }
        const uint32_t d0 = vt + 64 * a + 16 * (a & 2), d1 = vt + 64 * a + 16 * (~a & 2);
#pragma unroll
        for (int i = 0; i < 8; i += 2)
            sts128((i & 4 ? d1 : d0) + (VC_OFF - 16) * 4 + 8 * (i & 2), pack_bf16(S[10 + i] - S[5 + i], S[5 + i] - S[2 + i]), pack_bf16(S[18 + i] - S[13 + i], S[13 + i] - S[10 + i]),
                   pack_bf16(S[11 + i] - S[6 + i], S[6 + i] - S[3 + i]), pack_bf16(S[19 + i] - S[14 + i], S[14 + i] - S[11 + i]));
        if (withE) {
#pragma unroll
            for (int i = 26; i < 35; i++) { s += (i & 1) ? bf_hi(w[i >> 1]) : bf_lo(w[i >> 1]); S[i] = s; }
#pragma unroll
            for (int i = 0; i < 8; i += 2)
                sts128((i & 4 ? d1 : d0) + VE_BASE * 4 + 8 * (i & 2), pack_bf16(S[19 + i] - S[12 + i], S[12 + i] - S[3 + i]), pack_bf16(S[27 + i] - S[20 + i], S[20 + i] - S[11 + i]),
                       pack_bf16(S[20 + i] - S[13 + i], S[13 + i] - S[4 + i]), pack_bf16(S[28 + i] - S[21 + i], S[21 + i] - S[12 + i]));
        }
    }
}

template <class F>
__device__ __forceinline__ void kgen(const uint32_t (&q)[8], uint32_t sb, int half, uint32_t stage, uint32_t pstage, int barid, int lane, uint32_t (&w)[12], F shadow) {
    const int t = lane & 3, mi = lane >> 3, r8 = lane & 7;
    {
        const uint32_t pAr = q[0], pAi = q[1], pBr = q[2], pBi = q[3], pCr = q[4], pCi = q[5], pDt = q[6], pD = q[7];
        const uint32_t wb = fresh(stage + lane * 16), za = fresh(stage + 5120 + ((lane >> 1) & 3) * 16 + mi * 4 + (lane & 1) * 2), zr = fresh(stage + 5120 + t * 16);
        const uint32_t oA = fresh(stage + (mi & 1) * 1024 + (mi >> 1) * 512 + r8 * 16), oB = fresh(stage + 2048 + mi * 512 + r8 * 16), oC = fresh(stage + 4096 + (mi & 1) * 512 + (mi >> 1) * 128 + r8 * 16);
        float acc[6][4];
#pragma unroll
        for (int a = 0; a < 6; a++) { acc[a][0] = acc[a][1] = acc[a][2] = acc[a][3] = 0.f; asm volatile("" : "+f"(acc[a][0]), "+f"(acc[a][1]), "+f"(acc[a][2]), "+f"(acc[a][3])); }
        shadow();
        sts32(zr, clock32());
        const float dt = rbf(__expf(bf_lo(pDt)));
        float ar = dt * bf_lo(pAr), ai = dt * bf_lo(pAi), ar1 = dt * bf_hi(pAr), ai1 = dt * bf_hi(pAi);
        float wr, wi, wr1, wi1;
        { const float br = dt * bf_lo(pBr), bi = dt * bf_lo(pBi), cr = bf_lo(pCr), ci = bf_lo(pCi); wr = cr * br - ci * bi; wi = cr * bi + ci * br; }
        { const float br = dt * bf_hi(pBr), bi = dt * bf_hi(pBi), cr = bf_hi(pCr), ci = bf_hi(pCi); wr1 = cr * br - ci * bi; wi1 = cr * bi + ci * br; }
        const uint32_t ex = max(__reduce_max_sync(0xffffffffu, __float_as_uint(fmaxf(fmaxf(fabsf(wr), fabsf(wi)), fmaxf(fabsf(wr1), fabsf(wi1))))) >> 23, 14u);
        const float scl = __uint_as_float((267u - ex) << 23);
        uint32_t W = pack_f16(wr * scl, wi * -scl);
        const uint32_t W1 = pack_f16(wr1 * scl, wi1 * -scl);
        if (threadIdx.x < 32) TSTAMP(20);

#pragma unroll 1
        for (int r = 0; r < 2; r++) {
            const cplx z1 = cexpk(ar, ai, 1.f), z64 = cexpk(ar, ai, 64.f);
            const cplx z2 = csq(z1), z4 = csq(z2), z8 = csq(z4), z16 = csq(z8), z32 = csq(z16);
            const cplx z128 = csq(z64), z256 = csq(z128), z512 = csq(z256);
            auto put = [&](int grp, h2c a, h2c b, h2c c, h2c d) { sts128(wb + grp * 1024, a.re, b.re, c.re, d.re); sts128(wb + grp * 1024 + 512, a.im, b.im, c.im, d.im); };
            {
                const uint32_t s4 = pack_f16(z4.re, z4.im), s256 = pack_f16(z256.re, z256.im), s512 = pack_f16(z512.re, z512.im);
                auto mix = [](h2c a, h2c b, uint32_t sel) { return h2c{__byte_perm(a.re, b.re, sel), __byte_perm(a.im, b.im, sel)}; };
                const h2c c10 = cmul_vc(h2c{pack_f16(z1.re, 1.f), pack_f16(z1.im, 0.f)}, W), c32 = cmul_sc(c10, pack_f16(z2.re, z2.im)), c54 = cmul_sc(c10, s4);
                put(2, c10, c32, c54, cmul_sc(c32, s4));
                const h2c d20 = cmul_sc(mix(c32, c10, 0x7632), s256), e04 = cmul_sc(mix(c10, c54, 0x7632), s512), f04 = cmul_sc(e04, s256);
                put(3, d20, cmul_sc(d20, s4), e04, f04);
                const h2c ef = mix(e04, f04, 0x5410), gh = cmul_sc(ef, s512), g8 = cmul_sc(gh, pack_f16(z8.re, z8.im));
                put(4, g8, cmul_sc(g8, s512), gh, ef);
            }
            {
                const uint32_t s32 = pack_f16(z32.re, z32.im), s64 = pack_f16(z64.re, z64.im), s128 = pack_f16(z128.re, z128.im);
                const h2c p0 = {pack_f16(1.f, z8.re), pack_f16(0.f, z8.im)}, p1 = cmul_s(p0, pack_f16(z16.re, z16.im)), p2 = cmul_s(p0, s32), p3 = cmul_s(p1, s32);
                put(0, p0, p1, p2, p3);
                put(1, cmul_s(p0, s64), cmul_s(p1, s64), cmul_s(p2, s64), cmul_s(p3, s64));
                sts16(za, s128); sts16(za + 64, s128 >> 16);
            }
            __syncwarp();
            {
                const uint32_t aA = fresh(oA), aB = fresh(oB), aC = fresh(oC), aZ = fresh(zr);
                const uint4 zc = lds128(aZ), zd = lds128(aZ + 64);
                const uint32_t zcs[4] = {zc.x, zc.y, zc.z, zc.w}, zds[4] = {zd.x, zd.y, zd.z, zd.w};
                uint32_t c[4];
#pragma unroll
                for (int k = 0; k < 4; k++) {
                    uint32_t a[4], b[4];
                    ldsm4t(a, aA + 128 * k); ldsm4t(b, aB + 128 * k);
                    if (!(k & 1)) ldsm4t(c, aC + 128 * k);
                    const h2c x = cmul_cd(h2c{a[0], a[2]}, *(const __half2*)&zcs[k], *(const __half2*)&zds[k]), y = cmul_cd(h2c{a[1], a[3]}, *(const __half2*)&zcs[k], *(const __half2*)&zds[k]);
                    mma_h(acc[0], a[0], a[1], a[2], a[3], b[0], b[1]);
                    mma_h(acc[1], a[0], a[1], a[2], a[3], b[2], b[3]);
                    mma_h(acc[2], a[0], a[1], a[2], a[3], c[2 * (k & 1)], c[2 * (k & 1) + 1]);
                    mma_h(acc[3], x.re, y.re, x.im, y.im, b[0], b[1]);
                    mma_h(acc[4], x.re, y.re, x.im, y.im, b[2], b[3]);
                    mma_h(acc[5], x.re, y.re, x.im, y.im, c[2 * (k & 1)], c[2 * (k & 1) + 1]);
                }
                asm volatile("" :: "f"(acc[0][0]), "f"(acc[1][0]), "f"(acc[2][0]), "f"(acc[3][0]), "f"(acc[4][0]), "f"(acc[5][0]) : "memory");
            }
            __syncwarp();
            ar = ar1; ai = ai1; W = W1;
        }
        if (threadIdx.x < 32) TSTAMP(21);
        const float i0 = __uint_as_float((ex + 243u) << 23);
        if (half) {
#pragma unroll
            for (int a = 0; a < 6; a++) sts128(wb + a * 512, __float_as_uint(acc[a][0]), __float_as_uint(acc[a][1]), __float_as_uint(acc[a][2]), __float_as_uint(acc[a][3]));
            sts32(stage + 3072, __float_as_uint(i0));
            bar_arrive(barid, 64);
        } else {
#pragma unroll
            for (int a = 0; a < 6; a++) { acc[a][0] *= i0; acc[a][1] *= i0; acc[a][2] *= i0; acc[a][3] *= i0; }
            if (lane == 0) acc[0][1] -= bf_lo(pD);
            sts32(zr, clock32());
            bar_sync(barid, 64);
            const uint32_t src = fresh(pstage);
            const float i1 = __uint_as_float(lds32(src + 3072));
#pragma unroll
            for (int a = 0; a < 6; a++) {
                const uint4 y = lds128(src + lane * 16 + a * 512);
                w[2 * a] = pack_bf16(fmaf(__uint_as_float(y.x), i1, acc[a][0]), fmaf(__uint_as_float(y.y), i1, acc[a][1]));
                w[2 * a + 1] = pack_bf16(fmaf(__uint_as_float(y.z), i1, acc[a][2]), fmaf(__uint_as_float(y.w), i1, acc[a][3]));
            }
        }
    }
}

__device__ __forceinline__ int swap01(int i) { return (i & ~3) | ((i & 1) << 1) | ((i >> 1) & 1); }
enum { BC_AUX = 0, BC_S = 5, BC_KG = 15 };

__device__ __forceinline__ void conv_aux(const Params& p, const CUtensorMap* mU, uint32_t sb, int aw, int lane, int bid, unsigned epoch) {
    const unsigned t0 = clock32();
    const int g = lane >> 2, t = lane & 3, mi = lane >> 3, r8 = lane & 7;
    const int rank = bid & 1, slab = bid >> 1;
    const uint32_t bar_y = sb + SC_MISC, bar_u = bar_y + 32, bar_v = bar_y + 40, bar_box = bar_y + 64 + 8 * aw, s_bm = bar_y + 128;
    if (lane == 0) {
        mbar_init(bar_box, 1); mbar_fence();
        mbar_expect(bar_box, 4096);
        if (UDELAY) until(t0, UDELAY);
        tma4d(sb + SC_RT + 4096 * aw, mU, 16 * slab, 0, 0, 16 * rank + 2 * aw, bar_box);
        mbar_init(bar_y + 8 * aw, aw < 4 ? 9 : aw == 5 ? 8 : 1); mbar_fence();
        if (aw < 5) mbar_expect(bar_y + 8 * aw, aw == 4 ? 16384 : 4096);
    }
    __syncwarp();
    asm volatile("barrier.cluster.arrive.relaxed.aligned;" ::: "memory");
    asm volatile("setmaxnreg.dec.sync.aligned.u32 88;");
    const uint32_t ut = sb + SC_UT + aw * UT_STRIDE;
    sts128(ut + (mi >> 1) * (SC_ST - SC_UT) + (mi & 1) * UT_HALF + r8 * 16, 0, 0, 0, 0);
    if (lane < 16) sts128(s_bm + lane * 16, 0, 0, 0, 0);
    {
        const uint32_t dst = sb + SC_UT + swap01(g) * UT_STRIDE + (8 + 64 * rank + 8 * aw + t) * 16;
        const uint32_t rdst = mapa(dst, rank ^ 1), rbar = mapa(bar_u, rank ^ 1);
        asm volatile("barrier.cluster.wait.acquire.aligned;" ::: "memory");
        mbar_wait(bar_box);
        if (aw == 0) TSTAMP(1);
        const uint32_t src = fresh(sb + SC_RT) + aw * 4096 + (8 * mi + 4 * (r8 & 1) + (r8 >> 1)) * 32 + ((rank ^ (r8 & 1)) << 4);
        uint32_t x[8][4];
#pragma unroll
        for (int i = 0; i < 4; i++) { ldsm4t(x[i], src + 1024 * i); ldsm4t(x[4 + i], (src ^ 16) + 1024 * i); }
        asm volatile("" :: "r"(x[0][0]), "r"(x[1][0]), "r"(x[2][0]), "r"(x[3][0]) : "memory");
#pragma unroll
        for (int i = 0; i < 4; i++) st_async128(rdst + (i & 1) * UT_HALF + 32 * (i & 2), x[4 + i][0], x[4 + i][1], x[4 + i][2], x[4 + i][3], rbar);
#pragma unroll
        for (int i = 0; i < 4; i++) sts128(dst + (i & 1) * UT_HALF + 32 * (i & 2), x[i][0], x[i][1], x[i][2], x[i][3]);
    }
    bar_sync(BC_AUX, 256);
    mbar_wait_cluster(bar_u);
    if (aw == 0) TSTAMP(2);
    {
        const uint32_t a = fresh(ut) + (mi & 1) * UT_HALF + (64 * (mi >> 1) + r8) * 16;
        uint4 v = lds128(a);
#pragma unroll
        for (int i = 1; i <= 8; i++) {
            const uint4 w = lds128(a + 128 * i);
            sts128(a + 128 * i + (SC_ST - SC_UT), badd2(v.x, w.x), badd2(v.y, w.y), badd2(v.z, w.z), badd2(v.w, w.w));
            v = w;
        }
    }
    bar_arrive(BC_S + aw, 64);
    if (aw == 0) TSTAMP(3);
#pragma unroll 1
    for (int k = aw; k < 26; k += 8) {
        if (k - aw == 8) {
            bar_sync(BC_KG, 384);
            if (lane < 16) sts128(sb + SC_V + aw * V_STRIDE + lane * 16, 0, 0, 0, 0);
        }
        const int c = (k < 13 ? 0 : 4) + t, a = 8 * (k < 13 ? k : k - 13) + g;
        if (a < 97) window_task(fresh(sb + SC_UT) + c * UT_STRIDE, sb + SC_V + c * V_STRIDE, a, a < 64);
        __syncwarp();
    }
    if (aw == 0) TSTAMP(9);
    {
        {
            const uint32_t par = (epoch & 1) ? 0x80008000u : 0u;
            uint4 v;
            for (int it = 0;; it++) {
                v = ld_rlx128(p.s->gate + 256 * aw + 8 * lane);
                v.x ^= par; v.y ^= par; v.z ^= par; v.w ^= par;
                if (__all_sync(0xffffffffu, (v.x & v.y & v.z & v.w & 0x80008000u) == 0x80008000u)) break;
                if (it > (1 << 20)) __trap();
            }
            sts128(sb + SC_GT + (lane & 1) * UT_HALF + (8 + 16 * aw + (lane >> 1)) * 16, v.x, v.y, v.z, v.w);
        }
        __syncwarp();
        if (lane == 0) { mbar_arrive(bar_v); prefetch_map(mU + 6); }
        next_epoch(p, epoch);
        if (aw == 0) TSTAMP(4);
        if (aw == 7) {
            const int row = key_row(wait_sel(p, slab >> 1, r8, key_tag(epoch)));
            if (lane < 8) asm volatile("red.shared.or.b32 [%0], %1;" :: "r"(s_bm + (row >> 5) * 4), "r"(1u << (row & 31)) : "memory");
            TSTAMP(10);
        }
        bar_sync(BC_AUX, 256);
        const uint32_t src = sb + SC_RT + ((r8 >> 1) & 1) * Y_RS + (2 * mi + (r8 & 1)) * Y_CS + (2 * aw + (r8 >> 2)) * 16;
        const int L = 2 * aw + (t >> 1);
        const int row0 = 256 * rank + 128 * (g >> 2) + 32 * (L & 3) + 16 * (g & 1) + 8 * ((g >> 1) & 1) + (L >> 2);
        __nv_bfloat16* outp = p.out + (size_t)row0 * DM + 16 * slab + 8 * (t & 1);
        const uint32_t stg = sb + SC_ST + 4096 * aw, so = (g >> 1) * 256 + (t >> 1) * 64 + (g & 1) * 32 + (t & 1) * 16;
#pragma unroll 1
        for (int s = 0; s < 4; s++) {
            const uint32_t bm = lds32(fresh(s_bm) + (16 * s + (row0 >> 5)) * 4) >> (row0 & 31);
            const bool routed = __any_sync(0xffffffffu, bm & 0x11u) || s >= LASTS;
            mbar_wait_cluster(bar_y + 8 * s);
            const uint32_t sf = fresh(src) + 512 * s;
            uint32_t y[2][4];
            ldsm4t(y[0], sf); ldsm4t(y[1], sf + 256);
            if (routed) {
#pragma unroll
                for (int k = 0; k < 2; k++)
                    asm volatile("{ .reg .pred p; setp.ne.u32 p, %5, 0; @!p st.global.v4.u32 [%0], {%1,%2,%3,%4}; @p red.relaxed.gpu.global.add.noftz.v4.bf16x2 [%0], {%1,%2,%3,%4}; }"
                                 :: "l"(outp + (size_t)(512 * s + 4 * k) * DM), "r"(y[k][0]), "r"(y[k][1]), "r"(y[k][2]), "r"(y[k][3]), "r"(bm & (1u << (4 * k))) : "memory");
            } else {
                sts128(stg + so + 1024 * s, y[0][0], y[0][1], y[0][2], y[0][3]); sts128(stg + so + 1024 * s + 128, y[1][0], y[1][1], y[1][2], y[1][3]);
                asm volatile("fence.proxy.async.shared::cta;" ::: "memory");
                __syncwarp();
                if (lane == 0) asm volatile("cp.async.bulk.tensor.5d.global.shared::cta.bulk_group [%0, {%2, %3, %3, %3, %4}], [%1];"
                                            :: "l"(mU + 6), "r"(stg + 1024 * s), "r"(16 * slab), "r"(0), "r"(512 * s + 256 * rank + 64 * (aw & 1) + (aw >> 1)) : "memory");
            }
            if (aw == 0) TSTAMP(16 + s);
        }
        if (lane == 0) { asm volatile("cp.async.bulk.commit_group;" ::: "memory"); asm volatile("cp.async.bulk.wait_group.read 0;" ::: "memory"); }
        if (aw == 0) TFLUSH();
    }
}

__device__ __forceinline__ void conv_main(const Params& p, uint32_t sb, int warp, int lane, int bid, unsigned epoch, uint32_t (&w)[12]) {
    asm volatile("setmaxnreg.inc.sync.aligned.u32 168;");
    const int g = lane >> 2, t = lane & 3, mi = lane >> 3, r8 = lane & 7;
    const int rank = bid & 1;
    const uint32_t bar_y = sb + SC_MISC, bar_v = bar_y + 40;
    next_epoch(p, epoch);
    if (warp < 4) {
        asm volatile("" :: "r"(w[0]), "r"(w[2]), "r"(w[4]), "r"(w[6]), "r"(w[8]), "r"(w[10]) : "memory");
        bar_arrive(BC_KG, 384);
    } else {
        const uint4* src = p.s->kp + (4 * bid + warp - 4) * 128 + lane;
        for (int it = 0;; it++) {
            uint32_t bad = 0;
#pragma unroll
            for (int i = 0; i < 4; i++) { const uint4 v = ld_rlx128(src + 32 * i); w[3 * i] = v.x; w[3 * i + 1] = v.y; w[3 * i + 2] = v.z; bad |= v.w ^ ~epoch; }
            const bool ok = __all_sync(0xffffffffu, bad == 0);
            if (ok) break;
            if (it > (1 << 20)) __trap();
        }
    }
    if ((warp & 3) == 0) TSTAMP(5 + (warp >> 2));
    {
        const uint32_t kt = sb + SC_KT + warp * KT_BYTES;
        uint32_t e[4], x[4], re[4], rx[4];
#pragma unroll
        for (int i = 0; i < 4; i++) {
            e[i] = w[6 * (i >> 1) + (i & 1)]; x[i] = w[6 * (i >> 1) + 2 + (i & 1)];
            re[i] = __shfl_sync(0xffffffffu, e[i], lane + 31);
            rx[i] = __shfl_sync(0xffffffffu, x[i], lane + (i == 0 && lane == 29 ? 5 : 1 + 2 * t));
        }
        asm volatile("stmatrix.sync.aligned.m8n8.x4.trans.shared.b16 [%0], {%1,%2,%3,%4};"
                     :: "r"(kt + (r8 < 4 ? (KT_D + 7) * 4 + 64 * r8 + 16 * mi : 716 * 4)), "r"(w[4]), "r"(w[5]), "r"(w[10]), "r"(w[11]) : "memory");
        if (lane == 2) {
            sts32(kt + (KT_C + 78) * 4, w[4] & 0xffffu);
            sts128(kt + (KT_T + 2) * 4, 0, w[4] & 0xffffu, __byte_perm(w[4], 0, 0x1010), w[4] << 16);
        }
        if (lane == 29) x[3] = bsub2(x[3], rx[0] & 0xffffu);
#pragma unroll
        for (int i = 0; i < 4; i++) {
            sts64(kt + (16 + 64 * i) * 4 + 8 * lane, __byte_perm(e[i], lane ? re[i] : i ? re[i - 1] : 0, 0x5432), e[i]);
            const uint32_t aa = __byte_perm(x[i], 0, 0x3232);
            if (t < 2) sts128(kt + (272 + 64 * i + 8 * g + 4 * t) * 4, i == 0 && lane == 0 ? __byte_perm(x[0], re[3], 0x5432) : aa, aa, x[i],
                              __byte_perm(lane != 29 ? rx[i] : i < 3 ? rx[(i + 1) & 3] : 0, x[i], 0x5432));
            else sts32(kt + (KT_C - 50 + 8 * i + 32 * t + g) * 4, x[i]);
        }
    }
    asm volatile("barrier.cluster.wait.acquire.aligned;" ::: "memory");
    bar_sync(BC_S + swap01(warp), 64);
    if ((warp & 3) == 0) TSTAMP(7 + (warp >> 2));
    {
        const uint32_t ut = fresh(sb + SC_UT) + swap01(warp) * UT_STRIDE, kt = fresh(sb + SC_KT) + warp * KT_BYTES;
        uint32_t u1 = ut + (mi & 1) * UT_HALF + (8 + r8) * 16 + (mi >> 1) * 128;
        auto dup = [&](uint32_t v) { return v ^ p.zero; };
        uint32_t kp = kt + (16 + g - 2 * t) * 4;
        float acc[16][4];
        {
            const uint32_t c0 = lds32(kp + 2048), c1 = lds32(kp + 2080), c2 = lds32(kp + 2016), c3 = dup(c0);
            const uint32_t e0 = lds32(kp + (KT_T - 16) * 4), e1 = lds32(kp + (KT_T - 8) * 4), e2 = lds32(kp + (KT_T - 24) * 4), e3 = dup(e0);
            const uint32_t f0 = dup(e1), f1 = lds32(kp + KT_T * 4);
            const uint32_t uo = ut + UT_HALF + (7 + lane) * 16;
#pragma unroll
            for (int i = 0; i < 16; i++) { acc[i][0] = acc[i][1] = acc[i][2] = acc[i][3] = 0.f; }
#pragma unroll
            for (int mu = 0; mu < 8; mu += 4) {
                uint32_t b[4];
                ldsm4(b, uo + 128 * mu);
#pragma unroll
                for (int k = 0; k < 4; k++) mma_bf8(acc[mu + 8 + k], f0, f1, b[k]);
            }
#pragma unroll
            for (int mu = 0; mu < 12; mu += 2) {
                uint32_t b[4];
                ldsm4(b, u1 + 128 * mu);
                mma_bf(acc[mu + 4], c0, c1, c2, c3, b[0], b[1]);
                mma_bf(acc[mu + 5], c0, c1, c2, c3, b[2], b[3]);
                if (mu < 8) { mma_bf(acc[mu + 8], e0, e1, e2, e3, b[0], b[1]); mma_bf(acc[mu + 9], e0, e1, e2, e3, b[2], b[3]); }
            }
        }
        {
            float M[8][4];
#pragma unroll
            for (int i = 0; i < 8; i++) { M[i][0] = M[i][1] = M[i][2] = M[i][3] = 0.f; }
            uint32_t up = u1 + (mi >> 1) * 128, s[8][4], a3[4];
            auto frag = [&](uint32_t (&a)[4], uint32_t x) { a[0] = lds32(x); a[1] = lds32(x + 32); a[2] = lds32(x - 32); a[3] = dup(a[0]); };
            frag(a3, kp + 1536);
#pragma unroll
            for (int i = 0; i < 8; i++) ldsm4(s[i], u1 + (SC_ST - SC_UT) + 256 * i);
            __syncwarp();
#pragma unroll 1
            for (int j0 = 0; j0 < 8; j0++) {
                uint32_t a2[4], a1[4], a0[4], b[4][4];
                frag(a2, kp + 1024);
#pragma unroll
                for (int i = 0; i < 4; i++) ldsm4(b[i], up + 512 * i);
                frag(a1, kp + 512); frag(a0, kp);
                kp += 64; u1 -= 16; up -= 16;
#pragma unroll
                for (int i = 0; i < 7; i++) mma_bf(acc[2 * i + 2], a3[0], a3[1], a3[2], a3[3], s[i][0], s[i][1]);
#pragma unroll
                for (int e = 0; e < 4; e++) a3[e] = bsub2(a2[e], a3[e]);
#pragma unroll
                for (int i = 0; i < 7; i++) mma_bf(acc[2 * i + 3], a2[0], a2[1], a2[2], a2[3], s[i][2], s[i][3]);
#pragma unroll
                for (int i = 0; i < 7; i++) mma_bf(M[i + 1], a3[0], a3[1], a3[2], a3[3], b[i >> 1][2 * (i & 1)], b[i >> 1][2 * (i & 1) + 1]);
                frag(a3, kp + 1536);
#pragma unroll
                for (int i = 0; i < 8; i++) mma_bf(acc[2 * i], a1[0], a1[1], a1[2], a1[3], s[i][0], s[i][1]);
#pragma unroll
                for (int e = 0; e < 4; e++) a1[e] = bsub2(a0[e], a1[e]);
#pragma unroll
                for (int i = 0; i < 8; i++) { mma_bf(acc[2 * i + 1], a0[0], a0[1], a0[2], a0[3], s[i][2], s[i][3]); ldsm4(s[i], u1 + (SC_ST - SC_UT) + 256 * i); }
#pragma unroll
                for (int i = 0; i < 8; i++) mma_bf(M[i], a1[0], a1[1], a1[2], a1[3], b[i >> 1][2 * (i & 1)], b[i >> 1][2 * (i & 1) + 1]);
            }
            u1 = dup(u1) + 128;
#pragma unroll
            for (int i = 0; i < 8; i++)
#pragma unroll
                for (int c = 0; c < 4; c++) { acc[2 * i][c] += M[i][c]; acc[2 * i + 1][c] -= M[i][c]; }
        }
        if ((warp & 3) == 0) TSTAMP(11 + (warp >> 2));
        mbar_wait(bar_v);
        const uint32_t vt = fresh(sb + SC_V) + swap01(warp) * V_STRIDE;
        const uint32_t g1 = fresh(u1) - ut + sb + SC_GT;
        const uint32_t ydst = sb + SC_RT + rank * Y_RS + warp * Y_CS + lane * 16;
        const uint32_t ydr = mapa(ydst, rank ^ 1), ybr = mapa(bar_y, rank ^ 1);
        auto stairs = [&](auto R) {
        uint32_t ug[2][2][4];
        auto ld_ug = [&](int i) { ldsm4t(ug[i & 1][0], u1 + 256 * i); ldsm4t(ug[i & 1][1], g1 + 256 * i); };
        auto ship = [&](int i) {
            const uint32_t (&u)[4] = ug[i & 1][0], (&gg)[4] = ug[i & 1][1];
            const uint32_t y0 = gmix(gg[0], acc[2 * i][0], acc[2 * i][1], u[0]), y1 = gmix(gg[1], acc[2 * i][2], acc[2 * i][3], u[1]);
            const uint32_t y2 = gmix(gg[2], acc[2 * i + 1][0], acc[2 * i + 1][1], u[2]), y3 = gmix(gg[3], acc[2 * i + 1][2], acc[2 * i + 1][3], u[3]);
            if ((i & 1) != R.value) st_async128(ydr + 512 * (i >> 1), y0, y1, y2, y3, ybr + 8 * (i >> 1));
            else asm volatile("{ .reg .pred q; setp.eq.u32 q, %6, 0; st.shared.v4.u32 [%0], {%2,%3,%4,%5}; bar.warp.sync 0xffffffff; @q mbarrier.arrive.shared::cta.b64 _, [%1]; }"
                              :: "r"(ydst + 512 * (i >> 1)), "r"(bar_y + 8 * (i >> 1)), "r"(y0), "r"(y1), "r"(y2), "r"(y3), "r"(lane) : "memory");
        };
        const uint32_t VD = vt + (VC_OFF - 400 - 16 * t) * 4 + (8 * g ^ 16 * (-t & 2)), VD2 = vt + (VC_OFF - 415 - 16 * t) * 4 + (8 * g ^ 16 * (~t & 2));
        uint2 bd[10];
        uint32_t x[2][4][4];
        auto ld4 = [&](uint32_t (&v)[4], int dl) { const uint2 w = lds64(VD + 256 * dl); v[0] = w.x; v[1] = w.y; v[2] = lds32(VD2 + 256 * dl); v[3] = dup(w.x); };
        auto mm4 = [&](const uint32_t (&v)[4], int dl) {
#pragma unroll
            for (int s = dl & 1; s < 10; s += 2) if ((dl + s) / 2 < 16) mma_bf(acc[(dl + s) / 2], v[0], v[1], v[2], v[3], bd[s].x, bd[s].y);
        };
        const uint32_t KE = kt + (KT_D + g + t) * 4, VE = vt + (VE_BASE - 912 - 16 * t) * 4 + (8 * g ^ 16 * (~t & 2));
        uint32_t b0[8], b1[8];
        auto ld8 = [&](uint32_t (&v)[4], int dl) { const uint2 w = lds64(VE + 512 * dl), z = lds64(VE + 512 * dl - 256); v[0] = w.x; v[1] = w.y; v[2] = z.x; v[3] = z.y; };
        auto mm8 = [&](const uint32_t (&v)[4], int dl, int lo, int hi) {
#pragma unroll
            for (int s = 0; s < 8; s++) if (dl + s >= lo && dl + s < hi) mma_bf(acc[dl + s], v[0], v[1], v[2], v[3], b0[s], b1[s]);
        };
        ld_ug(0); ld4(x[0][0], 6);
#pragma unroll
        for (int s = 0; s < 10; s++) bd[s] = lds64(kt + (KT_C + 2 * g + 2 * t + 8 * s) * 4);
        ld_ug(1);
        ship(0);
        mm4(x[0][0], 6);
        uint32_t e[4][4];
#pragma unroll
        for (int k = 1; k < 6; k++) {
#pragma unroll
            for (int j = 0; j < 4; j++) ld4(x[k & 1][j], 4 * k + 3 + j);
            ld_ug(k + 1);
            if (k == 3) {
#pragma unroll
                for (int s = 0; s < 8; s++) { b0[s] = lds32(KE + 32 * s); b1[s] = lds32(KE + 32 * s + 16); }
            }
            ship(k);
#pragma unroll
            for (int j = 0; j < 4; j++) {
                mm4(x[k & 1][j], 4 * k + 3 + j);
                if (k == 3) { uint32_t v[4], z[4]; ld8(e[j], 8 + j); ld8(v, 12 + j); ld4(z, 30 - j); mm8(v, 12 + j, 12, 16); mm8(e[j], 8 + j, 8, 12); mm4(z, 30 - j); }
                if (k == 5) { ld8(e[j], 8 + j + p.zero); mm8(e[j], 8 + j, 12, 16); }
            }
        }
        ld_ug(7);
        ship(7 - R.value); ship(6 + R.value);
        };
        if (rank) stairs(std::integral_constant<int, 1>()); else stairs(std::integral_constant<int, 0>());
        if ((warp & 3) == 0) TSTAMP(14 + (warp >> 2)); else TSTAMP(21 + warp);
    }
}

constexpr int SF_WD = 147456;
constexpr int SF_H = 81920;
constexpr int SF_RED = 131072;
constexpr int SF_XS = 221184;
constexpr int SF_MISC = SF_XS + 8 * 1168;
constexpr int SF_KG = SF_MISC - 10 * KG_STAGE;
constexpr int SF_WR = SF_KG - 2304;
constexpr int FB_X = 64, FB_RDONE = 72, FB_FREE = 80, FB_KDONE = 88, FB_KEYS = 96, FB_W = 112, FB_D = FB_W + 72, FB_H = FB_D + 96, FS_PART = 512, FS_TOK = 896;
enum { BAR_F = 6, BAR_R = 7, BAR_GU = 8, BAR_RED = 9 };
static_assert(NPRE <= 10 && SF_KG % 128 == 0 && SF_KG >= 7 * 24576 && SF_WR - 4 * 9216 >= 5 * 24576 && SF_WR - 6 * 9216 >= 5 * 16384, "layout");

__device__ __forceinline__ void ffn_front(const Params& p, const CUtensorMap* maps, uint32_t sb, int warp, int lane, int f, unsigned epoch) {
    const unsigned t0 = clock32();
    const int g = lane >> 2, t = lane & 3, mi = lane >> 3, r8 = lane & 7;
    const bool isx = f < NX;
    const int nrw = f < 8 ? 6 : 4, r0 = f < 8 ? 48 * f : 128 + 32 * f;
    const int rw = warp < 12 ? 13 - warp : warp ^ (warp < 14 ? 10 : 15);
    const uint32_t bar_row = sb + SF_MISC  , bar_x = bar_row + FB_X;
    const uint32_t s_part = bar_row + FS_PART  , s_tok = bar_row + FS_TOK  ;
    const uint32_t rows = sb + SF_WR - 9216 * (rw + 1);
    if (lane == 0) {
        mbar_init(bar_row + 8 * rw, 1); mbar_fence();
        if (rw < nrw) { mbar_expect(bar_row + 8 * rw, 9216); until(t0, RDELAY); bulk_g2s(rows, p.u + (size_t)(r0 + 8 * rw) * DM, 9216, bar_row + 8 * rw); }
        else if (rw >= 6) { mbar_expect(bar_row + 8 * rw, 1152); bulk_g2s(sb + SF_WR + (rw & 1) * 1152, (rw & 1) ? p.gatew : p.wr, 1152, bar_row + 8 * rw); }
        if (warp >= 10) {
#pragma unroll 1
            for (int i = warp - 10; i < 39; i += 6) mbar_init(bar_x + 8 * i, i == 1 ? nrw : i == 2 ? 4 : 1);
        }
        mbar_fence();
    }
    const int ks0 = isx ? 4 * f : 6 * f - 72, nt = isx ? 4 : 6;
    if (warp == 13) {
        stg128(p.s->keys + (lane >> 1) * 128 + 2 * f + (lane & 1), 0, 0, 0, 0);
        if (lane < 8 && isx && !(f & 1)) st_rlx32(&p.s->sel[32 * f + lane], 0);
    }
    __syncwarp();
    bar_sync(BAR_F, f < 12 ? 256 : 192);
    bar_arrive(0, NTHR);
    if (warp == 15) TSTAMP(1);

    if (warp == 12) {
        if (lane == 0) {
            const CUtensorMap* m = maps + (isx ? 1 : 3);
            prefetch_map(m); prefetch_map(m + 1);
            unsigned tb = t0 + WDELAY;
#pragma unroll 1
            for (int n = 0; n < 18; n++) {
                if (n == NPRE) { mbar_wait(bar_row + FB_KEYS); tb = clock32(); }
                until(tb, 0); tb += WGAP;
                const uint32_t b = bar_row + FB_W + 8 * (n >> 1);
                if (!(n & 1)) mbar_expect(b, nt * 4096);
                tma3d(sb + n * nt * 2048, m + (n & 1), 0, 64 * (n >> 1), ks0 >> 1, b);
            }
            TSTAMP(12);
            if (isx) {
                prefetch_map(maps + 5);
#pragma unroll 1
                for (int n = 0; n < 12; n++) {
                    until(tb, 0); tb += DGAP;
                    if (n == 6) mbar_wait(bar_row + FB_FREE);
                    mbar_expect(bar_row + FB_D + 8 * n, 12288);
                    tma2d(sb + (n < 6 ? SF_WD : -6 * 12288) + n * 12288, maps + 5, 32 * (f >> 1), 2304 * (f & 1) + 192 * n, bar_row + FB_D + 8 * n);
                }
                TSTAMP(13);
            }
        }
    } else if (warp == 13) {
        const uint32_t tag = key_tag(epoch), par = (epoch & 1) ? 0u : 0x8000u;
        next_epoch(p, epoch);
        bar_sync(BAR_R, 32 * (nrw + 1));
        TSTAMP(3);
        uint32_t k[16];
        const uint2 va = lds64(fresh(s_part) + lane * 8), vb = lds64(fresh(s_part) + 256 + lane * 8);
        const bool two = nrw > 4 && lane < 16;
        {
            auto mk = [&](uint32_t r, int row) { const uint32_t rb = pack_bf16(0.f, __uint_as_float(r)); return (rb ^ (((int)rb >> 31) & 0x7fff0000u) ^ 0x80000000u) | tag | (uint32_t)(2047 - row); };
            uint32_t ka = mk(va.x, r0 + lane), kb = two ? mk(vb.x, r0 + 32 + lane) : 0;
#pragma unroll 1
            for (int h = 0; h < 2; h++)
#pragma unroll
                for (int r = 0; r < 4; r++) {
                    const uint32_t m = __reduce_max_sync(0xffffffffu, max(ka, kb));
                    if (ka == m) ka = 0;
                    if (kb == m) kb = 0;
                    if ((lane & 1) == h) k[r] = m;
                }
        }
        asm volatile("st.relaxed.gpu.global.v4.u32 [%0], {%1,%2,%3,%4};" :: "l"(p.s->keys + (lane >> 1) * 128 + 2 * f + (lane & 1)), "r"(k[0]), "r"(k[1]), "r"(k[2]), "r"(k[3]) : "memory");
        TSTAMP(4);
        {
            const uint32_t gb = pack_bf16(sigmoidf_(rbf(__uint_as_float(va.y))), sigmoidf_(rbf(__uint_as_float(vb.y)))) | par | (par << 16);
            asm volatile("st.relaxed.gpu.global.u16 [%0], %1;" :: "l"(p.s->gate + r0 + lane), "h"((unsigned short)gb) : "memory");
            if (two) asm volatile("st.relaxed.gpu.global.u16 [%0], %1;" :: "l"(p.s->gate + r0 + 32 + lane), "h"((unsigned short)(gb >> 16)) : "memory");
        }
        const uint4* src = p.s->keys + (f & 15) * 128 + lane;
        for (int it = 0;; it++) {
            uint32_t bad = 0;
#pragma unroll
            for (int i = 0; i < 4; i++) {
                const uint4 x = ld_rlx128(src + (i < 3 || lane < 24 ? 32 * i : 64));
                k[i] = x.x; k[4 + i] = x.y; k[8 + i] = x.z; k[12 + i] = x.w;
                bad |= x.x ^ tag;
            }
            const bool ok = __all_sync(0xffffffffu, (bad & 0xf800u) == 0);
            if (it < 8) TSTAMP(it < 4 ? 16 + it : 20 + it);
            if (ok) break;
            if (it > (1 << 20)) __trap();
        }
        TSTAMP(5);
        mbar_wait(bar_row + FB_KDONE);
        if (lane == 0) { mbar_arrive(bar_row + FB_KEYS); mbar_expect(bar_x, 8 * 1152); }
        uint32_t key = 0;
#pragma unroll 1
        for (int r = 0; r < 8; r++) {
            const uint32_t m = __reduce_max_sync(0xffffffffu, max(max(k[0], k[1]), max(k[2], k[3])));
#pragma unroll
            for (int i = 0; i < 4; i++) {
                const bool pop = k[i] == m;
                k[i] = pop ? k[4 + i] : k[i]; k[4 + i] = pop ? k[8 + i] : k[4 + i]; k[8 + i] = pop ? k[12 + i] : k[8 + i]; k[12 + i] = pop ? 0 : k[12 + i];
            }
            if (lane == 0) bulk_g2s(sb + SF_XS + r * 1168, p.u + (size_t)key_row(m) * DM, 1152, bar_x);
            if (r8 == r) key = m;
        }
        const int row = key_row(key);
        TSTAMP(6);
        if (isx) {
            if (!(f & 1)) {
                __nv_bfloat16* o = p.out + (size_t)row * DM + 16 * f + 8 * mi;
                asm volatile("st.relaxed.gpu.global.v4.u32 [%0], {%1,%1,%1,%1};" :: "l"(o), "r"(0) : "memory");
                if (__any_sync(0xffffffffu, ld_rlx32(o) != 0)) __trap();
                if (lane < 8) st_rlx32(&p.s->sel[32 * f + lane], key);
            } else wait_sel(p, f >> 1, r8, tag);
            uint32_t gb;
            for (int it = 0;; it++) {
                asm volatile("ld.relaxed.gpu.global.u16 %0, [%1];" : "=r"(gb) : "l"(p.s->gate + row) : "memory");
                gb ^= par;
                if (!(gb & 0x8000u)) break;
                if (it > (1 << 20)) __trap();
            }
            const uint32_t rb = key ^ 0x80000000u, rv = (rb ^ (((int)rb >> 31) & 0x7fff0000u)) & 0xffff0000u;
            sts64(s_tok + r8 * 8, row, __float_as_uint(rbf(1.0f - bf_lo(gb)) * rbf(sigmoidf_(__uint_as_float(rv)))));
            __syncwarp();
            TSTAMP(7);
            bar_arrive(BAR_RED, 416);
        }
    } else {
        if (rw < nrw) {
            float c[2][4];
#pragma unroll
            for (int i = 0; i < 2; i++) { c[i][0] = c[i][1] = c[i][2] = c[i][3] = 0.f; }
            mbar_wait(bar_row + 48); mbar_wait(bar_row + 56);
            const uint32_t b = fresh(sb + SF_WR) + (g & 1) * 1152 + (g >> 2) * 64 + t * 16 + (g & 2) * 2;
            uint32_t w[18][2];
#pragma unroll
            for (int kb = 0; kb < 18; kb++) { const uint32_t o = ((kb & 1) ? b ^ 64 : b) + 128 * (kb >> 1); w[kb][0] = lds32(o); w[kb][1] = lds32(o + 8); }
            mbar_wait(bar_row + 8 * rw);
            if (warp == 15) TSTAMP(2);
            const uint32_t a = fresh(rows) + g * 1152 + (g & 1) * 64 + t * 16;
#pragma unroll
            for (int kb = 0; kb < 18; kb++) {
                const uint4 x = lds128(((kb & 1) ? a ^ 64 : a) + 128 * (kb >> 1));
                mma_bf(c[kb & 1], x.x, x.y, x.z, x.w, w[kb][0], w[kb][1]);
            }
            const float sr = c[0][0] + c[1][0] + __shfl_down_sync(0xffffffffu, c[0][2] + c[1][2], 1);
            const float sg = c[0][1] + c[1][1] + __shfl_down_sync(0xffffffffu, c[0][3] + c[1][3], 1);
            if (t == 2 * (g & 1)) sts64(s_part + (8 * rw + g) * 8, __float_as_uint(sr), __float_as_uint(sg));
            __syncwarp();
            bar_arrive(BAR_R, 32 * (nrw + 1));
        }
    }
}

__device__ __forceinline__ void ffn_work(const Params& p, uint32_t sb, int warp, int lane, int f, unsigned epoch) {
    const int g = lane >> 2, t = lane & 3, mi = lane >> 3, r8 = lane & 7;
    const bool isx = f < NX;
    const int ks0 = isx ? 4 * f : 6 * f - 72, nt = isx ? 4 : 6;
    const uint32_t bar_x = sb + SF_MISC + FB_X, bar_free = sb + SF_MISC + FB_FREE, bar_w = sb + SF_MISC + FB_W, bar_d = sb + SF_MISC + FB_D, bar_h = sb + SF_MISC + FB_H, s_tok = sb + SF_MISC + FS_TOK;
    next_epoch(p, epoch);
    {
        if (warp < nt) {
            float ag[2][4], au[2][4];
#pragma unroll
            for (int i = 0; i < 2; i++) { ag[i][0] = ag[i][1] = ag[i][2] = ag[i][3] = 0.f; au[i][0] = au[i][1] = au[i][2] = au[i][3] = 0.f; }
            const uint32_t wb = sb + (warp >> 1) * 4096 + (r8 + 8 * (mi >> 1)) * 64 + (((2 * (warp & 1) + (mi & 1)) ^ (r8 >> 1)) << 4);
            const uint32_t xb = sb + SF_XS + r8 * 1168 + mi * 16;
            mbar_wait(bar_x);
            if (warp == 0) TSTAMP(8);
#pragma unroll 1
            for (int n = 0; n < 9; n++) {
                mbar_wait(bar_w + 8 * n);
                const uint32_t wk = fresh(wb) + n * nt * 4096, xk = fresh(xb) + 128 * n;
                uint32_t x[4];
#pragma unroll
                for (int s = 0; s < 4; s++) {
                    uint32_t a[4], b[4];
                    if (!(s & 1)) ldsm4(x, xk + 32 * s);
                    ldsm4t(a, wk + 1024 * s); ldsm4t(b, wk + 1024 * s + nt * 2048);
                    mma_bf(ag[s & 1], a[0], a[1], a[2], a[3], x[2 * (s & 1)], x[2 * (s & 1) + 1]);
                    mma_bf(au[s & 1], b[0], b[1], b[2], b[3], x[2 * (s & 1)], x[2 * (s & 1) + 1]);
                }
                asm volatile("" :: "f"(ag[0][0]), "f"(ag[1][0]), "f"(au[0][0]), "f"(au[1][0]) : "memory");
                if (n == 4 && lane == 0 && isx) mbar_arrive(bar_free);
            }
            if (warp == 0) TSTAMP(9);
            float h[4];
#pragma unroll
            for (int c = 0; c < 4; c++) {
                const float gv = rbf(ag[0][c] + ag[1][c]);
                h[c] = rbf(gv * sigmoidf_(gv)) * rbf(au[0][c] + au[1][c]);
            }
            uint32_t h0, h1;
            asm("movmatrix.sync.aligned.m8n8.trans.b16 %0, %1;" : "=r"(h0) : "r"(pack_bf16(h[0], h[1])));
            asm("movmatrix.sync.aligned.m8n8.trans.b16 %0, %1;" : "=r"(h1) : "r"(pack_bf16(h[2], h[3])));
            if (h0 == 0) h0 = 0x8000u;
            asm volatile("{ .reg .b64 v; mov.b64 v, {%1, %2}; st.relaxed.gpu.global.b64 [%0], v; }" :: "l"(p.s->h + ((epoch & 1) * 288 + ks0 + warp) * 32 + lane), "r"(h0), "r"(h1) : "memory");
        }
        if (isx) {
            bar_sync(BAR_GU, 384);
            if (warp == 0) TSTAMP(10);
            uint2 hb[12];
            const uint32_t hs = sb + SF_H + warp * 3072;
            const uint2* hsrc = p.s->h + ((__shfl_sync(0xffffffffu, epoch, 0) & 1) * 288 + 144 * (f & 1) + 12 * warp) * 32;
            for (int it = 0;; it++) {
                if (lane == 0) { mbar_expect(bar_h + 8 * warp, 3072); bulk_g2s(hs, hsrc, 3072, bar_h + 8 * warp); }
                mbar_wait(bar_h + 8 * warp, it & 1);
                const uint32_t hf = fresh(hs) + lane * 8;
                uint32_t mn = 0xffffffffu;
#pragma unroll
                for (int s = 0; s < 12; s++) { hb[s] = lds64(hf + 256 * s); mn = min(mn, hb[s].x); }
                if (__all_sync(0xffffffffu, mn != 0)) break;
                if (it > (1 << 16)) __trap();
            }
            if (warp == 0) TSTAMP(11);
            mbar_wait(bar_d + 8 * warp);
            if (warp == 11) TSTAMP(14);
            float ad[2][2][4];
#pragma unroll
            for (int i = 0; i < 4; i++) { ad[i >> 1][i & 1][0] = ad[i >> 1][i & 1][1] = ad[i >> 1][i & 1][2] = ad[i >> 1][i & 1][3] = 0.f; }
            const uint32_t wd = fresh(sb) + (warp < 6 ? SF_WD : -6 * 12288) + warp * 12288 + (r8 + 8 * (mi >> 1)) * 64 + (((mi & 1) ^ (r8 >> 1)) << 4);
#pragma unroll
            for (int s = 0; s < 12; s++) {
                uint32_t a[4], b[4];
                ldsm4t(a, wd + 1024 * s); ldsm4t(b, (wd ^ 32) + 1024 * s);
                mma_bf(ad[0][s & 1], a[0], a[1], a[2], a[3], hb[s].x, hb[s].y);
                mma_bf(ad[1][s & 1], b[0], b[1], b[2], b[3], hb[s].x, hb[s].y);
            }
            const uint32_t rd = sb + SF_RED + warp * 1152 + (72 * t + g) * 4;
#pragma unroll
            for (int i = 0; i < 8; i++) sts32(rd + (i >> 2) * 64 + (i & 1) * 144 + ((i >> 1) & 1) * 32, __float_as_uint(ad[i >> 2][0][i & 3] + ad[i >> 2][1][i & 3]));
            bar_sync(BAR_RED, 416);
            if (warp < 4) {
                const int tid = 32 * warp + lane;
                const uint32_t rs = fresh(sb + SF_RED) + (tid >> 4) * 144 + (tid & 15) * 8;
                const uint2 tk = lds64(fresh(s_tok) + (tid >> 4) * 8);
                float x = 0.f, y = 0.f;
#pragma unroll
                for (int w = 0; w < 12; w++) { const uint2 v = lds64(rs + w * 1152); x += __uint_as_float(v.x); y += __uint_as_float(v.y); }
                asm volatile("red.relaxed.gpu.global.add.noftz.bf16x2 [%0], %1;" :: "l"(p.out + (size_t)tk.x * DM + 32 * (f >> 1) + 2 * (tid & 15)),
                             "r"(pack_bf16(x * __uint_as_float(tk.y), y * __uint_as_float(tk.y))) : "memory");
            }
            if (warp == 0) TSTAMP(15);
        }
        if (warp == 0) TFLUSH();
    }
}

constexpr int SMEM_BYTES = 232448;
static_assert(SF_MISC + 1024 <= 232192, "layout");

struct Maps { CUtensorMap m[7]; };

__global__ void __cluster_dims__(2, 1, 1) __launch_bounds__(NTHR, 1)
fused_kernel(const Params p, const __grid_constant__ Maps maps) {
    extern __shared__ __align__(1024) uint8_t smem_raw[];
    uint32_t q[8];
    {
        const int b = blockIdx.x, x = threadIdx.x, rc = 4 * b + max(b - 84, 0) - 288 + (x >> 6);
        const int cv = (b - NCONV) >> 31, ca = 8 * b + ((x >> 5) & 3), cb = 2 * rc - (rc & 3) + 4;
        const uint32_t ch = (ca & cv) | (cb & ~cv), o = NST * ch + 2 * ((x & 31) + ((x >> (cv & 2)) & 32));
        const bool c = x < (b < 84 ? 256 : 320);
        q[6] = ldg16_if(c, p.logdt + ch);
        q[2] = ldg32_if(c, p.Bre + o); q[3] = ldg32_if(c, p.Bim + o); q[4] = ldg32_if(c, p.Cre + o); q[5] = ldg32_if(c, p.Cim + o); q[0] = ldg32_if(c, p.Are + o); q[1] = ldg32_if(c, p.Aim + o);
        q[7] = ldg16_if(c, p.Dskip + ch);
    }
    const unsigned epoch = ld_rlx32(&p.s->epoch[blockIdx.x * 16 + (threadIdx.x >> 5)]);
    const uint32_t sb = __shfl_sync(0xffffffffu, smem_u32(smem_raw), 0);
    const int warp = __shfl_sync(0xffffffffu, threadIdx.x >> 5, 0), bid = __shfl_sync(0xffffffffu, blockIdx.x, 0);
    const int lane = __shfl_sync(0xffffffffu, threadIdx.x & 31, threadIdx.x);
    const bool conv = bid < NCONV;
    const int f = bid - NCONV;
    uint32_t w[12];
    if (warp < (f < 12 ? 8 : 10)) {
        const int half = conv ? warp >> 2 : warp & 1, pr = conv ? warp & 3 : warp >> 1;
        const int rc = 4 * f + max(f - 12, 0) + pr;
        const uint32_t stage = sb + (conv ? SC_KG : SF_KG) + warp * KG_STAGE;
        uint4* const kp = p.s->kp + rc * 128 + lane;
        kgen(q, sb, half, stage, stage + (conv ? 4 : 1) * KG_STAGE, 1 + pr, lane, w, [&] {
            sts128z_if(conv && lane < 20, sb + SC_KT + warp * KT_BYTES + lane * 16 + (lane < 4 ? 0 : lane < 14 ? 2048 : 2288));
            stg128z_if(!conv, kp + 64 * half); stg128z_if(!conv, kp + 64 * half + 32);
            stg128z_if(!conv && warp < (f < NX ? 4 : 6), (uint4*)(p.s->h + ((lane >> 4) * 288 + (f < NX ? 4 * f : 6 * f - 72) + warp) * 32) + (lane & 15));
            if (conv) asm volatile("barrier.cluster.arrive.relaxed.aligned;" ::: "memory");
        });
        if (conv) { conv_main(p, sb, warp, lane, bid, epoch, w); return; }
        {
            if (!half) {
#pragma unroll
                for (int i = 0; i < 4; i++) asm volatile("st.relaxed.gpu.global.v4.u32 [%0], {%1,%2,%3,%4};" :: "l"(kp + 32 * i), "r"(w[3 * i]), "r"(w[3 * i + 1]), "r"(w[3 * i + 2]), "r"(~epoch) : "memory");
            }
            if (warp == 0) TSTAMP(22);
            if (warp == 2) TSTAMP(23);
            bar_sync(0, NTHR);
            if (warp == 0 && lane == 0) mbar_arrive(sb + SF_MISC + FB_KDONE);
        }
    } else if (conv) {
        conv_aux(p, maps.m, sb, warp - 8, lane, bid, epoch);
        return;
    } else {
        ffn_front(p, maps.m, sb, warp, lane, f, epoch);
        if (warp >= 12) return;
    }
    __syncwarp();
    ffn_work(p, sb, warp, lane, f, epoch);
}

typedef CUresult (*EncodeFn)(CUtensorMap*, CUtensorMapDataType, cuuint32_t, void*, const cuuint64_t*, const cuuint64_t*, const cuuint32_t*, const cuuint32_t*,
                             CUtensorMapInterleave, CUtensorMapSwizzle, CUtensorMapL2promotion, CUtensorMapFloatOOBfill);

void make_map(EncodeFn fn, CUtensorMap* m, const void* base, int rank, const cuuint64_t* dims, const cuuint64_t* strides, const cuuint32_t* box, CUtensorMapSwizzle sw) {
    const cuuint32_t es[5] = {1, 1, 1, 1, 1};
    fn(m, CU_TENSOR_MAP_DATA_TYPE_BFLOAT16, rank, (void*)base, dims, strides, box, es, CU_TENSOR_MAP_INTERLEAVE_NONE, sw,
       CU_TENSOR_MAP_L2_PROMOTION_NONE, CU_TENSOR_MAP_FLOAT_OOB_FILL_NONE);
}

}

extern "C" void kernel_launch(void* const* d_in, const int* in_sizes, int n_in, void* d_out, int out_size) {
    (void)in_sizes; (void)n_in; (void)out_size;
    static EncodeFn fn = nullptr;
    static void* scratch = nullptr;
    if (!fn) {
        void* ptr = nullptr; cudaDriverEntryPointQueryResult qr;
        cudaGetDriverEntryPoint("cuTensorMapEncodeTiled", &ptr, cudaEnableDefault, &qr);
        fn = (EncodeFn)ptr;
        cudaGetSymbolAddress(&scratch, g_scratch);
        cudaFuncSetAttribute(fused_kernel, cudaFuncAttributeMaxDynamicSharedMemorySize, SMEM_BYTES);
    }
    typedef const __nv_bfloat16* bp;
    Params p;
    p.u = (bp)d_in[0]; p.Are = (bp)d_in[1]; p.Aim = (bp)d_in[2]; p.Bre = (bp)d_in[3]; p.Bim = (bp)d_in[4]; p.Cre = (bp)d_in[5]; p.Cim = (bp)d_in[6];
    p.logdt = (bp)d_in[7]; p.Dskip = (bp)d_in[8]; p.wr = (bp)d_in[10]; p.gatew = (bp)d_in[14];
    p.out = (__nv_bfloat16*)d_out; p.s = (Scratch*)scratch; p.zero = 0;
    Maps maps;
    {
        const cuuint64_t dims[4] = {DM, 4, 16, 32}, strides[3] = {16 * DM * 2, DM * 2, 64 * DM * 2};
        const cuuint32_t box[4] = {16, 4, 16, 2};
        make_map(fn, &maps.m[0], d_in[0], 4, dims, strides, box, CU_TENSOR_MAP_SWIZZLE_32B);
    }
    for (int i = 0; i < 4; i++) {
        const cuuint64_t dims[3] = {32, DM, FF / 32}, strides[2] = {FF * 2, 64};
        const cuuint32_t box[3] = {32, 64, i < 2 ? 2u : 3u};
        make_map(fn, &maps.m[1 + i], d_in[11 + (i & 1)], 3, dims, strides, box, CU_TENSOR_MAP_SWIZZLE_64B);
    }
    {
        const cuuint64_t dims[2] = {DM, FF}, strides[1] = {DM * 2};
        const cuuint32_t box[2] = {32, 192};
        make_map(fn, &maps.m[5], d_in[13], 2, dims, strides, box, CU_TENSOR_MAP_SWIZZLE_64B);
    }
    {
        const cuuint64_t dims[5] = {DM, 4, 4, 2, L_SEQ}, strides[4] = {16 * DM * 2, 4 * DM * 2, 128 * DM * 2, DM * 2};
        const cuuint32_t box[5] = {16, 4, 4, 2, 1};
        make_map(fn, &maps.m[6], d_out, 5, dims, strides, box, CU_TENSOR_MAP_SWIZZLE_NONE);
    }
    fused_kernel<<<NCTA, NTHR, SMEM_BYTES>>>(p, maps);
}
```

```cpp
#include <cuda_runtime.h>
#include <cuda_bf16.h>
#include <cuda_fp16.h>
#include <cuda.h>
#include <stdint.h>
#include <type_traits>

#define LASTS 4
#define RESUME 400
#define UDELAY 0
#define RDELAY 900
#define WDELAY 2200
#define WGAP 290
#define NPRE 6
#define DGAP 220

namespace {

constexpr int DM = 576, NST = 128, FF = 4608, L_SEQ = 2048;
constexpr int NCONV = 72, NX = 36, NFFN = 60, NCTA = 132, NTHR = 512;

struct __align__(128) Scratch {
    unsigned epoch[NCTA * 16];
    uint4 keys[16 * 128];
    uint32_t sel[18 * 64];
    uint16_t gate[L_SEQ];
    uint2 h[2 * 288 * 32];
    uint4 kp[288 * 128];
};
__device__ Scratch g_scratch;
#define TFLUSH()
#define TSTAMP(i)

struct Params {
    const __nv_bfloat16 *Are, *Aim, *Bre, *Bim, *Cre, *Cim, *logdt, *Dskip, *u, *wr, *gatew;
    __nv_bfloat16* out;
    Scratch* s;
    uint32_t zero;
};

__device__ __forceinline__ uint32_t smem_u32(const void* p) { return (uint32_t)__cvta_generic_to_shared(p); }
__device__ __forceinline__ uint32_t pack_bf16(float lo, float hi) { uint32_t r; asm("cvt.rn.bf16x2.f32 %0, %1, %2;" : "=r"(r) : "f"(hi), "f"(lo)); return r; }
__device__ __forceinline__ uint32_t pack_f16(float lo, float hi) { uint32_t r; asm("cvt.rn.f16x2.f32 %0, %1, %2;" : "=r"(r) : "f"(hi), "f"(lo)); return r; }
__device__ __forceinline__ float bf_lo(uint32_t w) { return __uint_as_float(w << 16); }
__device__ __forceinline__ float bf_hi(uint32_t w) { return __uint_as_float(w & 0xffff0000u); }
__device__ __forceinline__ float rbf(float x) { return bf_lo(pack_bf16(x, 0.f)); }
__device__ __forceinline__ uint32_t badd2(uint32_t a, uint32_t b) { uint32_t r; asm("add.rn.bf16x2 %0, %1, %2;" : "=r"(r) : "r"(a), "r"(b)); return r; }
__device__ __forceinline__ uint32_t bsub2(uint32_t a, uint32_t b) { uint32_t r; asm("sub.rn.bf16x2 %0, %1, %2;" : "=r"(r) : "r"(a), "r"(b)); return r; }
__device__ __forceinline__ uint32_t gmix(uint32_t ng, float ny0, float ny1, uint32_t u) {
    uint32_t r; asm("{ .reg .b32 t; fma.rn.bf16x2 t, %1, %3, %3; fma.rn.bf16x2 %0, %1, %2, t; }" : "=r"(r) : "r"(ng), "r"(pack_bf16(ny0, ny1)), "r"(u)); return r;
}
__device__ __forceinline__ void mma_bf(float (&c)[4], uint32_t a0, uint32_t a1, uint32_t a2, uint32_t a3, uint32_t b0, uint32_t b1) {
    asm("mma.sync.aligned.m16n8k16.row.col.f32.bf16.bf16.f32 {%0,%1,%2,%3}, {%4,%5,%6,%7}, {%8,%9}, {%0,%1,%2,%3};"
        : "+f"(c[0]), "+f"(c[1]), "+f"(c[2]), "+f"(c[3]) : "r"(a0), "r"(a1), "r"(a2), "r"(a3), "r"(b0), "r"(b1));
}
__device__ __forceinline__ void mma_bf8(float (&c)[4], uint32_t a0, uint32_t a1, uint32_t b0) {
    asm("mma.sync.aligned.m16n8k8.row.col.f32.bf16.bf16.f32 {%0,%1,%2,%3}, {%4,%5}, {%6}, {%0,%1,%2,%3};"
        : "+f"(c[0]), "+f"(c[1]), "+f"(c[2]), "+f"(c[3]) : "r"(a0), "r"(a1), "r"(b0));
}
__device__ __forceinline__ void mma_h(float (&c)[4], uint32_t a0, uint32_t a1, uint32_t a2, uint32_t a3, uint32_t b0, uint32_t b1) {
    asm("mma.sync.aligned.m16n8k16.row.col.f32.f16.f16.f32 {%0,%1,%2,%3}, {%4,%5,%6,%7}, {%8,%9}, {%0,%1,%2,%3};"
        : "+f"(c[0]), "+f"(c[1]), "+f"(c[2]), "+f"(c[3]) : "r"(a0), "r"(a1), "r"(a2), "r"(a3), "r"(b0), "r"(b1));
}
__device__ __forceinline__ uint32_t fresh(uint32_t a) { asm volatile("" : "+r"(a) :: "memory"); return a; }
__device__ __forceinline__ uint32_t lds16(uint32_t a) { uint32_t v; asm("ld.shared.u16 %0, [%1];" : "=r"(v) : "r"(a)); return v; }
__device__ __forceinline__ uint32_t lds32(uint32_t a) { uint32_t v; asm("ld.shared.u32 %0, [%1];" : "=r"(v) : "r"(a)); return v; }
__device__ __forceinline__ uint2 lds64(uint32_t a) { uint2 v; asm("ld.shared.v2.u32 {%0,%1}, [%2];" : "=r"(v.x), "=r"(v.y) : "r"(a)); return v; }
__device__ __forceinline__ uint4 lds128(uint32_t a) { uint4 v; asm("ld.shared.v4.u32 {%0,%1,%2,%3}, [%4];" : "=r"(v.x), "=r"(v.y), "=r"(v.z), "=r"(v.w) : "r"(a)); return v; }
__device__ __forceinline__ uint4 lds128v(uint32_t a) { uint4 v; asm volatile("ld.shared.v4.u32 {%0,%1,%2,%3}, [%4];" : "=r"(v.x), "=r"(v.y), "=r"(v.z), "=r"(v.w) : "r"(a) : "memory"); return v; }
__device__ __forceinline__ void ldsm4(uint32_t (&r)[4], uint32_t a) {
    asm("ldmatrix.sync.aligned.m8n8.x4.shared.b16 {%0,%1,%2,%3}, [%4];" : "=r"(r[0]), "=r"(r[1]), "=r"(r[2]), "=r"(r[3]) : "r"(a));
}
__device__ __forceinline__ void ldsm4t(uint32_t (&r)[4], uint32_t a) {
    asm("ldmatrix.sync.aligned.m8n8.x4.trans.shared.b16 {%0,%1,%2,%3}, [%4];" : "=r"(r[0]), "=r"(r[1]), "=r"(r[2]), "=r"(r[3]) : "r"(a));
}
__device__ __forceinline__ void sts16(uint32_t a, uint32_t v) { asm volatile("st.shared.u16 [%0], %1;" :: "r"(a), "h"((unsigned short)v) : "memory"); }
__device__ __forceinline__ void sts32(uint32_t a, uint32_t v) { asm volatile("st.shared.u32 [%0], %1;" :: "r"(a), "r"(v) : "memory"); }
__device__ __forceinline__ void sts64(uint32_t a, uint32_t x, uint32_t y) { asm volatile("st.shared.v2.u32 [%0], {%1,%2};" :: "r"(a), "r"(x), "r"(y) : "memory"); }
__device__ __forceinline__ void sts128(uint32_t a, uint32_t x, uint32_t y, uint32_t z, uint32_t w) {
    asm volatile("st.shared.v4.u32 [%0], {%1,%2,%3,%4};" :: "r"(a), "r"(x), "r"(y), "r"(z), "r"(w) : "memory");
}
__device__ __forceinline__ void st_async128(uint32_t a, uint32_t x, uint32_t y, uint32_t z, uint32_t w, uint32_t bar) {
    asm volatile("st.async.weak.shared::cluster.mbarrier::complete_tx::bytes.v4.b32 [%0], {%1,%2,%3,%4}, [%5];" :: "r"(a), "r"(x), "r"(y), "r"(z), "r"(w), "r"(bar) : "memory");
}
__device__ __forceinline__ void mbar_init(uint32_t b, uint32_t cnt) { asm volatile("mbarrier.init.shared::cta.b64 [%0], %1;" :: "r"(b), "r"(cnt) : "memory"); }
__device__ __forceinline__ void mbar_fence() { asm volatile("fence.mbarrier_init.release.cluster;" ::: "memory"); }
__device__ __forceinline__ void mbar_expect(uint32_t b, uint32_t bytes) { asm volatile("mbarrier.arrive.expect_tx.shared::cta.b64 _, [%0], %1;" :: "r"(b), "r"(bytes) : "memory"); }
__device__ __forceinline__ void mbar_arrive(uint32_t b) { asm volatile("mbarrier.arrive.shared::cta.b64 _, [%0];" :: "r"(b) : "memory"); }
#define CHINT ""
#define HINT ""
__device__ __forceinline__ void mbar_wait(uint32_t b, uint32_t parity = 0) {
    asm volatile("{ .reg .pred p; .reg .u32 n; mov.u32 n, 0;\n"
                 "LW: mbarrier.try_wait.parity.shared::cta.b64 p, [%0], %1" HINT "; @p bra LD; add.u32 n, n, 1; setp.lt.u32 p, n, 65536; @p bra LW; trap;\n"
                 "LD: }" :: "r"(b), "r"(parity) : "memory");
}
__device__ __forceinline__ void mbar_wait_cluster(uint32_t b) {
    asm volatile("{ .reg .pred p; .reg .u32 n; mov.u32 n, 0;\n"
                 "LW: mbarrier.try_wait.parity.acquire.cluster.shared::cta.b64 p, [%0], 0" CHINT "; @p bra LD; add.u32 n, n, 1; setp.lt.u32 p, n, 65536; @p bra LW; trap;\n"
                 "LD: }" :: "r"(b) : "memory");
}
__device__ __forceinline__ void tma2d(uint32_t dst, const CUtensorMap* m, int c0, int c1, uint32_t bar) {
    asm volatile("cp.async.bulk.tensor.2d.shared::cluster.global.mbarrier::complete_tx::bytes [%0], [%1, {%3, %4}], [%2];"
                 :: "r"(dst), "l"(m), "r"(bar), "r"(c0), "r"(c1) : "memory");
}
__device__ __forceinline__ void tma3d(uint32_t dst, const CUtensorMap* m, int c0, int c1, int c2, uint32_t bar) {
    asm volatile("cp.async.bulk.tensor.3d.shared::cluster.global.mbarrier::complete_tx::bytes [%0], [%1, {%3, %4, %5}], [%2];"
                 :: "r"(dst), "l"(m), "r"(bar), "r"(c0), "r"(c1), "r"(c2) : "memory");
}
__device__ __forceinline__ void tma4d(uint32_t dst, const CUtensorMap* m, int c0, int c1, int c2, int c3, uint32_t bar) {
    asm volatile("cp.async.bulk.tensor.4d.shared::cluster.global.mbarrier::complete_tx::bytes [%0], [%1, {%3, %4, %5, %6}], [%2];"
                 :: "r"(dst), "l"(m), "r"(bar), "r"(c0), "r"(c1), "r"(c2), "r"(c3) : "memory");
}
__device__ __forceinline__ void bulk_g2s(uint32_t dst, const void* src, uint32_t bytes, uint32_t bar) {
    asm volatile("cp.async.bulk.shared::cluster.global.mbarrier::complete_tx::bytes [%0], [%1], %2, [%3];"
                 :: "r"(dst), "l"(src), "r"(bytes), "r"(bar) : "memory");
}
__device__ __forceinline__ uint32_t mapa(uint32_t a, uint32_t rank) { uint32_t r; asm("mapa.shared::cluster.u32 %0, %1, %2;" : "=r"(r) : "r"(a), "r"(rank)); return r; }
__device__ __forceinline__ void prefetch_map(const CUtensorMap* m) { asm volatile("prefetch.tensormap [%0];" :: "l"(m) : "memory"); }
__device__ __forceinline__ void bar_sync(int id, int n) { asm volatile("bar.sync %0, %1;" :: "r"(id), "r"(n) : "memory"); }
__device__ __forceinline__ void bar_arrive(int id, int n) { asm volatile("bar.arrive %0, %1;" :: "r"(id), "r"(n) : "memory"); }
__device__ __forceinline__ uint32_t ldg16_if(bool c, const void* p) { uint32_t v; asm volatile("{ .reg .pred p; setp.ne.u32 p, %2, 0; @p ld.global.nc.u16 %0, [%1]; }" : "=r"(v) : "l"(p), "r"((uint32_t)c)); return v; }
__device__ __forceinline__ uint32_t ldg32_if(bool c, const void* p) { uint32_t v; asm volatile("{ .reg .pred p; setp.ne.u32 p, %2, 0; @p ld.global.nc.u32 %0, [%1]; }" : "=r"(v) : "l"(p), "r"((uint32_t)c)); return v; }
__device__ __forceinline__ uint32_t ld_rlx32(const void* p) { uint32_t v; asm volatile("ld.relaxed.gpu.global.u32 %0, [%1];" : "=r"(v) : "l"(p) : "memory"); return v; }
__device__ __forceinline__ uint4 ld_rlx128(const void* p) {
    uint4 v; asm volatile("ld.relaxed.gpu.global.v4.u32 {%0,%1,%2,%3}, [%4];" : "=r"(v.x), "=r"(v.y), "=r"(v.z), "=r"(v.w) : "l"(p) : "memory"); return v;
}
__device__ __forceinline__ void st_rlx32(void* p, uint32_t v) { asm volatile("st.relaxed.gpu.global.u32 [%0], %1;" :: "l"(p), "r"(v) : "memory"); }
__device__ __forceinline__ void stg128(void* p, uint32_t x, uint32_t y, uint32_t z, uint32_t w) {
    asm volatile("st.global.v4.u32 [%0], {%1,%2,%3,%4};" :: "l"(p), "r"(x), "r"(y), "r"(z), "r"(w) : "memory");
}
__device__ __forceinline__ void next_epoch(const Params& p, unsigned e) { if ((threadIdx.x & 31) == 0) p.s->epoch[blockIdx.x * 16 + (threadIdx.x >> 5)] = e + 1; }
__device__ __forceinline__ void sts128z_if(bool c, uint32_t a) { asm volatile("{ .reg .pred p; setp.ne.u32 p, %1, 0; @p st.shared.v4.u32 [%0], {%2,%2,%2,%2}; }" :: "r"(a), "r"((uint32_t)c), "r"(0) : "memory"); }
__device__ __forceinline__ void stg128z_if(bool c, void* a) { asm volatile("{ .reg .pred p; setp.ne.u32 p, %1, 0; @p st.global.v4.u32 [%0], {%2,%2,%2,%2}; }" :: "l"(a), "r"((uint32_t)c), "r"(0) : "memory"); }
__device__ __forceinline__ unsigned clock32() { unsigned c; asm volatile("mov.u32 %0, %clock;" : "=r"(c) :: "memory"); return c; }
__device__ __forceinline__ void until(unsigned t0, int c) { while ((int)(clock32() - t0) < c) { } }
__device__ __forceinline__ float sigmoidf_(float x) { return __fdividef(1.0f, 1.0f + __expf(-x)); }
__device__ __forceinline__ uint32_t key_tag(unsigned epoch) { return ((epoch & 15u) | 16u) << 11; }
__device__ __forceinline__ int key_row(uint32_t key) { return 2047 - (int)(key & 2047u); }
__device__ __forceinline__ uint32_t wait_sel(const Params& p, int s32, int r8, uint32_t tag) {
    uint32_t k;
    for (int it = 0;; it++) {
        k = ld_rlx32(&p.s->sel[s32 * 64 + r8]);
        if (__all_sync(0xffffffffu, (k & 0xf800u) == tag)) break;
        if (it > (1 << 20)) __trap();
    }
    return k;
}

struct cplx { float re, im; };
__device__ __forceinline__ cplx csq(cplx a) { cplx r; r.re = a.re * a.re - a.im * a.im; r.im = (a.re * a.im) * 2.f; return r; }
__device__ __forceinline__ cplx cexpk(float ar, float ai, float k) {
    float mag, s, c;
    asm("ex2.approx.ftz.f32 %0, %1;" : "=f"(mag) : "f"(ar * (k * 1.4426950408889634f)));
    const float r = ai * k;
    asm("sin.approx.ftz.f32 %0, %1;" : "=f"(s) : "f"(r));
    asm("cos.approx.ftz.f32 %0, %1;" : "=f"(c) : "f"(r));
    cplx o; o.re = mag * c; o.im = mag * s; return o;
}
struct h2c { uint32_t re, im; };
__device__ __forceinline__ h2c cmul_cd(h2c v, __half2 c, __half2 d) {
    const __half2 r = *(const __half2*)&v.re, i = *(const __half2*)&v.im;
    const __half2 x = __hfma2(__hneg2(i), d, __hmul2(r, c)), y = __hfma2(i, c, __hmul2(r, d));
    h2c o; o.re = *(const uint32_t*)&x; o.im = *(const uint32_t*)&y; return o;
}
__device__ __forceinline__ h2c cmul_s(h2c v, uint32_t s) { const __half2 h = *(const __half2*)&s; return cmul_cd(v, __low2half2(h), __high2half2(h)); }
__device__ __forceinline__ h2c cmul_sc(h2c v, uint32_t s) {
    const __half2 h = *(const __half2*)&s, c = __low2half2(h), d = __high2half2(h), r = *(const __half2*)&v.re, i = *(const __half2*)&v.im;
    const __half2 x = __hfma2(i, d, __hmul2(r, c)), y = __hfma2(__hneg2(r), d, __hmul2(i, c));
    h2c o; o.re = *(const uint32_t*)&x; o.im = *(const uint32_t*)&y; return o;
}
__device__ __forceinline__ h2c cmul_vc(h2c v, uint32_t s) {
    const __half2 h = *(const __half2*)&s, c = __low2half2(h), d = __high2half2(h), r = *(const __half2*)&v.re, i = *(const __half2*)&v.im;
    const __half2 x = __hfma2(i, d, __hmul2(r, c)), y = __hfma2(__hneg2(i), c, __hmul2(r, d));
    h2c o; o.re = *(const uint32_t*)&x; o.im = *(const uint32_t*)&y; return o;
}

constexpr int UT_HALF = 2240, UT_STRIDE = 4448;
constexpr int KT_T = 542, KT_C = 552, KT_D = 645, KT_BYTES = 720 * 4;
constexpr int VC_OFF = 80, VE_BASE = 1616;
constexpr int V_STRIDE = (1616 + 1024) * 4 + 80;
constexpr int KG_STAGE = 5248;
constexpr int Y_CS = 2080, Y_RS = 8 * Y_CS + 64;

constexpr int SC_RT = 0;
constexpr int SC_UT = 33408;
constexpr int SC_ST = SC_UT + 8 * UT_STRIDE;
constexpr int SC_KT = SC_ST + 8 * UT_STRIDE;
constexpr int SC_GT = SC_KT + 8 * KT_BYTES;
constexpr int SC_V = SC_GT + UT_STRIDE;
constexpr int SC_KG = SC_V + 4 * V_STRIDE;
constexpr int SC_MISC = SC_V + 8 * V_STRIDE;
static_assert(V_STRIDE % 128 == 16 && 8 * KG_STAGE <= 4 * V_STRIDE && 2 * Y_RS <= SC_UT && SC_UT % 128 == 0 && SC_ST % 128 == 0, "layout");
static_assert(SC_MISC % 16 == 0 && SC_MISC + 512 <= 232192, "layout");

__device__ __forceinline__ void window_task(uint32_t src, uint32_t d0, uint32_t d1, bool withE) {
    float S[35];
    {
        uint32_t w[20];
#pragma unroll
        for (int i = 0; i < 5; i++) {
            const uint4 v = lds128(src + ((i & 1) ? 0 : UT_HALF) + ((i + 1) >> 1) * 16);
            w[4 * i] = v.x; w[4 * i + 1] = v.y; w[4 * i + 2] = v.z; w[4 * i + 3] = v.w;
        }
        float s = 0.f; S[2] = 0.f;
#pragma unroll
        for (int i = 3; i < 26; i++) { s += (i & 1) ? bf_hi(w[i >> 1]) : bf_lo(w[i >> 1]); S[i] = s; }
#pragma unroll
        for (int i = 0; i < 8; i += 2)
            sts128((i & 4 ? d1 : d0) + (VC_OFF - 16) * 4 + 8 * (i & 2), pack_bf16(S[10 + i] - S[5 + i], S[5 + i] - S[2 + i]), pack_bf16(S[18 + i] - S[13 + i], S[13 + i] - S[10 + i]),
                   pack_bf16(S[11 + i] - S[6 + i], S[6 + i] - S[3 + i]), pack_bf16(S[19 + i] - S[14 + i], S[14 + i] - S[11 + i]));
        if (withE) {
#pragma unroll
            for (int i = 26; i < 35; i++) { s += (i & 1) ? bf_hi(w[i >> 1]) : bf_lo(w[i >> 1]); S[i] = s; }
#pragma unroll
            for (int i = 0; i < 8; i += 2)
                sts128((i & 4 ? d1 : d0) + VE_BASE * 4 + 8 * (i & 2), pack_bf16(S[19 + i] - S[12 + i], S[12 + i] - S[3 + i]), pack_bf16(S[27 + i] - S[20 + i], S[20 + i] - S[11 + i]),
                       pack_bf16(S[20 + i] - S[13 + i], S[13 + i] - S[4 + i]), pack_bf16(S[28 + i] - S[21 + i], S[21 + i] - S[12 + i]));
        }
    }
}

template <class F>
__device__ __forceinline__ void kgen(const uint32_t (&q)[8], uint32_t sb, int half, uint32_t stage, uint32_t pstage, int barid, int lane, uint32_t (&w)[12], F shadow) {
    const int t = lane & 3, mi = lane >> 3, r8 = lane & 7;
    {
        const uint32_t pAr = q[0], pAi = q[1], pBr = q[2], pBi = q[3], pCr = q[4], pCi = q[5], pDt = q[6], pD = q[7];
        const uint32_t wb = fresh(stage + lane * 16), za = fresh(stage + 5120 + ((lane >> 1) & 3) * 16 + mi * 4 + (lane & 1) * 2), zr = fresh(stage + 5120 + t * 16);
        const uint32_t oA = fresh(stage + (mi & 1) * 1024 + (mi >> 1) * 512 + r8 * 16), oB = fresh(stage + 2048 + mi * 512 + r8 * 16), oC = fresh(stage + 4096 + (mi & 1) * 512 + (mi >> 1) * 128 + r8 * 16);
        float acc[6][4];
#pragma unroll
        for (int a = 0; a < 6; a++) { acc[a][0] = acc[a][1] = acc[a][2] = acc[a][3] = 0.f; asm volatile("" : "+f"(acc[a][0]), "+f"(acc[a][1]), "+f"(acc[a][2]), "+f"(acc[a][3])); }
        shadow();
        sts32(zr, clock32());
        const float dt = rbf(__expf(bf_lo(pDt)));
        float ar = dt * bf_lo(pAr), ai = dt * bf_lo(pAi), ar1 = dt * bf_hi(pAr), ai1 = dt * bf_hi(pAi);
        float wr, wi, wr1, wi1;
        { const float br = dt * bf_lo(pBr), bi = dt * bf_lo(pBi), cr = bf_lo(pCr), ci = bf_lo(pCi); wr = cr * br - ci * bi; wi = cr * bi + ci * br; }
        { const float br = dt * bf_hi(pBr), bi = dt * bf_hi(pBi), cr = bf_hi(pCr), ci = bf_hi(pCi); wr1 = cr * br - ci * bi; wi1 = cr * bi + ci * br; }
        const uint32_t ex = max(__reduce_max_sync(0xffffffffu, __float_as_uint(fmaxf(fmaxf(fabsf(wr), fabsf(wi)), fmaxf(fabsf(wr1), fabsf(wi1))))) >> 23, 14u);
        const float scl = __uint_as_float((267u - ex) << 23);
        uint32_t W = pack_f16(wr * scl, wi * -scl);
        const uint32_t W1 = pack_f16(wr1 * scl, wi1 * -scl);
        if (threadIdx.x < 32) TSTAMP(20);

#pragma unroll 1
        for (int r = 0; r < 2; r++) {
            const cplx z1 = cexpk(ar, ai, 1.f), z64 = cexpk(ar, ai, 64.f);
            const cplx z2 = csq(z1), z4 = csq(z2), z8 = csq(z4), z16 = csq(z8), z32 = csq(z16);
            const cplx z128 = csq(z64), z256 = csq(z128), z512 = csq(z256);
            auto put = [&](int grp, h2c a, h2c b, h2c c, h2c d) { sts128(wb + grp * 1024, a.re, b.re, c.re, d.re); sts128(wb + grp * 1024 + 512, a.im, b.im, c.im, d.im); };
            {
                const uint32_t s4 = pack_f16(z4.re, z4.im), s256 = pack_f16(z256.re, z256.im), s512 = pack_f16(z512.re, z512.im);
                auto mix = [](h2c a, h2c b, uint32_t sel) { return h2c{__byte_perm(a.re, b.re, sel), __byte_perm(a.im, b.im, sel)}; };
                const h2c c10 = cmul_vc(h2c{pack_f16(z1.re, 1.f), pack_f16(z1.im, 0.f)}, W), c32 = cmul_sc(c10, pack_f16(z2.re, z2.im)), c54 = cmul_sc(c10, s4);
                put(2, c10, c32, c54, cmul_sc(c32, s4));
                const h2c d20 = cmul_sc(mix(c32, c10, 0x7632), s256), e04 = cmul_sc(mix(c10, c54, 0x7632), s512), f04 = cmul_sc(e04, s256);
                put(3, d20, cmul_sc(d20, s4), e04, f04);
                const h2c ef = mix(e04, f04, 0x5410), gh = cmul_sc(ef, s512), g8 = cmul_sc(gh, pack_f16(z8.re, z8.im));
                put(4, g8, cmul_sc(g8, s512), gh, ef);
            }
            {
                const uint32_t s32 = pack_f16(z32.re, z32.im), s64 = pack_f16(z64.re, z64.im), s128 = pack_f16(z128.re, z128.im);
                const h2c p0 = {pack_f16(1.f, z8.re), pack_f16(0.f, z8.im)}, p1 = cmul_s(p0, pack_f16(z16.re, z16.im)), p2 = cmul_s(p0, s32), p3 = cmul_s(p1, s32);
                put(0, p0, p1, p2, p3);
                put(1, cmul_s(p0, s64), cmul_s(p1, s64), cmul_s(p2, s64), cmul_s(p3, s64));
                sts16(za, s128); sts16(za + 64, s128 >> 16);
            }
            __syncwarp();
            {
                const uint32_t aA = fresh(oA), aB = fresh(oB), aC = fresh(oC), aZ = fresh(zr);
                const uint4 zc = lds128(aZ), zd = lds128(aZ + 64);
                const uint32_t zcs[4] = {zc.x, zc.y, zc.z, zc.w}, zds[4] = {zd.x, zd.y, zd.z, zd.w};
                uint32_t c[4];
#pragma unroll
                for (int k = 0; k < 4; k++) {
                    uint32_t a[4], b[4];
                    ldsm4t(a, aA + 128 * k); ldsm4t(b, aB + 128 * k);
                    if (!(k & 1)) ldsm4t(c, aC + 128 * k);
                    const h2c x = cmul_cd(h2c{a[0], a[2]}, *(const __half2*)&zcs[k], *(const __half2*)&zds[k]), y = cmul_cd(h2c{a[1], a[3]}, *(const __half2*)&zcs[k], *(const __half2*)&zds[k]);
                    mma_h(acc[0], a[0], a[1], a[2], a[3], b[0], b[1]);
                    mma_h(acc[1], a[0], a[1], a[2], a[3], b[2], b[3]);
                    mma_h(acc[2], a[0], a[1], a[2], a[3], c[2 * (k & 1)], c[2 * (k & 1) + 1]);
                    mma_h(acc[3], x.re, y.re, x.im, y.im, b[0], b[1]);
                    mma_h(acc[4], x.re, y.re, x.im, y.im, b[2], b[3]);
                    mma_h(acc[5], x.re, y.re, x.im, y.im, c[2 * (k & 1)], c[2 * (k & 1) + 1]);
                }
                asm volatile("" :: "f"(acc[0][0]), "f"(acc[1][0]), "f"(acc[2][0]), "f"(acc[3][0]), "f"(acc[4][0]), "f"(acc[5][0]) : "memory");
            }
            __syncwarp();
            ar = ar1; ai = ai1; W = W1;
        }
        if (threadIdx.x < 32) TSTAMP(21);
        const float i0 = __uint_as_float((ex + 243u) << 23);
        if (half) {
#pragma unroll
            for (int a = 0; a < 6; a++) sts128(wb + a * 512, __float_as_uint(acc[a][0]), __float_as_uint(acc[a][1]), __float_as_uint(acc[a][2]), __float_as_uint(acc[a][3]));
            sts32(stage + 3072, __float_as_uint(i0));
            bar_arrive(barid, 64);
        } else {
#pragma unroll
            for (int a = 0; a < 6; a++) { acc[a][0] *= i0; acc[a][1] *= i0; acc[a][2] *= i0; acc[a][3] *= i0; }
            if (lane == 0) acc[0][1] -= bf_lo(pD);
            sts32(zr, clock32());
            bar_sync(barid, 64);
            const uint32_t src = fresh(pstage);
            const float i1 = __uint_as_float(lds32(src + 3072));
#pragma unroll
            for (int a = 0; a < 6; a++) {
                const uint4 y = lds128(src + lane * 16 + a * 512);
                w[2 * a] = pack_bf16(fmaf(__uint_as_float(y.x), i1, acc[a][0]), fmaf(__uint_as_float(y.y), i1, acc[a][1]));
                w[2 * a + 1] = pack_bf16(fmaf(__uint_as_float(y.z), i1, acc[a][2]), fmaf(__uint_as_float(y.w), i1, acc[a][3]));
            }
        }
    }
}

__device__ __forceinline__ int swap01(int i) { return (i & ~3) | ((i & 1) << 1) | ((i >> 1) & 1); }
enum { BC_AUX = 0, BC_S = 5, BC_KG = 15 };

__device__ __forceinline__ void conv_aux(const Params& p, const CUtensorMap* mU, uint32_t sb, int aw, int lane, int bid, unsigned epoch) {
    const unsigned t0 = clock32();
    const int g = lane >> 2, t = lane & 3, mi = lane >> 3, r8 = lane & 7;
    const int rank = bid & 1, slab = bid >> 1;
    const uint32_t bar_y = sb + SC_MISC, bar_u = bar_y + 32, bar_v = bar_y + 40, bar_box = bar_y + 64 + 8 * aw, s_bm = bar_y + 128;
    if (lane == 0) {
        mbar_init(bar_box, 1); mbar_fence();
        mbar_expect(bar_box, 4096);
        if (UDELAY) until(t0, UDELAY);
        tma4d(sb + SC_RT + 4096 * aw, mU, 16 * slab, 0, 0, 16 * rank + 2 * aw, bar_box);
        mbar_init(bar_y + 8 * aw, aw < 4 ? 9 : aw == 5 ? 8 : 1); mbar_fence();
        if (aw < 5) mbar_expect(bar_y + 8 * aw, aw == 4 ? 16384 : 4096);
    }
    __syncwarp();
    asm volatile("barrier.cluster.arrive.relaxed.aligned;" ::: "memory");
    asm volatile("setmaxnreg.dec.sync.aligned.u32 88;");
    const uint32_t ut = sb + SC_UT + aw * UT_STRIDE;
    sts128(ut + (mi >> 1) * (SC_ST - SC_UT) + (mi & 1) * UT_HALF + r8 * 16, 0, 0, 0, 0);
    if (lane < 16) sts128(s_bm + lane * 16, 0, 0, 0, 0);
    {
        const uint32_t dst = sb + SC_UT + swap01(g) * UT_STRIDE + (8 + 64 * rank + 8 * aw + t) * 16;
        const uint32_t rdst = mapa(dst, rank ^ 1), rbar = mapa(bar_u, rank ^ 1);
        asm volatile("barrier.cluster.wait.acquire.aligned;" ::: "memory");
        mbar_wait(bar_box);
        if (aw == 0) TSTAMP(1);
        const uint32_t src = fresh(sb + SC_RT) + aw * 4096 + (8 * mi + 4 * (r8 & 1) + (r8 >> 1)) * 32 + ((rank ^ (r8 & 1)) << 4);
        uint32_t x[8][4];
#pragma unroll
        for (int i = 0; i < 4; i++) { ldsm4t(x[i], src + 1024 * i); ldsm4t(x[4 + i], (src ^ 16) + 1024 * i); }
        asm volatile("" :: "r"(x[0][0]), "r"(x[1][0]), "r"(x[2][0]), "r"(x[3][0]) : "memory");
#pragma unroll
        for (int i = 0; i < 4; i++) st_async128(rdst + (i & 1) * UT_HALF + 32 * (i & 2), x[4 + i][0], x[4 + i][1], x[4 + i][2], x[4 + i][3], rbar);
#pragma unroll
        for (int i = 0; i < 4; i++) sts128(dst + (i & 1) * UT_HALF + 32 * (i & 2), x[i][0], x[i][1], x[i][2], x[i][3]);
    }
    bar_sync(BC_AUX, 256);
    mbar_wait_cluster(bar_u);
    if (aw == 0) TSTAMP(2);
    {
        const uint32_t a = fresh(ut) + (mi & 1) * UT_HALF + (64 * (mi >> 1) + r8) * 16;
        uint4 v = lds128(a);
#pragma unroll
        for (int i = 1; i <= 8; i++) {
            const uint4 w = lds128(a + 128 * i);
            sts128(a + 128 * i + (SC_ST - SC_UT), badd2(v.x, w.x), badd2(v.y, w.y), badd2(v.z, w.z), badd2(v.w, w.w));
            v = w;
        }
    }
    bar_arrive(BC_S + aw, 64);
    if (aw == 0) TSTAMP(3);
    {
        uint32_t ws = sb + SC_UT + t * UT_STRIDE + (g + 6) * 16, wd = sb + SC_V + t * V_STRIDE + 64 * g, sw = 16 * (g & 2);
#pragma unroll 1
        for (int k = aw; k < 25; k += 8) {
            if (k - aw == 8) {
                bar_sync(BC_KG, 384);
                if (lane < 16) sts128(sb + SC_V + aw * V_STRIDE + lane * 16, 0, 0, 0, 0);
            }
            if (k == 24) { ws -= (g & 1) * 4 * UT_STRIDE + 16 * g; wd -= (g & 1) * 4 * V_STRIDE + 64 * g; sw = 0; }
            const int h = k >= 12, a = k - 12 * h;
            const uint32_t d = wd + h * 4 * V_STRIDE + 512 * a;
            window_task(fresh(ws) + h * 4 * UT_STRIDE + 128 * a, d + sw, d + (sw ^ 32), a < 8);
        }
    }
    if (aw == 0) TSTAMP(9);
    {
        {
            const uint32_t par = (epoch & 1) ? 0x80008000u : 0u;
            uint4 v;
            for (int it = 0;; it++) {
                v = ld_rlx128(p.s->gate + 256 * aw + 8 * lane);
                v.x ^= par; v.y ^= par; v.z ^= par; v.w ^= par;
                if (__all_sync(0xffffffffu, (v.x & v.y & v.z & v.w & 0x80008000u) == 0x80008000u)) break;
                if (it > (1 << 20)) __trap();
            }
            sts128(sb + SC_GT + (lane & 1) * UT_HALF + (8 + 16 * aw + (lane >> 1)) * 16, v.x, v.y, v.z, v.w);
        }
        __syncwarp();
        if (lane == 0) { mbar_arrive(bar_v); prefetch_map(mU + 6); }
        next_epoch(p, epoch);
        if (aw == 0) TSTAMP(4);
        if (aw == 7) {
            const int row = key_row(wait_sel(p, slab >> 1, r8, key_tag(epoch)));
            if (lane < 8) asm volatile("red.shared.or.b32 [%0], %1;" :: "r"(s_bm + (row >> 5) * 4), "r"(1u << (row & 31)) : "memory");
            TSTAMP(10);
        }
        bar_sync(BC_AUX, 256);
        const uint32_t src = sb + SC_RT + ((r8 >> 1) & 1) * Y_RS + (2 * mi + (r8 & 1)) * Y_CS + (2 * aw + (r8 >> 2)) * 16;
        const int L = 2 * aw + (t >> 1);
        const int row0 = 256 * rank + 128 * (g >> 2) + 32 * (L & 3) + 16 * (g & 1) + 8 * ((g >> 1) & 1) + (L >> 2);
        __nv_bfloat16* outp = p.out + (size_t)row0 * DM + 16 * slab + 8 * (t & 1);
        const uint32_t stg = sb + SC_ST + 4096 * aw, so = (g >> 1) * 256 + (t >> 1) * 64 + (g & 1) * 32 + (t & 1) * 16;
#pragma unroll 1
        for (int s = 0; s < 4; s++) {
            const uint32_t bm = lds32(fresh(s_bm) + (16 * s + (row0 >> 5)) * 4) >> (row0 & 31);
            const bool routed = __any_sync(0xffffffffu, bm & 0x11u) || s >= LASTS;
            if (aw == s) mbar_wait_cluster(bar_y + 8 * s);
            bar_sync(BC_AUX, 256);
            const uint32_t sf = fresh(src) + 512 * s;
            uint32_t y[2][4];
            ldsm4t(y[0], sf); ldsm4t(y[1], sf + 256);
            if (routed) {
#pragma unroll
                for (int k = 0; k < 2; k++)
                    asm volatile("{ .reg .pred p; setp.ne.u32 p, %5, 0; @!p st.global.v4.u32 [%0], {%1,%2,%3,%4}; @p red.relaxed.gpu.global.add.noftz.v4.bf16x2 [%0], {%1,%2,%3,%4}; }"
                                 :: "l"(outp + (size_t)(512 * s + 4 * k) * DM), "r"(y[k][0]), "r"(y[k][1]), "r"(y[k][2]), "r"(y[k][3]), "r"(bm & (1u << (4 * k))) : "memory");
            } else {
                sts128(stg + so + 1024 * s, y[0][0], y[0][1], y[0][2], y[0][3]); sts128(stg + so + 1024 * s + 128, y[1][0], y[1][1], y[1][2], y[1][3]);
                asm volatile("fence.proxy.async.shared::cta;" ::: "memory");
                __syncwarp();
                if (lane == 0) asm volatile("cp.async.bulk.tensor.5d.global.shared::cta.bulk_group [%0, {%2, %3, %3, %3, %4}], [%1];"
                                            :: "l"(mU + 6), "r"(stg + 1024 * s), "r"(16 * slab), "r"(0), "r"(512 * s + 256 * rank + 64 * (aw & 1) + (aw >> 1)) : "memory");
            }
            if (aw == 0) TSTAMP(16 + s);
        }
        if (lane == 0) { asm volatile("cp.async.bulk.commit_group;" ::: "memory"); asm volatile("cp.async.bulk.wait_group.read 0;" ::: "memory"); }
        if (aw == 0) TFLUSH();
    }
}

__device__ __forceinline__ void conv_main(const Params& p, uint32_t sb, int warp, int lane, int bid, unsigned epoch, uint32_t (&w)[12]) {
    asm volatile("setmaxnreg.inc.sync.aligned.u32 168;");
    const int g = lane >> 2, t = lane & 3, mi = lane >> 3, r8 = lane & 7;
    const int rank = bid & 1;
    const uint32_t bar_y = sb + SC_MISC, bar_v = bar_y + 40;
    next_epoch(p, epoch);
    if (warp < 4) {
        asm volatile("" :: "r"(w[0]), "r"(w[2]), "r"(w[4]), "r"(w[6]), "r"(w[8]), "r"(w[10]) : "memory");
        bar_arrive(BC_KG, 384);
    } else {
        const uint4* src = p.s->kp + (4 * bid + warp - 4) * 128 + lane;
        for (int it = 0;; it++) {
            uint32_t bad = 0;
#pragma unroll
            for (int i = 0; i < 4; i++) { const uint4 v = ld_rlx128(src + 32 * i); w[3 * i] = v.x; w[3 * i + 1] = v.y; w[3 * i + 2] = v.z; bad |= v.w ^ ~epoch; }
            const bool ok = __all_sync(0xffffffffu, bad == 0);
            if (ok) break;
            if (it > (1 << 20)) __trap();
        }
    }
    if ((warp & 3) == 0) TSTAMP(5 + (warp >> 2));
    {
        const uint32_t kt = sb + SC_KT + warp * KT_BYTES;
        uint32_t e[4], x[4], re[4], rx[4];
#pragma unroll
        for (int i = 0; i < 4; i++) {
            e[i] = w[6 * (i >> 1) + (i & 1)]; x[i] = w[6 * (i >> 1) + 2 + (i & 1)];
            re[i] = __shfl_sync(0xffffffffu, e[i], lane + 31);
            rx[i] = __shfl_sync(0xffffffffu, x[i], lane + (i == 0 && lane == 29 ? 5 : 1 + 2 * t));
        }
        asm volatile("stmatrix.sync.aligned.m8n8.x4.trans.shared.b16 [%0], {%1,%2,%3,%4};"
                     :: "r"(kt + (r8 < 4 ? (KT_D + 7) * 4 + 64 * r8 + 16 * mi : 716 * 4)), "r"(w[4]), "r"(w[5]), "r"(w[10]), "r"(w[11]) : "memory");
        if (lane == 2) {
            sts32(kt + (KT_C + 78) * 4, w[4] & 0xffffu);
            sts128(kt + (KT_T + 2) * 4, 0, w[4] & 0xffffu, __byte_perm(w[4], 0, 0x1010), w[4] << 16);
        }
        if (lane == 29) x[3] = bsub2(x[3], rx[0] & 0xffffu);
#pragma unroll
        for (int i = 0; i < 4; i++) {
            sts64(kt + (16 + 64 * i) * 4 + 8 * lane, __byte_perm(e[i], lane ? re[i] : i ? re[i - 1] : 0, 0x5432), e[i]);
            const uint32_t aa = __byte_perm(x[i], 0, 0x3232);
            if (t < 2) sts128(kt + (272 + 64 * i + 8 * g + 4 * t) * 4, i == 0 && lane == 0 ? __byte_perm(x[0], re[3], 0x5432) : aa, aa, x[i],
                              __byte_perm(lane != 29 ? rx[i] : i < 3 ? rx[(i + 1) & 3] : 0, x[i], 0x5432));
            else sts32(kt + (KT_C - 50 + 8 * i + 32 * t + g) * 4, x[i]);
        }
    }
    asm volatile("barrier.cluster.wait.acquire.aligned;" ::: "memory");
    bar_sync(BC_S + swap01(warp), 64);
    if ((warp & 3) == 0) TSTAMP(7 + (warp >> 2));
    {
        const uint32_t ut = fresh(sb + SC_UT) + swap01(warp) * UT_STRIDE, kt = fresh(sb + SC_KT) + warp * KT_BYTES;
        uint32_t u1 = ut + (mi & 1) * UT_HALF + (8 + r8) * 16 + (mi >> 1) * 128;
        auto dup = [&](uint32_t v) { return v ^ p.zero; };
        uint32_t kp = kt + (16 + g - 2 * t) * 4;
        float acc[16][4];
        {
            const uint32_t c0 = lds32(kp + 2048), c1 = lds32(kp + 2080), c2 = lds32(kp + 2016), c3 = dup(c0);
            const uint32_t e0 = lds32(kp + (KT_T - 16) * 4), e1 = lds32(kp + (KT_T - 8) * 4), e2 = lds32(kp + (KT_T - 24) * 4), e3 = dup(e0);
            const uint32_t f0 = dup(e1), f1 = lds32(kp + KT_T * 4);
            const uint32_t uo = ut + UT_HALF + (7 + lane) * 16;
#pragma unroll
            for (int i = 0; i < 16; i++) { acc[i][0] = acc[i][1] = acc[i][2] = acc[i][3] = 0.f; }
#pragma unroll
            for (int mu = 0; mu < 8; mu += 4) {
                uint32_t b[4];
                ldsm4(b, uo + 128 * mu);
#pragma unroll
                for (int k = 0; k < 4; k++) mma_bf8(acc[mu + 8 + k], f0, f1, b[k]);
            }
#pragma unroll
            for (int mu = 0; mu < 12; mu += 2) {
                uint32_t b[4];
                ldsm4(b, u1 + 128 * mu);
                mma_bf(acc[mu + 4], c0, c1, c2, c3, b[0], b[1]);
                mma_bf(acc[mu + 5], c0, c1, c2, c3, b[2], b[3]);
                if (mu < 8) { mma_bf(acc[mu + 8], e0, e1, e2, e3, b[0], b[1]); mma_bf(acc[mu + 9], e0, e1, e2, e3, b[2], b[3]); }
            }
        }
        {
            float M[8][4];
#pragma unroll
            for (int i = 0; i < 8; i++) { M[i][0] = M[i][1] = M[i][2] = M[i][3] = 0.f; }
            uint32_t s[8][4], a3[4];
            const uint32_t kb = kp, ub = dup(u1), uc = u1 + (mi >> 1) * 128;
            auto frag = [&](uint32_t (&a)[4], uint32_t x) { a[0] = lds32(x); a[1] = lds32(x + 32); a[2] = lds32(x - 32); a[3] = dup(a[0]); };
            frag(a3, kp + 1536);
#pragma unroll
            for (int i = 0; i < 8; i++) ldsm4(s[i], u1 + (SC_ST - SC_UT) + 256 * i);
            __syncwarp();
#pragma unroll 1
            for (uint32_t ko = 0, uo = 0; ko != 512;) {
                uint32_t a2[4], a1[4], a0[4], b[4][4];
                ko = fresh(ko); uo = fresh(uo);
                kp = kb + ko; u1 = ub + uo;
                const uint32_t up = uc + uo;
                ko += 64; uo -= 16;
                frag(a2, kp + 1024);
#pragma unroll
                for (int i = 0; i < 4; i++) ldsm4(b[i], up + 512 * i);
                frag(a1, kp + 512); frag(a0, kp);
                kp += 64; u1 -= 16;
#pragma unroll
                for (int i = 0; i < 7; i++) mma_bf(acc[2 * i + 2], a3[0], a3[1], a3[2], a3[3], s[i][0], s[i][1]);
#pragma unroll
                for (int e = 0; e < 4; e++) a3[e] = bsub2(a2[e], a3[e]);
#pragma unroll
                for (int i = 0; i < 7; i++) mma_bf(acc[2 * i + 3], a2[0], a2[1], a2[2], a2[3], s[i][2], s[i][3]);
#pragma unroll
                for (int i = 0; i < 7; i++) mma_bf(M[i + 1], a3[0], a3[1], a3[2], a3[3], b[i >> 1][2 * (i & 1)], b[i >> 1][2 * (i & 1) + 1]);
                frag(a3, kp + 1536);
#pragma unroll
                for (int i = 0; i < 8; i++) mma_bf(acc[2 * i], a1[0], a1[1], a1[2], a1[3], s[i][0], s[i][1]);
#pragma unroll
                for (int e = 0; e < 4; e++) a1[e] = bsub2(a0[e], a1[e]);
#pragma unroll
                for (int i = 0; i < 8; i++) { mma_bf(acc[2 * i + 1], a0[0], a0[1], a0[2], a0[3], s[i][2], s[i][3]); ldsm4(s[i], u1 + (SC_ST - SC_UT) + 256 * i); }
#pragma unroll
                for (int i = 0; i < 8; i++) mma_bf(M[i], a1[0], a1[1], a1[2], a1[3], b[i >> 1][2 * (i & 1)], b[i >> 1][2 * (i & 1) + 1]);
            }
            u1 = ub;
#pragma unroll
            for (int i = 0; i < 8; i++)
#pragma unroll
                for (int c = 0; c < 4; c++) { acc[2 * i][c] += M[i][c]; acc[2 * i + 1][c] -= M[i][c]; }
        }
        if ((warp & 3) == 0) TSTAMP(11 + (warp >> 2));
        mbar_wait(bar_v);
        const uint32_t vt = fresh(sb + SC_V) + swap01(warp) * V_STRIDE;
        const uint32_t g1 = fresh(u1) - ut + sb + SC_GT;
        const uint32_t ydst = sb + SC_RT + rank * Y_RS + warp * Y_CS + lane * 16;
        const uint32_t ydr = mapa(ydst, rank ^ 1), ybr = mapa(bar_y, rank ^ 1);
        auto stairs = [&](auto R) {
        uint32_t ug[2][2][4];
        auto ld_ug = [&](int i) { ldsm4t(ug[i & 1][0], u1 + 256 * i); ldsm4t(ug[i & 1][1], g1 + 256 * i); };
        auto ship = [&](int i) {
            const uint32_t (&u)[4] = ug[i & 1][0], (&gg)[4] = ug[i & 1][1];
            const uint32_t y0 = gmix(gg[0], acc[2 * i][0], acc[2 * i][1], u[0]), y1 = gmix(gg[1], acc[2 * i][2], acc[2 * i][3], u[1]);
            const uint32_t y2 = gmix(gg[2], acc[2 * i + 1][0], acc[2 * i + 1][1], u[2]), y3 = gmix(gg[3], acc[2 * i + 1][2], acc[2 * i + 1][3], u[3]);
            if ((i & 1) != R.value) st_async128(ydr + 512 * (i >> 1), y0, y1, y2, y3, ybr + 8 * (i >> 1));
            else asm volatile("{ .reg .pred q; setp.eq.u32 q, %6, 0; st.shared.v4.u32 [%0], {%2,%3,%4,%5}; bar.warp.sync 0xffffffff; @q mbarrier.arrive.shared::cta.b64 _, [%1]; }"
                              :: "r"(ydst + 512 * (i >> 1)), "r"(bar_y + 8 * (i >> 1)), "r"(y0), "r"(y1), "r"(y2), "r"(y3), "r"(lane) : "memory");
        };
        const uint32_t VD = vt + (VC_OFF - 400 - 16 * t) * 4 + (8 * g ^ 16 * (-t & 2)), VD2 = vt + (VC_OFF - 415 - 16 * t) * 4 + (8 * g ^ 16 * (~t & 2));
        uint2 bd[10];
        uint32_t x[2][4][4];
        auto ld4 = [&](uint32_t (&v)[4], int dl) { const uint2 w = lds64(VD + 256 * dl); v[0] = w.x; v[1] = w.y; v[2] = lds32(VD2 + 256 * dl); v[3] = dup(w.x); };
        auto mm4 = [&](const uint32_t (&v)[4], int dl) {
#pragma unroll
            for (int s = dl & 1; s < 10; s += 2) if ((dl + s) / 2 < 16) mma_bf(acc[(dl + s) / 2], v[0], v[1], v[2], v[3], bd[s].x, bd[s].y);
        };
        const uint32_t KE = kt + (KT_D + g + t) * 4, VE = vt + (VE_BASE - 912 - 16 * t) * 4 + (8 * g ^ 16 * (~t & 2));
        uint32_t b0[8], b1[8];
        auto ld8 = [&](uint32_t (&v)[4], int dl) { const uint2 w = lds64(VE + 512 * dl), z = lds64(VE + 512 * dl - 256); v[0] = w.x; v[1] = w.y; v[2] = z.x; v[3] = z.y; };
        auto mm8 = [&](const uint32_t (&v)[4], int dl, int lo, int hi) {
#pragma unroll
            for (int s = 0; s < 8; s++) if (dl + s >= lo && dl + s < hi) mma_bf(acc[dl + s], v[0], v[1], v[2], v[3], b0[s], b1[s]);
        };
        ld_ug(0); ld4(x[0][0], 6);
#pragma unroll
        for (int s = 0; s < 10; s++) bd[s] = lds64(kt + (KT_C + 2 * g + 2 * t + 8 * s) * 4);
        ld_ug(1);
        ship(0);
        mm4(x[0][0], 6);
        uint32_t e[4][4];
#pragma unroll
        for (int k = 1; k < 6; k++) {
#pragma unroll
            for (int j = 0; j < 4; j++) ld4(x[k & 1][j], 4 * k + 3 + j);
            ld_ug(k + 1);
            if (k == 3) {
#pragma unroll
                for (int s = 0; s < 8; s++) { b0[s] = lds32(KE + 32 * s); b1[s] = lds32(KE + 32 * s + 16); }
            }
            ship(k);
#pragma unroll
            for (int j = 0; j < 4; j++) {
                mm4(x[k & 1][j], 4 * k + 3 + j);
                if (k == 3) { uint32_t v[4], z[4]; ld8(e[j], 8 + j); ld8(v, 12 + j); ld4(z, 30 - j); mm8(v, 12 + j, 12, 16); mm8(e[j], 8 + j, 8, 12); mm4(z, 30 - j); }
                if (k == 5) { ld8(e[j], 8 + j + p.zero); mm8(e[j], 8 + j, 12, 16); }
            }
        }
        ld_ug(7);
        ship(7 - R.value); ship(6 + R.value);
        };
        if (rank) stairs(std::integral_constant<int, 1>()); else stairs(std::integral_constant<int, 0>());
        if ((warp & 3) == 0) TSTAMP(14 + (warp >> 2)); else TSTAMP(21 + warp);
    }
}

constexpr int SF_WD = 147456;
constexpr int SF_H = 81920;
constexpr int SF_RED = 131072;
constexpr int SF_XS = 221184;
constexpr int SF_MISC = SF_XS + 8 * 1168;
constexpr int SF_KG = SF_MISC - 10 * KG_STAGE;
constexpr int SF_WR = SF_KG - 2304;
constexpr int FB_X = 64, FB_RDONE = 72, FB_FREE = 80, FB_KDONE = 88, FB_KEYS = 96, FB_W = 112, FB_D = FB_W + 72, FB_H = FB_D + 96, FS_PART = 512, FS_TOK = 896;
enum { BAR_F = 6, BAR_R = 7, BAR_GU = 8, BAR_RED = 9 };
static_assert(NPRE <= 10 && SF_KG % 128 == 0 && SF_KG >= 7 * 24576 && SF_WR - 4 * 9216 >= 5 * 24576 && SF_WR - 6 * 9216 >= 5 * 16384, "layout");

__device__ __forceinline__ void ffn_front(const Params& p, const CUtensorMap* maps, uint32_t sb, int warp, int lane, int f, unsigned epoch) {
    const unsigned t0 = clock32();
    const int g = lane >> 2, t = lane & 3, mi = lane >> 3, r8 = lane & 7;
    const bool isx = f < NX;
    const int nrw = f < 8 ? 6 : 4, r0 = f < 8 ? 48 * f : 128 + 32 * f;
    const int rw = warp < 12 ? 13 - warp : warp ^ (warp < 14 ? 10 : 15);
    const uint32_t bar_row = sb + SF_MISC  , bar_x = bar_row + FB_X;
    const uint32_t s_part = bar_row + FS_PART  , s_tok = bar_row + FS_TOK  ;
    const uint32_t rows = sb + SF_WR - 9216 * (rw + 1);
    if (lane == 0) {
        mbar_init(bar_row + 8 * rw, 1); mbar_fence();
        if (rw < nrw) { mbar_expect(bar_row + 8 * rw, 9216); until(t0, RDELAY); bulk_g2s(rows, p.u + (size_t)(r0 + 8 * rw) * DM, 9216, bar_row + 8 * rw); }
        else if (rw >= 6) { mbar_expect(bar_row + 8 * rw, 1152); bulk_g2s(sb + SF_WR + (rw & 1) * 1152, (rw & 1) ? p.gatew : p.wr, 1152, bar_row + 8 * rw); }
        if (warp >= 10) {
#pragma unroll 1
            for (int i = warp - 10; i < 39; i += 6) mbar_init(bar_x + 8 * i, i == 1 ? nrw : i == 2 ? 4 : 1);
        }
        mbar_fence();
    }
    const int ks0 = isx ? 4 * f : 6 * f - 72, nt = isx ? 4 : 6;
    if (warp == 13) {
        stg128(p.s->keys + (lane >> 1) * 128 + 2 * f + (lane & 1), 0, 0, 0, 0);
        if (lane < 8 && isx && !(f & 1)) st_rlx32(&p.s->sel[32 * f + lane], 0);
    }
    __syncwarp();
    bar_sync(BAR_F, f < 12 ? 256 : 192);
    bar_arrive(0, NTHR);
    if (warp == 15) TSTAMP(1);

    if (warp == 12) {
        if (lane == 0) {
            const CUtensorMap* m = maps + (isx ? 1 : 3);
            prefetch_map(m); prefetch_map(m + 1);
            unsigned tb = t0 + WDELAY;
#pragma unroll 1
            for (int n = 0; n < 18; n++) {
                if (n == NPRE) { mbar_wait(bar_row + FB_KEYS); mbar_wait(bar_row + FB_KDONE); tb = clock32() + RESUME; }
                until(tb, 0); tb += WGAP;
                const uint32_t b = bar_row + FB_W + 8 * (n >> 1);
                if (!(n & 1)) mbar_expect(b, nt * 4096);
                tma3d(sb + n * nt * 2048, m + (n & 1), 0, 64 * (n >> 1), ks0 >> 1, b);
            }
            TSTAMP(12);
            if (isx) {
                prefetch_map(maps + 5);
#pragma unroll 1
                for (int n = 0; n < 12; n++) {
                    until(tb, 0); tb += DGAP;
                    if (n == 6) mbar_wait(bar_row + FB_FREE);
                    mbar_expect(bar_row + FB_D + 8 * n, 12288);
                    tma2d(sb + (n < 6 ? SF_WD : -6 * 12288) + n * 12288, maps + 5, 32 * (f >> 1), 2304 * (f & 1) + 192 * n, bar_row + FB_D + 8 * n);
                }
                TSTAMP(13);
            }
        }
    } else if (warp == 13) {
        const uint32_t tag = key_tag(epoch), par = (epoch & 1) ? 0u : 0x8000u;
        next_epoch(p, epoch);
        bar_sync(BAR_R, 32 * (nrw + 1));
        TSTAMP(3);
        uint32_t k[16];
        const uint2 va = lds64(fresh(s_part) + lane * 8), vb = lds64(fresh(s_part) + 256 + lane * 8);
        const bool two = nrw > 4 && lane < 16;
        {
            auto mk = [&](uint32_t r, int row) { const uint32_t rb = pack_bf16(0.f, __uint_as_float(r)); return (rb ^ (((int)rb >> 31) & 0x7fff0000u) ^ 0x80000000u) | tag | (uint32_t)(2047 - row); };
            uint32_t ka = mk(va.x, r0 + lane), kb = two ? mk(vb.x, r0 + 32 + lane) : 0;
#pragma unroll 1
            for (int h = 0; h < 2; h++)
#pragma unroll
                for (int r = 0; r < 4; r++) {
                    const uint32_t m = __reduce_max_sync(0xffffffffu, max(ka, kb));
                    if (ka == m) ka = 0;
                    if (kb == m) kb = 0;
                    if ((lane & 1) == h) k[r] = m;
                }
        }
        asm volatile("st.relaxed.gpu.global.v4.u32 [%0], {%1,%2,%3,%4};" :: "l"(p.s->keys + (lane >> 1) * 128 + 2 * f + (lane & 1)), "r"(k[0]), "r"(k[1]), "r"(k[2]), "r"(k[3]) : "memory");
        TSTAMP(4);
        if (RESUME >= 0 && lane == 0) mbar_arrive(bar_row + FB_KEYS);
        {
            const uint32_t gb = pack_bf16(sigmoidf_(rbf(__uint_as_float(va.y))), sigmoidf_(rbf(__uint_as_float(vb.y)))) | par | (par << 16);
            asm volatile("st.relaxed.gpu.global.u16 [%0], %1;" :: "l"(p.s->gate + r0 + lane), "h"((unsigned short)gb) : "memory");
            if (two) asm volatile("st.relaxed.gpu.global.u16 [%0], %1;" :: "l"(p.s->gate + r0 + 32 + lane), "h"((unsigned short)(gb >> 16)) : "memory");
        }
        const uint4* src = p.s->keys + (f & 15) * 128 + lane;
        for (int it = 0;; it++) {
            uint32_t bad = 0;
#pragma unroll
            for (int i = 0; i < 4; i++) {
                const uint4 x = ld_rlx128(src + (i < 3 || lane < 24 ? 32 * i : 64));
                k[i] = x.x; k[4 + i] = x.y; k[8 + i] = x.z; k[12 + i] = x.w;
                bad |= x.x ^ tag;
            }
            const bool ok = __all_sync(0xffffffffu, (bad & 0xf800u) == 0);
            if (it < 8) TSTAMP(it < 4 ? 16 + it : 20 + it);
            if (ok) break;
            if (it > (1 << 20)) __trap();
        }
        TSTAMP(5);
        mbar_wait(bar_row + FB_KDONE);
        if (lane == 0) { if (RESUME < 0) mbar_arrive(bar_row + FB_KEYS); mbar_expect(bar_x, 8 * 1152); }
        uint32_t key = 0;
#pragma unroll 1
        for (int r = 0; r < 8; r++) {
            const uint32_t m = __reduce_max_sync(0xffffffffu, max(max(k[0], k[1]), max(k[2], k[3])));
#pragma unroll
            for (int i = 0; i < 4; i++) {
                const bool pop = k[i] == m;
                k[i] = pop ? k[4 + i] : k[i]; k[4 + i] = pop ? k[8 + i] : k[4 + i]; k[8 + i] = pop ? k[12 + i] : k[8 + i]; k[12 + i] = pop ? 0 : k[12 + i];
            }
            if (lane == 0) bulk_g2s(sb + SF_XS + r * 1168, p.u + (size_t)key_row(m) * DM, 1152, bar_x);
            if (r8 == r) key = m;
        }
        const int row = key_row(key);
        TSTAMP(6);
        if (isx) {
            if (!(f & 1)) {
                __nv_bfloat16* o = p.out + (size_t)row * DM + 16 * f + 8 * mi;
                asm volatile("st.relaxed.gpu.global.v4.u32 [%0], {%1,%1,%1,%1};" :: "l"(o), "r"(0) : "memory");
                if (__any_sync(0xffffffffu, ld_rlx32(o) != 0)) __trap();
                if (lane < 8) st_rlx32(&p.s->sel[32 * f + lane], key);
            } else wait_sel(p, f >> 1, r8, tag);
            uint32_t gb;
            for (int it = 0;; it++) {
                asm volatile("ld.relaxed.gpu.global.u16 %0, [%1];" : "=r"(gb) : "l"(p.s->gate + row) : "memory");
                gb ^= par;
                if (!(gb & 0x8000u)) break;
                if (it > (1 << 20)) __trap();
            }
            const uint32_t rb = key ^ 0x80000000u, rv = (rb ^ (((int)rb >> 31) & 0x7fff0000u)) & 0xffff0000u;
            sts64(s_tok + r8 * 8, row, __float_as_uint(rbf(1.0f - bf_lo(gb)) * rbf(sigmoidf_(__uint_as_float(rv)))));
            __syncwarp();
            TSTAMP(7);
            bar_arrive(BAR_RED, 416);
        }
    } else {
        if (rw < nrw) {
            float c[2][4];
#pragma unroll
            for (int i = 0; i < 2; i++) { c[i][0] = c[i][1] = c[i][2] = c[i][3] = 0.f; }
            mbar_wait(bar_row + 48); mbar_wait(bar_row + 56);
            const uint32_t b = fresh(sb + SF_WR) + (g & 1) * 1152 + (g >> 2) * 64 + t * 16 + (g & 2) * 2;
            uint32_t w[18][2];
#pragma unroll
            for (int kb = 0; kb < 18; kb++) { const uint32_t o = ((kb & 1) ? b ^ 64 : b) + 128 * (kb >> 1); w[kb][0] = lds32(o); w[kb][1] = lds32(o + 8); }
            mbar_wait(bar_row + 8 * rw);
            if (warp == 15) TSTAMP(2);
            const uint32_t a = fresh(rows) + g * 1152 + (g & 1) * 64 + t * 16;
#pragma unroll
            for (int kb = 0; kb < 18; kb++) {
                const uint4 x = lds128(((kb & 1) ? a ^ 64 : a) + 128 * (kb >> 1));
                mma_bf(c[kb & 1], x.x, x.y, x.z, x.w, w[kb][0], w[kb][1]);
            }
            const float sr = c[0][0] + c[1][0] + __shfl_down_sync(0xffffffffu, c[0][2] + c[1][2], 1);
            const float sg = c[0][1] + c[1][1] + __shfl_down_sync(0xffffffffu, c[0][3] + c[1][3], 1);
            if (t == 2 * (g & 1)) sts64(s_part + (8 * rw + g) * 8, __float_as_uint(sr), __float_as_uint(sg));
            __syncwarp();
            bar_arrive(BAR_R, 32 * (nrw + 1));
        }
    }
}

__device__ __forceinline__ void ffn_work(const Params& p, uint32_t sb, int warp, int lane, int f, unsigned epoch) {
    const int g = lane >> 2, t = lane & 3, mi = lane >> 3, r8 = lane & 7;
    const bool isx = f < NX;
    const int ks0 = isx ? 4 * f : 6 * f - 72, nt = isx ? 4 : 6;
    const uint32_t bar_x = sb + SF_MISC + FB_X, bar_free = sb + SF_MISC + FB_FREE, bar_w = sb + SF_MISC + FB_W, bar_d = sb + SF_MISC + FB_D, bar_h = sb + SF_MISC + FB_H, s_tok = sb + SF_MISC + FS_TOK;
    next_epoch(p, epoch);
    {
        if (warp < nt) {
            float ag[2][4], au[2][4];
#pragma unroll
            for (int i = 0; i < 2; i++) { ag[i][0] = ag[i][1] = ag[i][2] = ag[i][3] = 0.f; au[i][0] = au[i][1] = au[i][2] = au[i][3] = 0.f; }
            const uint32_t wb = sb + (warp >> 1) * 4096 + (r8 + 8 * (mi >> 1)) * 64 + (((2 * (warp & 1) + (mi & 1)) ^ (r8 >> 1)) << 4);
            const uint32_t xb = sb + SF_XS + r8 * 1168 + mi * 16;
            mbar_wait(bar_x);
            if (warp == 0) TSTAMP(8);
#pragma unroll 1
            for (int n = 0; n < 9; n++) {
                mbar_wait(bar_w + 8 * n);
                const uint32_t wk = fresh(wb) + n * nt * 4096, xk = fresh(xb) + 128 * n;
                uint32_t x[4];
#pragma unroll
                for (int s = 0; s < 4; s++) {
                    uint32_t a[4], b[4];
                    if (!(s & 1)) ldsm4(x, xk + 32 * s);
                    ldsm4t(a, wk + 1024 * s); ldsm4t(b, wk + 1024 * s + nt * 2048);
                    mma_bf(ag[s & 1], a[0], a[1], a[2], a[3], x[2 * (s & 1)], x[2 * (s & 1) + 1]);
                    mma_bf(au[s & 1], b[0], b[1], b[2], b[3], x[2 * (s & 1)], x[2 * (s & 1) + 1]);
                }
                asm volatile("" :: "f"(ag[0][0]), "f"(ag[1][0]), "f"(au[0][0]), "f"(au[1][0]) : "memory");
                if (n == 4 && lane == 0 && isx) mbar_arrive(bar_free);
            }
            if (warp == 0) TSTAMP(9);
            float h[4];
#pragma unroll
            for (int c = 0; c < 4; c++) {
                const float gv = rbf(ag[0][c] + ag[1][c]);
                h[c] = rbf(gv * sigmoidf_(gv)) * rbf(au[0][c] + au[1][c]);
            }
            uint32_t h0, h1;
            asm("movmatrix.sync.aligned.m8n8.trans.b16 %0, %1;" : "=r"(h0) : "r"(pack_bf16(h[0], h[1])));
            asm("movmatrix.sync.aligned.m8n8.trans.b16 %0, %1;" : "=r"(h1) : "r"(pack_bf16(h[2], h[3])));
            if (h0 == 0) h0 = 0x8000u;
            asm volatile("{ .reg .b64 v; mov.b64 v, {%1, %2}; st.relaxed.gpu.global.b64 [%0], v; }" :: "l"(p.s->h + ((epoch & 1) * 288 + ks0 + warp) * 32 + lane), "r"(h0), "r"(h1) : "memory");
        }
        if (isx) {
            bar_sync(BAR_GU, 384);
            if (warp == 0) TSTAMP(10);
            uint2 hb[12];
            const uint32_t hs = sb + SF_H + warp * 3072;
            const uint2* hsrc = p.s->h + ((__shfl_sync(0xffffffffu, epoch, 0) & 1) * 288 + 144 * (f & 1) + 12 * warp) * 32;
            for (int it = 0;; it++) {
                if (lane == 0) { mbar_expect(bar_h + 8 * warp, 3072); bulk_g2s(hs, hsrc, 3072, bar_h + 8 * warp); }
                mbar_wait(bar_h + 8 * warp, it & 1);
                const uint32_t hf = fresh(hs) + lane * 8;
                uint32_t mn = 0xffffffffu;
#pragma unroll
                for (int s = 0; s < 12; s++) { hb[s] = lds64(hf + 256 * s); mn = min(mn, hb[s].x); }
                if (__all_sync(0xffffffffu, mn != 0)) break;
                if (it > (1 << 16)) __trap();
            }
            if (warp == 0) TSTAMP(11);
            mbar_wait(bar_d + 8 * warp);
            if (warp == 11) TSTAMP(14);
            float ad[2][2][4];
#pragma unroll
            for (int i = 0; i < 4; i++) { ad[i >> 1][i & 1][0] = ad[i >> 1][i & 1][1] = ad[i >> 1][i & 1][2] = ad[i >> 1][i & 1][3] = 0.f; }
            const uint32_t wd = fresh(sb) + (warp < 6 ? SF_WD : -6 * 12288) + warp * 12288 + (r8 + 8 * (mi >> 1)) * 64 + (((mi & 1) ^ (r8 >> 1)) << 4);
#pragma unroll
            for (int s = 0; s < 12; s++) {
                uint32_t a[4], b[4];
                ldsm4t(a, wd + 1024 * s); ldsm4t(b, (wd ^ 32) + 1024 * s);
                mma_bf(ad[0][s & 1], a[0], a[1], a[2], a[3], hb[s].x, hb[s].y);
                mma_bf(ad[1][s & 1], b[0], b[1], b[2], b[3], hb[s].x, hb[s].y);
            }
            const uint32_t rd = sb + SF_RED + warp * 1152 + (72 * t + g) * 4;
#pragma unroll
            for (int i = 0; i < 8; i++) sts32(rd + (i >> 2) * 64 + (i & 1) * 144 + ((i >> 1) & 1) * 32, __float_as_uint(ad[i >> 2][0][i & 3] + ad[i >> 2][1][i & 3]));
            bar_sync(BAR_RED, 416);
            if (warp < 4) {
                const int tid = 32 * warp + lane;
                const uint32_t rs = fresh(sb + SF_RED) + (tid >> 4) * 144 + (tid & 15) * 8;
                const uint2 tk = lds64(fresh(s_tok) + (tid >> 4) * 8);
                float x = 0.f, y = 0.f;
#pragma unroll
                for (int w = 0; w < 12; w++) { const uint2 v = lds64(rs + w * 1152); x += __uint_as_float(v.x); y += __uint_as_float(v.y); }
                asm volatile("red.relaxed.gpu.global.add.noftz.bf16x2 [%0], %1;" :: "l"(p.out + (size_t)tk.x * DM + 32 * (f >> 1) + 2 * (tid & 15)),
                             "r"(pack_bf16(x * __uint_as_float(tk.y), y * __uint_as_float(tk.y))) : "memory");
            }
            if (warp == 0) TSTAMP(15);
        }
        if (warp == 0) TFLUSH();
    }
}

constexpr int SMEM_BYTES = 232448;
static_assert(SF_MISC + 1024 <= 232192, "layout");

struct Maps { CUtensorMap m[7]; };

__global__ void __cluster_dims__(2, 1, 1) __launch_bounds__(NTHR, 1)
fused_kernel(const Params p, const __grid_constant__ Maps maps) {
    extern __shared__ __align__(1024) uint8_t smem_raw[];
    uint32_t q[8];
    {
        const int b = blockIdx.x, x = threadIdx.x, rc = 4 * b + max(b - 84, 0) - 288 + (x >> 6);
        const int cv = (b - NCONV) >> 31, ca = 8 * b + ((x >> 5) & 3), cb = 2 * rc - (rc & 3) + 4;
        const uint32_t ch = (ca & cv) | (cb & ~cv), o = NST * ch + 2 * ((x & 31) + ((x >> (cv & 2)) & 32));
        const bool c = x < (b < 84 ? 256 : 320);
        q[6] = ldg16_if(c, p.logdt + ch);
        q[2] = ldg32_if(c, p.Bre + o); q[3] = ldg32_if(c, p.Bim + o); q[4] = ldg32_if(c, p.Cre + o); q[5] = ldg32_if(c, p.Cim + o); q[0] = ldg32_if(c, p.Are + o); q[1] = ldg32_if(c, p.Aim + o);
        q[7] = ldg16_if(c, p.Dskip + ch);
    }
    const unsigned epoch = ld_rlx32(&p.s->epoch[blockIdx.x * 16 + (threadIdx.x >> 5)]);
    const uint32_t sb = __shfl_sync(0xffffffffu, smem_u32(smem_raw), 0);
    const int warp = __shfl_sync(0xffffffffu, threadIdx.x >> 5, 0), bid = __shfl_sync(0xffffffffu, blockIdx.x, 0);
    const int lane = __shfl_sync(0xffffffffu, threadIdx.x & 31, threadIdx.x);
    const bool conv = bid < NCONV;
    const int f = bid - NCONV;
    uint32_t w[12];
    if (warp < (f < 12 ? 8 : 10)) {
        const int half = conv ? warp >> 2 : warp & 1, pr = conv ? warp & 3 : warp >> 1;
        const int rc = 4 * f + max(f - 12, 0) + pr;
        const uint32_t stage = sb + (conv ? SC_KG : SF_KG) + warp * KG_STAGE;
        uint4* const kp = p.s->kp + rc * 128 + lane;
        kgen(q, sb, half, stage, stage + (conv ? 4 : 1) * KG_STAGE, 1 + pr, lane, w, [&] {
            sts128z_if(conv && lane < 20, sb + SC_KT + warp * KT_BYTES + lane * 16 + (lane < 4 ? 0 : lane < 14 ? 2048 : 2288));
            stg128z_if(!conv, kp + 64 * half); stg128z_if(!conv, kp + 64 * half + 32);
            stg128z_if(!conv && warp < (f < NX ? 4 : 6), (uint4*)(p.s->h + ((lane >> 4) * 288 + (f < NX ? 4 * f : 6 * f - 72) + warp) * 32) + (lane & 15));
            if (conv) asm volatile("barrier.cluster.arrive.relaxed.aligned;" ::: "memory");
        });
        if (conv) { conv_main(p, sb, warp, lane, bid, epoch, w); return; }
        {
            if (!half) {
#pragma unroll
                for (int i = 0; i < 4; i++) asm volatile("st.relaxed.gpu.global.v4.u32 [%0], {%1,%2,%3,%4};" :: "l"(kp + 32 * i), "r"(w[3 * i]), "r"(w[3 * i + 1]), "r"(w[3 * i + 2]), "r"(~epoch) : "memory");
            }
            if (warp == 0) TSTAMP(22);
            if (warp == 2) TSTAMP(23);
            bar_sync(0, NTHR);
            if (warp == 0 && lane == 0) mbar_arrive(sb + SF_MISC + FB_KDONE);
        }
    } else if (conv) {
        conv_aux(p, maps.m, sb, warp - 8, lane, bid, epoch);
        return;
    } else {
        ffn_front(p, maps.m, sb, warp, lane, f, epoch);
        if (warp >= 12) return;
    }
    __syncwarp();
    ffn_work(p, sb, warp, lane, f, epoch);
}

typedef CUresult (*EncodeFn)(CUtensorMap*, CUtensorMapDataType, cuuint32_t, void*, const cuuint64_t*, const cuuint64_t*, const cuuint32_t*, const cuuint32_t*,
                             CUtensorMapInterleave, CUtensorMapSwizzle, CUtensorMapL2promotion, CUtensorMapFloatOOBfill);

void make_map(EncodeFn fn, CUtensorMap* m, const void* base, int rank, const cuuint64_t* dims, const cuuint64_t* strides, const cuuint32_t* box, CUtensorMapSwizzle sw) {
    const cuuint32_t es[5] = {1, 1, 1, 1, 1};
    fn(m, CU_TENSOR_MAP_DATA_TYPE_BFLOAT16, rank, (void*)base, dims, strides, box, es, CU_TENSOR_MAP_INTERLEAVE_NONE, sw,
       CU_TENSOR_MAP_L2_PROMOTION_NONE, CU_TENSOR_MAP_FLOAT_OOB_FILL_NONE);
}

}

extern "C" void kernel_launch(void* const* d_in, const int* in_sizes, int n_in, void* d_out, int out_size) {
    (void)in_sizes; (void)n_in; (void)out_size;
    static EncodeFn fn = nullptr;
    static void* scratch = nullptr;
    if (!fn) {
        void* ptr = nullptr; cudaDriverEntryPointQueryResult qr;
        cudaGetDriverEntryPoint("cuTensorMapEncodeTiled", &ptr, cudaEnableDefault, &qr);
        fn = (EncodeFn)ptr;
        cudaGetSymbolAddress(&scratch, g_scratch);
        cudaFuncSetAttribute(fused_kernel, cudaFuncAttributeMaxDynamicSharedMemorySize, SMEM_BYTES);
    }
    typedef const __nv_bfloat16* bp;
    Params p;
    p.u = (bp)d_in[0]; p.Are = (bp)d_in[1]; p.Aim = (bp)d_in[2]; p.Bre = (bp)d_in[3]; p.Bim = (bp)d_in[4]; p.Cre = (bp)d_in[5]; p.Cim = (bp)d_in[6];
    p.logdt = (bp)d_in[7]; p.Dskip = (bp)d_in[8]; p.wr = (bp)d_in[10]; p.gatew = (bp)d_in[14];
    p.out = (__nv_bfloat16*)d_out; p.s = (Scratch*)scratch; p.zero = 0;
    Maps maps;
    {
        const cuuint64_t dims[4] = {DM, 4, 16, 32}, strides[3] = {16 * DM * 2, DM * 2, 64 * DM * 2};
        const cuuint32_t box[4] = {16, 4, 16, 2};
        make_map(fn, &maps.m[0], d_in[0], 4, dims, strides, box, CU_TENSOR_MAP_SWIZZLE_32B);
    }
    for (int i = 0; i < 4; i++) {
        const cuuint64_t dims[3] = {32, DM, FF / 32}, strides[2] = {FF * 2, 64};
        const cuuint32_t box[3] = {32, 64, i < 2 ? 2u : 3u};
        make_map(fn, &maps.m[1 + i], d_in[11 + (i & 1)], 3, dims, strides, box, CU_TENSOR_MAP_SWIZZLE_64B);
    }
    {
        const cuuint64_t dims[2] = {DM, FF}, strides[1] = {DM * 2};
        const cuuint32_t box[2] = {32, 192};
        make_map(fn, &maps.m[5], d_in[13], 2, dims, strides, box, CU_TENSOR_MAP_SWIZZLE_64B);
    }
    {
        const cuuint64_t dims[5] = {DM, 4, 4, 2, L_SEQ}, strides[4] = {16 * DM * 2, 4 * DM * 2, 128 * DM * 2, DM * 2};
        const cuuint32_t box[5] = {16, 4, 4, 2, 1};
        make_map(fn, &maps.m[6], d_out, 5, dims, strides, box, CU_TENSOR_MAP_SWIZZLE_NONE);
    }
    fused_kernel<<<NCTA, NTHR, SMEM_BYTES>>>(p, maps);
}
```

```cpp
#include <cuda_runtime.h>
#include <cuda_bf16.h>
#include <cuda_fp16.h>
#include <cuda.h>
#include <stdint.h>
#include <type_traits>

#define LASTS 4
#define RESUME 400
#define NFAST 6
#define WJUMP 0
#define WGAP2 620
#define UDELAY 0
#define RDELAY 900
#define WDELAY 2200
#define WGAP 290
#define NPRE 6
#define DGAP 220

namespace {

constexpr int DM = 576, NST = 128, FF = 4608, L_SEQ = 2048;
constexpr int NCONV = 72, NX = 36, NFFN = 60, NCTA = 132, NTHR = 512;

struct __align__(128) Scratch {
    unsigned epoch[NCTA * 16];
    uint4 keys[16 * 128];
    uint32_t sel[18 * 64];
    uint16_t gate[L_SEQ];
    uint2 h[2 * 288 * 32];
    uint4 kp[288 * 128];
};
__device__ Scratch g_scratch;
#define TFLUSH()
#define TSTAMP(i)

struct Params {
    const __nv_bfloat16 *Are, *Aim, *Bre, *Bim, *Cre, *Cim, *logdt, *Dskip, *u, *wr, *gatew;
    __nv_bfloat16* out;
    Scratch* s;
    uint32_t zero;
};

__device__ __forceinline__ uint32_t smem_u32(const void* p) { return (uint32_t)__cvta_generic_to_shared(p); }
__device__ __forceinline__ uint32_t pack_bf16(float lo, float hi) { uint32_t r; asm("cvt.rn.bf16x2.f32 %0, %1, %2;" : "=r"(r) : "f"(hi), "f"(lo)); return r; }
__device__ __forceinline__ uint32_t pack_f16(float lo, float hi) { uint32_t r; asm("cvt.rn.f16x2.f32 %0, %1, %2;" : "=r"(r) : "f"(hi), "f"(lo)); return r; }
__device__ __forceinline__ float bf_lo(uint32_t w) { return __uint_as_float(w << 16); }
__device__ __forceinline__ float bf_hi(uint32_t w) { return __uint_as_float(w & 0xffff0000u); }
__device__ __forceinline__ float rbf(float x) { return bf_lo(pack_bf16(x, 0.f)); }
__device__ __forceinline__ uint32_t badd2(uint32_t a, uint32_t b) { uint32_t r; asm("add.rn.bf16x2 %0, %1, %2;" : "=r"(r) : "r"(a), "r"(b)); return r; }
__device__ __forceinline__ uint32_t bsub2(uint32_t a, uint32_t b) { uint32_t r; asm("sub.rn.bf16x2 %0, %1, %2;" : "=r"(r) : "r"(a), "r"(b)); return r; }
__device__ __forceinline__ uint32_t gmix(uint32_t ng, float ny0, float ny1, uint32_t u) {
    uint32_t r; asm("{ .reg .b32 t; fma.rn.bf16x2 t, %1, %3, %3; fma.rn.bf16x2 %0, %1, %2, t; }" : "=r"(r) : "r"(ng), "r"(pack_bf16(ny0, ny1)), "r"(u)); return r;
}
__device__ __forceinline__ void mma_bf(float (&c)[4], uint32_t a0, uint32_t a1, uint32_t a2, uint32_t a3, uint32_t b0, uint32_t b1) {
    asm("mma.sync.aligned.m16n8k16.row.col.f32.bf16.bf16.f32 {%0,%1,%2,%3}, {%4,%5,%6,%7}, {%8,%9}, {%0,%1,%2,%3};"
        : "+f"(c[0]), "+f"(c[1]), "+f"(c[2]), "+f"(c[3]) : "r"(a0), "r"(a1), "r"(a2), "r"(a3), "r"(b0), "r"(b1));
}
__device__ __forceinline__ void mma_bf8(float (&c)[4], uint32_t a0, uint32_t a1, uint32_t b0) {
    asm("mma.sync.aligned.m16n8k8.row.col.f32.bf16.bf16.f32 {%0,%1,%2,%3}, {%4,%5}, {%6}, {%0,%1,%2,%3};"
        : "+f"(c[0]), "+f"(c[1]), "+f"(c[2]), "+f"(c[3]) : "r"(a0), "r"(a1), "r"(b0));
}
__device__ __forceinline__ void mma_h(float (&c)[4], uint32_t a0, uint32_t a1, uint32_t a2, uint32_t a3, uint32_t b0, uint32_t b1) {
    asm("mma.sync.aligned.m16n8k16.row.col.f32.f16.f16.f32 {%0,%1,%2,%3}, {%4,%5,%6,%7}, {%8,%9}, {%0,%1,%2,%3};"
        : "+f"(c[0]), "+f"(c[1]), "+f"(c[2]), "+f"(c[3]) : "r"(a0), "r"(a1), "r"(a2), "r"(a3), "r"(b0), "r"(b1));
}
__device__ __forceinline__ uint32_t fresh(uint32_t a) { asm volatile("" : "+r"(a) :: "memory"); return a; }
__device__ __forceinline__ uint32_t lds16(uint32_t a) { uint32_t v; asm("ld.shared.u16 %0, [%1];" : "=r"(v) : "r"(a)); return v; }
__device__ __forceinline__ uint32_t lds32(uint32_t a) { uint32_t v; asm("ld.shared.u32 %0, [%1];" : "=r"(v) : "r"(a)); return v; }
__device__ __forceinline__ uint2 lds64(uint32_t a) { uint2 v; asm("ld.shared.v2.u32 {%0,%1}, [%2];" : "=r"(v.x), "=r"(v.y) : "r"(a)); return v; }
__device__ __forceinline__ uint4 lds128(uint32_t a) { uint4 v; asm("ld.shared.v4.u32 {%0,%1,%2,%3}, [%4];" : "=r"(v.x), "=r"(v.y), "=r"(v.z), "=r"(v.w) : "r"(a)); return v; }
__device__ __forceinline__ uint4 lds128v(uint32_t a) { uint4 v; asm volatile("ld.shared.v4.u32 {%0,%1,%2,%3}, [%4];" : "=r"(v.x), "=r"(v.y), "=r"(v.z), "=r"(v.w) : "r"(a) : "memory"); return v; }
__device__ __forceinline__ void ldsm4(uint32_t (&r)[4], uint32_t a) {
    asm("ldmatrix.sync.aligned.m8n8.x4.shared.b16 {%0,%1,%2,%3}, [%4];" : "=r"(r[0]), "=r"(r[1]), "=r"(r[2]), "=r"(r[3]) : "r"(a));
}
__device__ __forceinline__ void ldsm4t(uint32_t (&r)[4], uint32_t a) {
    asm("ldmatrix.sync.aligned.m8n8.x4.trans.shared.b16 {%0,%1,%2,%3}, [%4];" : "=r"(r[0]), "=r"(r[1]), "=r"(r[2]), "=r"(r[3]) : "r"(a));
}
__device__ __forceinline__ void sts16(uint32_t a, uint32_t v) { asm volatile("st.shared.u16 [%0], %1;" :: "r"(a), "h"((unsigned short)v) : "memory"); }
__device__ __forceinline__ void sts32(uint32_t a, uint32_t v) { asm volatile("st.shared.u32 [%0], %1;" :: "r"(a), "r"(v) : "memory"); }
__device__ __forceinline__ void sts64(uint32_t a, uint32_t x, uint32_t y) { asm volatile("st.shared.v2.u32 [%0], {%1,%2};" :: "r"(a), "r"(x), "r"(y) : "memory"); }
__device__ __forceinline__ void sts128(uint32_t a, uint32_t x, uint32_t y, uint32_t z, uint32_t w) {
    asm volatile("st.shared.v4.u32 [%0], {%1,%2,%3,%4};" :: "r"(a), "r"(x), "r"(y), "r"(z), "r"(w) : "memory");
}
__device__ __forceinline__ void st_async128(uint32_t a, uint32_t x, uint32_t y, uint32_t z, uint32_t w, uint32_t bar) {
    asm volatile("st.async.weak.shared::cluster.mbarrier::complete_tx::bytes.v4.b32 [%0], {%1,%2,%3,%4}, [%5];" :: "r"(a), "r"(x), "r"(y), "r"(z), "r"(w), "r"(bar) : "memory");
}
__device__ __forceinline__ void mbar_init(uint32_t b, uint32_t cnt) { asm volatile("mbarrier.init.shared::cta.b64 [%0], %1;" :: "r"(b), "r"(cnt) : "memory"); }
__device__ __forceinline__ void mbar_fence() { asm volatile("fence.mbarrier_init.release.cluster;" ::: "memory"); }
__device__ __forceinline__ void mbar_expect(uint32_t b, uint32_t bytes) { asm volatile("mbarrier.arrive.expect_tx.shared::cta.b64 _, [%0], %1;" :: "r"(b), "r"(bytes) : "memory"); }
__device__ __forceinline__ void mbar_arrive(uint32_t b) { asm volatile("mbarrier.arrive.shared::cta.b64 _, [%0];" :: "r"(b) : "memory"); }
#define CHINT ""
#define HINT ""
__device__ __forceinline__ void mbar_wait(uint32_t b, uint32_t parity = 0) {
    asm volatile("{ .reg .pred p; .reg .u32 n; mov.u32 n, 0;\n"
                 "LW: mbarrier.try_wait.parity.shared::cta.b64 p, [%0], %1" HINT "; @p bra LD; add.u32 n, n, 1; setp.lt.u32 p, n, 65536; @p bra LW; trap;\n"
                 "LD: }" :: "r"(b), "r"(parity) : "memory");
}
__device__ __forceinline__ void mbar_wait_cluster(uint32_t b) {
    asm volatile("{ .reg .pred p; .reg .u32 n; mov.u32 n, 0;\n"
                 "LW: mbarrier.try_wait.parity.acquire.cluster.shared::cta.b64 p, [%0], 0" CHINT "; @p bra LD; add.u32 n, n, 1; setp.lt.u32 p, n, 65536; @p bra LW; trap;\n"
                 "LD: }" :: "r"(b) : "memory");
}
__device__ __forceinline__ void tma2d(uint32_t dst, const CUtensorMap* m, int c0, int c1, uint32_t bar) {
    asm volatile("cp.async.bulk.tensor.2d.shared::cluster.global.mbarrier::complete_tx::bytes [%0], [%1, {%3, %4}], [%2];"
                 :: "r"(dst), "l"(m), "r"(bar), "r"(c0), "r"(c1) : "memory");
}
__device__ __forceinline__ void tma3d(uint32_t dst, const CUtensorMap* m, int c0, int c1, int c2, uint32_t bar) {
    asm volatile("cp.async.bulk.tensor.3d.shared::cluster.global.mbarrier::complete_tx::bytes [%0], [%1, {%3, %4, %5}], [%2];"
                 :: "r"(dst), "l"(m), "r"(bar), "r"(c0), "r"(c1), "r"(c2) : "memory");
}
__device__ __forceinline__ void tma4d(uint32_t dst, const CUtensorMap* m, int c0, int c1, int c2, int c3, uint32_t bar) {
    asm volatile("cp.async.bulk.tensor.4d.shared::cluster.global.mbarrier::complete_tx::bytes [%0], [%1, {%3, %4, %5, %6}], [%2];"
                 :: "r"(dst), "l"(m), "r"(bar), "r"(c0), "r"(c1), "r"(c2), "r"(c3) : "memory");
}
__device__ __forceinline__ void bulk_g2s(uint32_t dst, const void* src, uint32_t bytes, uint32_t bar) {
    asm volatile("cp.async.bulk.shared::cluster.global.mbarrier::complete_tx::bytes [%0], [%1], %2, [%3];"
                 :: "r"(dst), "l"(src), "r"(bytes), "r"(bar) : "memory");
}
__device__ __forceinline__ uint32_t mapa(uint32_t a, uint32_t rank) { uint32_t r; asm("mapa.shared::cluster.u32 %0, %1, %2;" : "=r"(r) : "r"(a), "r"(rank)); return r; }
__device__ __forceinline__ void prefetch_map(const CUtensorMap* m) { asm volatile("prefetch.tensormap [%0];" :: "l"(m) : "memory"); }
__device__ __forceinline__ void bar_sync(int id, int n) { asm volatile("bar.sync %0, %1;" :: "r"(id), "r"(n) : "memory"); }
__device__ __forceinline__ void bar_arrive(int id, int n) { asm volatile("bar.arrive %0, %1;" :: "r"(id), "r"(n) : "memory"); }
__device__ __forceinline__ uint32_t ldg16_if(bool c, const void* p) { uint32_t v; asm volatile("{ .reg .pred p; setp.ne.u32 p, %2, 0; @p ld.global.nc.u16 %0, [%1]; }" : "=r"(v) : "l"(p), "r"((uint32_t)c)); return v; }
__device__ __forceinline__ uint32_t ldg32_if(bool c, const void* p) { uint32_t v; asm volatile("{ .reg .pred p; setp.ne.u32 p, %2, 0; @p ld.global.nc.u32 %0, [%1]; }" : "=r"(v) : "l"(p), "r"((uint32_t)c)); return v; }
__device__ __forceinline__ uint32_t ld_rlx32(const void* p) { uint32_t v; asm volatile("ld.relaxed.gpu.global.u32 %0, [%1];" : "=r"(v) : "l"(p) : "memory"); return v; }
__device__ __forceinline__ uint4 ld_rlx128(const void* p) {
    uint4 v; asm volatile("ld.relaxed.gpu.global.v4.u32 {%0,%1,%2,%3}, [%4];" : "=r"(v.x), "=r"(v.y), "=r"(v.z), "=r"(v.w) : "l"(p) : "memory"); return v;
}
__device__ __forceinline__ void st_rlx32(void* p, uint32_t v) { asm volatile("st.relaxed.gpu.global.u32 [%0], %1;" :: "l"(p), "r"(v) : "memory"); }
__device__ __forceinline__ void stg128(void* p, uint32_t x, uint32_t y, uint32_t z, uint32_t w) {
    asm volatile("st.global.v4.u32 [%0], {%1,%2,%3,%4};" :: "l"(p), "r"(x), "r"(y), "r"(z), "r"(w) : "memory");
}
__device__ __forceinline__ void next_epoch(const Params& p, unsigned e) { if ((threadIdx.x & 31) == 0) p.s->epoch[blockIdx.x * 16 + (threadIdx.x >> 5)] = e + 1; }
__device__ __forceinline__ void sts128z_if(bool c, uint32_t a) { asm volatile("{ .reg .pred p; setp.ne.u32 p, %1, 0; @p st.shared.v4.u32 [%0], {%2,%2,%2,%2}; }" :: "r"(a), "r"((uint32_t)c), "r"(0) : "memory"); }
__device__ __forceinline__ void stg128z_if(bool c, void* a) { asm volatile("{ .reg .pred p; setp.ne.u32 p, %1, 0; @p st.global.v4.u32 [%0], {%2,%2,%2,%2}; }" :: "l"(a), "r"((uint32_t)c), "r"(0) : "memory"); }
__device__ __forceinline__ unsigned clock32() { unsigned c; asm volatile("mov.u32 %0, %clock;" : "=r"(c) :: "memory"); return c; }
__device__ __forceinline__ void until(unsigned t0, int c) { while ((int)(clock32() - t0) < c) { } }
__device__ __forceinline__ float sigmoidf_(float x) { return __fdividef(1.0f, 1.0f + __expf(-x)); }
__device__ __forceinline__ uint32_t key_tag(unsigned epoch) { return ((epoch & 15u) | 16u) << 11; }
__device__ __forceinline__ int key_row(uint32_t key) { return 2047 - (int)(key & 2047u); }
__device__ __forceinline__ uint32_t wait_sel(const Params& p, int s32, int r8, uint32_t tag) {
    uint32_t k;
    for (int it = 0;; it++) {
        k = ld_rlx32(&p.s->sel[s32 * 64 + r8]);
        if (__all_sync(0xffffffffu, (k & 0xf800u) == tag)) break;
        if (it > (1 << 20)) __trap();
    }
    return k;
}

struct cplx { float re, im; };
__device__ __forceinline__ cplx csq(cplx a) { cplx r; r.re = a.re * a.re - a.im * a.im; r.im = (a.re * a.im) * 2.f; return r; }
__device__ __forceinline__ cplx cexpk(float ar, float ai, float k) {
    float mag, s, c;
    asm("ex2.approx.ftz.f32 %0, %1;" : "=f"(mag) : "f"(ar * (k * 1.4426950408889634f)));
    const float r = ai * k;
    asm("sin.approx.ftz.f32 %0, %1;" : "=f"(s) : "f"(r));
    asm("cos.approx.ftz.f32 %0, %1;" : "=f"(c) : "f"(r));
    cplx o; o.re = mag * c; o.im = mag * s; return o;
}
struct h2c { uint32_t re, im; };
__device__ __forceinline__ h2c cmul_cd(h2c v, __half2 c, __half2 d) {
    const __half2 r = *(const __half2*)&v.re, i = *(const __half2*)&v.im;
    const __half2 x = __hfma2(__hneg2(i), d, __hmul2(r, c)), y = __hfma2(i, c, __hmul2(r, d));
    h2c o; o.re = *(const uint32_t*)&x; o.im = *(const uint32_t*)&y; return o;
}
__device__ __forceinline__ h2c cmul_s(h2c v, uint32_t s) { const __half2 h = *(const __half2*)&s; return cmul_cd(v, __low2half2(h), __high2half2(h)); }
__device__ __forceinline__ h2c cmul_sc(h2c v, uint32_t s) {
    const __half2 h = *(const __half2*)&s, c = __low2half2(h), d = __high2half2(h), r = *(const __half2*)&v.re, i = *(const __half2*)&v.im;
    const __half2 x = __hfma2(i, d, __hmul2(r, c)), y = __hfma2(__hneg2(r), d, __hmul2(i, c));
    h2c o; o.re = *(const uint32_t*)&x; o.im = *(const uint32_t*)&y; return o;
}
__device__ __forceinline__ h2c cmul_vc(h2c v, uint32_t s) {
    const __half2 h = *(const __half2*)&s, c = __low2half2(h), d = __high2half2(h), r = *(const __half2*)&v.re, i = *(const __half2*)&v.im;
    const __half2 x = __hfma2(i, d, __hmul2(r, c)), y = __hfma2(__hneg2(i), c, __hmul2(r, d));
    h2c o; o.re = *(const uint32_t*)&x; o.im = *(const uint32_t*)&y; return o;
}

constexpr int UT_HALF = 2240, UT_STRIDE = 4448;
constexpr int KT_T = 542, KT_C = 552, KT_D = 645, KT_BYTES = 720 * 4;
constexpr int VC_OFF = 80, VE_BASE = 1616;
constexpr int V_STRIDE = (1616 + 1024) * 4 + 80;
constexpr int KG_STAGE = 5248;
constexpr int Y_CS = 2080, Y_RS = 8 * Y_CS + 64;

constexpr int SC_RT = 0;
constexpr int SC_UT = 33408;
constexpr int SC_ST = SC_UT + 8 * UT_STRIDE;
constexpr int SC_KT = SC_ST + 8 * UT_STRIDE;
constexpr int SC_GT = SC_KT + 8 * KT_BYTES;
constexpr int SC_V = SC_GT + UT_STRIDE;
constexpr int SC_KG = SC_V + 4 * V_STRIDE;
constexpr int SC_MISC = SC_V + 8 * V_STRIDE;
static_assert(V_STRIDE % 128 == 16 && 8 * KG_STAGE <= 4 * V_STRIDE && 2 * Y_RS <= SC_UT && SC_UT % 128 == 0 && SC_ST % 128 == 0, "layout");
static_assert(SC_MISC % 16 == 0 && SC_MISC + 512 <= 232192, "layout");

__device__ __forceinline__ void window_task(uint32_t src, uint32_t d0, uint32_t d1, bool withE) {
    float S[35];
    {
        uint32_t w[20];
#pragma unroll
        for (int i = 0; i < 5; i++) {
            const uint4 v = lds128(src + ((i & 1) ? 0 : UT_HALF) + ((i + 1) >> 1) * 16);
            w[4 * i] = v.x; w[4 * i + 1] = v.y; w[4 * i + 2] = v.z; w[4 * i + 3] = v.w;
        }
        float s = 0.f; S[2] = 0.f;
#pragma unroll
        for (int i = 3; i < 26; i++) { s += (i & 1) ? bf_hi(w[i >> 1]) : bf_lo(w[i >> 1]); S[i] = s; }
#pragma unroll
        for (int i = 0; i < 8; i += 2)
            sts128((i & 4 ? d1 : d0) + (VC_OFF - 16) * 4 + 8 * (i & 2), pack_bf16(S[10 + i] - S[5 + i], S[5 + i] - S[2 + i]), pack_bf16(S[18 + i] - S[13 + i], S[13 + i] - S[10 + i]),
                   pack_bf16(S[11 + i] - S[6 + i], S[6 + i] - S[3 + i]), pack_bf16(S[19 + i] - S[14 + i], S[14 + i] - S[11 + i]));
        if (withE) {
#pragma unroll
            for (int i = 26; i < 35; i++) { s += (i & 1) ? bf_hi(w[i >> 1]) : bf_lo(w[i >> 1]); S[i] = s; }
#pragma unroll
            for (int i = 0; i < 8; i += 2)
                sts128((i & 4 ? d1 : d0) + VE_BASE * 4 + 8 * (i & 2), pack_bf16(S[19 + i] - S[12 + i], S[12 + i] - S[3 + i]), pack_bf16(S[27 + i] - S[20 + i], S[20 + i] - S[11 + i]),
                       pack_bf16(S[20 + i] - S[13 + i], S[13 + i] - S[4 + i]), pack_bf16(S[28 + i] - S[21 + i], S[21 + i] - S[12 + i]));
        }
    }
}

template <class F>
__device__ __forceinline__ void kgen(const uint32_t (&q)[8], uint32_t sb, int half, uint32_t stage, uint32_t pstage, int barid, int lane, uint32_t zero, uint32_t (&w)[12], F shadow) {
    const int t = lane & 3, mi = lane >> 3, r8 = lane & 7;
    {
        const uint32_t pAr = q[0], pAi = q[1], pBr = q[2], pBi = q[3], pCr = q[4], pCi = q[5], pDt = q[6], pD = q[7];
        const uint32_t wb = fresh(stage + lane * 16), za = fresh(stage + 5120 + ((lane >> 1) & 3) * 16 + mi * 4 + (lane & 1) * 2), zr = fresh(stage + 5120 + t * 16);
        const uint32_t oA = fresh(stage + (mi & 1) * 1024 + (mi >> 1) * 512 + r8 * 16), oB = fresh(stage + 2048 + mi * 512 + r8 * 16), oC = fresh(stage + 4096 + (mi & 1) * 512 + (mi >> 1) * 128 + r8 * 16);
        float acc[6][4];
#pragma unroll
        for (int a = 0; a < 6; a++) { acc[a][0] = acc[a][1] = acc[a][2] = acc[a][3] = 0.f; asm volatile("" : "+f"(acc[a][0]), "+f"(acc[a][1]), "+f"(acc[a][2]), "+f"(acc[a][3])); }
        shadow();
        sts32(zr, clock32());
        const float dt = rbf(__expf(bf_lo(pDt)));
        float ar = dt * bf_lo(pAr), ai = dt * bf_lo(pAi), ar1 = dt * bf_hi(pAr), ai1 = dt * bf_hi(pAi);
        float wr, wi, wr1, wi1;
        { const float br = dt * bf_lo(pBr), bi = dt * bf_lo(pBi), cr = bf_lo(pCr), ci = bf_lo(pCi); wr = cr * br - ci * bi; wi = cr * bi + ci * br; }
        { const float br = dt * bf_hi(pBr), bi = dt * bf_hi(pBi), cr = bf_hi(pCr), ci = bf_hi(pCi); wr1 = cr * br - ci * bi; wi1 = cr * bi + ci * br; }
        const uint32_t ex = max(__reduce_max_sync(0xffffffffu, __float_as_uint(fmaxf(fmaxf(fabsf(wr), fabsf(wi)), fmaxf(fabsf(wr1), fabsf(wi1))))) >> 23, 14u);
        const float scl = __uint_as_float((267u - ex) << 23);
        uint32_t W = pack_f16(wr * scl, wi * -scl);
        const uint32_t W1 = pack_f16(wr1 * scl, wi1 * -scl);
        if (threadIdx.x < 32) TSTAMP(20);

#pragma unroll 1
        for (int r = 0; r < 2; r++) {
            const cplx z1 = cexpk(ar, ai, 1.f), z64 = cexpk(ar, ai, 64.f);
            const cplx z2 = csq(z1), z4 = csq(z2), z8 = csq(z4), z16 = csq(z8), z32 = csq(z16);
            const cplx z128 = csq(z64), z256 = csq(z128), z512 = csq(z256);
            auto put = [&](int grp, h2c a, h2c b, h2c c, h2c d) { sts128(wb + grp * 1024, a.re, b.re, c.re, d.re); sts128(wb + grp * 1024 + 512, a.im, b.im, c.im, d.im); };
            {
                const uint32_t s4 = pack_f16(z4.re, z4.im), s256 = pack_f16(z256.re, z256.im), s512 = pack_f16(z512.re, z512.im);
                auto mix = [](h2c a, h2c b, uint32_t sel) { return h2c{__byte_perm(a.re, b.re, sel), __byte_perm(a.im, b.im, sel)}; };
                const h2c c10 = cmul_vc(h2c{pack_f16(z1.re, 1.f), pack_f16(z1.im, 0.f)}, W), c32 = cmul_sc(c10, pack_f16(z2.re, z2.im)), c54 = cmul_sc(c10, s4);
                put(2, c10, c32, c54, cmul_sc(c32, s4));
                const h2c d20 = cmul_sc(mix(c32, c10, 0x7632), s256), e04 = cmul_sc(mix(c10, c54, 0x7632), s512), f04 = cmul_sc(e04, s256);
                put(3, d20, cmul_sc(d20, s4), e04, f04);
                const h2c ef = mix(e04, f04, 0x5410), gh = cmul_sc(ef, s512), g8 = cmul_sc(gh, pack_f16(z8.re, z8.im));
                put(4, g8, cmul_sc(g8, s512), gh, ef);
            }
            {
                const uint32_t s32 = pack_f16(z32.re, z32.im), s64 = pack_f16(z64.re, z64.im), s128 = pack_f16(z128.re, z128.im);
                const h2c p0 = {pack_f16(1.f, z8.re), pack_f16(0.f, z8.im)}, p1 = cmul_s(p0, pack_f16(z16.re, z16.im)), p2 = cmul_s(p0, s32), p3 = cmul_s(p1, s32);
                put(0, p0, p1, p2, p3);
                put(1, cmul_s(p0, s64), cmul_s(p1, s64), cmul_s(p2, s64), cmul_s(p3, s64));
                sts16(za, s128); sts16(za + 64, s128 >> 16);
            }
            __syncwarp();
            {
                const uint32_t aA = fresh(oA), aB = fresh(oB), aC = fresh(oC), aZ = fresh(zr);
                const uint4 zc = lds128(aZ), zd = lds128(aZ + 64);
                const uint32_t zcs[4] = {zc.x, zc.y, zc.z, zc.w}, zds[4] = {zd.x, zd.y, zd.z, zd.w};
                uint32_t c[4];
#pragma unroll
                for (int k = 0; k < 4; k++) {
                    uint32_t a[4], b[4];
                    ldsm4t(a, aA + 128 * k); ldsm4t(b, aB + 128 * k);
                    if (!(k & 1)) ldsm4t(c, aC + 128 * k);
                    const h2c x = cmul_cd(h2c{a[0], a[2]}, *(const __half2*)&zcs[k], *(const __half2*)&zds[k]), y = cmul_cd(h2c{a[1], a[3]}, *(const __half2*)&zcs[k], *(const __half2*)&zds[k]);
                    mma_h(acc[0], a[0], a[1], a[2], a[3], b[0], b[1]);
                    mma_h(acc[1], a[0], a[1], a[2], a[3], b[2], b[3]);
                    mma_h(acc[2], a[0], a[1], a[2], a[3], c[2 * (k & 1)], c[2 * (k & 1) + 1]);
                    mma_h(acc[3], x.re, y.re, x.im, y.im, b[0], b[1]);
                    mma_h(acc[4], x.re, y.re, x.im, y.im, b[2], b[3]);
                    mma_h(acc[5], x.re, y.re, x.im, y.im, c[2 * (k & 1)], c[2 * (k & 1) + 1]);
                }
                asm volatile("" :: "f"(acc[0][0]), "f"(acc[1][0]), "f"(acc[2][0]), "f"(acc[3][0]), "f"(acc[4][0]), "f"(acc[5][0]) : "memory");
            }
            __syncwarp();
            ar = ar1; ai = ai1; W = W1;
        }
        if (threadIdx.x < 32) TSTAMP(21);
        const float i0 = __uint_as_float((ex + 243u) << 23);
        if (half) {
#pragma unroll
            for (int a = 0; a < 6; a++) sts128(wb + a * 512, __float_as_uint(acc[a][0]), __float_as_uint(acc[a][1]), __float_as_uint(acc[a][2]), __float_as_uint(acc[a][3]));
            sts32(stage + 3072, __float_as_uint(i0));
            bar_arrive(barid, 64);
        } else {
#pragma unroll
            for (int a = 0; a < 6; a++) { acc[a][0] *= i0; acc[a][1] *= i0; acc[a][2] *= i0; acc[a][3] *= i0; }
            if (lane == 0) acc[0][1] -= bf_lo(pD);
            sts32(zr, clock32());
            bar_sync(barid, 64);
            const uint32_t src = fresh(pstage);
            const float i1 = __uint_as_float(lds32(src + 3072));
#pragma unroll
            for (int a = 0; a < 6; a++) {
                const uint4 y = lds128(src + lane * 16 + a * 512);
                w[2 * a] = pack_bf16(fmaf(__uint_as_float(y.x), i1, acc[a][0]), fmaf(__uint_as_float(y.y), i1, acc[a][1]));
                w[2 * a + 1] = pack_bf16(fmaf(__uint_as_float(y.z), i1, acc[a][2]), fmaf(__uint_as_float(y.w), i1, acc[a][3]));
            }
        }
    }
}

__device__ __forceinline__ int swap01(int i) { return (i & ~3) | ((i & 1) << 1) | ((i >> 1) & 1); }
enum { BC_AUX = 0, BC_S = 5, BC_KG = 15 };

__device__ __forceinline__ void conv_aux(const Params& p, const CUtensorMap* mU, uint32_t sb, int aw, int lane, int bid, unsigned epoch) {
    const unsigned t0 = clock32();
    const int g = lane >> 2, t = lane & 3, mi = lane >> 3, r8 = lane & 7;
    const int rank = bid & 1, slab = bid >> 1;
    const uint32_t bar_y = sb + SC_MISC, bar_u = bar_y + 32, bar_v = bar_y + 40, bar_box = bar_y + 64 + 8 * aw, s_bm = bar_y + 128;
    if (lane == 0) {
        mbar_init(bar_box, 1); mbar_fence();
        mbar_expect(bar_box, 4096);
        if (UDELAY) until(t0, UDELAY);
        tma4d(sb + SC_RT + 4096 * aw, mU, 16 * slab, 0, 0, 16 * rank + 2 * aw, bar_box);
        mbar_init(bar_y + 8 * aw, aw < 4 ? 9 : aw == 5 ? 8 : 1); mbar_fence();
        if (aw < 5) mbar_expect(bar_y + 8 * aw, aw == 4 ? 16384 : 4096);
    }
    __syncwarp();
    asm volatile("barrier.cluster.arrive.relaxed.aligned;" ::: "memory");
    asm volatile("setmaxnreg.dec.sync.aligned.u32 88;");
    const uint32_t ut = sb + SC_UT + aw * UT_STRIDE;
    sts128(ut + (mi >> 1) * (SC_ST - SC_UT) + (mi & 1) * UT_HALF + r8 * 16, 0, 0, 0, 0);
    if (lane < 16) sts128(s_bm + lane * 16, 0, 0, 0, 0);
    {
        const uint32_t dst = sb + SC_UT + swap01(g) * UT_STRIDE + (8 + 64 * rank + 8 * aw + t) * 16;
        const uint32_t rdst = mapa(dst, rank ^ 1), rbar = mapa(bar_u, rank ^ 1);
        asm volatile("barrier.cluster.wait.acquire.aligned;" ::: "memory");
        mbar_wait(bar_box);
        if (aw == 0) TSTAMP(1);
        const uint32_t src = fresh(sb + SC_RT) + aw * 4096 + (8 * mi + 4 * (r8 & 1) + (r8 >> 1)) * 32 + ((rank ^ (r8 & 1)) << 4);
        uint32_t x[8][4];
#pragma unroll
        for (int i = 0; i < 4; i++) { ldsm4t(x[i], src + 1024 * i); ldsm4t(x[4 + i], (src ^ 16) + 1024 * i); }
        asm volatile("" :: "r"(x[0][0]), "r"(x[1][0]), "r"(x[2][0]), "r"(x[3][0]) : "memory");
#pragma unroll
        for (int i = 0; i < 4; i++) st_async128(rdst + (i & 1) * UT_HALF + 32 * (i & 2), x[4 + i][0], x[4 + i][1], x[4 + i][2], x[4 + i][3], rbar);
#pragma unroll
        for (int i = 0; i < 4; i++) sts128(dst + (i & 1) * UT_HALF + 32 * (i & 2), x[i][0], x[i][1], x[i][2], x[i][3]);
    }
    bar_sync(BC_AUX, 256);
    mbar_wait_cluster(bar_u);
    if (aw == 0) TSTAMP(2);
    {
        const uint32_t a = fresh(ut) + (mi & 1) * UT_HALF + (64 * (mi >> 1) + r8) * 16;
        uint4 v = lds128(a);
#pragma unroll
        for (int i = 1; i <= 8; i++) {
            const uint4 w = lds128(a + 128 * i);
            sts128(a + 128 * i + (SC_ST - SC_UT), badd2(v.x, w.x), badd2(v.y, w.y), badd2(v.z, w.z), badd2(v.w, w.w));
            v = w;
        }
    }
    bar_arrive(BC_S + aw, 64);
    if (aw == 0) TSTAMP(3);
    {
        uint32_t ws = sb + SC_UT + t * UT_STRIDE + (g + 6) * 16, wd = sb + SC_V + t * V_STRIDE + 64 * g, sw = 16 * (g & 2);
#pragma unroll 1
        for (int k = aw; k < 25; k += 8) {
            if (k - aw == 8) {
                bar_sync(BC_KG, 384);
                if (lane < 16) sts128(sb + SC_V + aw * V_STRIDE + lane * 16, 0, 0, 0, 0);
            }
            if (k == 24) { ws -= (g & 1) * 4 * UT_STRIDE + 16 * g; wd -= (g & 1) * 4 * V_STRIDE + 64 * g; sw = 0; }
            const int h = k >= 12, a = k - 12 * h;
            const uint32_t d = wd + h * 4 * V_STRIDE + 512 * a;
            window_task(fresh(ws) + h * 4 * UT_STRIDE + 128 * a, d + sw, d + (sw ^ 32), a < 8);
        }
    }
    if (aw == 0) TSTAMP(9);
    {
        {
            const uint32_t par = (epoch & 1) ? 0x80008000u : 0u;
            uint4 v;
            for (int it = 0;; it++) {
                v = ld_rlx128(p.s->gate + 256 * aw + 8 * lane);
                v.x ^= par; v.y ^= par; v.z ^= par; v.w ^= par;
                if (__all_sync(0xffffffffu, (v.x & v.y & v.z & v.w & 0x80008000u) == 0x80008000u)) break;
                if (it > (1 << 20)) __trap();
            }
            sts128(sb + SC_GT + (lane & 1) * UT_HALF + (8 + 16 * aw + (lane >> 1)) * 16, v.x, v.y, v.z, v.w);
        }
        __syncwarp();
        if (lane == 0) { mbar_arrive(bar_v); prefetch_map(mU + 6); }
        next_epoch(p, epoch);
        if (aw == 0) TSTAMP(4);
        if (aw == 7) {
            const int row = key_row(wait_sel(p, slab >> 1, r8, key_tag(epoch)));
            if (lane < 8) asm volatile("red.shared.or.b32 [%0], %1;" :: "r"(s_bm + (row >> 5) * 4), "r"(1u << (row & 31)) : "memory");
            TSTAMP(10);
        }
        bar_sync(BC_AUX, 256);
        const uint32_t src = sb + SC_RT + ((r8 >> 1) & 1) * Y_RS + (2 * mi + (r8 & 1)) * Y_CS + (2 * aw + (r8 >> 2)) * 16;
        const int L = 2 * aw + (t >> 1);
        const int row0 = 256 * rank + 128 * (g >> 2) + 32 * (L & 3) + 16 * (g & 1) + 8 * ((g >> 1) & 1) + (L >> 2);
        __nv_bfloat16* outp = p.out + (size_t)row0 * DM + 16 * slab + 8 * (t & 1);
        const uint32_t stg = sb + SC_ST + 4096 * aw, so = (g >> 1) * 256 + (t >> 1) * 64 + (g & 1) * 32 + (t & 1) * 16;
#pragma unroll 1
        for (int s = 0; s < 4; s++) {
            const uint32_t bm = lds32(fresh(s_bm) + (16 * s + (row0 >> 5)) * 4) >> (row0 & 31);
            const bool routed = __any_sync(0xffffffffu, bm & 0x11u) || s >= LASTS;
            if (aw == s) mbar_wait_cluster(bar_y + 8 * s);
            bar_sync(BC_AUX, 256);
            const uint32_t sf = fresh(src) + 512 * s;
            uint32_t y[2][4];
            ldsm4t(y[0], sf); ldsm4t(y[1], sf + 256);
            if (routed) {
#pragma unroll
                for (int k = 0; k < 2; k++)
                    asm volatile("{ .reg .pred p; setp.ne.u32 p, %5, 0; @!p st.global.v4.u32 [%0], {%1,%2,%3,%4}; @p red.relaxed.gpu.global.add.noftz.v4.bf16x2 [%0], {%1,%2,%3,%4}; }"
                                 :: "l"(outp + (size_t)(512 * s + 4 * k) * DM), "r"(y[k][0]), "r"(y[k][1]), "r"(y[k][2]), "r"(y[k][3]), "r"(bm & (1u << (4 * k))) : "memory");
            } else {
                sts128(stg + so + 1024 * s, y[0][0], y[0][1], y[0][2], y[0][3]); sts128(stg + so + 1024 * s + 128, y[1][0], y[1][1], y[1][2], y[1][3]);
                asm volatile("fence.proxy.async.shared::cta;" ::: "memory");
                __syncwarp();
                if (lane == 0) asm volatile("cp.async.bulk.tensor.5d.global.shared::cta.bulk_group [%0, {%2, %3, %3, %3, %4}], [%1];"
                                            :: "l"(mU + 6), "r"(stg + 1024 * s), "r"(16 * slab), "r"(0), "r"(512 * s + 256 * rank + 64 * (aw & 1) + (aw >> 1)) : "memory");
            }
            if (aw == 0) TSTAMP(16 + s);
        }
        if (lane == 0) { asm volatile("cp.async.bulk.commit_group;" ::: "memory"); asm volatile("cp.async.bulk.wait_group.read 0;" ::: "memory"); }
        if (aw == 0) TFLUSH();
    }
}

__device__ __forceinline__ void conv_main(const Params& p, uint32_t sb, int warp, int lane, int bid, unsigned epoch, uint32_t (&w)[12]) {
    asm volatile("setmaxnreg.inc.sync.aligned.u32 168;");
    const int g = lane >> 2, t = lane & 3, mi = lane >> 3, r8 = lane & 7;
    const int rank = bid & 1;
    const uint32_t bar_y = sb + SC_MISC, bar_v = bar_y + 40;
    next_epoch(p, epoch);
    if (warp < 4) {
        asm volatile("" :: "r"(w[0]), "r"(w[2]), "r"(w[4]), "r"(w[6]), "r"(w[8]), "r"(w[10]) : "memory");
        bar_arrive(BC_KG, 384);
    } else {
        const uint4* src = p.s->kp + (4 * bid + warp - 4) * 128 + lane;
        for (int it = 0;; it++) {
            uint32_t bad = 0;
#pragma unroll
            for (int i = 0; i < 4; i++) { const uint4 v = ld_rlx128(src + 32 * i); w[3 * i] = v.x; w[3 * i + 1] = v.y; w[3 * i + 2] = v.z; bad |= v.w ^ ~epoch; }
            const bool ok = __all_sync(0xffffffffu, bad == 0);
            if (ok) break;
            if (it > (1 << 20)) __trap();
        }
    }
    if ((warp & 3) == 0) TSTAMP(5 + (warp >> 2));
    {
        const uint32_t kt = sb + SC_KT + warp * KT_BYTES;
        uint32_t e[4], x[4], re[4], rx[4];
#pragma unroll
        for (int i = 0; i < 4; i++) {
            e[i] = w[6 * (i >> 1) + (i & 1)]; x[i] = w[6 * (i >> 1) + 2 + (i & 1)];
            re[i] = __shfl_sync(0xffffffffu, e[i], lane + 31);
            rx[i] = __shfl_sync(0xffffffffu, x[i], lane + (i == 0 && lane == 29 ? 5 : 1 + 2 * t));
        }
        asm volatile("stmatrix.sync.aligned.m8n8.x4.trans.shared.b16 [%0], {%1,%2,%3,%4};"
                     :: "r"(kt + (r8 < 4 ? (KT_D + 7) * 4 + 64 * r8 + 16 * mi : 716 * 4)), "r"(w[4]), "r"(w[5]), "r"(w[10]), "r"(w[11]) : "memory");
        if (lane == 2) {
            sts32(kt + (KT_C + 78) * 4, w[4] & 0xffffu);
            sts128(kt + (KT_T + 2) * 4, 0, w[4] & 0xffffu, __byte_perm(w[4], 0, 0x1010), w[4] << 16);
        }
        if (lane == 29) x[3] = bsub2(x[3], rx[0] & 0xffffu);
#pragma unroll
        for (int i = 0; i < 4; i++) {
            sts64(kt + (16 + 64 * i) * 4 + 8 * lane, __byte_perm(e[i], lane ? re[i] : i ? re[i - 1] : 0, 0x5432), e[i]);
            const uint32_t aa = __byte_perm(x[i], 0, 0x3232);
            if (t < 2) sts128(kt + (272 + 64 * i + 8 * g + 4 * t) * 4, i == 0 && lane == 0 ? __byte_perm(x[0], re[3], 0x5432) : aa, aa, x[i],
                              __byte_perm(lane != 29 ? rx[i] : i < 3 ? rx[(i + 1) & 3] : 0, x[i], 0x5432));
            else sts32(kt + (KT_C - 50 + 8 * i + 32 * t + g) * 4, x[i]);
        }
    }
    asm volatile("barrier.cluster.wait.acquire.aligned;" ::: "memory");
    bar_sync(BC_S + swap01(warp), 64);
    if ((warp & 3) == 0) TSTAMP(7 + (warp >> 2));
    {
        const uint32_t ut = fresh(sb + SC_UT) + swap01(warp) * UT_STRIDE, kt = fresh(sb + SC_KT) + warp * KT_BYTES;
        uint32_t u1 = ut + (mi & 1) * UT_HALF + (8 + r8) * 16 + (mi >> 1) * 128;
        auto dup = [&](uint32_t v) { return v ^ p.zero; };
        uint32_t kp = kt + (16 + g - 2 * t) * 4;
        float acc[16][4];
        {
            const uint32_t c0 = lds32(kp + 2048), c1 = lds32(kp + 2080), c2 = lds32(kp + 2016), c3 = dup(c0);
            const uint32_t e0 = lds32(kp + (KT_T - 16) * 4), e1 = lds32(kp + (KT_T - 8) * 4), e2 = lds32(kp + (KT_T - 24) * 4), e3 = dup(e0);
            const uint32_t f0 = dup(e1), f1 = lds32(kp + KT_T * 4);
            const uint32_t uo = ut + UT_HALF + (7 + lane) * 16;
#pragma unroll
            for (int i = 0; i < 16; i++) { acc[i][0] = acc[i][1] = acc[i][2] = acc[i][3] = 0.f; }
#pragma unroll
            for (int mu = 0; mu < 8; mu += 4) {
                uint32_t b[4];
                ldsm4(b, uo + 128 * mu);
#pragma unroll
                for (int k = 0; k < 4; k++) mma_bf8(acc[mu + 8 + k], f0, f1, b[k]);
            }
#pragma unroll
            for (int mu = 0; mu < 12; mu += 2) {
                uint32_t b[4];
                ldsm4(b, u1 + 128 * mu);
                mma_bf(acc[mu + 4], c0, c1, c2, c3, b[0], b[1]);
                mma_bf(acc[mu + 5], c0, c1, c2, c3, b[2], b[3]);
                if (mu < 8) { mma_bf(acc[mu + 8], e0, e1, e2, e3, b[0], b[1]); mma_bf(acc[mu + 9], e0, e1, e2, e3, b[2], b[3]); }
            }
        }
        {
            float M[8][4];
#pragma unroll
            for (int i = 0; i < 8; i++) { M[i][0] = M[i][1] = M[i][2] = M[i][3] = 0.f; }
            uint32_t s[8][4], a3[4];
            const uint32_t kb = kp, ub = dup(u1), uc = u1 + (mi >> 1) * 128;
            auto frag = [&](uint32_t (&a)[4], uint32_t x) { a[0] = lds32(x); a[1] = lds32(x + 32); a[2] = lds32(x - 32); a[3] = dup(a[0]); };
            frag(a3, kp + 1536);
#pragma unroll
            for (int i = 0; i < 8; i++) ldsm4(s[i], u1 + (SC_ST - SC_UT) + 256 * i);
            __syncwarp();
#pragma unroll 1
            for (uint32_t ko = 0, uo = 0; ko != 512;) {
                uint32_t a2[4], a1[4], a0[4], b[4][4];
                ko = fresh(ko); uo = fresh(uo);
                kp = kb + ko; u1 = ub + uo;
                const uint32_t up = uc + uo;
                ko += 64; uo -= 16;
                frag(a2, kp + 1024);
#pragma unroll
                for (int i = 0; i < 4; i++) ldsm4(b[i], up + 512 * i);
                frag(a1, kp + 512); frag(a0, kp);
                kp += 64; u1 -= 16;
#pragma unroll
                for (int i = 0; i < 7; i++) mma_bf(acc[2 * i + 2], a3[0], a3[1], a3[2], a3[3], s[i][0], s[i][1]);
#pragma unroll
                for (int e = 0; e < 4; e++) a3[e] = bsub2(a2[e], a3[e]);
#pragma unroll
                for (int i = 0; i < 7; i++) mma_bf(acc[2 * i + 3], a2[0], a2[1], a2[2], a2[3], s[i][2], s[i][3]);
#pragma unroll
                for (int i = 0; i < 7; i++) mma_bf(M[i + 1], a3[0], a3[1], a3[2], a3[3], b[i >> 1][2 * (i & 1)], b[i >> 1][2 * (i & 1) + 1]);
                frag(a3, kp + 1536);
#pragma unroll
                for (int i = 0; i < 8; i++) mma_bf(acc[2 * i], a1[0], a1[1], a1[2], a1[3], s[i][0], s[i][1]);
#pragma unroll
                for (int e = 0; e < 4; e++) a1[e] = bsub2(a0[e], a1[e]);
#pragma unroll
                for (int i = 0; i < 8; i++) { mma_bf(acc[2 * i + 1], a0[0], a0[1], a0[2], a0[3], s[i][2], s[i][3]); ldsm4(s[i], u1 + (SC_ST - SC_UT) + 256 * i); }
#pragma unroll
                for (int i = 0; i < 8; i++) mma_bf(M[i], a1[0], a1[1], a1[2], a1[3], b[i >> 1][2 * (i & 1)], b[i >> 1][2 * (i & 1) + 1]);
            }
            u1 = ub;
#pragma unroll
            for (int i = 0; i < 8; i++)
#pragma unroll
                for (int c = 0; c < 4; c++) { acc[2 * i][c] += M[i][c]; acc[2 * i + 1][c] -= M[i][c]; }
        }
        if ((warp & 3) == 0) TSTAMP(11 + (warp >> 2));
        mbar_wait(bar_v);
        const uint32_t vt = fresh(sb + SC_V) + swap01(warp) * V_STRIDE;
        const uint32_t g1 = fresh(u1) - ut + sb + SC_GT;
        const uint32_t ydst = sb + SC_RT + rank * Y_RS + warp * Y_CS + lane * 16;
        const uint32_t ydr = mapa(ydst, rank ^ 1), ybr = mapa(bar_y, rank ^ 1);
        auto stairs = [&](auto R) {
        uint32_t ug[2][2][4];
        auto ld_ug = [&](int i) { ldsm4t(ug[i & 1][0], u1 + 256 * i); ldsm4t(ug[i & 1][1], g1 + 256 * i); };
        auto ship = [&](int i) {
            const uint32_t (&u)[4] = ug[i & 1][0], (&gg)[4] = ug[i & 1][1];
            const uint32_t y0 = gmix(gg[0], acc[2 * i][0], acc[2 * i][1], u[0]), y1 = gmix(gg[1], acc[2 * i][2], acc[2 * i][3], u[1]);
            const uint32_t y2 = gmix(gg[2], acc[2 * i + 1][0], acc[2 * i + 1][1], u[2]), y3 = gmix(gg[3], acc[2 * i + 1][2], acc[2 * i + 1][3], u[3]);
            if ((i & 1) != R.value) st_async128(ydr + 512 * (i >> 1), y0, y1, y2, y3, ybr + 8 * (i >> 1));
            else asm volatile("{ .reg .pred q; setp.eq.u32 q, %6, 0; st.shared.v4.u32 [%0], {%2,%3,%4,%5}; bar.warp.sync 0xffffffff; @q mbarrier.arrive.shared::cta.b64 _, [%1]; }"
                              :: "r"(ydst + 512 * (i >> 1)), "r"(bar_y + 8 * (i >> 1)), "r"(y0), "r"(y1), "r"(y2), "r"(y3), "r"(lane) : "memory");
        };
        const uint32_t VD = vt + (VC_OFF - 400 - 16 * t) * 4 + (8 * g ^ 16 * (-t & 2)), VD2 = vt + (VC_OFF - 415 - 16 * t) * 4 + (8 * g ^ 16 * (~t & 2));
        uint2 bd[10];
        uint32_t x[2][4][4];
        auto ld4 = [&](uint32_t (&v)[4], int dl) { const uint2 w = lds64(VD + 256 * dl); v[0] = w.x; v[1] = w.y; v[2] = lds32(VD2 + 256 * dl); v[3] = dup(w.x); };
        auto mm4 = [&](const uint32_t (&v)[4], int dl) {
#pragma unroll
            for (int s = dl & 1; s < 10; s += 2) if ((dl + s) / 2 < 16) mma_bf(acc[(dl + s) / 2], v[0], v[1], v[2], v[3], bd[s].x, bd[s].y);
        };
        const uint32_t KE = kt + (KT_D + g + t) * 4, VE = vt + (VE_BASE - 912 - 16 * t) * 4 + (8 * g ^ 16 * (~t & 2));
        uint32_t b0[8], b1[8];
        auto ld8 = [&](uint32_t (&v)[4], int dl) { const uint2 w = lds64(VE + 512 * dl), z = lds64(VE + 512 * dl - 256); v[0] = w.x; v[1] = w.y; v[2] = z.x; v[3] = z.y; };
        auto mm8 = [&](const uint32_t (&v)[4], int dl, int lo, int hi) {
#pragma unroll
            for (int s = 0; s < 8; s++) if (dl + s >= lo && dl + s < hi) mma_bf(acc[dl + s], v[0], v[1], v[2], v[3], b0[s], b1[s]);
        };
        ld_ug(0); ld4(x[0][0], 6);
#pragma unroll
        for (int s = 0; s < 10; s++) bd[s] = lds64(kt + (KT_C + 2 * g + 2 * t + 8 * s) * 4);
        ld_ug(1);
        ship(0);
        mm4(x[0][0], 6);
        uint32_t e[4][4];
#pragma unroll
        for (int k = 1; k < 6; k++) {
#pragma unroll
            for (int j = 0; j < 4; j++) ld4(x[k & 1][j], 4 * k + 3 + j);
            ld_ug(k + 1);
            if (k == 3) {
#pragma unroll
                for (int s = 0; s < 8; s++) { b0[s] = lds32(KE + 32 * s); b1[s] = lds32(KE + 32 * s + 16); }
            }
            ship(k);
#pragma unroll
            for (int j = 0; j < 4; j++) {
                mm4(x[k & 1][j], 4 * k + 3 + j);
                if (k == 3) { uint32_t v[4], z[4]; ld8(e[j], 8 + j); ld8(v, 12 + j); ld4(z, 30 - j); mm8(v, 12 + j, 12, 16); mm8(e[j], 8 + j, 8, 12); mm4(z, 30 - j); }
                if (k == 5) { ld8(e[j], 8 + j + p.zero); mm8(e[j], 8 + j, 12, 16); }
            }
        }
        ld_ug(7);
        ship(7 - R.value); ship(6 + R.value);
        };
        if (rank) stairs(std::integral_constant<int, 1>()); else stairs(std::integral_constant<int, 0>());
        if ((warp & 3) == 0) TSTAMP(14 + (warp >> 2)); else TSTAMP(21 + warp);
    }
}

constexpr int SF_WD = 147456;
constexpr int SF_H = 81920;
constexpr int SF_RED = 131072;
constexpr int SF_XS = 221184;
constexpr int SF_MISC = SF_XS + 8 * 1168;
constexpr int SF_KG = SF_MISC - 10 * KG_STAGE;
constexpr int SF_WR = SF_KG - 2304;
constexpr int FB_X = 64, FB_RDONE = 72, FB_FREE = 80, FB_KDONE = 88, FB_KEYS = 96, FB_W = 112, FB_D = FB_W + 72, FB_H = FB_D + 96, FS_PART = 512, FS_TOK = 896;
enum { BAR_F = 6, BAR_R = 7, BAR_GU = 8, BAR_RED = 9, BAR_R2 = 10, BAR_X = 11 };
static_assert(NPRE <= 10 && SF_KG % 128 == 0 && SF_KG >= 7 * 24576 && SF_WR - 4 * 9216 >= 5 * 24576 && SF_WR - 6 * 9216 >= 5 * 16384, "layout");

__device__ __forceinline__ void ffn_front(const Params& p, const CUtensorMap* maps, uint32_t sb, int warp, int lane, int f, unsigned epoch) {
    const unsigned t0 = clock32();
    const int g = lane >> 2, t = lane & 3, mi = lane >> 3, r8 = lane & 7;
    const bool isx = f < NX;
    const int nrw = f < 8 ? 6 : 4, r0 = f < 8 ? 48 * f : 128 + 32 * f;
    const int rw = warp < 12 ? 13 - warp : warp ^ (warp < 14 ? 10 : 15);
    const uint32_t bar_row = sb + SF_MISC  , bar_x = bar_row + FB_X;
    const uint32_t s_part = bar_row + FS_PART  , s_tok = bar_row + FS_TOK  ;
    const uint32_t rows = sb + SF_WR - 9216 * (rw + 1);
    if (lane == 0) {
        mbar_init(bar_row + 8 * rw, 1); mbar_fence();
        if (rw < nrw) { mbar_expect(bar_row + 8 * rw, 9216); until(t0, RDELAY); bulk_g2s(rows, p.u + (size_t)(r0 + 8 * rw) * DM, 9216, bar_row + 8 * rw); }
        else if (rw >= 6) { mbar_expect(bar_row + 8 * rw, 1152); bulk_g2s(sb + SF_WR + (rw & 1) * 1152, (rw & 1) ? p.gatew : p.wr, 1152, bar_row + 8 * rw); }
        if (warp >= 10) {
#pragma unroll 1
            for (int i = warp - 10; i < 39; i += 6) mbar_init(bar_x + 8 * i, i == 1 ? nrw : i == 2 ? 4 : 1);
        }
        mbar_fence();
    }
    const int ks0 = isx ? 4 * f : 6 * f - 72, nt = isx ? 4 : 6;
    uint4* const kdst = p.s->keys + (lane >> 1) * 128 + 2 * f + (lane & 1);
    if (warp == 13) {
        stg128(kdst, 0, 0, 0, 0);
        sts32(s_part + 64 + lane * 4, 0);
        if (lane < 8 && isx && !(f & 1)) st_rlx32(&p.s->sel[32 * f + lane], 0);
    }
    __syncwarp();
    bar_sync(BAR_F, f < 12 ? 256 : 192);
    bar_arrive(0, NTHR);
    if (warp == 15) TSTAMP(1);

    if (warp == 12) {
        if (lane == 0) {
            const CUtensorMap* m = maps + (isx ? 1 : 3);
            prefetch_map(m); prefetch_map(m + 1);
            unsigned tb = t0 + WDELAY;
#pragma unroll 1
            for (int n = 0; n < 18; n++) {
                if (n == NPRE) { mbar_wait(bar_row + FB_KEYS); mbar_wait(bar_row + FB_KDONE); tb = clock32() + RESUME; }
                until(tb, 0); tb += n < NFAST - 1 || n >= NPRE ? WGAP : n == NFAST - 1 ? WJUMP : WGAP2;
                const uint32_t b = bar_row + FB_W + 8 * (n >> 1);
                if (!(n & 1)) mbar_expect(b, nt * 4096);
                tma3d(sb + n * nt * 2048, m + (n & 1), 0, 64 * (n >> 1), ks0 >> 1, b);
            }
            TSTAMP(12);
            if (isx) {
                prefetch_map(maps + 5);
#pragma unroll 1
                for (int n = 0; n < 12; n++) {
                    until(tb, 0); tb += DGAP;
                    if (n == 6) mbar_wait(bar_row + FB_FREE);
                    mbar_expect(bar_row + FB_D + 8 * n, 12288);
                    tma2d(sb + (n < 6 ? SF_WD : -6 * 12288) + n * 12288, maps + 5, 32 * (f >> 1), 2304 * (f & 1) + 192 * n, bar_row + FB_D + 8 * n);
                }
                TSTAMP(13);
            }
        }
    } else if (warp == 13) {
        const uint32_t tag = key_tag(epoch), par = (epoch & 1) ? 0u : 0x8000u;
        next_epoch(p, epoch);
        bar_sync(BAR_R, 32 * (nrw + 1));
        TSTAMP(3);
        {
            const uint32_t sg = fresh(s_part) + 192 + lane * 4;
            const uint32_t gb = pack_bf16(sigmoidf_(rbf(__uint_as_float(lds32(sg)))), sigmoidf_(rbf(__uint_as_float(lds32(sg + 128))))) | par | (par << 16);
            asm volatile("st.relaxed.gpu.global.u16 [%0], %1;" :: "l"(p.s->gate + r0 + lane), "h"((unsigned short)gb) : "memory");
            if (nrw > 4 && lane < 16) asm volatile("st.relaxed.gpu.global.u16 [%0], %1;" :: "l"(p.s->gate + r0 + 32 + lane), "h"((unsigned short)(gb >> 16)) : "memory");
        }
        bar_sync(BAR_R2, 32 * (nrw + 1));
        {
            const uint4 v = lds128(fresh(s_tok) + (lane & 1) * 16);
            asm volatile("st.relaxed.gpu.global.v4.u32 [%0], {%1,%2,%3,%4};" :: "l"(kdst), "r"(v.x | tag), "r"(v.y | tag), "r"(v.z | tag), "r"(v.w | tag) : "memory");
        }
        TSTAMP(4);
        if (lane == 0) { mbar_arrive(bar_row + FB_KEYS); mbar_expect(bar_x, 8 * 1152); }
        uint32_t k[16];
        const uint4* src = p.s->keys + (f & 15) * 128 + lane;
        for (int it = 0;; it++) {
            uint32_t bad = 0;
#pragma unroll
            for (int i = 0; i < 4; i++) {
                const uint4 x = ld_rlx128(src + (i < 3 || lane < 24 ? 32 * i : 64));
                k[i] = x.x; k[4 + i] = x.y; k[8 + i] = x.z; k[12 + i] = x.w;
                bad |= x.x ^ tag;
            }
            const bool ok = __all_sync(0xffffffffu, (bad & 0xf800u) == 0);
            if (it < 8) TSTAMP(it < 4 ? 16 + it : 20 + it);
            if (ok) break;
            if (it > (1 << 20)) __trap();
        }
        TSTAMP(5);
        uint32_t key = 0;
#pragma unroll 2
        for (int r = 0; r < 8; r++) {
            const uint32_t m = __reduce_max_sync(0xffffffffu, max(max(k[0], k[1]), max(k[2], k[3])));
#pragma unroll
            for (int i = 0; i < 4; i++) {
                const bool pop = k[i] == m;
                k[i] = pop ? k[4 + i] : k[i]; k[4 + i] = pop ? k[8 + i] : k[4 + i]; k[8 + i] = pop ? k[12 + i] : k[8 + i]; k[12 + i] = pop ? 0 : k[12 + i];
            }
            if (r8 == r) key = m;
        }
        const int row = key_row(key);
        sts32(s_tok + r8 * 8, row);
        bar_arrive(BAR_X, 288);
        TSTAMP(6);
        if (isx) {
            if (!(f & 1)) {
                __nv_bfloat16* o = p.out + (size_t)row * DM + 16 * f + 8 * mi;
                asm volatile("st.relaxed.gpu.global.v4.u32 [%0], {%1,%1,%1,%1};" :: "l"(o), "r"(0) : "memory");
                if (__any_sync(0xffffffffu, ld_rlx32(o) != 0)) __trap();
                if (lane < 8) st_rlx32(&p.s->sel[32 * f + lane], key);
            } else wait_sel(p, f >> 1, r8, tag);
            uint32_t gb;
            for (int it = 0;; it++) {
                asm volatile("ld.relaxed.gpu.global.u16 %0, [%1];" : "=r"(gb) : "l"(p.s->gate + row) : "memory");
                gb ^= par;
                if (!(gb & 0x8000u)) break;
                if (it > (1 << 20)) __trap();
            }
            const uint32_t rb = key ^ 0x80000000u, rv = (rb ^ (((int)rb >> 31) & 0x7fff0000u)) & 0xffff0000u;
            sts32(s_tok + r8 * 8 + 4, __float_as_uint(rbf(1.0f - bf_lo(gb)) * rbf(sigmoidf_(__uint_as_float(rv)))));
            __syncwarp();
            TSTAMP(7);
            bar_arrive(BAR_RED, 416);
        }
    } else {
        if (rw < nrw) {
            float c[3][4];
#pragma unroll
            for (int i = 0; i < 3; i++) { c[i][0] = c[i][1] = c[i][2] = c[i][3] = 0.f; }
            mbar_wait(bar_row + 48); mbar_wait(bar_row + 56);
            const uint32_t b = fresh(sb + SF_WR) + (g & 1) * 1152 + (g >> 2) * 64 + t * 16 + (g & 2) * 2;
            uint32_t w[18][2];
#pragma unroll
            for (int kb = 0; kb < 18; kb++) { const uint32_t o = ((kb & 1) ? b ^ 64 : b) + 128 * (kb >> 1); w[kb][0] = lds32(o); w[kb][1] = lds32(o + 8); }
            mbar_wait(bar_row + 8 * rw);
            if (warp == 15) TSTAMP(2);
            const uint32_t a = fresh(rows) + g * 1152 + (g & 1) * 64 + t * 16;
#pragma unroll
            for (int kb = 0; kb < 18; kb++) {
                const uint4 x = lds128(((kb & 1) ? a ^ 64 : a) + 128 * (kb >> 1));
                mma_bf(c[kb % 3], x.x, x.y, x.z, x.w, w[kb][0], w[kb][1]);
            }
            const float sr = c[0][0] + c[1][0] + c[2][0] + __shfl_down_sync(0xffffffffu, c[0][2] + c[1][2] + c[2][2], 1);
            const float sg = c[0][1] + c[1][1] + c[2][1] + __shfl_down_sync(0xffffffffu, c[0][3] + c[1][3] + c[2][3], 1);
            const uint32_t rb = pack_bf16(0.f, sr);
            if (t == 2 * (g & 1)) {
                sts32(s_part + (8 * rw + g) * 4, (rb ^ (((int)rb >> 31) & 0x7fff0000u) ^ 0x80000000u) | (uint32_t)(2047 - r0 - 8 * rw - g));
                sts32(s_part + 192 + (8 * rw + g) * 4, __float_as_uint(sg));
            }
            __syncwarp();
            bar_sync(BAR_R, 32 * (nrw + 1));
            const uint32_t sk = fresh(s_part), kk = lds32(sk + (8 * rw + r8) * 4);
            int n = 0;
#pragma unroll
            for (int i = 0; i < 3; i++) { const uint4 v = lds128(sk + mi * 48 + 16 * i); n += (v.x > kk) + (v.y > kk) + (v.z > kk) + (v.w > kk); }
            n += __shfl_xor_sync(0xffffffffu, n, 8); n += __shfl_xor_sync(0xffffffffu, n, 16);
            if (n < 8) sts32(s_tok + 4 * n, kk);
            __syncwarp();
            bar_arrive(BAR_R2, 32 * (nrw + 1));
        }
    }
}

__device__ __forceinline__ void ffn_work(const Params& p, uint32_t sb, int warp, int lane, int f, unsigned epoch) {
    const int g = lane >> 2, t = lane & 3, mi = lane >> 3, r8 = lane & 7;
    const bool isx = f < NX;
    const int ks0 = isx ? 4 * f : 6 * f - 72, nt = isx ? 4 : 6;
    const uint32_t bar_x = sb + SF_MISC + FB_X, bar_free = sb + SF_MISC + FB_FREE, bar_w = sb + SF_MISC + FB_W, bar_d = sb + SF_MISC + FB_D, bar_h = sb + SF_MISC + FB_H, s_tok = sb + SF_MISC + FS_TOK;
    next_epoch(p, epoch);
    if (warp < 8) {
        bar_sync(BAR_X, 288);
        const int row = __shfl_sync(0xffffffffu, lds32(fresh(s_tok) + 8 * warp), 0);
        if (lane == 0) bulk_g2s(sb + SF_XS + warp * 1168, p.u + (size_t)row * DM, 1152, bar_x);
        __syncwarp();
    }
    {
        if (warp < nt) {
            float ag[2][4], au[2][4];
#pragma unroll
            for (int i = 0; i < 2; i++) { ag[i][0] = ag[i][1] = ag[i][2] = ag[i][3] = 0.f; au[i][0] = au[i][1] = au[i][2] = au[i][3] = 0.f; }
            const uint32_t wb = sb + (warp >> 1) * 4096 + (r8 + 8 * (mi >> 1)) * 64 + (((2 * (warp & 1) + (mi & 1)) ^ (r8 >> 1)) << 4);
            const uint32_t xb = sb + SF_XS + r8 * 1168 + mi * 16;
            mbar_wait(bar_x);
            if (warp == 0) TSTAMP(8);
            uint32_t fr[2][10][4];
            auto load = [&](uint32_t (&v)[10][4], int n) {
                mbar_wait(bar_w + 8 * n);
                const uint32_t wk = fresh(wb) + n * nt * 4096, xk = fresh(xb) + 128 * n;
                ldsm4(v[8], xk); ldsm4(v[9], xk + 64);
#pragma unroll
                for (int s = 0; s < 4; s++) { ldsm4t(v[s], wk + 1024 * s); ldsm4t(v[4 + s], wk + 1024 * s + nt * 2048); }
            };
            auto mul = [&](const uint32_t (&v)[10][4]) {
#pragma unroll
                for (int s = 0; s < 4; s++) {
                    mma_bf(ag[s & 1], v[s][0], v[s][1], v[s][2], v[s][3], v[8 + (s >> 1)][2 * (s & 1)], v[8 + (s >> 1)][2 * (s & 1) + 1]);
                    mma_bf(au[s & 1], v[4 + s][0], v[4 + s][1], v[4 + s][2], v[4 + s][3], v[8 + (s >> 1)][2 * (s & 1)], v[8 + (s >> 1)][2 * (s & 1) + 1]);
                }
            };
            load(fr[0], 0);
#pragma unroll 1
            for (int n = 1; n < 9; n += 2) {
                load(fr[1], n); mul(fr[0]);
                if (n == 5) {
                    asm volatile("" :: "f"(ag[0][0]), "f"(ag[1][0]), "f"(au[0][0]), "f"(au[1][0]) : "memory");
                    if (lane == 0 && isx) mbar_arrive(bar_free);
                }
                load(fr[0], n + 1); mul(fr[1]);
            }
            mul(fr[0]);
            if (warp == 0) TSTAMP(9);
            float h[4];
#pragma unroll
            for (int c = 0; c < 4; c++) {
                const float gv = rbf(ag[0][c] + ag[1][c]);
                h[c] = rbf(gv * sigmoidf_(gv)) * rbf(au[0][c] + au[1][c]);
            }
            uint32_t h0, h1;
            asm("movmatrix.sync.aligned.m8n8.trans.b16 %0, %1;" : "=r"(h0) : "r"(pack_bf16(h[0], h[1])));
            asm("movmatrix.sync.aligned.m8n8.trans.b16 %0, %1;" : "=r"(h1) : "r"(pack_bf16(h[2], h[3])));
            if (h0 == 0) h0 = 0x8000u;
            asm volatile("{ .reg .b64 v; mov.b64 v, {%1, %2}; st.relaxed.gpu.global.b64 [%0], v; }" :: "l"(p.s->h + ((epoch & 1) * 288 + ks0 + warp) * 32 + lane), "r"(h0), "r"(h1) : "memory");
        }
        if (isx) {
            bar_sync(BAR_GU, 384);
            if (warp == 0) TSTAMP(10);
            uint2 hb[12];
            const uint32_t hs = sb + SF_H + warp * 3072;
            const uint2* hsrc = p.s->h + ((__shfl_sync(0xffffffffu, epoch, 0) & 1) * 288 + 144 * (f & 1) + 12 * warp) * 32;
            for (int it = 0;; it++) {
                if (lane == 0) { mbar_expect(bar_h + 8 * warp, 3072); bulk_g2s(hs, hsrc, 3072, bar_h + 8 * warp); }
                mbar_wait(bar_h + 8 * warp, it & 1);
                const uint32_t hf = fresh(hs) + lane * 8;
                uint32_t mn = 0xffffffffu;
#pragma unroll
                for (int s = 0; s < 12; s++) { hb[s] = lds64(hf + 256 * s); mn = min(mn, hb[s].x); }
                if (__all_sync(0xffffffffu, mn != 0)) break;
                if (it > (1 << 16)) __trap();
            }
            if (warp == 0) TSTAMP(11);
            mbar_wait(bar_d + 8 * warp);
            if (warp == 11) TSTAMP(14);
            float ad[2][2][4];
#pragma unroll
            for (int i = 0; i < 4; i++) { ad[i >> 1][i & 1][0] = ad[i >> 1][i & 1][1] = ad[i >> 1][i & 1][2] = ad[i >> 1][i & 1][3] = 0.f; }
            const uint32_t wd = fresh(sb) + (warp < 6 ? SF_WD : -6 * 12288) + warp * 12288 + (r8 + 8 * (mi >> 1)) * 64 + (((mi & 1) ^ (r8 >> 1)) << 4);
#pragma unroll
            for (int s = 0; s < 12; s++) {
                uint32_t a[4], b[4];
                ldsm4t(a, wd + 1024 * s); ldsm4t(b, (wd ^ 32) + 1024 * s);
                mma_bf(ad[0][s & 1], a[0], a[1], a[2], a[3], hb[s].x, hb[s].y);
                mma_bf(ad[1][s & 1], b[0], b[1], b[2], b[3], hb[s].x, hb[s].y);
            }
            const uint32_t rd = sb + SF_RED + warp * 1152 + (72 * t + g) * 4;
#pragma unroll
            for (int i = 0; i < 8; i++) sts32(rd + (i >> 2) * 64 + (i & 1) * 144 + ((i >> 1) & 1) * 32, __float_as_uint(ad[i >> 2][0][i & 3] + ad[i >> 2][1][i & 3]));
            bar_sync(BAR_RED, 416);
            if (warp < 4) {
                const int tid = 32 * warp + lane;
                const uint32_t rs = fresh(sb + SF_RED) + (tid >> 4) * 144 + (tid & 15) * 8;
                const uint2 tk = lds64(fresh(s_tok) + (tid >> 4) * 8);
                float x = 0.f, y = 0.f;
#pragma unroll
                for (int w = 0; w < 12; w++) { const uint2 v = lds64(rs + w * 1152); x += __uint_as_float(v.x); y += __uint_as_float(v.y); }
                asm volatile("red.relaxed.gpu.global.add.noftz.bf16x2 [%0], %1;" :: "l"(p.out + (size_t)tk.x * DM + 32 * (f >> 1) + 2 * (tid & 15)),
                             "r"(pack_bf16(x * __uint_as_float(tk.y), y * __uint_as_float(tk.y))) : "memory");
            }
            if (warp == 0) TSTAMP(15);
        }
        if (warp == 0) TFLUSH();
    }
}

constexpr int SMEM_BYTES = 232448;
static_assert(SF_MISC + 1024 <= 232192, "layout");

struct Maps { CUtensorMap m[7]; };

__global__ void __cluster_dims__(2, 1, 1) __launch_bounds__(NTHR, 1)
fused_kernel(const Params p, const __grid_constant__ Maps maps) {
    extern __shared__ __align__(1024) uint8_t smem_raw[];
    uint32_t q[8];
    {
        const int b = blockIdx.x, x = threadIdx.x, rc = 4 * b + max(b - 84, 0) - 288 + (x >> 6);
        const int cv = (b - NCONV) >> 31, ca = 8 * b + ((x >> 5) & 3), cb = 2 * rc - (rc & 3) + 4;
        const uint32_t ch = (ca & cv) | (cb & ~cv), o = NST * ch + 2 * ((x & 31) + ((x >> (cv & 2)) & 32));
        const bool c = x < (b < 84 ? 256 : 320);
        q[6] = ldg16_if(c, p.logdt + ch);
        q[2] = ldg32_if(c, p.Bre + o); q[3] = ldg32_if(c, p.Bim + o); q[4] = ldg32_if(c, p.Cre + o); q[5] = ldg32_if(c, p.Cim + o); q[0] = ldg32_if(c, p.Are + o); q[1] = ldg32_if(c, p.Aim + o);
        q[7] = ldg16_if(c, p.Dskip + ch);
    }
    const unsigned epoch = ld_rlx32(&p.s->epoch[blockIdx.x * 16 + (threadIdx.x >> 5)]);
    const uint32_t sb = __shfl_sync(0xffffffffu, smem_u32(smem_raw), 0);
    const int warp = __shfl_sync(0xffffffffu, threadIdx.x >> 5, 0), bid = __shfl_sync(0xffffffffu, blockIdx.x, 0);
    const int lane = __shfl_sync(0xffffffffu, threadIdx.x & 31, threadIdx.x);
    const bool conv = bid < NCONV;
    const int f = bid - NCONV;
    uint32_t w[12];
    if (warp < (f < 12 ? 8 : 10)) {
        const int half = conv ? warp >> 2 : warp & 1, pr = conv ? warp & 3 : warp >> 1;
        const int rc = 4 * f + max(f - 12, 0) + pr;
        const uint32_t stage = sb + (conv ? SC_KG : SF_KG) + warp * KG_STAGE;
        uint4* const kp = p.s->kp + rc * 128 + lane;
        kgen(q, sb, half, stage, stage + (conv ? 4 : 1) * KG_STAGE, 1 + pr, lane, p.zero, w, [&] {
            sts128z_if(conv && lane < 20, sb + SC_KT + warp * KT_BYTES + lane * 16 + (lane < 4 ? 0 : lane < 14 ? 2048 : 2288));
            stg128z_if(!conv, kp + 64 * half); stg128z_if(!conv, kp + 64 * half + 32);
            stg128z_if(!conv && warp < (f < NX ? 4 : 6), (uint4*)(p.s->h + ((lane >> 4) * 288 + (f < NX ? 4 * f : 6 * f - 72) + warp) * 32) + (lane & 15));
            if (conv) asm volatile("barrier.cluster.arrive.relaxed.aligned;" ::: "memory");
        });
        if (conv) { conv_main(p, sb, warp, lane, bid, epoch, w); return; }
        {
            if (!half) {
#pragma unroll
                for (int i = 0; i < 4; i++) asm volatile("st.relaxed.gpu.global.v4.u32 [%0], {%1,%2,%3,%4};" :: "l"(kp + 32 * i), "r"(w[3 * i]), "r"(w[3 * i + 1]), "r"(w[3 * i + 2]), "r"(~epoch) : "memory");
            }
            if (warp == 0) TSTAMP(22);
            if (warp == 2) TSTAMP(23);
            bar_sync(0, NTHR);
            if (warp == 0 && lane == 0) mbar_arrive(sb + SF_MISC + FB_KDONE);
        }
    } else if (conv) {
        conv_aux(p, maps.m, sb, warp - 8, lane, bid, epoch);
        return;
    } else {
        ffn_front(p, maps.m, sb, warp, lane, f, epoch);
        if (warp >= 12) return;
    }
    __syncwarp();
    ffn_work(p, sb, warp, lane, f, epoch);
}

typedef CUresult (*EncodeFn)(CUtensorMap*, CUtensorMapDataType, cuuint32_t, void*, const cuuint64_t*, const cuuint64_t*, const cuuint32_t*, const cuuint32_t*,
                             CUtensorMapInterleave, CUtensorMapSwizzle, CUtensorMapL2promotion, CUtensorMapFloatOOBfill);

void make_map(EncodeFn fn, CUtensorMap* m, const void* base, int rank, const cuuint64_t* dims, const cuuint64_t* strides, const cuuint32_t* box, CUtensorMapSwizzle sw) {
    const cuuint32_t es[5] = {1, 1, 1, 1, 1};
    fn(m, CU_TENSOR_MAP_DATA_TYPE_BFLOAT16, rank, (void*)base, dims, strides, box, es, CU_TENSOR_MAP_INTERLEAVE_NONE, sw,
       CU_TENSOR_MAP_L2_PROMOTION_NONE, CU_TENSOR_MAP_FLOAT_OOB_FILL_NONE);
}

}

extern "C" void kernel_launch(void* const* d_in, const int* in_sizes, int n_in, void* d_out, int out_size) {
    (void)in_sizes; (void)n_in; (void)out_size;
    static EncodeFn fn = nullptr;
    static void* scratch = nullptr;
    if (!fn) {
        void* ptr = nullptr; cudaDriverEntryPointQueryResult qr;
        cudaGetDriverEntryPoint("cuTensorMapEncodeTiled", &ptr, cudaEnableDefault, &qr);
        fn = (EncodeFn)ptr;
        cudaGetSymbolAddress(&scratch, g_scratch);
        cudaFuncSetAttribute(fused_kernel, cudaFuncAttributeMaxDynamicSharedMemorySize, SMEM_BYTES);
    }
    typedef const __nv_bfloat16* bp;
    Params p;
    p.u = (bp)d_in[0]; p.Are = (bp)d_in[1]; p.Aim = (bp)d_in[2]; p.Bre = (bp)d_in[3]; p.Bim = (bp)d_in[4]; p.Cre = (bp)d_in[5]; p.Cim = (bp)d_in[6];
    p.logdt = (bp)d_in[7]; p.Dskip = (bp)d_in[8]; p.wr = (bp)d_in[10]; p.gatew = (bp)d_in[14];
    p.out = (__nv_bfloat16*)d_out; p.s = (Scratch*)scratch; p.zero = 0;
    Maps maps;
    {
        const cuuint64_t dims[4] = {DM, 4, 16, 32}, strides[3] = {16 * DM * 2, DM * 2, 64 * DM * 2};
        const cuuint32_t box[4] = {16, 4, 16, 2};
        make_map(fn, &maps.m[0], d_in[0], 4, dims, strides, box, CU_TENSOR_MAP_SWIZZLE_32B);
    }
    for (int i = 0; i < 4; i++) {
        const cuuint64_t dims[3] = {32, DM, FF / 32}, strides[2] = {FF * 2, 64};
        const cuuint32_t box[3] = {32, 64, i < 2 ? 2u : 3u};
        make_map(fn, &maps.m[1 + i], d_in[11 + (i & 1)], 3, dims, strides, box, CU_TENSOR_MAP_SWIZZLE_64B);
    }
    {
        const cuuint64_t dims[2] = {DM, FF}, strides[1] = {DM * 2};
        const cuuint32_t box[2] = {32, 192};
        make_map(fn, &maps.m[5], d_in[13], 2, dims, strides, box, CU_TENSOR_MAP_SWIZZLE_64B);
    }
    {
        const cuuint64_t dims[5] = {DM, 4, 4, 2, L_SEQ}, strides[4] = {16 * DM * 2, 4 * DM * 2, 128 * DM * 2, DM * 2};
        const cuuint32_t box[5] = {16, 4, 4, 2, 1};
        make_map(fn, &maps.m[6], d_out, 5, dims, strides, box, CU_TENSOR_MAP_SWIZZLE_NONE);
    }
    fused_kernel<<<NCTA, NTHR, SMEM_BYTES>>>(p, maps);
}
```

```cpp
#include <cuda_runtime.h>
#include <cuda_bf16.h>
#include <cuda_fp16.h>
#include <cuda.h>
#include <stdint.h>
#include <type_traits>

#define RESUME 0
#define UDELAY 0
#define RDELAY 900
#define WDELAY 2000
#define WGAP 310
#define NPRE 7
#define DGAP 260

namespace {

constexpr int DM = 576, NST = 128, FF = 4608, L_SEQ = 2048;
constexpr int NCONV = 72, NX = 36, NFFN = 60, NCTA = 132, NTHR = 512;

struct __align__(128) Scratch {
    unsigned epoch[NCTA * 16];
    uint4 keys[16 * 128];
    uint32_t sel[18 * 64];
    uint16_t gate[L_SEQ];
    uint2 h[2 * 288 * 32];
    uint4 kp[288 * 128];
};
__device__ Scratch g_scratch;
#define TFLUSH()
#define TSTAMP(i)

struct Params {
    const __nv_bfloat16 *Are, *Aim, *Bre, *Bim, *Cre, *Cim, *logdt, *Dskip, *u, *wr, *gatew;
    __nv_bfloat16* out;
    Scratch* s;
    uint32_t zero;
};

__device__ __forceinline__ uint32_t smem_u32(const void* p) { return (uint32_t)__cvta_generic_to_shared(p); }
__device__ __forceinline__ uint32_t pack_bf16(float lo, float hi) { uint32_t r; asm("cvt.rn.bf16x2.f32 %0, %1, %2;" : "=r"(r) : "f"(hi), "f"(lo)); return r; }
__device__ __forceinline__ uint32_t pack_f16(float lo, float hi) { uint32_t r; asm("cvt.rn.f16x2.f32 %0, %1, %2;" : "=r"(r) : "f"(hi), "f"(lo)); return r; }
__device__ __forceinline__ float bf_lo(uint32_t w) { return __uint_as_float(w << 16); }
__device__ __forceinline__ float bf_hi(uint32_t w) { return __uint_as_float(w & 0xffff0000u); }
__device__ __forceinline__ float rbf(float x) { return bf_lo(pack_bf16(x, 0.f)); }
__device__ __forceinline__ uint32_t badd2(uint32_t a, uint32_t b) { uint32_t r; asm("add.rn.bf16x2 %0, %1, %2;" : "=r"(r) : "r"(a), "r"(b)); return r; }
__device__ __forceinline__ uint32_t bsub2(uint32_t a, uint32_t b) { uint32_t r; asm("sub.rn.bf16x2 %0, %1, %2;" : "=r"(r) : "r"(a), "r"(b)); return r; }
__device__ __forceinline__ uint32_t gmix(uint32_t ng, float ny0, float ny1, uint32_t u) {
    uint32_t r; asm("{ .reg .b32 t; fma.rn.bf16x2 t, %1, %3, %3; fma.rn.bf16x2 %0, %1, %2, t; }" : "=r"(r) : "r"(ng), "r"(pack_bf16(ny0, ny1)), "r"(u)); return r;
}
__device__ __forceinline__ void mma_bf(float (&c)[4], uint32_t a0, uint32_t a1, uint32_t a2, uint32_t a3, uint32_t b0, uint32_t b1) {
    asm("mma.sync.aligned.m16n8k16.row.col.f32.bf16.bf16.f32 {%0,%1,%2,%3}, {%4,%5,%6,%7}, {%8,%9}, {%0,%1,%2,%3};"
        : "+f"(c[0]), "+f"(c[1]), "+f"(c[2]), "+f"(c[3]) : "r"(a0), "r"(a1), "r"(a2), "r"(a3), "r"(b0), "r"(b1));
}
__device__ __forceinline__ void mma_bf8(float (&c)[4], uint32_t a0, uint32_t a1, uint32_t b0) {
    asm("mma.sync.aligned.m16n8k8.row.col.f32.bf16.bf16.f32 {%0,%1,%2,%3}, {%4,%5}, {%6}, {%0,%1,%2,%3};"
        : "+f"(c[0]), "+f"(c[1]), "+f"(c[2]), "+f"(c[3]) : "r"(a0), "r"(a1), "r"(b0));
}
__device__ __forceinline__ void mma_h(float (&c)[4], uint32_t a0, uint32_t a1, uint32_t a2, uint32_t a3, uint32_t b0, uint32_t b1) {
    asm("mma.sync.aligned.m16n8k16.row.col.f32.f16.f16.f32 {%0,%1,%2,%3}, {%4,%5,%6,%7}, {%8,%9}, {%0,%1,%2,%3};"
        : "+f"(c[0]), "+f"(c[1]), "+f"(c[2]), "+f"(c[3]) : "r"(a0), "r"(a1), "r"(a2), "r"(a3), "r"(b0), "r"(b1));
}
__device__ __forceinline__ uint32_t fresh(uint32_t a) { asm volatile("" : "+r"(a) :: "memory"); return a; }
__device__ __forceinline__ uint32_t lds16(uint32_t a) { uint32_t v; asm("ld.shared.u16 %0, [%1];" : "=r"(v) : "r"(a)); return v; }
__device__ __forceinline__ uint32_t lds32(uint32_t a) { uint32_t v; asm("ld.shared.u32 %0, [%1];" : "=r"(v) : "r"(a)); return v; }
__device__ __forceinline__ uint2 lds64(uint32_t a) { uint2 v; asm("ld.shared.v2.u32 {%0,%1}, [%2];" : "=r"(v.x), "=r"(v.y) : "r"(a)); return v; }
__device__ __forceinline__ uint4 lds128(uint32_t a) { uint4 v; asm("ld.shared.v4.u32 {%0,%1,%2,%3}, [%4];" : "=r"(v.x), "=r"(v.y), "=r"(v.z), "=r"(v.w) : "r"(a)); return v; }
__device__ __forceinline__ uint4 lds128v(uint32_t a) { uint4 v; asm volatile("ld.shared.v4.u32 {%0,%1,%2,%3}, [%4];" : "=r"(v.x), "=r"(v.y), "=r"(v.z), "=r"(v.w) : "r"(a) : "memory"); return v; }
__device__ __forceinline__ void ldsm4(uint32_t (&r)[4], uint32_t a) {
    asm("ldmatrix.sync.aligned.m8n8.x4.shared.b16 {%0,%1,%2,%3}, [%4];" : "=r"(r[0]), "=r"(r[1]), "=r"(r[2]), "=r"(r[3]) : "r"(a));
}
__device__ __forceinline__ void ldsm4t(uint32_t (&r)[4], uint32_t a) {
    asm("ldmatrix.sync.aligned.m8n8.x4.trans.shared.b16 {%0,%1,%2,%3}, [%4];" : "=r"(r[0]), "=r"(r[1]), "=r"(r[2]), "=r"(r[3]) : "r"(a));
}
__device__ __forceinline__ void sts16(uint32_t a, uint32_t v) { asm volatile("st.shared.u16 [%0], %1;" :: "r"(a), "h"((unsigned short)v) : "memory"); }
__device__ __forceinline__ void sts32(uint32_t a, uint32_t v) { asm volatile("st.shared.u32 [%0], %1;" :: "r"(a), "r"(v) : "memory"); }
__device__ __forceinline__ void sts64(uint32_t a, uint32_t x, uint32_t y) { asm volatile("st.shared.v2.u32 [%0], {%1,%2};" :: "r"(a), "r"(x), "r"(y) : "memory"); }
__device__ __forceinline__ void sts128(uint32_t a, uint32_t x, uint32_t y, uint32_t z, uint32_t w) {
    asm volatile("st.shared.v4.u32 [%0], {%1,%2,%3,%4};" :: "r"(a), "r"(x), "r"(y), "r"(z), "r"(w) : "memory");
}
__device__ __forceinline__ void st_async128(uint32_t a, uint32_t x, uint32_t y, uint32_t z, uint32_t w, uint32_t bar) {
    asm volatile("st.async.weak.shared::cluster.mbarrier::complete_tx::bytes.v4.b32 [%0], {%1,%2,%3,%4}, [%5];" :: "r"(a), "r"(x), "r"(y), "r"(z), "r"(w), "r"(bar) : "memory");
}
__device__ __forceinline__ void mbar_init(uint32_t b, uint32_t cnt) { asm volatile("mbarrier.init.shared::cta.b64 [%0], %1;" :: "r"(b), "r"(cnt) : "memory"); }
__device__ __forceinline__ void mbar_fence() { asm volatile("fence.mbarrier_init.release.cluster;" ::: "memory"); }
__device__ __forceinline__ void mbar_expect(uint32_t b, uint32_t bytes) { asm volatile("mbarrier.arrive.expect_tx.shared::cta.b64 _, [%0], %1;" :: "r"(b), "r"(bytes) : "memory"); }
__device__ __forceinline__ void mbar_arrive(uint32_t b) { asm volatile("mbarrier.arrive.shared::cta.b64 _, [%0];" :: "r"(b) : "memory"); }
#define CHINT ""
#define HINT ""
__device__ __forceinline__ void mbar_wait(uint32_t b, uint32_t parity = 0) {
    asm volatile("{ .reg .pred p; .reg .u32 n; mov.u32 n, 0;\n"
                 "LW: mbarrier.try_wait.parity.shared::cta.b64 p, [%0], %1" HINT "; @p bra LD; add.u32 n, n, 1; setp.lt.u32 p, n, 65536; @p bra LW; trap;\n"
                 "LD: }" :: "r"(b), "r"(parity) : "memory");
}
__device__ __forceinline__ void mbar_wait_cluster(uint32_t b) {
    asm volatile("{ .reg .pred p; .reg .u32 n; mov.u32 n, 0;\n"
                 "LW: mbarrier.try_wait.parity.acquire.cluster.shared::cta.b64 p, [%0], 0" CHINT "; @p bra LD; add.u32 n, n, 1; setp.lt.u32 p, n, 65536; @p bra LW; trap;\n"
                 "LD: }" :: "r"(b) : "memory");
}
__device__ __forceinline__ void tma2d(uint32_t dst, const CUtensorMap* m, int c0, int c1, uint32_t bar) {
    asm volatile("cp.async.bulk.tensor.2d.shared::cluster.global.mbarrier::complete_tx::bytes [%0], [%1, {%3, %4}], [%2];"
                 :: "r"(dst), "l"(m), "r"(bar), "r"(c0), "r"(c1) : "memory");
}
__device__ __forceinline__ void tma3d(uint32_t dst, const CUtensorMap* m, int c0, int c1, int c2, uint32_t bar) {
    asm volatile("cp.async.bulk.tensor.3d.shared::cluster.global.mbarrier::complete_tx::bytes [%0], [%1, {%3, %4, %5}], [%2];"
                 :: "r"(dst), "l"(m), "r"(bar), "r"(c0), "r"(c1), "r"(c2) : "memory");
}
__device__ __forceinline__ void tma4d(uint32_t dst, const CUtensorMap* m, int c0, int c1, int c2, int c3, uint32_t bar) {
    asm volatile("cp.async.bulk.tensor.4d.shared::cluster.global.mbarrier::complete_tx::bytes [%0], [%1, {%3, %4, %5, %6}], [%2];"
                 :: "r"(dst), "l"(m), "r"(bar), "r"(c0), "r"(c1), "r"(c2), "r"(c3) : "memory");
}
__device__ __forceinline__ void bulk_g2s(uint32_t dst, const void* src, uint32_t bytes, uint32_t bar) {
    asm volatile("cp.async.bulk.shared::cluster.global.mbarrier::complete_tx::bytes [%0], [%1], %2, [%3];"
                 :: "r"(dst), "l"(src), "r"(bytes), "r"(bar) : "memory");
}
__device__ __forceinline__ uint32_t mapa(uint32_t a, uint32_t rank) { uint32_t r; asm("mapa.shared::cluster.u32 %0, %1, %2;" : "=r"(r) : "r"(a), "r"(rank)); return r; }
__device__ __forceinline__ void prefetch_map(const CUtensorMap* m) { asm volatile("prefetch.tensormap [%0];" :: "l"(m) : "memory"); }
__device__ __forceinline__ void bar_sync(int id, int n) { asm volatile("bar.sync %0, %1;" :: "r"(id), "r"(n) : "memory"); }
__device__ __forceinline__ void bar_arrive(int id, int n) { asm volatile("bar.arrive %0, %1;" :: "r"(id), "r"(n) : "memory"); }
__device__ __forceinline__ uint32_t ldg16_if(bool c, const void* p) { uint32_t v; asm volatile("{ .reg .pred p; setp.ne.u32 p, %2, 0; @p ld.global.nc.u16 %0, [%1]; }" : "=r"(v) : "l"(p), "r"((uint32_t)c)); return v; }
__device__ __forceinline__ uint32_t ldg32_if(bool c, const void* p) { uint32_t v; asm volatile("{ .reg .pred p; setp.ne.u32 p, %2, 0; @p ld.global.nc.u32 %0, [%1]; }" : "=r"(v) : "l"(p), "r"((uint32_t)c)); return v; }
__device__ __forceinline__ uint32_t ld_rlx32(const void* p) { uint32_t v; asm volatile("ld.relaxed.gpu.global.u32 %0, [%1];" : "=r"(v) : "l"(p) : "memory"); return v; }
__device__ __forceinline__ uint4 ld_rlx128(const void* p) {
    uint4 v; asm volatile("ld.relaxed.gpu.global.v4.u32 {%0,%1,%2,%3}, [%4];" : "=r"(v.x), "=r"(v.y), "=r"(v.z), "=r"(v.w) : "l"(p) : "memory"); return v;
}
__device__ __forceinline__ void st_rlx32(void* p, uint32_t v) { asm volatile("st.relaxed.gpu.global.u32 [%0], %1;" :: "l"(p), "r"(v) : "memory"); }
__device__ __forceinline__ void stg128(void* p, uint32_t x, uint32_t y, uint32_t z, uint32_t w) {
    asm volatile("st.global.v4.u32 [%0], {%1,%2,%3,%4};" :: "l"(p), "r"(x), "r"(y), "r"(z), "r"(w) : "memory");
}
__device__ __forceinline__ void next_epoch(const Params& p, unsigned e) { if ((threadIdx.x & 31) == 0) p.s->epoch[blockIdx.x * 16 + (threadIdx.x >> 5)] = e + 1; }
__device__ __forceinline__ void sts128z_if(bool c, uint32_t a) { asm volatile("{ .reg .pred p; setp.ne.u32 p, %1, 0; @p st.shared.v4.u32 [%0], {%2,%2,%2,%2}; }" :: "r"(a), "r"((uint32_t)c), "r"(0) : "memory"); }
__device__ __forceinline__ void stg128z_if(bool c, void* a) { asm volatile("{ .reg .pred p; setp.ne.u32 p, %1, 0; @p st.global.v4.u32 [%0], {%2,%2,%2,%2}; }" :: "l"(a), "r"((uint32_t)c), "r"(0) : "memory"); }
__device__ __forceinline__ unsigned clock32() { unsigned c; asm volatile("mov.u32 %0, %clock;" : "=r"(c) :: "memory"); return c; }
__device__ __forceinline__ void until(unsigned t0, int c) { while ((int)(clock32() - t0) < c) { } }
__device__ __forceinline__ float sigmoidf_(float x) { return __fdividef(1.0f, 1.0f + __expf(-x)); }
__device__ __forceinline__ uint32_t key_tag(unsigned epoch) { return ((epoch & 15u) | 16u) << 11; }
__device__ __forceinline__ int key_row(uint32_t key) { return 2047 - (int)(key & 2047u); }
__device__ __forceinline__ uint32_t wait_sel(const Params& p, int s32, int r8, uint32_t tag) {
    uint32_t k;
    for (int it = 0;; it++) {
        k = ld_rlx32(&p.s->sel[s32 * 64 + r8]);
        if (__all_sync(0xffffffffu, (k & 0xf800u) == tag)) break;
        if (it > (1 << 20)) __trap();
    }
    return k;
}

struct cplx { float re, im; };
__device__ __forceinline__ cplx csq(cplx a) { cplx r; r.re = a.re * a.re - a.im * a.im; r.im = (a.re * a.im) * 2.f; return r; }
__device__ __forceinline__ cplx cexpk(float ar, float ai, float k) {
    float mag, s, c;
    asm("ex2.approx.ftz.f32 %0, %1;" : "=f"(mag) : "f"(ar * (k * 1.4426950408889634f)));
    const float r = ai * k;
    asm("sin.approx.ftz.f32 %0, %1;" : "=f"(s) : "f"(r));
    asm("cos.approx.ftz.f32 %0, %1;" : "=f"(c) : "f"(r));
    cplx o; o.re = mag * c; o.im = mag * s; return o;
}
struct h2c { uint32_t re, im; };
__device__ __forceinline__ h2c cmul_cd(h2c v, __half2 c, __half2 d) {
    const __half2 r = *(const __half2*)&v.re, i = *(const __half2*)&v.im;
    const __half2 x = __hfma2(__hneg2(i), d, __hmul2(r, c)), y = __hfma2(i, c, __hmul2(r, d));
    h2c o; o.re = *(const uint32_t*)&x; o.im = *(const uint32_t*)&y; return o;
}
__device__ __forceinline__ h2c cmul_s(h2c v, uint32_t s) { const __half2 h = *(const __half2*)&s; return cmul_cd(v, __low2half2(h), __high2half2(h)); }
__device__ __forceinline__ h2c cmul_sc(h2c v, uint32_t s) {
    const __half2 h = *(const __half2*)&s, c = __low2half2(h), d = __high2half2(h), r = *(const __half2*)&v.re, i = *(const __half2*)&v.im;
    const __half2 x = __hfma2(i, d, __hmul2(r, c)), y = __hfma2(__hneg2(r), d, __hmul2(i, c));
    h2c o; o.re = *(const uint32_t*)&x; o.im = *(const uint32_t*)&y; return o;
}
__device__ __forceinline__ h2c cmul_vc(h2c v, uint32_t s) {
    const __half2 h = *(const __half2*)&s, c = __low2half2(h), d = __high2half2(h), r = *(const __half2*)&v.re, i = *(const __half2*)&v.im;
    const __half2 x = __hfma2(i, d, __hmul2(r, c)), y = __hfma2(__hneg2(i), c, __hmul2(r, d));
    h2c o; o.re = *(const uint32_t*)&x; o.im = *(const uint32_t*)&y; return o;
}

constexpr int UT_HALF = 2240, UT_STRIDE = 4448;
constexpr int KT_T = 542, KT_C = 552, KT_D = 645, KT_BYTES = 720 * 4;
constexpr int VC_OFF = 80, VE_BASE = 1616;
constexpr int V_STRIDE = (1616 + 1024) * 4 + 80;
constexpr int KG_STAGE = 5248;
constexpr int Y_CS = 2080, Y_RS = 8 * Y_CS + 64;

constexpr int SC_RT = 0;
constexpr int SC_UT = 33408;
constexpr int SC_ST = SC_UT + 8 * UT_STRIDE;
constexpr int SC_KT = SC_ST + 8 * UT_STRIDE;
constexpr int SC_GT = SC_KT + 8 * KT_BYTES;
constexpr int SC_V = SC_GT + UT_STRIDE;
constexpr int SC_KG = SC_V + 4 * V_STRIDE;
constexpr int SC_MISC = SC_V + 8 * V_STRIDE;
static_assert(V_STRIDE % 128 == 16 && 8 * KG_STAGE <= 4 * V_STRIDE && 2 * Y_RS <= SC_UT && SC_UT % 128 == 0 && SC_ST % 128 == 0, "layout");
static_assert(SC_MISC % 16 == 0 && SC_MISC + 512 <= 232192, "layout");

__device__ __forceinline__ void window_task(uint32_t src, uint32_t d0, uint32_t d1, bool withE) {
    float S[35];
    {
        uint32_t w[20];
#pragma unroll
        for (int i = 0; i < 5; i++) {
            const uint4 v = lds128(src + ((i & 1) ? 0 : UT_HALF) + ((i + 1) >> 1) * 16);
            w[4 * i] = v.x; w[4 * i + 1] = v.y; w[4 * i + 2] = v.z; w[4 * i + 3] = v.w;
        }
        float s = 0.f; S[2] = 0.f;
#pragma unroll
        for (int i = 3; i < 26; i++) { s += (i & 1) ? bf_hi(w[i >> 1]) : bf_lo(w[i >> 1]); S[i] = s; }
#pragma unroll
        for (int i = 0; i < 8; i += 2)
            sts128((i & 4 ? d1 : d0) + (VC_OFF - 16) * 4 + 8 * (i & 2), pack_bf16(S[10 + i] - S[5 + i], S[5 + i] - S[2 + i]), pack_bf16(S[18 + i] - S[13 + i], S[13 + i] - S[10 + i]),
                   pack_bf16(S[11 + i] - S[6 + i], S[6 + i] - S[3 + i]), pack_bf16(S[19 + i] - S[14 + i], S[14 + i] - S[11 + i]));
        if (withE) {
#pragma unroll
            for (int i = 26; i < 35; i++) { s += (i & 1) ? bf_hi(w[i >> 1]) : bf_lo(w[i >> 1]); S[i] = s; }
#pragma unroll
            for (int i = 0; i < 8; i += 2)
                sts128((i & 4 ? d1 : d0) + VE_BASE * 4 + 8 * (i & 2), pack_bf16(S[19 + i] - S[12 + i], S[12 + i] - S[3 + i]), pack_bf16(S[27 + i] - S[20 + i], S[20 + i] - S[11 + i]),
                       pack_bf16(S[20 + i] - S[13 + i], S[13 + i] - S[4 + i]), pack_bf16(S[28 + i] - S[21 + i], S[21 + i] - S[12 + i]));
        }
    }
}

template <class F>
__device__ __forceinline__ void kgen(const uint32_t (&q)[8], uint32_t sb, int half, uint32_t stage, uint32_t pstage, int barid, int lane, uint32_t zero, uint32_t (&w)[12], F shadow) {
    const int t = lane & 3, mi = lane >> 3, r8 = lane & 7;
    {
        const uint32_t pAr = q[0], pAi = q[1], pBr = q[2], pBi = q[3], pCr = q[4], pCi = q[5], pDt = q[6], pD = q[7];
        const uint32_t wb = fresh(stage + lane * 16), za = fresh(stage + 5120 + ((lane >> 1) & 3) * 16 + mi * 4 + (lane & 1) * 2), zr = fresh(stage + 5120 + t * 16);
        const uint32_t oA = fresh(stage + (mi & 1) * 1024 + (mi >> 1) * 512 + r8 * 16), oB = fresh(stage + 2048 + mi * 512 + r8 * 16), oC = fresh(stage + 4096 + (mi & 1) * 512 + (mi >> 1) * 128 + r8 * 16);
        float acc[6][4];
#pragma unroll
        for (int a = 0; a < 6; a++) { acc[a][0] = acc[a][1] = acc[a][2] = acc[a][3] = 0.f; asm volatile("" : "+f"(acc[a][0]), "+f"(acc[a][1]), "+f"(acc[a][2]), "+f"(acc[a][3])); }
        shadow();
        sts32(zr, clock32());
        const float dt = rbf(__expf(bf_lo(pDt)));
        float ar = dt * bf_lo(pAr), ai = dt * bf_lo(pAi), ar1 = dt * bf_hi(pAr), ai1 = dt * bf_hi(pAi);
        float wr, wi, wr1, wi1;
        { const float br = dt * bf_lo(pBr), bi = dt * bf_lo(pBi), cr = bf_lo(pCr), ci = bf_lo(pCi); wr = cr * br - ci * bi; wi = cr * bi + ci * br; }
        { const float br = dt * bf_hi(pBr), bi = dt * bf_hi(pBi), cr = bf_hi(pCr), ci = bf_hi(pCi); wr1 = cr * br - ci * bi; wi1 = cr * bi + ci * br; }
        const uint32_t ex = max(__reduce_max_sync(0xffffffffu, __float_as_uint(fmaxf(fmaxf(fabsf(wr), fabsf(wi)), fmaxf(fabsf(wr1), fabsf(wi1))))) >> 23, 14u);
        const float scl = __uint_as_float((267u - ex) << 23);
        uint32_t W = pack_f16(wr * scl, wi * -scl);
        const uint32_t W1 = pack_f16(wr1 * scl, wi1 * -scl);
        if (threadIdx.x < 32) TSTAMP(20);

#pragma unroll 1
        for (int r = 0; r < 2; r++) {
            const cplx z1 = cexpk(ar, ai, 1.f), z64 = cexpk(ar, ai, 64.f);
            const cplx z2 = csq(z1), z4 = csq(z2), z8 = csq(z4), z16 = csq(z8), z32 = csq(z16);
            const cplx z128 = csq(z64), z256 = csq(z128), z512 = csq(z256);
            auto put = [&](int grp, h2c a, h2c b, h2c c, h2c d) { sts128(wb + grp * 1024, a.re, b.re, c.re, d.re); sts128(wb + grp * 1024 + 512, a.im, b.im, c.im, d.im); };
            {
                const uint32_t s4 = pack_f16(z4.re, z4.im), s256 = pack_f16(z256.re, z256.im), s512 = pack_f16(z512.re, z512.im);
                auto mix = [](h2c a, h2c b, uint32_t sel) { return h2c{__byte_perm(a.re, b.re, sel), __byte_perm(a.im, b.im, sel)}; };
                const h2c c10 = cmul_vc(h2c{pack_f16(z1.re, 1.f), pack_f16(z1.im, 0.f)}, W), c32 = cmul_sc(c10, pack_f16(z2.re, z2.im)), c54 = cmul_sc(c10, s4);
                put(2, c10, c32, c54, cmul_sc(c32, s4));
                const h2c d20 = cmul_sc(mix(c32, c10, 0x7632), s256), e04 = cmul_sc(mix(c10, c54, 0x7632), s512), f04 = cmul_sc(e04, s256);
                put(3, d20, cmul_sc(d20, s4), e04, f04);
                const h2c ef = mix(e04, f04, 0x5410), gh = cmul_sc(ef, s512), g8 = cmul_sc(gh, pack_f16(z8.re, z8.im));
                put(4, g8, cmul_sc(g8, s512), gh, ef);
            }
            {
                const uint32_t s32 = pack_f16(z32.re, z32.im), s64 = pack_f16(z64.re, z64.im), s128 = pack_f16(z128.re, z128.im);
                const h2c p0 = {pack_f16(1.f, z8.re), pack_f16(0.f, z8.im)}, p1 = cmul_s(p0, pack_f16(z16.re, z16.im)), p2 = cmul_s(p0, s32), p3 = cmul_s(p1, s32);
                put(0, p0, p1, p2, p3);
                put(1, cmul_s(p0, s64), cmul_s(p1, s64), cmul_s(p2, s64), cmul_s(p3, s64));
                sts16(za, s128); sts16(za + 64, s128 >> 16);
            }
            __syncwarp();
            {
                const uint32_t aA = fresh(oA), aB = fresh(oB), aC = fresh(oC), aZ = fresh(zr);
                const uint4 zc = lds128(aZ), zd = lds128(aZ + 64);
                const uint32_t zcs[4] = {zc.x, zc.y, zc.z, zc.w}, zds[4] = {zd.x, zd.y, zd.z, zd.w};
                uint32_t c[4];
#pragma unroll
                for (int k = 0; k < 4; k++) {
                    uint32_t a[4], b[4];
                    ldsm4t(a, aA + 128 * k); ldsm4t(b, aB + 128 * k);
                    if (!(k & 1)) ldsm4t(c, aC + 128 * k);
                    const h2c x = cmul_cd(h2c{a[0], a[2]}, *(const __half2*)&zcs[k], *(const __half2*)&zds[k]), y = cmul_cd(h2c{a[1], a[3]}, *(const __half2*)&zcs[k], *(const __half2*)&zds[k]);
                    mma_h(acc[0], a[0], a[1], a[2], a[3], b[0], b[1]);
                    mma_h(acc[1], a[0], a[1], a[2], a[3], b[2], b[3]);
                    mma_h(acc[2], a[0], a[1], a[2], a[3], c[2 * (k & 1)], c[2 * (k & 1) + 1]);
                    mma_h(acc[3], x.re, y.re, x.im, y.im, b[0], b[1]);
                    mma_h(acc[4], x.re, y.re, x.im, y.im, b[2], b[3]);
                    mma_h(acc[5], x.re, y.re, x.im, y.im, c[2 * (k & 1)], c[2 * (k & 1) + 1]);
                }
                asm volatile("" :: "f"(acc[0][0]), "f"(acc[1][0]), "f"(acc[2][0]), "f"(acc[3][0]), "f"(acc[4][0]), "f"(acc[5][0]) : "memory");
            }
            __syncwarp();
            ar = ar1; ai = ai1; W = W1;
        }
        if (threadIdx.x < 32) TSTAMP(21);
        const float i0 = __uint_as_float((ex + 243u) << 23);
        if (half) {
#pragma unroll
            for (int a = 0; a < 6; a++) sts128(wb + a * 512, __float_as_uint(acc[a][0]), __float_as_uint(acc[a][1]), __float_as_uint(acc[a][2]), __float_as_uint(acc[a][3]));
            sts32(stage + 3072, __float_as_uint(i0));
            bar_arrive(barid, 64);
        } else {
#pragma unroll
            for (int a = 0; a < 6; a++) { acc[a][0] *= i0; acc[a][1] *= i0; acc[a][2] *= i0; acc[a][3] *= i0; }
            if (lane == 0) acc[0][1] -= bf_lo(pD);
            sts32(zr, clock32());
            bar_sync(barid, 64);
            const uint32_t src = fresh(pstage);
            const float i1 = __uint_as_float(lds32(src + 3072));
#pragma unroll
            for (int a = 0; a < 6; a++) {
                const uint4 y = lds128(src + lane * 16 + a * 512);
                w[2 * a] = pack_bf16(fmaf(__uint_as_float(y.x), i1, acc[a][0]), fmaf(__uint_as_float(y.y), i1, acc[a][1]));
                w[2 * a + 1] = pack_bf16(fmaf(__uint_as_float(y.z), i1, acc[a][2]), fmaf(__uint_as_float(y.w), i1, acc[a][3]));
            }
        }
    }
}

__device__ __forceinline__ int swap01(int i) { return (i & ~3) | ((i & 1) << 1) | ((i >> 1) & 1); }
enum { BC_AUX = 0, BC_S = 5, BC_KG = 15 };

__device__ __forceinline__ void conv_aux(const Params& p, const CUtensorMap* mU, uint32_t sb, int aw, int lane, int bid, unsigned epoch) {
    const unsigned t0 = clock32();
    const int g = lane >> 2, t = lane & 3, mi = lane >> 3, r8 = lane & 7;
    const int rank = bid & 1, slab = bid >> 1;
    const uint32_t bar_y = sb + SC_MISC, bar_u = bar_y + 32, bar_v = bar_y + 40, bar_box = bar_y + 64 + 8 * aw, s_bm = bar_y + 128;
    if (lane == 0) {
        mbar_init(bar_box, 1); mbar_fence();
        mbar_expect(bar_box, 4096);
        if (UDELAY) until(t0, UDELAY);
        tma4d(sb + SC_RT + 4096 * aw, mU, 16 * slab, 0, 0, 16 * rank + 2 * aw, bar_box);
        mbar_init(bar_y + 8 * aw, aw < 4 ? 9 : aw == 5 ? 8 : 1); mbar_fence();
        if (aw < 5) mbar_expect(bar_y + 8 * aw, aw == 4 ? 16384 : 4096);
    }
    __syncwarp();
    asm volatile("barrier.cluster.arrive.relaxed.aligned;" ::: "memory");
    asm volatile("setmaxnreg.dec.sync.aligned.u32 88;");
    const uint32_t ut = sb + SC_UT + aw * UT_STRIDE;
    sts128(ut + (mi >> 1) * (SC_ST - SC_UT) + (mi & 1) * UT_HALF + r8 * 16, 0, 0, 0, 0);
    if (lane < 16) sts128(s_bm + lane * 16, 0, 0, 0, 0);
    {
        const uint32_t dst = sb + SC_UT + swap01(g) * UT_STRIDE + (8 + 64 * rank + 8 * aw + t) * 16;
        const uint32_t rdst = mapa(dst, rank ^ 1), rbar = mapa(bar_u, rank ^ 1);
        asm volatile("barrier.cluster.wait.acquire.aligned;" ::: "memory");
        mbar_wait(bar_box);
        if (aw == 0) TSTAMP(1);
        const uint32_t src = fresh(sb + SC_RT) + aw * 4096 + (8 * mi + 4 * (r8 & 1) + (r8 >> 1)) * 32 + ((rank ^ (r8 & 1)) << 4);
        uint32_t x[8][4];
#pragma unroll
        for (int i = 0; i < 4; i++) { ldsm4t(x[i], src + 1024 * i); ldsm4t(x[4 + i], (src ^ 16) + 1024 * i); }
        asm volatile("" :: "r"(x[0][0]), "r"(x[1][0]), "r"(x[2][0]), "r"(x[3][0]) : "memory");
#pragma unroll
        for (int i = 0; i < 4; i++) st_async128(rdst + (i & 1) * UT_HALF + 32 * (i & 2), x[4 + i][0], x[4 + i][1], x[4 + i][2], x[4 + i][3], rbar);
#pragma unroll
        for (int i = 0; i < 4; i++) sts128(dst + (i & 1) * UT_HALF + 32 * (i & 2), x[i][0], x[i][1], x[i][2], x[i][3]);
    }
    bar_sync(BC_AUX, 256);
    mbar_wait_cluster(bar_u);
    if (aw == 0) TSTAMP(2);
    {
        const uint32_t a = fresh(ut) + (mi & 1) * UT_HALF + (64 * (mi >> 1) + r8) * 16;
        uint4 v = lds128(a);
#pragma unroll
        for (int i = 1; i <= 8; i++) {
            const uint4 w = lds128(a + 128 * i);
            sts128(a + 128 * i + (SC_ST - SC_UT), badd2(v.x, w.x), badd2(v.y, w.y), badd2(v.z, w.z), badd2(v.w, w.w));
            v = w;
        }
    }
    bar_arrive(BC_S + aw, 64);
    if (aw == 0) TSTAMP(3);
    {
        uint32_t ws = sb + SC_UT + t * UT_STRIDE + (g + 6) * 16, wd = sb + SC_V + t * V_STRIDE + 64 * g, sw = 16 * (g & 2);
#pragma unroll 1
        for (int k = aw; k < 25; k += 8) {
            if (k - aw == 8) {
                bar_sync(BC_KG, 384);
                if (lane < 16) sts128(sb + SC_V + aw * V_STRIDE + lane * 16, 0, 0, 0, 0);
            }
            if (k == 24) { ws -= (g & 1) * 4 * UT_STRIDE + 16 * g; wd -= (g & 1) * 4 * V_STRIDE + 64 * g; sw = 0; }
            const int h = k >= 12, a = k - 12 * h;
            const uint32_t d = wd + h * 4 * V_STRIDE + 512 * a;
            window_task(fresh(ws) + h * 4 * UT_STRIDE + 128 * a, d + sw, d + (sw ^ 32), a < 8);
        }
    }
    if (aw == 0) TSTAMP(9);
    {
        {
            const uint32_t par = (epoch & 1) ? 0x80008000u : 0u;
            uint4 v;
            for (int it = 0;; it++) {
                v = ld_rlx128(p.s->gate + 256 * aw + 8 * lane);
                v.x ^= par; v.y ^= par; v.z ^= par; v.w ^= par;
                if (__all_sync(0xffffffffu, (v.x & v.y & v.z & v.w & 0x80008000u) == 0x80008000u)) break;
                if (it > (1 << 20)) __trap();
            }
            sts128(sb + SC_GT + (lane & 1) * UT_HALF + (8 + 16 * aw + (lane >> 1)) * 16, v.x, v.y, v.z, v.w);
        }
        __syncwarp();
        if (lane == 0) { mbar_arrive(bar_v); prefetch_map(mU + 6); }
        next_epoch(p, epoch);
        if (aw == 0) TSTAMP(4);
        if (aw == 7) {
            const int row = key_row(wait_sel(p, slab >> 1, r8, key_tag(epoch)));
            if (lane < 8) asm volatile("red.shared.or.b32 [%0], %1;" :: "r"(s_bm + (row >> 5) * 4), "r"(1u << (row & 31)) : "memory");
            TSTAMP(10);
        }
        bar_sync(BC_AUX, 256);
        const uint32_t src = sb + SC_RT + ((r8 >> 1) & 1) * Y_RS + (2 * mi + (r8 & 1)) * Y_CS + (2 * aw + (r8 >> 2)) * 16;
        const int L = 2 * aw + (t >> 1);
        const int row0 = 256 * rank + 128 * (g >> 2) + 32 * (L & 3) + 16 * (g & 1) + 8 * ((g >> 1) & 1) + (L >> 2);
        __nv_bfloat16* outp = p.out + (size_t)row0 * DM + 16 * slab + 8 * (t & 1);
        const uint32_t stg = sb + SC_ST + 4096 * aw, so = (g >> 1) * 256 + (t >> 1) * 64 + (g & 1) * 32 + (t & 1) * 16;
#pragma unroll 1
        for (int s = 0; s < 4; s++) {
            const uint32_t bm = lds32(fresh(s_bm) + (16 * s + (row0 >> 5)) * 4) >> (row0 & 31);
            const bool routed = __any_sync(0xffffffffu, bm & 0x11u);
            if (aw == s) mbar_wait_cluster(bar_y + 8 * s);
            bar_sync(BC_AUX, 256);
            const uint32_t sf = fresh(src) + 512 * s;
            uint32_t y[2][4];
            ldsm4t(y[0], sf); ldsm4t(y[1], sf + 256);
            if (routed) {
#pragma unroll
                for (int k = 0; k < 2; k++)
                    asm volatile("{ .reg .pred p; setp.ne.u32 p, %5, 0; @!p st.global.v4.u32 [%0], {%1,%2,%3,%4}; @p red.relaxed.gpu.global.add.noftz.v4.bf16x2 [%0], {%1,%2,%3,%4}; }"
                                 :: "l"(outp + (size_t)(512 * s + 4 * k) * DM), "r"(y[k][0]), "r"(y[k][1]), "r"(y[k][2]), "r"(y[k][3]), "r"(bm & (1u << (4 * k))) : "memory");
            } else {
                sts128(stg + so + 1024 * s, y[0][0], y[0][1], y[0][2], y[0][3]); sts128(stg + so + 1024 * s + 128, y[1][0], y[1][1], y[1][2], y[1][3]);
                asm volatile("fence.proxy.async.shared::cta;" ::: "memory");
                __syncwarp();
                if (lane == 0) asm volatile("cp.async.bulk.tensor.5d.global.shared::cta.bulk_group [%0, {%2, %3, %3, %3, %4}], [%1];"
                                            :: "l"(mU + 6), "r"(stg + 1024 * s), "r"(16 * slab), "r"(0), "r"(512 * s + 256 * rank + 64 * (aw & 1) + (aw >> 1)) : "memory");
            }
            if (aw == 0) TSTAMP(16 + s);
        }
        if (lane == 0) { asm volatile("cp.async.bulk.commit_group;" ::: "memory"); asm volatile("cp.async.bulk.wait_group.read 0;" ::: "memory"); }
        if (aw == 0) TFLUSH();
    }
}

__device__ __forceinline__ void conv_main(const Params& p, uint32_t sb, int warp, int lane, int bid, unsigned epoch, uint32_t (&w)[12]) {
    asm volatile("setmaxnreg.inc.sync.aligned.u32 168;");
    const int g = lane >> 2, t = lane & 3, mi = lane >> 3, r8 = lane & 7;
    const int rank = bid & 1;
    const uint32_t bar_y = sb + SC_MISC, bar_v = bar_y + 40;
    next_epoch(p, epoch);
    if (warp < 4) {
        asm volatile("" :: "r"(w[0]), "r"(w[2]), "r"(w[4]), "r"(w[6]), "r"(w[8]), "r"(w[10]) : "memory");
        bar_arrive(BC_KG, 384);
    } else {
        const uint4* src = p.s->kp + (4 * bid + warp - 4) * 128 + lane;
        for (int it = 0;; it++) {
            uint32_t bad = 0;
#pragma unroll
            for (int i = 0; i < 4; i++) { const uint4 v = ld_rlx128(src + 32 * i); w[3 * i] = v.x; w[3 * i + 1] = v.y; w[3 * i + 2] = v.z; bad |= v.w ^ ~epoch; }
            const bool ok = __all_sync(0xffffffffu, bad == 0);
            if (ok) break;
            if (it > (1 << 20)) __trap();
        }
    }
    if ((warp & 3) == 0) TSTAMP(5 + (warp >> 2));
    {
        const uint32_t kt = sb + SC_KT + warp * KT_BYTES;
        uint32_t e[4], x[4], re[4], rx[4];
#pragma unroll
        for (int i = 0; i < 4; i++) {
            e[i] = w[6 * (i >> 1) + (i & 1)]; x[i] = w[6 * (i >> 1) + 2 + (i & 1)];
            re[i] = __shfl_sync(0xffffffffu, e[i], lane + 31);
            rx[i] = __shfl_sync(0xffffffffu, x[i], lane + (i == 0 && lane == 29 ? 5 : 1 + 2 * t));
        }
        asm volatile("stmatrix.sync.aligned.m8n8.x4.trans.shared.b16 [%0], {%1,%2,%3,%4};"
                     :: "r"(kt + (r8 < 4 ? (KT_D + 7) * 4 + 64 * r8 + 16 * mi : 716 * 4)), "r"(w[4]), "r"(w[5]), "r"(w[10]), "r"(w[11]) : "memory");
        if (lane == 2) {
            sts32(kt + (KT_C + 78) * 4, w[4] & 0xffffu);
            sts128(kt + (KT_T + 2) * 4, 0, w[4] & 0xffffu, __byte_perm(w[4], 0, 0x1010), w[4] << 16);
        }
        if (lane == 29) x[3] = bsub2(x[3], rx[0] & 0xffffu);
#pragma unroll
        for (int i = 0; i < 4; i++) {
            sts64(kt + (16 + 64 * i) * 4 + 8 * lane, __byte_perm(e[i], lane ? re[i] : i ? re[i - 1] : 0, 0x5432), e[i]);
            const uint32_t aa = __byte_perm(x[i], 0, 0x3232);
            if (t < 2) sts128(kt + (272 + 64 * i + 8 * g + 4 * t) * 4, i == 0 && lane == 0 ? __byte_perm(x[0], re[3], 0x5432) : aa, aa, x[i],
                              __byte_perm(lane != 29 ? rx[i] : i < 3 ? rx[(i + 1) & 3] : 0, x[i], 0x5432));
            else sts32(kt + (KT_C - 50 + 8 * i + 32 * t + g) * 4, x[i]);
        }
    }
    asm volatile("barrier.cluster.wait.acquire.aligned;" ::: "memory");
    bar_sync(BC_S + swap01(warp), 64);
    if ((warp & 3) == 0) TSTAMP(7 + (warp >> 2));
    {
        const uint32_t ut = fresh(sb + SC_UT) + swap01(warp) * UT_STRIDE, kt = fresh(sb + SC_KT) + warp * KT_BYTES;
        uint32_t u1 = ut + (mi & 1) * UT_HALF + (8 + r8) * 16 + (mi >> 1) * 128;
        auto dup = [&](uint32_t v) { return v ^ p.zero; };
        uint32_t kp = kt + (16 + g - 2 * t) * 4;
        float acc[16][4];
        {
            const uint32_t c0 = lds32(kp + 2048), c1 = lds32(kp + 2080), c2 = lds32(kp + 2016), c3 = dup(c0);
            const uint32_t e0 = lds32(kp + (KT_T - 16) * 4), e1 = lds32(kp + (KT_T - 8) * 4), e2 = lds32(kp + (KT_T - 24) * 4), e3 = dup(e0);
            const uint32_t f0 = dup(e1), f1 = lds32(kp + KT_T * 4);
            const uint32_t uo = ut + UT_HALF + (7 + lane) * 16;
#pragma unroll
            for (int i = 0; i < 16; i++) { acc[i][0] = acc[i][1] = acc[i][2] = acc[i][3] = 0.f; }
#pragma unroll
            for (int mu = 0; mu < 8; mu += 4) {
                uint32_t b[4];
                ldsm4(b, uo + 128 * mu);
#pragma unroll
                for (int k = 0; k < 4; k++) mma_bf8(acc[mu + 8 + k], f0, f1, b[k]);
            }
#pragma unroll
            for (int mu = 0; mu < 12; mu += 2) {
                uint32_t b[4];
                ldsm4(b, u1 + 128 * mu);
                mma_bf(acc[mu + 4], c0, c1, c2, c3, b[0], b[1]);
                mma_bf(acc[mu + 5], c0, c1, c2, c3, b[2], b[3]);
                if (mu < 8) { mma_bf(acc[mu + 8], e0, e1, e2, e3, b[0], b[1]); mma_bf(acc[mu + 9], e0, e1, e2, e3, b[2], b[3]); }
            }
        }
        {
            float M[8][4];
#pragma unroll
            for (int i = 0; i < 8; i++) { M[i][0] = M[i][1] = M[i][2] = M[i][3] = 0.f; }
            uint32_t s[8][4], a3[4];
            const uint32_t kb = kp, ub = dup(u1), uc = u1 + (mi >> 1) * 128;
            auto frag = [&](uint32_t (&a)[4], uint32_t x) { a[0] = lds32(x); a[1] = lds32(x + 32); a[2] = lds32(x - 32); a[3] = dup(a[0]); };
            frag(a3, kp + 1536);
#pragma unroll
            for (int i = 0; i < 8; i++) ldsm4(s[i], u1 + (SC_ST - SC_UT) + 256 * i);
            __syncwarp();
#pragma unroll 1
            for (uint32_t ko = 0, uo = 0; ko != 512;) {
                uint32_t a2[4], a1[4], a0[4], b[4][4];
                ko = fresh(ko); uo = fresh(uo);
                kp = kb + ko; u1 = ub + uo;
                const uint32_t up = uc + uo;
                ko += 64; uo -= 16;
                frag(a2, kp + 1024);
#pragma unroll
                for (int i = 0; i < 4; i++) ldsm4(b[i], up + 512 * i);
                frag(a1, kp + 512); frag(a0, kp);
                kp += 64; u1 -= 16;
#pragma unroll
                for (int i = 0; i < 7; i++) mma_bf(acc[2 * i + 2], a3[0], a3[1], a3[2], a3[3], s[i][0], s[i][1]);
#pragma unroll
                for (int e = 0; e < 4; e++) a3[e] = bsub2(a2[e], a3[e]);
#pragma unroll
                for (int i = 0; i < 7; i++) mma_bf(acc[2 * i + 3], a2[0], a2[1], a2[2], a2[3], s[i][2], s[i][3]);
#pragma unroll
                for (int i = 0; i < 7; i++) mma_bf(M[i + 1], a3[0], a3[1], a3[2], a3[3], b[i >> 1][2 * (i & 1)], b[i >> 1][2 * (i & 1) + 1]);
                frag(a3, kp + 1536);
#pragma unroll
                for (int i = 0; i < 8; i++) mma_bf(acc[2 * i], a1[0], a1[1], a1[2], a1[3], s[i][0], s[i][1]);
#pragma unroll
                for (int e = 0; e < 4; e++) a1[e] = bsub2(a0[e], a1[e]);
#pragma unroll
                for (int i = 0; i < 8; i++) { mma_bf(acc[2 * i + 1], a0[0], a0[1], a0[2], a0[3], s[i][2], s[i][3]); ldsm4(s[i], u1 + (SC_ST - SC_UT) + 256 * i); }
#pragma unroll
                for (int i = 0; i < 8; i++) mma_bf(M[i], a1[0], a1[1], a1[2], a1[3], b[i >> 1][2 * (i & 1)], b[i >> 1][2 * (i & 1) + 1]);
            }
            u1 = ub;
#pragma unroll
            for (int i = 0; i < 8; i++)
#pragma unroll
                for (int c = 0; c < 4; c++) { acc[2 * i][c] += M[i][c]; acc[2 * i + 1][c] -= M[i][c]; }
        }
        if ((warp & 3) == 0) TSTAMP(11 + (warp >> 2));
        mbar_wait(bar_v);
        const uint32_t vt = fresh(sb + SC_V) + swap01(warp) * V_STRIDE;
        const uint32_t g1 = fresh(u1) - ut + sb + SC_GT;
        const uint32_t ydst = sb + SC_RT + rank * Y_RS + warp * Y_CS + lane * 16;
        const uint32_t ydr = mapa(ydst, rank ^ 1), ybr = mapa(bar_y, rank ^ 1);
        auto stairs = [&](auto R) {
        uint32_t ug[2][2][4];
        auto ld_ug = [&](int i) { ldsm4t(ug[i & 1][0], u1 + 256 * i); ldsm4t(ug[i & 1][1], g1 + 256 * i); };
        auto ship = [&](int i) {
            const uint32_t (&u)[4] = ug[i & 1][0], (&gg)[4] = ug[i & 1][1];
            const uint32_t y0 = gmix(gg[0], acc[2 * i][0], acc[2 * i][1], u[0]), y1 = gmix(gg[1], acc[2 * i][2], acc[2 * i][3], u[1]);
            const uint32_t y2 = gmix(gg[2], acc[2 * i + 1][0], acc[2 * i + 1][1], u[2]), y3 = gmix(gg[3], acc[2 * i + 1][2], acc[2 * i + 1][3], u[3]);
            if ((i & 1) != R.value) st_async128(ydr + 512 * (i >> 1), y0, y1, y2, y3, ybr + 8 * (i >> 1));
            else asm volatile("{ .reg .pred q; setp.eq.u32 q, %6, 0; st.shared.v4.u32 [%0], {%2,%3,%4,%5}; bar.warp.sync 0xffffffff; @q mbarrier.arrive.shared::cta.b64 _, [%1]; }"
                              :: "r"(ydst + 512 * (i >> 1)), "r"(bar_y + 8 * (i >> 1)), "r"(y0), "r"(y1), "r"(y2), "r"(y3), "r"(lane) : "memory");
        };
        const uint32_t VD = vt + (VC_OFF - 400 - 16 * t) * 4 + (8 * g ^ 16 * (-t & 2)), VD2 = vt + (VC_OFF - 415 - 16 * t) * 4 + (8 * g ^ 16 * (~t & 2));
        uint2 bd[10];
        uint32_t x[2][4][4];
        auto ld4 = [&](uint32_t (&v)[4], int dl) { const uint2 w = lds64(VD + 256 * dl); v[0] = w.x; v[1] = w.y; v[2] = lds32(VD2 + 256 * dl); v[3] = dup(w.x); };
        auto mm4 = [&](const uint32_t (&v)[4], int dl) {
#pragma unroll
            for (int s = dl & 1; s < 10; s += 2) if ((dl + s) / 2 < 16) mma_bf(acc[(dl + s) / 2], v[0], v[1], v[2], v[3], bd[s].x, bd[s].y);
        };
        const uint32_t KE = kt + (KT_D + g + t) * 4, VE = vt + (VE_BASE - 912 - 16 * t) * 4 + (8 * g ^ 16 * (~t & 2));
        uint32_t b0[8], b1[8];
        auto ld8 = [&](uint32_t (&v)[4], int dl) { const uint2 w = lds64(VE + 512 * dl), z = lds64(VE + 512 * dl - 256); v[0] = w.x; v[1] = w.y; v[2] = z.x; v[3] = z.y; };
        auto mm8 = [&](const uint32_t (&v)[4], int dl, int lo, int hi) {
#pragma unroll
            for (int s = 0; s < 8; s++) if (dl + s >= lo && dl + s < hi) mma_bf(acc[dl + s], v[0], v[1], v[2], v[3], b0[s], b1[s]);
        };
        ld_ug(0); ld4(x[0][0], 6);
#pragma unroll
        for (int s = 0; s < 10; s++) bd[s] = lds64(kt + (KT_C + 2 * g + 2 * t + 8 * s) * 4);
        ld_ug(1);
        ship(0);
        mm4(x[0][0], 6);
        uint32_t e[4][4];
#pragma unroll
        for (int k = 1; k < 6; k++) {
#pragma unroll
            for (int j = 0; j < 4; j++) ld4(x[k & 1][j], 4 * k + 3 + j);
            ld_ug(k + 1);
            if (k == 3) {
#pragma unroll
                for (int s = 0; s < 8; s++) { b0[s] = lds32(KE + 32 * s); b1[s] = lds32(KE + 32 * s + 16); }
            }
            ship(k);
#pragma unroll
            for (int j = 0; j < 4; j++) {
                mm4(x[k & 1][j], 4 * k + 3 + j);
                if (k == 3) { uint32_t v[4], z[4]; ld8(e[j], 8 + j); ld8(v, 12 + j); ld4(z, 30 - j); mm8(v, 12 + j, 12, 16); mm8(e[j], 8 + j, 8, 12); mm4(z, 30 - j); }
                if (k == 5) { ld8(e[j], 8 + j + p.zero); mm8(e[j], 8 + j, 12, 16); }
            }
        }
        ld_ug(7);
        ship(7 - R.value); ship(6 + R.value);
        };
        if (rank) stairs(std::integral_constant<int, 1>()); else stairs(std::integral_constant<int, 0>());
        if ((warp & 3) == 0) TSTAMP(14 + (warp >> 2)); else TSTAMP(21 + warp);
    }
}

constexpr int SF_WD = 147456;
constexpr int SF_H = 81920;
constexpr int SF_RED = 131072;
constexpr int SF_SUM = 73728;
constexpr int SF_XS = 221184;
constexpr int SF_MISC = SF_XS + 8 * 1168;
constexpr int SF_KG = SF_MISC - 10 * KG_STAGE;
constexpr int SF_WR = SF_KG - 2304;
constexpr int FB_X = 64, FB_KDONE = 72, FB_KEYS = 80, FB_FREE = 88  , FB_W = 112, FB_D = FB_W + 72, FB_H = FB_D + 96, FS_PART = 512, FS_TOK = 896;
enum { BAR_F = 6, BAR_R = 7, BAR_GU = 8, BAR_RED = 9, BAR_R2 = 10, BAR_X = 11, BAR_G = 12 };
static_assert(NPRE <= 10 && SF_KG % 128 == 0 && SF_KG >= 7 * 24576 && SF_WR - 4 * 9216 >= 5 * 24576 && SF_WR - 6 * 9216 >= 5 * 16384, "layout");

__device__ __forceinline__ void ffn_front(const Params& p, const CUtensorMap* maps, uint32_t sb, int warp, int lane, int f, unsigned epoch) {
    const unsigned t0 = clock32();
    const int g = lane >> 2, t = lane & 3, mi = lane >> 3, r8 = lane & 7;
    const bool isx = f < NX;
    const int nrw = f < 8 ? 6 : 4, r0 = f < 8 ? 48 * f : 128 + 32 * f;
    const int rw = warp < 12 ? 13 - warp : warp ^ (warp < 14 ? 10 : 15);
    const uint32_t bar_row = sb + SF_MISC  , bar_x = bar_row + FB_X;
    const uint32_t s_part = bar_row + FS_PART  , s_tok = bar_row + FS_TOK  ;
    const uint32_t rows = sb + SF_WR - 9216 * (rw + 1);
    if (lane == 0) {
        mbar_init(bar_row + 8 * rw, 1); mbar_fence();
        if (rw < nrw) { mbar_expect(bar_row + 8 * rw, 9216); until(t0, RDELAY); bulk_g2s(rows, p.u + (size_t)(r0 + 8 * rw) * DM, 9216, bar_row + 8 * rw); }
        else if (rw >= 6) { mbar_expect(bar_row + 8 * rw, 1152); bulk_g2s(sb + SF_WR + (rw & 1) * 1152, (rw & 1) ? p.gatew : p.wr, 1152, bar_row + 8 * rw); }
        if (warp >= 10) {
#pragma unroll 1
            for (int i = warp - 10; i < 27; i += 6) mbar_init(bar_x + 8 * i, 1);
        }
        mbar_fence();
    }
    const int ks0 = isx ? 4 * f : 6 * f - 72, nt = isx ? 4 : 6;
    uint4* const kdst = p.s->keys + (lane >> 1) * 128 + 2 * f + (lane & 1);
    if (warp == 13) {
        stg128(kdst, 0, 0, 0, 0);
        sts32(s_part + 64 + lane * 4, 0);
        if (lane < 8 && isx && !(f & 1)) st_rlx32(&p.s->sel[32 * f + lane], 0);
    }
    __syncwarp();
    bar_sync(BAR_F, f < 12 ? 256 : 192);
    bar_arrive(0, NTHR);
    if (warp == 15) TSTAMP(1);

    if (warp == 12) {
        if (lane == 0) {
            const CUtensorMap* m = maps + (isx ? 1 : 3);
            prefetch_map(m); prefetch_map(m + 1);
            unsigned tb = t0 + WDELAY;
#pragma unroll 1
            for (int n = 0; n < 18; n++) {
                if (n == NPRE) { mbar_wait(bar_row + FB_KEYS); mbar_wait(bar_row + FB_KDONE); tb = clock32() + RESUME; }
                until(tb, 0); tb += WGAP;
                const uint32_t b = bar_row + FB_W + 8 * (n >> 1);
                if (!(n & 1)) mbar_expect(b, nt * 4096);
                tma3d(sb + n * nt * 2048, m + (n & 1), 0, 64 * (n >> 1), ks0 >> 1, b);
            }
            TSTAMP(12);
            if (isx) {
                prefetch_map(maps + 5);
#pragma unroll 1
                for (int n = 0; n < 12; n++) {
                    until(tb, 0); tb += DGAP;
                    if ((n & 3) == 2 && n > 2) mbar_wait(bar_row + FB_FREE + (n & 8));
                    mbar_expect(bar_row + FB_D + 8 * n, 12288);
                    tma2d(sb + (n < 6 ? SF_WD : -6 * 12288) + n * 12288, maps + 5, 32 * (f >> 1), 2304 * (f & 1) + 192 * n, bar_row + FB_D + 8 * n);
                }
                TSTAMP(13);
            }
        }
    } else if (warp == 13) {
        const uint32_t tag = key_tag(epoch), par = (epoch & 1) ? 0u : 0x8000u;
        next_epoch(p, epoch);
        bar_sync(BAR_R, 32 * (nrw + 1));
        TSTAMP(3);
        {
            const uint32_t sg = fresh(s_part) + 192 + lane * 4;
            const uint32_t gb = pack_bf16(sigmoidf_(rbf(__uint_as_float(lds32(sg)))), sigmoidf_(rbf(__uint_as_float(lds32(sg + 128))))) | par | (par << 16);
            asm volatile("st.relaxed.gpu.global.u16 [%0], %1;" :: "l"(p.s->gate + r0 + lane), "h"((unsigned short)gb) : "memory");
            if (nrw > 4 && lane < 16) asm volatile("st.relaxed.gpu.global.u16 [%0], %1;" :: "l"(p.s->gate + r0 + 32 + lane), "h"((unsigned short)(gb >> 16)) : "memory");
        }
        bar_sync(BAR_R2, 32 * (nrw + 1));
        {
            const uint4 v = lds128(fresh(s_tok) + (lane & 1) * 16);
            asm volatile("st.relaxed.gpu.global.v4.u32 [%0], {%1,%2,%3,%4};" :: "l"(kdst), "r"(v.x | tag), "r"(v.y | tag), "r"(v.z | tag), "r"(v.w | tag) : "memory");
        }
        TSTAMP(4);
        if (lane == 0) { mbar_arrive(bar_row + FB_KEYS); mbar_expect(bar_x, 8 * 1152); }
        uint32_t k[16];
        const uint4* src = p.s->keys + (f & 15) * 128 + lane;
        for (int it = 0;; it++) {
            uint32_t bad = 0;
#pragma unroll
            for (int i = 0; i < 4; i++) {
                const uint4 x = ld_rlx128(src + (i < 3 || lane < 24 ? 32 * i : 64));
                k[i] = x.x; k[4 + i] = x.y; k[8 + i] = x.z; k[12 + i] = x.w;
                bad |= x.x ^ tag;
            }
            const bool ok = __all_sync(0xffffffffu, (bad & 0xf800u) == 0);
            if (ok) break;
            if (it > (1 << 20)) __trap();
        }
        TSTAMP(5);
        uint32_t key = 0;
#pragma unroll 2
        for (int r = 0; r < 8; r++) {
            const uint32_t m = __reduce_max_sync(0xffffffffu, max(max(k[0], k[1]), max(k[2], k[3])));
#pragma unroll
            for (int i = 0; i < 4; i++) {
                const bool pop = k[i] == m;
                k[i] = pop ? k[4 + i] : k[i]; k[4 + i] = pop ? k[8 + i] : k[4 + i]; k[8 + i] = pop ? k[12 + i] : k[8 + i]; k[12 + i] = pop ? 0 : k[12 + i];
            }
            if (r8 == r) key = m;
        }
        const int row = key_row(key);
        sts32(s_tok + r8 * 8, row);
        bar_arrive(BAR_X, 160);
        TSTAMP(6);
        if (isx) {
            if (!(f & 1)) {
                __nv_bfloat16* o = p.out + (size_t)row * DM + 16 * f + 8 * mi;
                asm volatile("st.relaxed.gpu.global.v4.u32 [%0], {%1,%1,%1,%1};" :: "l"(o), "r"(0) : "memory");
                if (__any_sync(0xffffffffu, ld_rlx32(o) != 0)) __trap();
                if (lane < 8) st_rlx32(&p.s->sel[32 * f + lane], key);
            } else wait_sel(p, f >> 1, r8, tag);
            uint32_t gb;
            for (int it = 0;; it++) {
                asm volatile("ld.relaxed.gpu.global.u16 %0, [%1];" : "=r"(gb) : "l"(p.s->gate + row) : "memory");
                gb ^= par;
                if (!(gb & 0x8000u)) break;
                if (it > (1 << 20)) __trap();
            }
            const uint32_t rb = key ^ 0x80000000u, rv = (rb ^ (((int)rb >> 31) & 0x7fff0000u)) & 0xffff0000u;
            sts32(s_tok + r8 * 8 + 4, __float_as_uint(rbf(1.0f - bf_lo(gb)) * rbf(sigmoidf_(__uint_as_float(rv)))));
            __syncwarp();
            TSTAMP(7);
            bar_arrive(BAR_RED, 416);
        }
    } else {
        if (rw < nrw) {
            float c[3][4];
#pragma unroll
            for (int i = 0; i < 3; i++) { c[i][0] = c[i][1] = c[i][2] = c[i][3] = 0.f; }
            mbar_wait(bar_row + 48); mbar_wait(bar_row + 56);
            const uint32_t b = fresh(sb + SF_WR) + (g & 1) * 1152 + (g >> 2) * 64 + t * 16 + (g & 2) * 2;
            uint32_t w[18][2];
#pragma unroll
            for (int kb = 0; kb < 18; kb++) { const uint32_t o = ((kb & 1) ? b ^ 64 : b) + 128 * (kb >> 1); w[kb][0] = lds32(o); w[kb][1] = lds32(o + 8); }
            mbar_wait(bar_row + 8 * rw);
            if (warp == 15) TSTAMP(2);
            const uint32_t a = fresh(rows) + g * 1152 + (g & 1) * 64 + t * 16;
#pragma unroll
            for (int kb = 0; kb < 18; kb++) {
                const uint4 x = lds128(((kb & 1) ? a ^ 64 : a) + 128 * (kb >> 1));
                mma_bf(c[kb % 3], x.x, x.y, x.z, x.w, w[kb][0], w[kb][1]);
            }
            const float sr = c[0][0] + c[1][0] + c[2][0] + __shfl_down_sync(0xffffffffu, c[0][2] + c[1][2] + c[2][2], 1);
            const float sg = c[0][1] + c[1][1] + c[2][1] + __shfl_down_sync(0xffffffffu, c[0][3] + c[1][3] + c[2][3], 1);
            const uint32_t rb = pack_bf16(0.f, sr);
            if (t == 2 * (g & 1)) {
                sts32(s_part + (8 * rw + g) * 4, (rb ^ (((int)rb >> 31) & 0x7fff0000u) ^ 0x80000000u) | (uint32_t)(2047 - r0 - 8 * rw - g));
                sts32(s_part + 192 + (8 * rw + g) * 4, __float_as_uint(sg));
            }
            __syncwarp();
            bar_sync(BAR_R, 32 * (nrw + 1));
            const uint32_t sk = fresh(s_part), kk = lds32(sk + (8 * rw + r8) * 4);
            int n = 0;
#pragma unroll
            for (int i = 0; i < 3; i++) { const uint4 v = lds128(sk + mi * 48 + 16 * i); n += (v.x > kk) + (v.y > kk) + (v.z > kk) + (v.w > kk); }
            n += __shfl_xor_sync(0xffffffffu, n, 8); n += __shfl_xor_sync(0xffffffffu, n, 16);
            if (n < 8) sts32(s_tok + 4 * n, kk);
            __syncwarp();
            bar_arrive(BAR_R2, 32 * (nrw + 1));
        }
    }
}

__device__ __forceinline__ void ffn_work(const Params& p, uint32_t sb, int warp, int lane, int f, unsigned epoch) {
    const int g = lane >> 2, t = lane & 3, mi = lane >> 3, r8 = lane & 7;
    const bool isx = f < NX;
    const int ks0 = isx ? 4 * f : 6 * f - 72, nt = isx ? 4 : 6;
    const uint32_t bar_x = sb + SF_MISC + FB_X, bar_free = sb + SF_MISC + FB_FREE, bar_w = sb + SF_MISC + FB_W, bar_d = sb + SF_MISC + FB_D, s_tok = sb + SF_MISC + FS_TOK;
    next_epoch(p, epoch);
    uint32_t fr[24][4];
    auto pin = [&] {
#pragma unroll
        for (int i = 0; i < 24; i += 8) asm volatile("" :: "r"(fr[i][0]), "r"(fr[i + 1][0]), "r"(fr[i + 2][0]), "r"(fr[i + 3][0]), "r"(fr[i + 4][0]), "r"(fr[i + 5][0]), "r"(fr[i + 6][0]), "r"(fr[i + 7][0]) : "memory");
    };
    {
        const int j = isx ? warp >> 2 : warp >= 6, w = warp - j * nt;
        float ag[2][4], au[2][4];
#pragma unroll
        for (int i = 0; i < 2; i++) { ag[i][0] = ag[i][1] = ag[i][2] = ag[i][3] = 0.f; au[i][0] = au[i][1] = au[i][2] = au[i][3] = 0.f; }
        const uint32_t wb = sb + (w >> 1) * 4096 + (r8 + 8 * (mi >> 1)) * 64 + (((2 * (w & 1) + (mi & 1)) ^ (r8 >> 1)) << 4);
        const uint32_t xb = sb + SF_XS + r8 * 1168 + mi * 16;
        auto load = [&](int i, int n) {
            mbar_wait(bar_w + 8 * n);
            const uint32_t wk = fresh(wb) + n * nt * 4096;
#pragma unroll
            for (int s = 0; s < 4; s++) { ldsm4t(fr[8 * i + s], wk + 1024 * s); ldsm4t(fr[8 * i + 4 + s], wk + 1024 * s + nt * 2048); }
        };
        auto mul = [&](int i, uint32_t xk) {
            uint32_t x[2][4];
            ldsm4(x[0], xk); ldsm4(x[1], xk + 64);
#pragma unroll
            for (int s = 0; s < 4; s++) {
                const uint32_t (&a)[4] = fr[8 * i + s], (&b)[4] = fr[8 * i + 4 + s];
                mma_bf(ag[s & 1], a[0], a[1], a[2], a[3], x[s >> 1][2 * (s & 1)], x[s >> 1][2 * (s & 1) + 1]);
                mma_bf(au[s & 1], b[0], b[1], b[2], b[3], x[s >> 1][2 * (s & 1)], x[s >> 1][2 * (s & 1) + 1]);
            }
        };
#pragma unroll
        for (int i = 0; i < 3; i++) load(i, 3 * j + i);
        pin();
        bar_sync(BAR_G + j, 32 * nt);
        if (w == 0 && lane == 0) mbar_arrive(bar_free + 8 * j);
        if (warp < 4) {
            bar_sync(BAR_X, 160);
            const uint32_t rows = lds32(fresh(s_tok) + 8 * r8);
#pragma unroll 1
            for (int i = warp; i < 8; i += 4) {
                const int row = __shfl_sync(0xffffffffu, rows, i);
                if (lane == 0) bulk_g2s(sb + SF_XS + i * 1168, p.u + (size_t)row * DM, 1152, bar_x);
                __syncwarp();
            }
        }
        mbar_wait(bar_x);
        if (warp == 0) TSTAMP(8);
        {
            const uint32_t xk = fresh(xb) + 384 * j;
#pragma unroll
            for (int i = 0; i < 3; i++) { mul(i, (i ? fresh(xk) : xk) + 128 * i); if (i == 0) { asm volatile("" :: "f"(ag[0][0]), "f"(ag[1][0]), "f"(au[0][0]), "f"(au[1][0])); sts32(s_tok + 64, clock32()); } }
        }
        if (!isx) {
#pragma unroll 1
            for (int n = 6 + j; n < 9; n += 2) { load(0, n); mul(0, fresh(xb) + 128 * n); }
        }
#pragma unroll
        for (int c = 0; c < 4; c++) { ag[0][c] += ag[1][c]; au[0][c] += au[1][c]; }
        const uint32_t sc = sb + SF_SUM + 1024 * w + 16 * lane;
        if (j) {
            sts128(sc + (j - 1) * 49152, __float_as_uint(ag[0][0]), __float_as_uint(ag[0][1]), __float_as_uint(ag[0][2]), __float_as_uint(ag[0][3]));
            sts128(sc + (j - 1) * 49152 + 512, __float_as_uint(au[0][0]), __float_as_uint(au[0][1]), __float_as_uint(au[0][2]), __float_as_uint(au[0][3]));
        }
        bar_sync(BAR_GU, 384);
        if (!j) {
            const uint32_t sf = fresh(sc);
            const uint4 g1 = lds128(sf), u1 = lds128(sf + 512), g2 = lds128(sf + 49152), u2 = lds128(sf + 49664);
            const uint32_t gs[2][4] = {{g1.x, g1.y, g1.z, g1.w}, {g2.x, g2.y, g2.z, g2.w}}, us[2][4] = {{u1.x, u1.y, u1.z, u1.w}, {u2.x, u2.y, u2.z, u2.w}};
            if (warp == 0) TSTAMP(9);
            float h[4];
#pragma unroll
            for (int c = 0; c < 4; c++) {
                const float gv = rbf(ag[0][c] + __uint_as_float(gs[0][c]) + (isx ? __uint_as_float(gs[1][c]) : 0.f));
                h[c] = rbf(gv * sigmoidf_(gv)) * rbf(au[0][c] + __uint_as_float(us[0][c]) + (isx ? __uint_as_float(us[1][c]) : 0.f));
            }
            uint32_t h0, h1;
            asm("movmatrix.sync.aligned.m8n8.trans.b16 %0, %1;" : "=r"(h0) : "r"(pack_bf16(h[0], h[1])));
            asm("movmatrix.sync.aligned.m8n8.trans.b16 %0, %1;" : "=r"(h1) : "r"(pack_bf16(h[2], h[3])));
            if (h0 == 0) h0 = 0x8000u;
            asm volatile("{ .reg .b64 v; mov.b64 v, {%1, %2}; st.relaxed.gpu.global.b64 [%0], v; }" :: "l"(p.s->h + ((epoch & 1) * 288 + ks0 + warp) * 32 + lane), "r"(h0), "r"(h1) : "memory");
        }
        if (isx) {
            if (warp == 0) TSTAMP(10);
            const uint2* hsrc = p.s->h + ((epoch & 1) * 288 + 144 * (f & 1) + 12 * warp) * 32 + lane;
            uint2 hb[12];
            auto ldh = [&](int s) { asm volatile("ld.relaxed.gpu.global.v2.u32 {%0, %1}, [%2];" : "=r"(hb[s].x), "=r"(hb[s].y) : "l"(hsrc + 32 * s) : "memory"); };
#pragma unroll
            for (int s = 0; s < 12; s++) ldh(s);
            for (int it = 0;; it++) {
                bool again = false;
#pragma unroll
                for (int s = 0; s < 12; s += 2) if (__any_sync(0xffffffffu, min(hb[s].x, hb[s + 1].x) == 0)) { ldh(s); ldh(s + 1); again = true; }
                if (!again) break;
                if (it > (1 << 16)) __trap();
            }
            if (warp == 0) TSTAMP(11);
            mbar_wait(bar_d + 8 * warp);
            if (warp == 11) TSTAMP(14);
            float ad[2][2][4];
#pragma unroll
            for (int i = 0; i < 4; i++) { ad[i >> 1][i & 1][0] = ad[i >> 1][i & 1][1] = ad[i >> 1][i & 1][2] = ad[i >> 1][i & 1][3] = 0.f; }
            const uint32_t wd = fresh(sb) + (warp < 6 ? SF_WD : -6 * 12288) + warp * 12288 + (r8 + 8 * (mi >> 1)) * 64 + (((mi & 1) ^ (r8 >> 1)) << 4);
#pragma unroll
            for (int s = 0; s < 12; s++) {
                uint32_t a[4], b[4];
                ldsm4t(a, wd + 1024 * s); ldsm4t(b, (wd ^ 32) + 1024 * s);
                mma_bf(ad[0][s & 1], a[0], a[1], a[2], a[3], hb[s].x, hb[s].y);
                mma_bf(ad[1][s & 1], b[0], b[1], b[2], b[3], hb[s].x, hb[s].y);
            }
            const uint32_t rd = sb + SF_RED + warp * 1152 + (72 * t + g) * 4;
#pragma unroll
            for (int i = 0; i < 8; i++) sts32(rd + (i >> 2) * 64 + (i & 1) * 144 + ((i >> 1) & 1) * 32, __float_as_uint(ad[i >> 2][0][i & 3] + ad[i >> 2][1][i & 3]));
            bar_sync(BAR_RED, 416);
            if (warp < 4) {
                const int tid = 32 * warp + lane;
                const uint32_t rs = fresh(sb + SF_RED) + (tid >> 4) * 144 + (tid & 15) * 8;
                const uint2 tk = lds64(fresh(s_tok) + (tid >> 4) * 8);
                float x = 0.f, y = 0.f;
#pragma unroll
                for (int w = 0; w < 12; w++) { const uint2 v = lds64(rs + w * 1152); x += __uint_as_float(v.x); y += __uint_as_float(v.y); }
                asm volatile("red.relaxed.gpu.global.add.noftz.bf16x2 [%0], %1;" :: "l"(p.out + (size_t)tk.x * DM + 32 * (f >> 1) + 2 * (tid & 15)),
                             "r"(pack_bf16(x * __uint_as_float(tk.y), y * __uint_as_float(tk.y))) : "memory");
            }
            if (warp == 0) TSTAMP(15);
        }
        if (warp == 0) TFLUSH();
    }
}

constexpr int SMEM_BYTES = 232448;
static_assert(SF_MISC + 1024 <= 232192, "layout");

struct Maps { CUtensorMap m[7]; };

__global__ void __cluster_dims__(2, 1, 1) __launch_bounds__(NTHR, 1)
fused_kernel(const Params p, const __grid_constant__ Maps maps) {
    extern __shared__ __align__(1024) uint8_t smem_raw[];
    uint32_t q[8];
    {
        const int b = blockIdx.x, x = threadIdx.x, rc = 4 * b + max(b - 84, 0) - 288 + (x >> 6);
        const int cv = (b - NCONV) >> 31, ca = 8 * b + ((x >> 5) & 3), cb = 2 * rc - (rc & 3) + 4;
        const uint32_t ch = (ca & cv) | (cb & ~cv), o = NST * ch + 2 * ((x & 31) + ((x >> (cv & 2)) & 32));
        const bool c = x < (b < 84 ? 256 : 320);
        q[6] = ldg16_if(c, p.logdt + ch);
        q[2] = ldg32_if(c, p.Bre + o); q[3] = ldg32_if(c, p.Bim + o); q[4] = ldg32_if(c, p.Cre + o); q[5] = ldg32_if(c, p.Cim + o); q[0] = ldg32_if(c, p.Are + o); q[1] = ldg32_if(c, p.Aim + o);
        q[7] = ldg16_if(c, p.Dskip + ch);
    }
    const unsigned epoch = ld_rlx32(&p.s->epoch[blockIdx.x * 16 + (threadIdx.x >> 5)]);
    const uint32_t sb = __shfl_sync(0xffffffffu, smem_u32(smem_raw), 0);
    const int warp = __shfl_sync(0xffffffffu, threadIdx.x >> 5, 0), bid = __shfl_sync(0xffffffffu, blockIdx.x, 0);
    const int lane = __shfl_sync(0xffffffffu, threadIdx.x & 31, threadIdx.x);
    const bool conv = bid < NCONV;
    const int f = bid - NCONV;
    uint32_t w[12];
    if (warp < (f < 12 ? 8 : 10)) {
        const int half = conv ? warp >> 2 : warp & 1, pr = conv ? warp & 3 : warp >> 1;
        const int rc = 4 * f + max(f - 12, 0) + pr;
        const uint32_t stage = sb + (conv ? SC_KG : SF_KG) + warp * KG_STAGE;
        uint4* const kp = p.s->kp + rc * 128 + lane;
        kgen(q, sb, half, stage, stage + (conv ? 4 : 1) * KG_STAGE, 1 + pr, lane, p.zero, w, [&] {
            sts128z_if(conv && lane < 20, sb + SC_KT + warp * KT_BYTES + lane * 16 + (lane < 4 ? 0 : lane < 14 ? 2048 : 2288));
            stg128z_if(!conv, kp + 64 * half); stg128z_if(!conv, kp + 64 * half + 32);
            stg128z_if(!conv && warp < (f < NX ? 4 : 6), (uint4*)(p.s->h + ((lane >> 4) * 288 + (f < NX ? 4 * f : 6 * f - 72) + warp) * 32) + (lane & 15));
            if (conv) asm volatile("barrier.cluster.arrive.relaxed.aligned;" ::: "memory");
        });
        if (conv) { conv_main(p, sb, warp, lane, bid, epoch, w); return; }
        {
            if (!half) {
#pragma unroll
                for (int i = 0; i < 4; i++) asm volatile("st.relaxed.gpu.global.v4.u32 [%0], {%1,%2,%3,%4};" :: "l"(kp + 32 * i), "r"(w[3 * i]), "r"(w[3 * i + 1]), "r"(w[3 * i + 2]), "r"(~epoch) : "memory");
            }
            if (warp == 0) TSTAMP(22);
            if (warp == 2) TSTAMP(23);
            bar_sync(0, NTHR);
            if (warp == 0 && lane == 0) mbar_arrive(sb + SF_MISC + FB_KDONE);
        }
    } else if (conv) {
        conv_aux(p, maps.m, sb, warp - 8, lane, bid, epoch);
        return;
    } else {
        ffn_front(p, maps.m, sb, warp, lane, f, epoch);
        if (warp >= 12) return;
    }
    __syncwarp();
    ffn_work(p, sb, warp, lane, f, epoch);
}

typedef CUresult (*EncodeFn)(CUtensorMap*, CUtensorMapDataType, cuuint32_t, void*, const cuuint64_t*, const cuuint64_t*, const cuuint32_t*, const cuuint32_t*,
                             CUtensorMapInterleave, CUtensorMapSwizzle, CUtensorMapL2promotion, CUtensorMapFloatOOBfill);

void make_map(EncodeFn fn, CUtensorMap* m, const void* base, int rank, const cuuint64_t* dims, const cuuint64_t* strides, const cuuint32_t* box, CUtensorMapSwizzle sw) {
    const cuuint32_t es[5] = {1, 1, 1, 1, 1};
    fn(m, CU_TENSOR_MAP_DATA_TYPE_BFLOAT16, rank, (void*)base, dims, strides, box, es, CU_TENSOR_MAP_INTERLEAVE_NONE, sw,
       CU_TENSOR_MAP_L2_PROMOTION_NONE, CU_TENSOR_MAP_FLOAT_OOB_FILL_NONE);
}

}

extern "C" void kernel_launch(void* const* d_in, const int* in_sizes, int n_in, void* d_out, int out_size) {
    (void)in_sizes; (void)n_in; (void)out_size;
    static EncodeFn fn = nullptr;
    static void* scratch = nullptr;
    if (!fn) {
        void* ptr = nullptr; cudaDriverEntryPointQueryResult qr;
        cudaGetDriverEntryPoint("cuTensorMapEncodeTiled", &ptr, cudaEnableDefault, &qr);
        fn = (EncodeFn)ptr;
        cudaGetSymbolAddress(&scratch, g_scratch);
        cudaFuncSetAttribute(fused_kernel, cudaFuncAttributeMaxDynamicSharedMemorySize, SMEM_BYTES);
    }
    typedef const __nv_bfloat16* bp;
    Params p;
    p.u = (bp)d_in[0]; p.Are = (bp)d_in[1]; p.Aim = (bp)d_in[2]; p.Bre = (bp)d_in[3]; p.Bim = (bp)d_in[4]; p.Cre = (bp)d_in[5]; p.Cim = (bp)d_in[6];
    p.logdt = (bp)d_in[7]; p.Dskip = (bp)d_in[8]; p.wr = (bp)d_in[10]; p.gatew = (bp)d_in[14];
    p.out = (__nv_bfloat16*)d_out; p.s = (Scratch*)scratch; p.zero = 0;
    Maps maps;
    {
        const cuuint64_t dims[4] = {DM, 4, 16, 32}, strides[3] = {16 * DM * 2, DM * 2, 64 * DM * 2};
        const cuuint32_t box[4] = {16, 4, 16, 2};
        make_map(fn, &maps.m[0], d_in[0], 4, dims, strides, box, CU_TENSOR_MAP_SWIZZLE_32B);
    }
    for (int i = 0; i < 4; i++) {
        const cuuint64_t dims[3] = {32, DM, FF / 32}, strides[2] = {FF * 2, 64};
        const cuuint32_t box[3] = {32, 64, i < 2 ? 2u : 3u};
        make_map(fn, &maps.m[1 + i], d_in[11 + (i & 1)], 3, dims, strides, box, CU_TENSOR_MAP_SWIZZLE_64B);
    }
    {
        const cuuint64_t dims[2] = {DM, FF}, strides[1] = {DM * 2};
        const cuuint32_t box[2] = {32, 192};
        make_map(fn, &maps.m[5], d_in[13], 2, dims, strides, box, CU_TENSOR_MAP_SWIZZLE_64B);
    }
    {
        const cuuint64_t dims[5] = {DM, 4, 4, 2, L_SEQ}, strides[4] = {16 * DM * 2, 4 * DM * 2, 128 * DM * 2, DM * 2};
        const cuuint32_t box[5] = {16, 4, 4, 2, 1};
        make_map(fn, &maps.m[6], d_out, 5, dims, strides, box, CU_TENSOR_MAP_SWIZZLE_NONE);
    }
    fused_kernel<<<NCTA, NTHR, SMEM_BYTES>>>(p, maps);
}
```

```cpp
#include <cuda_runtime.h>
#include <cuda_bf16.h>
#include <cuda_fp16.h>
#include <cuda.h>
#include <stdint.h>
#include <type_traits>

#define RESUME 0
#define PUBIT 1
#define YSEQ 2
#define FPOS 3
#define PUBV 0
#define PUBST "st.relaxed.gpu.global"
#define FPOSY 0
#define PUBY 0
#define TW 12
#define MPOS 1
#define UDELAY 0
#define RDELAY 900
#define WDELAY 2000
#define WGAP 310
#define NPRE 7
#define DGAP 260

namespace {

constexpr int DM = 576, NST = 128, FF = 4608, L_SEQ = 2048;
constexpr int NCONV = 72, NX = 36, NW = 48, NCTA = 132, NTHR = 512;

struct __align__(128) Scratch {
    unsigned epoch[NCTA * 16];
    uint4 keys[16 * 128];
    uint32_t sel[18 * 64];
    uint16_t gate[L_SEQ];
    uint2 h[2 * 288 * 32];
    uint4 kp[DM * 128];
};
__device__ Scratch g_scratch;
#define TFLUSH()
#define TSTAMP(i)

struct Params {
    const __nv_bfloat16 *Are, *Aim, *Bre, *Bim, *Cre, *Cim, *logdt, *Dskip, *u, *wr, *gatew;
    __nv_bfloat16* out;
    Scratch* s;
    uint32_t zero;
};

__device__ __forceinline__ void give_up() { asm volatile("trap; exit;"); __builtin_unreachable(); }
__device__ __forceinline__ void converged() { __syncwarp(); asm volatile("{ .reg .b32 t; mov.b32 t, 0; movmatrix.sync.aligned.m8n8.trans.b16 t, t; }" ::: "memory"); }
__device__ __forceinline__ uint32_t smem_u32(const void* p) { return (uint32_t)__cvta_generic_to_shared(p); }
__device__ __forceinline__ uint32_t pack_bf16(float lo, float hi) { uint32_t r; asm("cvt.rn.bf16x2.f32 %0, %1, %2;" : "=r"(r) : "f"(hi), "f"(lo)); return r; }
__device__ __forceinline__ uint32_t pack_f16(float lo, float hi) { uint32_t r; asm("cvt.rn.f16x2.f32 %0, %1, %2;" : "=r"(r) : "f"(hi), "f"(lo)); return r; }
__device__ __forceinline__ float bf_lo(uint32_t w) { return __uint_as_float(w << 16); }
__device__ __forceinline__ float bf_hi(uint32_t w) { return __uint_as_float(w & 0xffff0000u); }
__device__ __forceinline__ float rbf(float x) { return bf_lo(pack_bf16(x, 0.f)); }
__device__ __forceinline__ uint32_t badd2(uint32_t a, uint32_t b) { uint32_t r; asm("add.rn.bf16x2 %0, %1, %2;" : "=r"(r) : "r"(a), "r"(b)); return r; }
__device__ __forceinline__ uint32_t bsub2(uint32_t a, uint32_t b) { uint32_t r; asm("sub.rn.bf16x2 %0, %1, %2;" : "=r"(r) : "r"(a), "r"(b)); return r; }
__device__ __forceinline__ uint32_t gmix(uint32_t ng, float ny0, float ny1, uint32_t u) {
    uint32_t r; asm("{ .reg .b32 t; fma.rn.bf16x2 t, %1, %3, %3; fma.rn.bf16x2 %0, %1, %2, t; }" : "=r"(r) : "r"(ng), "r"(pack_bf16(ny0, ny1)), "r"(u)); return r;
}
__device__ __forceinline__ void mma_bf(float (&c)[4], uint32_t a0, uint32_t a1, uint32_t a2, uint32_t a3, uint32_t b0, uint32_t b1) {
    asm("mma.sync.aligned.m16n8k16.row.col.f32.bf16.bf16.f32 {%0,%1,%2,%3}, {%4,%5,%6,%7}, {%8,%9}, {%0,%1,%2,%3};"
        : "+f"(c[0]), "+f"(c[1]), "+f"(c[2]), "+f"(c[3]) : "r"(a0), "r"(a1), "r"(a2), "r"(a3), "r"(b0), "r"(b1));
}
__device__ __forceinline__ void mma_bf8(float (&c)[4], uint32_t a0, uint32_t a1, uint32_t b0) {
    asm("mma.sync.aligned.m16n8k8.row.col.f32.bf16.bf16.f32 {%0,%1,%2,%3}, {%4,%5}, {%6}, {%0,%1,%2,%3};"
        : "+f"(c[0]), "+f"(c[1]), "+f"(c[2]), "+f"(c[3]) : "r"(a0), "r"(a1), "r"(b0));
}
__device__ __forceinline__ void mma_h(float (&c)[4], uint32_t a0, uint32_t a1, uint32_t a2, uint32_t a3, uint32_t b0, uint32_t b1) {
    asm("mma.sync.aligned.m16n8k16.row.col.f32.f16.f16.f32 {%0,%1,%2,%3}, {%4,%5,%6,%7}, {%8,%9}, {%0,%1,%2,%3};"
        : "+f"(c[0]), "+f"(c[1]), "+f"(c[2]), "+f"(c[3]) : "r"(a0), "r"(a1), "r"(a2), "r"(a3), "r"(b0), "r"(b1));
}
__device__ __forceinline__ uint32_t fresh(uint32_t a) { asm volatile("" : "+r"(a) :: "memory"); return a; }
__device__ __forceinline__ uint32_t lds16(uint32_t a) { uint32_t v; asm("ld.shared.u16 %0, [%1];" : "=r"(v) : "r"(a)); return v; }
__device__ __forceinline__ uint32_t lds32(uint32_t a) { uint32_t v; asm("ld.shared.u32 %0, [%1];" : "=r"(v) : "r"(a)); return v; }
__device__ __forceinline__ uint2 lds64(uint32_t a) { uint2 v; asm("ld.shared.v2.u32 {%0,%1}, [%2];" : "=r"(v.x), "=r"(v.y) : "r"(a)); return v; }
__device__ __forceinline__ uint4 lds128(uint32_t a) { uint4 v; asm("ld.shared.v4.u32 {%0,%1,%2,%3}, [%4];" : "=r"(v.x), "=r"(v.y), "=r"(v.z), "=r"(v.w) : "r"(a)); return v; }
__device__ __forceinline__ uint4 lds128v(uint32_t a) { uint4 v; asm volatile("ld.shared.v4.u32 {%0,%1,%2,%3}, [%4];" : "=r"(v.x), "=r"(v.y), "=r"(v.z), "=r"(v.w) : "r"(a) : "memory"); return v; }
__device__ __forceinline__ void ldsm4(uint32_t (&r)[4], uint32_t a) {
    asm("ldmatrix.sync.aligned.m8n8.x4.shared.b16 {%0,%1,%2,%3}, [%4];" : "=r"(r[0]), "=r"(r[1]), "=r"(r[2]), "=r"(r[3]) : "r"(a));
}
__device__ __forceinline__ void ldsm4t(uint32_t (&r)[4], uint32_t a) {
    asm("ldmatrix.sync.aligned.m8n8.x4.trans.shared.b16 {%0,%1,%2,%3}, [%4];" : "=r"(r[0]), "=r"(r[1]), "=r"(r[2]), "=r"(r[3]) : "r"(a));
}
__device__ __forceinline__ void sts16(uint32_t a, uint32_t v) { asm volatile("st.shared.u16 [%0], %1;" :: "r"(a), "h"((unsigned short)v) : "memory"); }
__device__ __forceinline__ void sts32(uint32_t a, uint32_t v) { asm volatile("st.shared.u32 [%0], %1;" :: "r"(a), "r"(v) : "memory"); }
__device__ __forceinline__ void sts64(uint32_t a, uint32_t x, uint32_t y) { asm volatile("st.shared.v2.u32 [%0], {%1,%2};" :: "r"(a), "r"(x), "r"(y) : "memory"); }
__device__ __forceinline__ void sts128(uint32_t a, uint32_t x, uint32_t y, uint32_t z, uint32_t w) {
    asm volatile("st.shared.v4.u32 [%0], {%1,%2,%3,%4};" :: "r"(a), "r"(x), "r"(y), "r"(z), "r"(w) : "memory");
}
__device__ __forceinline__ void st_async128(uint32_t a, uint32_t x, uint32_t y, uint32_t z, uint32_t w, uint32_t bar) {
    asm volatile("st.async.weak.shared::cluster.mbarrier::complete_tx::bytes.v4.b32 [%0], {%1,%2,%3,%4}, [%5];" :: "r"(a), "r"(x), "r"(y), "r"(z), "r"(w), "r"(bar) : "memory");
}
__device__ __forceinline__ void mbar_init(uint32_t b, uint32_t cnt) { asm volatile("mbarrier.init.shared::cta.b64 [%0], %1;" :: "r"(b), "r"(cnt) : "memory"); }
__device__ __forceinline__ void mbar_fence() { asm volatile("fence.mbarrier_init.release.cluster;" ::: "memory"); }
__device__ __forceinline__ void mbar_expect(uint32_t b, uint32_t bytes) { asm volatile("mbarrier.arrive.expect_tx.shared::cta.b64 _, [%0], %1;" :: "r"(b), "r"(bytes) : "memory"); }
__device__ __forceinline__ void mbar_arrive(uint32_t b) { asm volatile("mbarrier.arrive.shared::cta.b64 _, [%0];" :: "r"(b) : "memory"); }
#define CHINT ""
#define HINT ""
__device__ __forceinline__ void mbar_wait(uint32_t b, uint32_t parity = 0) {
    asm volatile("{ .reg .pred p; .reg .u32 n; mov.u32 n, 0;\n"
                 "LW: mbarrier.try_wait.parity.shared::cta.b64 p, [%0], %1" HINT "; @p bra LD; add.u32 n, n, 1; setp.lt.u32 p, n, 65536; @p bra LW; trap;\n"
                 "LD: }" :: "r"(b), "r"(parity) : "memory");
}
__device__ __forceinline__ void mbar_wait_cluster(uint32_t b) {
    asm volatile("{ .reg .pred p; .reg .u32 n; mov.u32 n, 0;\n"
                 "LW: mbarrier.try_wait.parity.acquire.cluster.shared::cta.b64 p, [%0], 0" CHINT "; @p bra LD; add.u32 n, n, 1; setp.lt.u32 p, n, 65536; @p bra LW; trap;\n"
                 "LD: }" :: "r"(b) : "memory");
}
__device__ __forceinline__ void tma2d(uint32_t dst, const CUtensorMap* m, int c0, int c1, uint32_t bar) {
    asm volatile("cp.async.bulk.tensor.2d.shared::cluster.global.mbarrier::complete_tx::bytes [%0], [%1, {%3, %4}], [%2];"
                 :: "r"(dst), "l"(m), "r"(bar), "r"(c0), "r"(c1) : "memory");
}
__device__ __forceinline__ void tma3d(uint32_t dst, const CUtensorMap* m, int c0, int c1, int c2, uint32_t bar) {
    asm volatile("cp.async.bulk.tensor.3d.shared::cluster.global.mbarrier::complete_tx::bytes [%0], [%1, {%3, %4, %5}], [%2];"
                 :: "r"(dst), "l"(m), "r"(bar), "r"(c0), "r"(c1), "r"(c2) : "memory");
}
__device__ __forceinline__ void tma4d(uint32_t dst, const CUtensorMap* m, int c0, int c1, int c2, int c3, uint32_t bar) {
    asm volatile("cp.async.bulk.tensor.4d.shared::cluster.global.mbarrier::complete_tx::bytes [%0], [%1, {%3, %4, %5, %6}], [%2];"
                 :: "r"(dst), "l"(m), "r"(bar), "r"(c0), "r"(c1), "r"(c2), "r"(c3) : "memory");
}
__device__ __forceinline__ void bulk_g2s(uint32_t dst, const void* src, uint32_t bytes, uint32_t bar) {
    asm volatile("cp.async.bulk.shared::cluster.global.mbarrier::complete_tx::bytes [%0], [%1], %2, [%3];"
                 :: "r"(dst), "l"(src), "r"(bytes), "r"(bar) : "memory");
}
__device__ __forceinline__ uint32_t mapa(uint32_t a, uint32_t rank) { uint32_t r; asm("mapa.shared::cluster.u32 %0, %1, %2;" : "=r"(r) : "r"(a), "r"(rank)); return r; }
__device__ __forceinline__ void prefetch_map(const CUtensorMap* m) { asm volatile("prefetch.tensormap [%0];" :: "l"(m) : "memory"); }
__device__ __forceinline__ void bar_sync(int id, int n) { asm volatile("bar.sync %0, %1;" :: "r"(id), "r"(n) : "memory"); }
__device__ __forceinline__ void bar_arrive(int id, int n) { asm volatile("bar.arrive %0, %1;" :: "r"(id), "r"(n) : "memory"); }
__device__ __forceinline__ uint32_t ldg16_if(bool c, const void* p) { uint32_t v; asm volatile("{ .reg .pred p; setp.ne.u32 p, %2, 0; @p ld.global.nc.u16 %0, [%1]; }" : "=r"(v) : "l"(p), "r"((uint32_t)c)); return v; }
__device__ __forceinline__ uint32_t ldg32_if(bool c, const void* p) { uint32_t v; asm volatile("{ .reg .pred p; setp.ne.u32 p, %2, 0; @p ld.global.nc.u32 %0, [%1]; }" : "=r"(v) : "l"(p), "r"((uint32_t)c)); return v; }
__device__ __forceinline__ uint32_t ld_rlx32(const void* p) { uint32_t v; asm volatile("ld.relaxed.gpu.global.u32 %0, [%1];" : "=r"(v) : "l"(p) : "memory"); return v; }
__device__ __forceinline__ uint4 ld_rlx128(const void* p) {
    uint4 v; asm volatile("ld.relaxed.gpu.global.v4.u32 {%0,%1,%2,%3}, [%4];" : "=r"(v.x), "=r"(v.y), "=r"(v.z), "=r"(v.w) : "l"(p) : "memory"); return v;
}
__device__ __forceinline__ void st_rlx32(void* p, uint32_t v) { asm volatile("st.relaxed.gpu.global.u32 [%0], %1;" :: "l"(p), "r"(v) : "memory"); }
__device__ __forceinline__ void stg128(void* p, uint32_t x, uint32_t y, uint32_t z, uint32_t w) {
    asm volatile("st.global.v4.u32 [%0], {%1,%2,%3,%4};" :: "l"(p), "r"(x), "r"(y), "r"(z), "r"(w) : "memory");
}
__device__ __forceinline__ void next_epoch(const Params& p, unsigned e) { if ((threadIdx.x & 31) == 0) p.s->epoch[blockIdx.x * 16 + (threadIdx.x >> 5)] = e + 1; }
__device__ __forceinline__ void sts128z_if(bool c, uint32_t a) { asm volatile("{ .reg .pred p; setp.ne.u32 p, %1, 0; @p st.shared.v4.u32 [%0], {%2,%2,%2,%2}; }" :: "r"(a), "r"((uint32_t)c), "r"(0) : "memory"); }
__device__ __forceinline__ void stg128z_if(bool c, void* a) { asm volatile("{ .reg .pred p; setp.ne.u32 p, %1, 0; @p st.global.v4.u32 [%0], {%2,%2,%2,%2}; }" :: "l"(a), "r"((uint32_t)c), "r"(0) : "memory"); }
__device__ __forceinline__ unsigned clock32() { unsigned c; asm volatile("mov.u32 %0, %clock;" : "=r"(c) :: "memory"); return c; }
__device__ __forceinline__ void until(unsigned t0, int c) { while ((int)(clock32() - t0) < c) { } }
__device__ __forceinline__ float sigmoidf_(float x) { return __fdividef(1.0f, 1.0f + __expf(-x)); }
__device__ __forceinline__ uint32_t key_tag(unsigned epoch) { return ((epoch & 15u) | 16u) << 11; }
__device__ __forceinline__ int key_row(uint32_t key) { return 2047 - (int)(key & 2047u); }
__device__ __forceinline__ uint32_t wait_sel(const Params& p, int s32, int r8, uint32_t tag) {
    uint32_t k;
#pragma unroll 1
    for (int it = 0;; it++) {
        k = ld_rlx32(&p.s->sel[s32 * 64 + r8]);
        if (__all_sync(0xffffffffu, (k & 0xf800u) == tag)) break;
        if (it > (1 << 20)) give_up();
    }
    return k;
}

struct cplx { float re, im; };
__device__ __forceinline__ cplx csq(cplx a) { cplx r; r.re = a.re * a.re - a.im * a.im; r.im = (a.re * a.im) * 2.f; return r; }
__device__ __forceinline__ cplx cexpk(float ar, float ai, float k) {
    float mag, s, c;
    asm("ex2.approx.ftz.f32 %0, %1;" : "=f"(mag) : "f"(ar * (k * 1.4426950408889634f)));
    const float r = ai * k;
    asm("sin.approx.ftz.f32 %0, %1;" : "=f"(s) : "f"(r));
    asm("cos.approx.ftz.f32 %0, %1;" : "=f"(c) : "f"(r));
    cplx o; o.re = mag * c; o.im = mag * s; return o;
}
struct h2c { uint32_t re, im; };
__device__ __forceinline__ h2c cmul_cd(h2c v, __half2 c, __half2 d) {
    const __half2 r = *(const __half2*)&v.re, i = *(const __half2*)&v.im;
    const __half2 x = __hfma2(__hneg2(i), d, __hmul2(r, c)), y = __hfma2(i, c, __hmul2(r, d));
    h2c o; o.re = *(const uint32_t*)&x; o.im = *(const uint32_t*)&y; return o;
}
__device__ __forceinline__ h2c cmul_s(h2c v, uint32_t s) { const __half2 h = *(const __half2*)&s; return cmul_cd(v, __low2half2(h), __high2half2(h)); }
__device__ __forceinline__ h2c cmul_sc(h2c v, uint32_t s) {
    const __half2 h = *(const __half2*)&s, c = __low2half2(h), d = __high2half2(h), r = *(const __half2*)&v.re, i = *(const __half2*)&v.im;
    const __half2 x = __hfma2(i, d, __hmul2(r, c)), y = __hfma2(__hneg2(r), d, __hmul2(i, c));
    h2c o; o.re = *(const uint32_t*)&x; o.im = *(const uint32_t*)&y; return o;
}
__device__ __forceinline__ h2c cmul_vc(h2c v, uint32_t s) {
    const __half2 h = *(const __half2*)&s, c = __low2half2(h), d = __high2half2(h), r = *(const __half2*)&v.re, i = *(const __half2*)&v.im;
    const __half2 x = __hfma2(i, d, __hmul2(r, c)), y = __hfma2(__hneg2(i), c, __hmul2(r, d));
    h2c o; o.re = *(const uint32_t*)&x; o.im = *(const uint32_t*)&y; return o;
}

constexpr int UT_HALF = 2240, UT_STRIDE = 4448;
constexpr int KT_T = 542, KT_C = 552, KT_D = 645, KT_BYTES = 720 * 4;
constexpr int VC_OFF = 80, VE_BASE = 1616;
constexpr int V_STRIDE = (1616 + 1024) * 4 + 80;
constexpr int KG_STAGE = 5248;
constexpr int Y_CS = 2080, Y_RS = 8 * Y_CS + 64;

constexpr int SC_RT = 0;
constexpr int SC_UT = 33408;
constexpr int SC_ST = SC_UT + 8 * UT_STRIDE;
constexpr int SC_KT = SC_ST + 8 * UT_STRIDE;
constexpr int SC_GT = SC_KT + 8 * KT_BYTES;
constexpr int SC_V = SC_GT + UT_STRIDE;
constexpr int SC_KG = SC_V + 4 * V_STRIDE;
constexpr int SC_MISC = SC_V + 8 * V_STRIDE;
static_assert(V_STRIDE % 128 == 16 && 8 * KG_STAGE <= 4 * V_STRIDE && 2 * Y_RS <= SC_UT && SC_UT % 128 == 0 && SC_ST % 128 == 0, "layout");
static_assert(SC_MISC % 16 == 0 && SC_MISC + 512 <= 232192, "layout");

__device__ __forceinline__ void window_task(uint32_t src, uint32_t d0, uint32_t d1, bool withE) {
    float S[35];
    {
        uint32_t w[20];
#pragma unroll
        for (int i = 0; i < 5; i++) {
            const uint4 v = lds128(src + ((i & 1) ? 0 : UT_HALF) + ((i + 1) >> 1) * 16);
            w[4 * i] = v.x; w[4 * i + 1] = v.y; w[4 * i + 2] = v.z; w[4 * i + 3] = v.w;
        }
        float s = 0.f; S[2] = 0.f;
#pragma unroll
        for (int i = 3; i < 26; i++) { s += (i & 1) ? bf_hi(w[i >> 1]) : bf_lo(w[i >> 1]); S[i] = s; }
#pragma unroll
        for (int i = 0; i < 8; i += 2)
            sts128((i & 4 ? d1 : d0) + (VC_OFF - 16) * 4 + 8 * (i & 2), pack_bf16(S[10 + i] - S[5 + i], S[5 + i] - S[2 + i]), pack_bf16(S[18 + i] - S[13 + i], S[13 + i] - S[10 + i]),
                   pack_bf16(S[11 + i] - S[6 + i], S[6 + i] - S[3 + i]), pack_bf16(S[19 + i] - S[14 + i], S[14 + i] - S[11 + i]));
        if (withE) {
#pragma unroll
            for (int i = 26; i < 35; i++) { s += (i & 1) ? bf_hi(w[i >> 1]) : bf_lo(w[i >> 1]); S[i] = s; }
#pragma unroll
            for (int i = 0; i < 8; i += 2)
                sts128((i & 4 ? d1 : d0) + VE_BASE * 4 + 8 * (i & 2), pack_bf16(S[19 + i] - S[12 + i], S[12 + i] - S[3 + i]), pack_bf16(S[27 + i] - S[20 + i], S[20 + i] - S[11 + i]),
                       pack_bf16(S[20 + i] - S[13 + i], S[13 + i] - S[4 + i]), pack_bf16(S[28 + i] - S[21 + i], S[21 + i] - S[12 + i]));
        }
    }
}

template <class F>
__device__ __forceinline__ void kgen(const uint32_t (&q)[8], uint32_t sb, int half, uint32_t stage, uint32_t pstage, int barid, int lane, uint32_t zero, uint32_t (&w)[12], F shadow) {
    const int t = lane & 3, mi = lane >> 3, r8 = lane & 7;
    {
        const uint32_t pAr = q[0], pAi = q[1], pBr = q[2], pBi = q[3], pCr = q[4], pCi = q[5], pDt = q[6], pD = q[7];
        const uint32_t wb = fresh(stage + lane * 16), za = fresh(stage + 5120 + ((lane >> 1) & 3) * 16 + mi * 4 + (lane & 1) * 2), zr = fresh(stage + 5120 + t * 16);
        const uint32_t oA = fresh(stage + (mi & 1) * 1024 + (mi >> 1) * 512 + r8 * 16), oB = fresh(stage + 2048 + mi * 512 + r8 * 16), oC = fresh(stage + 4096 + (mi & 1) * 512 + (mi >> 1) * 128 + r8 * 16);
        float acc[6][4];
#pragma unroll
        for (int a = 0; a < 6; a++) { acc[a][0] = acc[a][1] = acc[a][2] = acc[a][3] = 0.f; asm volatile("" : "+f"(acc[a][0]), "+f"(acc[a][1]), "+f"(acc[a][2]), "+f"(acc[a][3])); }
        shadow();
        sts32(zr, clock32());
        const float dt = rbf(__expf(bf_lo(pDt)));
        float ar = dt * bf_lo(pAr), ai = dt * bf_lo(pAi), ar1 = dt * bf_hi(pAr), ai1 = dt * bf_hi(pAi);
        float wr, wi, wr1, wi1;
        { const float br = dt * bf_lo(pBr), bi = dt * bf_lo(pBi), cr = bf_lo(pCr), ci = bf_lo(pCi); wr = cr * br - ci * bi; wi = cr * bi + ci * br; }
        { const float br = dt * bf_hi(pBr), bi = dt * bf_hi(pBi), cr = bf_hi(pCr), ci = bf_hi(pCi); wr1 = cr * br - ci * bi; wi1 = cr * bi + ci * br; }
        const uint32_t ex = max(__reduce_max_sync(0xffffffffu, __float_as_uint(fmaxf(fmaxf(fabsf(wr), fabsf(wi)), fmaxf(fabsf(wr1), fabsf(wi1))))) >> 23, 14u);
        const float scl = __uint_as_float((267u - ex) << 23);
        uint32_t W = pack_f16(wr * scl, wi * -scl);
        const uint32_t W1 = pack_f16(wr1 * scl, wi1 * -scl);
        if (threadIdx.x < 32) TSTAMP(20);

#pragma unroll 1
        for (int r = 0; r < 2; r++) {
            const cplx z1 = cexpk(ar, ai, 1.f), z64 = cexpk(ar, ai, 64.f);
            const cplx z2 = csq(z1), z4 = csq(z2), z8 = csq(z4), z16 = csq(z8), z32 = csq(z16);
            const cplx z128 = csq(z64), z256 = csq(z128), z512 = csq(z256);
            auto put = [&](int grp, h2c a, h2c b, h2c c, h2c d) { sts128(wb + grp * 1024, a.re, b.re, c.re, d.re); sts128(wb + grp * 1024 + 512, a.im, b.im, c.im, d.im); };
            {
                const uint32_t s4 = pack_f16(z4.re, z4.im), s256 = pack_f16(z256.re, z256.im), s512 = pack_f16(z512.re, z512.im);
                auto mix = [](h2c a, h2c b, uint32_t sel) { return h2c{__byte_perm(a.re, b.re, sel), __byte_perm(a.im, b.im, sel)}; };
                const h2c c10 = cmul_vc(h2c{pack_f16(z1.re, 1.f), pack_f16(z1.im, 0.f)}, W), c32 = cmul_sc(c10, pack_f16(z2.re, z2.im)), c54 = cmul_sc(c10, s4);
                put(2, c10, c32, c54, cmul_sc(c32, s4));
                const h2c d20 = cmul_sc(mix(c32, c10, 0x7632), s256), e04 = cmul_sc(mix(c10, c54, 0x7632), s512), f04 = cmul_sc(e04, s256);
                put(3, d20, cmul_sc(d20, s4), e04, f04);
                const h2c ef = mix(e04, f04, 0x5410), gh = cmul_sc(ef, s512), g8 = cmul_sc(gh, pack_f16(z8.re, z8.im));
                put(4, g8, cmul_sc(g8, s512), gh, ef);
            }
            {
                const uint32_t s32 = pack_f16(z32.re, z32.im), s64 = pack_f16(z64.re, z64.im), s128 = pack_f16(z128.re, z128.im);
                const h2c p0 = {pack_f16(1.f, z8.re), pack_f16(0.f, z8.im)}, p1 = cmul_s(p0, pack_f16(z16.re, z16.im)), p2 = cmul_s(p0, s32), p3 = cmul_s(p1, s32);
                put(0, p0, p1, p2, p3);
                put(1, cmul_s(p0, s64), cmul_s(p1, s64), cmul_s(p2, s64), cmul_s(p3, s64));
                sts16(za, s128); sts16(za + 64, s128 >> 16);
            }
            __syncwarp();
            {
                const uint32_t aA = fresh(oA), aB = fresh(oB), aC = fresh(oC), aZ = fresh(zr);
                const uint4 zc = lds128(aZ), zd = lds128(aZ + 64);
                const uint32_t zcs[4] = {zc.x, zc.y, zc.z, zc.w}, zds[4] = {zd.x, zd.y, zd.z, zd.w};
                uint32_t c[4];
#pragma unroll
                for (int k = 0; k < 4; k++) {
                    uint32_t a[4], b[4];
                    ldsm4t(a, aA + 128 * k); ldsm4t(b, aB + 128 * k);
                    if (!(k & 1)) ldsm4t(c, aC + 128 * k);
                    const h2c x = cmul_cd(h2c{a[0], a[2]}, *(const __half2*)&zcs[k], *(const __half2*)&zds[k]), y = cmul_cd(h2c{a[1], a[3]}, *(const __half2*)&zcs[k], *(const __half2*)&zds[k]);
                    mma_h(acc[0], a[0], a[1], a[2], a[3], b[0], b[1]);
                    mma_h(acc[1], a[0], a[1], a[2], a[3], b[2], b[3]);
                    mma_h(acc[2], a[0], a[1], a[2], a[3], c[2 * (k & 1)], c[2 * (k & 1) + 1]);
                    mma_h(acc[3], x.re, y.re, x.im, y.im, b[0], b[1]);
                    mma_h(acc[4], x.re, y.re, x.im, y.im, b[2], b[3]);
                    mma_h(acc[5], x.re, y.re, x.im, y.im, c[2 * (k & 1)], c[2 * (k & 1) + 1]);
                }
                asm volatile("" :: "f"(acc[0][0]), "f"(acc[1][0]), "f"(acc[2][0]), "f"(acc[3][0]), "f"(acc[4][0]), "f"(acc[5][0]) : "memory");
            }
            __syncwarp();
            ar = ar1; ai = ai1; W = W1;
        }
        if (threadIdx.x < 32) TSTAMP(21);
        const float i0 = __uint_as_float((ex + 243u) << 23);
        if (half) {
#pragma unroll
            for (int a = 0; a < 6; a++) sts128(wb + a * 512, __float_as_uint(acc[a][0]), __float_as_uint(acc[a][1]), __float_as_uint(acc[a][2]), __float_as_uint(acc[a][3]));
            sts32(stage + 3072, __float_as_uint(i0));
            bar_arrive(barid, 64);
        } else {
#pragma unroll
            for (int a = 0; a < 6; a++) { acc[a][0] *= i0; acc[a][1] *= i0; acc[a][2] *= i0; acc[a][3] *= i0; }
            if (lane == 0) acc[0][1] -= bf_lo(pD);
            sts32(zr, clock32());
            bar_sync(barid, 64);
            const uint32_t src = fresh(pstage);
            const float i1 = __uint_as_float(lds32(src + 3072));
#pragma unroll
            for (int a = 0; a < 6; a++) {
                const uint4 y = lds128(src + lane * 16 + a * 512);
                w[4 * (a % 3) + 2 * (a / 3)] = pack_bf16(fmaf(__uint_as_float(y.x), i1, acc[a][0]), fmaf(__uint_as_float(y.y), i1, acc[a][1]));
                w[4 * (a % 3) + 2 * (a / 3) + 1] = pack_bf16(fmaf(__uint_as_float(y.z), i1, acc[a][2]), fmaf(__uint_as_float(y.w), i1, acc[a][3]));
            }
        }
    }
}

__device__ __forceinline__ int swap01(int i) { return (i & ~3) | ((i & 1) << 1) | ((i >> 1) & 1); }
enum { BC_AUX = 0, BC_S = 5, BC_KG = 15 };

__device__ __forceinline__ void fetch_gates(const Params& p, int i, int lane, unsigned epoch, uint32_t dst) {
    const uint32_t par = (epoch & 1) ? 0x80008000u : 0u;
    uint4 v;
#pragma unroll 1
    for (int it = 0;; it++) {
        v = ld_rlx128(p.s->gate + 256 * i + 8 * lane);
        v.x ^= par; v.y ^= par; v.z ^= par; v.w ^= par;
        if (__all_sync(0xffffffffu, (v.x & v.y & v.z & v.w & 0x80008000u) == 0x80008000u)) break;
        if (it > (1 << 20)) give_up();
    }
    sts128(dst + (8 + 16 * i + (lane >> 1)) * 16, v.x, v.y, v.z, v.w);
}
__device__ __forceinline__ void store_rows(const CUtensorMap* m, uint32_t src, int col, int row) {
    asm volatile("cp.async.bulk.tensor.5d.global.shared::cta.bulk_group [%0, {%2, %3, %3, %3, %4}], [%1];" :: "l"(m), "r"(src), "r"(col), "r"(0), "r"(row) : "memory");
}

__device__ __forceinline__ void store_or_add(void* o, const uint32_t (&y)[4], uint32_t add) {
    asm volatile("{ .reg .pred p; setp.ne.u32 p, %5, 0; @!p st.global.v4.u32 [%0], {%1,%2,%3,%4}; @p red.relaxed.gpu.global.add.noftz.v4.bf16x2 [%0], {%1,%2,%3,%4}; }"
                 :: "l"(o), "r"(y[0]), "r"(y[1]), "r"(y[2]), "r"(y[3]), "r"(add) : "memory");
}

__device__ __forceinline__ void conv_aux(const Params& p, const CUtensorMap* mU, uint32_t sb, int aw, int lane, int bid, unsigned epoch) {
    const unsigned t0 = clock32();
    const int g = lane >> 2, t = lane & 3, mi = lane >> 3, r8 = lane & 7;
    const int rank = bid & 1, slab = bid >> 1;
    const uint32_t bar_y = sb + SC_MISC, bar_u = bar_y + 32, bar_v = bar_y + 40, bar_box = bar_y + 64 + 8 * aw, s_bm = bar_y + 128;
    if (lane == 0) {
        mbar_init(bar_box, 1); mbar_fence();
        mbar_expect(bar_box, 4096);
        if (UDELAY) until(t0, UDELAY);
        tma4d(sb + SC_RT + 4096 * aw, mU, 16 * slab, 0, 0, 16 * rank + 2 * aw, bar_box);
        mbar_init(bar_y + 8 * aw, aw < 4 ? 9 : aw == 5 ? 8 : 1); mbar_fence();
        if (aw < 5) mbar_expect(bar_y + 8 * aw, aw == 4 ? 16384 : 4096);
    }
    __syncwarp();
    asm volatile("barrier.cluster.arrive.relaxed.aligned;" ::: "memory");
    asm volatile("setmaxnreg.dec.sync.aligned.u32 88;");
    const uint32_t ut = sb + SC_UT + aw * UT_STRIDE;
    sts128(ut + (mi >> 1) * (SC_ST - SC_UT) + (mi & 1) * UT_HALF + r8 * 16, 0, 0, 0, 0);
    if (lane < 16) sts128(s_bm + lane * 16, 0, 0, 0, 0);
    {
        const uint32_t dst = sb + SC_UT + swap01(g) * UT_STRIDE + (8 + 64 * rank + 8 * aw + t) * 16;
        const uint32_t rdst = mapa(dst, rank ^ 1), rbar = mapa(bar_u, rank ^ 1);
        asm volatile("barrier.cluster.wait.acquire.aligned;" ::: "memory");
        mbar_wait(bar_box);
        if (aw == 0) TSTAMP(1);
        const uint32_t src = fresh(sb + SC_RT) + aw * 4096 + (8 * mi + 4 * (r8 & 1) + (r8 >> 1)) * 32 + ((rank ^ (r8 & 1)) << 4);
        uint32_t x[8][4];
#pragma unroll
        for (int i = 0; i < 4; i++) { ldsm4t(x[i], src + 1024 * i); ldsm4t(x[4 + i], (src ^ 16) + 1024 * i); }
        asm volatile("" :: "r"(x[0][0]), "r"(x[1][0]), "r"(x[2][0]), "r"(x[3][0]) : "memory");
#pragma unroll
        for (int i = 0; i < 4; i++) st_async128(rdst + (i & 1) * UT_HALF + 32 * (i & 2), x[4 + i][0], x[4 + i][1], x[4 + i][2], x[4 + i][3], rbar);
#pragma unroll
        for (int i = 0; i < 4; i++) sts128(dst + (i & 1) * UT_HALF + 32 * (i & 2), x[i][0], x[i][1], x[i][2], x[i][3]);
    }
    bar_sync(BC_AUX, 256);
    mbar_wait_cluster(bar_u);
    if (aw == 0) TSTAMP(2);
    {
        const uint32_t a = fresh(ut) + (mi & 1) * UT_HALF + (64 * (mi >> 1) + r8) * 16;
        uint4 v = lds128(a);
#pragma unroll
        for (int i = 1; i <= 8; i++) {
            const uint4 w = lds128(a + 128 * i);
            sts128(a + 128 * i + (SC_ST - SC_UT), badd2(v.x, w.x), badd2(v.y, w.y), badd2(v.z, w.z), badd2(v.w, w.w));
            v = w;
        }
    }
    bar_arrive(BC_S + aw, 64);
    if (aw == 0) TSTAMP(3);
    {
        uint32_t ws = sb + SC_UT + t * UT_STRIDE + (g + 6) * 16, wd = sb + SC_V + t * V_STRIDE + 64 * g, sw = 16 * (g & 2);
#pragma unroll 1
        for (int k = aw; k < 25; k += 8) {
            if (k - aw == 8) {
                bar_sync(BC_KG, 384);
                if (lane < 16) sts128(sb + SC_V + aw * V_STRIDE + lane * 16, 0, 0, 0, 0);
            }
            if (k == 24) { ws -= (g & 1) * 4 * UT_STRIDE + 16 * g; wd -= (g & 1) * 4 * V_STRIDE + 64 * g; sw = 0; }
            const int h = k >= 12, a = k - 12 * h;
            const uint32_t d = wd + h * 4 * V_STRIDE + 512 * a;
            window_task(fresh(ws) + h * 4 * UT_STRIDE + 128 * a, d + sw, d + (sw ^ 32), a < 8);
        }
    }
    if (aw == 0) TSTAMP(9);
    {
        if (aw >= 2) fetch_gates(p, aw, lane, epoch, sb + SC_GT + (lane & 1) * UT_HALF);
        __syncwarp();
        if (lane == 0) { mbar_arrive(bar_v); prefetch_map(mU + 4); }
        next_epoch(p, epoch);
        if (aw == 0) TSTAMP(4);
        if (aw == 7) {
            const int row = key_row(wait_sel(p, slab >> 1, r8, key_tag(epoch)));
            if (lane < 8) asm volatile("red.shared.or.b32 [%0], %1;" :: "r"(s_bm + (row >> 5) * 4), "r"(1u << (row & 31)) : "memory");
            TSTAMP(10);
        }
        bar_sync(BC_AUX, 256);
        const uint32_t src = sb + SC_RT + ((r8 >> 1) & 1) * Y_RS + (2 * mi + (r8 & 1)) * Y_CS + (2 * aw + (r8 >> 2)) * 16;
        const int L = 2 * aw + (t >> 1);
        const int row0 = 256 * rank + 128 * (g >> 2) + 32 * (L & 3) + 16 * (g & 1) + 8 * ((g >> 1) & 1) + (L >> 2);
        __nv_bfloat16* outp = p.out + (size_t)row0 * DM + 16 * slab + 8 * (t & 1);
        const uint32_t stg = sb + SC_ST + 4096 * aw, so = (g >> 1) * 256 + (t >> 1) * 64 + (g & 1) * 32 + (t & 1) * 16;
#pragma unroll 1
        for (int s = 1; s < 4; s++) {
            const uint32_t bm = lds32(fresh(s_bm) + (16 * s + (row0 >> 5)) * 4) >> (row0 & 31);
            const bool routed = __any_sync(0xffffffffu, bm & 0x11u);
            if (aw == s) mbar_wait_cluster(bar_y + 8 * s);
            bar_sync(BC_AUX, 256);
            const uint32_t sf = fresh(src) + 512 * s;
            uint32_t y[2][4];
            ldsm4t(y[0], sf); ldsm4t(y[1], sf + 256);
            if (routed) {
#pragma unroll
                for (int k = 0; k < 2; k++) store_or_add(outp + (size_t)(512 * s + 4 * k) * DM, y[k], bm & (1u << (4 * k)));
            } else {
                sts128(stg + so + 1024 * s, y[0][0], y[0][1], y[0][2], y[0][3]); sts128(stg + so + 1024 * s + 128, y[1][0], y[1][1], y[1][2], y[1][3]);
                asm volatile("fence.proxy.async.shared::cta;" ::: "memory");
                __syncwarp();
                if (lane == 0) store_rows(mU + 4, stg + 1024 * s, 16 * slab, 512 * s + 256 * rank + 64 * (aw & 1) + (aw >> 1));
            }
            if (aw == 0) TSTAMP(16 + s);
        }
        if (lane == 0) { asm volatile("cp.async.bulk.commit_group;" ::: "memory"); asm volatile("cp.async.bulk.wait_group.read 0;" ::: "memory"); }
        if (aw == 0) TFLUSH();
    }
}

__device__ __forceinline__ void publish_k(uint4* kp, const uint32_t (&w)[12], int n, unsigned epoch) {
#pragma unroll
    for (int i = 0; i < n; i++) asm volatile(PUBST ".v4.u32 [%0], {%1,%2,%3,%4};" :: "l"(kp + 32 * i), "r"(w[3 * i]), "r"(w[3 * i + 1]), "r"(w[3 * i + 2]), "r"(~epoch));
}
template <bool FULL>
__device__ __forceinline__ void k_tables(uint32_t kt, int lane, const uint32_t (&w)[12]) {
    const int g = lane >> 2, t = lane & 3, mi = lane >> 3, r8 = lane & 7;
    uint32_t x3 = w[7], re[4], rx[4];
#pragma unroll
    for (int i = 0; i < 4; i++) {
        re[i] = __shfl_sync(0xffffffffu, w[i], lane + 31);
        rx[i] = __shfl_sync(0xffffffffu, w[4 + i], lane + (i == 0 && lane == 29 ? 5 : 1 + 2 * t));
    }
    if (FULL) {
        asm volatile("stmatrix.sync.aligned.m8n8.x4.trans.shared.b16 [%0], {%1,%2,%3,%4};"
                     :: "r"(kt + (r8 < 4 ? (KT_D + 7) * 4 + 64 * r8 + 16 * mi : 716 * 4)), "r"(w[8]), "r"(w[9]), "r"(w[10]), "r"(w[11]) : "memory");
        if (lane == 2) {
            sts32(kt + (KT_C + 78) * 4, w[8] & 0xffffu);
            sts128(kt + (KT_T + 2) * 4, 0, w[8] & 0xffffu, __byte_perm(w[8], 0, 0x1010), w[8] << 16);
        }
        if (lane == 29) x3 = bsub2(x3, rx[0] & 0xffffu);
    }
#pragma unroll
    for (int i = 0; i < 4; i++) {
        sts64(kt + (16 + 64 * i) * 4 + 8 * lane, __byte_perm(w[i], lane ? re[i] : i ? re[i - 1] : 0, 0x5432), w[i]);
        const uint32_t x = i < 3 ? w[4 + i] : x3, aa = __byte_perm(x, 0, 0x3232);
        if (t < 2) sts128(kt + (272 + 64 * i + 8 * g + 4 * t) * 4, i == 0 && lane == 0 ? __byte_perm(x, re[3], 0x5432) : aa, aa, x,
                          __byte_perm(lane != 29 ? rx[i] : i < 3 ? rx[(i + 1) & 3] : FULL ? 0 : rx[0] << 16, x, 0x5432));
        else if (FULL) sts32(kt + (KT_C - 50 + 8 * i + 32 * t + g) * 4, x);
    }
}

__device__ __forceinline__ void conv_main(const Params& p, uint32_t sb, int warp, int lane0, int bid, unsigned epoch, uint32_t (&w)[12]) {
    asm volatile("setmaxnreg.inc.sync.aligned.u32 168;");
    const int lane = __shfl_sync(0xffffffffu, lane0, lane0);
    const int g = lane >> 2, t = lane & 3, mi = lane >> 3, r8 = lane & 7;
    const int rank = bid & 1;
    const uint32_t bar_y = sb + SC_MISC, bar_v = bar_y + 40;
    next_epoch(p, epoch);
    if (warp < 4) {
        asm volatile("" :: "r"(w[0]), "r"(w[2]), "r"(w[4]), "r"(w[6]), "r"(w[8]), "r"(w[10]) : "memory");
        bar_arrive(BC_KG, 384);
    } else {
        const uint4* src = p.s->kp + (8 * bid + warp) * 128 + lane0;
#pragma unroll 1
        for (int it = 0;; it++) {
            uint32_t bad = 0;
#pragma unroll
            for (int i = 0; i < 4; i++) { const uint4 v = ld_rlx128(src + 32 * i); w[3 * i] = v.x; w[3 * i + 1] = v.y; w[3 * i + 2] = v.z; bad |= v.w ^ ~epoch; }
            const bool ok = __all_sync(0xffffffffu, bad == 0);
            if (ok) break;
            if (it > (1 << 20)) give_up();
        }
    }
    if ((warp & 3) == 0) TSTAMP(5 + (warp >> 2));
    k_tables<true>(sb + SC_KT + warp * KT_BYTES, lane0, w);
    asm volatile("barrier.cluster.wait.acquire.aligned;" ::: "memory");
    bar_sync(BC_S + swap01(warp), 64);
    __syncwarp();
    if ((warp & 3) == 0) TSTAMP(7 + (warp >> 2));
    {
        const uint32_t ut = fresh(sb + SC_UT) + swap01(warp) * UT_STRIDE, kt = fresh(sb + SC_KT) + warp * KT_BYTES;
        uint32_t u1 = ut + (mi & 1) * UT_HALF + (8 + r8) * 16 + (mi >> 1) * 128;
        auto dup = [&](uint32_t v) { return v ^ p.zero; };
        uint32_t kp = kt + (16 + g - 2 * t) * 4;
        float acc[16][4];
        {
            const uint32_t c0 = lds32(kp + 2048), c1 = lds32(kp + 2080), c2 = lds32(kp + 2016), c3 = dup(c0);
            const uint32_t e0 = lds32(kp + (KT_T - 16) * 4), e1 = lds32(kp + (KT_T - 8) * 4), e2 = lds32(kp + (KT_T - 24) * 4), e3 = dup(e0);
            const uint32_t f0 = dup(e1), f1 = lds32(kp + KT_T * 4);
            const uint32_t uo = ut + UT_HALF + (7 + lane) * 16;
#pragma unroll
            for (int i = 0; i < 16; i++) { acc[i][0] = acc[i][1] = acc[i][2] = acc[i][3] = 0.f; }
#pragma unroll
            for (int mu = 0; mu < 8; mu += 4) {
                uint32_t b[4];
                ldsm4(b, uo + 128 * mu);
#pragma unroll
                for (int k = 0; k < 4; k++) mma_bf8(acc[mu + 8 + k], f0, f1, b[k]);
            }
#pragma unroll
            for (int mu = 0; mu < 12; mu += 2) {
                uint32_t b[4];
                ldsm4(b, u1 + 128 * mu);
                mma_bf(acc[mu + 4], c0, c1, c2, c3, b[0], b[1]);
                mma_bf(acc[mu + 5], c0, c1, c2, c3, b[2], b[3]);
                if (mu < 8) { mma_bf(acc[mu + 8], e0, e1, e2, e3, b[0], b[1]); mma_bf(acc[mu + 9], e0, e1, e2, e3, b[2], b[3]); }
            }
        }
        {
            float M[8][4];
#pragma unroll
            for (int i = 0; i < 8; i++) { M[i][0] = M[i][1] = M[i][2] = M[i][3] = 0.f; }
            uint32_t s[8][4], a3[4];
            const uint32_t kb = kp, ub = dup(u1), uc = u1 + (mi >> 1) * 128;
            auto frag = [&](uint32_t (&a)[4], uint32_t x) { a[0] = lds32(x); a[1] = lds32(x + 32); a[2] = lds32(x - 32); a[3] = dup(a[0]); };
            frag(a3, kp + 1536);
#pragma unroll
            for (int i = 1; i < 8; i++) ldsm4(s[i], u1 + (SC_ST - SC_UT) + 256 * i);
            __syncwarp();
            uint32_t ko = 0, uo = 0;
#pragma unroll 1
            for (uint32_t n = warp < 4 ? (bid < 48 ? PUBIT : PUBY) : 8;; n = bid < 48 ? 8 - PUBIT : 8 - PUBY) {
#pragma unroll 1
            for (; n; n--) {
                uint32_t a2[4], a1[4], a0[4], b[4][4];
                ko = fresh(ko); uo = fresh(uo);
                kp = kb + ko; u1 = ub + uo;
                const uint32_t up = uc + uo;
                ko += 64; uo -= 16;
                frag(a2, kp + 1024);
#pragma unroll
                for (int i = 1; i < 4; i++) ldsm4(b[i], up + 512 * i);
                asm("ldmatrix.sync.aligned.m8n8.x2.shared.b16 {%0,%1}, [%2];" : "=r"(b[0][2]), "=r"(b[0][3]) : "r"(up + 256));
                frag(a1, kp + 512); frag(a0, kp);
                kp += 64; u1 -= 16;
#pragma unroll
                for (int i = 1; i < 7; i++) mma_bf(acc[2 * i + 2], a3[0], a3[1], a3[2], a3[3], s[i][0], s[i][1]);
#pragma unroll
                for (int e = 0; e < 4; e++) a3[e] = bsub2(a2[e], a3[e]);
#pragma unroll
                for (int i = 1; i < 7; i++) mma_bf(acc[2 * i + 3], a2[0], a2[1], a2[2], a2[3], s[i][2], s[i][3]);
                ldsm4(s[1], u1 + (SC_ST - SC_UT) + 256);
#pragma unroll
                for (int i = 1; i < 7; i++) mma_bf(M[i + 1], a3[0], a3[1], a3[2], a3[3], b[i >> 1][2 * (i & 1)], b[i >> 1][2 * (i & 1) + 1]);
                frag(a3, kp + 1536);
#pragma unroll
                for (int i = 2; i < 8; i++) mma_bf(acc[2 * i], a1[0], a1[1], a1[2], a1[3], s[i][0], s[i][1]);
#pragma unroll
                for (int e = 0; e < 4; e++) a1[e] = bsub2(a0[e], a1[e]);
#pragma unroll
                for (int i = 2; i < 8; i++) { mma_bf(acc[2 * i + 1], a0[0], a0[1], a0[2], a0[3], s[i][2], s[i][3]); ldsm4(s[i], u1 + (SC_ST - SC_UT) + 256 * i); }
#pragma unroll
                for (int i = 2; i < 8; i++) mma_bf(M[i], a1[0], a1[1], a1[2], a1[3], b[i >> 1][2 * (i & 1)], b[i >> 1][2 * (i & 1) + 1]);
            }
            if (ko == 512) break;
            publish_k(p.s->kp + (8 * bid + warp) * 128 + lane, w, 3, epoch);
            }
            u1 = ub;
#pragma unroll
            for (int i = 2; i < 8; i++)
#pragma unroll
                for (int c = 0; c < 4; c++) { acc[2 * i][c] += M[i][c]; acc[2 * i + 1][c] -= M[i][c]; }
        }
        if ((warp & 3) == 0) TSTAMP(11 + (warp >> 2));
        mbar_wait(bar_v);
        const uint32_t vt = fresh(sb + SC_V) + swap01(warp) * V_STRIDE;
        const uint32_t g1 = fresh(u1) - ut + sb + SC_GT;
        const uint32_t ydst = sb + SC_RT + rank * Y_RS + warp * Y_CS + lane * 16;
        const uint32_t ydr = mapa(ydst, rank ^ 1), ybr = mapa(bar_y, rank ^ 1);
        auto stairs = [&](auto R) {
        uint32_t ug[2][2][4];
        auto ld_ug = [&](int i) { ldsm4t(ug[i & 1][0], u1 + 256 * i); ldsm4t(ug[i & 1][1], g1 + 256 * i); };
        auto ship = [&](int i) {
            const uint32_t (&u)[4] = ug[i & 1][0], (&gg)[4] = ug[i & 1][1];
            const uint32_t y0 = gmix(gg[0], acc[2 * i][0], acc[2 * i][1], u[0]), y1 = gmix(gg[1], acc[2 * i][2], acc[2 * i][3], u[1]);
            const uint32_t y2 = gmix(gg[2], acc[2 * i + 1][0], acc[2 * i + 1][1], u[2]), y3 = gmix(gg[3], acc[2 * i + 1][2], acc[2 * i + 1][3], u[3]);
            if ((i & 1) != R.value) st_async128(ydr + 512 * (i >> 1), y0, y1, y2, y3, ybr + 8 * (i >> 1));
            else asm volatile("{ .reg .pred q; setp.eq.u32 q, %6, 0; st.shared.v4.u32 [%0], {%2,%3,%4,%5}; bar.warp.sync 0xffffffff; @q mbarrier.arrive.shared::cta.b64 _, [%1]; }"
                              :: "r"(ydst + 512 * (i >> 1)), "r"(bar_y + 8 * (i >> 1)), "r"(y0), "r"(y1), "r"(y2), "r"(y3), "r"(lane) : "memory");
        };
        const uint32_t VD = vt + (VC_OFF - 400 - 16 * t) * 4 + (8 * g ^ 16 * (-t & 2)), VD2 = vt + (VC_OFF - 415 - 16 * t) * 4 + (8 * g ^ 16 * (~t & 2));
        uint2 bd[10];
        uint32_t x[2][4][4];
        auto ld4 = [&](uint32_t (&v)[4], int dl) { const uint2 w = lds64(VD + 256 * dl); v[0] = w.x; v[1] = w.y; v[2] = lds32(VD2 + 256 * dl); v[3] = dup(w.x); };
        auto mm4 = [&](const uint32_t (&v)[4], int dl) {
#pragma unroll
            for (int s = dl & 1; s < 10; s += 2) if ((dl + s) / 2 >= 4 && (dl + s) / 2 < 16) mma_bf(acc[(dl + s) / 2], v[0], v[1], v[2], v[3], bd[s].x, bd[s].y);
        };
        const uint32_t KE = kt + (KT_D + g + t) * 4, VE = vt + (VE_BASE - 912 - 16 * t) * 4 + (8 * g ^ 16 * (~t & 2));
        uint32_t b0[8], b1[8];
        auto ld8 = [&](uint32_t (&v)[4], int dl) { const uint2 w = lds64(VE + 512 * dl), z = lds64(VE + 512 * dl - 256); v[0] = w.x; v[1] = w.y; v[2] = z.x; v[3] = z.y; };
        auto mm8 = [&](const uint32_t (&v)[4], int dl, int lo, int hi) {
#pragma unroll
            for (int s = 0; s < 8; s++) if (dl + s >= lo && dl + s < hi) mma_bf(acc[dl + s], v[0], v[1], v[2], v[3], b0[s], b1[s]);
        };
        ld4(x[0][0], 6);
#pragma unroll
        for (int s = 0; s < 10; s++) bd[s] = lds64(kt + (KT_C + 2 * g + 2 * t + 8 * s) * 4);
        mm4(x[0][0], 6);
        uint32_t e[4][4];
#pragma unroll
        for (int k = 1; k < 6; k++) {
#pragma unroll
            for (int j = 0; j < 4; j++) ld4(x[k & 1][j], 4 * k + 3 + j);
            ld_ug(k + 1);
            if (k == 3) {
#pragma unroll
                for (int s = 0; s < 8; s++) { b0[s] = lds32(KE + 32 * s); b1[s] = lds32(KE + 32 * s + 16); }
            }
            if (k > 1) ship(k);
#pragma unroll
            for (int j = 0; j < 4; j++) {
                mm4(x[k & 1][j], 4 * k + 3 + j);
                if (k == 3) { uint32_t v[4], z[4]; ld8(e[j], 8 + j); ld8(v, 12 + j); ld4(z, 30 - j); mm8(v, 12 + j, 12, 16); mm8(e[j], 8 + j, 8, 12); mm4(z, 30 - j); }
                if (k == 5) { ld8(e[j], 8 + j + p.zero); mm8(e[j], 8 + j, 12, 16); }
            }
        }
        ld_ug(7);
        ship(7 - R.value); ship(6 + R.value);
        };
        if (rank) stairs(std::integral_constant<int, 1>()); else stairs(std::integral_constant<int, 0>());
        if ((warp & 3) == 0) TSTAMP(14 + (warp >> 2)); else TSTAMP(21 + warp);
    }
}

constexpr int SF_WD = 73728;
constexpr int SF_RED = 49152;
constexpr int MU_HALF = 640, MU_STRIDE = 1344, SM_RAW = 98304, SM_UT = SM_RAW + 16384, SM_G = SM_UT + 16 * MU_STRIDE, SM_Y = 196608, SM_KT = 138880, SM_KW = SM_G - 49152;
constexpr int SF_XS = 221184;
constexpr int SF_MISC = SF_XS + 8 * 1168;
constexpr int SF_KG = SF_MISC - 10 * KG_STAGE;
constexpr int SF_WR = SF_KG - 2304;
constexpr int FB_X = 64, FB_KDONE = 72, FB_KEYS = 80, FB_FREE = 88  , FB_W = 104, FB_D = FB_W + 72, FB_MU = FB_D + 96, FB_GU = FB_MU + 8, FB_MG = FB_MU + 16, FB_MT = FB_MU + 24, FS_PART = 512, FS_TOK = 896;
enum { BAR_F = 6, BAR_R = 7, BAR_GU = 8, BAR_RED = 9, BAR_R2 = 10, BAR_X = 11, BAR_G = 12  , BAR_M = 15 };
static_assert(SF_KG % 128 == 0 && NPRE <= 8 && SM_KT + 4 * 2112 <= 147456 && SM_G + MU_STRIDE <= SF_WR - 4 * 9216 && SM_KW + 6 * 2112 >= SM_RAW && SM_KW + 12 * 2112 <= SM_UT, "layout");

__device__ __forceinline__ int mini_ch0(int f) { return f < NW ? 16 * (f - 12) : 32 * (f - NW); }

__device__ __forceinline__ void ffn_front(const Params& p, const CUtensorMap* maps, uint32_t sb, int warp, int lane, int f, unsigned epoch) {
    const unsigned t0 = clock32();
    const int g = lane >> 2, t = lane & 3, mi = lane >> 3, r8 = lane & 7;
    const bool isx = f < NX;
    const int nrw = f < 8 ? 6 : 4, r0 = f < 8 ? 48 * f : 128 + 32 * f;
    const int rw = warp < 12 ? 13 - warp : warp ^ (warp < 14 ? 10 : 15);
    const uint32_t bar_row = sb + SF_MISC  , bar_x = bar_row + FB_X;
    const uint32_t s_part = bar_row + FS_PART  , s_tok = bar_row + FS_TOK  ;
    const uint32_t rows = sb + SF_WR - 9216 * (rw + 1);
    if (lane == 0) {
        mbar_init(bar_row + 8 * rw, 1); mbar_fence();
        if (rw < nrw) { mbar_expect(bar_row + 8 * rw, 9216); until(t0, RDELAY); bulk_g2s(rows, p.u + (size_t)(r0 + 8 * rw) * DM, 9216, bar_row + 8 * rw); }
        else if (rw >= 6) { mbar_expect(bar_row + 8 * rw, 1152); bulk_g2s(sb + SF_WR + (rw & 1) * 1152, (rw & 1) ? p.gatew : p.wr, 1152, bar_row + 8 * rw); }
        if (warp >= 10) {
#pragma unroll 1
            for (int i = warp - 10; i < 30; i += 6) mbar_init(bar_x + 8 * i, max(2 * i - 54, 1));
        }
        mbar_fence();
    }
    uint4* const kdst = p.s->keys + (lane >> 1) * 128 + 2 * f + (lane & 1);
    if (warp == 13) {
        stg128(kdst, 0, 0, 0, 0);
        sts32(s_part + 64 + lane * 4, 0);
        if (lane < 8 && isx && !(f & 1)) st_rlx32(&p.s->sel[32 * f + lane], 0);
    }
    __syncwarp();
    bar_sync(BAR_F, f < 12 ? 256 : 192);
    bar_arrive(0, NTHR);
    if (warp == 15) TSTAMP(1);

    if (warp == 12) {
        if (lane == 0) {
            prefetch_map(maps + 1); prefetch_map(maps + 2); prefetch_map(maps + (isx ? 3 : 5));
            unsigned tb = t0 + WDELAY;
            uint32_t dst = sb;
#pragma unroll 1
            for (int n = 0; n < 18; n++) {
                if (n == NPRE) { mbar_wait(bar_row + FB_KEYS); mbar_wait(bar_row + FB_KDONE); tb = clock32() + RESUME; }
                if (n == 8) dst += 49152;
                if (n == 12) { mbar_wait(bar_row + FB_FREE); dst = sb; }
                until(tb, 0); tb += WGAP;
                if (n == MPOS && !isx) {
                    mbar_expect(bar_row + FB_MU, f < NW ? 16384 : 32768);
                    tma4d(sb + SM_RAW, maps + 5, mini_ch0(f), 0, 0, 0, bar_row + FB_MU);
                    if (f >= NW) { tma4d(sb + SM_RAW - 49152, maps + 5, mini_ch0(f) + 16, 0, 0, 0, bar_row + FB_MU); break; }
                }
                if (f >= NW) continue;
                const uint32_t b = bar_row + FB_W + 8 * (n >> 1);
                if (!(n & 1)) mbar_expect(b, 24576);
                tma3d(dst, maps + 1 + (n & 1), 0, 64 * (n >> 1), 3 * f, b);
                dst += 12288;
            }
            TSTAMP(12);
            if (isx) {
#pragma unroll 1
                for (int i = 0; i < 12; i++) {
                    const int n = (0x987610ba5432ull >> (4 * i)) & 15;
                    until(tb, 0); tb += DGAP;
                    if (i == 6) mbar_wait(bar_row + FB_FREE + 8);
                    mbar_expect(bar_row + FB_D + 8 * n, 12288);
                    tma2d(sb + SF_WD + n * 12288, maps + 3, 32 * (f >> 1), 2304 * (f & 1) + 192 * n, bar_row + FB_D + 8 * n);
                }
                TSTAMP(13);
            }
        }
    } else if (warp == 13) {
        const uint32_t tag = key_tag(epoch), par = (epoch & 1) ? 0u : 0x8000u;
        bar_sync(BAR_R, 32 * (nrw + 1));
        TSTAMP(3);
        {
            const uint32_t sg = fresh(s_part) + 192 + lane * 4;
            const uint32_t gb = pack_bf16(sigmoidf_(rbf(__uint_as_float(lds32(sg)))), sigmoidf_(rbf(__uint_as_float(lds32(sg + 128))))) | par | (par << 16);
            asm volatile("st.relaxed.gpu.global.u16 [%0], %1;" :: "l"(p.s->gate + r0 + lane), "h"((unsigned short)gb) : "memory");
            if (nrw > 4 && lane < 16) asm volatile("st.relaxed.gpu.global.u16 [%0], %1;" :: "l"(p.s->gate + r0 + 32 + lane), "h"((unsigned short)(gb >> 16)) : "memory");
        }
        bar_sync(BAR_R2, 32 * (nrw + 1));
        {
            const uint4 v = lds128(fresh(s_tok) + (lane & 1) * 16);
            asm volatile("st.relaxed.gpu.global.v4.u32 [%0], {%1,%2,%3,%4};" :: "l"(kdst), "r"(v.x | tag), "r"(v.y | tag), "r"(v.z | tag), "r"(v.w | tag) : "memory");
        }
        TSTAMP(4);
        if (lane == 0) { mbar_arrive(bar_row + FB_KEYS); mbar_expect(bar_x, 8 * 1152); }
        if (f >= NW) return;
        uint32_t k[16];
        const uint4* src = p.s->keys + (f & 15) * 128 + lane;
#pragma unroll 1
        for (int it = 0;; it++) {
            uint32_t bad = 0;
#pragma unroll
            for (int i = 0; i < 4; i++) {
                const uint4 x = ld_rlx128(src + (i < 3 || lane < 24 ? 32 * i : 64));
                k[i] = x.x; k[4 + i] = x.y; k[8 + i] = x.z; k[12 + i] = x.w;
                bad |= x.x ^ tag;
            }
            const bool ok = __all_sync(0xffffffffu, (bad & 0xf800u) == 0);
            if (ok) break;
            if (it > (1 << 20)) give_up();
        }
        TSTAMP(5);
        uint32_t key = 0;
#pragma unroll 2
        for (int r = 0; r < 8; r++) {
            const uint32_t m = __reduce_max_sync(0xffffffffu, max(max(k[0], k[1]), max(k[2], k[3])));
#pragma unroll
            for (int i = 0; i < 4; i++) {
                const bool pop = k[i] == m;
                k[i] = pop ? k[4 + i] : k[i]; k[4 + i] = pop ? k[8 + i] : k[4 + i]; k[8 + i] = pop ? k[12 + i] : k[8 + i]; k[12 + i] = pop ? 0 : k[12 + i];
            }
            if (r8 == r) key = m;
        }
        const int row = key_row(key);
        sts32(s_tok + r8 * 8, row);
        bar_arrive(BAR_X, 160);
        TSTAMP(6);
        if (isx) {
            if (!(f & 1)) {
                __nv_bfloat16* o = p.out + (size_t)row * DM + 16 * f + 8 * mi;
                asm volatile("st.relaxed.gpu.global.v4.u32 [%0], {%1,%1,%1,%1};" :: "l"(o), "r"(0) : "memory");
                if (__any_sync(0xffffffffu, ld_rlx32(o) != 0)) give_up();
                if (lane < 8) st_rlx32(&p.s->sel[32 * f + lane], key);
            } else wait_sel(p, f >> 1, r8, tag);
            uint32_t gb;
#pragma unroll 1
            for (int it = 0;; it++) {
                asm volatile("ld.relaxed.gpu.global.u16 %0, [%1];" : "=r"(gb) : "l"(p.s->gate + row) : "memory");
                gb ^= par;
                if (!(gb & 0x8000u)) break;
                if (it > (1 << 20)) give_up();
            }
            const uint32_t rb = key ^ 0x80000000u, rv = (rb ^ (((int)rb >> 31) & 0x7fff0000u)) & 0xffff0000u;
            sts32(s_tok + r8 * 8 + 4, __float_as_uint(rbf(1.0f - bf_lo(gb)) * rbf(sigmoidf_(__uint_as_float(rv)))));
            __syncwarp();
            TSTAMP(7);
            bar_arrive(BAR_RED, 416);
        }
    } else {
        if (rw < nrw) {
            float c[3][4];
#pragma unroll
            for (int i = 0; i < 3; i++) { c[i][0] = c[i][1] = c[i][2] = c[i][3] = 0.f; }
            mbar_wait(bar_row + 48); mbar_wait(bar_row + 56);
            const uint32_t b = fresh(sb + SF_WR) + (g & 1) * 1152 + (g >> 2) * 64 + t * 16 + (g & 2) * 2;
            uint32_t w[18][2];
#pragma unroll
            for (int kb = 0; kb < 18; kb++) { const uint32_t o = ((kb & 1) ? b ^ 64 : b) + 128 * (kb >> 1); w[kb][0] = lds32(o); w[kb][1] = lds32(o + 8); }
            mbar_wait(bar_row + 8 * rw);
            if (warp == 15) TSTAMP(2);
            const uint32_t a = fresh(rows) + g * 1152 + (g & 1) * 64 + t * 16;
#pragma unroll
            for (int kb = 0; kb < 18; kb++) {
                const uint4 x = lds128(((kb & 1) ? a ^ 64 : a) + 128 * (kb >> 1));
                mma_bf(c[kb % 3], x.x, x.y, x.z, x.w, w[kb][0], w[kb][1]);
            }
            const float sr = c[0][0] + c[1][0] + c[2][0] + __shfl_down_sync(0xffffffffu, c[0][2] + c[1][2] + c[2][2], 1);
            const float sg = c[0][1] + c[1][1] + c[2][1] + __shfl_down_sync(0xffffffffu, c[0][3] + c[1][3] + c[2][3], 1);
            const uint32_t rb = pack_bf16(0.f, sr);
            if (t == 2 * (g & 1)) {
                sts32(s_part + (8 * rw + g) * 4, (rb ^ (((int)rb >> 31) & 0x7fff0000u) ^ 0x80000000u) | (uint32_t)(2047 - r0 - 8 * rw - g));
                sts32(s_part + 192 + (8 * rw + g) * 4, __float_as_uint(sg));
            }
            __syncwarp();
            bar_sync(BAR_R, 32 * (nrw + 1));
            const uint32_t sk = fresh(s_part), kk = lds32(sk + (8 * rw + r8) * 4);
            int n = 0;
#pragma unroll
            for (int i = 0; i < 3; i++) { const uint4 v = lds128(sk + mi * 48 + 16 * i); n += (v.x > kk) + (v.y > kk) + (v.z > kk) + (v.w > kk); }
            n += __shfl_xor_sync(0xffffffffu, n, 8); n += __shfl_xor_sync(0xffffffffu, n, 16);
            if (n < 8) sts32(s_tok + 4 * n, kk);
            __syncwarp();
            bar_arrive(BAR_R2, 32 * (nrw + 1));
        }
    }
}

__device__ __forceinline__ void ffn_work(const Params& p, uint32_t sb, int warp, int lane, int f, unsigned epoch) {
    const int g = lane >> 2, t = lane & 3, mi = lane >> 3, r8 = lane & 7;
    const bool isx = f < NX;
    const uint32_t bar_x = sb + SF_MISC + FB_X, bar_free = sb + SF_MISC + FB_FREE, bar_w = sb + SF_MISC + FB_W, bar_d = sb + SF_MISC + FB_D, s_tok = sb + SF_MISC + FS_TOK;
    uint32_t fr[24][4];
    auto pin = [&] {
#pragma unroll
        for (int i = 0; i < 24; i += 8) asm volatile("" :: "r"(fr[i][0]), "r"(fr[i + 1][0]), "r"(fr[i + 2][0]), "r"(fr[i + 3][0]), "r"(fr[i + 4][0]), "r"(fr[i + 5][0]), "r"(fr[i + 6][0]), "r"(fr[i + 7][0]) : "memory");
    };
    {
        const int j = warp >= 6, w = warp - 6 * j;
        float ag[2][4], au[2][4];
#pragma unroll
        for (int i = 0; i < 2; i++) { ag[i][0] = ag[i][1] = ag[i][2] = ag[i][3] = 0.f; au[i][0] = au[i][1] = au[i][2] = au[i][3] = 0.f; }
        const uint32_t wb = sb + (w >> 1) * 4096 + (r8 + 8 * (mi >> 1)) * 64 + (((2 * (w & 1) + (mi & 1)) ^ (r8 >> 1)) << 4);
        const uint32_t xb = sb + SF_XS + r8 * 1168 + mi * 16;
        auto load = [&](int i, int n, int place) {
            mbar_wait(bar_w + 8 * n);
            const uint32_t wk = fresh(wb) + place * 24576;
#pragma unroll
            for (int s = 0; s < 4; s++) { ldsm4t(fr[8 * i + s], wk + 1024 * s); ldsm4t(fr[8 * i + 4 + s], wk + 1024 * s + 12288); }
        };
        auto mul = [&](int i, uint32_t xk) {
            uint32_t x[2][4];
            ldsm4(x[0], xk); ldsm4(x[1], xk + 64);
#pragma unroll
            for (int s = 0; s < 4; s++) {
                const uint32_t (&a)[4] = fr[8 * i + s], (&b)[4] = fr[8 * i + 4 + s];
                mma_bf(ag[s & 1], a[0], a[1], a[2], a[3], x[s >> 1][2 * (s & 1)], x[s >> 1][2 * (s & 1) + 1]);
                mma_bf(au[s & 1], b[0], b[1], b[2], b[3], x[s >> 1][2 * (s & 1)], x[s >> 1][2 * (s & 1) + 1]);
            }
        };
#pragma unroll
        for (int i = 0; i < 3; i++) load(i, 3 * j + i, (i ? 5 : 3) * j + i);
        pin();
        bar_sync(BAR_G + j, 192);
        if (w == 0 && lane == 0) mbar_arrive(bar_free + 8 * j);
        if (warp < 4) {
            bar_sync(BAR_X, 160);
            const uint32_t rows = lds32(fresh(s_tok) + 8 * r8);
#pragma unroll 1
            for (int i = warp; i < 8; i += 4) {
                const int row = __shfl_sync(0xffffffffu, rows, i);
                if (lane == 0) bulk_g2s(sb + SF_XS + i * 1168, p.u + (size_t)row * DM, 1152, bar_x);
                __syncwarp();
            }
        }
        mbar_wait(bar_x);
        if (warp == 0) TSTAMP(8);
        {
            const uint32_t xk = fresh(xb) + 384 * j;
#pragma unroll
            for (int i = 0; i < 3; i++) { mul(i, (i ? fresh(xk) : xk) + 128 * i); if (i == 0) { asm volatile("" :: "f"(ag[0][0]), "f"(ag[1][0]), "f"(au[0][0]), "f"(au[1][0])); sts32(s_tok + 64, clock32()); } }
        }
#pragma unroll 1
        for (int n = 6 + j; n < 9; n += 2) { load(0, n, n - 6); mul(0, fresh(xb) + 128 * n); }
#pragma unroll
        for (int c = 0; c < 4; c++) { ag[0][c] += ag[1][c]; au[0][c] += au[1][c]; }
        if (j) {
            sts128(wb + 24576, __float_as_uint(ag[0][0]), __float_as_uint(ag[0][1]), __float_as_uint(ag[0][2]), __float_as_uint(ag[0][3]));
            sts128(wb + 25600, __float_as_uint(au[0][0]), __float_as_uint(au[0][1]), __float_as_uint(au[0][2]), __float_as_uint(au[0][3]));
        }
        bar_sync(BAR_GU, 384);
        if (warp == 6 && lane == 0) mbar_arrive(sb + SF_MISC + FB_GU);
        if (!j) {
            const uint32_t sf = fresh(wb);
            const uint4 g1 = lds128(sf + 24576), u1 = lds128(sf + 25600);
            const uint32_t gs[4] = {g1.x, g1.y, g1.z, g1.w}, us[4] = {u1.x, u1.y, u1.z, u1.w};
            if (warp == 0) TSTAMP(9);
            float h[4];
#pragma unroll
            for (int c = 0; c < 4; c++) {
                const float gv = rbf(ag[0][c] + __uint_as_float(gs[c]));
                h[c] = rbf(gv * sigmoidf_(gv)) * rbf(au[0][c] + __uint_as_float(us[c]));
            }
            uint32_t h0, h1;
            asm("movmatrix.sync.aligned.m8n8.trans.b16 %0, %1;" : "=r"(h0) : "r"(pack_bf16(h[0], h[1])));
            asm("movmatrix.sync.aligned.m8n8.trans.b16 %0, %1;" : "=r"(h1) : "r"(pack_bf16(h[2], h[3])));
            if (h0 == 0) h0 = 0x8000u;
            asm volatile("{ .reg .b64 v; mov.b64 v, {%1, %2}; st.relaxed.gpu.global.b64 [%0], v; }" :: "l"(p.s->h + ((epoch & 1) * 288 + 6 * f + warp) * 32 + lane), "r"(h0), "r"(h1) : "memory");
        }
        if (isx) {
            if (warp == 0) TSTAMP(10);
            const uint2* hsrc = p.s->h + ((epoch & 1) * 288 + 144 * (f & 1) + 12 * warp) * 32 + lane;
            uint2 hb[12];
            auto ldh = [&](int s) { asm volatile("ld.relaxed.gpu.global.v2.u32 {%0, %1}, [%2];" : "=r"(hb[s].x), "=r"(hb[s].y) : "l"(hsrc + 32 * s) : "memory"); };
#pragma unroll
            for (int s = 0; s < 12; s++) ldh(s);
#pragma unroll 1
            for (int it = 0;; it++) {
                bool again = false;
#pragma unroll
                for (int s = 0; s < 12; s += 2) if (__any_sync(0xffffffffu, min(hb[s].x, hb[s + 1].x) == 0)) { ldh(s); ldh(s + 1); again = true; }
                if (!again) break;
                if (it > (1 << 16)) give_up();
            }
            if (warp == 0) TSTAMP(11);
            mbar_wait(bar_d + 8 * warp);
            if (warp == 9) TSTAMP(14);
            float ad[2][2][4];
#pragma unroll
            for (int i = 0; i < 4; i++) { ad[i >> 1][i & 1][0] = ad[i >> 1][i & 1][1] = ad[i >> 1][i & 1][2] = ad[i >> 1][i & 1][3] = 0.f; }
            const uint32_t wd = fresh(sb) + SF_WD + warp * 12288 + (r8 + 8 * (mi >> 1)) * 64 + (((mi & 1) ^ (r8 >> 1)) << 4);
#pragma unroll
            for (int s = 0; s < 12; s++) {
                uint32_t a[4], b[4];
                ldsm4t(a, wd + 1024 * s); ldsm4t(b, (wd ^ 32) + 1024 * s);
                mma_bf(ad[0][s & 1], a[0], a[1], a[2], a[3], hb[s].x, hb[s].y);
                mma_bf(ad[1][s & 1], b[0], b[1], b[2], b[3], hb[s].x, hb[s].y);
            }
            const uint32_t rd = sb + SF_RED + warp * 1152 + (72 * t + g) * 4;
#pragma unroll
            for (int i = 0; i < 8; i++) sts32(rd + (i >> 2) * 64 + (i & 1) * 144 + ((i >> 1) & 1) * 32, __float_as_uint(ad[i >> 2][0][i & 3] + ad[i >> 2][1][i & 3]));
            bar_sync(BAR_RED, 416);
            if (warp < 4) {
                const int tid = 32 * warp + lane;
                const uint32_t rs = fresh(sb + SF_RED) + (tid >> 4) * 144 + (tid & 15) * 8;
                const uint2 tk = lds64(fresh(s_tok) + (tid >> 4) * 8);
                float x = 0.f, y = 0.f;
#pragma unroll
                for (int w = 0; w < 12; w++) { const uint2 v = lds64(rs + w * 1152); x += __uint_as_float(v.x); y += __uint_as_float(v.y); }
                asm volatile("red.relaxed.gpu.global.add.noftz.bf16x2 [%0], %1;" :: "l"(p.out + (size_t)tk.x * DM + 32 * (f >> 1) + 2 * (tid & 15)),
                             "r"(pack_bf16(x * __uint_as_float(tk.y), y * __uint_as_float(tk.y))) : "memory");
            }
            if (warp == 0) { TSTAMP(15); TFLUSH(); }
            asm volatile("exit;"); __builtin_unreachable();
        }
    }
}

__device__ __forceinline__ void fetch_k(const uint4* src, uint64_t (&v)[6], uint32_t a, uint32_t b) {
    asm volatile("{ .reg .pred p; setp.eq.u32 p, %7, %8; @p ld.relaxed.gpu.global.v2.u64 {%0,%1}, [%6]; @p ld.relaxed.gpu.global.v2.u64 {%2,%3}, [%6 + 512]; @p ld.relaxed.gpu.global.v2.u64 {%4,%5}, [%6 + 1024]; }"
                 : "+l"(v[0]), "+l"(v[1]), "+l"(v[2]), "+l"(v[3]), "+l"(v[4]), "+l"(v[5]) : "l"(src), "r"(a), "r"(b));
}
__device__ __forceinline__ void mini_conv(const Params& p, uint32_t sb, int warp, int lane, int f, unsigned epoch) {
    const int g = lane >> 2, t = lane & 3, mi = lane >> 3, r8 = lane & 7;
    const uint32_t fb = sb + SF_MISC, kt = sb + (warp < 12 ? SM_KW : SM_KT - 12 * 2112) + warp * 2112;
    const bool ism = f >= NW;
    const int ch0 = mini_ch0(f);
    uint32_t seq = 128;
    uint64_t v[6] = {};
    const uint4* src = p.s->kp + lane;
    auto hi = [&](int i) { return (uint32_t)(v[i] >> 32); };
    if (f >= (warp < 6 ? NW : NX)) {
    {
        const uint32_t c = 36 + (warp & 3) + 2 * (warp & 12), y = (uint32_t)(0x222e682000acaa26ull >> ((8 * warp) & 48)) & 0xffff;
        seq = ism ? 0x101 * c - 0x400 : (warp < 8 ? 0xa4 : y) + (warp & 1) * (warp & 2 && warp < 12 ? 1 : 0x101);
        if (!ism && warp >= 12) seq = warp < 14 ? seq >> 8 : seq + (0x12 + warp) * 0x10000;
        src += (ch0 + (seq & 31)) * 128;
    }
    if (warp >= 10 && (warp & 2)) {
        const int q = (warp & 1) + (warp < 12 ? 2 : 0), n0 = ism ? 2 * (q & 1) : q;
        const uint32_t ab = sb - (ism ? 49152 * (q >> 1) : 0);
        mbar_wait(fb + FB_MU);
        if (warp == 15) TSTAMP(16);
        uint32_t a = fresh(ab + SM_RAW) + n0 * 4096 + (8 * mi + 4 * (r8 & 1) + (r8 >> 1)) * 32 + ((r8 & 1) << 4), d = ab + SM_UT + g * MU_STRIDE + (8 + 8 * n0 + t) * 16;
        uint32_t z = ab + SM_UT + (4 * n0 + (mi >> 1)) * MU_STRIDE + (mi & 1) * MU_HALF + r8 * 16;
#pragma unroll 1
        for (int n = 0; n <= ism; n++, a += 4096, d += 128, z += 4 * MU_STRIDE) {
            uint32_t x[8][4];
#pragma unroll
            for (int i = 0; i < 8; i++) ldsm4t(x[i], (i & 4 ? a ^ 16 : a) + 1024 * (i & 3));
            sts128(z, 0, 0, 0, 0); sts128(z + 2 * MU_STRIDE, 0, 0, 0, 0);
#pragma unroll
            for (int i = 0; i < 8; i++) sts128(d + (i & 1) * MU_HALF + (i & 2) * 32 + (i & 4) * 2 * MU_STRIDE, x[i][0], x[i][1], x[i][2], x[i][3]);
        }
        __syncwarp();
        if (lane == 0) mbar_arrive(fb + FB_MT);
    }
    if ((warp >> 1) == 3) { fetch_gates(p, warp & 1, lane, epoch, sb + SM_G + (lane & 1) * MU_HALF); __syncwarp(); if (lane == 0) mbar_arrive(fb + FB_MG); }
    mbar_wait(fb + FB_KDONE);
    fetch_k(src, v, 0, 0);
    mbar_wait(fb + FB_KEYS); mbar_wait(fb + FB_MT);
    sts128(kt + t * 16, 0, 0, 0, 0);
    if (warp == TW) TSTAMP(17);
    }
    const uint32_t lo = (mi & 1) * MU_HALF + (8 + r8) * 16 + (mi >> 1) * 128;
#pragma unroll 1
    do {
        const int c = seq & 31;
        if (seq & 32) {
#pragma unroll 1
        for (int it = 0; !__all_sync(0xffffffffu, ((hi(1) ^ ~epoch) | (hi(3) ^ ~epoch) | (hi(5) ^ ~epoch) | ((uint32_t)v[5] & p.zero)) == 0); it++) {
            fetch_k(src, v, 0, 0);
            if (it > (1 << 20)) give_up();
        }
        if (warp == TW) TSTAMP(seq >> 8 ? 7 : 10);
        const uint32_t w[12] = {(uint32_t)v[0], hi(0), (uint32_t)v[1], (uint32_t)v[2], hi(2), (uint32_t)v[3], (uint32_t)v[4], hi(4), 0, 0, 0, 0};
        k_tables<false>(fresh(kt), fresh(lane), w);
        }
        __syncwarp();
        if (seq & 128) ffn_work(p, sb, warp, fresh(lane), f, epoch);
        if (!(seq & 32)) break;
        if (seq & 64) mbar_wait(fb + FB_GU);
        const uint32_t ab = sb - 49152 * (c >> 4), kb = fresh(kt) + (16 + g - 2 * t) * 4, ub = fresh(ab + SM_UT + (c & 15) * MU_STRIDE) + lo;
        const uint32_t yd = ab + SM_Y + (c & 15) * 1056 + (c & 8) * 8 + lane * 16;
        uint32_t kp = kb, u1 = ub;
        if (warp == TW && !(seq >> 8)) TSTAMP(13);
        seq >>= 8;
        src += ((int)(seq & 31) - c) * 128;
#pragma unroll
        for (int i = 0; i < 6; i++) v[i] = 0;
        const uint32_t kf = seq ? 128 * (ism ? FPOS : FPOSY) : 1;
        float acc[6][4];
#pragma unroll
        for (int i = 0; i < 6; i++) { acc[i][0] = acc[i][1] = acc[i][2] = acc[i][3] = 0.f; }
        uint32_t a[4][4], b[2][2][4];
        auto lda = [&](int j, int o) { const uint32_t x = kp + 64 * o + 512 * j; a[j][2] = o ? a[j][1] ^ p.zero : lds32(x - 32); a[j][0] = lds32(x); a[j][1] = lds32(x + 32); a[j][3] = a[j][0] ^ p.zero; };
        auto ldb = [&](int s, int o) { ldsm4(b[s][0], u1 - 16 * o); ldsm4(b[s][1], u1 + 256 - 16 * o); };
        ldb(0, 0);
#pragma unroll
        for (int j = 0; j < 4; j++) lda(j, 0);
#pragma unroll 1
        for (uint32_t ko = 0, uo = 0; ko != 512;) {
            ko = fresh(ko); uo = fresh(uo);
            kp = kb + ko; u1 = ub + uo;
            fetch_k(src, v, ko, kf);
            ko += 128; uo -= 32;
#pragma unroll
            for (int s = 0; s < 2; s++) {
                ldb(s ^ 1, s + 1);
#pragma unroll
                for (int i = 0; i < 4; i++) {
                    const int j = (i >> 1) + 2 * (i & 1);
#pragma unroll
                    for (int mu = 3 - j; mu >= 0; mu--) mma_bf(acc[j + mu + (j & 2)], a[j][0], a[j][1], a[j][2], a[j][3], b[s][mu >> 1][2 * (mu & 1)], b[s][mu >> 1][2 * (mu & 1) + 1]);
                    lda(j, s + 1);
                }
            }
        }
        if (warp == TW && !seq) TSTAMP(14);
        mbar_wait(fb + FB_MG);
#pragma unroll
        for (int e = 0; e < 4; e++) { acc[2][e] += acc[4][e]; acc[3][e] += acc[5][e]; }
        uint32_t ug[4][4];
#pragma unroll
        for (int i = 0; i < 2; i++) { ldsm4t(ug[i], ub + 256 * i); ldsm4t(ug[2 + i], fresh(sb + SM_G) + lo + 256 * i); }
#pragma unroll
        for (int i = 0; i < 2; i++) {
            const uint32_t (&u)[4] = ug[i], (&gg)[4] = ug[2 + i];
            sts128(yd + 512 * i, gmix(gg[0], acc[2 * i][0], acc[2 * i][1], u[0]), gmix(gg[1], acc[2 * i][2], acc[2 * i][3], u[1]),
                   gmix(gg[2], acc[2 * i + 1][0], acc[2 * i + 1][1], u[2]), gmix(gg[3], acc[2 * i + 1][2], acc[2 * i + 1][3], u[3]));
        }
        __syncwarp();
        if (warp == TW) TSTAMP(18 + (seq != 0));
    } while (seq);
    if (warp >= 12) TSTAMP(12 + warp);
}
__device__ __forceinline__ void mini_out(const Params& p, const CUtensorMap* maps, uint32_t sb, int warp, int lane, int f, unsigned epoch) {
    const int g = lane >> 2, t = lane & 3, mi = lane >> 3, r8 = lane & 7;
    const uint32_t fb = sb + SF_MISC;
    const bool ism = f >= NW;
    const int ch0 = mini_ch0(f);
    const int m = warp & 7, k = ism ? warp >> 3 : 0;
    const uint32_t list = fb + FS_PART + 32 * k, ab = sb - 49152 * k;
    uint32_t first = 1;
    if (lane == 0) asm volatile("atom.shared.exch.b32 %0, [%1], 1;" : "=r"(first) : "r"(list + 128) : "memory");
    if (!__all_sync(0xffffffffu, first)) { sts32(list + 4 * r8, key_row(wait_sel(p, ch0 >> 5, r8, key_tag(epoch)))); if (lane == 0) prefetch_map(maps + 4); }
    int i = ism ? 0 : warp >> 3, r0 = 256 * i + 64 * (m & 1) + (m >> 1);
    const int dr = 128 * (g >> 2) + 32 * (t >> 1) + 16 * (g & 1) + 8 * ((g >> 1) & 1);
    uint32_t y = ab + SM_Y + ((r8 >> 1) & 1) * 8512 + (2 * mi + (r8 & 1)) * 1056 + (2 * m + (r8 >> 2)) * 16 + 512 * i, stg = ab + SM_UT + 2048 * m + 1024 * i;
    const uint32_t so = (g >> 1) * 256 + (t >> 1) * 64 + (g & 1) * 32 + (t & 1) * 16;
    bar_sync(BAR_M - k, ism ? 256 : NTHR);
    const uint32_t rr = lds32(fresh(list) + 4 * r8);
    y = fresh(y);
#pragma unroll 1
    do {
        uint32_t x[2][4];
        ldsm4t(x[0], y); ldsm4t(x[1], y + 256);
        if (warp == 0 && x[0][0] != 0x12345) TSTAMP(28);
        if (__any_sync(0xffffffffu, (rr & ~0xbcu) == r0)) {
            uint32_t bm = 0;
#pragma unroll 1
            for (int n = 0; n < 8; n++) { const uint32_t d = __shfl_sync(0xffffffffu, rr, n) ^ (r0 + dr); bm |= d == 0 ? 1 : d == 4 ? 2 : 0; }
#pragma unroll
            for (int n = 0; n < 2; n++) store_or_add(p.out + (size_t)(r0 + dr + 4 * n) * DM + ch0 + 16 * k + 8 * (t & 1), x[n], bm & (1 << n));
        } else {
#pragma unroll
            for (int n = 0; n < 2; n++) sts128(stg + so + 128 * n, x[n][0], x[n][1], x[n][2], x[n][3]);
            asm volatile("fence.proxy.async.shared::cta;" ::: "memory");
            __syncwarp();
            if (lane == 0) store_rows(maps + 4, stg, ch0 + 16 * k, r0);
        }
        y += 512; stg += 1024; r0 += 256;
    } while (ism && r0 < 512);
    if (lane == 0) { asm volatile("cp.async.bulk.commit_group;" ::: "memory"); asm volatile("cp.async.bulk.wait_group.read 0;" ::: "memory"); }
    if (warp == 8) TSTAMP(11);
    if (warp == 0) { TSTAMP(15); TFLUSH(); }
}

constexpr int SMEM_BYTES = 232448;
static_assert(SF_MISC + 1024 <= 232192, "layout");

struct Maps { CUtensorMap m[6]; };

__global__ void __cluster_dims__(2, 1, 1) __launch_bounds__(NTHR, 1)
fused_kernel(const Params p, const __grid_constant__ Maps maps) {
    extern __shared__ __align__(1024) uint8_t smem_raw[];
    uint32_t q[8];
    {
        const int b = blockIdx.x, x = threadIdx.x, rc = 4 * b + max(b - 84, 0) - 288 + (x >> 6);
        const int cv = (b - NCONV) >> 31, ca = 8 * b + ((x >> 5) & 3), cb = 2 * rc - (rc & 3) + 4;
        const uint32_t ch = (ca & cv) | (cb & ~cv), o = NST * ch + 2 * ((x & 31) + ((x >> (cv & 2)) & 32));
        const bool c = x < (b < 84 ? 256 : 320);
        q[6] = ldg16_if(c, p.logdt + ch);
        q[2] = ldg32_if(c, p.Bre + o); q[3] = ldg32_if(c, p.Bim + o); q[4] = ldg32_if(c, p.Cre + o); q[5] = ldg32_if(c, p.Cim + o); q[0] = ldg32_if(c, p.Are + o); q[1] = ldg32_if(c, p.Aim + o);
        q[7] = ldg16_if(c, p.Dskip + ch);
    }
    const unsigned epoch = ld_rlx32(&p.s->epoch[blockIdx.x * 16 + (threadIdx.x >> 5)]);
    const uint32_t sb = __shfl_sync(0xffffffffu, smem_u32(smem_raw), 0);
    const int warp = __shfl_sync(0xffffffffu, threadIdx.x >> 5, 0), bid = __shfl_sync(0xffffffffu, blockIdx.x, 0);
    const int lane = __shfl_sync(0xffffffffu, threadIdx.x & 31, threadIdx.x);
    const bool conv = bid < NCONV;
    const int f = bid - NCONV;
    uint32_t w[12];
    if (warp < (f < 12 ? 8 : 10)) {
        const int half = conv ? warp >> 2 : warp & 1, pr = conv ? warp & 3 : warp >> 1;
        const int rc = 4 * f + max(f - 12, 0) + pr;
        const uint32_t stage = sb + (conv ? SC_KG : SF_KG) + warp * KG_STAGE;
        uint4* const kp = p.s->kp + (conv ? 8 * bid + pr : 2 * rc - (rc & 3) + 4) * 128 + lane;
        kgen(q, sb, half, stage, stage + (conv ? 4 : 1) * KG_STAGE, 1 + pr, lane, p.zero, w, [&] {
            sts128z_if(conv && lane < 20, sb + SC_KT + warp * KT_BYTES + lane * 16 + (lane < 4 ? 0 : lane < 14 ? 2048 : 2288));
            stg128(kp + 64 * half, 0, 0, 0, 0); stg128z_if(!conv || !half, kp + 64 * half + 32);
            stg128z_if((unsigned)f < NW && warp < 6, (uint4*)(p.s->h + ((lane >> 4) * 288 + 6 * f + warp) * 32) + (lane & 15));
            if (conv) asm volatile("barrier.cluster.arrive.relaxed.aligned;" ::: "memory");
        });
        if (conv) { conv_main(p, sb, warp, lane, bid, epoch, w); return; }
        {
            if (!half) publish_k(kp, w, 4, epoch);
            if (warp == 0) TSTAMP(22);
            if (warp == 2) TSTAMP(23);
            bar_sync(0, NTHR);
            if (warp == 0 && lane == 0) mbar_arrive(sb + SF_MISC + FB_KDONE);
        }
    } else if (conv) {
        conv_aux(p, maps.m, sb, warp - 8, lane, bid, epoch);
        return;
    } else {
        ffn_front(p, maps.m, sb, warp, lane, f, epoch);
    }
    converged();
    next_epoch(p, epoch);
    if (warp >= 12 && f < NX) return;
    mini_conv(p, sb, warp, __shfl_sync(0xffffffffu, lane, lane), f, epoch);
    mini_out(p, maps.m, sb, warp, lane, f, epoch);
}

typedef CUresult (*EncodeFn)(CUtensorMap*, CUtensorMapDataType, cuuint32_t, void*, const cuuint64_t*, const cuuint64_t*, const cuuint32_t*, const cuuint32_t*,
                             CUtensorMapInterleave, CUtensorMapSwizzle, CUtensorMapL2promotion, CUtensorMapFloatOOBfill);

void make_map(EncodeFn fn, CUtensorMap* m, const void* base, int rank, const cuuint64_t* dims, const cuuint64_t* strides, const cuuint32_t* box, CUtensorMapSwizzle sw) {
    const cuuint32_t es[5] = {1, 1, 1, 1, 1};
    fn(m, CU_TENSOR_MAP_DATA_TYPE_BFLOAT16, rank, (void*)base, dims, strides, box, es, CU_TENSOR_MAP_INTERLEAVE_NONE, sw,
       CU_TENSOR_MAP_L2_PROMOTION_NONE, CU_TENSOR_MAP_FLOAT_OOB_FILL_NONE);
}

}

extern "C" void kernel_launch(void* const* d_in, const int* in_sizes, int n_in, void* d_out, int out_size) {
    (void)in_sizes; (void)n_in; (void)out_size;
    static EncodeFn fn = nullptr;
    static void* scratch = nullptr;
    if (!fn) {
        void* ptr = nullptr; cudaDriverEntryPointQueryResult qr;
        cudaGetDriverEntryPoint("cuTensorMapEncodeTiled", &ptr, cudaEnableDefault, &qr);
        fn = (EncodeFn)ptr;
        cudaGetSymbolAddress(&scratch, g_scratch);
        cudaFuncSetAttribute(fused_kernel, cudaFuncAttributeMaxDynamicSharedMemorySize, SMEM_BYTES);
    }
    typedef const __nv_bfloat16* bp;
    Params p;
    p.u = (bp)d_in[0]; p.Are = (bp)d_in[1]; p.Aim = (bp)d_in[2]; p.Bre = (bp)d_in[3]; p.Bim = (bp)d_in[4]; p.Cre = (bp)d_in[5]; p.Cim = (bp)d_in[6];
    p.logdt = (bp)d_in[7]; p.Dskip = (bp)d_in[8]; p.wr = (bp)d_in[10]; p.gatew = (bp)d_in[14];
    p.out = (__nv_bfloat16*)d_out; p.s = (Scratch*)scratch; p.zero = 0;
    Maps maps;
    {
        const cuuint64_t dims[4] = {DM, 4, 16, 32}, strides[3] = {16 * DM * 2, DM * 2, 64 * DM * 2};
        const cuuint32_t box[4] = {16, 4, 16, 2};
        make_map(fn, &maps.m[0], d_in[0], 4, dims, strides, box, CU_TENSOR_MAP_SWIZZLE_32B);
        const cuuint32_t box2[4] = {16, 4, 16, 8};
        make_map(fn, &maps.m[5], d_in[0], 4, dims, strides, box2, CU_TENSOR_MAP_SWIZZLE_32B);
    }
    for (int i = 0; i < 2; i++) {
        const cuuint64_t dims[3] = {32, DM, FF / 32}, strides[2] = {FF * 2, 64};
        const cuuint32_t box[3] = {32, 64, 3};
        make_map(fn, &maps.m[1 + i], d_in[11 + i], 3, dims, strides, box, CU_TENSOR_MAP_SWIZZLE_64B);
    }
    {
        const cuuint64_t dims[2] = {DM, FF}, strides[1] = {DM * 2};
        const cuuint32_t box[2] = {32, 192};
        make_map(fn, &maps.m[3], d_in[13], 2, dims, strides, box, CU_TENSOR_MAP_SWIZZLE_64B);
    }
    {
        const cuuint64_t dims[5] = {DM, 4, 4, 2, L_SEQ}, strides[4] = {16 * DM * 2, 4 * DM * 2, 128 * DM * 2, DM * 2};
        const cuuint32_t box[5] = {16, 4, 4, 2, 1};
        make_map(fn, &maps.m[4], d_out, 5, dims, strides, box, CU_TENSOR_MAP_SWIZZLE_NONE);
    }
    fused_kernel<<<NCTA, NTHR, SMEM_BYTES>>>(p, maps);
}
```

```cpp
#include <cuda_runtime.h>
#include <cuda_bf16.h>
#include <cuda_fp16.h>
#include <cuda.h>
#include <stdint.h>
#include <type_traits>

#define RESUME 0
#define PUBIT 1
#define YSEQ 2
#define FPOS 4
#define PUBV 0
#define PUBST "st.relaxed.gpu.global"
#define HPOS 2
#define PUBY 0
#define MSTG 0
#define CSTG 0
#define TW 12
#define MPOS 1
#define UDELAY 0
#define RDELAY 900
#define WDELAY 2000
#define WGAP 310
#define NPRE 7
#define DGAP 260

namespace {

constexpr int DM = 576, NST = 128, FF = 4608, L_SEQ = 2048;
constexpr int NCONV = 72, NX = 36, NW = 48, NCTA = 132, NTHR = 512;

struct __align__(128) Scratch {
    unsigned epoch[NCTA * 16];
    uint4 keys[16 * 128];
    uint32_t sel[18 * 64];
    uint16_t gate[L_SEQ];
    uint2 h[2 * 288 * 32];
    uint4 kp[DM * 128];
};
__device__ Scratch g_scratch;
#define TFLUSH()
#define TSTAMP(i)

struct Params {
    const __nv_bfloat16 *Are, *Aim, *Bre, *Bim, *Cre, *Cim, *logdt, *Dskip, *u, *wr, *gatew;
    __nv_bfloat16* out;
    Scratch* s;
    uint32_t zero;
};

__device__ __forceinline__ void give_up() { asm volatile("trap; exit;"); __builtin_unreachable(); }
__device__ __forceinline__ void converged() { __syncwarp(); asm volatile("{ .reg .b32 t; mov.b32 t, 0; movmatrix.sync.aligned.m8n8.trans.b16 t, t; }" ::: "memory"); }
__device__ __forceinline__ uint32_t smem_u32(const void* p) { return (uint32_t)__cvta_generic_to_shared(p); }
__device__ __forceinline__ uint32_t pack_bf16(float lo, float hi) { uint32_t r; asm("cvt.rn.bf16x2.f32 %0, %1, %2;" : "=r"(r) : "f"(hi), "f"(lo)); return r; }
__device__ __forceinline__ uint32_t pack_f16(float lo, float hi) { uint32_t r; asm("cvt.rn.f16x2.f32 %0, %1, %2;" : "=r"(r) : "f"(hi), "f"(lo)); return r; }
__device__ __forceinline__ float bf_lo(uint32_t w) { return __uint_as_float(w << 16); }
__device__ __forceinline__ float bf_hi(uint32_t w) { return __uint_as_float(w & 0xffff0000u); }
__device__ __forceinline__ float rbf(float x) { return bf_lo(pack_bf16(x, 0.f)); }
__device__ __forceinline__ uint32_t badd2(uint32_t a, uint32_t b) { uint32_t r; asm("add.rn.bf16x2 %0, %1, %2;" : "=r"(r) : "r"(a), "r"(b)); return r; }
__device__ __forceinline__ uint32_t bsub2(uint32_t a, uint32_t b) { uint32_t r; asm("sub.rn.bf16x2 %0, %1, %2;" : "=r"(r) : "r"(a), "r"(b)); return r; }
__device__ __forceinline__ uint32_t gmix(uint32_t ng, float ny0, float ny1, uint32_t u) {
    uint32_t r; asm("{ .reg .b32 t; fma.rn.bf16x2 t, %1, %3, %3; fma.rn.bf16x2 %0, %1, %2, t; }" : "=r"(r) : "r"(ng), "r"(pack_bf16(ny0, ny1)), "r"(u)); return r;
}
__device__ __forceinline__ void mma_bf(float (&c)[4], uint32_t a0, uint32_t a1, uint32_t a2, uint32_t a3, uint32_t b0, uint32_t b1) {
    asm("mma.sync.aligned.m16n8k16.row.col.f32.bf16.bf16.f32 {%0,%1,%2,%3}, {%4,%5,%6,%7}, {%8,%9}, {%0,%1,%2,%3};"
        : "+f"(c[0]), "+f"(c[1]), "+f"(c[2]), "+f"(c[3]) : "r"(a0), "r"(a1), "r"(a2), "r"(a3), "r"(b0), "r"(b1));
}
__device__ __forceinline__ void mma_bf8(float (&c)[4], uint32_t a0, uint32_t a1, uint32_t b0) {
    asm("mma.sync.aligned.m16n8k8.row.col.f32.bf16.bf16.f32 {%0,%1,%2,%3}, {%4,%5}, {%6}, {%0,%1,%2,%3};"
        : "+f"(c[0]), "+f"(c[1]), "+f"(c[2]), "+f"(c[3]) : "r"(a0), "r"(a1), "r"(b0));
}
__device__ __forceinline__ void mma_h(float (&c)[4], uint32_t a0, uint32_t a1, uint32_t a2, uint32_t a3, uint32_t b0, uint32_t b1) {
    asm("mma.sync.aligned.m16n8k16.row.col.f32.f16.f16.f32 {%0,%1,%2,%3}, {%4,%5,%6,%7}, {%8,%9}, {%0,%1,%2,%3};"
        : "+f"(c[0]), "+f"(c[1]), "+f"(c[2]), "+f"(c[3]) : "r"(a0), "r"(a1), "r"(a2), "r"(a3), "r"(b0), "r"(b1));
}
__device__ __forceinline__ uint32_t fresh(uint32_t a) { asm volatile("" : "+r"(a) :: "memory"); return a; }
__device__ __forceinline__ uint32_t lds16(uint32_t a) { uint32_t v; asm("ld.shared.u16 %0, [%1];" : "=r"(v) : "r"(a)); return v; }
__device__ __forceinline__ uint32_t lds32(uint32_t a) { uint32_t v; asm("ld.shared.u32 %0, [%1];" : "=r"(v) : "r"(a)); return v; }
__device__ __forceinline__ uint2 lds64(uint32_t a) { uint2 v; asm("ld.shared.v2.u32 {%0,%1}, [%2];" : "=r"(v.x), "=r"(v.y) : "r"(a)); return v; }
__device__ __forceinline__ uint4 lds128(uint32_t a) { uint4 v; asm("ld.shared.v4.u32 {%0,%1,%2,%3}, [%4];" : "=r"(v.x), "=r"(v.y), "=r"(v.z), "=r"(v.w) : "r"(a)); return v; }
__device__ __forceinline__ uint4 lds128v(uint32_t a) { uint4 v; asm volatile("ld.shared.v4.u32 {%0,%1,%2,%3}, [%4];" : "=r"(v.x), "=r"(v.y), "=r"(v.z), "=r"(v.w) : "r"(a) : "memory"); return v; }
__device__ __forceinline__ void ldsm4(uint32_t (&r)[4], uint32_t a) {
    asm("ldmatrix.sync.aligned.m8n8.x4.shared.b16 {%0,%1,%2,%3}, [%4];" : "=r"(r[0]), "=r"(r[1]), "=r"(r[2]), "=r"(r[3]) : "r"(a));
}
__device__ __forceinline__ void ldsm4t(uint32_t (&r)[4], uint32_t a) {
    asm("ldmatrix.sync.aligned.m8n8.x4.trans.shared.b16 {%0,%1,%2,%3}, [%4];" : "=r"(r[0]), "=r"(r[1]), "=r"(r[2]), "=r"(r[3]) : "r"(a));
}
__device__ __forceinline__ void sts16(uint32_t a, uint32_t v) { asm volatile("st.shared.u16 [%0], %1;" :: "r"(a), "h"((unsigned short)v) : "memory"); }
__device__ __forceinline__ void sts32(uint32_t a, uint32_t v) { asm volatile("st.shared.u32 [%0], %1;" :: "r"(a), "r"(v) : "memory"); }
__device__ __forceinline__ void sts64(uint32_t a, uint32_t x, uint32_t y) { asm volatile("st.shared.v2.u32 [%0], {%1,%2};" :: "r"(a), "r"(x), "r"(y) : "memory"); }
__device__ __forceinline__ void sts128(uint32_t a, uint32_t x, uint32_t y, uint32_t z, uint32_t w) {
    asm volatile("st.shared.v4.u32 [%0], {%1,%2,%3,%4};" :: "r"(a), "r"(x), "r"(y), "r"(z), "r"(w) : "memory");
}
__device__ __forceinline__ void st_async128(uint32_t a, uint32_t x, uint32_t y, uint32_t z, uint32_t w, uint32_t bar) {
    asm volatile("st.async.weak.shared::cluster.mbarrier::complete_tx::bytes.v4.b32 [%0], {%1,%2,%3,%4}, [%5];" :: "r"(a), "r"(x), "r"(y), "r"(z), "r"(w), "r"(bar) : "memory");
}
__device__ __forceinline__ void mbar_init(uint32_t b, uint32_t cnt) { asm volatile("mbarrier.init.shared::cta.b64 [%0], %1;" :: "r"(b), "r"(cnt) : "memory"); }
__device__ __forceinline__ void mbar_fence() { asm volatile("fence.mbarrier_init.release.cluster;" ::: "memory"); }
__device__ __forceinline__ void mbar_expect(uint32_t b, uint32_t bytes) { asm volatile("mbarrier.arrive.expect_tx.shared::cta.b64 _, [%0], %1;" :: "r"(b), "r"(bytes) : "memory"); }
__device__ __forceinline__ void mbar_arrive(uint32_t b) { asm volatile("mbarrier.arrive.shared::cta.b64 _, [%0];" :: "r"(b) : "memory"); }
#define CHINT ""
#define HINT ""
__device__ __forceinline__ void mbar_wait(uint32_t b, uint32_t parity = 0) {
    asm volatile("{ .reg .pred p; .reg .u32 n; mov.u32 n, 0;\n"
                 "LW: mbarrier.try_wait.parity.shared::cta.b64 p, [%0], %1" HINT "; @p bra LD; add.u32 n, n, 1; setp.lt.u32 p, n, 65536; @p bra LW; trap;\n"
                 "LD: }" :: "r"(b), "r"(parity) : "memory");
}
__device__ __forceinline__ void mbar_wait_cluster(uint32_t b) {
    asm volatile("{ .reg .pred p; .reg .u32 n; mov.u32 n, 0;\n"
                 "LW: mbarrier.try_wait.parity.acquire.cluster.shared::cta.b64 p, [%0], 0" CHINT "; @p bra LD; add.u32 n, n, 1; setp.lt.u32 p, n, 65536; @p bra LW; trap;\n"
                 "LD: }" :: "r"(b) : "memory");
}
__device__ __forceinline__ void tma2d(uint32_t dst, const CUtensorMap* m, int c0, int c1, uint32_t bar) {
    asm volatile("cp.async.bulk.tensor.2d.shared::cluster.global.mbarrier::complete_tx::bytes [%0], [%1, {%3, %4}], [%2];"
                 :: "r"(dst), "l"(m), "r"(bar), "r"(c0), "r"(c1) : "memory");
}
__device__ __forceinline__ void tma3d(uint32_t dst, const CUtensorMap* m, int c0, int c1, int c2, uint32_t bar) {
    asm volatile("cp.async.bulk.tensor.3d.shared::cluster.global.mbarrier::complete_tx::bytes [%0], [%1, {%3, %4, %5}], [%2];"
                 :: "r"(dst), "l"(m), "r"(bar), "r"(c0), "r"(c1), "r"(c2) : "memory");
}
__device__ __forceinline__ void tma4d(uint32_t dst, const CUtensorMap* m, int c0, int c1, int c2, int c3, uint32_t bar) {
    asm volatile("cp.async.bulk.tensor.4d.shared::cluster.global.mbarrier::complete_tx::bytes [%0], [%1, {%3, %4, %5, %6}], [%2];"
                 :: "r"(dst), "l"(m), "r"(bar), "r"(c0), "r"(c1), "r"(c2), "r"(c3) : "memory");
}
__device__ __forceinline__ void bulk_g2s(uint32_t dst, const void* src, uint32_t bytes, uint32_t bar) {
    asm volatile("cp.async.bulk.shared::cluster.global.mbarrier::complete_tx::bytes [%0], [%1], %2, [%3];"
                 :: "r"(dst), "l"(src), "r"(bytes), "r"(bar) : "memory");
}
__device__ __forceinline__ uint32_t mapa(uint32_t a, uint32_t rank) { uint32_t r; asm("mapa.shared::cluster.u32 %0, %1, %2;" : "=r"(r) : "r"(a), "r"(rank)); return r; }
__device__ __forceinline__ void prefetch_map(const CUtensorMap* m) { asm volatile("prefetch.tensormap [%0];" :: "l"(m) : "memory"); }
__device__ __forceinline__ void bar_sync(int id, int n) { asm volatile("bar.sync %0, %1;" :: "r"(id), "r"(n) : "memory"); }
__device__ __forceinline__ void bar_arrive(int id, int n) { asm volatile("bar.arrive %0, %1;" :: "r"(id), "r"(n) : "memory"); }
__device__ __forceinline__ uint32_t ldg16_if(bool c, const void* p) { uint32_t v; asm volatile("{ .reg .pred p; setp.ne.u32 p, %2, 0; @p ld.global.nc.u16 %0, [%1]; }" : "=r"(v) : "l"(p), "r"((uint32_t)c)); return v; }
__device__ __forceinline__ uint32_t ldg32_if(bool c, const void* p) { uint32_t v; asm volatile("{ .reg .pred p; setp.ne.u32 p, %2, 0; @p ld.global.nc.u32 %0, [%1]; }" : "=r"(v) : "l"(p), "r"((uint32_t)c)); return v; }
__device__ __forceinline__ uint32_t ld_rlx32(const void* p) { uint32_t v; asm volatile("ld.relaxed.gpu.global.u32 %0, [%1];" : "=r"(v) : "l"(p) : "memory"); return v; }
__device__ __forceinline__ uint4 ld_rlx128(const void* p) {
    uint4 v; asm volatile("ld.relaxed.gpu.global.v4.u32 {%0,%1,%2,%3}, [%4];" : "=r"(v.x), "=r"(v.y), "=r"(v.z), "=r"(v.w) : "l"(p) : "memory"); return v;
}
__device__ __forceinline__ void st_rlx32(void* p, uint32_t v) { asm volatile("st.relaxed.gpu.global.u32 [%0], %1;" :: "l"(p), "r"(v) : "memory"); }
__device__ __forceinline__ void stg128(void* p, uint32_t x, uint32_t y, uint32_t z, uint32_t w) {
    asm volatile("st.global.v4.u32 [%0], {%1,%2,%3,%4};" :: "l"(p), "r"(x), "r"(y), "r"(z), "r"(w) : "memory");
}
__device__ __forceinline__ void next_epoch(const Params& p, unsigned e) { if ((threadIdx.x & 31) == 0) p.s->epoch[blockIdx.x * 16 + (threadIdx.x >> 5)] = e + 1; }
__device__ __forceinline__ void sts128z_if(bool c, uint32_t a) { asm volatile("{ .reg .pred p; setp.ne.u32 p, %1, 0; @p st.shared.v4.u32 [%0], {%2,%2,%2,%2}; }" :: "r"(a), "r"((uint32_t)c), "r"(0) : "memory"); }
__device__ __forceinline__ void stg128z_if(bool c, void* a) { asm volatile("{ .reg .pred p; setp.ne.u32 p, %1, 0; @p st.global.v4.u32 [%0], {%2,%2,%2,%2}; }" :: "l"(a), "r"((uint32_t)c), "r"(0) : "memory"); }
__device__ __forceinline__ unsigned clock32() { unsigned c; asm volatile("mov.u32 %0, %clock;" : "=r"(c) :: "memory"); return c; }
__device__ __forceinline__ void until(unsigned t0, int c) { while ((int)(clock32() - t0) < c) { } }
__device__ __forceinline__ float sigmoidf_(float x) { return __fdividef(1.0f, 1.0f + __expf(-x)); }
__device__ __forceinline__ uint32_t key_tag(unsigned epoch) { return ((epoch & 15u) | 16u) << 11; }
__device__ __forceinline__ int key_row(uint32_t key) { return 2047 - (int)(key & 2047u); }
__device__ __forceinline__ uint32_t wait_sel(const Params& p, int s32, int r8, uint32_t tag) {
    uint32_t k;
#pragma unroll 1
    for (int it = 0;; it++) {
        k = ld_rlx32(&p.s->sel[s32 * 64 + r8]);
        if (__all_sync(0xffffffffu, (k & 0xf800u) == tag)) break;
        if (it > (1 << 20)) give_up();
    }
    return k;
}

struct cplx { float re, im; };
__device__ __forceinline__ cplx csq(cplx a) { cplx r; r.re = a.re * a.re - a.im * a.im; r.im = (a.re * a.im) * 2.f; return r; }
__device__ __forceinline__ cplx cexpk(float ar, float ai, float k) {
    float mag, s, c;
    asm("ex2.approx.ftz.f32 %0, %1;" : "=f"(mag) : "f"(ar * (k * 1.4426950408889634f)));
    const float r = ai * k;
    asm("sin.approx.ftz.f32 %0, %1;" : "=f"(s) : "f"(r));
    asm("cos.approx.ftz.f32 %0, %1;" : "=f"(c) : "f"(r));
    cplx o; o.re = mag * c; o.im = mag * s; return o;
}
struct h2c { uint32_t re, im; };
__device__ __forceinline__ h2c cmul_cd(h2c v, __half2 c, __half2 d) {
    const __half2 r = *(const __half2*)&v.re, i = *(const __half2*)&v.im;
    const __half2 x = __hfma2(__hneg2(i), d, __hmul2(r, c)), y = __hfma2(i, c, __hmul2(r, d));
    h2c o; o.re = *(const uint32_t*)&x; o.im = *(const uint32_t*)&y; return o;
}
__device__ __forceinline__ h2c cmul_s(h2c v, uint32_t s) { const __half2 h = *(const __half2*)&s; return cmul_cd(v, __low2half2(h), __high2half2(h)); }
__device__ __forceinline__ h2c cmul_sc(h2c v, uint32_t s) {
    const __half2 h = *(const __half2*)&s, c = __low2half2(h), d = __high2half2(h), r = *(const __half2*)&v.re, i = *(const __half2*)&v.im;
    const __half2 x = __hfma2(i, d, __hmul2(r, c)), y = __hfma2(__hneg2(r), d, __hmul2(i, c));
    h2c o; o.re = *(const uint32_t*)&x; o.im = *(const uint32_t*)&y; return o;
}
__device__ __forceinline__ h2c cmul_vc(h2c v, uint32_t s) {
    const __half2 h = *(const __half2*)&s, c = __low2half2(h), d = __high2half2(h), r = *(const __half2*)&v.re, i = *(const __half2*)&v.im;
    const __half2 x = __hfma2(i, d, __hmul2(r, c)), y = __hfma2(__hneg2(i), c, __hmul2(r, d));
    h2c o; o.re = *(const uint32_t*)&x; o.im = *(const uint32_t*)&y; return o;
}

constexpr int UT_HALF = 2240, UT_STRIDE = 4448;
constexpr int KT_T = 542, KT_C = 552, KT_D = 645, KT_BYTES = 720 * 4;
constexpr int VC_OFF = 80, VE_BASE = 1616;
constexpr int V_STRIDE = (1616 + 1024) * 4 + 80;
constexpr int KG_STAGE = 5248;
constexpr int Y_CS = 2080, Y_RS = 8 * Y_CS + 64;

constexpr int SC_RT = 0;
constexpr int SC_UT = 33408;
constexpr int SC_ST = SC_UT + 8 * UT_STRIDE;
constexpr int SC_KT = SC_ST + 8 * UT_STRIDE;
constexpr int SC_GT = SC_KT + 8 * KT_BYTES;
constexpr int SC_V = SC_GT + UT_STRIDE;
constexpr int SC_KG = SC_V + 4 * V_STRIDE;
constexpr int SC_MISC = SC_V + 8 * V_STRIDE;
static_assert(V_STRIDE % 128 == 16 && 8 * KG_STAGE <= 4 * V_STRIDE && 2 * Y_RS <= SC_UT && SC_UT % 128 == 0 && SC_ST % 128 == 0, "layout");
static_assert(SC_MISC % 16 == 0 && SC_MISC + 512 <= 232192, "layout");

__device__ __forceinline__ void window_task(uint32_t src, uint32_t d0, uint32_t d1, bool withE) {
    float S[35];
    {
        uint32_t w[20];
#pragma unroll
        for (int i = 0; i < 5; i++) {
            const uint4 v = lds128(src + ((i & 1) ? 0 : UT_HALF) + ((i + 1) >> 1) * 16);
            w[4 * i] = v.x; w[4 * i + 1] = v.y; w[4 * i + 2] = v.z; w[4 * i + 3] = v.w;
        }
        float s = 0.f; S[2] = 0.f;
#pragma unroll
        for (int i = 3; i < 26; i++) { s += (i & 1) ? bf_hi(w[i >> 1]) : bf_lo(w[i >> 1]); S[i] = s; }
#pragma unroll
        for (int i = 0; i < 8; i += 2)
            sts128((i & 4 ? d1 : d0) + (VC_OFF - 16) * 4 + 8 * (i & 2), pack_bf16(S[10 + i] - S[5 + i], S[5 + i] - S[2 + i]), pack_bf16(S[18 + i] - S[13 + i], S[13 + i] - S[10 + i]),
                   pack_bf16(S[11 + i] - S[6 + i], S[6 + i] - S[3 + i]), pack_bf16(S[19 + i] - S[14 + i], S[14 + i] - S[11 + i]));
        if (withE) {
#pragma unroll
            for (int i = 26; i < 35; i++) { s += (i & 1) ? bf_hi(w[i >> 1]) : bf_lo(w[i >> 1]); S[i] = s; }
#pragma unroll
            for (int i = 0; i < 8; i += 2)
                sts128((i & 4 ? d1 : d0) + VE_BASE * 4 + 8 * (i & 2), pack_bf16(S[19 + i] - S[12 + i], S[12 + i] - S[3 + i]), pack_bf16(S[27 + i] - S[20 + i], S[20 + i] - S[11 + i]),
                       pack_bf16(S[20 + i] - S[13 + i], S[13 + i] - S[4 + i]), pack_bf16(S[28 + i] - S[21 + i], S[21 + i] - S[12 + i]));
        }
    }
}

template <class F>
__device__ __forceinline__ void kgen(const uint32_t (&q)[8], uint32_t sb, int half, uint32_t stage, uint32_t pstage, int barid, int lane, uint32_t zero, uint32_t (&w)[12], F shadow) {
    const int t = lane & 3, mi = lane >> 3, r8 = lane & 7;
    {
        const uint32_t pAr = q[0], pAi = q[1], pBr = q[2], pBi = q[3], pCr = q[4], pCi = q[5], pDt = q[6], pD = q[7];
        const uint32_t wb = fresh(stage + lane * 16), za = fresh(stage + 5120 + ((lane >> 1) & 3) * 16 + mi * 4 + (lane & 1) * 2), zr = fresh(stage + 5120 + t * 16);
        const uint32_t oA = fresh(stage + (mi & 1) * 1024 + (mi >> 1) * 512 + r8 * 16), oB = fresh(stage + 2048 + mi * 512 + r8 * 16), oC = fresh(stage + 4096 + (mi & 1) * 512 + (mi >> 1) * 128 + r8 * 16);
        float acc[6][4];
#pragma unroll
        for (int a = 0; a < 6; a++) { acc[a][0] = acc[a][1] = acc[a][2] = acc[a][3] = 0.f; asm volatile("" : "+f"(acc[a][0]), "+f"(acc[a][1]), "+f"(acc[a][2]), "+f"(acc[a][3])); }
        shadow();
        sts32(zr, clock32());
        const float dt = rbf(__expf(bf_lo(pDt)));
        float ar = dt * bf_lo(pAr), ai = dt * bf_lo(pAi), ar1 = dt * bf_hi(pAr), ai1 = dt * bf_hi(pAi);
        float wr, wi, wr1, wi1;
        { const float br = dt * bf_lo(pBr), bi = dt * bf_lo(pBi), cr = bf_lo(pCr), ci = bf_lo(pCi); wr = cr * br - ci * bi; wi = cr * bi + ci * br; }
        { const float br = dt * bf_hi(pBr), bi = dt * bf_hi(pBi), cr = bf_hi(pCr), ci = bf_hi(pCi); wr1 = cr * br - ci * bi; wi1 = cr * bi + ci * br; }
        const uint32_t ex = max(__reduce_max_sync(0xffffffffu, __float_as_uint(fmaxf(fmaxf(fabsf(wr), fabsf(wi)), fmaxf(fabsf(wr1), fabsf(wi1))))) >> 23, 14u);
        const float scl = __uint_as_float((267u - ex) << 23);
        uint32_t W = pack_f16(wr * scl, wi * -scl);
        const uint32_t W1 = pack_f16(wr1 * scl, wi1 * -scl);
        if (threadIdx.x < 32) TSTAMP(20);

#pragma unroll 1
        for (int r = 0; r < 2; r++) {
            const cplx z1 = cexpk(ar, ai, 1.f), z64 = cexpk(ar, ai, 64.f);
            const cplx z2 = csq(z1), z4 = csq(z2), z8 = csq(z4), z16 = csq(z8), z32 = csq(z16);
            const cplx z128 = csq(z64), z256 = csq(z128), z512 = csq(z256);
            auto put = [&](int grp, h2c a, h2c b, h2c c, h2c d) { sts128(wb + grp * 1024, a.re, b.re, c.re, d.re); sts128(wb + grp * 1024 + 512, a.im, b.im, c.im, d.im); };
            {
                const uint32_t s4 = pack_f16(z4.re, z4.im), s256 = pack_f16(z256.re, z256.im), s512 = pack_f16(z512.re, z512.im);
                auto mix = [](h2c a, h2c b, uint32_t sel) { return h2c{__byte_perm(a.re, b.re, sel), __byte_perm(a.im, b.im, sel)}; };
                const h2c c10 = cmul_vc(h2c{pack_f16(z1.re, 1.f), pack_f16(z1.im, 0.f)}, W), c32 = cmul_sc(c10, pack_f16(z2.re, z2.im)), c54 = cmul_sc(c10, s4);
                put(2, c10, c32, c54, cmul_sc(c32, s4));
                const h2c d20 = cmul_sc(mix(c32, c10, 0x7632), s256), e04 = cmul_sc(mix(c10, c54, 0x7632), s512), f04 = cmul_sc(e04, s256);
                put(3, d20, cmul_sc(d20, s4), e04, f04);
                const h2c ef = mix(e04, f04, 0x5410), gh = cmul_sc(ef, s512), g8 = cmul_sc(gh, pack_f16(z8.re, z8.im));
                put(4, g8, cmul_sc(g8, s512), gh, ef);
            }
            {
                const uint32_t s32 = pack_f16(z32.re, z32.im), s64 = pack_f16(z64.re, z64.im), s128 = pack_f16(z128.re, z128.im);
                const h2c p0 = {pack_f16(1.f, z8.re), pack_f16(0.f, z8.im)}, p1 = cmul_s(p0, pack_f16(z16.re, z16.im)), p2 = cmul_s(p0, s32), p3 = cmul_s(p1, s32);
                put(0, p0, p1, p2, p3);
                put(1, cmul_s(p0, s64), cmul_s(p1, s64), cmul_s(p2, s64), cmul_s(p3, s64));
                sts16(za, s128); sts16(za + 64, s128 >> 16);
            }
            __syncwarp();
            {
                const uint32_t aA = fresh(oA), aB = fresh(oB), aC = fresh(oC), aZ = fresh(zr);
                const uint4 zc = lds128(aZ), zd = lds128(aZ + 64);
                const uint32_t zcs[4] = {zc.x, zc.y, zc.z, zc.w}, zds[4] = {zd.x, zd.y, zd.z, zd.w};
                uint32_t c[4];
#pragma unroll
                for (int k = 0; k < 4; k++) {
                    uint32_t a[4], b[4];
                    ldsm4t(a, aA + 128 * k); ldsm4t(b, aB + 128 * k);
                    if (!(k & 1)) ldsm4t(c, aC + 128 * k);
                    const h2c x = cmul_cd(h2c{a[0], a[2]}, *(const __half2*)&zcs[k], *(const __half2*)&zds[k]), y = cmul_cd(h2c{a[1], a[3]}, *(const __half2*)&zcs[k], *(const __half2*)&zds[k]);
                    mma_h(acc[0], a[0], a[1], a[2], a[3], b[0], b[1]);
                    mma_h(acc[1], a[0], a[1], a[2], a[3], b[2], b[3]);
                    mma_h(acc[2], a[0], a[1], a[2], a[3], c[2 * (k & 1)], c[2 * (k & 1) + 1]);
                    mma_h(acc[3], x.re, y.re, x.im, y.im, b[0], b[1]);
                    mma_h(acc[4], x.re, y.re, x.im, y.im, b[2], b[3]);
                    mma_h(acc[5], x.re, y.re, x.im, y.im, c[2 * (k & 1)], c[2 * (k & 1) + 1]);
                }
                asm volatile("" :: "f"(acc[0][0]), "f"(acc[1][0]), "f"(acc[2][0]), "f"(acc[3][0]), "f"(acc[4][0]), "f"(acc[5][0]) : "memory");
            }
            __syncwarp();
            ar = ar1; ai = ai1; W = W1;
        }
        if (threadIdx.x < 32) TSTAMP(21);
        const float i0 = __uint_as_float((ex + 243u) << 23);
        if (half) {
#pragma unroll
            for (int a = 0; a < 6; a++) sts128(wb + a * 512, __float_as_uint(acc[a][0]), __float_as_uint(acc[a][1]), __float_as_uint(acc[a][2]), __float_as_uint(acc[a][3]));
            sts32(stage + 3072, __float_as_uint(i0));
            bar_arrive(barid, 64);
        } else {
#pragma unroll
            for (int a = 0; a < 6; a++) { acc[a][0] *= i0; acc[a][1] *= i0; acc[a][2] *= i0; acc[a][3] *= i0; }
            if (lane == 0) acc[0][1] -= bf_lo(pD);
            sts32(zr, clock32());
            bar_sync(barid, 64);
            const uint32_t src = fresh(pstage);
            const float i1 = __uint_as_float(lds32(src + 3072));
#pragma unroll
            for (int a = 0; a < 6; a++) {
                const uint4 y = lds128(src + lane * 16 + a * 512);
                w[4 * (a % 3) + 2 * (a / 3)] = pack_bf16(fmaf(__uint_as_float(y.x), i1, acc[a][0]), fmaf(__uint_as_float(y.y), i1, acc[a][1]));
                w[4 * (a % 3) + 2 * (a / 3) + 1] = pack_bf16(fmaf(__uint_as_float(y.z), i1, acc[a][2]), fmaf(__uint_as_float(y.w), i1, acc[a][3]));
            }
        }
    }
}

__device__ __forceinline__ int swap01(int i) { return (i & ~3) | ((i & 1) << 1) | ((i >> 1) & 1); }
enum { BC_AUX = 0, BC_S = 5, BC_KG = 15 };

__device__ __forceinline__ void fetch_gates(const Params& p, int i, int lane, unsigned epoch, uint32_t dst) {
    const uint32_t par = (epoch & 1) ? 0x80008000u : 0u;
    uint4 v;
#pragma unroll 1
    for (int it = 0;; it++) {
        v = ld_rlx128(p.s->gate + 256 * i + 8 * lane);
        v.x ^= par; v.y ^= par; v.z ^= par; v.w ^= par;
        if (__all_sync(0xffffffffu, (v.x & v.y & v.z & v.w & 0x80008000u) == 0x80008000u)) break;
        if (it > (1 << 20)) give_up();
    }
    sts128(dst + (8 + 16 * i + (lane >> 1)) * 16, v.x, v.y, v.z, v.w);
}
__device__ __forceinline__ void store_rows(const CUtensorMap* m, uint32_t src, int col, int row) {
    asm volatile("cp.async.bulk.tensor.5d.global.shared::cta.bulk_group [%0, {%2, %3, %3, %3, %4}], [%1];" :: "l"(m), "r"(src), "r"(col), "r"(0), "r"(row) : "memory");
}

__device__ __forceinline__ void store_or_add(void* o, const uint32_t (&y)[4], uint32_t add) {
    asm volatile("{ .reg .pred p; setp.ne.u32 p, %5, 0; @!p st.global.v4.u32 [%0], {%1,%2,%3,%4}; @p red.relaxed.gpu.global.add.noftz.v4.bf16x2 [%0], {%1,%2,%3,%4}; }"
                 :: "l"(o), "r"(y[0]), "r"(y[1]), "r"(y[2]), "r"(y[3]), "r"(add) : "memory");
}

__device__ __forceinline__ void conv_aux(const Params& p, const CUtensorMap* mU, uint32_t sb, int aw, int lane, int bid, unsigned epoch) {
    const unsigned t0 = clock32();
    const int g = lane >> 2, t = lane & 3, mi = lane >> 3, r8 = lane & 7;
    const int rank = bid & 1, slab = bid >> 1;
    const uint32_t bar_y = sb + SC_MISC, bar_u = bar_y + 32, bar_v = bar_y + 40, bar_box = bar_y + 64 + 8 * aw, s_bm = bar_y + 128;
    if (lane == 0) {
        mbar_init(bar_box, 1); mbar_fence();
        mbar_expect(bar_box, 4096);
        if (UDELAY) until(t0, UDELAY);
        tma4d(sb + SC_RT + 4096 * aw, mU, 16 * slab, 0, 0, 16 * rank + 2 * aw, bar_box);
        mbar_init(bar_y + 8 * aw, aw < 4 ? 9 : aw == 5 ? 8 : 1); mbar_fence();
        if (aw < 5) mbar_expect(bar_y + 8 * aw, aw == 4 ? 16384 : 4096);
    }
    __syncwarp();
    asm volatile("barrier.cluster.arrive.relaxed.aligned;" ::: "memory");
    asm volatile("setmaxnreg.dec.sync.aligned.u32 88;");
    const uint32_t ut = sb + SC_UT + aw * UT_STRIDE;
    sts128(ut + (mi >> 1) * (SC_ST - SC_UT) + (mi & 1) * UT_HALF + r8 * 16, 0, 0, 0, 0);
    if (lane < 16) sts128(s_bm + lane * 16, 0, 0, 0, 0);
    {
        const uint32_t dst = sb + SC_UT + swap01(g) * UT_STRIDE + (8 + 64 * rank + 8 * aw + t) * 16;
        const uint32_t rdst = mapa(dst, rank ^ 1), rbar = mapa(bar_u, rank ^ 1);
        asm volatile("barrier.cluster.wait.acquire.aligned;" ::: "memory");
        mbar_wait(bar_box);
        if (aw == 0) TSTAMP(1);
        const uint32_t src = fresh(sb + SC_RT) + aw * 4096 + (8 * mi + 4 * (r8 & 1) + (r8 >> 1)) * 32 + ((rank ^ (r8 & 1)) << 4);
        uint32_t x[8][4];
#pragma unroll
        for (int i = 0; i < 4; i++) { ldsm4t(x[i], src + 1024 * i); ldsm4t(x[4 + i], (src ^ 16) + 1024 * i); }
        asm volatile("" :: "r"(x[0][0]), "r"(x[1][0]), "r"(x[2][0]), "r"(x[3][0]) : "memory");
#pragma unroll
        for (int i = 0; i < 4; i++) st_async128(rdst + (i & 1) * UT_HALF + 32 * (i & 2), x[4 + i][0], x[4 + i][1], x[4 + i][2], x[4 + i][3], rbar);
#pragma unroll
        for (int i = 0; i < 4; i++) sts128(dst + (i & 1) * UT_HALF + 32 * (i & 2), x[i][0], x[i][1], x[i][2], x[i][3]);
    }
    bar_sync(BC_AUX, 256);
    mbar_wait_cluster(bar_u);
    if (aw == 0) TSTAMP(2);
    {
        const uint32_t a = fresh(ut) + (mi & 1) * UT_HALF + (64 * (mi >> 1) + r8) * 16;
        uint4 v = lds128(a);
#pragma unroll
        for (int i = 1; i <= 8; i++) {
            const uint4 w = lds128(a + 128 * i);
            sts128(a + 128 * i + (SC_ST - SC_UT), badd2(v.x, w.x), badd2(v.y, w.y), badd2(v.z, w.z), badd2(v.w, w.w));
            v = w;
        }
    }
    bar_arrive(BC_S + aw, 64);
    if (aw == 0) TSTAMP(3);
    {
        uint32_t ws = sb + SC_UT + t * UT_STRIDE + (g + 6) * 16, wd = sb + SC_V + t * V_STRIDE + 64 * g, sw = 16 * (g & 2);
#pragma unroll 1
        for (int k = aw; k < 25; k += 8) {
            if (k - aw == 8) {
                bar_sync(BC_KG, 384);
                if (lane < 16) sts128(sb + SC_V + aw * V_STRIDE + lane * 16, 0, 0, 0, 0);
            }
            if (k == 24) { ws -= (g & 1) * 4 * UT_STRIDE + 16 * g; wd -= (g & 1) * 4 * V_STRIDE + 64 * g; sw = 0; }
            const int h = k >= 12, a = k - 12 * h;
            const uint32_t d = wd + h * 4 * V_STRIDE + 512 * a;
            window_task(fresh(ws) + h * 4 * UT_STRIDE + 128 * a, d + sw, d + (sw ^ 32), a < 8);
        }
    }
    if (aw == 0) TSTAMP(9);
    {
        if (aw >= 2) fetch_gates(p, aw, lane, epoch, sb + SC_GT + (lane & 1) * UT_HALF);
        __syncwarp();
        if (lane == 0) { mbar_arrive(bar_v); prefetch_map(mU + 4); }
        next_epoch(p, epoch);
        if (aw == 0) TSTAMP(4);
        if (aw == 7) {
            const int row = key_row(wait_sel(p, slab >> 1, r8, key_tag(epoch)));
            if (lane < 8) asm volatile("red.shared.or.b32 [%0], %1;" :: "r"(s_bm + (row >> 5) * 4), "r"(1u << (row & 31)) : "memory");
            TSTAMP(10);
        }
        bar_sync(BC_AUX, 256);
        const uint32_t src = sb + SC_RT + ((r8 >> 1) & 1) * Y_RS + (2 * mi + (r8 & 1)) * Y_CS + (2 * aw + (r8 >> 2)) * 16;
        const int L = 2 * aw + (t >> 1);
        const int row0 = 256 * rank + 128 * (g >> 2) + 32 * (L & 3) + 16 * (g & 1) + 8 * ((g >> 1) & 1) + (L >> 2);
        __nv_bfloat16* outp = p.out + (size_t)row0 * DM + 16 * slab + 8 * (t & 1);
        const uint32_t stg = sb + SC_ST + 4096 * aw, so = (g >> 1) * 256 + (t >> 1) * 64 + (g & 1) * 32 + (t & 1) * 16;
#pragma unroll 1
        for (int s = 1; s < 4; s++) {
            const uint32_t bm = lds32(fresh(s_bm) + (16 * s + (row0 >> 5)) * 4) >> (row0 & 31);
            const bool routed = __any_sync(0xffffffffu, bm & 0x11u);
            if (aw == s) mbar_wait_cluster(bar_y + 8 * s);
            bar_sync(BC_AUX, 256);
            const uint32_t sf = fresh(src) + 512 * s;
            uint32_t y[2][4];
            ldsm4t(y[0], sf); ldsm4t(y[1], sf + 256);
            if (routed || (s == 3 && (CSTG >> aw & 1))) {
#pragma unroll
                for (int k = 0; k < 2; k++) store_or_add(outp + (size_t)(512 * s + 4 * k) * DM, y[k], bm & (1u << (4 * k)));
            } else {
                sts128(stg + so + 1024 * s, y[0][0], y[0][1], y[0][2], y[0][3]); sts128(stg + so + 1024 * s + 128, y[1][0], y[1][1], y[1][2], y[1][3]);
                asm volatile("fence.proxy.async.shared::cta;" ::: "memory");
                __syncwarp();
                if (lane == 0) store_rows(mU + 4, stg + 1024 * s, 16 * slab, 512 * s + 256 * rank + 64 * (aw & 1) + (aw >> 1));
            }
            if (aw == 0) TSTAMP(16 + s);
        }
        if (lane == 0) { asm volatile("cp.async.bulk.commit_group;" ::: "memory"); asm volatile("cp.async.bulk.wait_group.read 0;" ::: "memory"); }
        if (aw == 0) TFLUSH();
    }
}

__device__ __forceinline__ void publish_k(uint4* kp, const uint32_t (&w)[12], int n, unsigned epoch) {
#pragma unroll
    for (int i = 0; i < n; i++) asm volatile(PUBST ".v4.u32 [%0], {%1,%2,%3,%4};" :: "l"(kp + 32 * i), "r"(w[3 * i]), "r"(w[3 * i + 1]), "r"(w[3 * i + 2]), "r"(~epoch));
}
template <bool FULL>
__device__ __forceinline__ void k_tables(uint32_t kt, int lane, const uint32_t (&w)[12]) {
    const int g = lane >> 2, t = lane & 3, mi = lane >> 3, r8 = lane & 7;
    uint32_t x3 = w[7], re[4], rx[4];
#pragma unroll
    for (int i = 0; i < 4; i++) {
        re[i] = __shfl_sync(0xffffffffu, w[i], lane + 31);
        rx[i] = __shfl_sync(0xffffffffu, w[4 + i], lane + (i == 0 && lane == 29 ? 5 : 1 + 2 * t));
    }
    if (FULL) {
        asm volatile("stmatrix.sync.aligned.m8n8.x4.trans.shared.b16 [%0], {%1,%2,%3,%4};"
                     :: "r"(kt + (r8 < 4 ? (KT_D + 7) * 4 + 64 * r8 + 16 * mi : 716 * 4)), "r"(w[8]), "r"(w[9]), "r"(w[10]), "r"(w[11]) : "memory");
        if (lane == 2) {
            sts32(kt + (KT_C + 78) * 4, w[8] & 0xffffu);
            sts128(kt + (KT_T + 2) * 4, 0, w[8] & 0xffffu, __byte_perm(w[8], 0, 0x1010), w[8] << 16);
        }
        if (lane == 29) x3 = bsub2(x3, rx[0] & 0xffffu);
    }
#pragma unroll
    for (int i = 0; i < 4; i++) {
        sts64(kt + (16 + 64 * i) * 4 + 8 * lane, __byte_perm(w[i], lane ? re[i] : i ? re[i - 1] : 0, 0x5432), w[i]);
        const uint32_t x = i < 3 ? w[4 + i] : x3, aa = __byte_perm(x, 0, 0x3232);
        if (t < 2) sts128(kt + (272 + 64 * i + 8 * g + 4 * t) * 4, i == 0 && lane == 0 ? __byte_perm(x, re[3], 0x5432) : aa, aa, x,
                          __byte_perm(lane != 29 ? rx[i] : i < 3 ? rx[(i + 1) & 3] : FULL ? 0 : rx[0] << 16, x, 0x5432));
        else if (FULL) sts32(kt + (KT_C - 50 + 8 * i + 32 * t + g) * 4, x);
    }
}

__device__ __forceinline__ void conv_main(const Params& p, uint32_t sb, int warp, int lane0, int bid, unsigned epoch, uint32_t (&w)[12]) {
    asm volatile("setmaxnreg.inc.sync.aligned.u32 168;");
    const int lane = __shfl_sync(0xffffffffu, lane0, lane0);
    const int g = lane >> 2, t = lane & 3, mi = lane >> 3, r8 = lane & 7;
    const int rank = bid & 1;
    const uint32_t bar_y = sb + SC_MISC, bar_v = bar_y + 40;
    next_epoch(p, epoch);
    if (warp < 4) {
        asm volatile("" :: "r"(w[0]), "r"(w[2]), "r"(w[4]), "r"(w[6]), "r"(w[8]), "r"(w[10]) : "memory");
        bar_arrive(BC_KG, 384);
    } else {
        const uint4* src = p.s->kp + (8 * bid + warp) * 128 + lane0;
#pragma unroll 1
        for (int it = 0;; it++) {
            uint32_t bad = 0;
#pragma unroll
            for (int i = 0; i < 4; i++) { const uint4 v = ld_rlx128(src + 32 * i); w[3 * i] = v.x; w[3 * i + 1] = v.y; w[3 * i + 2] = v.z; bad |= v.w ^ ~epoch; }
            const bool ok = __all_sync(0xffffffffu, bad == 0);
            if (ok) break;
            if (it > (1 << 20)) give_up();
        }
    }
    if ((warp & 3) == 0) TSTAMP(5 + (warp >> 2));
    k_tables<true>(sb + SC_KT + warp * KT_BYTES, lane0, w);
    asm volatile("barrier.cluster.wait.acquire.aligned;" ::: "memory");
    bar_sync(BC_S + swap01(warp), 64);
    __syncwarp();
    if ((warp & 3) == 0) TSTAMP(7 + (warp >> 2));
    {
        const uint32_t ut = fresh(sb + SC_UT) + swap01(warp) * UT_STRIDE, kt = fresh(sb + SC_KT) + warp * KT_BYTES;
        uint32_t u1 = ut + (mi & 1) * UT_HALF + (8 + r8) * 16 + (mi >> 1) * 128;
        auto dup = [&](uint32_t v) { return v ^ p.zero; };
        uint32_t kp = kt + (16 + g - 2 * t) * 4;
        float acc[16][4];
        {
            const uint32_t c0 = lds32(kp + 2048), c1 = lds32(kp + 2080), c2 = lds32(kp + 2016), c3 = dup(c0);
            const uint32_t e0 = lds32(kp + (KT_T - 16) * 4), e1 = lds32(kp + (KT_T - 8) * 4), e2 = lds32(kp + (KT_T - 24) * 4), e3 = dup(e0);
            const uint32_t f0 = dup(e1), f1 = lds32(kp + KT_T * 4);
            const uint32_t uo = ut + UT_HALF + (7 + lane) * 16;
#pragma unroll
            for (int i = 0; i < 16; i++) { acc[i][0] = acc[i][1] = acc[i][2] = acc[i][3] = 0.f; }
#pragma unroll
            for (int mu = 0; mu < 8; mu += 4) {
                uint32_t b[4];
                ldsm4(b, uo + 128 * mu);
#pragma unroll
                for (int k = 0; k < 4; k++) mma_bf8(acc[mu + 8 + k], f0, f1, b[k]);
            }
#pragma unroll
            for (int mu = 0; mu < 12; mu += 2) {
                uint32_t b[4];
                ldsm4(b, u1 + 128 * mu);
                mma_bf(acc[mu + 4], c0, c1, c2, c3, b[0], b[1]);
                mma_bf(acc[mu + 5], c0, c1, c2, c3, b[2], b[3]);
                if (mu < 8) { mma_bf(acc[mu + 8], e0, e1, e2, e3, b[0], b[1]); mma_bf(acc[mu + 9], e0, e1, e2, e3, b[2], b[3]); }
            }
        }
        {
            float M[8][4];
#pragma unroll
            for (int i = 0; i < 8; i++) { M[i][0] = M[i][1] = M[i][2] = M[i][3] = 0.f; }
            uint32_t s[8][4], a3[4];
            const uint32_t kb = kp, ub = dup(u1), uc = u1 + (mi >> 1) * 128;
            auto frag = [&](uint32_t (&a)[4], uint32_t x) { a[0] = lds32(x); a[1] = lds32(x + 32); a[2] = lds32(x - 32); a[3] = dup(a[0]); };
            frag(a3, kp + 1536);
#pragma unroll
            for (int i = 1; i < 8; i++) ldsm4(s[i], u1 + (SC_ST - SC_UT) + 256 * i);
            __syncwarp();
            uint32_t ko = 0, uo = 0;
#pragma unroll 1
            for (uint32_t n = warp < 4 ? (bid < 48 ? PUBIT : PUBY) : 8;; n = bid < 48 ? 8 - PUBIT : 8 - PUBY) {
#pragma unroll 1
            for (; n; n--) {
                uint32_t a2[4], a1[4], a0[4], b[4][4];
                ko = fresh(ko); uo = fresh(uo);
                kp = kb + ko; u1 = ub + uo;
                const uint32_t up = uc + uo;
                ko += 64; uo -= 16;
                frag(a2, kp + 1024);
#pragma unroll
                for (int i = 1; i < 4; i++) ldsm4(b[i], up + 512 * i);
                asm("ldmatrix.sync.aligned.m8n8.x2.shared.b16 {%0,%1}, [%2];" : "=r"(b[0][2]), "=r"(b[0][3]) : "r"(up + 256));
                frag(a1, kp + 512); frag(a0, kp);
                kp += 64; u1 -= 16;
#pragma unroll
                for (int i = 1; i < 7; i++) mma_bf(acc[2 * i + 2], a3[0], a3[1], a3[2], a3[3], s[i][0], s[i][1]);
#pragma unroll
                for (int e = 0; e < 4; e++) a3[e] = bsub2(a2[e], a3[e]);
#pragma unroll
                for (int i = 1; i < 7; i++) mma_bf(acc[2 * i + 3], a2[0], a2[1], a2[2], a2[3], s[i][2], s[i][3]);
                ldsm4(s[1], u1 + (SC_ST - SC_UT) + 256);
#pragma unroll
                for (int i = 1; i < 7; i++) mma_bf(M[i + 1], a3[0], a3[1], a3[2], a3[3], b[i >> 1][2 * (i & 1)], b[i >> 1][2 * (i & 1) + 1]);
                frag(a3, kp + 1536);
#pragma unroll
                for (int i = 2; i < 8; i++) mma_bf(acc[2 * i], a1[0], a1[1], a1[2], a1[3], s[i][0], s[i][1]);
#pragma unroll
                for (int e = 0; e < 4; e++) a1[e] = bsub2(a0[e], a1[e]);
#pragma unroll
                for (int i = 2; i < 8; i++) { mma_bf(acc[2 * i + 1], a0[0], a0[1], a0[2], a0[3], s[i][2], s[i][3]); ldsm4(s[i], u1 + (SC_ST - SC_UT) + 256 * i); }
#pragma unroll
                for (int i = 2; i < 8; i++) mma_bf(M[i], a1[0], a1[1], a1[2], a1[3], b[i >> 1][2 * (i & 1)], b[i >> 1][2 * (i & 1) + 1]);
            }
            if (ko == 512) break;
            publish_k(p.s->kp + (8 * bid + warp) * 128 + lane, w, 3, epoch);
            }
            u1 = ub;
#pragma unroll
            for (int i = 2; i < 8; i++)
#pragma unroll
                for (int c = 0; c < 4; c++) { acc[2 * i][c] += M[i][c]; acc[2 * i + 1][c] -= M[i][c]; }
        }
        if ((warp & 3) == 0) TSTAMP(11 + (warp >> 2));
        mbar_wait(bar_v);
        const uint32_t vt = fresh(sb + SC_V) + swap01(warp) * V_STRIDE;
        const uint32_t g1 = fresh(u1) - ut + sb + SC_GT;
        const uint32_t ydst = sb + SC_RT + rank * Y_RS + warp * Y_CS + lane * 16;
        const uint32_t ydr = mapa(ydst, rank ^ 1), ybr = mapa(bar_y, rank ^ 1);
        auto stairs = [&](auto R) {
        uint32_t ug[2][2][4];
        auto ld_ug = [&](int i) { ldsm4t(ug[i & 1][0], u1 + 256 * i); ldsm4t(ug[i & 1][1], g1 + 256 * i); };
        auto ship = [&](int i) {
            const uint32_t (&u)[4] = ug[i & 1][0], (&gg)[4] = ug[i & 1][1];
            const uint32_t y0 = gmix(gg[0], acc[2 * i][0], acc[2 * i][1], u[0]), y1 = gmix(gg[1], acc[2 * i][2], acc[2 * i][3], u[1]);
            const uint32_t y2 = gmix(gg[2], acc[2 * i + 1][0], acc[2 * i + 1][1], u[2]), y3 = gmix(gg[3], acc[2 * i + 1][2], acc[2 * i + 1][3], u[3]);
            if ((i & 1) != R.value) st_async128(ydr + 512 * (i >> 1), y0, y1, y2, y3, ybr + 8 * (i >> 1));
            else asm volatile("{ .reg .pred q; setp.eq.u32 q, %6, 0; st.shared.v4.u32 [%0], {%2,%3,%4,%5}; bar.warp.sync 0xffffffff; @q mbarrier.arrive.shared::cta.b64 _, [%1]; }"
                              :: "r"(ydst + 512 * (i >> 1)), "r"(bar_y + 8 * (i >> 1)), "r"(y0), "r"(y1), "r"(y2), "r"(y3), "r"(lane) : "memory");
        };
        const uint32_t VD = vt + (VC_OFF - 400 - 16 * t) * 4 + (8 * g ^ 16 * (-t & 2)), VD2 = vt + (VC_OFF - 415 - 16 * t) * 4 + (8 * g ^ 16 * (~t & 2));
        uint2 bd[10];
        uint32_t x[2][4][4];
        auto ld4 = [&](uint32_t (&v)[4], int dl) { const uint2 w = lds64(VD + 256 * dl); v[0] = w.x; v[1] = w.y; v[2] = lds32(VD2 + 256 * dl); v[3] = dup(w.x); };
        auto mm4 = [&](const uint32_t (&v)[4], int dl) {
#pragma unroll
            for (int s = dl & 1; s < 10; s += 2) if ((dl + s) / 2 >= 4 && (dl + s) / 2 < 16) mma_bf(acc[(dl + s) / 2], v[0], v[1], v[2], v[3], bd[s].x, bd[s].y);
        };
        const uint32_t KE = kt + (KT_D + g + t) * 4, VE = vt + (VE_BASE - 912 - 16 * t) * 4 + (8 * g ^ 16 * (~t & 2));
        uint32_t b0[8], b1[8];
        auto ld8 = [&](uint32_t (&v)[4], int dl) { const uint2 w = lds64(VE + 512 * dl), z = lds64(VE + 512 * dl - 256); v[0] = w.x; v[1] = w.y; v[2] = z.x; v[3] = z.y; };
        auto mm8 = [&](const uint32_t (&v)[4], int dl, int lo, int hi) {
#pragma unroll
            for (int s = 0; s < 8; s++) if (dl + s >= lo && dl + s < hi) mma_bf(acc[dl + s], v[0], v[1], v[2], v[3], b0[s], b1[s]);
        };
        ld4(x[0][0], 6);
#pragma unroll
        for (int s = 0; s < 10; s++) bd[s] = lds64(kt + (KT_C + 2 * g + 2 * t + 8 * s) * 4);
        mm4(x[0][0], 6);
        uint32_t e[4][4];
#pragma unroll
        for (int k = 1; k < 6; k++) {
#pragma unroll
            for (int j = 0; j < 4; j++) ld4(x[k & 1][j], 4 * k + 3 + j);
            ld_ug(k + 1);
            if (k == 3) {
#pragma unroll
                for (int s = 0; s < 8; s++) { b0[s] = lds32(KE + 32 * s); b1[s] = lds32(KE + 32 * s + 16); }
            }
            if (k > 1) ship(k);
#pragma unroll
            for (int j = 0; j < 4; j++) {
                mm4(x[k & 1][j], 4 * k + 3 + j);
                if (k == 3) { uint32_t v[4], z[4]; ld8(e[j], 8 + j); ld8(v, 12 + j); ld4(z, 30 - j); mm8(v, 12 + j, 12, 16); mm8(e[j], 8 + j, 8, 12); mm4(z, 30 - j); }
                if (k == 5) { ld8(e[j], 8 + j + p.zero); mm8(e[j], 8 + j, 12, 16); }
            }
        }
        ld_ug(7);
        ship(7 - R.value); ship(6 + R.value);
        };
        if (rank) stairs(std::integral_constant<int, 1>()); else stairs(std::integral_constant<int, 0>());
        if ((warp & 3) == 0) TSTAMP(14 + (warp >> 2)); else TSTAMP(21 + warp);
    }
}

constexpr int SF_WD = 73728;
constexpr int SF_RED = 49152;
constexpr int MU_HALF = 640, MU_STRIDE = 1344, SM_RAW = 98304, SM_UT = SM_RAW + 16384, SM_G = SM_UT + 16 * MU_STRIDE, SM_Y = 196608, SM_KT = 138880, SM_KW = SM_G - 49152;
constexpr int SF_XS = 221184;
constexpr int SF_MISC = SF_XS + 8 * 1168;
constexpr int SF_KG = SF_MISC - 10 * KG_STAGE;
constexpr int SF_WR = SF_KG - 2304;
constexpr int FB_X = 64, FB_KDONE = 72, FB_KEYS = 80, FB_FREE = 88  , FB_W = 104, FB_D = FB_W + 72, FB_MU = FB_D + 96, FB_GU = FB_MU + 8, FB_MG = FB_MU + 16, FB_MT = FB_MU + 24, FS_PART = 512, FS_TOK = 896;
enum { BAR_F = 6, BAR_R = 7, BAR_GU = 8, BAR_RED = 9, BAR_R2 = 10, BAR_X = 11, BAR_G = 12  , BAR_M = 15 };
static_assert(SF_KG % 128 == 0 && NPRE <= 8 && SM_KT + 4 * 2112 <= 147456 && SM_G + MU_STRIDE <= SF_WR - 4 * 9216 && SM_KW + 6 * 2112 >= SM_RAW && SM_KW + 12 * 2112 <= SM_UT, "layout");

__device__ __forceinline__ int mini_ch0(int f) { return f < NW ? 16 * (f - 12) : 32 * (f - NW); }

__device__ __forceinline__ void ffn_front(const Params& p, const CUtensorMap* maps, uint32_t sb, int warp, int lane, int f, unsigned epoch) {
    const unsigned t0 = clock32();
    const int g = lane >> 2, t = lane & 3, mi = lane >> 3, r8 = lane & 7;
    const bool isx = f < NX;
    const int nrw = f < 8 ? 6 : 4, r0 = f < 8 ? 48 * f : 128 + 32 * f;
    const int rw = warp < 12 ? 13 - warp : warp ^ (warp < 14 ? 10 : 15);
    const uint32_t bar_row = sb + SF_MISC  , bar_x = bar_row + FB_X;
    const uint32_t s_part = bar_row + FS_PART  , s_tok = bar_row + FS_TOK  ;
    const uint32_t rows = sb + SF_WR - 9216 * (rw + 1);
    if (lane == 0) {
        mbar_init(bar_row + 8 * rw, 1); mbar_fence();
        if (rw < nrw) { mbar_expect(bar_row + 8 * rw, 9216); until(t0, RDELAY); bulk_g2s(rows, p.u + (size_t)(r0 + 8 * rw) * DM, 9216, bar_row + 8 * rw); }
        else if (rw >= 6) { mbar_expect(bar_row + 8 * rw, 1152); bulk_g2s(sb + SF_WR + (rw & 1) * 1152, (rw & 1) ? p.gatew : p.wr, 1152, bar_row + 8 * rw); }
        if (warp >= 10) {
#pragma unroll 1
            for (int i = warp - 10; i < 30; i += 6) mbar_init(bar_x + 8 * i, max(2 * i - 54, 1));
        }
        mbar_fence();
    }
    uint4* const kdst = p.s->keys + (lane >> 1) * 128 + 2 * f + (lane & 1);
    if (warp == 13) {
        stg128(kdst, 0, 0, 0, 0);
        sts32(s_part + 64 + lane * 4, 0);
        if (lane < 8 && isx && !(f & 1)) st_rlx32(&p.s->sel[32 * f + lane], 0);
    }
    __syncwarp();
    bar_sync(BAR_F, f < 12 ? 256 : 192);
    bar_arrive(0, NTHR);
    if (warp == 15) TSTAMP(1);

    if (warp == 12) {
        if (lane == 0) {
            prefetch_map(maps + 1); prefetch_map(maps + 2); prefetch_map(maps + (isx ? 3 : 5));
            unsigned tb = t0 + WDELAY;
            uint32_t dst = sb;
#pragma unroll 1
            for (int n = 0; n < 18; n++) {
                if (n == NPRE) { mbar_wait(bar_row + FB_KEYS); mbar_wait(bar_row + FB_KDONE); tb = clock32() + RESUME; }
                if (n == 8) dst += 49152;
                if (n == 12) { mbar_wait(bar_row + FB_FREE); dst = sb; }
                until(tb, 0); tb += WGAP;
                if (n == MPOS && !isx) {
                    mbar_expect(bar_row + FB_MU, f < NW ? 16384 : 32768);
                    tma4d(sb + SM_RAW, maps + 5, mini_ch0(f), 0, 0, 0, bar_row + FB_MU);
                    if (f >= NW) { tma4d(sb + SM_RAW - 49152, maps + 5, mini_ch0(f) + 16, 0, 0, 0, bar_row + FB_MU); break; }
                }
                if (f >= NW) continue;
                const uint32_t b = bar_row + FB_W + 8 * (n >> 1);
                if (!(n & 1)) mbar_expect(b, 24576);
                tma3d(dst, maps + 1 + (n & 1), 0, 64 * (n >> 1), 3 * f, b);
                dst += 12288;
            }
            TSTAMP(12);
            if (isx) {
#pragma unroll 1
                for (int i = 0; i < 12; i++) {
                    const int n = (0x987610ba5432ull >> (4 * i)) & 15;
                    until(tb, 0); tb += DGAP;
                    if (i == 6) mbar_wait(bar_row + FB_FREE + 8);
                    mbar_expect(bar_row + FB_D + 8 * n, 12288);
                    tma2d(sb + SF_WD + n * 12288, maps + 3, 32 * (f >> 1), 2304 * (f & 1) + 192 * n, bar_row + FB_D + 8 * n);
                }
                TSTAMP(13);
            }
        }
    } else if (warp == 13) {
        const uint32_t tag = key_tag(epoch), par = (epoch & 1) ? 0u : 0x8000u;
        bar_sync(BAR_R, 32 * (nrw + 1));
        TSTAMP(3);
        {
            const uint32_t sg = fresh(s_part) + 192 + lane * 4;
            const uint32_t gb = pack_bf16(sigmoidf_(rbf(__uint_as_float(lds32(sg)))), sigmoidf_(rbf(__uint_as_float(lds32(sg + 128))))) | par | (par << 16);
            asm volatile("st.relaxed.gpu.global.u16 [%0], %1;" :: "l"(p.s->gate + r0 + lane), "h"((unsigned short)gb) : "memory");
            if (nrw > 4 && lane < 16) asm volatile("st.relaxed.gpu.global.u16 [%0], %1;" :: "l"(p.s->gate + r0 + 32 + lane), "h"((unsigned short)(gb >> 16)) : "memory");
        }
        bar_sync(BAR_R2, 32 * (nrw + 1));
        {
            const uint4 v = lds128(fresh(s_tok) + (lane & 1) * 16);
            asm volatile("st.relaxed.gpu.global.v4.u32 [%0], {%1,%2,%3,%4};" :: "l"(kdst), "r"(v.x | tag), "r"(v.y | tag), "r"(v.z | tag), "r"(v.w | tag) : "memory");
        }
        TSTAMP(4);
        if (lane == 0) { mbar_arrive(bar_row + FB_KEYS); mbar_expect(bar_x, 8 * 1152); }
        if (f >= NW) return;
        uint32_t k[16];
        const uint4* src = p.s->keys + (f & 15) * 128 + lane;
#pragma unroll 1
        for (int it = 0;; it++) {
            uint32_t bad = 0;
#pragma unroll
            for (int i = 0; i < 4; i++) {
                const uint4 x = ld_rlx128(src + (i < 3 || lane < 24 ? 32 * i : 64));
                k[i] = x.x; k[4 + i] = x.y; k[8 + i] = x.z; k[12 + i] = x.w;
                bad |= x.x ^ tag;
            }
            const bool ok = __all_sync(0xffffffffu, (bad & 0xf800u) == 0);
            if (ok) break;
            if (it > (1 << 20)) give_up();
        }
        TSTAMP(5);
        uint32_t key = 0;
#pragma unroll 2
        for (int r = 0; r < 8; r++) {
            const uint32_t m = __reduce_max_sync(0xffffffffu, max(max(k[0], k[1]), max(k[2], k[3])));
#pragma unroll
            for (int i = 0; i < 4; i++) {
                const bool pop = k[i] == m;
                k[i] = pop ? k[4 + i] : k[i]; k[4 + i] = pop ? k[8 + i] : k[4 + i]; k[8 + i] = pop ? k[12 + i] : k[8 + i]; k[12 + i] = pop ? 0 : k[12 + i];
            }
            if (r8 == r) key = m;
        }
        const int row = key_row(key);
        sts32(s_tok + r8 * 8, row);
        bar_arrive(BAR_X, 160);
        TSTAMP(6);
        if (isx) {
            if (!(f & 1)) {
                __nv_bfloat16* o = p.out + (size_t)row * DM + 16 * f + 8 * mi;
                asm volatile("st.relaxed.gpu.global.v4.u32 [%0], {%1,%1,%1,%1};" :: "l"(o), "r"(0) : "memory");
                if (__any_sync(0xffffffffu, ld_rlx32(o) != 0)) give_up();
                if (lane < 8) st_rlx32(&p.s->sel[32 * f + lane], key);
            } else wait_sel(p, f >> 1, r8, tag);
            uint32_t gb;
#pragma unroll 1
            for (int it = 0;; it++) {
                asm volatile("ld.relaxed.gpu.global.u16 %0, [%1];" : "=r"(gb) : "l"(p.s->gate + row) : "memory");
                gb ^= par;
                if (!(gb & 0x8000u)) break;
                if (it > (1 << 20)) give_up();
            }
            const uint32_t rb = key ^ 0x80000000u, rv = (rb ^ (((int)rb >> 31) & 0x7fff0000u)) & 0xffff0000u;
            sts32(s_tok + r8 * 8 + 4, __float_as_uint(rbf(1.0f - bf_lo(gb)) * rbf(sigmoidf_(__uint_as_float(rv)))));
            __syncwarp();
            TSTAMP(7);
            bar_arrive(BAR_RED, 416);
        }
    } else {
        if (rw < nrw) {
            float c[3][4];
#pragma unroll
            for (int i = 0; i < 3; i++) { c[i][0] = c[i][1] = c[i][2] = c[i][3] = 0.f; }
            mbar_wait(bar_row + 48); mbar_wait(bar_row + 56);
            const uint32_t b = fresh(sb + SF_WR) + (g & 1) * 1152 + (g >> 2) * 64 + t * 16 + (g & 2) * 2;
            uint32_t w[18][2];
#pragma unroll
            for (int kb = 0; kb < 18; kb++) { const uint32_t o = ((kb & 1) ? b ^ 64 : b) + 128 * (kb >> 1); w[kb][0] = lds32(o); w[kb][1] = lds32(o + 8); }
            mbar_wait(bar_row + 8 * rw);
            if (warp == 15) TSTAMP(2);
            const uint32_t a = fresh(rows) + g * 1152 + (g & 1) * 64 + t * 16;
#pragma unroll
            for (int kb = 0; kb < 18; kb++) {
                const uint4 x = lds128(((kb & 1) ? a ^ 64 : a) + 128 * (kb >> 1));
                mma_bf(c[kb % 3], x.x, x.y, x.z, x.w, w[kb][0], w[kb][1]);
            }
            const float sr = c[0][0] + c[1][0] + c[2][0] + __shfl_down_sync(0xffffffffu, c[0][2] + c[1][2] + c[2][2], 1);
            const float sg = c[0][1] + c[1][1] + c[2][1] + __shfl_down_sync(0xffffffffu, c[0][3] + c[1][3] + c[2][3], 1);
            const uint32_t rb = pack_bf16(0.f, sr);
            if (t == 2 * (g & 1)) {
                sts32(s_part + (8 * rw + g) * 4, (rb ^ (((int)rb >> 31) & 0x7fff0000u) ^ 0x80000000u) | (uint32_t)(2047 - r0 - 8 * rw - g));
                sts32(s_part + 192 + (8 * rw + g) * 4, __float_as_uint(sg));
            }
            __syncwarp();
            bar_sync(BAR_R, 32 * (nrw + 1));
            const uint32_t sk = fresh(s_part), kk = lds32(sk + (8 * rw + r8) * 4);
            int n = 0;
#pragma unroll
            for (int i = 0; i < 3; i++) { const uint4 v = lds128(sk + mi * 48 + 16 * i); n += (v.x > kk) + (v.y > kk) + (v.z > kk) + (v.w > kk); }
            n += __shfl_xor_sync(0xffffffffu, n, 8); n += __shfl_xor_sync(0xffffffffu, n, 16);
            if (n < 8) sts32(s_tok + 4 * n, kk);
            __syncwarp();
            bar_arrive(BAR_R2, 32 * (nrw + 1));
        }
    }
}

__device__ __forceinline__ void ffn_work(const Params& p, uint32_t sb, int warp, int lane, int f, unsigned epoch) {
    const int g = lane >> 2, t = lane & 3, mi = lane >> 3, r8 = lane & 7;
    const bool isx = f < NX;
    const uint32_t bar_x = sb + SF_MISC + FB_X, bar_free = sb + SF_MISC + FB_FREE, bar_w = sb + SF_MISC + FB_W, bar_d = sb + SF_MISC + FB_D, s_tok = sb + SF_MISC + FS_TOK;
    uint32_t fr[24][4];
    auto pin = [&] {
#pragma unroll
        for (int i = 0; i < 24; i += 8) asm volatile("" :: "r"(fr[i][0]), "r"(fr[i + 1][0]), "r"(fr[i + 2][0]), "r"(fr[i + 3][0]), "r"(fr[i + 4][0]), "r"(fr[i + 5][0]), "r"(fr[i + 6][0]), "r"(fr[i + 7][0]) : "memory");
    };
    {
        const int j = (unsigned)(warp - 4) < 6, w = warp - (j ? 4 : warp < 4 ? 0 : 6);
        float ag[2][4], au[2][4];
#pragma unroll
        for (int i = 0; i < 2; i++) { ag[i][0] = ag[i][1] = ag[i][2] = ag[i][3] = 0.f; au[i][0] = au[i][1] = au[i][2] = au[i][3] = 0.f; }
        const uint32_t wb = sb + (w >> 1) * 4096 + (r8 + 8 * (mi >> 1)) * 64 + (((2 * (w & 1) + (mi & 1)) ^ (r8 >> 1)) << 4);
        const uint32_t xb = sb + SF_XS + r8 * 1168 + mi * 16;
        auto load = [&](int i, int n, int place) {
            mbar_wait(bar_w + 8 * n);
            const uint32_t wk = fresh(wb) + place * 24576;
#pragma unroll
            for (int s = 0; s < 4; s++) { ldsm4t(fr[8 * i + s], wk + 1024 * s); ldsm4t(fr[8 * i + 4 + s], wk + 1024 * s + 12288); }
        };
        auto mul = [&](int i, uint32_t xk) {
            uint32_t x[2][4];
            ldsm4(x[0], xk); ldsm4(x[1], xk + 64);
#pragma unroll
            for (int s = 0; s < 4; s++) {
                const uint32_t (&a)[4] = fr[8 * i + s], (&b)[4] = fr[8 * i + 4 + s];
                mma_bf(ag[s & 1], a[0], a[1], a[2], a[3], x[s >> 1][2 * (s & 1)], x[s >> 1][2 * (s & 1) + 1]);
                mma_bf(au[s & 1], b[0], b[1], b[2], b[3], x[s >> 1][2 * (s & 1)], x[s >> 1][2 * (s & 1) + 1]);
            }
        };
#pragma unroll
        for (int i = 0; i < 3; i++) load(i, 3 * j + i, (i ? 5 : 3) * j + i);
        pin();
        bar_sync(BAR_G + j, 192);
        if (w == 0 && lane == 0) mbar_arrive(bar_free + 8 * j);
        if (warp < 4) {
            bar_sync(BAR_X, 160);
            const uint32_t rows = lds32(fresh(s_tok) + 8 * r8);
#pragma unroll 1
            for (int i = warp; i < 8; i += 4) {
                const int row = __shfl_sync(0xffffffffu, rows, i);
                if (lane == 0) bulk_g2s(sb + SF_XS + i * 1168, p.u + (size_t)row * DM, 1152, bar_x);
                __syncwarp();
            }
        }
        mbar_wait(bar_x);
        if (warp == 0) TSTAMP(8);
        {
            const uint32_t xk = fresh(xb) + 384 * j;
#pragma unroll
            for (int i = 0; i < 3; i++) { mul(i, (i ? fresh(xk) : xk) + 128 * i); if (i == 0) { asm volatile("" :: "f"(ag[0][0]), "f"(ag[1][0]), "f"(au[0][0]), "f"(au[1][0])); sts32(s_tok + 64, clock32()); } }
        }
#pragma unroll 1
        for (int n = 6 + j; n < 9; n += 2) { load(0, n, n - 6); mul(0, fresh(xb) + 128 * n); }
#pragma unroll
        for (int c = 0; c < 4; c++) { ag[0][c] += ag[1][c]; au[0][c] += au[1][c]; }
        if (j) {
            sts128(wb + 24576, __float_as_uint(ag[0][0]), __float_as_uint(ag[0][1]), __float_as_uint(ag[0][2]), __float_as_uint(ag[0][3]));
            sts128(wb + 25600, __float_as_uint(au[0][0]), __float_as_uint(au[0][1]), __float_as_uint(au[0][2]), __float_as_uint(au[0][3]));
        }
        bar_sync(BAR_GU, 384);
        if (!j) {
            const uint32_t sf = fresh(wb);
            const uint4 g1 = lds128(sf + 24576), u1 = lds128(sf + 25600);
            const uint32_t gs[4] = {g1.x, g1.y, g1.z, g1.w}, us[4] = {u1.x, u1.y, u1.z, u1.w};
            if (warp == 0) TSTAMP(9);
            float h[4];
#pragma unroll
            for (int c = 0; c < 4; c++) {
                const float gv = rbf(ag[0][c] + __uint_as_float(gs[c]));
                h[c] = rbf(gv * sigmoidf_(gv)) * rbf(au[0][c] + __uint_as_float(us[c]));
            }
            uint32_t h0, h1;
            asm("movmatrix.sync.aligned.m8n8.trans.b16 %0, %1;" : "=r"(h0) : "r"(pack_bf16(h[0], h[1])));
            asm("movmatrix.sync.aligned.m8n8.trans.b16 %0, %1;" : "=r"(h1) : "r"(pack_bf16(h[2], h[3])));
            if (h0 == 0) h0 = 0x8000u;
            asm volatile("{ .reg .b64 v; mov.b64 v, {%1, %2}; st.relaxed.gpu.global.b64 [%0], v; }" :: "l"(p.s->h + ((epoch & 1) * 288 + 6 * f + w) * 32 + lane), "r"(h0), "r"(h1) : "memory");
        }
        if (isx) {
            if (warp == 0) TSTAMP(10);
            const uint2* hsrc = p.s->h + ((epoch & 1) * 288 + 144 * (f & 1) + 12 * warp) * 32 + lane;
            uint2 hb[12];
            auto ldh = [&](int s) { asm volatile("ld.relaxed.gpu.global.v2.u32 {%0, %1}, [%2];" : "=r"(hb[s].x), "=r"(hb[s].y) : "l"(hsrc + 32 * s) : "memory"); };
#pragma unroll
            for (int s = 0; s < 12; s++) ldh(s);
#pragma unroll 1
            for (int it = 0;; it++) {
                bool again = false;
#pragma unroll
                for (int s = 0; s < 12; s += 2) if (__any_sync(0xffffffffu, min(hb[s].x, hb[s + 1].x) == 0)) { ldh(s); ldh(s + 1); again = true; }
                if (!again) break;
                if (it > (1 << 16)) give_up();
            }
            if (warp == 0) TSTAMP(11);
            mbar_wait(bar_d + 8 * warp);
            if (warp == 9) TSTAMP(14);
            float ad[2][2][4];
#pragma unroll
            for (int i = 0; i < 4; i++) { ad[i >> 1][i & 1][0] = ad[i >> 1][i & 1][1] = ad[i >> 1][i & 1][2] = ad[i >> 1][i & 1][3] = 0.f; }
            const uint32_t wd = fresh(sb) + SF_WD + warp * 12288 + (r8 + 8 * (mi >> 1)) * 64 + (((mi & 1) ^ (r8 >> 1)) << 4);
#pragma unroll
            for (int s = 0; s < 12; s++) {
                uint32_t a[4], b[4];
                ldsm4t(a, wd + 1024 * s); ldsm4t(b, (wd ^ 32) + 1024 * s);
                mma_bf(ad[0][s & 1], a[0], a[1], a[2], a[3], hb[s].x, hb[s].y);
                mma_bf(ad[1][s & 1], b[0], b[1], b[2], b[3], hb[s].x, hb[s].y);
            }
            const uint32_t rd = sb + SF_RED + warp * 1152 + (72 * t + g) * 4;
#pragma unroll
            for (int i = 0; i < 8; i++) sts32(rd + (i >> 2) * 64 + (i & 1) * 144 + ((i >> 1) & 1) * 32, __float_as_uint(ad[i >> 2][0][i & 3] + ad[i >> 2][1][i & 3]));
            bar_sync(BAR_RED, 416);
            if (warp < 4) {
                const int tid = 32 * warp + lane;
                const uint32_t rs = fresh(sb + SF_RED) + (tid >> 4) * 144 + (tid & 15) * 8;
                const uint2 tk = lds64(fresh(s_tok) + (tid >> 4) * 8);
                float x = 0.f, y = 0.f;
#pragma unroll
                for (int w = 0; w < 12; w++) { const uint2 v = lds64(rs + w * 1152); x += __uint_as_float(v.x); y += __uint_as_float(v.y); }
                asm volatile("red.relaxed.gpu.global.add.noftz.bf16x2 [%0], %1;" :: "l"(p.out + (size_t)tk.x * DM + 32 * (f >> 1) + 2 * (tid & 15)),
                             "r"(pack_bf16(x * __uint_as_float(tk.y), y * __uint_as_float(tk.y))) : "memory");
            }
            if (warp == 0) { TSTAMP(15); TFLUSH(); }
            asm volatile("exit;"); __builtin_unreachable();
        }
    }
}

__device__ __forceinline__ void fetch_k(const uint4* src, uint64_t (&v)[6], uint32_t a, uint32_t b) {
    asm volatile("{ .reg .pred p; setp.eq.u32 p, %7, %8; @p ld.relaxed.gpu.global.v2.u64 {%0,%1}, [%6]; @p ld.relaxed.gpu.global.v2.u64 {%2,%3}, [%6 + 512]; @p ld.relaxed.gpu.global.v2.u64 {%4,%5}, [%6 + 1024]; }"
                 : "+l"(v[0]), "+l"(v[1]), "+l"(v[2]), "+l"(v[3]), "+l"(v[4]), "+l"(v[5]) : "l"(src), "r"(a), "r"(b));
}
__device__ __forceinline__ void mini_conv(const Params& p, uint32_t sb, int warp, int lane, int f, unsigned epoch) {
    const int g = lane >> 2, t = lane & 3, mi = lane >> 3, r8 = lane & 7;
    const uint32_t fb = sb + SF_MISC, kt = sb + (warp >= 12 ? SM_KT - 12 * 2112 : f < NW ? SM_KW + 2 * 2112 : SM_KW) + warp * 2112;
    const bool ism = f >= NW;
    const int ch0 = mini_ch0(f);
    uint32_t seq = 128;
    uint64_t v[6] = {};
    const uint4* src = p.s->kp + lane;
    auto hi = [&](int i) { return (uint32_t)(v[i] >> 32); };
    if (f >= (warp < 4 ? NW : NX)) {
    {
        const uint32_t c = 36 + (warp & 3) + 2 * (warp & 12), y = (uint32_t)((warp < 8 ? 0xa026802400000000ull : 0x2a2e00280080a22cull) >> ((8 * warp) & 48)) & 0xffff;
        seq = ism ? 0x101 * c - 0x400 : y + (warp & 1) * ((y >> 5) & 0x101);
        src += (ch0 + (seq & 31)) * 128;
    }
    if (warp >= 10 && (warp & 2)) {
        const int q = (warp & 1) + (warp < 12 ? 2 : 0), n0 = ism ? 2 * (q & 1) : q;
        const uint32_t ab = sb - (ism ? 49152 * (q >> 1) : 0);
        mbar_wait(fb + FB_MU);
        if (warp == 15) TSTAMP(16);
        uint32_t a = fresh(ab + SM_RAW) + n0 * 4096 + (8 * mi + 4 * (r8 & 1) + (r8 >> 1)) * 32 + ((r8 & 1) << 4), d = ab + SM_UT + g * MU_STRIDE + (8 + 8 * n0 + t) * 16;
        uint32_t z = ab + SM_UT + (4 * n0 + (mi >> 1)) * MU_STRIDE + (mi & 1) * MU_HALF + r8 * 16;
#pragma unroll 1
        for (int n = 0; n <= ism; n++, a += 4096, d += 128, z += 4 * MU_STRIDE) {
            uint32_t x[8][4];
#pragma unroll
            for (int i = 0; i < 8; i++) ldsm4t(x[i], (i & 4 ? a ^ 16 : a) + 1024 * (i & 3));
            sts128(z, 0, 0, 0, 0); sts128(z + 2 * MU_STRIDE, 0, 0, 0, 0);
#pragma unroll
            for (int i = 0; i < 8; i++) sts128(d + (i & 1) * MU_HALF + (i & 2) * 32 + (i & 4) * 2 * MU_STRIDE, x[i][0], x[i][1], x[i][2], x[i][3]);
        }
        __syncwarp();
        if (lane == 0) mbar_arrive(fb + FB_MT);
    }
    if (seq & 32) {
        mbar_wait(fb + FB_KDONE);
        fetch_k(src, v, 0, 0);
        if ((warp >> 1) == 2) { fetch_gates(p, warp & 1, lane, epoch, sb + SM_G + (lane & 1) * MU_HALF); __syncwarp(); if (lane == 0) mbar_arrive(fb + FB_MG); }
        mbar_wait(fb + FB_KEYS); mbar_wait(fb + FB_MT);
        sts128(kt + t * 16, 0, 0, 0, 0);
        if (warp == TW) TSTAMP(17);
    }
    }
    const uint32_t lo = (mi & 1) * MU_HALF + (8 + r8) * 16 + (mi >> 1) * 128;
#pragma unroll 1
    do {
        const int c = seq & 31;
        if (seq & 32) {
#pragma unroll 1
        for (int it = 0; !__all_sync(0xffffffffu, ((hi(1) ^ ~epoch) | (hi(3) ^ ~epoch) | (hi(5) ^ ~epoch) | ((uint32_t)v[5] & p.zero)) == 0); it++) {
            fetch_k(src, v, 0, 0);
            if (it > (1 << 20)) give_up();
        }
        if (warp == TW) TSTAMP(seq >> 8 ? 7 : 10);
        const uint32_t w[12] = {(uint32_t)v[0], hi(0), (uint32_t)v[1], (uint32_t)v[2], hi(2), (uint32_t)v[3], (uint32_t)v[4], hi(4), 0, 0, 0, 0};
        k_tables<false>(fresh(kt), fresh(lane), w);
        }
        __syncwarp();
        if (seq & 128) ffn_work(p, sb, warp, fresh(lane), f, epoch);
        if (!(seq & 32)) break;
        const uint32_t ab = sb - 49152 * (c >> 4), kb = fresh(kt) + (16 + g - 2 * t) * 4, ub = fresh(ab + SM_UT + (c & 15) * MU_STRIDE) + lo;
        const uint32_t yd = ab + SM_Y + (c & 15) * 1056 + (c & 8) * 8 + lane * 16;
        uint32_t kp = kb, u1 = ub;
        if (warp == TW && !(seq >> 8)) TSTAMP(13);
        seq >>= 8;
        src += ((int)(seq & 31) - c) * 128;
#pragma unroll
        for (int i = 0; i < 6; i++) v[i] = 0;
        fetch_k(src, v, seq & 32 && !ism, 1);
        uint32_t hint = seq && ism ? ~epoch : epoch;
        float acc[6][4];
#pragma unroll
        for (int i = 0; i < 6; i++) { acc[i][0] = acc[i][1] = acc[i][2] = acc[i][3] = 0.f; }
        uint32_t a[4][4], b[2][2][4];
        auto lda = [&](int j, int o) { const uint32_t x = kp + 64 * o + 512 * j; a[j][2] = o ? a[j][1] ^ p.zero : lds32((kp ^ p.zero) + 512 * j - 32); a[j][0] = lds32(x); a[j][1] = lds32(x + 32); a[j][3] = a[j][0] ^ p.zero; };
        auto ldb = [&](int s, int o) { ldsm4(b[s][0], u1 - 16 * o); ldsm4(b[s][1], u1 + 256 - 16 * o); };
        ldb(0, 0);
#pragma unroll
        for (int j = 0; j < 4; j++) lda(j, 0);
#pragma unroll
        for (int s = 0; s < 8; s++) {
            if (s == FPOS) fetch_k(src, v, hint, ~epoch | (__float_as_uint(acc[0][0]) & p.zero));
            if (s < 7) ldb(~s & 1, s + 1);
#pragma unroll
            for (int i = 0; i < 4; i++) {
                const int j = (i >> 1) + 2 * (i & 1);
#pragma unroll
                for (int mu = 3 - j; mu >= 0; mu--) mma_bf(acc[j + mu + (j & 2)], a[j][0], a[j][1], a[j][2], a[j][3], b[s & 1][mu >> 1][2 * (mu & 1)], b[s & 1][mu >> 1][2 * (mu & 1) + 1]);
                if (s < 7) lda(j, s + 1);
            }
        }
        if (warp == TW && !seq) TSTAMP(14);
        mbar_wait(fb + FB_MG);
#pragma unroll
        for (int e = 0; e < 4; e++) { acc[2][e] += acc[4][e]; acc[3][e] += acc[5][e]; }
        uint32_t ug[4][4];
#pragma unroll
        for (int i = 0; i < 2; i++) { ldsm4t(ug[i], ub + 256 * i); ldsm4t(ug[2 + i], fresh(sb + SM_G) + lo + 256 * i); }
#pragma unroll
        for (int i = 0; i < 2; i++) {
            const uint32_t (&u)[4] = ug[i], (&gg)[4] = ug[2 + i];
            sts128(yd + 512 * i, gmix(gg[0], acc[2 * i][0], acc[2 * i][1], u[0]), gmix(gg[1], acc[2 * i][2], acc[2 * i][3], u[1]),
                   gmix(gg[2], acc[2 * i + 1][0], acc[2 * i + 1][1], u[2]), gmix(gg[3], acc[2 * i + 1][2], acc[2 * i + 1][3], u[3]));
        }
        __syncwarp();
        if (warp == TW) TSTAMP(18 + (seq != 0));
    } while (seq);
    if (warp >= 12) TSTAMP(12 + warp);
}
__device__ __forceinline__ void mini_out(const Params& p, const CUtensorMap* maps, uint32_t sb, int warp, int lane, int f, unsigned epoch) {
    const int g = lane >> 2, t = lane & 3, mi = lane >> 3, r8 = lane & 7;
    const uint32_t fb = sb + SF_MISC;
    const bool ism = f >= NW;
    const int ch0 = mini_ch0(f);
    const int m = warp & 7, k = ism ? warp >> 3 : 0;
    const uint32_t list = fb + FS_PART + 32 * k, ab = sb - 49152 * k;
    uint32_t first = 1;
    if (lane == 0) asm volatile("atom.shared.exch.b32 %0, [%1], 1;" : "=r"(first) : "r"(list + 128) : "memory");
    if (!__all_sync(0xffffffffu, first)) { sts32(list + 4 * r8, key_row(wait_sel(p, ch0 >> 5, r8, key_tag(epoch)))); if (lane == 0) prefetch_map(maps + 4); }
    int i = ism ? 0 : warp >> 3, r0 = 256 * i + 64 * (m & 1) + (m >> 1);
    const int dr = 128 * (g >> 2) + 32 * (t >> 1) + 16 * (g & 1) + 8 * ((g >> 1) & 1);
    uint32_t y = ab + SM_Y + ((r8 >> 1) & 1) * 8512 + (2 * mi + (r8 & 1)) * 1056 + (2 * m + (r8 >> 2)) * 16 + 512 * i, stg = ab + SM_UT + 2048 * m + 1024 * i;
    const uint32_t so = (g >> 1) * 256 + (t >> 1) * 64 + (g & 1) * 32 + (t & 1) * 16;
    bar_sync(BAR_M - k, ism ? 256 : NTHR);
    const uint32_t rr = lds32(fresh(list) + 4 * r8);
    y = fresh(y);
#pragma unroll 1
    do {
        uint32_t x[2][4];
        ldsm4t(x[0], y); ldsm4t(x[1], y + 256);
        if (warp == 0 && x[0][0] != 0x12345) TSTAMP(28);
        const bool routed = __any_sync(0xffffffffu, (rr & ~0xbcu) == r0);
        if (routed || (MSTG >> m & 1)) {
            uint32_t bm = 0;
#pragma unroll 1
            for (int n = routed ? 0 : 8; n < 8; n++) { const uint32_t d = __shfl_sync(0xffffffffu, rr, n) ^ (r0 + dr); bm |= d == 0 ? 1 : d == 4 ? 2 : 0; }
#pragma unroll
            for (int n = 0; n < 2; n++) store_or_add(p.out + (size_t)(r0 + dr + 4 * n) * DM + ch0 + 16 * k + 8 * (t & 1), x[n], bm & (1 << n));
        } else {
#pragma unroll
            for (int n = 0; n < 2; n++) sts128(stg + so + 128 * n, x[n][0], x[n][1], x[n][2], x[n][3]);
            asm volatile("fence.proxy.async.shared::cta;" ::: "memory");
            __syncwarp();
            if (lane == 0) store_rows(maps + 4, stg, ch0 + 16 * k, r0);
        }
        y += 512; stg += 1024; r0 += 256;
    } while (ism && r0 < 512);
    if (lane == 0) { asm volatile("cp.async.bulk.commit_group;" ::: "memory"); asm volatile("cp.async.bulk.wait_group.read 0;" ::: "memory"); }
    if (warp == 8) TSTAMP(11);
    if (warp == 0) { TSTAMP(15); TFLUSH(); }
}

constexpr int SMEM_BYTES = 232448;
static_assert(SF_MISC + 1024 <= 232192, "layout");

struct Maps { CUtensorMap m[6]; };

__global__ void __cluster_dims__(2, 1, 1) __launch_bounds__(NTHR, 1)
fused_kernel(const Params p, const __grid_constant__ Maps maps) {
    extern __shared__ __align__(1024) uint8_t smem_raw[];
    uint32_t q[8];
    {
        const int b = blockIdx.x, x = threadIdx.x, rc = 4 * b + max(b - 84, 0) - 288 + (x >> 6);
        const int cv = (b - NCONV) >> 31, ca = 8 * b + ((x >> 5) & 3), cb = 2 * rc - (rc & 3) + 4;
        const uint32_t ch = (ca & cv) | (cb & ~cv), o = NST * ch + 2 * ((x & 31) + ((x >> (cv & 2)) & 32));
        const bool c = x < (b < 84 ? 256 : 320);
        q[6] = ldg16_if(c, p.logdt + ch);
        q[2] = ldg32_if(c, p.Bre + o); q[3] = ldg32_if(c, p.Bim + o); q[4] = ldg32_if(c, p.Cre + o); q[5] = ldg32_if(c, p.Cim + o); q[0] = ldg32_if(c, p.Are + o); q[1] = ldg32_if(c, p.Aim + o);
        q[7] = ldg16_if(c, p.Dskip + ch);
    }
    const unsigned epoch = ld_rlx32(&p.s->epoch[blockIdx.x * 16 + (threadIdx.x >> 5)]);
    const uint32_t sb = __shfl_sync(0xffffffffu, smem_u32(smem_raw), 0);
    const int warp = __shfl_sync(0xffffffffu, threadIdx.x >> 5, 0), bid = __shfl_sync(0xffffffffu, blockIdx.x, 0);
    const int lane = __shfl_sync(0xffffffffu, threadIdx.x & 31, threadIdx.x);
    const bool conv = bid < NCONV;
    const int f = bid - NCONV;
    uint32_t w[12];
    if (warp < (f < 12 ? 8 : 10)) {
        const int half = conv ? warp >> 2 : warp & 1, pr = conv ? warp & 3 : warp >> 1;
        const int rc = 4 * f + max(f - 12, 0) + pr;
        const uint32_t stage = sb + (conv ? SC_KG : SF_KG) + warp * KG_STAGE;
        uint4* const kp = p.s->kp + (conv ? 8 * bid + pr : 2 * rc - (rc & 3) + 4) * 128 + lane;
        kgen(q, sb, half, stage, stage + (conv ? 4 : 1) * KG_STAGE, 1 + pr, lane, p.zero, w, [&] {
            sts128z_if(conv && lane < 20, sb + SC_KT + warp * KT_BYTES + lane * 16 + (lane < 4 ? 0 : lane < 14 ? 2048 : 2288));
            stg128(kp + 64 * half, 0, 0, 0, 0); stg128z_if(!conv || !half, kp + 64 * half + 32);
            stg128z_if((unsigned)f < NW && warp < 6, (uint4*)(p.s->h + ((lane >> 4) * 288 + 6 * f + warp) * 32) + (lane & 15));
            if (conv) asm volatile("barrier.cluster.arrive.relaxed.aligned;" ::: "memory");
        });
        if (conv) { conv_main(p, sb, warp, lane, bid, epoch, w); return; }
        {
            if (!half) publish_k(kp, w, 4, epoch);
            if (warp == 0) TSTAMP(22);
            if (warp == 2) TSTAMP(23);
            bar_sync(0, NTHR);
            if (warp == 0 && lane == 0) mbar_arrive(sb + SF_MISC + FB_KDONE);
        }
    } else if (conv) {
        conv_aux(p, maps.m, sb, warp - 8, lane, bid, epoch);
        return;
    } else {
        ffn_front(p, maps.m, sb, warp, lane, f, epoch);
    }
    converged();
    next_epoch(p, epoch);
    if (warp >= 12 && f < NX) return;
    mini_conv(p, sb, warp, __shfl_sync(0xffffffffu, lane, lane), f, epoch);
    mini_out(p, maps.m, sb, warp, lane, f, epoch);
}

typedef CUresult (*EncodeFn)(CUtensorMap*, CUtensorMapDataType, cuuint32_t, void*, const cuuint64_t*, const cuuint64_t*, const cuuint32_t*, const cuuint32_t*,
                             CUtensorMapInterleave, CUtensorMapSwizzle, CUtensorMapL2promotion, CUtensorMapFloatOOBfill);

void make_map(EncodeFn fn, CUtensorMap* m, const void* base, int rank, const cuuint64_t* dims, const cuuint64_t* strides, const cuuint32_t* box, CUtensorMapSwizzle sw) {
    const cuuint32_t es[5] = {1, 1, 1, 1, 1};
    fn(m, CU_TENSOR_MAP_DATA_TYPE_BFLOAT16, rank, (void*)base, dims, strides, box, es, CU_TENSOR_MAP_INTERLEAVE_NONE, sw,
       CU_TENSOR_MAP_L2_PROMOTION_NONE, CU_TENSOR_MAP_FLOAT_OOB_FILL_NONE);
}

}

extern "C" void kernel_launch(void* const* d_in, const int* in_sizes, int n_in, void* d_out, int out_size) {
    (void)in_sizes; (void)n_in; (void)out_size;
    static EncodeFn fn = nullptr;
    static void* scratch = nullptr;
    if (!fn) {
        void* ptr = nullptr; cudaDriverEntryPointQueryResult qr;
        cudaGetDriverEntryPoint("cuTensorMapEncodeTiled", &ptr, cudaEnableDefault, &qr);
        fn = (EncodeFn)ptr;
        cudaGetSymbolAddress(&scratch, g_scratch);
        cudaFuncSetAttribute(fused_kernel, cudaFuncAttributeMaxDynamicSharedMemorySize, SMEM_BYTES);
    }
    typedef const __nv_bfloat16* bp;
    Params p;
    p.u = (bp)d_in[0]; p.Are = (bp)d_in[1]; p.Aim = (bp)d_in[2]; p.Bre = (bp)d_in[3]; p.Bim = (bp)d_in[4]; p.Cre = (bp)d_in[5]; p.Cim = (bp)d_in[6];
    p.logdt = (bp)d_in[7]; p.Dskip = (bp)d_in[8]; p.wr = (bp)d_in[10]; p.gatew = (bp)d_in[14];
    p.out = (__nv_bfloat16*)d_out; p.s = (Scratch*)scratch; p.zero = 0;
    Maps maps;
    {
        const cuuint64_t dims[4] = {DM, 4, 16, 32}, strides[3] = {16 * DM * 2, DM * 2, 64 * DM * 2};
        const cuuint32_t box[4] = {16, 4, 16, 2};
        make_map(fn, &maps.m[0], d_in[0], 4, dims, strides, box, CU_TENSOR_MAP_SWIZZLE_32B);
        const cuuint32_t box2[4] = {16, 4, 16, 8};
        make_map(fn, &maps.m[5], d_in[0], 4, dims, strides, box2, CU_TENSOR_MAP_SWIZZLE_32B);
    }
    for (int i = 0; i < 2; i++) {
        const cuuint64_t dims[3] = {32, DM, FF / 32}, strides[2] = {FF * 2, 64};
        const cuuint32_t box[3] = {32, 64, 3};
        make_map(fn, &maps.m[1 + i], d_in[11 + i], 3, dims, strides, box, CU_TENSOR_MAP_SWIZZLE_64B);
    }
    {
        const cuuint64_t dims[2] = {DM, FF}, strides[1] = {DM * 2};
        const cuuint32_t box[2] = {32, 192};
        make_map(fn, &maps.m[3], d_in[13], 2, dims, strides, box, CU_TENSOR_MAP_SWIZZLE_64B);
    }
    {
        const cuuint64_t dims[5] = {DM, 4, 4, 2, L_SEQ}, strides[4] = {16 * DM * 2, 4 * DM * 2, 128 * DM * 2, DM * 2};
        const cuuint32_t box[5] = {16, 4, 4, 2, 1};
        make_map(fn, &maps.m[4], d_out, 5, dims, strides, box, CU_TENSOR_MAP_SWIZZLE_NONE);
    }
    fused_kernel<<<NCTA, NTHR, SMEM_BYTES>>>(p, maps);
}
```

```cpp
#include <cuda_runtime.h>
#include <cuda_bf16.h>
#include <cuda_fp16.h>
#include <cuda.h>
#include <stdint.h>
#include <type_traits>

#define RESUME 200
#define PUBIT 1
#define FPOS 2
#define PUBV 0
#define PUBST "st.relaxed.gpu.global"
#define PUBY 0
#define KEYPF 1
#define TW 12
#define MDELAY 0
#define UDELAY 0
#define RDELAY 900
#define WDELAY 2000
#define WGAP 290
#define NPRE 6
#define DGAP 260

namespace {

constexpr int DM = 576, NST = 128, FF = 4608, L_SEQ = 2048;
constexpr int NCONV = 72, NX = 36, NW = 48, NCTA = 132, NTHR = 512;

struct __align__(128) Scratch {
    unsigned epoch[NCTA * 16];
    uint4 keys[16 * 128];
    uint32_t sel[18 * 64];
    uint16_t gate[L_SEQ];
    uint2 h[2 * 288 * 32];
    uint4 kp[DM * 128];
};
__device__ Scratch g_scratch;
#define TFLUSH()
#define TSTAMP(i)

struct Params {
    const __nv_bfloat16 *Are, *Aim, *Bre, *Bim, *Cre, *Cim, *logdt, *Dskip, *u, *wr, *gatew;
    __nv_bfloat16* out;
    Scratch* s;
    uint32_t zero;
};

__device__ __forceinline__ void give_up() { asm volatile("trap; exit;"); __builtin_unreachable(); }
__device__ __forceinline__ void converged() { __syncwarp(); asm volatile("{ .reg .b32 t; mov.b32 t, 0; movmatrix.sync.aligned.m8n8.trans.b16 t, t; }" ::: "memory"); }
__device__ __forceinline__ bool elect() { uint32_t r; asm volatile("{ .reg .pred p; elect.sync _|p, 0xffffffff; selp.u32 %0, 1, 0, p; }" : "=r"(r)); return r; }
__device__ __forceinline__ uint32_t smem_u32(const void* p) { return (uint32_t)__cvta_generic_to_shared(p); }
__device__ __forceinline__ uint32_t pack_bf16(float lo, float hi) { uint32_t r; asm("cvt.rn.bf16x2.f32 %0, %1, %2;" : "=r"(r) : "f"(hi), "f"(lo)); return r; }
__device__ __forceinline__ uint32_t pack_f16(float lo, float hi) { uint32_t r; asm("cvt.rn.f16x2.f32 %0, %1, %2;" : "=r"(r) : "f"(hi), "f"(lo)); return r; }
__device__ __forceinline__ float bf_lo(uint32_t w) { return __uint_as_float(w << 16); }
__device__ __forceinline__ float bf_hi(uint32_t w) { return __uint_as_float(w & 0xffff0000u); }
__device__ __forceinline__ float rbf(float x) { return bf_lo(pack_bf16(x, 0.f)); }
__device__ __forceinline__ uint32_t badd2(uint32_t a, uint32_t b) { uint32_t r; asm("add.rn.bf16x2 %0, %1, %2;" : "=r"(r) : "r"(a), "r"(b)); return r; }
__device__ __forceinline__ uint32_t bsub2(uint32_t a, uint32_t b) { uint32_t r; asm("sub.rn.bf16x2 %0, %1, %2;" : "=r"(r) : "r"(a), "r"(b)); return r; }
__device__ __forceinline__ uint32_t gmix(uint32_t ng, float ny0, float ny1, uint32_t u) {
    uint32_t r; asm("{ .reg .b32 t; fma.rn.bf16x2 t, %1, %3, %3; fma.rn.bf16x2 %0, %1, %2, t; }" : "=r"(r) : "r"(ng), "r"(pack_bf16(ny0, ny1)), "r"(u)); return r;
}
__device__ __forceinline__ void mma_bf(float (&c)[4], uint32_t a0, uint32_t a1, uint32_t a2, uint32_t a3, uint32_t b0, uint32_t b1) {
    asm("mma.sync.aligned.m16n8k16.row.col.f32.bf16.bf16.f32 {%0,%1,%2,%3}, {%4,%5,%6,%7}, {%8,%9}, {%0,%1,%2,%3};"
        : "+f"(c[0]), "+f"(c[1]), "+f"(c[2]), "+f"(c[3]) : "r"(a0), "r"(a1), "r"(a2), "r"(a3), "r"(b0), "r"(b1));
}
__device__ __forceinline__ void mma_bf8(float (&c)[4], uint32_t a0, uint32_t a1, uint32_t b0) {
    asm("mma.sync.aligned.m16n8k8.row.col.f32.bf16.bf16.f32 {%0,%1,%2,%3}, {%4,%5}, {%6}, {%0,%1,%2,%3};"
        : "+f"(c[0]), "+f"(c[1]), "+f"(c[2]), "+f"(c[3]) : "r"(a0), "r"(a1), "r"(b0));
}
__device__ __forceinline__ void mma_h(float (&c)[4], uint32_t a0, uint32_t a1, uint32_t a2, uint32_t a3, uint32_t b0, uint32_t b1) {
    asm("mma.sync.aligned.m16n8k16.row.col.f32.f16.f16.f32 {%0,%1,%2,%3}, {%4,%5,%6,%7}, {%8,%9}, {%0,%1,%2,%3};"
        : "+f"(c[0]), "+f"(c[1]), "+f"(c[2]), "+f"(c[3]) : "r"(a0), "r"(a1), "r"(a2), "r"(a3), "r"(b0), "r"(b1));
}
__device__ __forceinline__ uint32_t fresh(uint32_t a) { asm volatile("" : "+r"(a) :: "memory"); return a; }
__device__ __forceinline__ uint32_t lds16(uint32_t a) { uint32_t v; asm("ld.shared.u16 %0, [%1];" : "=r"(v) : "r"(a)); return v; }
__device__ __forceinline__ uint32_t lds32(uint32_t a) { uint32_t v; asm("ld.shared.u32 %0, [%1];" : "=r"(v) : "r"(a)); return v; }
__device__ __forceinline__ uint2 lds64(uint32_t a) { uint2 v; asm("ld.shared.v2.u32 {%0,%1}, [%2];" : "=r"(v.x), "=r"(v.y) : "r"(a)); return v; }
__device__ __forceinline__ uint4 lds128(uint32_t a) { uint4 v; asm("ld.shared.v4.u32 {%0,%1,%2,%3}, [%4];" : "=r"(v.x), "=r"(v.y), "=r"(v.z), "=r"(v.w) : "r"(a)); return v; }
__device__ __forceinline__ uint4 lds128v(uint32_t a) { uint4 v; asm volatile("ld.shared.v4.u32 {%0,%1,%2,%3}, [%4];" : "=r"(v.x), "=r"(v.y), "=r"(v.z), "=r"(v.w) : "r"(a) : "memory"); return v; }
__device__ __forceinline__ void ldsm4(uint32_t (&r)[4], uint32_t a) {
    asm("ldmatrix.sync.aligned.m8n8.x4.shared.b16 {%0,%1,%2,%3}, [%4];" : "=r"(r[0]), "=r"(r[1]), "=r"(r[2]), "=r"(r[3]) : "r"(a));
}
__device__ __forceinline__ void ldsm4t(uint32_t (&r)[4], uint32_t a) {
    asm("ldmatrix.sync.aligned.m8n8.x4.trans.shared.b16 {%0,%1,%2,%3}, [%4];" : "=r"(r[0]), "=r"(r[1]), "=r"(r[2]), "=r"(r[3]) : "r"(a));
}
__device__ __forceinline__ void sts16(uint32_t a, uint32_t v) { asm volatile("st.shared.u16 [%0], %1;" :: "r"(a), "h"((unsigned short)v) : "memory"); }
__device__ __forceinline__ void sts32(uint32_t a, uint32_t v) { asm volatile("st.shared.u32 [%0], %1;" :: "r"(a), "r"(v) : "memory"); }
__device__ __forceinline__ void sts64(uint32_t a, uint32_t x, uint32_t y) { asm volatile("st.shared.v2.u32 [%0], {%1,%2};" :: "r"(a), "r"(x), "r"(y) : "memory"); }
__device__ __forceinline__ void sts128(uint32_t a, uint32_t x, uint32_t y, uint32_t z, uint32_t w) {
    asm volatile("st.shared.v4.u32 [%0], {%1,%2,%3,%4};" :: "r"(a), "r"(x), "r"(y), "r"(z), "r"(w) : "memory");
}
__device__ __forceinline__ void st_async128(uint32_t a, uint32_t x, uint32_t y, uint32_t z, uint32_t w, uint32_t bar) {
    asm volatile("st.async.weak.shared::cluster.mbarrier::complete_tx::bytes.v4.b32 [%0], {%1,%2,%3,%4}, [%5];" :: "r"(a), "r"(x), "r"(y), "r"(z), "r"(w), "r"(bar) : "memory");
}
__device__ __forceinline__ void mbar_init(uint32_t b, uint32_t cnt) { asm volatile("mbarrier.init.shared::cta.b64 [%0], %1;" :: "r"(b), "r"(cnt) : "memory"); }
__device__ __forceinline__ void mbar_fence() { asm volatile("fence.mbarrier_init.release.cluster;" ::: "memory"); }
__device__ __forceinline__ void mbar_expect(uint32_t b, uint32_t bytes) { asm volatile("mbarrier.arrive.expect_tx.shared::cta.b64 _, [%0], %1;" :: "r"(b), "r"(bytes) : "memory"); }
__device__ __forceinline__ void mbar_arrive(uint32_t b) { asm volatile("mbarrier.arrive.shared::cta.b64 _, [%0];" :: "r"(b) : "memory"); }
#define CHINT ""
#define HINT ""
__device__ __forceinline__ void mbar_wait(uint32_t b, uint32_t parity = 0) {
    asm volatile("{ .reg .pred p; .reg .u32 n; mov.u32 n, 0;\n"
                 "LW: mbarrier.try_wait.parity.shared::cta.b64 p, [%0], %1" HINT "; @p bra LD; add.u32 n, n, 1; setp.lt.u32 p, n, 65536; @p bra LW; trap;\n"
                 "LD: }" :: "r"(b), "r"(parity) : "memory");
}
__device__ __forceinline__ void mbar_wait_cluster(uint32_t b) {
    asm volatile("{ .reg .pred p; .reg .u32 n; mov.u32 n, 0;\n"
                 "LW: mbarrier.try_wait.parity.acquire.cluster.shared::cta.b64 p, [%0], 0" CHINT "; @p bra LD; add.u32 n, n, 1; setp.lt.u32 p, n, 65536; @p bra LW; trap;\n"
                 "LD: }" :: "r"(b) : "memory");
}
__device__ __forceinline__ void tma2d(uint32_t dst, const CUtensorMap* m, int c0, int c1, uint32_t bar) {
    asm volatile("cp.async.bulk.tensor.2d.shared::cluster.global.mbarrier::complete_tx::bytes [%0], [%1, {%3, %4}], [%2];"
                 :: "r"(dst), "l"(m), "r"(bar), "r"(c0), "r"(c1) : "memory");
}
__device__ __forceinline__ void tma3d(uint32_t dst, const CUtensorMap* m, int c0, int c1, int c2, uint32_t bar) {
    asm volatile("cp.async.bulk.tensor.3d.shared::cluster.global.mbarrier::complete_tx::bytes [%0], [%1, {%3, %4, %5}], [%2];"
                 :: "r"(dst), "l"(m), "r"(bar), "r"(c0), "r"(c1), "r"(c2) : "memory");
}
__device__ __forceinline__ void tma4d(uint32_t dst, const CUtensorMap* m, int c0, int c1, int c2, int c3, uint32_t bar) {
    asm volatile("cp.async.bulk.tensor.4d.shared::cluster.global.mbarrier::complete_tx::bytes [%0], [%1, {%3, %4, %5, %6}], [%2];"
                 :: "r"(dst), "l"(m), "r"(bar), "r"(c0), "r"(c1), "r"(c2), "r"(c3) : "memory");
}
__device__ __forceinline__ void bulk_g2s(uint32_t dst, const void* src, uint32_t bytes, uint32_t bar) {
    asm volatile("cp.async.bulk.shared::cluster.global.mbarrier::complete_tx::bytes [%0], [%1], %2, [%3];"
                 :: "r"(dst), "l"(src), "r"(bytes), "r"(bar) : "memory");
}
__device__ __forceinline__ uint32_t mapa(uint32_t a, uint32_t rank) { uint32_t r; asm("mapa.shared::cluster.u32 %0, %1, %2;" : "=r"(r) : "r"(a), "r"(rank)); return r; }
__device__ __forceinline__ void prefetch_map(const CUtensorMap* m) { asm volatile("prefetch.tensormap [%0];" :: "l"(m) : "memory"); }
__device__ __forceinline__ void bar_sync(int id, int n) { asm volatile("bar.sync %0, %1;" :: "r"(id), "r"(n) : "memory"); }
__device__ __forceinline__ void bar_arrive(int id, int n) { asm volatile("bar.arrive %0, %1;" :: "r"(id), "r"(n) : "memory"); }
__device__ __forceinline__ uint32_t ldg16_if(bool c, const void* p) { uint32_t v; asm volatile("{ .reg .pred p; setp.ne.u32 p, %2, 0; @p ld.global.nc.u16 %0, [%1]; }" : "=r"(v) : "l"(p), "r"((uint32_t)c)); return v; }
__device__ __forceinline__ uint32_t ldg32_if(bool c, const void* p) { uint32_t v; asm volatile("{ .reg .pred p; setp.ne.u32 p, %2, 0; @p ld.global.nc.u32 %0, [%1]; }" : "=r"(v) : "l"(p), "r"((uint32_t)c)); return v; }
__device__ __forceinline__ uint32_t ld_rlx32(const void* p) { uint32_t v; asm volatile("ld.relaxed.gpu.global.u32 %0, [%1];" : "=r"(v) : "l"(p) : "memory"); return v; }
__device__ __forceinline__ uint4 ld_rlx128(const void* p) {
    uint4 v; asm volatile("ld.relaxed.gpu.global.v4.u32 {%0,%1,%2,%3}, [%4];" : "=r"(v.x), "=r"(v.y), "=r"(v.z), "=r"(v.w) : "l"(p) : "memory"); return v;
}
__device__ __forceinline__ void st_rlx32(void* p, uint32_t v) { asm volatile("st.relaxed.gpu.global.u32 [%0], %1;" :: "l"(p), "r"(v) : "memory"); }
__device__ __forceinline__ void stg128(void* p, uint32_t x, uint32_t y, uint32_t z, uint32_t w) {
    asm volatile("st.global.v4.u32 [%0], {%1,%2,%3,%4};" :: "l"(p), "r"(x), "r"(y), "r"(z), "r"(w) : "memory");
}
__device__ __forceinline__ void next_epoch(const Params& p, unsigned e) { if ((threadIdx.x & 31) == 0) p.s->epoch[blockIdx.x * 16 + (threadIdx.x >> 5)] = e + 1; }
__device__ __forceinline__ void sts128z_if(bool c, uint32_t a) { asm volatile("{ .reg .pred p; setp.ne.u32 p, %1, 0; @p st.shared.v4.u32 [%0], {%2,%2,%2,%2}; }" :: "r"(a), "r"((uint32_t)c), "r"(0) : "memory"); }
__device__ __forceinline__ void stg128z_if(bool c, void* a) { asm volatile("{ .reg .pred p; setp.ne.u32 p, %1, 0; @p st.global.v4.u32 [%0], {%2,%2,%2,%2}; }" :: "l"(a), "r"((uint32_t)c), "r"(0) : "memory"); }
__device__ __forceinline__ unsigned clock32() { unsigned c; asm volatile("mov.u32 %0, %clock;" : "=r"(c) :: "memory"); return c; }
__device__ __forceinline__ void until(unsigned t0, int c) { while ((int)(clock32() - t0) < c) { } }
__device__ __forceinline__ float sigmoidf_(float x) { return __fdividef(1.0f, 1.0f + __expf(-x)); }
__device__ __forceinline__ uint32_t key_tag(unsigned epoch) { return ((epoch & 15u) | 16u) << 11; }
__device__ __forceinline__ int key_row(uint32_t key) { return 2047 - (int)(key & 2047u); }
__device__ __forceinline__ uint32_t wait_sel(const Params& p, int s32, int r8, uint32_t tag, uint32_t k = 0) {
#pragma unroll 1
    for (int it = 0; !__all_sync(0xffffffffu, (k & 0xf800u) == tag); it++) {
        k = ld_rlx32(&p.s->sel[s32 * 64 + r8]);
        if (it > (1 << 20)) give_up();
    }
    return k;
}

struct cplx { float re, im; };
__device__ __forceinline__ cplx csq(cplx a) { cplx r; r.re = a.re * a.re - a.im * a.im; r.im = (a.re * a.im) * 2.f; return r; }
__device__ __forceinline__ cplx cexpk(float ar, float ai, float k) {
    float mag, s, c;
    asm("ex2.approx.ftz.f32 %0, %1;" : "=f"(mag) : "f"(ar * (k * 1.4426950408889634f)));
    const float r = ai * k;
    asm("sin.approx.ftz.f32 %0, %1;" : "=f"(s) : "f"(r));
    asm("cos.approx.ftz.f32 %0, %1;" : "=f"(c) : "f"(r));
    cplx o; o.re = mag * c; o.im = mag * s; return o;
}
struct h2c { uint32_t re, im; };
__device__ __forceinline__ h2c cmul_cd(h2c v, __half2 c, __half2 d) {
    const __half2 r = *(const __half2*)&v.re, i = *(const __half2*)&v.im;
    const __half2 x = __hfma2(__hneg2(i), d, __hmul2(r, c)), y = __hfma2(i, c, __hmul2(r, d));
    h2c o; o.re = *(const uint32_t*)&x; o.im = *(const uint32_t*)&y; return o;
}
__device__ __forceinline__ h2c cmul_s(h2c v, uint32_t s) { const __half2 h = *(const __half2*)&s; return cmul_cd(v, __low2half2(h), __high2half2(h)); }
__device__ __forceinline__ h2c cmul_sc(h2c v, uint32_t s) {
    const __half2 h = *(const __half2*)&s, c = __low2half2(h), d = __high2half2(h), r = *(const __half2*)&v.re, i = *(const __half2*)&v.im;
    const __half2 x = __hfma2(i, d, __hmul2(r, c)), y = __hfma2(__hneg2(r), d, __hmul2(i, c));
    h2c o; o.re = *(const uint32_t*)&x; o.im = *(const uint32_t*)&y; return o;
}
__device__ __forceinline__ h2c cmul_vc(h2c v, uint32_t s) {
    const __half2 h = *(const __half2*)&s, c = __low2half2(h), d = __high2half2(h), r = *(const __half2*)&v.re, i = *(const __half2*)&v.im;
    const __half2 x = __hfma2(i, d, __hmul2(r, c)), y = __hfma2(__hneg2(i), c, __hmul2(r, d));
    h2c o; o.re = *(const uint32_t*)&x; o.im = *(const uint32_t*)&y; return o;
}

constexpr int UT_HALF = 2240, UT_STRIDE = 4448;
constexpr int KT_T = 542, KT_C = 552, KT_D = 645, KT_BYTES = 720 * 4;
constexpr int VC_OFF = 80, VE_BASE = 1616;
constexpr int V_STRIDE = (1616 + 1024) * 4 + 80;
constexpr int KG_STAGE = 5248;
constexpr int Y_CS = 2080, Y_RS = 8 * Y_CS + 64;

constexpr int SC_RT = 0;
constexpr int SC_UT = 33408;
constexpr int SC_ST = SC_UT + 8 * UT_STRIDE;
constexpr int SC_KT = SC_ST + 8 * UT_STRIDE;
constexpr int SC_GT = SC_KT + 8 * KT_BYTES;
constexpr int SC_V = SC_GT + UT_STRIDE;
constexpr int SC_KG = SC_V + 4 * V_STRIDE;
constexpr int SC_MISC = SC_V + 8 * V_STRIDE;
static_assert(V_STRIDE % 128 == 16 && 8 * KG_STAGE <= 4 * V_STRIDE && 2 * Y_RS <= SC_UT && SC_UT % 128 == 0 && SC_ST % 128 == 0, "layout");
static_assert(SC_MISC % 16 == 0 && SC_MISC + 512 <= 232192, "layout");

__device__ __forceinline__ void window_task(uint32_t src, uint32_t d0, uint32_t d1, bool withE) {
    float S[35];
    {
        uint32_t w[20];
#pragma unroll
        for (int i = 0; i < 5; i++) {
            const uint4 v = lds128(src + ((i & 1) ? 0 : UT_HALF) + ((i + 1) >> 1) * 16);
            w[4 * i] = v.x; w[4 * i + 1] = v.y; w[4 * i + 2] = v.z; w[4 * i + 3] = v.w;
        }
        float s = 0.f; S[2] = 0.f;
#pragma unroll
        for (int i = 3; i < 26; i++) { s += (i & 1) ? bf_hi(w[i >> 1]) : bf_lo(w[i >> 1]); S[i] = s; }
#pragma unroll
        for (int i = 0; i < 8; i += 2)
            sts128((i & 4 ? d1 : d0) + (VC_OFF - 16) * 4 + 8 * (i & 2), pack_bf16(S[10 + i] - S[5 + i], S[5 + i] - S[2 + i]), pack_bf16(S[18 + i] - S[13 + i], S[13 + i] - S[10 + i]),
                   pack_bf16(S[11 + i] - S[6 + i], S[6 + i] - S[3 + i]), pack_bf16(S[19 + i] - S[14 + i], S[14 + i] - S[11 + i]));
        if (withE) {
#pragma unroll
            for (int i = 26; i < 35; i++) { s += (i & 1) ? bf_hi(w[i >> 1]) : bf_lo(w[i >> 1]); S[i] = s; }
#pragma unroll
            for (int i = 0; i < 8; i += 2)
                sts128((i & 4 ? d1 : d0) + VE_BASE * 4 + 8 * (i & 2), pack_bf16(S[19 + i] - S[12 + i], S[12 + i] - S[3 + i]), pack_bf16(S[27 + i] - S[20 + i], S[20 + i] - S[11 + i]),
                       pack_bf16(S[20 + i] - S[13 + i], S[13 + i] - S[4 + i]), pack_bf16(S[28 + i] - S[21 + i], S[21 + i] - S[12 + i]));
        }
    }
}

template <class F>
__device__ __forceinline__ void kgen(const uint32_t (&q)[8], uint32_t sb, int half, uint32_t stage, uint32_t pstage, int barid, int lane, uint32_t zero, uint32_t (&w)[12], F shadow) {
    const int t = lane & 3, mi = lane >> 3, r8 = lane & 7;
    {
        const uint32_t pAr = q[0], pAi = q[1], pBr = q[2], pBi = q[3], pCr = q[4], pCi = q[5], pDt = q[6], pD = q[7];
        const uint32_t wb = fresh(stage + lane * 16), za = fresh(stage + 5120 + ((lane >> 1) & 3) * 16 + mi * 4 + (lane & 1) * 2), zr = fresh(stage + 5120 + t * 16);
        const uint32_t oA = fresh(stage + (mi & 1) * 1024 + (mi >> 1) * 512 + r8 * 16), oB = fresh(stage + 2048 + mi * 512 + r8 * 16), oC = fresh(stage + 4096 + (mi & 1) * 512 + (mi >> 1) * 128 + r8 * 16);
        float acc[6][4];
#pragma unroll
        for (int a = 0; a < 6; a++) { acc[a][0] = acc[a][1] = acc[a][2] = acc[a][3] = 0.f; asm volatile("" : "+f"(acc[a][0]), "+f"(acc[a][1]), "+f"(acc[a][2]), "+f"(acc[a][3])); }
        shadow();
        sts32(zr, clock32());
        const float dt = rbf(__expf(bf_lo(pDt)));
        float ar = dt * bf_lo(pAr), ai = dt * bf_lo(pAi), ar1 = dt * bf_hi(pAr), ai1 = dt * bf_hi(pAi);
        float wr, wi, wr1, wi1;
        { const float br = dt * bf_lo(pBr), bi = dt * bf_lo(pBi), cr = bf_lo(pCr), ci = bf_lo(pCi); wr = cr * br - ci * bi; wi = cr * bi + ci * br; }
        { const float br = dt * bf_hi(pBr), bi = dt * bf_hi(pBi), cr = bf_hi(pCr), ci = bf_hi(pCi); wr1 = cr * br - ci * bi; wi1 = cr * bi + ci * br; }
        const uint32_t ex = max(__reduce_max_sync(0xffffffffu, __float_as_uint(fmaxf(fmaxf(fabsf(wr), fabsf(wi)), fmaxf(fabsf(wr1), fabsf(wi1))))) >> 23, 14u);
        const float scl = __uint_as_float((267u - ex) << 23);
        uint32_t W = pack_f16(wr * scl, wi * -scl);
        const uint32_t W1 = pack_f16(wr1 * scl, wi1 * -scl);
        if (threadIdx.x < 32) TSTAMP(20);

#pragma unroll 1
        for (int r = 0; r < 2; r++) {
            const cplx z1 = cexpk(ar, ai, 1.f), z64 = cexpk(ar, ai, 64.f);
            const cplx z2 = csq(z1), z4 = csq(z2), z8 = csq(z4), z16 = csq(z8), z32 = csq(z16);
            const cplx z128 = csq(z64), z256 = csq(z128), z512 = csq(z256);
            auto put = [&](int grp, h2c a, h2c b, h2c c, h2c d) { sts128(wb + grp * 1024, a.re, b.re, c.re, d.re); sts128(wb + grp * 1024 + 512, a.im, b.im, c.im, d.im); };
            {
                const uint32_t s4 = pack_f16(z4.re, z4.im), s256 = pack_f16(z256.re, z256.im), s512 = pack_f16(z512.re, z512.im);
                auto mix = [](h2c a, h2c b, uint32_t sel) { return h2c{__byte_perm(a.re, b.re, sel), __byte_perm(a.im, b.im, sel)}; };
                const h2c c10 = cmul_vc(h2c{pack_f16(z1.re, 1.f), pack_f16(z1.im, 0.f)}, W), c32 = cmul_sc(c10, pack_f16(z2.re, z2.im)), c54 = cmul_sc(c10, s4);
                put(2, c10, c32, c54, cmul_sc(c32, s4));
                const h2c d20 = cmul_sc(mix(c32, c10, 0x7632), s256), e04 = cmul_sc(mix(c10, c54, 0x7632), s512), f04 = cmul_sc(e04, s256);
                put(3, d20, cmul_sc(d20, s4), e04, f04);
                const h2c ef = mix(e04, f04, 0x5410), gh = cmul_sc(ef, s512), g8 = cmul_sc(gh, pack_f16(z8.re, z8.im));
                put(4, g8, cmul_sc(g8, s512), gh, ef);
            }
            {
                const uint32_t s32 = pack_f16(z32.re, z32.im), s64 = pack_f16(z64.re, z64.im), s128 = pack_f16(z128.re, z128.im);
                const h2c p0 = {pack_f16(1.f, z8.re), pack_f16(0.f, z8.im)}, p1 = cmul_s(p0, pack_f16(z16.re, z16.im)), p2 = cmul_s(p0, s32), p3 = cmul_s(p1, s32);
                put(0, p0, p1, p2, p3);
                put(1, cmul_s(p0, s64), cmul_s(p1, s64), cmul_s(p2, s64), cmul_s(p3, s64));
                sts16(za, s128); sts16(za + 64, s128 >> 16);
            }
            __syncwarp();
            {
                const uint32_t aA = fresh(oA), aB = fresh(oB), aC = fresh(oC), aZ = fresh(zr);
                const uint4 zc = lds128(aZ), zd = lds128(aZ + 64);
                const uint32_t zcs[4] = {zc.x, zc.y, zc.z, zc.w}, zds[4] = {zd.x, zd.y, zd.z, zd.w};
                uint32_t c[4];
#pragma unroll
                for (int k = 0; k < 4; k++) {
                    uint32_t a[4], b[4];
                    ldsm4t(a, aA + 128 * k); ldsm4t(b, aB + 128 * k);
                    if (!(k & 1)) ldsm4t(c, aC + 128 * k);
                    const h2c x = cmul_cd(h2c{a[0], a[2]}, *(const __half2*)&zcs[k], *(const __half2*)&zds[k]), y = cmul_cd(h2c{a[1], a[3]}, *(const __half2*)&zcs[k], *(const __half2*)&zds[k]);
                    mma_h(acc[0], a[0], a[1], a[2], a[3], b[0], b[1]);
                    mma_h(acc[1], a[0], a[1], a[2], a[3], b[2], b[3]);
                    mma_h(acc[2], a[0], a[1], a[2], a[3], c[2 * (k & 1)], c[2 * (k & 1) + 1]);
                    mma_h(acc[3], x.re, y.re, x.im, y.im, b[0], b[1]);
                    mma_h(acc[4], x.re, y.re, x.im, y.im, b[2], b[3]);
                    mma_h(acc[5], x.re, y.re, x.im, y.im, c[2 * (k & 1)], c[2 * (k & 1) + 1]);
                }
                asm volatile("" :: "f"(acc[0][0]), "f"(acc[1][0]), "f"(acc[2][0]), "f"(acc[3][0]), "f"(acc[4][0]), "f"(acc[5][0]) : "memory");
            }
            __syncwarp();
            ar = ar1; ai = ai1; W = W1;
        }
        if (threadIdx.x < 32) TSTAMP(21);
        const float i0 = __uint_as_float((ex + 243u) << 23);
        if (half) {
#pragma unroll
            for (int a = 0; a < 6; a++) sts128(wb + a * 512, __float_as_uint(acc[a][0]), __float_as_uint(acc[a][1]), __float_as_uint(acc[a][2]), __float_as_uint(acc[a][3]));
            sts32(stage + 3072, __float_as_uint(i0));
            bar_arrive(barid, 64);
        } else {
#pragma unroll
            for (int a = 0; a < 6; a++) { acc[a][0] *= i0; acc[a][1] *= i0; acc[a][2] *= i0; acc[a][3] *= i0; }
            if (lane == 0) acc[0][1] -= bf_lo(pD);
            sts32(zr, clock32());
            bar_sync(barid, 64);
            const uint32_t src = fresh(pstage);
            const float i1 = __uint_as_float(lds32(src + 3072));
#pragma unroll
            for (int a = 0; a < 6; a++) {
                const uint4 y = lds128(src + lane * 16 + a * 512);
                w[4 * (a % 3) + 2 * (a / 3)] = pack_bf16(fmaf(__uint_as_float(y.x), i1, acc[a][0]), fmaf(__uint_as_float(y.y), i1, acc[a][1]));
                w[4 * (a % 3) + 2 * (a / 3) + 1] = pack_bf16(fmaf(__uint_as_float(y.z), i1, acc[a][2]), fmaf(__uint_as_float(y.w), i1, acc[a][3]));
            }
        }
    }
}

__device__ __forceinline__ int swap01(int i) { return (i & ~3) | ((i & 1) << 1) | ((i >> 1) & 1); }
enum { BC_AUX = 0, BC_S = 5, BC_KG = 15 };

__device__ __forceinline__ void fetch_gates(const Params& p, int i, int lane, unsigned epoch, uint32_t dst) {
    const uint32_t par = (epoch & 1) ? 0x80008000u : 0u;
    uint4 v;
#pragma unroll 1
    for (int it = 0;; it++) {
        v = ld_rlx128(p.s->gate + 256 * i + 8 * lane);
        v.x ^= par; v.y ^= par; v.z ^= par; v.w ^= par;
        if (__all_sync(0xffffffffu, (v.x & v.y & v.z & v.w & 0x80008000u) == 0x80008000u)) break;
        if (it > (1 << 20)) give_up();
    }
    sts128(dst + (8 + 16 * i + (lane >> 1)) * 16, v.x, v.y, v.z, v.w);
}
__device__ __forceinline__ void store_rows(const CUtensorMap* m, uint32_t src, int col, int row) {
    asm volatile("cp.async.bulk.tensor.5d.global.shared::cta.bulk_group [%0, {%2, %3, %3, %3, %4}], [%1];" :: "l"(m), "r"(src), "r"(col), "r"(0), "r"(row) : "memory");
}

__device__ __forceinline__ void store_or_add(void* o, const uint32_t (&y)[4], uint32_t add) {
    asm volatile("{ .reg .pred p; setp.ne.u32 p, %5, 0; @!p st.global.v4.u32 [%0], {%1,%2,%3,%4}; @p red.relaxed.gpu.global.add.noftz.v4.bf16x2 [%0], {%1,%2,%3,%4}; }"
                 :: "l"(o), "r"(y[0]), "r"(y[1]), "r"(y[2]), "r"(y[3]), "r"(add) : "memory");
}

__device__ __forceinline__ void conv_aux(const Params& p, const CUtensorMap* mU, uint32_t sb, int aw, int lane, int bid, unsigned epoch) {
    const unsigned t0 = clock32();
    const int g = lane >> 2, t = lane & 3, mi = lane >> 3, r8 = lane & 7;
    const int rank = bid & 1, slab = bid >> 1;
    const uint32_t bar_y = sb + SC_MISC, bar_u = bar_y + 32, bar_v = bar_y + 40, bar_box = bar_y + 64 + 8 * aw, s_bm = bar_y + 128;
    if (elect()) {
        mbar_init(bar_box, 1); mbar_fence();
        mbar_expect(bar_box, 4096);
        if (UDELAY) until(t0, UDELAY);
        tma4d(sb + SC_RT + 4096 * aw, mU, 16 * slab, 0, 0, 16 * rank + 2 * aw, bar_box);
        mbar_init(bar_y + 8 * aw, aw < 4 ? 9 : aw == 5 ? 8 : 1); mbar_fence();
        if (aw < 5) mbar_expect(bar_y + 8 * aw, aw == 4 ? 16384 : 4096);
    }
    __syncwarp();
    asm volatile("barrier.cluster.arrive.relaxed.aligned;" ::: "memory");
    asm volatile("setmaxnreg.dec.sync.aligned.u32 88;");
    const uint32_t ut = sb + SC_UT + aw * UT_STRIDE;
    sts128(ut + (mi >> 1) * (SC_ST - SC_UT) + (mi & 1) * UT_HALF + r8 * 16, 0, 0, 0, 0);
    if (lane < 16) sts128(s_bm + lane * 16, 0, 0, 0, 0);
    {
        const uint32_t dst = sb + SC_UT + swap01(g) * UT_STRIDE + (8 + 64 * rank + 8 * aw + t) * 16;
        const uint32_t rdst = mapa(dst, rank ^ 1), rbar = mapa(bar_u, rank ^ 1);
        asm volatile("barrier.cluster.wait.acquire.aligned;" ::: "memory");
        mbar_wait(bar_box);
        if (aw == 0) TSTAMP(1);
        const uint32_t src = fresh(sb + SC_RT) + aw * 4096 + (8 * mi + 4 * (r8 & 1) + (r8 >> 1)) * 32 + ((rank ^ (r8 & 1)) << 4);
        uint32_t x[8][4];
#pragma unroll
        for (int i = 0; i < 4; i++) { ldsm4t(x[i], src + 1024 * i); ldsm4t(x[4 + i], (src ^ 16) + 1024 * i); }
        asm volatile("" :: "r"(x[0][0]), "r"(x[1][0]), "r"(x[2][0]), "r"(x[3][0]) : "memory");
#pragma unroll
        for (int i = 0; i < 4; i++) st_async128(rdst + (i & 1) * UT_HALF + 32 * (i & 2), x[4 + i][0], x[4 + i][1], x[4 + i][2], x[4 + i][3], rbar);
#pragma unroll
        for (int i = 0; i < 4; i++) sts128(dst + (i & 1) * UT_HALF + 32 * (i & 2), x[i][0], x[i][1], x[i][2], x[i][3]);
    }
    bar_sync(BC_AUX, 256);
    mbar_wait_cluster(bar_u);
    if (aw == 0) TSTAMP(2);
    {
        const uint32_t a = fresh(ut) + (mi & 1) * UT_HALF + (64 * (mi >> 1) + r8) * 16;
        uint4 v = lds128(a);
#pragma unroll
        for (int i = 1; i <= 8; i++) {
            const uint4 w = lds128(a + 128 * i);
            sts128(a + 128 * i + (SC_ST - SC_UT), badd2(v.x, w.x), badd2(v.y, w.y), badd2(v.z, w.z), badd2(v.w, w.w));
            v = w;
        }
    }
    bar_arrive(BC_S + aw, 64);
    if (aw == 0) TSTAMP(3);
    {
        uint32_t ws = sb + SC_UT + t * UT_STRIDE + (g + 6) * 16, wd = sb + SC_V + t * V_STRIDE + 64 * g, sw = 16 * (g & 2);
#pragma unroll 1
        for (int k = aw; k < 25; k += 8) {
            if (k - aw == 8) {
                bar_sync(BC_KG, 384);
                if (lane < 16) sts128(sb + SC_V + aw * V_STRIDE + lane * 16, 0, 0, 0, 0);
            }
            if (k == 24) { ws -= (g & 1) * 4 * UT_STRIDE + 16 * g; wd -= (g & 1) * 4 * V_STRIDE + 64 * g; sw = 0; }
            const int h = k >= 12, a = k - 12 * h;
            const uint32_t d = wd + h * 4 * V_STRIDE + 512 * a;
            window_task(fresh(ws) + h * 4 * UT_STRIDE + 128 * a, d + sw, d + (sw ^ 32), a < 8);
        }
    }
    if (aw == 0) TSTAMP(9);
    {
        if (aw >= 2) fetch_gates(p, aw, lane, epoch, sb + SC_GT + (lane & 1) * UT_HALF);
        __syncwarp();
        if (elect()) { mbar_arrive(bar_v); prefetch_map(mU + 4); }
        next_epoch(p, epoch);
        if (aw == 0) TSTAMP(4);
        if (aw == 7) {
            const int row = key_row(wait_sel(p, slab >> 1, r8, key_tag(epoch)));
            if (lane < 8) asm volatile("red.shared.or.b32 [%0], %1;" :: "r"(s_bm + (row >> 5) * 4), "r"(1u << (row & 31)) : "memory");
            TSTAMP(10);
        }
        bar_sync(BC_AUX, 256);
        const uint32_t src = sb + SC_RT + ((r8 >> 1) & 1) * Y_RS + (2 * mi + (r8 & 1)) * Y_CS + (2 * aw + (r8 >> 2)) * 16;
        const int L = 2 * aw + (t >> 1);
        const int row0 = 256 * rank + 128 * (g >> 2) + 32 * (L & 3) + 16 * (g & 1) + 8 * ((g >> 1) & 1) + (L >> 2);
        __nv_bfloat16* outp = p.out + (size_t)row0 * DM + 16 * slab + 8 * (t & 1);
        const uint32_t stg = sb + SC_ST + 4096 * aw, so = (g >> 1) * 256 + (t >> 1) * 64 + (g & 1) * 32 + (t & 1) * 16;
#pragma unroll 1
        for (int s = 1; s < 4; s++) {
            const uint32_t bm = lds32(fresh(s_bm) + (16 * s + (row0 >> 5)) * 4) >> (row0 & 31);
            const bool routed = __any_sync(0xffffffffu, bm & 0x11u);
            if (aw == s) mbar_wait_cluster(bar_y + 8 * s);
            bar_sync(BC_AUX, 256);
            const uint32_t sf = fresh(src) + 512 * s;
            uint32_t y[2][4];
            ldsm4t(y[0], sf); ldsm4t(y[1], sf + 256);
            if (routed) {
#pragma unroll
                for (int k = 0; k < 2; k++) store_or_add(outp + (size_t)(512 * s + 4 * k) * DM, y[k], bm & (1u << (4 * k)));
            } else {
                sts128(stg + so + 1024 * s, y[0][0], y[0][1], y[0][2], y[0][3]); sts128(stg + so + 1024 * s + 128, y[1][0], y[1][1], y[1][2], y[1][3]);
                asm volatile("fence.proxy.async.shared::cta;" ::: "memory");
                __syncwarp();
                if (elect()) store_rows(mU + 4, stg + 1024 * s, 16 * slab, 512 * s + 256 * rank + 64 * (aw & 1) + (aw >> 1));
            }
            if (aw == 0) TSTAMP(16 + s);
        }
        if (elect()) { asm volatile("cp.async.bulk.commit_group;" ::: "memory"); asm volatile("cp.async.bulk.wait_group.read 0;" ::: "memory"); }
        if (aw == 0) TFLUSH();
    }
}

__device__ __forceinline__ void publish_k(uint4* kp, const uint32_t (&w)[12], int n, unsigned epoch) {
#pragma unroll
    for (int i = 0; i < n; i++) asm volatile(PUBST ".v4.u32 [%0], {%1,%2,%3,%4};" :: "l"(kp + 32 * i), "r"(w[3 * i]), "r"(w[3 * i + 1]), "r"(w[3 * i + 2]), "r"(~epoch));
}
template <bool FULL>
__device__ __forceinline__ void k_tables(uint32_t kt, int lane, const uint32_t (&w)[12]) {
    const int g = lane >> 2, t = lane & 3, mi = lane >> 3, r8 = lane & 7;
    uint32_t x3 = w[7], re[4], rx[4];
#pragma unroll
    for (int i = 0; i < 4; i++) {
        re[i] = __shfl_sync(0xffffffffu, w[i], lane + 31);
        rx[i] = __shfl_sync(0xffffffffu, w[4 + i], lane + (i == 0 && lane == 29 ? 5 : 1 + 2 * t));
    }
    if (FULL) {
        asm volatile("stmatrix.sync.aligned.m8n8.x4.trans.shared.b16 [%0], {%1,%2,%3,%4};"
                     :: "r"(kt + (r8 < 4 ? (KT_D + 7) * 4 + 64 * r8 + 16 * mi : 716 * 4)), "r"(w[8]), "r"(w[9]), "r"(w[10]), "r"(w[11]) : "memory");
        if (lane == 2) {
            sts32(kt + (KT_C + 78) * 4, w[8] & 0xffffu);
            sts128(kt + (KT_T + 2) * 4, 0, w[8] & 0xffffu, __byte_perm(w[8], 0, 0x1010), w[8] << 16);
        }
        if (lane == 29) x3 = bsub2(x3, rx[0] & 0xffffu);
    }
#pragma unroll
    for (int i = 0; i < 4; i++) {
        sts64(kt + (16 + 64 * i) * 4 + 8 * lane, __byte_perm(w[i], lane ? re[i] : i ? re[i - 1] : 0, 0x5432), w[i]);
        const uint32_t x = i < 3 ? w[4 + i] : x3, aa = __byte_perm(x, 0, 0x3232);
        if (t < 2) sts128(kt + (272 + 64 * i + 8 * g + 4 * t) * 4, i == 0 && lane == 0 ? __byte_perm(x, re[3], 0x5432) : aa, aa, x,
                          __byte_perm(lane != 29 ? rx[i] : i < 3 ? rx[(i + 1) & 3] : FULL ? 0 : rx[0] << 16, x, 0x5432));
        else if (FULL) sts32(kt + (KT_C - 50 + 8 * i + 32 * t + g) * 4, x);
    }
}

__device__ __forceinline__ void conv_main(const Params& p, uint32_t sb, int warp, int lane0, int bid, unsigned epoch, uint32_t (&w)[12]) {
    asm volatile("setmaxnreg.inc.sync.aligned.u32 168;");
    const int lane = __shfl_sync(0xffffffffu, lane0, lane0);
    const int g = lane >> 2, t = lane & 3, mi = lane >> 3, r8 = lane & 7;
    const int rank = bid & 1;
    const uint32_t bar_y = sb + SC_MISC, bar_v = bar_y + 40;
    next_epoch(p, epoch);
    if (warp < 4) {
        asm volatile("" :: "r"(w[0]), "r"(w[2]), "r"(w[4]), "r"(w[6]), "r"(w[8]), "r"(w[10]) : "memory");
        bar_arrive(BC_KG, 384);
    } else {
        const uint4* src = p.s->kp + (8 * bid + warp) * 128 + lane0;
#pragma unroll 1
        for (int it = 0;; it++) {
            uint32_t bad = 0;
#pragma unroll
            for (int i = 0; i < 4; i++) { const uint4 v = ld_rlx128(src + 32 * i); w[3 * i] = v.x; w[3 * i + 1] = v.y; w[3 * i + 2] = v.z; bad |= v.w ^ ~epoch; }
            const bool ok = __all_sync(0xffffffffu, bad == 0);
            if (ok) break;
            if (it > (1 << 20)) give_up();
        }
    }
    if ((warp & 3) == 0) TSTAMP(5 + (warp >> 2));
    k_tables<true>(sb + SC_KT + warp * KT_BYTES, lane0, w);
    asm volatile("barrier.cluster.wait.acquire.aligned;" ::: "memory");
    bar_sync(BC_S + swap01(warp), 64);
    __syncwarp();
    if ((warp & 3) == 0) TSTAMP(7 + (warp >> 2));
    {
        const uint32_t ut = fresh(sb + SC_UT) + swap01(warp) * UT_STRIDE, kt = fresh(sb + SC_KT) + warp * KT_BYTES;
        uint32_t u1 = ut + (mi & 1) * UT_HALF + (8 + r8) * 16 + (mi >> 1) * 128;
        auto dup = [&](uint32_t v) { return v ^ p.zero; };
        uint32_t kp = kt + (16 + g - 2 * t) * 4;
        float acc[16][4];
        {
            const uint32_t c0 = lds32(kp + 2048), c1 = lds32(kp + 2080), c2 = lds32(kp + 2016), c3 = dup(c0);
            const uint32_t e0 = lds32(kp + (KT_T - 16) * 4), e1 = lds32(kp + (KT_T - 8) * 4), e2 = lds32(kp + (KT_T - 24) * 4), e3 = dup(e0);
            const uint32_t f0 = dup(e1), f1 = lds32(kp + KT_T * 4);
            const uint32_t uo = ut + UT_HALF + (7 + lane) * 16;
#pragma unroll
            for (int i = 0; i < 16; i++) { acc[i][0] = acc[i][1] = acc[i][2] = acc[i][3] = 0.f; }
#pragma unroll
            for (int mu = 0; mu < 8; mu += 4) {
                uint32_t b[4];
                ldsm4(b, uo + 128 * mu);
#pragma unroll
                for (int k = 0; k < 4; k++) mma_bf8(acc[mu + 8 + k], f0, f1, b[k]);
            }
#pragma unroll
            for (int mu = 0; mu < 12; mu += 2) {
                uint32_t b[4];
                ldsm4(b, u1 + 128 * mu);
                mma_bf(acc[mu + 4], c0, c1, c2, c3, b[0], b[1]);
                mma_bf(acc[mu + 5], c0, c1, c2, c3, b[2], b[3]);
                if (mu < 8) { mma_bf(acc[mu + 8], e0, e1, e2, e3, b[0], b[1]); mma_bf(acc[mu + 9], e0, e1, e2, e3, b[2], b[3]); }
            }
        }
        {
            float M[8][4];
#pragma unroll
            for (int i = 0; i < 8; i++) { M[i][0] = M[i][1] = M[i][2] = M[i][3] = 0.f; }
            uint32_t s[8][4], a3[4];
            const uint32_t kb = kp, ub = dup(u1), uc = u1 + (mi >> 1) * 128;
            auto frag = [&](uint32_t (&a)[4], uint32_t x) { a[0] = lds32(x); a[1] = lds32(x + 32); a[2] = lds32(x - 32); a[3] = dup(a[0]); };
            frag(a3, kp + 1536);
#pragma unroll
            for (int i = 1; i < 8; i++) ldsm4(s[i], u1 + (SC_ST - SC_UT) + 256 * i);
            __syncwarp();
            uint32_t ko = 0, uo = 0;
            const uint32_t pub = bid >= 48 ? PUBY : PUBIT;
#pragma unroll 1
            for (uint32_t n = warp < 4 ? pub : 8;; n = 8 - pub) {
#pragma unroll 1
            for (; n; n--) {
                uint32_t a2[4], a1[4], a0[4], b[4][4];
                ko = fresh(ko); uo = fresh(uo);
                kp = kb + ko; u1 = ub + uo;
                const uint32_t up = uc + uo;
                ko += 64; uo -= 16;
                frag(a2, kp + 1024);
#pragma unroll
                for (int i = 1; i < 4; i++) ldsm4(b[i], up + 512 * i);
                asm("ldmatrix.sync.aligned.m8n8.x2.shared.b16 {%0,%1}, [%2];" : "=r"(b[0][2]), "=r"(b[0][3]) : "r"(up + 256));
                frag(a1, kp + 512); frag(a0, kp);
                kp += 64; u1 -= 16;
#pragma unroll
                for (int i = 1; i < 7; i++) mma_bf(acc[2 * i + 2], a3[0], a3[1], a3[2], a3[3], s[i][0], s[i][1]);
#pragma unroll
                for (int e = 0; e < 4; e++) a3[e] = bsub2(a2[e], a3[e]);
#pragma unroll
                for (int i = 1; i < 7; i++) mma_bf(acc[2 * i + 3], a2[0], a2[1], a2[2], a2[3], s[i][2], s[i][3]);
                ldsm4(s[1], u1 + (SC_ST - SC_UT) + 256);
#pragma unroll
                for (int i = 1; i < 7; i++) mma_bf(M[i + 1], a3[0], a3[1], a3[2], a3[3], b[i >> 1][2 * (i & 1)], b[i >> 1][2 * (i & 1) + 1]);
                frag(a3, kp + 1536);
#pragma unroll
                for (int i = 2; i < 8; i++) mma_bf(acc[2 * i], a1[0], a1[1], a1[2], a1[3], s[i][0], s[i][1]);
#pragma unroll
                for (int e = 0; e < 4; e++) a1[e] = bsub2(a0[e], a1[e]);
#pragma unroll
                for (int i = 2; i < 8; i++) { mma_bf(acc[2 * i + 1], a0[0], a0[1], a0[2], a0[3], s[i][2], s[i][3]); ldsm4(s[i], u1 + (SC_ST - SC_UT) + 256 * i); }
#pragma unroll
                for (int i = 2; i < 8; i++) mma_bf(M[i], a1[0], a1[1], a1[2], a1[3], b[i >> 1][2 * (i & 1)], b[i >> 1][2 * (i & 1) + 1]);
            }
            if (ko == 512) break;
            publish_k(p.s->kp + (8 * bid + warp) * 128 + lane, w, 3, epoch);
            }
            u1 = ub;
#pragma unroll
            for (int i = 2; i < 8; i++)
#pragma unroll
                for (int c = 0; c < 4; c++) { acc[2 * i][c] += M[i][c]; acc[2 * i + 1][c] -= M[i][c]; }
        }
        if ((warp & 3) == 0) TSTAMP(11 + (warp >> 2));
        mbar_wait(bar_v);
        const uint32_t vt = fresh(sb + SC_V) + swap01(warp) * V_STRIDE;
        const uint32_t g1 = fresh(u1) - ut + sb + SC_GT;
        const uint32_t ydst = sb + SC_RT + rank * Y_RS + warp * Y_CS + lane * 16;
        const uint32_t ydr = mapa(ydst, rank ^ 1), ybr = mapa(bar_y, rank ^ 1);
        auto stairs = [&](auto R) {
        uint32_t ug[2][2][4];
        auto ld_ug = [&](int i) { ldsm4t(ug[i & 1][0], u1 + 256 * i); ldsm4t(ug[i & 1][1], g1 + 256 * i); };
        auto ship = [&](int i) {
            const uint32_t (&u)[4] = ug[i & 1][0], (&gg)[4] = ug[i & 1][1];
            const uint32_t y0 = gmix(gg[0], acc[2 * i][0], acc[2 * i][1], u[0]), y1 = gmix(gg[1], acc[2 * i][2], acc[2 * i][3], u[1]);
            const uint32_t y2 = gmix(gg[2], acc[2 * i + 1][0], acc[2 * i + 1][1], u[2]), y3 = gmix(gg[3], acc[2 * i + 1][2], acc[2 * i + 1][3], u[3]);
            if ((i & 1) != R.value) st_async128(ydr + 512 * (i >> 1), y0, y1, y2, y3, ybr + 8 * (i >> 1));
            else asm volatile("{ .reg .pred q; setp.eq.u32 q, %6, 0; st.shared.v4.u32 [%0], {%2,%3,%4,%5}; bar.warp.sync 0xffffffff; @q mbarrier.arrive.shared::cta.b64 _, [%1]; }"
                              :: "r"(ydst + 512 * (i >> 1)), "r"(bar_y + 8 * (i >> 1)), "r"(y0), "r"(y1), "r"(y2), "r"(y3), "r"(lane) : "memory");
        };
        const uint32_t VD = vt + (VC_OFF - 400 - 16 * t) * 4 + (8 * g ^ 16 * (-t & 2)), VD2 = vt + (VC_OFF - 415 - 16 * t) * 4 + (8 * g ^ 16 * (~t & 2));
        uint2 bd[10];
        uint32_t x[2][4][4];
        auto ld4 = [&](uint32_t (&v)[4], int dl) { const uint2 w = lds64(VD + 256 * dl); v[0] = w.x; v[1] = w.y; v[2] = lds32(VD2 + 256 * dl); v[3] = dup(w.x); };
        auto mm4 = [&](const uint32_t (&v)[4], int dl) {
#pragma unroll
            for (int s = dl & 1; s < 10; s += 2) if ((dl + s) / 2 >= 4 && (dl + s) / 2 < 16) mma_bf(acc[(dl + s) / 2], v[0], v[1], v[2], v[3], bd[s].x, bd[s].y);
        };
        const uint32_t KE = kt + (KT_D + g + t) * 4, VE = vt + (VE_BASE - 912 - 16 * t) * 4 + (8 * g ^ 16 * (~t & 2));
        uint32_t b0[8], b1[8];
        auto ld8 = [&](uint32_t (&v)[4], int dl) { const uint2 w = lds64(VE + 512 * dl), z = lds64(VE + 512 * dl - 256); v[0] = w.x; v[1] = w.y; v[2] = z.x; v[3] = z.y; };
        auto mm8 = [&](const uint32_t (&v)[4], int dl, int lo, int hi) {
#pragma unroll
            for (int s = 0; s < 8; s++) if (dl + s >= lo && dl + s < hi) mma_bf(acc[dl + s], v[0], v[1], v[2], v[3], b0[s], b1[s]);
        };
        ld4(x[0][0], 6);
#pragma unroll
        for (int s = 0; s < 10; s++) bd[s] = lds64(kt + (KT_C + 2 * g + 2 * t + 8 * s) * 4);
        mm4(x[0][0], 6);
        uint32_t e[4][4];
#pragma unroll
        for (int k = 1; k < 6; k++) {
#pragma unroll
            for (int j = 0; j < 4; j++) ld4(x[k & 1][j], 4 * k + 3 + j);
            ld_ug(k + 1);
            if (k == 3) {
#pragma unroll
                for (int s = 0; s < 8; s++) { b0[s] = lds32(KE + 32 * s); b1[s] = lds32(KE + 32 * s + 16); }
            }
            if (k > 1) ship(k);
#pragma unroll
            for (int j = 0; j < 4; j++) {
                mm4(x[k & 1][j], 4 * k + 3 + j);
                if (k == 3) { uint32_t v[4], z[4]; ld8(e[j], 8 + j); ld8(v, 12 + j); ld4(z, 30 - j); mm8(v, 12 + j, 12, 16); mm8(e[j], 8 + j, 8, 12); mm4(z, 30 - j); }
                if (k == 5) { ld8(e[j], 8 + j + p.zero); mm8(e[j], 8 + j, 12, 16); }
            }
        }
        ld_ug(7);
        ship(7 - R.value); ship(6 + R.value);
        };
        if (rank) stairs(std::integral_constant<int, 1>()); else stairs(std::integral_constant<int, 0>());
        if ((warp & 3) == 0) TSTAMP(14 + (warp >> 2)); else TSTAMP(21 + warp);
    }
}

constexpr int SF_WD = 73728;
constexpr int SF_RED = 49152;
constexpr int MU_HALF = 640, MU_STRIDE = 1344, SM_RAW = 98304, SM_UT = SM_RAW + 16384, SM_G = SM_UT + 16 * MU_STRIDE, SM_Y = 196608, SM_KT = 138880, SM_KW = SM_G - 49152;
constexpr int SF_XS = 221184;
constexpr int SF_MISC = SF_XS + 8 * 1168;
constexpr int SF_KG = SF_MISC - 10 * KG_STAGE;
constexpr int SF_WR = SF_KG - 2304;
constexpr int FB_X = 64, FB_KDONE = 72, FB_KEYS = 80, FB_FREE = 88  , FB_W = 104, FB_D = FB_W + 72, FB_MU = FB_D + 96, FB_MG = FB_MU + 8, FB_MT = FB_MU + 16, FS_PART = 512, FS_TOK = 896, FS_BM = 1024;
enum { BAR_F = 6, BAR_R = 7, BAR_GU = 8, BAR_RED = 9, BAR_R2 = 10, BAR_X = 11, BAR_G = 12  , BAR_M = 15 };
static_assert(SF_KG % 128 == 0 && NPRE <= 8 && SM_KT + 4 * 2112 <= 147456 && SM_G + MU_STRIDE <= SF_WR - 4 * 9216 && SM_KW + 6 * 2112 >= SM_RAW && SM_KW + 12 * 2112 <= SM_UT, "layout");

__device__ __forceinline__ int mini_ch0(int f) { return f < NW ? 16 * (f - 12) : 32 * (f - NW); }

__device__ __forceinline__ void ffn_front(const Params& p, const CUtensorMap* maps, uint32_t sb, int warp, int lane, int f, unsigned epoch) {
    const unsigned t0 = clock32();
    const int g = lane >> 2, t = lane & 3, mi = lane >> 3, r8 = lane & 7;
    const bool isx = f < NX;
    const int nrw = f < 8 ? 6 : 4, r0 = f < 8 ? 48 * f : 128 + 32 * f;
    const int rw = warp < 12 ? 13 - warp : warp ^ (warp < 14 ? 10 : 15);
    const uint32_t bar_row = sb + SF_MISC  , bar_x = bar_row + FB_X;
    const uint32_t s_part = bar_row + FS_PART  , s_tok = bar_row + FS_TOK  ;
    const uint32_t rows = sb + SF_WR - 9216 * (rw + 1);
    {
#pragma unroll 1
        for (int i = warp < 10 ? 30 : warp - 10; i < 29; i += 6) if (elect()) mbar_init(bar_x + 8 * i, 1 << max(i - 26, 0));
        const uint32_t bytes = rw < 6 ? 9216 : 1152, dst = rw < 6 ? rows : sb + SF_WR + (rw & 1) * 1152;
        const __nv_bfloat16* src = rw < 6 ? p.u + (size_t)(r0 + 8 * rw) * DM : (rw & 1) ? p.gatew : p.wr;
        if (elect()) { mbar_init(bar_row + 8 * rw, 1); mbar_fence(); mbar_expect(bar_row + 8 * rw, bytes); }
        if (rw < nrw) until(t0, RDELAY);
        if (rw < nrw || rw >= 6) { if (elect()) bulk_g2s(dst, src, bytes, bar_row + 8 * rw); }
    }
    uint4* const kdst = p.s->keys + (lane >> 1) * 128 + 2 * f + (lane & 1);
    if (warp == 13) {
        stg128(kdst, 0, 0, 0, 0);
        sts32(s_part + 64 + lane * 4, 0); sts32(bar_row + FS_BM + lane * 4, 0);
        if (lane < 8 && isx && !(f & 1)) st_rlx32(&p.s->sel[32 * f + lane], 0);
    }
    __syncwarp();
    bar_sync(BAR_F, f < 12 ? 256 : 192);
    bar_arrive(0, NTHR);
    if (warp == 15) TSTAMP(1);

    if (warp == 12) {
        if (lane < 22) mbar_expect(bar_row + FB_W + 8 * lane, lane < 9 ? 24576 : lane < 21 ? 12288 : f < NW ? 16384 : 32768);
        if (elect()) { prefetch_map(maps + 1); prefetch_map(maps + 2); prefetch_map(maps + (isx ? 3 : 5)); }
        unsigned tb = t0 + WDELAY;
        auto pieces = [&](int n, int end, uint32_t dst) {
#pragma unroll 1
            for (; n < end; n++, dst += 12288) {
                until(tb, 0); tb += WGAP;
                if (elect()) tma3d(dst, maps + 1 + (n & 1), 0, 64 * (n >> 1), 3 * f, bar_row + FB_W + 8 * (n >> 1));
            }
        };
        if (!isx) {
            until(tb, MDELAY);
#pragma unroll 1
            for (int k = f >= NW; k >= 0; k--) if (elect()) tma4d(sb + SM_RAW - 49152 * k, maps + 5, mini_ch0(f) + 16 * k, 0, 0, 0, bar_row + FB_MU);
            if (f >= NW) return;
        }
#pragma unroll 1
        for (int i = 0; i < 4; i++) {
            if (i == 1) { mbar_wait(bar_row + FB_KEYS); mbar_wait(bar_row + FB_KDONE); tb = clock32() + RESUME; }
            if (i == 3) mbar_wait(bar_row + FB_FREE);
            const int n = ((0x0c080000 + NPRE * 256) >> (8 * i)) & 255;
            pieces(n, ((0x120c0800 + NPRE) >> (8 * i)) & 255, sb + 12288 * (((0x000c0000 + NPRE * 256) >> (8 * i)) & 255));
        }
        TSTAMP(12);
        if (isx) {
#pragma unroll 1
            for (int i = 0; i < 12; i++) {
                const int n = (0x987610ba5432ull >> (4 * i)) & 15;
                if (i == 6) mbar_wait(bar_row + FB_FREE + 8);
                until(tb, 0); tb += DGAP;
                if (elect()) tma2d(sb + SF_WD + n * 12288, maps + 3, 32 * (f >> 1), 2304 * (f & 1) + 192 * n, bar_row + FB_D + 8 * n);
            }
            TSTAMP(13);
        }
    } else if (warp == 13) {
        const uint32_t tag = key_tag(epoch), par = (epoch & 1) ? 0u : 0x8000u;
        bar_sync(BAR_R, 32 * (nrw + 1));
        TSTAMP(3);
        {
            const uint32_t sg = fresh(s_part) + 192 + lane * 4;
            const uint32_t gb = pack_bf16(sigmoidf_(rbf(__uint_as_float(lds32(sg)))), sigmoidf_(rbf(__uint_as_float(lds32(sg + 128))))) | par | (par << 16);
            asm volatile("st.relaxed.gpu.global.u16 [%0], %1;" :: "l"(p.s->gate + r0 + lane), "h"((unsigned short)gb) : "memory");
            if (nrw > 4 && lane < 16) asm volatile("st.relaxed.gpu.global.u16 [%0], %1;" :: "l"(p.s->gate + r0 + 32 + lane), "h"((unsigned short)(gb >> 16)) : "memory");
        }
        bar_sync(BAR_R2, 32 * (nrw + 1));
        {
            const uint4 v = lds128(fresh(s_tok) + (lane & 1) * 16);
            asm volatile("st.relaxed.gpu.global.v4.u32 [%0], {%1,%2,%3,%4};" :: "l"(kdst), "r"(v.x | tag), "r"(v.y | tag), "r"(v.z | tag), "r"(v.w | tag) : "memory");
        }
        TSTAMP(4);
        if (lane == 0) { mbar_arrive(bar_row + FB_KEYS); mbar_expect(bar_x, 8 * 1152); }
        if (f >= NW) return;
        uint32_t k[16];
        const uint4* src = p.s->keys + (f & 15) * 128 + lane;
#pragma unroll 1
        for (int it = 0;; it++) {
            uint32_t bad = 0;
#pragma unroll
            for (int i = 0; i < 4; i++) {
                const uint4 x = ld_rlx128(src + (i < 3 || lane < 24 ? 32 * i : 64));
                k[i] = x.x; k[4 + i] = x.y; k[8 + i] = x.z; k[12 + i] = x.w;
                bad |= x.x ^ tag;
            }
            const bool ok = __all_sync(0xffffffffu, (bad & 0xf800u) == 0);
            if (ok) break;
            if (it > (1 << 20)) give_up();
        }
        TSTAMP(5);
        uint32_t key = 0;
#pragma unroll 2
        for (int r = 0; r < 8; r++) {
            const uint32_t m = __reduce_max_sync(0xffffffffu, max(max(k[0], k[1]), max(k[2], k[3])));
#pragma unroll
            for (int i = 0; i < 4; i++) {
                const bool pop = k[i] == m;
                k[i] = pop ? k[4 + i] : k[i]; k[4 + i] = pop ? k[8 + i] : k[4 + i]; k[8 + i] = pop ? k[12 + i] : k[8 + i]; k[12 + i] = pop ? 0 : k[12 + i];
            }
            if (r8 == r) key = m;
        }
        const int row = key_row(key);
        sts32(s_tok + r8 * 8, row);
        bar_arrive(BAR_X, 160);
        TSTAMP(6);
        if (isx) {
            if (!(f & 1)) {
                __nv_bfloat16* o = p.out + (size_t)row * DM + 16 * f + 8 * mi;
                asm volatile("st.relaxed.gpu.global.v4.u32 [%0], {%1,%1,%1,%1};" :: "l"(o), "r"(0) : "memory");
                if (__any_sync(0xffffffffu, ld_rlx32(o) != 0)) give_up();
                if (lane < 8) st_rlx32(&p.s->sel[32 * f + lane], key);
            } else wait_sel(p, f >> 1, r8, tag);
            uint32_t gb;
#pragma unroll 1
            for (int it = 0;; it++) {
                asm volatile("ld.relaxed.gpu.global.u16 %0, [%1];" : "=r"(gb) : "l"(p.s->gate + row) : "memory");
                gb ^= par;
                if (!(gb & 0x8000u)) break;
                if (it > (1 << 20)) give_up();
            }
            const uint32_t rb = key ^ 0x80000000u, rv = (rb ^ (((int)rb >> 31) & 0x7fff0000u)) & 0xffff0000u;
            sts32(s_tok + r8 * 8 + 4, __float_as_uint(rbf(1.0f - bf_lo(gb)) * rbf(sigmoidf_(__uint_as_float(rv)))));
            __syncwarp();
            TSTAMP(7);
            bar_arrive(BAR_RED, 416);
        }
    } else {
        if (rw < nrw) {
            float c[3][4];
#pragma unroll
            for (int i = 0; i < 3; i++) { c[i][0] = c[i][1] = c[i][2] = c[i][3] = 0.f; }
            mbar_wait(bar_row + 48); mbar_wait(bar_row + 56);
            const uint32_t b = fresh(sb + SF_WR) + (g & 1) * 1152 + (g >> 2) * 64 + t * 16 + (g & 2) * 2;
            uint32_t w[18][2];
#pragma unroll
            for (int kb = 0; kb < 18; kb++) { const uint32_t o = ((kb & 1) ? b ^ 64 : b) + 128 * (kb >> 1); w[kb][0] = lds32(o); w[kb][1] = lds32(o + 8); }
            mbar_wait(bar_row + 8 * rw);
            if (warp == 15) TSTAMP(2);
            const uint32_t a = fresh(rows) + g * 1152 + (g & 1) * 64 + t * 16;
#pragma unroll
            for (int kb = 0; kb < 18; kb++) {
                const uint4 x = lds128(((kb & 1) ? a ^ 64 : a) + 128 * (kb >> 1));
                mma_bf(c[kb % 3], x.x, x.y, x.z, x.w, w[kb][0], w[kb][1]);
            }
            const float sr = c[0][0] + c[1][0] + c[2][0] + __shfl_down_sync(0xffffffffu, c[0][2] + c[1][2] + c[2][2], 1);
            const float sg = c[0][1] + c[1][1] + c[2][1] + __shfl_down_sync(0xffffffffu, c[0][3] + c[1][3] + c[2][3], 1);
            const uint32_t rb = pack_bf16(0.f, sr);
            if (t == 2 * (g & 1)) {
                sts32(s_part + (8 * rw + g) * 4, (rb ^ (((int)rb >> 31) & 0x7fff0000u) ^ 0x80000000u) | (uint32_t)(2047 - r0 - 8 * rw - g));
                sts32(s_part + 192 + (8 * rw + g) * 4, __float_as_uint(sg));
            }
            __syncwarp();
            bar_sync(BAR_R, 32 * (nrw + 1));
            const uint32_t sk = fresh(s_part), kk = lds32(sk + (8 * rw + r8) * 4);
            int n = 0;
#pragma unroll
            for (int i = 0; i < 3; i++) { const uint4 v = lds128(sk + mi * 48 + 16 * i); n += (v.x > kk) + (v.y > kk) + (v.z > kk) + (v.w > kk); }
            n += __shfl_xor_sync(0xffffffffu, n, 8); n += __shfl_xor_sync(0xffffffffu, n, 16);
            if (n < 8) sts32(s_tok + 4 * n, kk);
            __syncwarp();
            bar_arrive(BAR_R2, 32 * (nrw + 1));
        }
    }
}

__device__ __forceinline__ void ffn_work(const Params& p, uint32_t sb, int warp, int lane, int f, unsigned epoch) {
    const int g = lane >> 2, t = lane & 3, mi = lane >> 3, r8 = lane & 7;
    const bool isx = f < NX;
    const uint32_t bar_x = sb + SF_MISC + FB_X, bar_free = sb + SF_MISC + FB_FREE, bar_w = sb + SF_MISC + FB_W, bar_d = sb + SF_MISC + FB_D, s_tok = sb + SF_MISC + FS_TOK;
    uint32_t fr[24][4];
    auto pin = [&] {
#pragma unroll
        for (int i = 0; i < 24; i += 8) asm volatile("" :: "r"(fr[i][0]), "r"(fr[i + 1][0]), "r"(fr[i + 2][0]), "r"(fr[i + 3][0]), "r"(fr[i + 4][0]), "r"(fr[i + 5][0]), "r"(fr[i + 6][0]), "r"(fr[i + 7][0]) : "memory");
    };
    {
        const int j = (unsigned)(warp - 4) < 6, w = warp - (j ? 4 : warp < 4 ? 0 : 6);
        float ag[2][4], au[2][4];
#pragma unroll
        for (int i = 0; i < 2; i++) { ag[i][0] = ag[i][1] = ag[i][2] = ag[i][3] = 0.f; au[i][0] = au[i][1] = au[i][2] = au[i][3] = 0.f; }
        const uint32_t wb = sb + (w >> 1) * 4096 + (r8 + 8 * (mi >> 1)) * 64 + (((2 * (w & 1) + (mi & 1)) ^ (r8 >> 1)) << 4);
        const uint32_t xb = sb + SF_XS + r8 * 1168 + mi * 16;
        auto load = [&](int i, int n, int place) {
            mbar_wait(bar_w + 8 * n);
            const uint32_t wk = fresh(wb) + place * 24576;
#pragma unroll
            for (int s = 0; s < 4; s++) { ldsm4t(fr[8 * i + s], wk + 1024 * s); ldsm4t(fr[8 * i + 4 + s], wk + 1024 * s + 12288); }
        };
        auto mul = [&](int i, uint32_t xk) {
            uint32_t x[2][4];
            ldsm4(x[0], xk); ldsm4(x[1], xk + 64);
#pragma unroll
            for (int s = 0; s < 4; s++) {
                const uint32_t (&a)[4] = fr[8 * i + s], (&b)[4] = fr[8 * i + 4 + s];
                mma_bf(ag[s & 1], a[0], a[1], a[2], a[3], x[s >> 1][2 * (s & 1)], x[s >> 1][2 * (s & 1) + 1]);
                mma_bf(au[s & 1], b[0], b[1], b[2], b[3], x[s >> 1][2 * (s & 1)], x[s >> 1][2 * (s & 1) + 1]);
            }
        };
#pragma unroll
        for (int i = 0; i < 3; i++) load(i, 3 * j + i, (i ? 5 : 3) * j + i);
        pin();
        bar_sync(BAR_G + j, 192);
        if (w == 0 && lane == 0) mbar_arrive(bar_free + 8 * j);
        if (warp < 4) {
            bar_sync(BAR_X, 160);
            const uint32_t rows = lds32(fresh(s_tok) + 8 * r8);
#pragma unroll 1
            for (int i = warp; i < 8; i += 4) {
                const int row = __shfl_sync(0xffffffffu, rows, i);
                if (elect()) bulk_g2s(sb + SF_XS + i * 1168, p.u + (size_t)row * DM, 1152, bar_x);
                __syncwarp();
            }
        }
        mbar_wait(bar_x);
        if (warp == 0) TSTAMP(8);
        {
            const uint32_t xk = fresh(xb) + 384 * j;
#pragma unroll
            for (int i = 0; i < 3; i++) { mul(i, (i ? fresh(xk) : xk) + 128 * i); if (i == 0) { asm volatile("" :: "f"(ag[0][0]), "f"(ag[1][0]), "f"(au[0][0]), "f"(au[1][0])); sts32(s_tok + 64, clock32()); } }
        }
#pragma unroll 1
        for (int n = 6 + j; n < 9; n += 2) { load(0, n, n - 6); mul(0, fresh(xb) + 128 * n); }
#pragma unroll
        for (int c = 0; c < 4; c++) { ag[0][c] += ag[1][c]; au[0][c] += au[1][c]; }
        if (j) {
            sts128(wb + 24576, __float_as_uint(ag[0][0]), __float_as_uint(ag[0][1]), __float_as_uint(ag[0][2]), __float_as_uint(ag[0][3]));
            sts128(wb + 25600, __float_as_uint(au[0][0]), __float_as_uint(au[0][1]), __float_as_uint(au[0][2]), __float_as_uint(au[0][3]));
        }
        bar_sync(BAR_GU, 384);
        if (!j) {
            const uint32_t sf = fresh(wb);
            const uint4 g1 = lds128(sf + 24576), u1 = lds128(sf + 25600);
            const uint32_t gs[4] = {g1.x, g1.y, g1.z, g1.w}, us[4] = {u1.x, u1.y, u1.z, u1.w};
            if (warp == 0) TSTAMP(9);
            float h[4];
#pragma unroll
            for (int c = 0; c < 4; c++) {
                const float gv = rbf(ag[0][c] + __uint_as_float(gs[c]));
                h[c] = rbf(gv * sigmoidf_(gv)) * rbf(au[0][c] + __uint_as_float(us[c]));
            }
            uint32_t h0, h1;
            asm("movmatrix.sync.aligned.m8n8.trans.b16 %0, %1;" : "=r"(h0) : "r"(pack_bf16(h[0], h[1])));
            asm("movmatrix.sync.aligned.m8n8.trans.b16 %0, %1;" : "=r"(h1) : "r"(pack_bf16(h[2], h[3])));
            if (h0 == 0) h0 = 0x8000u;
            asm volatile("{ .reg .b64 v; mov.b64 v, {%1, %2}; st.relaxed.gpu.global.b64 [%0], v; }" :: "l"(p.s->h + ((epoch & 1) * 288 + 6 * f + w) * 32 + lane), "r"(h0), "r"(h1) : "memory");
        }
        if (isx) {
            if (warp == 0) TSTAMP(10);
            const uint2* hsrc = p.s->h + ((epoch & 1) * 288 + 144 * (f & 1) + 12 * warp) * 32 + lane;
            uint2 hb[12];
            auto ldh = [&](int s) { asm volatile("ld.relaxed.gpu.global.v2.u32 {%0, %1}, [%2];" : "=r"(hb[s].x), "=r"(hb[s].y) : "l"(hsrc + 32 * s) : "memory"); };
#pragma unroll
            for (int s = 0; s < 12; s++) ldh(s);
#pragma unroll 1
            for (int it = 0;; it++) {
                bool again = false;
#pragma unroll
                for (int s = 0; s < 12; s += 2) if (__any_sync(0xffffffffu, min(hb[s].x, hb[s + 1].x) == 0)) { ldh(s); ldh(s + 1); again = true; }
                if (!again) break;
                if (it > (1 << 16)) give_up();
            }
            if (warp == 0) TSTAMP(11);
            mbar_wait(bar_d + 8 * warp);
            if (warp == 9) TSTAMP(14);
            float ad[2][2][4];
#pragma unroll
            for (int i = 0; i < 4; i++) { ad[i >> 1][i & 1][0] = ad[i >> 1][i & 1][1] = ad[i >> 1][i & 1][2] = ad[i >> 1][i & 1][3] = 0.f; }
            const uint32_t wd = fresh(sb) + SF_WD + warp * 12288 + (r8 + 8 * (mi >> 1)) * 64 + (((mi & 1) ^ (r8 >> 1)) << 4);
#pragma unroll
            for (int s = 0; s < 12; s++) {
                uint32_t a[4], b[4];
                ldsm4t(a, wd + 1024 * s); ldsm4t(b, (wd ^ 32) + 1024 * s);
                mma_bf(ad[0][s & 1], a[0], a[1], a[2], a[3], hb[s].x, hb[s].y);
                mma_bf(ad[1][s & 1], b[0], b[1], b[2], b[3], hb[s].x, hb[s].y);
            }
            const uint32_t rd = sb + SF_RED + warp * 1152 + (72 * t + g) * 4;
#pragma unroll
            for (int i = 0; i < 8; i++) sts32(rd + (i >> 2) * 64 + (i & 1) * 144 + ((i >> 1) & 1) * 32, __float_as_uint(ad[i >> 2][0][i & 3] + ad[i >> 2][1][i & 3]));
            bar_sync(BAR_RED, 416);
            if (warp < 4) {
                const int tid = 32 * warp + lane;
                const uint32_t rs = fresh(sb + SF_RED) + (tid >> 4) * 144 + (tid & 15) * 8;
                const uint2 tk = lds64(fresh(s_tok) + (tid >> 4) * 8);
                float x = 0.f, y = 0.f;
#pragma unroll
                for (int w = 0; w < 12; w++) { const uint2 v = lds64(rs + w * 1152); x += __uint_as_float(v.x); y += __uint_as_float(v.y); }
                asm volatile("red.relaxed.gpu.global.add.noftz.bf16x2 [%0], %1;" :: "l"(p.out + (size_t)tk.x * DM + 32 * (f >> 1) + 2 * (tid & 15)),
                             "r"(pack_bf16(x * __uint_as_float(tk.y), y * __uint_as_float(tk.y))) : "memory");
            }
            if (warp == 0) { TSTAMP(15); TFLUSH(); }
            asm volatile("exit;"); __builtin_unreachable();
        }
    }
}

__device__ __forceinline__ void fetch_k(const uint4* src, uint64_t (&v)[6], uint32_t a, uint32_t b) {
    asm volatile("{ .reg .pred p; setp.eq.u32 p, %7, %8; @p ld.relaxed.gpu.global.v2.u64 {%0,%1}, [%6]; @p ld.relaxed.gpu.global.v2.u64 {%2,%3}, [%6 + 512]; @p ld.relaxed.gpu.global.v2.u64 {%4,%5}, [%6 + 1024]; }"
                 : "+l"(v[0]), "+l"(v[1]), "+l"(v[2]), "+l"(v[3]), "+l"(v[4]), "+l"(v[5]) : "l"(src), "r"(a), "r"(b));
}
__device__ __forceinline__ uint32_t mini_conv(const Params& p, uint32_t sb, int warp, int lane, int f, unsigned epoch) {
    const int g = lane >> 2, t = lane & 3, mi = lane >> 3, r8 = lane & 7;
    const uint32_t fb = sb + SF_MISC, kt = sb + (warp >= 12 ? SM_KT - 12 * 2112 : f < NW ? SM_KW + 2 * 2112 : SM_KW) + warp * 2112;
    const bool ism = f >= NW;
    const int ch0 = mini_ch0(f);
    uint32_t seq = 128, key;
    uint64_t v[6] = {};
    const uint4* src = p.s->kp + lane;
    auto hi = [&](int i) { return (uint32_t)(v[i] >> 32); };
    if (f >= (warp < 4 ? NW : NX)) {
    {
        const uint32_t c = 36 + (warp & 3) + 2 * (warp & 12), y = (uint32_t)((warp < 8 ? 0xa026802400000000ull : 0x2a2e00280080a22cull) >> ((8 * warp) & 48)) & 0xffff;
        seq = ism ? 0x101 * c - 0x400 : y + (warp & 1) * ((y >> 5) & 0x101);
        src += (ch0 + (seq & 31)) * 128;
    }
    if (warp >= 10 && (warp & 2)) {
        const int q = (warp & 1) + (warp < 12 ? 2 : 0), n0 = ism ? 2 * (q & 1) : q;
        const uint32_t ab = sb - (ism ? 49152 * (q >> 1) : 0);
        mbar_wait(fb + FB_MU);
        if (warp == 15) TSTAMP(16);
        uint32_t a = fresh(ab + SM_RAW) + n0 * 4096 + (8 * mi + 4 * (r8 & 1) + (r8 >> 1)) * 32 + ((r8 & 1) << 4), d = ab + SM_UT + g * MU_STRIDE + (8 + 8 * n0 + t) * 16;
        uint32_t z = ab + SM_UT + (4 * n0 + (mi >> 1)) * MU_STRIDE + (mi & 1) * MU_HALF + r8 * 16;
#pragma unroll 1
        for (int n = 0; n <= ism; n++, a += 4096, d += 128, z += 4 * MU_STRIDE) {
            uint32_t x[8][4];
#pragma unroll
            for (int i = 0; i < 8; i++) ldsm4t(x[i], (i & 4 ? a ^ 16 : a) + 1024 * (i & 3));
            sts128(z, 0, 0, 0, 0); sts128(z + 2 * MU_STRIDE, 0, 0, 0, 0);
#pragma unroll
            for (int i = 0; i < 8; i++) sts128(d + (i & 1) * MU_HALF + (i & 2) * 32 + (i & 4) * 2 * MU_STRIDE, x[i][0], x[i][1], x[i][2], x[i][3]);
        }
        __syncwarp();
        if (lane == 0) mbar_arrive(fb + FB_MT);
    }
    if (seq & 32) {
        mbar_wait(fb + FB_KDONE);
        fetch_k(src, v, 0, 0);
        if ((warp >> 1) == (ism ? 6 : 2)) { fetch_gates(p, warp & 1, lane, epoch, sb + SM_G + (lane & 1) * MU_HALF); __syncwarp(); if (lane == 0) mbar_arrive(fb + FB_MG); }
        mbar_wait(fb + FB_KEYS); mbar_wait(fb + FB_MT);
        sts128(kt + t * 16, 0, 0, 0, 0);
        if (warp == TW) TSTAMP(17);
    }
    }
    const uint32_t lo = (mi & 1) * MU_HALF + (8 + r8) * 16 + (mi >> 1) * 128;
#pragma unroll 1
    do {
        const int c = seq & 31;
        if (seq & 32) {
#pragma unroll 1
        for (int it = 0; !__all_sync(0xffffffffu, ((hi(1) ^ ~epoch) | (hi(3) ^ ~epoch) | (hi(5) ^ ~epoch) | ((uint32_t)v[5] & p.zero)) == 0); it++) {
            fetch_k(src, v, 0, 0);
            if (it > (1 << 20)) give_up();
        }
        if (warp == TW) TSTAMP(seq >> 8 ? 7 : 10);
        const uint32_t w[12] = {(uint32_t)v[0], hi(0), (uint32_t)v[1], (uint32_t)v[2], hi(2), (uint32_t)v[3], (uint32_t)v[4], hi(4), 0, 0, 0, 0};
        k_tables<false>(fresh(kt), fresh(lane), w);
        }
        __syncwarp();
        if (seq & 128) ffn_work(p, sb, warp, fresh(lane), f, epoch);
        if (!(seq & 32)) return 0;
        const uint32_t ab = sb - 49152 * (c >> 4), kb = fresh(kt) + (16 + g - 2 * t) * 4, ub = fresh(ab + SM_UT + (c & 15) * MU_STRIDE) + lo;
        const uint32_t yd = ab + SM_Y + (c & 15) * 1056 + (c & 8) * 8 + lane * 16;
        uint32_t kp = kb, u1 = ub;
        if (warp == TW && !(seq >> 8)) TSTAMP(13);
        seq >>= 8;
        src += ((int)(seq & 31) - c) * 128;
#pragma unroll
        for (int i = 0; i < 6; i++) v[i] = 0;
        key = 0;
        float acc[6][4];
#pragma unroll
        for (int i = 0; i < 6; i++) { acc[i][0] = acc[i][1] = acc[i][2] = acc[i][3] = 0.f; }
        uint32_t a[4][4], b[2][2][4];
        auto lda = [&](int j, int o) { const uint32_t x = kp + 64 * o + 512 * j; a[j][2] = o ? a[j][1] ^ p.zero : lds32((kp ^ p.zero) + 512 * j - 32); a[j][0] = lds32(x); a[j][1] = lds32(x + 32); a[j][3] = a[j][0] ^ p.zero; };
        auto ldb = [&](int s, int o) { ldsm4(b[s][0], u1 - 16 * o); ldsm4(b[s][1], u1 + 256 - 16 * o); };
        ldb(0, 0);
#pragma unroll
        for (int j = 0; j < 4; j++) lda(j, 0);
#pragma unroll
        for (int s = 0; s < 8; s++) {
            if (s == FPOS) {
                const uint32_t e = seq | (__float_as_uint(acc[0][0]) & p.zero);
                fetch_k(src, v, e & 32, 32);
                if (KEYPF) asm volatile("{ .reg .pred p; setp.eq.u32 p, %2, 0; @p ld.relaxed.gpu.global.u32 %0, [%1]; }" : "+r"(key) : "l"(&p.s->sel[(ch0 >> 5) * 64 + r8]), "r"(e));
            }
            if (s < 7) ldb(~s & 1, s + 1);
#pragma unroll
            for (int i = 0; i < 4; i++) {
                const int j = (i >> 1) + 2 * (i & 1);
#pragma unroll
                for (int mu = 3 - j; mu >= 0; mu--) mma_bf(acc[j + mu + (j & 2)], a[j][0], a[j][1], a[j][2], a[j][3], b[s & 1][mu >> 1][2 * (mu & 1)], b[s & 1][mu >> 1][2 * (mu & 1) + 1]);
                if (s < 7) lda(j, s + 1);
            }
        }
        if (warp == TW && !seq) TSTAMP(14);
        mbar_wait(fb + FB_MG);
#pragma unroll
        for (int e = 0; e < 4; e++) { acc[2][e] += acc[4][e]; acc[3][e] += acc[5][e]; }
        uint32_t ug[4][4];
#pragma unroll
        for (int i = 0; i < 2; i++) { ldsm4t(ug[i], ub + 256 * i); ldsm4t(ug[2 + i], fresh(sb + SM_G) + lo + 256 * i); }
#pragma unroll
        for (int i = 0; i < 2; i++) {
            const uint32_t (&u)[4] = ug[i], (&gg)[4] = ug[2 + i];
            sts128(yd + 512 * i, gmix(gg[0], acc[2 * i][0], acc[2 * i][1], u[0]), gmix(gg[1], acc[2 * i][2], acc[2 * i][3], u[1]),
                   gmix(gg[2], acc[2 * i + 1][0], acc[2 * i + 1][1], u[2]), gmix(gg[3], acc[2 * i + 1][2], acc[2 * i + 1][3], u[3]));
        }
        __syncwarp();
        if (warp == TW) TSTAMP(18 + (seq != 0));
    } while (seq);
    if (warp >= 12) TSTAMP(12 + warp);
    return key;
}
__device__ __forceinline__ void mini_out(const Params& p, const CUtensorMap* maps, uint32_t sb, int warp, int lane, int f, unsigned epoch, uint32_t key) {
    const int g = lane >> 2, t = lane & 3, mi = lane >> 3, r8 = lane & 7;
    const uint32_t fb = sb + SF_MISC;
    const bool ism = f >= NW;
    const int ch0 = mini_ch0(f);
    const int k = ism ? warp >> 3 : 0;
    uint32_t first = 1;
    if (lane == 0) asm volatile("atom.shared.exch.b32 %0, [%1], 1;" : "=r"(first) : "r"(fb + FS_BM + 64 + 4 * k) : "memory");
    if (!__all_sync(0xffffffffu, first)) {
        if (elect()) prefetch_map(maps + 4);
        const int row = key_row(wait_sel(p, ch0 >> 5, r8, key_tag(epoch), key));
        if (row < 512) asm volatile("red.shared.or.b32 [%0], %1;" :: "r"(fb + FS_BM + (row >> 5) * 4), "r"(1u << (row & 31)) : "memory");
    }
    const int m = warp & 7, dr = 128 * (g >> 2) + 32 * (t >> 1) + 16 * (g & 1) + 8 * ((g >> 1) & 1);
    const uint32_t y = SM_Y + ((r8 >> 1) & 1) * 8512 + (2 * mi + (r8 & 1)) * 1056 + (2 * m + (r8 >> 2)) * 16;
    const uint32_t so = (g >> 1) * 256 + (t >> 1) * 64 + (g & 1) * 32 + (t & 1) * 16;
    bar_sync(BAR_M - k, ism ? 256 : NTHR);
#pragma unroll 1
    for (int h = ism ? 0 : warp >> 3;; h++) {
        const int r0 = 256 * h + 64 * (m & 1) + (m >> 1), row = r0 + dr;
        const uint32_t bm = lds32(fresh(fb) + FS_BM + (row >> 5) * 4) >> (row & 31), ab = fresh(sb - 49152 * k + 512 * h), stg = ab + SM_UT + 2048 * m + 512 * h;
        uint32_t x[2][4];
        ldsm4t(x[0], ab + y); ldsm4t(x[1], ab + y + 256);
        if (warp == 0 && x[0][0] != 0x12345) TSTAMP(28);
        if (__any_sync(0xffffffffu, bm & 0x11u)) {
#pragma unroll
            for (int i = 0; i < 2; i++) store_or_add(p.out + (size_t)(row + 4 * i) * DM + ch0 + 16 * k + 8 * (t & 1), x[i], bm & (1u << (4 * i)));
        } else {
#pragma unroll
            for (int i = 0; i < 2; i++) sts128(stg + so + 128 * i, x[i][0], x[i][1], x[i][2], x[i][3]);
            asm volatile("fence.proxy.async.shared::cta;" ::: "memory");
            __syncwarp();
            if (elect()) store_rows(maps + 4, stg, ch0 + 16 * k, r0);
        }
        if (h >= ism) break;
    }
    if (elect()) { asm volatile("cp.async.bulk.commit_group;" ::: "memory"); asm volatile("cp.async.bulk.wait_group.read 0;" ::: "memory"); }
    if (warp == 8) TSTAMP(11);
    if (warp == 0) { TSTAMP(15); TFLUSH(); }
}

constexpr int SMEM_BYTES = 232448;
static_assert(SF_MISC + 1152 <= 232192, "layout");

struct Maps { CUtensorMap m[6]; };

__global__ void __cluster_dims__(2, 1, 1) __launch_bounds__(NTHR, 1)
fused_kernel(const Params p, const __grid_constant__ Maps maps) {
    extern __shared__ __align__(1024) uint8_t smem_raw[];
    uint32_t q[8];
    {
        const int b = blockIdx.x, x = threadIdx.x, rc = 4 * b + max(b - 84, 0) - 288 + (x >> 6);
        const int cv = (b - NCONV) >> 31, ca = 8 * b + ((x >> 5) & 3), cb = 2 * rc - (rc & 3) + 4;
        const uint32_t ch = (ca & cv) | (cb & ~cv), o = NST * ch + 2 * ((x & 31) + ((x >> (cv & 2)) & 32));
        const bool c = x < (b < 84 ? 256 : 320);
        q[6] = ldg16_if(c, p.logdt + ch);
        q[2] = ldg32_if(c, p.Bre + o); q[3] = ldg32_if(c, p.Bim + o); q[4] = ldg32_if(c, p.Cre + o); q[5] = ldg32_if(c, p.Cim + o); q[0] = ldg32_if(c, p.Are + o); q[1] = ldg32_if(c, p.Aim + o);
        q[7] = ldg16_if(c, p.Dskip + ch);
    }
    const unsigned epoch = ld_rlx32(&p.s->epoch[blockIdx.x * 16 + (threadIdx.x >> 5)]);
    const uint32_t sb = __shfl_sync(0xffffffffu, smem_u32(smem_raw), 0);
    const int warp = __shfl_sync(0xffffffffu, threadIdx.x >> 5, 0), bid = __shfl_sync(0xffffffffu, blockIdx.x, 0);
    const int lane = __shfl_sync(0xffffffffu, threadIdx.x & 31, threadIdx.x);
    const bool conv = bid < NCONV;
    const int f = bid - NCONV;
    uint32_t w[12];
    if (warp < (f < 12 ? 8 : 10)) {
        const int half = conv ? warp >> 2 : warp & 1, pr = conv ? warp & 3 : warp >> 1;
        const int rc = 4 * f + max(f - 12, 0) + pr;
        const uint32_t stage = sb + (conv ? SC_KG : SF_KG) + warp * KG_STAGE;
        uint4* const kp = p.s->kp + (conv ? 8 * bid + pr : 2 * rc - (rc & 3) + 4) * 128 + lane;
        kgen(q, sb, half, stage, stage + (conv ? 4 : 1) * KG_STAGE, 1 + pr, lane, p.zero, w, [&] {
            sts128z_if(conv && lane < 20, sb + SC_KT + warp * KT_BYTES + lane * 16 + (lane < 4 ? 0 : lane < 14 ? 2048 : 2288));
            stg128(kp + 64 * half, 0, 0, 0, 0); stg128z_if(!conv || !half, kp + 64 * half + 32);
            stg128z_if((unsigned)f < NW && warp < 6, (uint4*)(p.s->h + ((lane >> 4) * 288 + 6 * f + warp) * 32) + (lane & 15));
            if (conv) asm volatile("barrier.cluster.arrive.relaxed.aligned;" ::: "memory");
        });
        if (conv) { conv_main(p, sb, warp, lane, bid, epoch, w); return; }
        {
            if (!half) publish_k(kp, w, 4, epoch);
            if (warp == 0) TSTAMP(22);
            if (warp == 2) TSTAMP(23);
            bar_sync(0, NTHR);
            if (warp == 0 && lane == 0) mbar_arrive(sb + SF_MISC + FB_KDONE);
        }
    } else if (conv) {
        conv_aux(p, maps.m, sb, warp - 8, lane, bid, epoch);
        return;
    } else {
        ffn_front(p, maps.m, sb, warp, lane, f, epoch);
    }
    converged();
    next_epoch(p, epoch);
    if (warp >= 12 && f < NX) return;
    mini_out(p, maps.m, sb, warp, lane, f, epoch, mini_conv(p, sb, warp, __shfl_sync(0xffffffffu, lane, lane), f, epoch));
}

typedef CUresult (*EncodeFn)(CUtensorMap*, CUtensorMapDataType, cuuint32_t, void*, const cuuint64_t*, const cuuint64_t*, const cuuint32_t*, const cuuint32_t*,
                             CUtensorMapInterleave, CUtensorMapSwizzle, CUtensorMapL2promotion, CUtensorMapFloatOOBfill);

void make_map(EncodeFn fn, CUtensorMap* m, const void* base, int rank, const cuuint64_t* dims, const cuuint64_t* strides, const cuuint32_t* box, CUtensorMapSwizzle sw) {
    const cuuint32_t es[5] = {1, 1, 1, 1, 1};
    fn(m, CU_TENSOR_MAP_DATA_TYPE_BFLOAT16, rank, (void*)base, dims, strides, box, es, CU_TENSOR_MAP_INTERLEAVE_NONE, sw,
       CU_TENSOR_MAP_L2_PROMOTION_NONE, CU_TENSOR_MAP_FLOAT_OOB_FILL_NONE);
}

}

extern "C" void kernel_launch(void* const* d_in, const int* in_sizes, int n_in, void* d_out, int out_size) {
    (void)in_sizes; (void)n_in; (void)out_size;
    static EncodeFn fn = nullptr;
    static void* scratch = nullptr;
    if (!fn) {
        void* ptr = nullptr; cudaDriverEntryPointQueryResult qr;
        cudaGetDriverEntryPoint("cuTensorMapEncodeTiled", &ptr, cudaEnableDefault, &qr);
        fn = (EncodeFn)ptr;
        cudaGetSymbolAddress(&scratch, g_scratch);
        cudaFuncSetAttribute(fused_kernel, cudaFuncAttributeMaxDynamicSharedMemorySize, SMEM_BYTES);
    }
    typedef const __nv_bfloat16* bp;
    Params p;
    p.u = (bp)d_in[0]; p.Are = (bp)d_in[1]; p.Aim = (bp)d_in[2]; p.Bre = (bp)d_in[3]; p.Bim = (bp)d_in[4]; p.Cre = (bp)d_in[5]; p.Cim = (bp)d_in[6];
    p.logdt = (bp)d_in[7]; p.Dskip = (bp)d_in[8]; p.wr = (bp)d_in[10]; p.gatew = (bp)d_in[14];
    p.out = (__nv_bfloat16*)d_out; p.s = (Scratch*)scratch; p.zero = 0;
    Maps maps;
    {
        const cuuint64_t dims[4] = {DM, 4, 16, 32}, strides[3] = {16 * DM * 2, DM * 2, 64 * DM * 2};
        const cuuint32_t box[4] = {16, 4, 16, 2};
        make_map(fn, &maps.m[0], d_in[0], 4, dims, strides, box, CU_TENSOR_MAP_SWIZZLE_32B);
        const cuuint32_t box2[4] = {16, 4, 16, 8};
        make_map(fn, &maps.m[5], d_in[0], 4, dims, strides, box2, CU_TENSOR_MAP_SWIZZLE_32B);
    }
    for (int i = 0; i < 2; i++) {
        const cuuint64_t dims[3] = {32, DM, FF / 32}, strides[2] = {FF * 2, 64};
        const cuuint32_t box[3] = {32, 64, 3};
        make_map(fn, &maps.m[1 + i], d_in[11 + i], 3, dims, strides, box, CU_TENSOR_MAP_SWIZZLE_64B);
    }
    {
        const cuuint64_t dims[2] = {DM, FF}, strides[1] = {DM * 2};
        const cuuint32_t box[2] = {32, 192};
        make_map(fn, &maps.m[3], d_in[13], 2, dims, strides, box, CU_TENSOR_MAP_SWIZZLE_64B);
    }
    {
        const cuuint64_t dims[5] = {DM, 4, 4, 2, L_SEQ}, strides[4] = {16 * DM * 2, 4 * DM * 2, 128 * DM * 2, DM * 2};
        const cuuint32_t box[5] = {16, 4, 4, 2, 1};
        make_map(fn, &maps.m[4], d_out, 5, dims, strides, box, CU_TENSOR_MAP_SWIZZLE_NONE);
    }
    fused_kernel<<<NCTA, NTHR, SMEM_BYTES>>>(p, maps);
}
```

```cpp
#include <cuda_runtime.h>
#include <cuda_bf16.h>
#include <cuda_fp16.h>
#include <cuda.h>
#include <stdint.h>
#include <type_traits>

#define RESUME 200
#define PUBIT 1
#define FPOS 2
#define PUBY 0
#define KEYPF 1
#define TW 12
#define MDELAY 0
#define UDELAY 0
#define RDELAY 900
#define WDELAY 2000
#define WGAP 290
#define NPRE 6
#define DGAP 260

namespace {

constexpr int DM = 576, NST = 128, FF = 4608, L_SEQ = 2048;
constexpr int NCONV = 72, NX = 36, NW = 48, NCTA = 132, NTHR = 512;

struct __align__(128) Scratch {
    unsigned epoch[NCTA * 16];
    uint4 keys[16 * 128];
    uint32_t sel[18 * 64];
    uint16_t gate[L_SEQ];
    uint2 h[2 * 288 * 32];
    uint4 kp[DM * 96];
};
__device__ Scratch g_scratch;
#define TFLUSH()
#define TSTAMP(i)

struct Params {
    const __nv_bfloat16 *Are, *Aim, *Bre, *Bim, *Cre, *Cim, *logdt, *Dskip, *u, *wr, *gatew;
    __nv_bfloat16* out;
    Scratch* s;
    uint32_t zero;
};

__device__ __forceinline__ void give_up() { asm volatile("trap; exit;"); __builtin_unreachable(); }
__device__ __forceinline__ void converged() { __syncwarp(); asm volatile("{ .reg .b32 t; mov.b32 t, 0; movmatrix.sync.aligned.m8n8.trans.b16 t, t; }" ::: "memory"); }
__device__ __forceinline__ bool elect() { uint32_t r; asm volatile("{ .reg .pred p; elect.sync _|p, 0xffffffff; selp.u32 %0, 1, 0, p; }" : "=r"(r)); return r; }
__device__ __forceinline__ uint32_t smem_u32(const void* p) { return (uint32_t)__cvta_generic_to_shared(p); }
__device__ __forceinline__ uint32_t pack_bf16(float lo, float hi) { uint32_t r; asm("cvt.rn.bf16x2.f32 %0, %1, %2;" : "=r"(r) : "f"(hi), "f"(lo)); return r; }
__device__ __forceinline__ uint32_t pack_f16(float lo, float hi) { uint32_t r; asm("cvt.rn.f16x2.f32 %0, %1, %2;" : "=r"(r) : "f"(hi), "f"(lo)); return r; }
__device__ __forceinline__ float bf_lo(uint32_t w) { return __uint_as_float(w << 16); }
__device__ __forceinline__ float bf_hi(uint32_t w) { return __uint_as_float(w & 0xffff0000u); }
__device__ __forceinline__ float rbf(float x) { return bf_lo(pack_bf16(x, 0.f)); }
__device__ __forceinline__ uint32_t badd2(uint32_t a, uint32_t b) { uint32_t r; asm("add.rn.bf16x2 %0, %1, %2;" : "=r"(r) : "r"(a), "r"(b)); return r; }
__device__ __forceinline__ uint32_t bsub2(uint32_t a, uint32_t b) { uint32_t r; asm("sub.rn.bf16x2 %0, %1, %2;" : "=r"(r) : "r"(a), "r"(b)); return r; }
__device__ __forceinline__ uint32_t gmix(uint32_t ng, float ny0, float ny1, uint32_t u) {
    uint32_t r; asm("{ .reg .b32 t; fma.rn.bf16x2 t, %1, %3, %3; fma.rn.bf16x2 %0, %1, %2, t; }" : "=r"(r) : "r"(ng), "r"(pack_bf16(ny0, ny1)), "r"(u)); return r;
}
__device__ __forceinline__ void mma_bf(float (&c)[4], uint32_t a0, uint32_t a1, uint32_t a2, uint32_t a3, uint32_t b0, uint32_t b1) {
    asm("mma.sync.aligned.m16n8k16.row.col.f32.bf16.bf16.f32 {%0,%1,%2,%3}, {%4,%5,%6,%7}, {%8,%9}, {%0,%1,%2,%3};"
        : "+f"(c[0]), "+f"(c[1]), "+f"(c[2]), "+f"(c[3]) : "r"(a0), "r"(a1), "r"(a2), "r"(a3), "r"(b0), "r"(b1));
}
__device__ __forceinline__ void mma_bf8(float (&c)[4], uint32_t a0, uint32_t a1, uint32_t b0) {
    asm("mma.sync.aligned.m16n8k8.row.col.f32.bf16.bf16.f32 {%0,%1,%2,%3}, {%4,%5}, {%6}, {%0,%1,%2,%3};"
        : "+f"(c[0]), "+f"(c[1]), "+f"(c[2]), "+f"(c[3]) : "r"(a0), "r"(a1), "r"(b0));
}
__device__ __forceinline__ void mma_h(float (&c)[4], uint32_t a0, uint32_t a1, uint32_t a2, uint32_t a3, uint32_t b0, uint32_t b1) {
    asm("mma.sync.aligned.m16n8k16.row.col.f32.f16.f16.f32 {%0,%1,%2,%3}, {%4,%5,%6,%7}, {%8,%9}, {%0,%1,%2,%3};"
        : "+f"(c[0]), "+f"(c[1]), "+f"(c[2]), "+f"(c[3]) : "r"(a0), "r"(a1), "r"(a2), "r"(a3), "r"(b0), "r"(b1));
}
__device__ __forceinline__ uint32_t fresh(uint32_t a) { asm volatile("" : "+r"(a) :: "memory"); return a; }
__device__ __forceinline__ uint32_t lds16(uint32_t a) { uint32_t v; asm("ld.shared.u16 %0, [%1];" : "=r"(v) : "r"(a)); return v; }
__device__ __forceinline__ uint32_t lds32(uint32_t a) { uint32_t v; asm("ld.shared.u32 %0, [%1];" : "=r"(v) : "r"(a)); return v; }
__device__ __forceinline__ uint2 lds64(uint32_t a) { uint2 v; asm("ld.shared.v2.u32 {%0,%1}, [%2];" : "=r"(v.x), "=r"(v.y) : "r"(a)); return v; }
__device__ __forceinline__ uint4 lds128(uint32_t a) { uint4 v; asm("ld.shared.v4.u32 {%0,%1,%2,%3}, [%4];" : "=r"(v.x), "=r"(v.y), "=r"(v.z), "=r"(v.w) : "r"(a)); return v; }
__device__ __forceinline__ uint4 lds128v(uint32_t a) { uint4 v; asm volatile("ld.shared.v4.u32 {%0,%1,%2,%3}, [%4];" : "=r"(v.x), "=r"(v.y), "=r"(v.z), "=r"(v.w) : "r"(a) : "memory"); return v; }
__device__ __forceinline__ void ldsm4(uint32_t (&r)[4], uint32_t a) {
    asm("ldmatrix.sync.aligned.m8n8.x4.shared.b16 {%0,%1,%2,%3}, [%4];" : "=r"(r[0]), "=r"(r[1]), "=r"(r[2]), "=r"(r[3]) : "r"(a));
}
__device__ __forceinline__ void ldsm4t(uint32_t (&r)[4], uint32_t a) {
    asm("ldmatrix.sync.aligned.m8n8.x4.trans.shared.b16 {%0,%1,%2,%3}, [%4];" : "=r"(r[0]), "=r"(r[1]), "=r"(r[2]), "=r"(r[3]) : "r"(a));
}
__device__ __forceinline__ void sts16(uint32_t a, uint32_t v) { asm volatile("st.shared.u16 [%0], %1;" :: "r"(a), "h"((unsigned short)v) : "memory"); }
__device__ __forceinline__ void sts32(uint32_t a, uint32_t v) { asm volatile("st.shared.u32 [%0], %1;" :: "r"(a), "r"(v) : "memory"); }
__device__ __forceinline__ void sts64(uint32_t a, uint32_t x, uint32_t y) { asm volatile("st.shared.v2.u32 [%0], {%1,%2};" :: "r"(a), "r"(x), "r"(y) : "memory"); }
__device__ __forceinline__ void sts128(uint32_t a, uint32_t x, uint32_t y, uint32_t z, uint32_t w) {
    asm volatile("st.shared.v4.u32 [%0], {%1,%2,%3,%4};" :: "r"(a), "r"(x), "r"(y), "r"(z), "r"(w) : "memory");
}
__device__ __forceinline__ void st_async128(uint32_t a, uint32_t x, uint32_t y, uint32_t z, uint32_t w, uint32_t bar) {
    asm volatile("st.async.weak.shared::cluster.mbarrier::complete_tx::bytes.v4.b32 [%0], {%1,%2,%3,%4}, [%5];" :: "r"(a), "r"(x), "r"(y), "r"(z), "r"(w), "r"(bar) : "memory");
}
__device__ __forceinline__ void mbar_init(uint32_t b, uint32_t cnt) { asm volatile("mbarrier.init.shared::cta.b64 [%0], %1;" :: "r"(b), "r"(cnt) : "memory"); }
__device__ __forceinline__ void mbar_fence() { asm volatile("fence.mbarrier_init.release.cluster;" ::: "memory"); }
__device__ __forceinline__ void mbar_expect(uint32_t b, uint32_t bytes) { asm volatile("mbarrier.arrive.expect_tx.shared::cta.b64 _, [%0], %1;" :: "r"(b), "r"(bytes) : "memory"); }
__device__ __forceinline__ void mbar_arrive(uint32_t b) { asm volatile("mbarrier.arrive.shared::cta.b64 _, [%0];" :: "r"(b) : "memory"); }
#define CHINT ""
#define HINT ""
__device__ __forceinline__ void mbar_wait(uint32_t b, uint32_t parity = 0) {
    asm volatile("{ .reg .pred p; .reg .u32 n; mov.u32 n, 0;\n"
                 "LW: mbarrier.try_wait.parity.shared::cta.b64 p, [%0], %1" HINT "; @p bra LD; add.u32 n, n, 1; setp.lt.u32 p, n, 65536; @p bra LW; trap;\n"
                 "LD: }" :: "r"(b), "r"(parity) : "memory");
}
__device__ __forceinline__ void mbar_wait_cluster(uint32_t b) {
    asm volatile("{ .reg .pred p; .reg .u32 n; mov.u32 n, 0;\n"
                 "LW: mbarrier.try_wait.parity.acquire.cluster.shared::cta.b64 p, [%0], 0" CHINT "; @p bra LD; add.u32 n, n, 1; setp.lt.u32 p, n, 65536; @p bra LW; trap;\n"
                 "LD: }" :: "r"(b) : "memory");
}
__device__ __forceinline__ void tma2d(uint32_t dst, const CUtensorMap* m, int c0, int c1, uint32_t bar) {
    asm volatile("cp.async.bulk.tensor.2d.shared::cluster.global.mbarrier::complete_tx::bytes [%0], [%1, {%3, %4}], [%2];"
                 :: "r"(dst), "l"(m), "r"(bar), "r"(c0), "r"(c1) : "memory");
}
__device__ __forceinline__ void tma3d(uint32_t dst, const CUtensorMap* m, int c0, int c1, int c2, uint32_t bar) {
    asm volatile("cp.async.bulk.tensor.3d.shared::cluster.global.mbarrier::complete_tx::bytes [%0], [%1, {%3, %4, %5}], [%2];"
                 :: "r"(dst), "l"(m), "r"(bar), "r"(c0), "r"(c1), "r"(c2) : "memory");
}
__device__ __forceinline__ void tma4d(uint32_t dst, const CUtensorMap* m, int c0, int c1, int c2, int c3, uint32_t bar) {
    asm volatile("cp.async.bulk.tensor.4d.shared::cluster.global.mbarrier::complete_tx::bytes [%0], [%1, {%3, %4, %5, %6}], [%2];"
                 :: "r"(dst), "l"(m), "r"(bar), "r"(c0), "r"(c1), "r"(c2), "r"(c3) : "memory");
}
__device__ __forceinline__ void bulk_g2s(uint32_t dst, const void* src, uint32_t bytes, uint32_t bar) {
    asm volatile("cp.async.bulk.shared::cluster.global.mbarrier::complete_tx::bytes [%0], [%1], %2, [%3];"
                 :: "r"(dst), "l"(src), "r"(bytes), "r"(bar) : "memory");
}
__device__ __forceinline__ uint32_t mapa(uint32_t a, uint32_t rank) { uint32_t r; asm("mapa.shared::cluster.u32 %0, %1, %2;" : "=r"(r) : "r"(a), "r"(rank)); return r; }
__device__ __forceinline__ void prefetch_map(const CUtensorMap* m) { asm volatile("prefetch.tensormap [%0];" :: "l"(m) : "memory"); }
__device__ __forceinline__ void bar_sync(int id, int n) { asm volatile("bar.sync %0, %1;" :: "r"(id), "r"(n) : "memory"); }
__device__ __forceinline__ void bar_arrive(int id, int n) { asm volatile("bar.arrive %0, %1;" :: "r"(id), "r"(n) : "memory"); }
__device__ __forceinline__ uint32_t ldg16_if(bool c, const void* p) { uint32_t v; asm volatile("{ .reg .pred p; setp.ne.u32 p, %2, 0; @p ld.global.nc.u16 %0, [%1]; }" : "=r"(v) : "l"(p), "r"((uint32_t)c)); return v; }
__device__ __forceinline__ uint32_t ldg32_if(bool c, const void* p) { uint32_t v; asm volatile("{ .reg .pred p; setp.ne.u32 p, %2, 0; @p ld.global.nc.u32 %0, [%1]; }" : "=r"(v) : "l"(p), "r"((uint32_t)c)); return v; }
__device__ __forceinline__ uint32_t ld_rlx32(const void* p) { uint32_t v; asm volatile("ld.relaxed.gpu.global.u32 %0, [%1];" : "=r"(v) : "l"(p) : "memory"); return v; }
__device__ __forceinline__ uint4 ld_rlx128(const void* p) {
    uint4 v; asm volatile("ld.relaxed.gpu.global.v4.u32 {%0,%1,%2,%3}, [%4];" : "=r"(v.x), "=r"(v.y), "=r"(v.z), "=r"(v.w) : "l"(p) : "memory"); return v;
}
__device__ __forceinline__ void st_rlx32(void* p, uint32_t v) { asm volatile("st.relaxed.gpu.global.u32 [%0], %1;" :: "l"(p), "r"(v) : "memory"); }
__device__ __forceinline__ void stg128(void* p, uint32_t x, uint32_t y, uint32_t z, uint32_t w) {
    asm volatile("st.global.v4.u32 [%0], {%1,%2,%3,%4};" :: "l"(p), "r"(x), "r"(y), "r"(z), "r"(w) : "memory");
}
__device__ __forceinline__ void next_epoch(const Params& p, unsigned e) { if ((threadIdx.x & 31) == 0) p.s->epoch[blockIdx.x * 16 + (threadIdx.x >> 5)] = e + 1; }
__device__ __forceinline__ void sts128z_if(bool c, uint32_t a) { asm volatile("{ .reg .pred p; setp.ne.u32 p, %1, 0; @p st.shared.v4.u32 [%0], {%2,%2,%2,%2}; }" :: "r"(a), "r"((uint32_t)c), "r"(0) : "memory"); }
__device__ __forceinline__ void stg128z_if(bool c, void* a) { asm volatile("{ .reg .pred p; setp.ne.u32 p, %1, 0; @p st.global.v4.u32 [%0], {%2,%2,%2,%2}; }" :: "l"(a), "r"((uint32_t)c), "r"(0) : "memory"); }
__device__ __forceinline__ unsigned clock32() { unsigned c; asm volatile("mov.u32 %0, %clock;" : "=r"(c) :: "memory"); return c; }
__device__ __forceinline__ void until(unsigned t0, int c) { while ((int)(clock32() - t0) < c) { } }
__device__ __forceinline__ float sigmoidf_(float x) { return __fdividef(1.0f, 1.0f + __expf(-x)); }
__device__ __forceinline__ uint32_t key_tag(unsigned epoch) { return ((epoch & 15u) | 16u) << 11; }
__device__ __forceinline__ int key_row(uint32_t key) { return 2047 - (int)(key & 2047u); }
__device__ __forceinline__ uint32_t wait_sel(const Params& p, int s32, int r8, uint32_t tag, uint32_t k = 0) {
#pragma unroll 1
    for (int it = 0; !__all_sync(0xffffffffu, (k & 0xf800u) == tag); it++) {
        k = ld_rlx32(&p.s->sel[s32 * 64 + r8]);
        if (it > (1 << 20)) give_up();
    }
    return k;
}

struct cplx { float re, im; };
__device__ __forceinline__ cplx csq(cplx a) { cplx r; r.re = a.re * a.re - a.im * a.im; r.im = (a.re * a.im) * 2.f; return r; }
__device__ __forceinline__ cplx cexpk(float ar, float ai, float k) {
    float mag, s, c;
    asm("ex2.approx.ftz.f32 %0, %1;" : "=f"(mag) : "f"(ar * (k * 1.4426950408889634f)));
    const float r = ai * k;
    asm("sin.approx.ftz.f32 %0, %1;" : "=f"(s) : "f"(r));
    asm("cos.approx.ftz.f32 %0, %1;" : "=f"(c) : "f"(r));
    cplx o; o.re = mag * c; o.im = mag * s; return o;
}
struct h2c { uint32_t re, im; };
__device__ __forceinline__ h2c cmul_cd(h2c v, __half2 c, __half2 d) {
    const __half2 r = *(const __half2*)&v.re, i = *(const __half2*)&v.im;
    const __half2 x = __hfma2(__hneg2(i), d, __hmul2(r, c)), y = __hfma2(i, c, __hmul2(r, d));
    h2c o; o.re = *(const uint32_t*)&x; o.im = *(const uint32_t*)&y; return o;
}
__device__ __forceinline__ h2c cmul_s(h2c v, uint32_t s) { const __half2 h = *(const __half2*)&s; return cmul_cd(v, __low2half2(h), __high2half2(h)); }
__device__ __forceinline__ h2c cmul_sc(h2c v, uint32_t s) {
    const __half2 h = *(const __half2*)&s, c = __low2half2(h), d = __high2half2(h), r = *(const __half2*)&v.re, i = *(const __half2*)&v.im;
    const __half2 x = __hfma2(i, d, __hmul2(r, c)), y = __hfma2(__hneg2(r), d, __hmul2(i, c));
    h2c o; o.re = *(const uint32_t*)&x; o.im = *(const uint32_t*)&y; return o;
}
__device__ __forceinline__ h2c cmul_vc(h2c v, uint32_t s) {
    const __half2 h = *(const __half2*)&s, c = __low2half2(h), d = __high2half2(h), r = *(const __half2*)&v.re, i = *(const __half2*)&v.im;
    const __half2 x = __hfma2(i, d, __hmul2(r, c)), y = __hfma2(__hneg2(i), c, __hmul2(r, d));
    h2c o; o.re = *(const uint32_t*)&x; o.im = *(const uint32_t*)&y; return o;
}

constexpr int UT_HALF = 2240, UT_STRIDE = 4448;
constexpr int KT_T = 542, KT_C = 552, KT_D = 645, KT_BYTES = 720 * 4;
constexpr int VC_OFF = 80, VE_BASE = 1616;
constexpr int V_STRIDE = (1616 + 1024) * 4 + 80;
constexpr int KG_STAGE = 5248;
constexpr int Y_CS = 2080, Y_RS = 8 * Y_CS + 64;

constexpr int SC_RT = 0;
constexpr int SC_UT = 33408;
constexpr int SC_ST = SC_UT + 8 * UT_STRIDE;
constexpr int SC_KT = SC_ST + 8 * UT_STRIDE;
constexpr int SC_GT = SC_KT + 8 * KT_BYTES;
constexpr int SC_V = SC_GT + UT_STRIDE;
constexpr int SC_KG = SC_V + 4 * V_STRIDE;
constexpr int SC_MISC = SC_V + 8 * V_STRIDE;
static_assert(V_STRIDE % 128 == 16 && 8 * KG_STAGE <= 4 * V_STRIDE && 2 * Y_RS <= SC_UT && SC_UT % 128 == 0 && SC_ST % 128 == 0, "layout");
static_assert(SC_MISC % 16 == 0 && SC_MISC + 512 <= 232192, "layout");

__device__ __forceinline__ void window_task(uint32_t src, uint32_t d0, uint32_t d1, bool withE) {
    float S[35];
    {
        uint32_t w[20];
#pragma unroll
        for (int i = 0; i < 5; i++) {
            const uint4 v = lds128(src + ((i & 1) ? 0 : UT_HALF) + ((i + 1) >> 1) * 16);
            w[4 * i] = v.x; w[4 * i + 1] = v.y; w[4 * i + 2] = v.z; w[4 * i + 3] = v.w;
        }
        float s = 0.f; S[2] = 0.f;
#pragma unroll
        for (int i = 3; i < 26; i++) { s += (i & 1) ? bf_hi(w[i >> 1]) : bf_lo(w[i >> 1]); S[i] = s; }
#pragma unroll
        for (int i = 0; i < 8; i += 2)
            sts128((i & 4 ? d1 : d0) + (VC_OFF - 16) * 4 + 8 * (i & 2), pack_bf16(S[10 + i] - S[5 + i], S[5 + i] - S[2 + i]), pack_bf16(S[18 + i] - S[13 + i], S[13 + i] - S[10 + i]),
                   pack_bf16(S[11 + i] - S[6 + i], S[6 + i] - S[3 + i]), pack_bf16(S[19 + i] - S[14 + i], S[14 + i] - S[11 + i]));
        if (withE) {
#pragma unroll
            for (int i = 26; i < 35; i++) { s += (i & 1) ? bf_hi(w[i >> 1]) : bf_lo(w[i >> 1]); S[i] = s; }
#pragma unroll
            for (int i = 0; i < 8; i += 2)
                sts128((i & 4 ? d1 : d0) + VE_BASE * 4 + 8 * (i & 2), pack_bf16(S[19 + i] - S[12 + i], S[12 + i] - S[3 + i]), pack_bf16(S[27 + i] - S[20 + i], S[20 + i] - S[11 + i]),
                       pack_bf16(S[20 + i] - S[13 + i], S[13 + i] - S[4 + i]), pack_bf16(S[28 + i] - S[21 + i], S[21 + i] - S[12 + i]));
        }
    }
}

template <class F>
__device__ __forceinline__ void kgen(const uint32_t (&q)[8], uint32_t sb, int half, uint32_t stage, uint32_t pstage, int barid, int lane, uint32_t zero, uint32_t (&w)[12], F shadow) {
    const int t = lane & 3, mi = lane >> 3, r8 = lane & 7;
    {
        const uint32_t pAr = q[0], pAi = q[1], pBr = q[2], pBi = q[3], pCr = q[4], pCi = q[5], pDt = q[6], pD = q[7];
        const uint32_t wb = fresh(stage + lane * 16), za = fresh(stage + 5120 + ((lane >> 1) & 3) * 16 + mi * 4 + (lane & 1) * 2), zr = fresh(stage + 5120 + t * 16);
        const uint32_t oA = fresh(stage + (mi & 1) * 1024 + (mi >> 1) * 512 + r8 * 16), oB = fresh(stage + 2048 + mi * 512 + r8 * 16), oC = fresh(stage + 4096 + (mi & 1) * 512 + (mi >> 1) * 128 + r8 * 16);
        float acc[6][4];
#pragma unroll
        for (int a = 0; a < 6; a++) { acc[a][0] = acc[a][1] = acc[a][2] = acc[a][3] = 0.f; asm volatile("" : "+f"(acc[a][0]), "+f"(acc[a][1]), "+f"(acc[a][2]), "+f"(acc[a][3])); }
        shadow();
        sts32(zr, clock32());
        const float dt = rbf(__expf(bf_lo(pDt)));
        float ar = dt * bf_lo(pAr), ai = dt * bf_lo(pAi), ar1 = dt * bf_hi(pAr), ai1 = dt * bf_hi(pAi);
        float wr, wi, wr1, wi1;
        { const float br = dt * bf_lo(pBr), bi = dt * bf_lo(pBi), cr = bf_lo(pCr), ci = bf_lo(pCi); wr = cr * br - ci * bi; wi = cr * bi + ci * br; }
        { const float br = dt * bf_hi(pBr), bi = dt * bf_hi(pBi), cr = bf_hi(pCr), ci = bf_hi(pCi); wr1 = cr * br - ci * bi; wi1 = cr * bi + ci * br; }
        const uint32_t ex = max(__reduce_max_sync(0xffffffffu, __float_as_uint(fmaxf(fmaxf(fabsf(wr), fabsf(wi)), fmaxf(fabsf(wr1), fabsf(wi1))))) >> 23, 14u);
        const float scl = __uint_as_float((267u - ex) << 23);
        uint32_t W = pack_f16(wr * scl, wi * -scl);
        const uint32_t W1 = pack_f16(wr1 * scl, wi1 * -scl);
        if (threadIdx.x < 32) TSTAMP(20);

#pragma unroll 1
        for (int r = 0; r < 2; r++) {
            const cplx z1 = cexpk(ar, ai, 1.f), z64 = cexpk(ar, ai, 64.f);
            const cplx z2 = csq(z1), z4 = csq(z2), z8 = csq(z4), z16 = csq(z8), z32 = csq(z16);
            const cplx z128 = csq(z64), z256 = csq(z128), z512 = csq(z256);
            auto put = [&](int grp, h2c a, h2c b, h2c c, h2c d) { sts128(wb + grp * 1024, a.re, b.re, c.re, d.re); sts128(wb + grp * 1024 + 512, a.im, b.im, c.im, d.im); };
            {
                const uint32_t s4 = pack_f16(z4.re, z4.im), s256 = pack_f16(z256.re, z256.im), s512 = pack_f16(z512.re, z512.im);
                auto mix = [](h2c a, h2c b, uint32_t sel) { return h2c{__byte_perm(a.re, b.re, sel), __byte_perm(a.im, b.im, sel)}; };
                const h2c c10 = cmul_vc(h2c{pack_f16(z1.re, 1.f), pack_f16(z1.im, 0.f)}, W), c32 = cmul_sc(c10, pack_f16(z2.re, z2.im)), c54 = cmul_sc(c10, s4);
                put(2, c10, c32, c54, cmul_sc(c32, s4));
                const h2c d20 = cmul_sc(mix(c32, c10, 0x7632), s256), e04 = cmul_sc(mix(c10, c54, 0x7632), s512), f04 = cmul_sc(e04, s256);
                put(3, d20, cmul_sc(d20, s4), e04, f04);
                const h2c ef = mix(e04, f04, 0x5410), gh = cmul_sc(ef, s512), g8 = cmul_sc(gh, pack_f16(z8.re, z8.im));
                put(4, g8, cmul_sc(g8, s512), gh, ef);
            }
            {
                const uint32_t s32 = pack_f16(z32.re, z32.im), s64 = pack_f16(z64.re, z64.im), s128 = pack_f16(z128.re, z128.im);
                const h2c p0 = {pack_f16(1.f, z8.re), pack_f16(0.f, z8.im)}, p1 = cmul_s(p0, pack_f16(z16.re, z16.im)), p2 = cmul_s(p0, s32), p3 = cmul_s(p1, s32);
                put(0, p0, p1, p2, p3);
                put(1, cmul_s(p0, s64), cmul_s(p1, s64), cmul_s(p2, s64), cmul_s(p3, s64));
                sts16(za, s128); sts16(za + 64, s128 >> 16);
            }
            __syncwarp();
            {
                const uint32_t aA = fresh(oA), aB = fresh(oB), aC = fresh(oC), aZ = fresh(zr);
                const uint4 zc = lds128(aZ), zd = lds128(aZ + 64);
                const uint32_t zcs[4] = {zc.x, zc.y, zc.z, zc.w}, zds[4] = {zd.x, zd.y, zd.z, zd.w};
                uint32_t c[4];
#pragma unroll
                for (int k = 0; k < 4; k++) {
                    uint32_t a[4], b[4];
                    ldsm4t(a, aA + 128 * k); ldsm4t(b, aB + 128 * k);
                    if (!(k & 1)) ldsm4t(c, aC + 128 * k);
                    const h2c x = cmul_cd(h2c{a[0], a[2]}, *(const __half2*)&zcs[k], *(const __half2*)&zds[k]), y = cmul_cd(h2c{a[1], a[3]}, *(const __half2*)&zcs[k], *(const __half2*)&zds[k]);
                    mma_h(acc[0], a[0], a[1], a[2], a[3], b[0], b[1]);
                    mma_h(acc[1], a[0], a[1], a[2], a[3], b[2], b[3]);
                    mma_h(acc[2], a[0], a[1], a[2], a[3], c[2 * (k & 1)], c[2 * (k & 1) + 1]);
                    mma_h(acc[3], x.re, y.re, x.im, y.im, b[0], b[1]);
                    mma_h(acc[4], x.re, y.re, x.im, y.im, b[2], b[3]);
                    mma_h(acc[5], x.re, y.re, x.im, y.im, c[2 * (k & 1)], c[2 * (k & 1) + 1]);
                }
                asm volatile("" :: "f"(acc[0][0]), "f"(acc[1][0]), "f"(acc[2][0]), "f"(acc[3][0]), "f"(acc[4][0]), "f"(acc[5][0]) : "memory");
            }
            __syncwarp();
            ar = ar1; ai = ai1; W = W1;
        }
        if (threadIdx.x < 32) TSTAMP(21);
        const float i0 = __uint_as_float((ex + 243u) << 23);
        if (half) {
#pragma unroll
            for (int a = 0; a < 6; a++) sts128(wb + a * 512, __float_as_uint(acc[a][0]), __float_as_uint(acc[a][1]), __float_as_uint(acc[a][2]), __float_as_uint(acc[a][3]));
            sts32(stage + 3072, __float_as_uint(i0));
            bar_arrive(barid, 64);
        } else {
#pragma unroll
            for (int a = 0; a < 6; a++) { acc[a][0] *= i0; acc[a][1] *= i0; acc[a][2] *= i0; acc[a][3] *= i0; }
            if (lane == 0) acc[0][1] -= bf_lo(pD);
            sts32(zr, clock32());
            bar_sync(barid, 64);
            const uint32_t src = fresh(pstage);
            const float i1 = __uint_as_float(lds32(src + 3072));
#pragma unroll
            for (int a = 0; a < 6; a++) {
                const uint4 y = lds128(src + lane * 16 + a * 512);
                w[4 * (a % 3) + 2 * (a / 3)] = pack_bf16(fmaf(__uint_as_float(y.x), i1, acc[a][0]), fmaf(__uint_as_float(y.y), i1, acc[a][1]));
                w[4 * (a % 3) + 2 * (a / 3) + 1] = pack_bf16(fmaf(__uint_as_float(y.z), i1, acc[a][2]), fmaf(__uint_as_float(y.w), i1, acc[a][3]));
            }
            const uint32_t x0 = __shfl_up_sync(0xffffffffu, w[10], 2), x1 = __shfl_up_sync(0xffffffffu, w[11], 2);
            w[10] = w[8];
            if (t >= 2) { w[8] = x0; w[9] = x1; }
        }
    }
}

__device__ __forceinline__ int swap01(int i) { return (i & ~3) | ((i & 1) << 1) | ((i >> 1) & 1); }
enum { BC_AUX = 0, BC_S = 5, BC_KG = 15 };

__device__ __forceinline__ void fetch_gates(const Params& p, int i, int lane, unsigned epoch, uint32_t dst) {
    const uint32_t par = (epoch & 1) ? 0x80008000u : 0u;
    uint4 v;
#pragma unroll 1
    for (int it = 0;; it++) {
        v = ld_rlx128(p.s->gate + 256 * i + 8 * lane);
        v.x ^= par; v.y ^= par; v.z ^= par; v.w ^= par;
        if (__all_sync(0xffffffffu, (v.x & v.y & v.z & v.w & 0x80008000u) == 0x80008000u)) break;
        if (it > (1 << 20)) give_up();
    }
    sts128(dst + (8 + 16 * i + (lane >> 1)) * 16, v.x, v.y, v.z, v.w);
}
__device__ __forceinline__ void store_rows(const CUtensorMap* m, uint32_t src, int col, int row) {
    asm volatile("cp.async.bulk.tensor.5d.global.shared::cta.bulk_group [%0, {%2, %3, %3, %3, %4}], [%1];" :: "l"(m), "r"(src), "r"(col), "r"(0), "r"(row) : "memory");
}

__device__ __forceinline__ void store_or_add(void* o, const uint32_t (&y)[4], uint32_t add) {
    asm volatile("{ .reg .pred p; setp.ne.u32 p, %5, 0; @!p st.global.v4.u32 [%0], {%1,%2,%3,%4}; @p red.relaxed.gpu.global.add.noftz.v4.bf16x2 [%0], {%1,%2,%3,%4}; }"
                 :: "l"(o), "r"(y[0]), "r"(y[1]), "r"(y[2]), "r"(y[3]), "r"(add) : "memory");
}

__device__ __forceinline__ void conv_aux(const Params& p, const CUtensorMap* mU, uint32_t sb, int aw, int lane, int bid, unsigned epoch) {
    const unsigned t0 = clock32();
    const int g = lane >> 2, t = lane & 3, mi = lane >> 3, r8 = lane & 7;
    const int rank = bid & 1, slab = bid >> 1;
    const uint32_t bar_y = sb + SC_MISC, bar_u = bar_y + 32, bar_v = bar_y + 40, bar_box = bar_y + 64 + 8 * aw, s_bm = bar_y + 128;
    if (elect()) {
        mbar_init(bar_box, 1); mbar_fence();
        mbar_expect(bar_box, 4096);
        if (UDELAY) until(t0, UDELAY);
        tma4d(sb + SC_RT + 4096 * aw, mU, 16 * slab, 0, 0, 16 * rank + 2 * aw, bar_box);
        mbar_init(bar_y + 8 * aw, aw < 4 ? 9 : aw == 5 ? 8 : 1); mbar_fence();
        if (aw < 5) mbar_expect(bar_y + 8 * aw, aw == 4 ? 16384 : 4096);
    }
    __syncwarp();
    asm volatile("barrier.cluster.arrive.relaxed.aligned;" ::: "memory");
    asm volatile("setmaxnreg.dec.sync.aligned.u32 88;");
    const uint32_t ut = sb + SC_UT + aw * UT_STRIDE;
    sts128(ut + (mi >> 1) * (SC_ST - SC_UT) + (mi & 1) * UT_HALF + r8 * 16, 0, 0, 0, 0);
    if (lane < 16) sts128(s_bm + lane * 16, 0, 0, 0, 0);
    {
        const uint32_t dst = sb + SC_UT + swap01(g) * UT_STRIDE + (8 + 64 * rank + 8 * aw + t) * 16;
        const uint32_t rdst = mapa(dst, rank ^ 1), rbar = mapa(bar_u, rank ^ 1);
        asm volatile("barrier.cluster.wait.acquire.aligned;" ::: "memory");
        mbar_wait(bar_box);
        if (aw == 0) TSTAMP(1);
        const uint32_t src = fresh(sb + SC_RT) + aw * 4096 + (8 * mi + 4 * (r8 & 1) + (r8 >> 1)) * 32 + ((rank ^ (r8 & 1)) << 4);
        uint32_t x[8][4];
#pragma unroll
        for (int i = 0; i < 4; i++) { ldsm4t(x[i], src + 1024 * i); ldsm4t(x[4 + i], (src ^ 16) + 1024 * i); }
        asm volatile("" :: "r"(x[0][0]), "r"(x[1][0]), "r"(x[2][0]), "r"(x[3][0]) : "memory");
#pragma unroll
        for (int i = 0; i < 4; i++) st_async128(rdst + (i & 1) * UT_HALF + 32 * (i & 2), x[4 + i][0], x[4 + i][1], x[4 + i][2], x[4 + i][3], rbar);
#pragma unroll
        for (int i = 0; i < 4; i++) sts128(dst + (i & 1) * UT_HALF + 32 * (i & 2), x[i][0], x[i][1], x[i][2], x[i][3]);
    }
    bar_sync(BC_AUX, 256);
    mbar_wait_cluster(bar_u);
    if (aw == 0) TSTAMP(2);
    {
        const uint32_t a = fresh(ut) + (mi & 1) * UT_HALF + (64 * (mi >> 1) + r8) * 16;
        uint4 v = lds128(a);
#pragma unroll
        for (int i = 1; i <= 8; i++) {
            const uint4 w = lds128(a + 128 * i);
            sts128(a + 128 * i + (SC_ST - SC_UT), badd2(v.x, w.x), badd2(v.y, w.y), badd2(v.z, w.z), badd2(v.w, w.w));
            v = w;
        }
    }
    bar_arrive(BC_S + aw, 64);
    if (aw == 0) TSTAMP(3);
    {
        uint32_t ws = sb + SC_UT + t * UT_STRIDE + (g + 6) * 16, wd = sb + SC_V + t * V_STRIDE + 64 * g, sw = 16 * (g & 2);
#pragma unroll 1
        for (int k = aw; k < 25; k += 8) {
            if (k - aw == 8) {
                bar_sync(BC_KG, 384);
                if (lane < 16) sts128(sb + SC_V + aw * V_STRIDE + lane * 16, 0, 0, 0, 0);
            }
            if (k == 24) { ws -= (g & 1) * 4 * UT_STRIDE + 16 * g; wd -= (g & 1) * 4 * V_STRIDE + 64 * g; sw = 0; }
            const int h = k >= 12, a = k - 12 * h;
            const uint32_t d = wd + h * 4 * V_STRIDE + 512 * a;
            window_task(fresh(ws) + h * 4 * UT_STRIDE + 128 * a, d + sw, d + (sw ^ 32), a < 8);
        }
    }
    if (aw == 0) TSTAMP(9);
    {
        if (aw >= 2) fetch_gates(p, aw, lane, epoch, sb + SC_GT + (lane & 1) * UT_HALF);
        __syncwarp();
        if (elect()) { mbar_arrive(bar_v); prefetch_map(mU + 4); }
        next_epoch(p, epoch);
        if (aw == 0) TSTAMP(4);
        if (aw == 7) {
            const int row = key_row(wait_sel(p, slab >> 1, r8, key_tag(epoch)));
            if (lane < 8) asm volatile("red.shared.or.b32 [%0], %1;" :: "r"(s_bm + (row >> 5) * 4), "r"(1u << (row & 31)) : "memory");
            TSTAMP(10);
        }
        bar_sync(BC_AUX, 256);
        const uint32_t src = sb + SC_RT + ((r8 >> 1) & 1) * Y_RS + (2 * mi + (r8 & 1)) * Y_CS + (2 * aw + (r8 >> 2)) * 16;
        const int L = 2 * aw + (t >> 1);
        const int row0 = 256 * rank + 128 * (g >> 2) + 32 * (L & 3) + 16 * (g & 1) + 8 * ((g >> 1) & 1) + (L >> 2);
        __nv_bfloat16* outp = p.out + (size_t)row0 * DM + 16 * slab + 8 * (t & 1);
        const uint32_t stg = sb + SC_ST + 4096 * aw, so = (g >> 1) * 256 + (t >> 1) * 64 + (g & 1) * 32 + (t & 1) * 16;
#pragma unroll 1
        for (int s = 1; s < 4; s++) {
            const uint32_t bm = lds32(fresh(s_bm) + (16 * s + (row0 >> 5)) * 4) >> (row0 & 31);
            const bool routed = __any_sync(0xffffffffu, bm & 0x11u);
            if (aw == s) mbar_wait_cluster(bar_y + 8 * s);
            bar_sync(BC_AUX, 256);
            const uint32_t sf = fresh(src) + 512 * s;
            uint32_t y[2][4];
            ldsm4t(y[0], sf); ldsm4t(y[1], sf + 256);
            if (routed) {
#pragma unroll
                for (int k = 0; k < 2; k++) store_or_add(outp + (size_t)(512 * s + 4 * k) * DM, y[k], bm & (1u << (4 * k)));
            } else {
                sts128(stg + so + 1024 * s, y[0][0], y[0][1], y[0][2], y[0][3]); sts128(stg + so + 1024 * s + 128, y[1][0], y[1][1], y[1][2], y[1][3]);
                asm volatile("fence.proxy.async.shared::cta;" ::: "memory");
                __syncwarp();
                if (elect()) store_rows(mU + 4, stg + 1024 * s, 16 * slab, 512 * s + 256 * rank + 64 * (aw & 1) + (aw >> 1));
            }
            if (aw == 0) TSTAMP(16 + s);
        }
        if (elect()) { asm volatile("cp.async.bulk.commit_group;" ::: "memory"); asm volatile("cp.async.bulk.wait_group.read 0;" ::: "memory"); }
        if (aw == 0) TFLUSH();
    }
}

__device__ __forceinline__ uint32_t k_tag(unsigned epoch) { return epoch << 16 | 0x80000000u; }
__device__ __forceinline__ void publish_k(uint4* kp, const uint32_t (&w)[12], unsigned epoch, bool full) {
#pragma unroll
    for (int i = 0; i < 3; i++)
        asm volatile("st.relaxed.gpu.global.v4.u32 [%0], {%1,%2,%3,%4};" :: "l"(kp + 32 * i), "r"(w[3 * i]), "r"(w[3 * i + 1]), "r"(w[3 * i + 2]),
                     "r"(full ? __byte_perm(w[9 + (i >> 1)], k_tag(epoch), i == 1 ? 0x7632 : 0x7610) : k_tag(epoch)));
}
template <bool FULL>
__device__ __forceinline__ void k_tables(uint32_t kt, int lane, const uint32_t (&w)[12]) {
    const int g = lane >> 2, t = lane & 3, mi = lane >> 3, r8 = lane & 7;
    uint32_t x3 = w[7], re[4], rx[4];
#pragma unroll
    for (int i = 0; i < 4; i++) {
        re[i] = __shfl_sync(0xffffffffu, w[i], lane + 31);
        rx[i] = __shfl_sync(0xffffffffu, w[4 + i], lane + (i == 0 && lane == 29 ? 5 : 1 + 2 * t));
    }
    if (FULL) {
        asm volatile("stmatrix.sync.aligned.m8n8.x2.trans.shared.b16 [%0], {%1,%2};" :: "r"(kt + (KT_D + 7) * 4 + 64 * t + 16 * (mi & 1) + 8 * (r8 & 4)), "r"(w[8]), "r"(w[9]) : "memory");
        if (lane == 2) {
            sts32(kt + (KT_C + 78) * 4, w[10] & 0xffffu);
            sts128(kt + (KT_T + 2) * 4, 0, w[10] & 0xffffu, __byte_perm(w[10], 0, 0x1010), w[10] << 16);
        }
        if (lane == 29) x3 = bsub2(x3, rx[0] & 0xffffu);
    }
#pragma unroll
    for (int i = 0; i < 4; i++) {
        sts64(kt + (16 + 64 * i) * 4 + 8 * lane, __byte_perm(w[i], lane ? re[i] : i ? re[i - 1] : 0, 0x5432), w[i]);
        const uint32_t x = i < 3 ? w[4 + i] : x3, aa = __byte_perm(x, 0, 0x3232);
        if (t < 2) sts128(kt + (272 + 64 * i + 8 * g + 4 * t) * 4, i == 0 && lane == 0 ? __byte_perm(x, re[3], 0x5432) : aa, aa, x,
                          __byte_perm(lane != 29 ? rx[i] : i < 3 ? rx[(i + 1) & 3] : FULL ? 0 : rx[0] << 16, x, 0x5432));
        else if (FULL) sts32(kt + (KT_C - 50 + 8 * i + 32 * t + g) * 4, x);
    }
}

__device__ __forceinline__ void conv_main(const Params& p, uint32_t sb, int warp, int lane0, int bid, unsigned epoch, uint32_t (&w)[12]) {
    asm volatile("setmaxnreg.inc.sync.aligned.u32 168;");
    const int lane = __shfl_sync(0xffffffffu, lane0, lane0);
    const int g = lane >> 2, t = lane & 3, mi = lane >> 3, r8 = lane & 7;
    const int rank = bid & 1;
    const uint32_t bar_y = sb + SC_MISC, bar_v = bar_y + 40;
    next_epoch(p, epoch);
    if (warp < 4) {
        asm volatile("" :: "r"(w[0]), "r"(w[2]), "r"(w[4]), "r"(w[6]), "r"(w[8]), "r"(w[10]) : "memory");
        bar_arrive(BC_KG, 384);
    } else {
        const uint4* src = p.s->kp + (8 * bid + warp) * 96 + lane0;
#pragma unroll 1
        for (int it = 0;; it++) {
            uint32_t bad = 0, e[3];
#pragma unroll
            for (int i = 0; i < 3; i++) { const uint4 v = ld_rlx128(src + 32 * i); w[3 * i] = v.x; w[3 * i + 1] = v.y; w[3 * i + 2] = v.z; e[i] = v.w; bad |= v.w ^ k_tag(epoch); }
            w[9] = __byte_perm(e[0], e[1], 0x5410); w[10] = e[2];
            const bool ok = __all_sync(0xffffffffu, bad < 65536);
            if (ok) break;
            if (it > (1 << 20)) give_up();
        }
    }
    if ((warp & 3) == 0) TSTAMP(5 + (warp >> 2));
    k_tables<true>(sb + SC_KT + warp * KT_BYTES, lane0, w);
    asm volatile("barrier.cluster.wait.acquire.aligned;" ::: "memory");
    bar_sync(BC_S + swap01(warp), 64);
    __syncwarp();
    if ((warp & 3) == 0) TSTAMP(7 + (warp >> 2));
    {
        const uint32_t ut = fresh(sb + SC_UT) + swap01(warp) * UT_STRIDE, kt = fresh(sb + SC_KT) + warp * KT_BYTES;
        uint32_t u1 = ut + (mi & 1) * UT_HALF + (8 + r8) * 16 + (mi >> 1) * 128;
        auto dup = [&](uint32_t v) { return v ^ p.zero; };
        uint32_t kp = kt + (16 + g - 2 * t) * 4;
        float acc[16][4];
        {
            const uint32_t c0 = lds32(kp + 2048), c1 = lds32(kp + 2080), c2 = lds32(kp + 2016), c3 = dup(c0);
            const uint32_t e0 = lds32(kp + (KT_T - 16) * 4), e1 = lds32(kp + (KT_T - 8) * 4), e2 = lds32(kp + (KT_T - 24) * 4), e3 = dup(e0);
            const uint32_t f0 = dup(e1), f1 = lds32(kp + KT_T * 4);
            const uint32_t uo = ut + UT_HALF + (7 + lane) * 16;
#pragma unroll
            for (int i = 0; i < 16; i++) { acc[i][0] = acc[i][1] = acc[i][2] = acc[i][3] = 0.f; }
#pragma unroll
            for (int mu = 0; mu < 8; mu += 4) {
                uint32_t b[4];
                ldsm4(b, uo + 128 * mu);
#pragma unroll
                for (int k = 0; k < 4; k++) mma_bf8(acc[mu + 8 + k], f0, f1, b[k]);
            }
#pragma unroll
            for (int mu = 0; mu < 12; mu += 2) {
                uint32_t b[4];
                ldsm4(b, u1 + 128 * mu);
                mma_bf(acc[mu + 4], c0, c1, c2, c3, b[0], b[1]);
                mma_bf(acc[mu + 5], c0, c1, c2, c3, b[2], b[3]);
                if (mu < 8) { mma_bf(acc[mu + 8], e0, e1, e2, e3, b[0], b[1]); mma_bf(acc[mu + 9], e0, e1, e2, e3, b[2], b[3]); }
            }
        }
        {
            float M[8][4];
#pragma unroll
            for (int i = 0; i < 8; i++) { M[i][0] = M[i][1] = M[i][2] = M[i][3] = 0.f; }
            uint32_t s[8][4], a3[4];
            const uint32_t kb = kp, ub = dup(u1), uc = u1 + (mi >> 1) * 128;
            auto frag = [&](uint32_t (&a)[4], uint32_t x) { a[0] = lds32(x); a[1] = lds32(x + 32); a[2] = lds32(x - 32); a[3] = dup(a[0]); };
            frag(a3, kp + 1536);
#pragma unroll
            for (int i = 1; i < 8; i++) ldsm4(s[i], u1 + (SC_ST - SC_UT) + 256 * i);
            __syncwarp();
            uint32_t ko = 0, uo = 0;
            const uint32_t pub = bid >= 48 ? PUBY : PUBIT;
#pragma unroll 1
            for (uint32_t n = warp < 4 ? pub : 8;; n = 8 - pub) {
#pragma unroll 1
            for (; n; n--) {
                uint32_t a2[4], a1[4], a0[4], b[4][4];
                ko = fresh(ko); uo = fresh(uo);
                kp = kb + ko; u1 = ub + uo;
                const uint32_t up = uc + uo;
                ko += 64; uo -= 16;
                frag(a2, kp + 1024);
#pragma unroll
                for (int i = 1; i < 4; i++) ldsm4(b[i], up + 512 * i);
                asm("ldmatrix.sync.aligned.m8n8.x2.shared.b16 {%0,%1}, [%2];" : "=r"(b[0][2]), "=r"(b[0][3]) : "r"(up + 256));
                frag(a1, kp + 512); frag(a0, kp);
                kp += 64; u1 -= 16;
#pragma unroll
                for (int i = 1; i < 7; i++) mma_bf(acc[2 * i + 2], a3[0], a3[1], a3[2], a3[3], s[i][0], s[i][1]);
#pragma unroll
                for (int e = 0; e < 4; e++) a3[e] = bsub2(a2[e], a3[e]);
#pragma unroll
                for (int i = 1; i < 7; i++) mma_bf(acc[2 * i + 3], a2[0], a2[1], a2[2], a2[3], s[i][2], s[i][3]);
                ldsm4(s[1], u1 + (SC_ST - SC_UT) + 256);
#pragma unroll
                for (int i = 1; i < 7; i++) mma_bf(M[i + 1], a3[0], a3[1], a3[2], a3[3], b[i >> 1][2 * (i & 1)], b[i >> 1][2 * (i & 1) + 1]);
                frag(a3, kp + 1536);
#pragma unroll
                for (int i = 2; i < 8; i++) mma_bf(acc[2 * i], a1[0], a1[1], a1[2], a1[3], s[i][0], s[i][1]);
#pragma unroll
                for (int e = 0; e < 4; e++) a1[e] = bsub2(a0[e], a1[e]);
#pragma unroll
                for (int i = 2; i < 8; i++) { mma_bf(acc[2 * i + 1], a0[0], a0[1], a0[2], a0[3], s[i][2], s[i][3]); ldsm4(s[i], u1 + (SC_ST - SC_UT) + 256 * i); }
#pragma unroll
                for (int i = 2; i < 8; i++) mma_bf(M[i], a1[0], a1[1], a1[2], a1[3], b[i >> 1][2 * (i & 1)], b[i >> 1][2 * (i & 1) + 1]);
            }
            if (ko == 512) break;
            publish_k(p.s->kp + (8 * bid + warp) * 96 + lane, w, epoch, false);
            }
            u1 = ub;
#pragma unroll
            for (int i = 2; i < 8; i++)
#pragma unroll
                for (int c = 0; c < 4; c++) { acc[2 * i][c] += M[i][c]; acc[2 * i + 1][c] -= M[i][c]; }
        }
        if ((warp & 3) == 0) TSTAMP(11 + (warp >> 2));
        mbar_wait(bar_v);
        const uint32_t vt = fresh(sb + SC_V) + swap01(warp) * V_STRIDE;
        const uint32_t g1 = fresh(u1) - ut + sb + SC_GT;
        const uint32_t ydst = sb + SC_RT + rank * Y_RS + warp * Y_CS + lane * 16;
        const uint32_t ydr = mapa(ydst, rank ^ 1), ybr = mapa(bar_y, rank ^ 1);
        auto stairs = [&](auto R) {
        uint32_t ug[2][2][4];
        auto ld_ug = [&](int i) { ldsm4t(ug[i & 1][0], u1 + 256 * i); ldsm4t(ug[i & 1][1], g1 + 256 * i); };
        auto ship = [&](int i) {
            const uint32_t (&u)[4] = ug[i & 1][0], (&gg)[4] = ug[i & 1][1];
            const uint32_t y0 = gmix(gg[0], acc[2 * i][0], acc[2 * i][1], u[0]), y1 = gmix(gg[1], acc[2 * i][2], acc[2 * i][3], u[1]);
            const uint32_t y2 = gmix(gg[2], acc[2 * i + 1][0], acc[2 * i + 1][1], u[2]), y3 = gmix(gg[3], acc[2 * i + 1][2], acc[2 * i + 1][3], u[3]);
            if ((i & 1) != R.value) st_async128(ydr + 512 * (i >> 1), y0, y1, y2, y3, ybr + 8 * (i >> 1));
            else asm volatile("{ .reg .pred q; setp.eq.u32 q, %6, 0; st.shared.v4.u32 [%0], {%2,%3,%4,%5}; bar.warp.sync 0xffffffff; @q mbarrier.arrive.shared::cta.b64 _, [%1]; }"
                              :: "r"(ydst + 512 * (i >> 1)), "r"(bar_y + 8 * (i >> 1)), "r"(y0), "r"(y1), "r"(y2), "r"(y3), "r"(lane) : "memory");
        };
        const uint32_t VD = vt + (VC_OFF - 400 - 16 * t) * 4 + (8 * g ^ 16 * (-t & 2)), VD2 = vt + (VC_OFF - 415 - 16 * t) * 4 + (8 * g ^ 16 * (~t & 2));
        uint2 bd[10];
        uint32_t x[2][4][4];
        auto ld4 = [&](uint32_t (&v)[4], int dl) { const uint2 w = lds64(VD + 256 * dl); v[0] = w.x; v[1] = w.y; v[2] = lds32(VD2 + 256 * dl); v[3] = dup(w.x); };
        auto mm4 = [&](const uint32_t (&v)[4], int dl) {
#pragma unroll
            for (int s = dl & 1; s < 10; s += 2) if ((dl + s) / 2 >= 4 && (dl + s) / 2 < 16) mma_bf(acc[(dl + s) / 2], v[0], v[1], v[2], v[3], bd[s].x, bd[s].y);
        };
        const uint32_t KE = kt + (KT_D + g + t) * 4, VE = vt + (VE_BASE - 912 - 16 * t) * 4 + (8 * g ^ 16 * (~t & 2));
        uint32_t b0[8], b1[8];
        auto ld8 = [&](uint32_t (&v)[4], int dl) { const uint2 w = lds64(VE + 512 * dl), z = lds64(VE + 512 * dl - 256); v[0] = w.x; v[1] = w.y; v[2] = z.x; v[3] = z.y; };
        auto mm8 = [&](const uint32_t (&v)[4], int dl, int lo, int hi) {
#pragma unroll
            for (int s = 0; s < 8; s++) if (dl + s >= lo && dl + s < hi) mma_bf(acc[dl + s], v[0], v[1], v[2], v[3], b0[s], b1[s]);
        };
        ld4(x[0][0], 6);
#pragma unroll
        for (int s = 0; s < 10; s++) bd[s] = lds64(kt + (KT_C + 2 * g + 2 * t + 8 * s) * 4);
        mm4(x[0][0], 6);
        uint32_t e[4][4];
#pragma unroll
        for (int k = 1; k < 6; k++) {
#pragma unroll
            for (int j = 0; j < 4; j++) ld4(x[k & 1][j], 4 * k + 3 + j);
            ld_ug(k + 1);
            if (k == 3) {
#pragma unroll
                for (int s = 0; s < 8; s++) { b0[s] = lds32(KE + 32 * s); b1[s] = lds32(KE + 32 * s + 16); }
            }
            if (k > 1) ship(k);
#pragma unroll
            for (int j = 0; j < 4; j++) {
                mm4(x[k & 1][j], 4 * k + 3 + j);
                if (k == 3) { uint32_t v[4], z[4]; ld8(e[j], 8 + j); ld8(v, 12 + j); ld4(z, 30 - j); mm8(v, 12 + j, 12, 16); mm8(e[j], 8 + j, 8, 12); mm4(z, 30 - j); }
                if (k == 5) { ld8(e[j], 8 + j + p.zero); mm8(e[j], 8 + j, 12, 16); }
            }
        }
        ld_ug(7);
        ship(7 - R.value); ship(6 + R.value);
        };
        if (rank) stairs(std::integral_constant<int, 1>()); else stairs(std::integral_constant<int, 0>());
        if ((warp & 3) == 0) TSTAMP(14 + (warp >> 2)); else TSTAMP(21 + warp);
    }
}

constexpr int SF_WD = 73728;
constexpr int SF_RED = 49152;
constexpr int MU_HALF = 640, MU_STRIDE = 1344, SM_RAW = 98304, SM_UT = SM_RAW + 16384, SM_G = SM_UT + 16 * MU_STRIDE, SM_Y = 196608, SM_KT = 138880, SM_KW = SM_G - 49152;
constexpr int SF_XS = 221184;
constexpr int SF_MISC = SF_XS + 8 * 1168;
constexpr int SF_KG = SF_MISC - 10 * KG_STAGE;
constexpr int SF_WR = SF_KG - 2304;
constexpr int FB_X = 64, FB_KDONE = 72, FB_KEYS = 80, FB_FREE = 88  , FB_W = 104, FB_D = FB_W + 72, FB_MU = FB_D + 96, FB_MG = FB_MU + 8, FB_MT = FB_MU + 16, FS_PART = 512, FS_TOK = 896, FS_BM = 1024;
enum { BAR_F = 6, BAR_R = 7, BAR_GU = 8, BAR_RED = 9, BAR_R2 = 10, BAR_X = 11, BAR_G = 12  , BAR_M = 15 };
static_assert(SF_KG % 128 == 0 && NPRE <= 8 && SM_KT + 4 * 2112 <= 147456 && SM_G + MU_STRIDE <= SF_WR - 4 * 9216 && SM_KW + 6 * 2112 >= SM_RAW && SM_KW + 12 * 2112 <= SM_UT, "layout");

__device__ __forceinline__ int mini_ch0(int f) { return f < NW ? 16 * (f - 12) : 32 * (f - NW); }

__device__ __forceinline__ void ffn_front(const Params& p, const CUtensorMap* maps, uint32_t sb, int warp, int lane, int f, unsigned epoch) {
    const unsigned t0 = clock32();
    const int g = lane >> 2, t = lane & 3, mi = lane >> 3, r8 = lane & 7;
    const bool isx = f < NX;
    const int nrw = f < 8 ? 6 : 4, r0 = f < 8 ? 48 * f : 128 + 32 * f;
    const int rw = warp < 12 ? 13 - warp : warp ^ (warp < 14 ? 10 : 15);
    const uint32_t bar_row = sb + SF_MISC  , bar_x = bar_row + FB_X;
    const uint32_t s_part = bar_row + FS_PART  , s_tok = bar_row + FS_TOK  ;
    const uint32_t rows = sb + SF_WR - 9216 * (rw + 1);
    {
#pragma unroll 1
        for (int i = warp < 10 ? 30 : warp - 10; i < 29; i += 6) if (elect()) mbar_init(bar_x + 8 * i, 1 << max(i - 26, 0));
        const uint32_t bytes = rw < 6 ? 9216 : 1152, dst = rw < 6 ? rows : sb + SF_WR + (rw & 1) * 1152;
        const __nv_bfloat16* src = rw < 6 ? p.u + (size_t)(r0 + 8 * rw) * DM : (rw & 1) ? p.gatew : p.wr;
        if (elect()) { mbar_init(bar_row + 8 * rw, 1); mbar_fence(); mbar_expect(bar_row + 8 * rw, bytes); }
        if (rw < nrw) until(t0, RDELAY);
        if (rw < nrw || rw >= 6) { if (elect()) bulk_g2s(dst, src, bytes, bar_row + 8 * rw); }
    }
    uint4* const kdst = p.s->keys + (lane >> 1) * 128 + 2 * f + (lane & 1);
    if (warp == 13) {
        stg128(kdst, 0, 0, 0, 0);
        sts32(s_part + 64 + lane * 4, 0); sts32(bar_row + FS_BM + lane * 4, 0);
        if (lane < 8 && isx && !(f & 1)) st_rlx32(&p.s->sel[32 * f + lane], 0);
    }
    __syncwarp();
    bar_sync(BAR_F, f < 12 ? 256 : 192);
    bar_arrive(0, NTHR);
    if (warp == 15) TSTAMP(1);

    if (warp == 12) {
        if (lane < 22) mbar_expect(bar_row + FB_W + 8 * lane, lane < 9 ? 24576 : lane < 21 ? 12288 : f < NW ? 16384 : 32768);
        if (elect()) { prefetch_map(maps + 1); prefetch_map(maps + 2); prefetch_map(maps + (isx ? 3 : 5)); }
        unsigned tb = t0 + WDELAY;
        auto pieces = [&](int n, int end, uint32_t dst) {
#pragma unroll 1
            for (; n < end; n++, dst += 12288) {
                until(tb, 0); tb += WGAP;
                if (elect()) tma3d(dst, maps + 1 + (n & 1), 0, 64 * (n >> 1), 3 * f, bar_row + FB_W + 8 * (n >> 1));
            }
        };
        if (!isx) {
            until(tb, MDELAY);
#pragma unroll 1
            for (int k = f >= NW; k >= 0; k--) if (elect()) tma4d(sb + SM_RAW - 49152 * k, maps + 5, mini_ch0(f) + 16 * k, 0, 0, 0, bar_row + FB_MU);
            if (f >= NW) return;
        }
#pragma unroll 1
        for (int i = 0; i < 4; i++) {
            if (i == 1) { mbar_wait(bar_row + FB_KEYS); mbar_wait(bar_row + FB_KDONE); tb = clock32() + RESUME; }
            if (i == 3) mbar_wait(bar_row + FB_FREE);
            const int n = ((0x0c080000 + NPRE * 256) >> (8 * i)) & 255;
            pieces(n, ((0x120c0800 + NPRE) >> (8 * i)) & 255, sb + 12288 * (((0x000c0000 + NPRE * 256) >> (8 * i)) & 255));
        }
        TSTAMP(12);
        if (isx) {
#pragma unroll 1
            for (int i = 0; i < 12; i++) {
                const int n = (0x987610ba5432ull >> (4 * i)) & 15;
                if (i == 6) mbar_wait(bar_row + FB_FREE + 8);
                until(tb, 0); tb += DGAP;
                if (elect()) tma2d(sb + SF_WD + n * 12288, maps + 3, 32 * (f >> 1), 2304 * (f & 1) + 192 * n, bar_row + FB_D + 8 * n);
            }
            TSTAMP(13);
        }
    } else if (warp == 13) {
        const uint32_t tag = key_tag(epoch), par = (epoch & 1) ? 0u : 0x8000u;
        bar_sync(BAR_R, 32 * (nrw + 1));
        TSTAMP(3);
        {
            const uint32_t sg = fresh(s_part) + 192 + lane * 4;
            const uint32_t gb = pack_bf16(sigmoidf_(rbf(__uint_as_float(lds32(sg)))), sigmoidf_(rbf(__uint_as_float(lds32(sg + 128))))) | par | (par << 16);
            asm volatile("st.relaxed.gpu.global.u16 [%0], %1;" :: "l"(p.s->gate + r0 + lane), "h"((unsigned short)gb) : "memory");
            if (nrw > 4 && lane < 16) asm volatile("st.relaxed.gpu.global.u16 [%0], %1;" :: "l"(p.s->gate + r0 + 32 + lane), "h"((unsigned short)(gb >> 16)) : "memory");
        }
        bar_sync(BAR_R2, 32 * (nrw + 1));
        {
            const uint4 v = lds128(fresh(s_tok) + (lane & 1) * 16);
            asm volatile("st.relaxed.gpu.global.v4.u32 [%0], {%1,%2,%3,%4};" :: "l"(kdst), "r"(v.x | tag), "r"(v.y | tag), "r"(v.z | tag), "r"(v.w | tag) : "memory");
        }
        TSTAMP(4);
        if (lane == 0) { mbar_arrive(bar_row + FB_KEYS); mbar_expect(bar_x, 8 * 1152); }
        if (f >= NW) return;
        uint32_t k[16];
        const uint4* src = p.s->keys + (f & 15) * 128 + lane;
#pragma unroll 1
        for (int it = 0;; it++) {
            uint32_t bad = 0;
#pragma unroll
            for (int i = 0; i < 4; i++) {
                const uint4 x = ld_rlx128(src + (i < 3 || lane < 24 ? 32 * i : 64));
                k[i] = x.x; k[4 + i] = x.y; k[8 + i] = x.z; k[12 + i] = x.w;
                bad |= x.x ^ tag;
            }
            const bool ok = __all_sync(0xffffffffu, (bad & 0xf800u) == 0);
            if (ok) break;
            if (it > (1 << 20)) give_up();
        }
        TSTAMP(5);
        uint32_t key = 0;
#pragma unroll 2
        for (int r = 0; r < 8; r++) {
            const uint32_t m = __reduce_max_sync(0xffffffffu, max(max(k[0], k[1]), max(k[2], k[3])));
#pragma unroll
            for (int i = 0; i < 4; i++) {
                const bool pop = k[i] == m;
                k[i] = pop ? k[4 + i] : k[i]; k[4 + i] = pop ? k[8 + i] : k[4 + i]; k[8 + i] = pop ? k[12 + i] : k[8 + i]; k[12 + i] = pop ? 0 : k[12 + i];
            }
            if (r8 == r) key = m;
        }
        const int row = key_row(key);
        sts32(s_tok + r8 * 8, row);
        bar_arrive(BAR_X, 160);
        TSTAMP(6);
        if (isx) {
            if (!(f & 1)) {
                __nv_bfloat16* o = p.out + (size_t)row * DM + 16 * f + 8 * mi;
                asm volatile("st.relaxed.gpu.global.v4.u32 [%0], {%1,%1,%1,%1};" :: "l"(o), "r"(0) : "memory");
                if (__any_sync(0xffffffffu, ld_rlx32(o) != 0)) give_up();
                if (lane < 8) st_rlx32(&p.s->sel[32 * f + lane], key);
            } else wait_sel(p, f >> 1, r8, tag);
            uint32_t gb;
#pragma unroll 1
            for (int it = 0;; it++) {
                asm volatile("ld.relaxed.gpu.global.u16 %0, [%1];" : "=r"(gb) : "l"(p.s->gate + row) : "memory");
                gb ^= par;
                if (!(gb & 0x8000u)) break;
                if (it > (1 << 20)) give_up();
            }
            const uint32_t rb = key ^ 0x80000000u, rv = (rb ^ (((int)rb >> 31) & 0x7fff0000u)) & 0xffff0000u;
            sts32(s_tok + r8 * 8 + 4, __float_as_uint(rbf(1.0f - bf_lo(gb)) * rbf(sigmoidf_(__uint_as_float(rv)))));
            __syncwarp();
            TSTAMP(7);
            bar_arrive(BAR_RED, 416);
        }
    } else {
        if (rw < nrw) {
            float c[3][4];
#pragma unroll
            for (int i = 0; i < 3; i++) { c[i][0] = c[i][1] = c[i][2] = c[i][3] = 0.f; }
            mbar_wait(bar_row + 48); mbar_wait(bar_row + 56);
            const uint32_t b = fresh(sb + SF_WR) + (g & 1) * 1152 + (g >> 2) * 64 + t * 16 + (g & 2) * 2;
            uint32_t w[18][2];
#pragma unroll
            for (int kb = 0; kb < 18; kb++) { const uint32_t o = ((kb & 1) ? b ^ 64 : b) + 128 * (kb >> 1); w[kb][0] = lds32(o); w[kb][1] = lds32(o + 8); }
            mbar_wait(bar_row + 8 * rw);
            if (warp == 15) TSTAMP(2);
            const uint32_t a = fresh(rows) + g * 1152 + (g & 1) * 64 + t * 16;
#pragma unroll
            for (int kb = 0; kb < 18; kb++) {
                const uint4 x = lds128(((kb & 1) ? a ^ 64 : a) + 128 * (kb >> 1));
                mma_bf(c[kb % 3], x.x, x.y, x.z, x.w, w[kb][0], w[kb][1]);
            }
            const float sr = c[0][0] + c[1][0] + c[2][0] + __shfl_down_sync(0xffffffffu, c[0][2] + c[1][2] + c[2][2], 1);
            const float sg = c[0][1] + c[1][1] + c[2][1] + __shfl_down_sync(0xffffffffu, c[0][3] + c[1][3] + c[2][3], 1);
            const uint32_t rb = pack_bf16(0.f, sr);
            if (t == 2 * (g & 1)) {
                sts32(s_part + (8 * rw + g) * 4, (rb ^ (((int)rb >> 31) & 0x7fff0000u) ^ 0x80000000u) | (uint32_t)(2047 - r0 - 8 * rw - g));
                sts32(s_part + 192 + (8 * rw + g) * 4, __float_as_uint(sg));
            }
            __syncwarp();
            bar_sync(BAR_R, 32 * (nrw + 1));
            const uint32_t sk = fresh(s_part), kk = lds32(sk + (8 * rw + r8) * 4);
            int n = 0;
#pragma unroll
            for (int i = 0; i < 3; i++) { const uint4 v = lds128(sk + mi * 48 + 16 * i); n += (v.x > kk) + (v.y > kk) + (v.z > kk) + (v.w > kk); }
            n += __shfl_xor_sync(0xffffffffu, n, 8); n += __shfl_xor_sync(0xffffffffu, n, 16);
            if (n < 8) sts32(s_tok + 4 * n, kk);
            __syncwarp();
            bar_arrive(BAR_R2, 32 * (nrw + 1));
        }
    }
}

__device__ __forceinline__ void ffn_work(const Params& p, uint32_t sb, int warp, int lane, int f, unsigned epoch) {
    const int g = lane >> 2, t = lane & 3, mi = lane >> 3, r8 = lane & 7;
    const bool isx = f < NX;
    const uint32_t bar_x = sb + SF_MISC + FB_X, bar_free = sb + SF_MISC + FB_FREE, bar_w = sb + SF_MISC + FB_W, bar_d = sb + SF_MISC + FB_D, s_tok = sb + SF_MISC + FS_TOK;
    uint32_t fr[24][4];
    auto pin = [&] {
#pragma unroll
        for (int i = 0; i < 24; i += 8) asm volatile("" :: "r"(fr[i][0]), "r"(fr[i + 1][0]), "r"(fr[i + 2][0]), "r"(fr[i + 3][0]), "r"(fr[i + 4][0]), "r"(fr[i + 5][0]), "r"(fr[i + 6][0]), "r"(fr[i + 7][0]) : "memory");
    };
    {
        const int j = (unsigned)(warp - 4) < 6, w = warp - (j ? 4 : warp < 4 ? 0 : 6);
        float ag[2][4], au[2][4];
#pragma unroll
        for (int i = 0; i < 2; i++) { ag[i][0] = ag[i][1] = ag[i][2] = ag[i][3] = 0.f; au[i][0] = au[i][1] = au[i][2] = au[i][3] = 0.f; }
        const uint32_t wb = sb + (w >> 1) * 4096 + (r8 + 8 * (mi >> 1)) * 64 + (((2 * (w & 1) + (mi & 1)) ^ (r8 >> 1)) << 4);
        const uint32_t xb = sb + SF_XS + r8 * 1168 + mi * 16;
        auto load = [&](int i, int n, int place) {
            mbar_wait(bar_w + 8 * n);
            const uint32_t wk = fresh(wb) + place * 24576;
#pragma unroll
            for (int s = 0; s < 4; s++) { ldsm4t(fr[8 * i + s], wk + 1024 * s); ldsm4t(fr[8 * i + 4 + s], wk + 1024 * s + 12288); }
        };
        auto mul = [&](int i, uint32_t xk) {
            uint32_t x[2][4];
            ldsm4(x[0], xk); ldsm4(x[1], xk + 64);
#pragma unroll
            for (int s = 0; s < 4; s++) {
                const uint32_t (&a)[4] = fr[8 * i + s], (&b)[4] = fr[8 * i + 4 + s];
                mma_bf(ag[s & 1], a[0], a[1], a[2], a[3], x[s >> 1][2 * (s & 1)], x[s >> 1][2 * (s & 1) + 1]);
                mma_bf(au[s & 1], b[0], b[1], b[2], b[3], x[s >> 1][2 * (s & 1)], x[s >> 1][2 * (s & 1) + 1]);
            }
        };
#pragma unroll
        for (int i = 0; i < 3; i++) load(i, 3 * j + i, (i ? 5 : 3) * j + i);
        pin();
        bar_sync(BAR_G + j, 192);
        if (w == 0 && lane == 0) mbar_arrive(bar_free + 8 * j);
        if (warp < 4) {
            bar_sync(BAR_X, 160);
            const uint32_t rows = lds32(fresh(s_tok) + 8 * r8);
#pragma unroll 1
            for (int i = warp; i < 8; i += 4) {
                const int row = __shfl_sync(0xffffffffu, rows, i);
                if (elect()) bulk_g2s(sb + SF_XS + i * 1168, p.u + (size_t)row * DM, 1152, bar_x);
                __syncwarp();
            }
        }
        mbar_wait(bar_x);
        if (warp == 0) TSTAMP(8);
        {
            const uint32_t xk = fresh(xb) + 384 * j;
#pragma unroll
            for (int i = 0; i < 3; i++) { mul(i, (i ? fresh(xk) : xk) + 128 * i); if (i == 0) { asm volatile("" :: "f"(ag[0][0]), "f"(ag[1][0]), "f"(au[0][0]), "f"(au[1][0])); sts32(s_tok + 64, clock32()); } }
        }
#pragma unroll 1
        for (int n = 6 + j; n < 9; n += 2) { load(0, n, n - 6); mul(0, fresh(xb) + 128 * n); }
#pragma unroll
        for (int c = 0; c < 4; c++) { ag[0][c] += ag[1][c]; au[0][c] += au[1][c]; }
        if (j) {
            sts128(wb + 24576, __float_as_uint(ag[0][0]), __float_as_uint(ag[0][1]), __float_as_uint(ag[0][2]), __float_as_uint(ag[0][3]));
            sts128(wb + 25600, __float_as_uint(au[0][0]), __float_as_uint(au[0][1]), __float_as_uint(au[0][2]), __float_as_uint(au[0][3]));
        }
        bar_sync(BAR_GU, 384);
        if (!j) {
            const uint32_t sf = fresh(wb);
            const uint4 g1 = lds128(sf + 24576), u1 = lds128(sf + 25600);
            const uint32_t gs[4] = {g1.x, g1.y, g1.z, g1.w}, us[4] = {u1.x, u1.y, u1.z, u1.w};
            if (warp == 0) TSTAMP(9);
            float h[4];
#pragma unroll
            for (int c = 0; c < 4; c++) {
                const float gv = rbf(ag[0][c] + __uint_as_float(gs[c]));
                h[c] = rbf(gv * sigmoidf_(gv)) * rbf(au[0][c] + __uint_as_float(us[c]));
            }
            uint32_t h0, h1;
            asm("movmatrix.sync.aligned.m8n8.trans.b16 %0, %1;" : "=r"(h0) : "r"(pack_bf16(h[0], h[1])));
            asm("movmatrix.sync.aligned.m8n8.trans.b16 %0, %1;" : "=r"(h1) : "r"(pack_bf16(h[2], h[3])));
            if (h0 == 0) h0 = 0x8000u;
            asm volatile("{ .reg .b64 v; mov.b64 v, {%1, %2}; st.relaxed.gpu.global.b64 [%0], v; }" :: "l"(p.s->h + ((epoch & 1) * 288 + 6 * f + w) * 32 + lane), "r"(h0), "r"(h1) : "memory");
        }
        if (isx) {
            if (warp == 0) TSTAMP(10);
            const uint2* hsrc = p.s->h + ((epoch & 1) * 288 + 144 * (f & 1) + 12 * warp) * 32 + lane;
            uint2 hb[12];
            auto ldh = [&](int s) { asm volatile("ld.relaxed.gpu.global.v2.u32 {%0, %1}, [%2];" : "=r"(hb[s].x), "=r"(hb[s].y) : "l"(hsrc + 32 * s) : "memory"); };
#pragma unroll
            for (int s = 0; s < 12; s++) ldh(s);
#pragma unroll 1
            for (int it = 0;; it++) {
                bool again = false;
#pragma unroll
                for (int s = 0; s < 12; s += 2) if (__any_sync(0xffffffffu, min(hb[s].x, hb[s + 1].x) == 0)) { ldh(s); ldh(s + 1); again = true; }
                if (!again) break;
                if (it > (1 << 16)) give_up();
            }
            if (warp == 0) TSTAMP(11);
            mbar_wait(bar_d + 8 * warp);
            if (warp == 9) TSTAMP(14);
            float ad[2][2][4];
#pragma unroll
            for (int i = 0; i < 4; i++) { ad[i >> 1][i & 1][0] = ad[i >> 1][i & 1][1] = ad[i >> 1][i & 1][2] = ad[i >> 1][i & 1][3] = 0.f; }
            const uint32_t wd = fresh(sb) + SF_WD + warp * 12288 + (r8 + 8 * (mi >> 1)) * 64 + (((mi & 1) ^ (r8 >> 1)) << 4);
#pragma unroll
            for (int s = 0; s < 12; s++) {
                uint32_t a[4], b[4];
                ldsm4t(a, wd + 1024 * s); ldsm4t(b, (wd ^ 32) + 1024 * s);
                mma_bf(ad[0][s & 1], a[0], a[1], a[2], a[3], hb[s].x, hb[s].y);
                mma_bf(ad[1][s & 1], b[0], b[1], b[2], b[3], hb[s].x, hb[s].y);
            }
            const uint32_t rd = sb + SF_RED + warp * 1152 + (72 * t + g) * 4;
#pragma unroll
            for (int i = 0; i < 8; i++) sts32(rd + (i >> 2) * 64 + (i & 1) * 144 + ((i >> 1) & 1) * 32, __float_as_uint(ad[i >> 2][0][i & 3] + ad[i >> 2][1][i & 3]));
            bar_sync(BAR_RED, 416);
            if (warp < 4) {
                const int tid = 32 * warp + lane;
                const uint32_t rs = fresh(sb + SF_RED) + (tid >> 4) * 144 + (tid & 15) * 8;
                const uint2 tk = lds64(fresh(s_tok) + (tid >> 4) * 8);
                float x = 0.f, y = 0.f;
#pragma unroll
                for (int w = 0; w < 12; w++) { const uint2 v = lds64(rs + w * 1152); x += __uint_as_float(v.x); y += __uint_as_float(v.y); }
                asm volatile("red.relaxed.gpu.global.add.noftz.bf16x2 [%0], %1;" :: "l"(p.out + (size_t)tk.x * DM + 32 * (f >> 1) + 2 * (tid & 15)),
                             "r"(pack_bf16(x * __uint_as_float(tk.y), y * __uint_as_float(tk.y))) : "memory");
            }
            if (warp == 0) { TSTAMP(15); TFLUSH(); }
            asm volatile("exit;"); __builtin_unreachable();
        }
    }
}

__device__ __forceinline__ void fetch_k(const uint4* src, uint64_t (&v)[6], uint32_t a, uint32_t b) {
    asm volatile("{ .reg .pred p; setp.eq.u32 p, %7, %8; @p ld.relaxed.gpu.global.v2.u64 {%0,%1}, [%6]; @p ld.relaxed.gpu.global.v2.u64 {%2,%3}, [%6 + 512]; @p ld.relaxed.gpu.global.v2.u64 {%4,%5}, [%6 + 1024]; }"
                 : "+l"(v[0]), "+l"(v[1]), "+l"(v[2]), "+l"(v[3]), "+l"(v[4]), "+l"(v[5]) : "l"(src), "r"(a), "r"(b));
}
__device__ __forceinline__ uint32_t mini_conv(const Params& p, uint32_t sb, int warp, int lane, int f, unsigned epoch) {
    const int g = lane >> 2, t = lane & 3, mi = lane >> 3, r8 = lane & 7;
    const uint32_t fb = sb + SF_MISC, kt = sb + (warp >= 12 ? SM_KT - 12 * 2112 : f < NW ? SM_KW + 2 * 2112 : SM_KW) + warp * 2112;
    const bool ism = f >= NW;
    const int ch0 = mini_ch0(f);
    uint32_t seq = 128, key;
    uint64_t v[6] = {};
    const uint4* src = p.s->kp + lane;
    auto hi = [&](int i) { return (uint32_t)(v[i] >> 32); };
    if (f >= (warp < 4 ? NW : NX)) {
    {
        const uint32_t c = 36 + (warp & 3) + 2 * (warp & 12), y = (uint32_t)((warp < 8 ? 0xa026802400000000ull : 0x2a2e00280080a22cull) >> ((8 * warp) & 48)) & 0xffff;
        seq = ism ? 0x101 * c - 0x400 : y + (warp & 1) * ((y >> 5) & 0x101);
        src += (ch0 + (seq & 31)) * 96;
    }
    if (warp >= 10 && (warp & 2)) {
        const int q = (warp & 1) + (warp < 12 ? 2 : 0), n0 = ism ? 2 * (q & 1) : q;
        const uint32_t ab = sb - (ism ? 49152 * (q >> 1) : 0);
        mbar_wait(fb + FB_MU);
        if (warp == 15) TSTAMP(16);
        uint32_t a = fresh(ab + SM_RAW) + n0 * 4096 + (8 * mi + 4 * (r8 & 1) + (r8 >> 1)) * 32 + ((r8 & 1) << 4), d = ab + SM_UT + g * MU_STRIDE + (8 + 8 * n0 + t) * 16;
        uint32_t z = ab + SM_UT + (4 * n0 + (mi >> 1)) * MU_STRIDE + (mi & 1) * MU_HALF + r8 * 16;
#pragma unroll 1
        for (int n = 0; n <= ism; n++, a += 4096, d += 128, z += 4 * MU_STRIDE) {
            uint32_t x[8][4];
#pragma unroll
            for (int i = 0; i < 8; i++) ldsm4t(x[i], (i & 4 ? a ^ 16 : a) + 1024 * (i & 3));
            sts128(z, 0, 0, 0, 0); sts128(z + 2 * MU_STRIDE, 0, 0, 0, 0);
#pragma unroll
            for (int i = 0; i < 8; i++) sts128(d + (i & 1) * MU_HALF + (i & 2) * 32 + (i & 4) * 2 * MU_STRIDE, x[i][0], x[i][1], x[i][2], x[i][3]);
        }
        __syncwarp();
        if (lane == 0) mbar_arrive(fb + FB_MT);
    }
    if (seq & 32) {
        mbar_wait(fb + FB_KDONE);
        fetch_k(src, v, 0, 0);
        if ((warp >> 1) == (ism ? 6 : 2)) { fetch_gates(p, warp & 1, lane, epoch, sb + SM_G + (lane & 1) * MU_HALF); __syncwarp(); if (lane == 0) mbar_arrive(fb + FB_MG); }
        mbar_wait(fb + FB_KEYS); mbar_wait(fb + FB_MT);
        sts128(kt + t * 16, 0, 0, 0, 0);
        if (warp == TW) TSTAMP(17);
    }
    }
    const uint32_t lo = (mi & 1) * MU_HALF + (8 + r8) * 16 + (mi >> 1) * 128;
#pragma unroll 1
    do {
        const int c = seq & 31;
        if (seq & 32) {
#pragma unroll 1
        for (int it = 0; !__all_sync(0xffffffffu, ((hi(1) ^ k_tag(epoch)) | (hi(3) ^ k_tag(epoch)) | (hi(5) ^ k_tag(epoch)) | ((uint32_t)v[5] & p.zero)) < 65536); it++) {
            fetch_k(src, v, 0, 0);
            if (it > (1 << 20)) give_up();
        }
        if (warp == TW) TSTAMP(seq >> 8 ? 7 : 10);
        const uint32_t w[12] = {(uint32_t)v[0], hi(0), (uint32_t)v[1], (uint32_t)v[2], hi(2), (uint32_t)v[3], (uint32_t)v[4], hi(4), 0, 0, 0, 0};
        k_tables<false>(fresh(kt), fresh(lane), w);
        }
        __syncwarp();
        if (seq & 128) ffn_work(p, sb, warp, fresh(lane), f, epoch);
        if (!(seq & 32)) return 0;
        const uint32_t ab = sb - 49152 * (c >> 4), kb = fresh(kt) + (16 + g - 2 * t) * 4, ub = fresh(ab + SM_UT + (c & 15) * MU_STRIDE) + lo;
        const uint32_t yd = ab + SM_Y + (c & 15) * 1056 + (c & 8) * 8 + lane * 16;
        uint32_t kp = kb, u1 = ub;
        if (warp == TW && !(seq >> 8)) TSTAMP(13);
        seq >>= 8;
        src += ((int)(seq & 31) - c) * 96;
#pragma unroll
        for (int i = 0; i < 6; i++) v[i] = 0;
        key = 0;
        float acc[6][4];
#pragma unroll
        for (int i = 0; i < 6; i++) { acc[i][0] = acc[i][1] = acc[i][2] = acc[i][3] = 0.f; }
        uint32_t a[4][4], b[2][2][4];
        auto lda = [&](int j, int o) { const uint32_t x = kp + 64 * o + 512 * j; a[j][2] = o ? a[j][1] ^ p.zero : lds32((kp ^ p.zero) + 512 * j - 32); a[j][0] = lds32(x); a[j][1] = lds32(x + 32); a[j][3] = a[j][0] ^ p.zero; };
        auto ldb = [&](int s, int o) { ldsm4(b[s][0], u1 - 16 * o); ldsm4(b[s][1], u1 + 256 - 16 * o); };
        ldb(0, 0);
#pragma unroll
        for (int j = 0; j < 4; j++) lda(j, 0);
#pragma unroll
        for (int s = 0; s < 8; s++) {
            if (s == FPOS) {
                const uint32_t e = seq | (__float_as_uint(acc[0][0]) & p.zero);
                fetch_k(src, v, e & 32, 32);
                if (KEYPF) asm volatile("{ .reg .pred p; setp.eq.u32 p, %2, 0; @p ld.relaxed.gpu.global.u32 %0, [%1]; }" : "+r"(key) : "l"(&p.s->sel[(ch0 >> 5) * 64 + r8]), "r"(e));
            }
            if (s < 7) ldb(~s & 1, s + 1);
#pragma unroll
            for (int i = 0; i < 4; i++) {
                const int j = (i >> 1) + 2 * (i & 1);
#pragma unroll
                for (int mu = 3 - j; mu >= 0; mu--) mma_bf(acc[j + mu + (j & 2)], a[j][0], a[j][1], a[j][2], a[j][3], b[s & 1][mu >> 1][2 * (mu & 1)], b[s & 1][mu >> 1][2 * (mu & 1) + 1]);
                if (s < 7) lda(j, s + 1);
            }
        }
        if (warp == TW && !seq) TSTAMP(14);
        mbar_wait(fb + FB_MG);
#pragma unroll
        for (int e = 0; e < 4; e++) { acc[2][e] += acc[4][e]; acc[3][e] += acc[5][e]; }
        uint32_t ug[4][4];
#pragma unroll
        for (int i = 0; i < 2; i++) { ldsm4t(ug[i], ub + 256 * i); ldsm4t(ug[2 + i], fresh(sb + SM_G) + lo + 256 * i); }
#pragma unroll
        for (int i = 0; i < 2; i++) {
            const uint32_t (&u)[4] = ug[i], (&gg)[4] = ug[2 + i];
            sts128(yd + 512 * i, gmix(gg[0], acc[2 * i][0], acc[2 * i][1], u[0]), gmix(gg[1], acc[2 * i][2], acc[2 * i][3], u[1]),
                   gmix(gg[2], acc[2 * i + 1][0], acc[2 * i + 1][1], u[2]), gmix(gg[3], acc[2 * i + 1][2], acc[2 * i + 1][3], u[3]));
        }
        __syncwarp();
        if (warp == TW) TSTAMP(18 + (seq != 0));
    } while (seq);
    if (warp >= 12) TSTAMP(12 + warp);
    return key;
}
__device__ __forceinline__ void mini_out(const Params& p, const CUtensorMap* maps, uint32_t sb, int warp, int lane, int f, unsigned epoch, uint32_t key) {
    const int g = lane >> 2, t = lane & 3, mi = lane >> 3, r8 = lane & 7;
    const uint32_t fb = sb + SF_MISC;
    const bool ism = f >= NW;
    const int ch0 = mini_ch0(f);
    const int k = ism ? warp >> 3 : 0;
    uint32_t first = 1;
    if (lane == 0) asm volatile("atom.shared.exch.b32 %0, [%1], 1;" : "=r"(first) : "r"(fb + FS_BM + 64 + 4 * k) : "memory");
    if (!__all_sync(0xffffffffu, first)) {
        if (elect()) prefetch_map(maps + 4);
        const int row = key_row(wait_sel(p, ch0 >> 5, r8, key_tag(epoch), key));
        if (row < 512) asm volatile("red.shared.or.b32 [%0], %1;" :: "r"(fb + FS_BM + (row >> 5) * 4), "r"(1u << (row & 31)) : "memory");
    }
    const int m = warp & 7, dr = 128 * (g >> 2) + 32 * (t >> 1) + 16 * (g & 1) + 8 * ((g >> 1) & 1);
    const uint32_t y = SM_Y + ((r8 >> 1) & 1) * 8512 + (2 * mi + (r8 & 1)) * 1056 + (2 * m + (r8 >> 2)) * 16;
    const uint32_t so = (g >> 1) * 256 + (t >> 1) * 64 + (g & 1) * 32 + (t & 1) * 16;
    bar_sync(BAR_M - k, ism ? 256 : NTHR);
#pragma unroll 1
    for (int h = ism ? 0 : warp >> 3;; h++) {
        const int r0 = 256 * h + 64 * (m & 1) + (m >> 1), row = r0 + dr;
        const uint32_t bm = lds32(fresh(fb) + FS_BM + (row >> 5) * 4) >> (row & 31), ab = fresh(sb - 49152 * k + 512 * h), stg = ab + SM_UT + 2048 * m + 512 * h;
        uint32_t x[2][4];
        ldsm4t(x[0], ab + y); ldsm4t(x[1], ab + y + 256);
        if (warp == 0 && x[0][0] != 0x12345) TSTAMP(28);
        if (__any_sync(0xffffffffu, bm & 0x11u)) {
#pragma unroll
            for (int i = 0; i < 2; i++) store_or_add(p.out + (size_t)(row + 4 * i) * DM + ch0 + 16 * k + 8 * (t & 1), x[i], bm & (1u << (4 * i)));
        } else {
#pragma unroll
            for (int i = 0; i < 2; i++) sts128(stg + so + 128 * i, x[i][0], x[i][1], x[i][2], x[i][3]);
            asm volatile("fence.proxy.async.shared::cta;" ::: "memory");
            __syncwarp();
            if (elect()) store_rows(maps + 4, stg, ch0 + 16 * k, r0);
        }
        if (h >= ism) break;
    }
    if (elect()) { asm volatile("cp.async.bulk.commit_group;" ::: "memory"); asm volatile("cp.async.bulk.wait_group.read 0;" ::: "memory"); }
    if (warp == 8) TSTAMP(11);
    if (warp == 0) { TSTAMP(15); TFLUSH(); }
}

constexpr int SMEM_BYTES = 232448;
static_assert(SF_MISC + 1152 <= 232192, "layout");

struct Maps { CUtensorMap m[6]; };

__global__ void __cluster_dims__(2, 1, 1) __launch_bounds__(NTHR, 1)
fused_kernel(const Params p, const __grid_constant__ Maps maps) {
    extern __shared__ __align__(1024) uint8_t smem_raw[];
    uint32_t q[8];
    {
        const int b = blockIdx.x, x = threadIdx.x, rc = 4 * b + max(b - 84, 0) - 288 + (x >> 6);
        const int cv = (b - NCONV) >> 31, ca = 8 * b + ((x >> 5) & 3), cb = 2 * rc - (rc & 3) + 4;
        const uint32_t ch = (ca & cv) | (cb & ~cv), o = NST * ch + 2 * ((x & 31) + ((x >> (cv & 2)) & 32));
        const bool c = x < (b < 84 ? 256 : 320);
        q[6] = ldg16_if(c, p.logdt + ch);
        q[2] = ldg32_if(c, p.Bre + o); q[3] = ldg32_if(c, p.Bim + o); q[4] = ldg32_if(c, p.Cre + o); q[5] = ldg32_if(c, p.Cim + o); q[0] = ldg32_if(c, p.Are + o); q[1] = ldg32_if(c, p.Aim + o);
        q[7] = ldg16_if(c, p.Dskip + ch);
    }
    const unsigned epoch = ld_rlx32(&p.s->epoch[blockIdx.x * 16 + (threadIdx.x >> 5)]);
    const uint32_t sb = __shfl_sync(0xffffffffu, smem_u32(smem_raw), 0);
    const int warp = __shfl_sync(0xffffffffu, threadIdx.x >> 5, 0), bid = __shfl_sync(0xffffffffu, blockIdx.x, 0);
    const int lane = __shfl_sync(0xffffffffu, threadIdx.x & 31, threadIdx.x);
    const bool conv = bid < NCONV;
    const int f = bid - NCONV;
    uint32_t w[12];
    if (warp < (f < 12 ? 8 : 10)) {
        const int half = conv ? warp >> 2 : warp & 1, pr = conv ? warp & 3 : warp >> 1;
        const int rc = 4 * f + max(f - 12, 0) + pr;
        const uint32_t stage = sb + (conv ? SC_KG : SF_KG) + warp * KG_STAGE;
        uint4* const kp = p.s->kp + (conv ? 8 * bid + pr : 2 * rc - (rc & 3) + 4) * 96 + lane;
        kgen(q, sb, half, stage, stage + (conv ? 4 : 1) * KG_STAGE, 1 + pr, lane, p.zero, w, [&] {
            sts128z_if(conv && lane < 20, sb + SC_KT + warp * KT_BYTES + lane * 16 + (lane < 4 ? 0 : lane < 14 ? 2048 : 2288));
            stg128(kp + 64 * half, 0, 0, 0, 0); stg128z_if(!half, kp + 32);
            stg128z_if((unsigned)f < NW && warp < 6, (uint4*)(p.s->h + ((lane >> 4) * 288 + 6 * f + warp) * 32) + (lane & 15));
            if (conv) asm volatile("barrier.cluster.arrive.relaxed.aligned;" ::: "memory");
        });
        if (conv) { conv_main(p, sb, warp, lane, bid, epoch, w); return; }
        {
            if (!half) publish_k(kp, w, epoch, true);
            if (warp == 0) TSTAMP(22);
            if (warp == 2) TSTAMP(23);
            bar_sync(0, NTHR);
            if (warp == 0 && lane == 0) mbar_arrive(sb + SF_MISC + FB_KDONE);
        }
    } else if (conv) {
        conv_aux(p, maps.m, sb, warp - 8, lane, bid, epoch);
        return;
    } else {
        ffn_front(p, maps.m, sb, warp, lane, f, epoch);
    }
    converged();
    next_epoch(p, epoch);
    if (warp >= 12 && f < NX) return;
    mini_out(p, maps.m, sb, warp, lane, f, epoch, mini_conv(p, sb, warp, __shfl_sync(0xffffffffu, lane, lane), f, epoch));
}

typedef CUresult (*EncodeFn)(CUtensorMap*, CUtensorMapDataType, cuuint32_t, void*, const cuuint64_t*, const cuuint64_t*, const cuuint32_t*, const cuuint32_t*,
                             CUtensorMapInterleave, CUtensorMapSwizzle, CUtensorMapL2promotion, CUtensorMapFloatOOBfill);

void make_map(EncodeFn fn, CUtensorMap* m, const void* base, int rank, const cuuint64_t* dims, const cuuint64_t* strides, const cuuint32_t* box, CUtensorMapSwizzle sw) {
    const cuuint32_t es[5] = {1, 1, 1, 1, 1};
    fn(m, CU_TENSOR_MAP_DATA_TYPE_BFLOAT16, rank, (void*)base, dims, strides, box, es, CU_TENSOR_MAP_INTERLEAVE_NONE, sw,
       CU_TENSOR_MAP_L2_PROMOTION_NONE, CU_TENSOR_MAP_FLOAT_OOB_FILL_NONE);
}

}

extern "C" void kernel_launch(void* const* d_in, const int* in_sizes, int n_in, void* d_out, int out_size) {
    (void)in_sizes; (void)n_in; (void)out_size;
    static EncodeFn fn = nullptr;
    static void* scratch = nullptr;
    if (!fn) {
        void* ptr = nullptr; cudaDriverEntryPointQueryResult qr;
        cudaGetDriverEntryPoint("cuTensorMapEncodeTiled", &ptr, cudaEnableDefault, &qr);
        fn = (EncodeFn)ptr;
        cudaGetSymbolAddress(&scratch, g_scratch);
        cudaFuncSetAttribute(fused_kernel, cudaFuncAttributeMaxDynamicSharedMemorySize, SMEM_BYTES);
    }
    typedef const __nv_bfloat16* bp;
    Params p;
    p.u = (bp)d_in[0]; p.Are = (bp)d_in[1]; p.Aim = (bp)d_in[2]; p.Bre = (bp)d_in[3]; p.Bim = (bp)d_in[4]; p.Cre = (bp)d_in[5]; p.Cim = (bp)d_in[6];
    p.logdt = (bp)d_in[7]; p.Dskip = (bp)d_in[8]; p.wr = (bp)d_in[10]; p.gatew = (bp)d_in[14];
    p.out = (__nv_bfloat16*)d_out; p.s = (Scratch*)scratch; p.zero = 0;
    Maps maps;
    {
        const cuuint64_t dims[4] = {DM, 4, 16, 32}, strides[3] = {16 * DM * 2, DM * 2, 64 * DM * 2};
        const cuuint32_t box[4] = {16, 4, 16, 2};
        make_map(fn, &maps.m[0], d_in[0], 4, dims, strides, box, CU_TENSOR_MAP_SWIZZLE_32B);
        const cuuint32_t box2[4] = {16, 4, 16, 8};
        make_map(fn, &maps.m[5], d_in[0], 4, dims, strides, box2, CU_TENSOR_MAP_SWIZZLE_32B);
    }
    for (int i = 0; i < 2; i++) {
        const cuuint64_t dims[3] = {32, DM, FF / 32}, strides[2] = {FF * 2, 64};
        const cuuint32_t box[3] = {32, 64, 3};
        make_map(fn, &maps.m[1 + i], d_in[11 + i], 3, dims, strides, box, CU_TENSOR_MAP_SWIZZLE_64B);
    }
    {
        const cuuint64_t dims[2] = {DM, FF}, strides[1] = {DM * 2};
        const cuuint32_t box[2] = {32, 192};
        make_map(fn, &maps.m[3], d_in[13], 2, dims, strides, box, CU_TENSOR_MAP_SWIZZLE_64B);
    }
    {
        const cuuint64_t dims[5] = {DM, 4, 4, 2, L_SEQ}, strides[4] = {16 * DM * 2, 4 * DM * 2, 128 * DM * 2, DM * 2};
        const cuuint32_t box[5] = {16, 4, 4, 2, 1};
        make_map(fn, &maps.m[4], d_out, 5, dims, strides, box, CU_TENSOR_MAP_SWIZZLE_NONE);
    }
    fused_kernel<<<NCTA, NTHR, SMEM_BYTES>>>(p, maps);
}
```

```cpp
#include <cuda_runtime.h>
#include <cuda_bf16.h>
#include <cuda_fp16.h>
#include <cuda.h>
#include <stdint.h>
#include <type_traits>

#define RESUME 300
#define PUBIT 1
#define FPOS 2
#define PUBY 0
#define KEYPF 1
#define TW 12
#define MDELAY 2000
#define UDELAY 0
#define RDELAY 900
#define WDELAY 2000
#define WGAP 290
#define NPRE 7
#define DGAP 260

namespace {

constexpr int DM = 576, NST = 128, FF = 4608, L_SEQ = 2048;
constexpr int NCONV = 72, NX = 36, NW = 48, NCTA = 132, NTHR = 512;

struct __align__(128) Scratch {
    unsigned epoch[NCTA * 16];
    uint4 keys[16 * 128];
    uint32_t sel[18 * 64];
    uint16_t gate[L_SEQ];
    uint2 h[2 * 288 * 32];
    uint4 kp[DM * 96];
};
__device__ Scratch g_scratch;
#define TFLUSH()
#define TSTAMP(i)

struct Params {
    const __nv_bfloat16 *Are, *Aim, *Bre, *Bim, *Cre, *Cim, *logdt, *Dskip, *u, *wr, *gatew;
    __nv_bfloat16* out;
    Scratch* s;
    uint32_t zero;
};

__device__ __forceinline__ void give_up() { asm volatile("trap; exit;"); __builtin_unreachable(); }
__device__ __forceinline__ void converged() { __syncwarp(); asm volatile("{ .reg .b32 t; mov.b32 t, 0; movmatrix.sync.aligned.m8n8.trans.b16 t, t; }" ::: "memory"); }
__device__ __forceinline__ bool elect() { uint32_t r; asm volatile("{ .reg .pred p; elect.sync _|p, 0xffffffff; selp.u32 %0, 1, 0, p; }" : "=r"(r)); return r; }
__device__ __forceinline__ uint32_t smem_u32(const void* p) { return (uint32_t)__cvta_generic_to_shared(p); }
__device__ __forceinline__ uint32_t pack_bf16(float lo, float hi) { uint32_t r; asm("cvt.rn.bf16x2.f32 %0, %1, %2;" : "=r"(r) : "f"(hi), "f"(lo)); return r; }
__device__ __forceinline__ uint32_t pack_f16(float lo, float hi) { uint32_t r; asm("cvt.rn.f16x2.f32 %0, %1, %2;" : "=r"(r) : "f"(hi), "f"(lo)); return r; }
__device__ __forceinline__ float bf_lo(uint32_t w) { return __uint_as_float(w << 16); }
__device__ __forceinline__ float bf_hi(uint32_t w) { return __uint_as_float(w & 0xffff0000u); }
__device__ __forceinline__ float rbf(float x) { return bf_lo(pack_bf16(x, 0.f)); }
__device__ __forceinline__ uint32_t badd2(uint32_t a, uint32_t b) { uint32_t r; asm("add.rn.bf16x2 %0, %1, %2;" : "=r"(r) : "r"(a), "r"(b)); return r; }
__device__ __forceinline__ uint32_t bsub2(uint32_t a, uint32_t b) { uint32_t r; asm("sub.rn.bf16x2 %0, %1, %2;" : "=r"(r) : "r"(a), "r"(b)); return r; }
__device__ __forceinline__ uint32_t gmix(uint32_t ng, float ny0, float ny1, uint32_t u) {
    uint32_t r; asm("{ .reg .b32 t; fma.rn.bf16x2 t, %1, %3, %3; fma.rn.bf16x2 %0, %1, %2, t; }" : "=r"(r) : "r"(ng), "r"(pack_bf16(ny0, ny1)), "r"(u)); return r;
}
__device__ __forceinline__ void mma_bf(float (&c)[4], uint32_t a0, uint32_t a1, uint32_t a2, uint32_t a3, uint32_t b0, uint32_t b1) {
    asm("mma.sync.aligned.m16n8k16.row.col.f32.bf16.bf16.f32 {%0,%1,%2,%3}, {%4,%5,%6,%7}, {%8,%9}, {%0,%1,%2,%3};"
        : "+f"(c[0]), "+f"(c[1]), "+f"(c[2]), "+f"(c[3]) : "r"(a0), "r"(a1), "r"(a2), "r"(a3), "r"(b0), "r"(b1));
}
__device__ __forceinline__ void mma_bf8(float (&c)[4], uint32_t a0, uint32_t a1, uint32_t b0) {
    asm("mma.sync.aligned.m16n8k8.row.col.f32.bf16.bf16.f32 {%0,%1,%2,%3}, {%4,%5}, {%6}, {%0,%1,%2,%3};"
        : "+f"(c[0]), "+f"(c[1]), "+f"(c[2]), "+f"(c[3]) : "r"(a0), "r"(a1), "r"(b0));
}
__device__ __forceinline__ void mma_h(float (&c)[4], uint32_t a0, uint32_t a1, uint32_t a2, uint32_t a3, uint32_t b0, uint32_t b1) {
    asm("mma.sync.aligned.m16n8k16.row.col.f32.f16.f16.f32 {%0,%1,%2,%3}, {%4,%5,%6,%7}, {%8,%9}, {%0,%1,%2,%3};"
        : "+f"(c[0]), "+f"(c[1]), "+f"(c[2]), "+f"(c[3]) : "r"(a0), "r"(a1), "r"(a2), "r"(a3), "r"(b0), "r"(b1));
}
__device__ __forceinline__ uint32_t fresh(uint32_t a) { asm volatile("" : "+r"(a) :: "memory"); return a; }
__device__ __forceinline__ uint32_t lds16(uint32_t a) { uint32_t v; asm("ld.shared.u16 %0, [%1];" : "=r"(v) : "r"(a)); return v; }
__device__ __forceinline__ uint32_t lds32(uint32_t a) { uint32_t v; asm("ld.shared.u32 %0, [%1];" : "=r"(v) : "r"(a)); return v; }
__device__ __forceinline__ uint2 lds64(uint32_t a) { uint2 v; asm("ld.shared.v2.u32 {%0,%1}, [%2];" : "=r"(v.x), "=r"(v.y) : "r"(a)); return v; }
__device__ __forceinline__ uint4 lds128(uint32_t a) { uint4 v; asm("ld.shared.v4.u32 {%0,%1,%2,%3}, [%4];" : "=r"(v.x), "=r"(v.y), "=r"(v.z), "=r"(v.w) : "r"(a)); return v; }
__device__ __forceinline__ uint4 lds128v(uint32_t a) { uint4 v; asm volatile("ld.shared.v4.u32 {%0,%1,%2,%3}, [%4];" : "=r"(v.x), "=r"(v.y), "=r"(v.z), "=r"(v.w) : "r"(a) : "memory"); return v; }
__device__ __forceinline__ void ldsm4(uint32_t (&r)[4], uint32_t a) {
    asm("ldmatrix.sync.aligned.m8n8.x4.shared.b16 {%0,%1,%2,%3}, [%4];" : "=r"(r[0]), "=r"(r[1]), "=r"(r[2]), "=r"(r[3]) : "r"(a));
}
__device__ __forceinline__ void ldsm4t(uint32_t (&r)[4], uint32_t a) {
    asm("ldmatrix.sync.aligned.m8n8.x4.trans.shared.b16 {%0,%1,%2,%3}, [%4];" : "=r"(r[0]), "=r"(r[1]), "=r"(r[2]), "=r"(r[3]) : "r"(a));
}
__device__ __forceinline__ void sts16(uint32_t a, uint32_t v) { asm volatile("st.shared.u16 [%0], %1;" :: "r"(a), "h"((unsigned short)v) : "memory"); }
__device__ __forceinline__ void sts32(uint32_t a, uint32_t v) { asm volatile("st.shared.u32 [%0], %1;" :: "r"(a), "r"(v) : "memory"); }
__device__ __forceinline__ void sts64(uint32_t a, uint32_t x, uint32_t y) { asm volatile("st.shared.v2.u32 [%0], {%1,%2};" :: "r"(a), "r"(x), "r"(y) : "memory"); }
__device__ __forceinline__ void sts128(uint32_t a, uint32_t x, uint32_t y, uint32_t z, uint32_t w) {
    asm volatile("st.shared.v4.u32 [%0], {%1,%2,%3,%4};" :: "r"(a), "r"(x), "r"(y), "r"(z), "r"(w) : "memory");
}
__device__ __forceinline__ void st_async128(uint32_t a, uint32_t x, uint32_t y, uint32_t z, uint32_t w, uint32_t bar) {
    asm volatile("st.async.weak.shared::cluster.mbarrier::complete_tx::bytes.v4.b32 [%0], {%1,%2,%3,%4}, [%5];" :: "r"(a), "r"(x), "r"(y), "r"(z), "r"(w), "r"(bar) : "memory");
}
__device__ __forceinline__ void mbar_init(uint32_t b, uint32_t cnt) { asm volatile("mbarrier.init.shared::cta.b64 [%0], %1;" :: "r"(b), "r"(cnt) : "memory"); }
__device__ __forceinline__ void mbar_fence() { asm volatile("fence.mbarrier_init.release.cluster;" ::: "memory"); }
__device__ __forceinline__ void mbar_expect(uint32_t b, uint32_t bytes) { asm volatile("mbarrier.arrive.expect_tx.shared::cta.b64 _, [%0], %1;" :: "r"(b), "r"(bytes) : "memory"); }
__device__ __forceinline__ void mbar_arrive(uint32_t b) { asm volatile("mbarrier.arrive.shared::cta.b64 _, [%0];" :: "r"(b) : "memory"); }
#define CHINT ""
#define HINT ""
__device__ __forceinline__ void mbar_wait(uint32_t b, uint32_t parity = 0) {
    asm volatile("{ .reg .pred p; .reg .u32 n; mov.u32 n, 0;\n"
                 "LW: mbarrier.try_wait.parity.shared::cta.b64 p, [%0], %1" HINT "; @p bra LD; add.u32 n, n, 1; setp.lt.u32 p, n, 65536; @p bra LW; trap;\n"
                 "LD: }" :: "r"(b), "r"(parity) : "memory");
}
__device__ __forceinline__ void mbar_wait_cluster(uint32_t b) {
    asm volatile("{ .reg .pred p; .reg .u32 n; mov.u32 n, 0;\n"
                 "LW: mbarrier.try_wait.parity.acquire.cluster.shared::cta.b64 p, [%0], 0" CHINT "; @p bra LD; add.u32 n, n, 1; setp.lt.u32 p, n, 65536; @p bra LW; trap;\n"
                 "LD: }" :: "r"(b) : "memory");
}
__device__ __forceinline__ void tma2d(uint32_t dst, const CUtensorMap* m, int c0, int c1, uint32_t bar) {
    asm volatile("cp.async.bulk.tensor.2d.shared::cluster.global.mbarrier::complete_tx::bytes [%0], [%1, {%3, %4}], [%2];"
                 :: "r"(dst), "l"(m), "r"(bar), "r"(c0), "r"(c1) : "memory");
}
__device__ __forceinline__ void tma3d(uint32_t dst, const CUtensorMap* m, int c0, int c1, int c2, uint32_t bar) {
    asm volatile("cp.async.bulk.tensor.3d.shared::cluster.global.mbarrier::complete_tx::bytes [%0], [%1, {%3, %4, %5}], [%2];"
                 :: "r"(dst), "l"(m), "r"(bar), "r"(c0), "r"(c1), "r"(c2) : "memory");
}
__device__ __forceinline__ void tma4d(uint32_t dst, const CUtensorMap* m, int c0, int c1, int c2, int c3, uint32_t bar) {
    asm volatile("cp.async.bulk.tensor.4d.shared::cluster.global.mbarrier::complete_tx::bytes [%0], [%1, {%3, %4, %5, %6}], [%2];"
                 :: "r"(dst), "l"(m), "r"(bar), "r"(c0), "r"(c1), "r"(c2), "r"(c3) : "memory");
}
__device__ __forceinline__ void bulk_g2s(uint32_t dst, const void* src, uint32_t bytes, uint32_t bar) {
    asm volatile("cp.async.bulk.shared::cluster.global.mbarrier::complete_tx::bytes [%0], [%1], %2, [%3];"
                 :: "r"(dst), "l"(src), "r"(bytes), "r"(bar) : "memory");
}
__device__ __forceinline__ uint32_t mapa(uint32_t a, uint32_t rank) { uint32_t r; asm("mapa.shared::cluster.u32 %0, %1, %2;" : "=r"(r) : "r"(a), "r"(rank)); return r; }
__device__ __forceinline__ void prefetch_map(const CUtensorMap* m) { asm volatile("prefetch.tensormap [%0];" :: "l"(m) : "memory"); }
__device__ __forceinline__ void bar_sync(int id, int n) { asm volatile("bar.sync %0, %1;" :: "r"(id), "r"(n) : "memory"); }
__device__ __forceinline__ void bar_arrive(int id, int n) { asm volatile("bar.arrive %0, %1;" :: "r"(id), "r"(n) : "memory"); }
__device__ __forceinline__ uint32_t ldg16_if(bool c, const void* p) { uint32_t v; asm volatile("{ .reg .pred p; setp.ne.u32 p, %2, 0; @p ld.global.nc.u16 %0, [%1]; }" : "=r"(v) : "l"(p), "r"((uint32_t)c)); return v; }
__device__ __forceinline__ uint32_t ldg32_if(bool c, const void* p) { uint32_t v; asm volatile("{ .reg .pred p; setp.ne.u32 p, %2, 0; @p ld.global.nc.u32 %0, [%1]; }" : "=r"(v) : "l"(p), "r"((uint32_t)c)); return v; }
__device__ __forceinline__ uint32_t ld_rlx32(const void* p) { uint32_t v; asm volatile("ld.relaxed.gpu.global.u32 %0, [%1];" : "=r"(v) : "l"(p) : "memory"); return v; }
__device__ __forceinline__ uint4 ld_rlx128(const void* p) {
    uint4 v; asm volatile("ld.relaxed.gpu.global.v4.u32 {%0,%1,%2,%3}, [%4];" : "=r"(v.x), "=r"(v.y), "=r"(v.z), "=r"(v.w) : "l"(p) : "memory"); return v;
}
__device__ __forceinline__ void st_rlx32(void* p, uint32_t v) { asm volatile("st.relaxed.gpu.global.u32 [%0], %1;" :: "l"(p), "r"(v) : "memory"); }
__device__ __forceinline__ void stg128(void* p, uint32_t x, uint32_t y, uint32_t z, uint32_t w) {
    asm volatile("st.global.v4.u32 [%0], {%1,%2,%3,%4};" :: "l"(p), "r"(x), "r"(y), "r"(z), "r"(w) : "memory");
}
__device__ __forceinline__ void next_epoch(const Params& p, unsigned e) { if ((threadIdx.x & 31) == 0) p.s->epoch[blockIdx.x * 16 + (threadIdx.x >> 5)] = e + 1; }
__device__ __forceinline__ void sts128z_if(bool c, uint32_t a) { asm volatile("{ .reg .pred p; setp.ne.u32 p, %1, 0; @p st.shared.v4.u32 [%0], {%2,%2,%2,%2}; }" :: "r"(a), "r"((uint32_t)c), "r"(0) : "memory"); }
__device__ __forceinline__ void stg128z_if(bool c, void* a) { asm volatile("{ .reg .pred p; setp.ne.u32 p, %1, 0; @p st.global.v4.u32 [%0], {%2,%2,%2,%2}; }" :: "l"(a), "r"((uint32_t)c), "r"(0) : "memory"); }
__device__ __forceinline__ unsigned clock32() { unsigned c; asm volatile("mov.u32 %0, %clock;" : "=r"(c) :: "memory"); return c; }
__device__ __forceinline__ void until(unsigned t0, int c) { while ((int)(clock32() - t0) < c) { } }
__device__ __forceinline__ float sigmoidf_(float x) { return __fdividef(1.0f, 1.0f + __expf(-x)); }
__device__ __forceinline__ uint32_t key_tag(unsigned epoch) { return ((epoch & 15u) | 16u) << 11; }
__device__ __forceinline__ int key_row(uint32_t key) { return 2047 - (int)(key & 2047u); }
__device__ __forceinline__ uint32_t wait_sel(const Params& p, int s32, int r8, uint32_t tag, uint32_t k = 0) {
#pragma unroll 1
    for (int it = 0; !__all_sync(0xffffffffu, (k & 0xf800u) == tag); it++) {
        k = ld_rlx32(&p.s->sel[s32 * 64 + r8]);
        if (it > (1 << 20)) give_up();
    }
    return k;
}

struct cplx { float re, im; };
__device__ __forceinline__ cplx csq(cplx a) { cplx r; r.re = a.re * a.re - a.im * a.im; r.im = (a.re * a.im) * 2.f; return r; }
__device__ __forceinline__ cplx cexpk(float ar, float ai, float k) {
    float mag, s, c;
    asm("ex2.approx.ftz.f32 %0, %1;" : "=f"(mag) : "f"(ar * (k * 1.4426950408889634f)));
    const float r = ai * k;
    asm("sin.approx.ftz.f32 %0, %1;" : "=f"(s) : "f"(r));
    asm("cos.approx.ftz.f32 %0, %1;" : "=f"(c) : "f"(r));
    cplx o; o.re = mag * c; o.im = mag * s; return o;
}
struct h2c { uint32_t re, im; };
__device__ __forceinline__ h2c cmul_cd(h2c v, __half2 c, __half2 d) {
    const __half2 r = *(const __half2*)&v.re, i = *(const __half2*)&v.im;
    const __half2 x = __hfma2(__hneg2(i), d, __hmul2(r, c)), y = __hfma2(i, c, __hmul2(r, d));
    h2c o; o.re = *(const uint32_t*)&x; o.im = *(const uint32_t*)&y; return o;
}
__device__ __forceinline__ h2c cmul_s(h2c v, uint32_t s) { const __half2 h = *(const __half2*)&s; return cmul_cd(v, __low2half2(h), __high2half2(h)); }
__device__ __forceinline__ h2c cmul_sc(h2c v, uint32_t s) {
    const __half2 h = *(const __half2*)&s, c = __low2half2(h), d = __high2half2(h), r = *(const __half2*)&v.re, i = *(const __half2*)&v.im;
    const __half2 x = __hfma2(i, d, __hmul2(r, c)), y = __hfma2(__hneg2(r), d, __hmul2(i, c));
    h2c o; o.re = *(const uint32_t*)&x; o.im = *(const uint32_t*)&y; return o;
}
__device__ __forceinline__ h2c cmul_vc(h2c v, uint32_t s) {
    const __half2 h = *(const __half2*)&s, c = __low2half2(h), d = __high2half2(h), r = *(const __half2*)&v.re, i = *(const __half2*)&v.im;
    const __half2 x = __hfma2(i, d, __hmul2(r, c)), y = __hfma2(__hneg2(i), c, __hmul2(r, d));
    h2c o; o.re = *(const uint32_t*)&x; o.im = *(const uint32_t*)&y; return o;
}

constexpr int UT_HALF = 2240, UT_STRIDE = 4448;
constexpr int KT_T = 542, KT_C = 552, KT_D = 645, KT_BYTES = 720 * 4;
constexpr int VC_OFF = 80, VE_BASE = 1616;
constexpr int V_STRIDE = (1616 + 1024) * 4 + 80;
constexpr int KG_STAGE = 5248;
constexpr int Y_CS = 2080, Y_RS = 8 * Y_CS + 64;

constexpr int SC_RT = 0;
constexpr int SC_UT = 33408;
constexpr int SC_ST = SC_UT + 8 * UT_STRIDE;
constexpr int SC_KT = SC_ST + 8 * UT_STRIDE;
constexpr int SC_GT = SC_KT + 8 * KT_BYTES;
constexpr int SC_V = SC_GT + UT_STRIDE;
constexpr int SC_KG = SC_V + 4 * V_STRIDE;
constexpr int SC_MISC = SC_V + 8 * V_STRIDE;
static_assert(V_STRIDE % 128 == 16 && 8 * KG_STAGE <= 4 * V_STRIDE && 2 * Y_RS <= SC_UT && SC_UT % 128 == 0 && SC_ST % 128 == 0, "layout");
static_assert(SC_MISC % 16 == 0 && SC_MISC + 512 <= 232192, "layout");

__device__ __forceinline__ void window_task(uint32_t src, uint32_t d0, uint32_t d1, bool withE) {
    float S[35];
    {
        uint32_t w[20];
#pragma unroll
        for (int i = 0; i < 5; i++) {
            const uint4 v = lds128(src + ((i & 1) ? 0 : UT_HALF) + ((i + 1) >> 1) * 16);
            w[4 * i] = v.x; w[4 * i + 1] = v.y; w[4 * i + 2] = v.z; w[4 * i + 3] = v.w;
        }
        float s = 0.f; S[2] = 0.f;
#pragma unroll
        for (int i = 3; i < 26; i++) { s += (i & 1) ? bf_hi(w[i >> 1]) : bf_lo(w[i >> 1]); S[i] = s; }
#pragma unroll
        for (int i = 0; i < 8; i += 2)
            sts128((i & 4 ? d1 : d0) + (VC_OFF - 16) * 4 + 8 * (i & 2), pack_bf16(S[10 + i] - S[5 + i], S[5 + i] - S[2 + i]), pack_bf16(S[18 + i] - S[13 + i], S[13 + i] - S[10 + i]),
                   pack_bf16(S[11 + i] - S[6 + i], S[6 + i] - S[3 + i]), pack_bf16(S[19 + i] - S[14 + i], S[14 + i] - S[11 + i]));
        if (withE) {
#pragma unroll
            for (int i = 26; i < 35; i++) { s += (i & 1) ? bf_hi(w[i >> 1]) : bf_lo(w[i >> 1]); S[i] = s; }
#pragma unroll
            for (int i = 0; i < 8; i += 2)
                sts128((i & 4 ? d1 : d0) + VE_BASE * 4 + 8 * (i & 2), pack_bf16(S[19 + i] - S[12 + i], S[12 + i] - S[3 + i]), pack_bf16(S[27 + i] - S[20 + i], S[20 + i] - S[11 + i]),
                       pack_bf16(S[20 + i] - S[13 + i], S[13 + i] - S[4 + i]), pack_bf16(S[28 + i] - S[21 + i], S[21 + i] - S[12 + i]));
        }
    }
}

template <class F>
__device__ __forceinline__ void kgen(const uint32_t (&q)[8], uint32_t sb, int half, uint32_t stage, uint32_t pstage, int barid, int lane, uint32_t zero, uint32_t (&w)[12], F shadow) {
    const int t = lane & 3, mi = lane >> 3, r8 = lane & 7;
    {
        const uint32_t pAr = q[0], pAi = q[1], pBr = q[2], pBi = q[3], pCr = q[4], pCi = q[5], pDt = q[6], pD = q[7];
        const uint32_t wb = fresh(stage + lane * 16), za = fresh(stage + 5120 + ((lane >> 1) & 3) * 16 + mi * 4 + (lane & 1) * 2), zr = fresh(stage + 5120 + t * 16);
        const uint32_t oA = fresh(stage + (mi & 1) * 1024 + (mi >> 1) * 512 + r8 * 16), oB = fresh(stage + 2048 + mi * 512 + r8 * 16), oC = fresh(stage + 4096 + (mi & 1) * 512 + (mi >> 1) * 128 + r8 * 16);
        float acc[6][4];
#pragma unroll
        for (int a = 0; a < 6; a++) { acc[a][0] = acc[a][1] = acc[a][2] = acc[a][3] = 0.f; asm volatile("" : "+f"(acc[a][0]), "+f"(acc[a][1]), "+f"(acc[a][2]), "+f"(acc[a][3])); }
        shadow();
        sts32(zr, clock32());
        const float dt = rbf(__expf(bf_lo(pDt)));
        float ar = dt * bf_lo(pAr), ai = dt * bf_lo(pAi), ar1 = dt * bf_hi(pAr), ai1 = dt * bf_hi(pAi);
        float wr, wi, wr1, wi1;
        { const float br = dt * bf_lo(pBr), bi = dt * bf_lo(pBi), cr = bf_lo(pCr), ci = bf_lo(pCi); wr = cr * br - ci * bi; wi = cr * bi + ci * br; }
        { const float br = dt * bf_hi(pBr), bi = dt * bf_hi(pBi), cr = bf_hi(pCr), ci = bf_hi(pCi); wr1 = cr * br - ci * bi; wi1 = cr * bi + ci * br; }
        const uint32_t ex = max(__reduce_max_sync(0xffffffffu, __float_as_uint(fmaxf(fmaxf(fabsf(wr), fabsf(wi)), fmaxf(fabsf(wr1), fabsf(wi1))))) >> 23, 14u);
        const float scl = __uint_as_float((267u - ex) << 23);
        uint32_t W = pack_f16(wr * scl, wi * -scl);
        const uint32_t W1 = pack_f16(wr1 * scl, wi1 * -scl);
        if (threadIdx.x < 32) TSTAMP(20);

#pragma unroll 1
        for (int r = 0; r < 2; r++) {
            const cplx z1 = cexpk(ar, ai, 1.f), z64 = cexpk(ar, ai, 64.f);
            const cplx z2 = csq(z1), z4 = csq(z2), z8 = csq(z4), z16 = csq(z8), z32 = csq(z16);
            const cplx z128 = csq(z64), z256 = csq(z128), z512 = csq(z256);
            auto put = [&](int grp, h2c a, h2c b, h2c c, h2c d) { sts128(wb + grp * 1024, a.re, b.re, c.re, d.re); sts128(wb + grp * 1024 + 512, a.im, b.im, c.im, d.im); };
            {
                const uint32_t s4 = pack_f16(z4.re, z4.im), s256 = pack_f16(z256.re, z256.im), s512 = pack_f16(z512.re, z512.im);
                auto mix = [](h2c a, h2c b, uint32_t sel) { return h2c{__byte_perm(a.re, b.re, sel), __byte_perm(a.im, b.im, sel)}; };
                const h2c c10 = cmul_vc(h2c{pack_f16(z1.re, 1.f), pack_f16(z1.im, 0.f)}, W), c32 = cmul_sc(c10, pack_f16(z2.re, z2.im)), c54 = cmul_sc(c10, s4);
                put(2, c10, c32, c54, cmul_sc(c32, s4));
                const h2c d20 = cmul_sc(mix(c32, c10, 0x7632), s256), e04 = cmul_sc(mix(c10, c54, 0x7632), s512), f04 = cmul_sc(e04, s256);
                put(3, d20, cmul_sc(d20, s4), e04, f04);
                const h2c ef = mix(e04, f04, 0x5410), gh = cmul_sc(ef, s512), g8 = cmul_sc(gh, pack_f16(z8.re, z8.im));
                put(4, g8, cmul_sc(g8, s512), gh, ef);
            }
            {
                const uint32_t s32 = pack_f16(z32.re, z32.im), s64 = pack_f16(z64.re, z64.im), s128 = pack_f16(z128.re, z128.im);
                const h2c p0 = {pack_f16(1.f, z8.re), pack_f16(0.f, z8.im)}, p1 = cmul_s(p0, pack_f16(z16.re, z16.im)), p2 = cmul_s(p0, s32), p3 = cmul_s(p1, s32);
                put(0, p0, p1, p2, p3);
                put(1, cmul_s(p0, s64), cmul_s(p1, s64), cmul_s(p2, s64), cmul_s(p3, s64));
                sts16(za, s128); sts16(za + 64, s128 >> 16);
            }
            __syncwarp();
            {
                const uint32_t aA = fresh(oA), aB = fresh(oB), aC = fresh(oC), aZ = fresh(zr);
                const uint4 zc = lds128(aZ), zd = lds128(aZ + 64);
                const uint32_t zcs[4] = {zc.x, zc.y, zc.z, zc.w}, zds[4] = {zd.x, zd.y, zd.z, zd.w};
                uint32_t c[4];
#pragma unroll
                for (int k = 0; k < 4; k++) {
                    uint32_t a[4], b[4];
                    ldsm4t(a, aA + 128 * k); ldsm4t(b, aB + 128 * k);
                    if (!(k & 1)) ldsm4t(c, aC + 128 * k);
                    const h2c x = cmul_cd(h2c{a[0], a[2]}, *(const __half2*)&zcs[k], *(const __half2*)&zds[k]), y = cmul_cd(h2c{a[1], a[3]}, *(const __half2*)&zcs[k], *(const __half2*)&zds[k]);
                    mma_h(acc[0], a[0], a[1], a[2], a[3], b[0], b[1]);
                    mma_h(acc[1], a[0], a[1], a[2], a[3], b[2], b[3]);
                    mma_h(acc[2], a[0], a[1], a[2], a[3], c[2 * (k & 1)], c[2 * (k & 1) + 1]);
                    mma_h(acc[3], x.re, y.re, x.im, y.im, b[0], b[1]);
                    mma_h(acc[4], x.re, y.re, x.im, y.im, b[2], b[3]);
                    mma_h(acc[5], x.re, y.re, x.im, y.im, c[2 * (k & 1)], c[2 * (k & 1) + 1]);
                }
                asm volatile("" :: "f"(acc[0][0]), "f"(acc[1][0]), "f"(acc[2][0]), "f"(acc[3][0]), "f"(acc[4][0]), "f"(acc[5][0]) : "memory");
            }
            __syncwarp();
            ar = ar1; ai = ai1; W = W1;
        }
        if (threadIdx.x < 32) TSTAMP(21);
        const float i0 = __uint_as_float((ex + 243u) << 23);
        if (half) {
#pragma unroll
            for (int a = 0; a < 6; a++) sts128(wb + a * 512, __float_as_uint(acc[a][0]), __float_as_uint(acc[a][1]), __float_as_uint(acc[a][2]), __float_as_uint(acc[a][3]));
            sts32(stage + 3072, __float_as_uint(i0));
            bar_arrive(barid, 64);
        } else {
#pragma unroll
            for (int a = 0; a < 6; a++) { acc[a][0] *= i0; acc[a][1] *= i0; acc[a][2] *= i0; acc[a][3] *= i0; }
            if (lane == 0) acc[0][1] -= bf_lo(pD);
            sts32(zr, clock32());
            bar_sync(barid, 64);
            const uint32_t src = fresh(pstage);
            const float i1 = __uint_as_float(lds32(src + 3072));
#pragma unroll
            for (int a = 0; a < 6; a++) {
                const uint4 y = lds128(src + lane * 16 + a * 512);
                w[4 * (a % 3) + 2 * (a / 3)] = pack_bf16(fmaf(__uint_as_float(y.x), i1, acc[a][0]), fmaf(__uint_as_float(y.y), i1, acc[a][1]));
                w[4 * (a % 3) + 2 * (a / 3) + 1] = pack_bf16(fmaf(__uint_as_float(y.z), i1, acc[a][2]), fmaf(__uint_as_float(y.w), i1, acc[a][3]));
            }
            const uint32_t x0 = __shfl_up_sync(0xffffffffu, w[10], 2), x1 = __shfl_up_sync(0xffffffffu, w[11], 2);
            w[10] = w[8];
            if (t >= 2) { w[8] = x0; w[9] = x1; }
        }
    }
}

__device__ __forceinline__ int swap01(int i) { return (i & ~3) | ((i & 1) << 1) | ((i >> 1) & 1); }
enum { BC_AUX = 0, BC_S = 5, BC_KG = 15 };

__device__ __forceinline__ void fetch_gates(const Params& p, int i, int lane, unsigned epoch, uint32_t dst) {
    const uint32_t par = (epoch & 1) ? 0x80008000u : 0u;
    uint4 v;
#pragma unroll 1
    for (int it = 0;; it++) {
        v = ld_rlx128(p.s->gate + 256 * i + 8 * lane);
        v.x ^= par; v.y ^= par; v.z ^= par; v.w ^= par;
        if (__all_sync(0xffffffffu, (v.x & v.y & v.z & v.w & 0x80008000u) == 0x80008000u)) break;
        if (it > (1 << 20)) give_up();
    }
    sts128(dst + (8 + 16 * i + (lane >> 1)) * 16, v.x, v.y, v.z, v.w);
}
__device__ __forceinline__ void store_rows(const CUtensorMap* m, uint32_t src, int col, int row) {
    asm volatile("cp.async.bulk.tensor.5d.global.shared::cta.bulk_group [%0, {%2, %3, %3, %3, %4}], [%1];" :: "l"(m), "r"(src), "r"(col), "r"(0), "r"(row) : "memory");
}

__device__ __forceinline__ void store_or_add(void* o, const uint32_t (&y)[4], uint32_t add) {
    asm volatile("{ .reg .pred p; setp.ne.u32 p, %5, 0; @!p st.global.v4.u32 [%0], {%1,%2,%3,%4}; @p red.relaxed.gpu.global.add.noftz.v4.bf16x2 [%0], {%1,%2,%3,%4}; }"
                 :: "l"(o), "r"(y[0]), "r"(y[1]), "r"(y[2]), "r"(y[3]), "r"(add) : "memory");
}

__device__ __forceinline__ void conv_aux(const Params& p, const CUtensorMap* mU, uint32_t sb, int aw, int lane, int bid, unsigned epoch) {
    const unsigned t0 = clock32();
    const int g = lane >> 2, t = lane & 3, mi = lane >> 3, r8 = lane & 7;
    const int rank = bid & 1, slab = bid >> 1;
    const uint32_t bar_y = sb + SC_MISC, bar_u = bar_y + 32, bar_v = bar_y + 40, bar_box = bar_y + 64 + 8 * aw, s_bm = bar_y + 128;
    if (elect()) {
        mbar_init(bar_box, 1); mbar_fence();
        mbar_expect(bar_box, 4096);
        if (UDELAY) until(t0, UDELAY);
        tma4d(sb + SC_RT + 4096 * aw, mU, 16 * slab, 0, 0, 16 * rank + 2 * aw, bar_box);
        mbar_init(bar_y + 8 * aw, aw < 4 ? 9 : aw == 5 ? 8 : 1); mbar_fence();
        if (aw < 5) mbar_expect(bar_y + 8 * aw, aw == 4 ? 16384 : 4096);
    }
    __syncwarp();
    asm volatile("barrier.cluster.arrive.relaxed.aligned;" ::: "memory");
    asm volatile("setmaxnreg.dec.sync.aligned.u32 88;");
    const uint32_t ut = sb + SC_UT + aw * UT_STRIDE;
    sts128(ut + (mi >> 1) * (SC_ST - SC_UT) + (mi & 1) * UT_HALF + r8 * 16, 0, 0, 0, 0);
    if (lane < 16) sts128(s_bm + lane * 16, 0, 0, 0, 0);
    {
        const uint32_t dst = sb + SC_UT + swap01(g) * UT_STRIDE + (8 + 64 * rank + 8 * aw + t) * 16;
        const uint32_t rdst = mapa(dst, rank ^ 1), rbar = mapa(bar_u, rank ^ 1);
        asm volatile("barrier.cluster.wait.acquire.aligned;" ::: "memory");
        mbar_wait(bar_box);
        if (aw == 0) TSTAMP(1);
        const uint32_t src = fresh(sb + SC_RT) + aw * 4096 + (8 * mi + 4 * (r8 & 1) + (r8 >> 1)) * 32 + ((rank ^ (r8 & 1)) << 4);
        uint32_t x[8][4];
#pragma unroll
        for (int i = 0; i < 4; i++) { ldsm4t(x[i], src + 1024 * i); ldsm4t(x[4 + i], (src ^ 16) + 1024 * i); }
        asm volatile("" :: "r"(x[0][0]), "r"(x[1][0]), "r"(x[2][0]), "r"(x[3][0]) : "memory");
#pragma unroll
        for (int i = 0; i < 4; i++) st_async128(rdst + (i & 1) * UT_HALF + 32 * (i & 2), x[4 + i][0], x[4 + i][1], x[4 + i][2], x[4 + i][3], rbar);
#pragma unroll
        for (int i = 0; i < 4; i++) sts128(dst + (i & 1) * UT_HALF + 32 * (i & 2), x[i][0], x[i][1], x[i][2], x[i][3]);
    }
    bar_sync(BC_AUX, 256);
    mbar_wait_cluster(bar_u);
    if (aw == 0) TSTAMP(2);
    {
        const uint32_t a = fresh(ut) + (mi & 1) * UT_HALF + (64 * (mi >> 1) + r8) * 16;
        uint4 v = lds128(a);
#pragma unroll
        for (int i = 1; i <= 8; i++) {
            const uint4 w = lds128(a + 128 * i);
            sts128(a + 128 * i + (SC_ST - SC_UT), badd2(v.x, w.x), badd2(v.y, w.y), badd2(v.z, w.z), badd2(v.w, w.w));
            v = w;
        }
    }
    bar_arrive(BC_S + aw, 64);
    if (aw == 0) TSTAMP(3);
    {
        uint32_t ws = sb + SC_UT + t * UT_STRIDE + (g + 6) * 16, wd = sb + SC_V + t * V_STRIDE + 64 * g, sw = 16 * (g & 2);
#pragma unroll 1
        for (int k = aw; k < 25; k += 8) {
            if (k - aw == 8) {
                bar_sync(BC_KG, 384);
                if (lane < 16) sts128(sb + SC_V + aw * V_STRIDE + lane * 16, 0, 0, 0, 0);
            }
            if (k == 24) { ws -= (g & 1) * 4 * UT_STRIDE + 16 * g; wd -= (g & 1) * 4 * V_STRIDE + 64 * g; sw = 0; }
            const int h = k >= 12, a = k - 12 * h;
            const uint32_t d = wd + h * 4 * V_STRIDE + 512 * a;
            window_task(fresh(ws) + h * 4 * UT_STRIDE + 128 * a, d + sw, d + (sw ^ 32), a < 8);
        }
    }
    if (aw == 0) TSTAMP(9);
    {
        if (aw >= 2) fetch_gates(p, aw, lane, epoch, sb + SC_GT + (lane & 1) * UT_HALF);
        __syncwarp();
        if (elect()) { mbar_arrive(bar_v); prefetch_map(mU + 4); }
        next_epoch(p, epoch);
        if (aw == 0) TSTAMP(4);
        if (aw == 7) {
            const int row = key_row(wait_sel(p, slab >> 1, r8, key_tag(epoch)));
            if (lane < 8) asm volatile("red.shared.or.b32 [%0], %1;" :: "r"(s_bm + (row >> 5) * 4), "r"(1u << (row & 31)) : "memory");
            TSTAMP(10);
        }
        bar_sync(BC_AUX, 256);
        const uint32_t src = sb + SC_RT + ((r8 >> 1) & 1) * Y_RS + (2 * mi + (r8 & 1)) * Y_CS + (2 * aw + (r8 >> 2)) * 16;
        const int L = 2 * aw + (t >> 1);
        const int row0 = 256 * rank + 128 * (g >> 2) + 32 * (L & 3) + 16 * (g & 1) + 8 * ((g >> 1) & 1) + (L >> 2);
        __nv_bfloat16* outp = p.out + (size_t)row0 * DM + 16 * slab + 8 * (t & 1);
        const uint32_t stg = sb + SC_ST + 4096 * aw, so = (g >> 1) * 256 + (t >> 1) * 64 + (g & 1) * 32 + (t & 1) * 16;
#pragma unroll 1
        for (int s = 1; s < 4; s++) {
            const uint32_t bm = lds32(fresh(s_bm) + (16 * s + (row0 >> 5)) * 4) >> (row0 & 31);
            const bool routed = __any_sync(0xffffffffu, bm & 0x11u);
            if (aw == s) mbar_wait_cluster(bar_y + 8 * s);
            bar_sync(BC_AUX, 256);
            const uint32_t sf = fresh(src) + 512 * s;
            uint32_t y[2][4];
            ldsm4t(y[0], sf); ldsm4t(y[1], sf + 256);
            if (routed) {
#pragma unroll
                for (int k = 0; k < 2; k++) store_or_add(outp + (size_t)(512 * s + 4 * k) * DM, y[k], bm & (1u << (4 * k)));
            } else {
                sts128(stg + so + 1024 * s, y[0][0], y[0][1], y[0][2], y[0][3]); sts128(stg + so + 1024 * s + 128, y[1][0], y[1][1], y[1][2], y[1][3]);
                asm volatile("fence.proxy.async.shared::cta;" ::: "memory");
                __syncwarp();
                if (elect()) store_rows(mU + 4, stg + 1024 * s, 16 * slab, 512 * s + 256 * rank + 64 * (aw & 1) + (aw >> 1));
            }
            if (aw == 0) TSTAMP(16 + s);
        }
        if (elect()) { asm volatile("cp.async.bulk.commit_group;" ::: "memory"); asm volatile("cp.async.bulk.wait_group.read 0;" ::: "memory"); }
        if (aw == 0) TFLUSH();
    }
}

__device__ __forceinline__ uint32_t k_tag(unsigned epoch) { return epoch << 16 | 0x80000000u; }
__device__ __forceinline__ void publish_k(uint4* kp, const uint32_t (&w)[12], unsigned epoch, bool full) {
#pragma unroll
    for (int i = 0; i < 3; i++)
        asm volatile("st.relaxed.gpu.global.v4.u32 [%0], {%1,%2,%3,%4};" :: "l"(kp + 32 * i), "r"(w[3 * i]), "r"(w[3 * i + 1]), "r"(w[3 * i + 2]),
                     "r"(full ? __byte_perm(w[9 + (i >> 1)], k_tag(epoch), i == 1 ? 0x7632 : 0x7610) : k_tag(epoch)));
}
template <bool FULL>
__device__ __forceinline__ void k_tables(uint32_t kt, int lane, const uint32_t (&w)[12]) {
    const int g = lane >> 2, t = lane & 3, mi = lane >> 3, r8 = lane & 7;
    uint32_t x3 = w[7], re[4], rx[4];
#pragma unroll
    for (int i = 0; i < 4; i++) {
        re[i] = __shfl_sync(0xffffffffu, w[i], lane + 31);
        rx[i] = __shfl_sync(0xffffffffu, w[4 + i], lane + (i == 0 && lane == 29 ? 5 : 1 + 2 * t));
    }
    if (FULL) {
        asm volatile("stmatrix.sync.aligned.m8n8.x2.trans.shared.b16 [%0], {%1,%2};" :: "r"(kt + (KT_D + 7) * 4 + 64 * t + 16 * (mi & 1) + 8 * (r8 & 4)), "r"(w[8]), "r"(w[9]) : "memory");
        if (lane == 2) {
            sts32(kt + (KT_C + 78) * 4, w[10] & 0xffffu);
            sts128(kt + (KT_T + 2) * 4, 0, w[10] & 0xffffu, __byte_perm(w[10], 0, 0x1010), w[10] << 16);
        }
        if (lane == 29) x3 = bsub2(x3, rx[0] & 0xffffu);
    }
#pragma unroll
    for (int i = 0; i < 4; i++) {
        sts64(kt + (16 + 64 * i) * 4 + 8 * lane, __byte_perm(w[i], lane ? re[i] : i ? re[i - 1] : 0, 0x5432), w[i]);
        const uint32_t x = i < 3 ? w[4 + i] : x3, aa = __byte_perm(x, 0, 0x3232);
        if (t < 2) sts128(kt + (272 + 64 * i + 8 * g + 4 * t) * 4, i == 0 && lane == 0 ? __byte_perm(x, re[3], 0x5432) : aa, aa, x,
                          __byte_perm(lane != 29 ? rx[i] : i < 3 ? rx[(i + 1) & 3] : FULL ? 0 : rx[0] << 16, x, 0x5432));
        else if (FULL) sts32(kt + (KT_C - 50 + 8 * i + 32 * t + g) * 4, x);
    }
}

__device__ __forceinline__ void conv_main(const Params& p, uint32_t sb, int warp, int lane0, int bid, unsigned epoch, uint32_t (&w)[12]) {
    asm volatile("setmaxnreg.inc.sync.aligned.u32 168;");
    const int lane = __shfl_sync(0xffffffffu, lane0, lane0);
    const int g = lane >> 2, t = lane & 3, mi = lane >> 3, r8 = lane & 7;
    const int rank = bid & 1;
    const uint32_t bar_y = sb + SC_MISC, bar_v = bar_y + 40;
    next_epoch(p, epoch);
    if (warp < 4) {
        asm volatile("" :: "r"(w[0]), "r"(w[2]), "r"(w[4]), "r"(w[6]), "r"(w[8]), "r"(w[10]) : "memory");
        bar_arrive(BC_KG, 384);
    } else {
        bar_sync(BC_S + swap01(warp), 64);
        const uint4* src = p.s->kp + (8 * bid + warp) * 96 + lane0;
#pragma unroll 1
        for (int it = 0;; it++) {
            uint32_t bad = 0, e[3];
#pragma unroll
            for (int i = 0; i < 3; i++) { const uint4 v = ld_rlx128(src + 32 * i); w[3 * i] = v.x; w[3 * i + 1] = v.y; w[3 * i + 2] = v.z; e[i] = v.w; bad |= v.w ^ k_tag(epoch); }
            w[9] = __byte_perm(e[0], e[1], 0x5410); w[10] = e[2];
            const bool ok = __all_sync(0xffffffffu, bad < 65536);
            if (ok) break;
            if (it > (1 << 20)) give_up();
        }
    }
    if ((warp & 3) == 0) TSTAMP(5 + (warp >> 2));
    k_tables<true>(sb + SC_KT + warp * KT_BYTES, lane0, w);
    asm volatile("barrier.cluster.wait.acquire.aligned;" ::: "memory");
    if (warp < 4)
    bar_sync(BC_S + swap01(warp), 64);
    __syncwarp();
    if ((warp & 3) == 0) TSTAMP(7 + (warp >> 2));
    {
        const uint32_t ut = fresh(sb + SC_UT) + swap01(warp) * UT_STRIDE, kt = fresh(sb + SC_KT) + warp * KT_BYTES;
        uint32_t u1 = ut + (mi & 1) * UT_HALF + (8 + r8) * 16 + (mi >> 1) * 128;
        auto dup = [&](uint32_t v) { return v ^ p.zero; };
        uint32_t kp = kt + (16 + g - 2 * t) * 4;
        float acc[16][4];
        {
            const uint32_t c0 = lds32(kp + 2048), c1 = lds32(kp + 2080), c2 = lds32(kp + 2016), c3 = dup(c0);
            const uint32_t e0 = lds32(kp + (KT_T - 16) * 4), e1 = lds32(kp + (KT_T - 8) * 4), e2 = lds32(kp + (KT_T - 24) * 4), e3 = dup(e0);
            const uint32_t f0 = dup(e1), f1 = lds32(kp + KT_T * 4);
            const uint32_t uo = ut + UT_HALF + (7 + lane) * 16;
#pragma unroll
            for (int i = 0; i < 16; i++) { acc[i][0] = acc[i][1] = acc[i][2] = acc[i][3] = 0.f; }
#pragma unroll
            for (int mu = 0; mu < 8; mu += 4) {
                uint32_t b[4];
                ldsm4(b, uo + 128 * mu);
#pragma unroll
                for (int k = 0; k < 4; k++) mma_bf8(acc[mu + 8 + k], f0, f1, b[k]);
            }
#pragma unroll
            for (int mu = 0; mu < 12; mu += 2) {
                uint32_t b[4];
                ldsm4(b, u1 + 128 * mu);
                mma_bf(acc[mu + 4], c0, c1, c2, c3, b[0], b[1]);
                mma_bf(acc[mu + 5], c0, c1, c2, c3, b[2], b[3]);
                if (mu < 8) { mma_bf(acc[mu + 8], e0, e1, e2, e3, b[0], b[1]); mma_bf(acc[mu + 9], e0, e1, e2, e3, b[2], b[3]); }
            }
        }
        {
            float M[8][4];
#pragma unroll
            for (int i = 0; i < 8; i++) { M[i][0] = M[i][1] = M[i][2] = M[i][3] = 0.f; }
            uint32_t s[8][4], a3[4];
            const uint32_t kb = kp, ub = dup(u1), uc = u1 + (mi >> 1) * 128;
            auto frag = [&](uint32_t (&a)[4], uint32_t x) { a[0] = lds32(x); a[1] = lds32(x + 32); a[2] = lds32(x - 32); a[3] = dup(a[0]); };
            frag(a3, kp + 1536);
#pragma unroll
            for (int i = 1; i < 8; i++) ldsm4(s[i], u1 + (SC_ST - SC_UT) + 256 * i);
            __syncwarp();
            uint32_t ko = 0, uo = 0;
            const uint32_t pub = bid >= 48 ? PUBY : PUBIT;
#pragma unroll 1
            for (uint32_t n = warp < 4 ? pub : 8;; n = 8 - pub) {
#pragma unroll 1
            for (; n; n--) {
                uint32_t a2[4], a1[4], a0[4], b[4][4];
                ko = fresh(ko); uo = fresh(uo);
                kp = kb + ko; u1 = ub + uo;
                const uint32_t up = uc + uo;
                ko += 64; uo -= 16;
                frag(a2, kp + 1024);
#pragma unroll
                for (int i = 1; i < 4; i++) ldsm4(b[i], up + 512 * i);
                asm("ldmatrix.sync.aligned.m8n8.x2.shared.b16 {%0,%1}, [%2];" : "=r"(b[0][2]), "=r"(b[0][3]) : "r"(up + 256));
                frag(a1, kp + 512); frag(a0, kp);
                kp += 64; u1 -= 16;
#pragma unroll
                for (int i = 1; i < 7; i++) mma_bf(acc[2 * i + 2], a3[0], a3[1], a3[2], a3[3], s[i][0], s[i][1]);
#pragma unroll
                for (int e = 0; e < 4; e++) a3[e] = bsub2(a2[e], a3[e]);
#pragma unroll
                for (int i = 1; i < 7; i++) mma_bf(acc[2 * i + 3], a2[0], a2[1], a2[2], a2[3], s[i][2], s[i][3]);
                ldsm4(s[1], u1 + (SC_ST - SC_UT) + 256);
#pragma unroll
                for (int i = 1; i < 7; i++) mma_bf(M[i + 1], a3[0], a3[1], a3[2], a3[3], b[i >> 1][2 * (i & 1)], b[i >> 1][2 * (i & 1) + 1]);
                frag(a3, kp + 1536);
#pragma unroll
                for (int i = 2; i < 8; i++) mma_bf(acc[2 * i], a1[0], a1[1], a1[2], a1[3], s[i][0], s[i][1]);
#pragma unroll
                for (int e = 0; e < 4; e++) a1[e] = bsub2(a0[e], a1[e]);
#pragma unroll
                for (int i = 2; i < 8; i++) { mma_bf(acc[2 * i + 1], a0[0], a0[1], a0[2], a0[3], s[i][2], s[i][3]); ldsm4(s[i], u1 + (SC_ST - SC_UT) + 256 * i); }
#pragma unroll
                for (int i = 2; i < 8; i++) mma_bf(M[i], a1[0], a1[1], a1[2], a1[3], b[i >> 1][2 * (i & 1)], b[i >> 1][2 * (i & 1) + 1]);
            }
            if (ko == 512) break;
            publish_k(p.s->kp + (8 * bid + warp) * 96 + lane, w, epoch, false);
            }
            u1 = ub;
#pragma unroll
            for (int i = 2; i < 8; i++)
#pragma unroll
                for (int c = 0; c < 4; c++) { acc[2 * i][c] += M[i][c]; acc[2 * i + 1][c] -= M[i][c]; }
        }
        if ((warp & 3) == 0) TSTAMP(11 + (warp >> 2));
        mbar_wait(bar_v);
        const uint32_t vt = fresh(sb + SC_V) + swap01(warp) * V_STRIDE;
        const uint32_t g1 = fresh(u1) - ut + sb + SC_GT;
        const uint32_t ydst = sb + SC_RT + rank * Y_RS + warp * Y_CS + lane * 16;
        const uint32_t ydr = mapa(ydst, rank ^ 1), ybr = mapa(bar_y, rank ^ 1);
        auto stairs = [&](auto R) {
        uint32_t ug[2][2][4];
        auto ld_ug = [&](int i) { ldsm4t(ug[i & 1][0], u1 + 256 * i); ldsm4t(ug[i & 1][1], g1 + 256 * i); };
        auto ship = [&](int i) {
            const uint32_t (&u)[4] = ug[i & 1][0], (&gg)[4] = ug[i & 1][1];
            const uint32_t y0 = gmix(gg[0], acc[2 * i][0], acc[2 * i][1], u[0]), y1 = gmix(gg[1], acc[2 * i][2], acc[2 * i][3], u[1]);
            const uint32_t y2 = gmix(gg[2], acc[2 * i + 1][0], acc[2 * i + 1][1], u[2]), y3 = gmix(gg[3], acc[2 * i + 1][2], acc[2 * i + 1][3], u[3]);
            if ((i & 1) != R.value) st_async128(ydr + 512 * (i >> 1), y0, y1, y2, y3, ybr + 8 * (i >> 1));
            else asm volatile("{ .reg .pred q; setp.eq.u32 q, %6, 0; st.shared.v4.u32 [%0], {%2,%3,%4,%5}; bar.warp.sync 0xffffffff; @q mbarrier.arrive.shared::cta.b64 _, [%1]; }"
                              :: "r"(ydst + 512 * (i >> 1)), "r"(bar_y + 8 * (i >> 1)), "r"(y0), "r"(y1), "r"(y2), "r"(y3), "r"(lane) : "memory");
        };
        const uint32_t VD = vt + (VC_OFF - 400 - 16 * t) * 4 + (8 * g ^ 16 * (-t & 2)), VD2 = vt + (VC_OFF - 415 - 16 * t) * 4 + (8 * g ^ 16 * (~t & 2));
        uint2 bd[10];
        uint32_t x[2][4][4];
        auto ld4 = [&](uint32_t (&v)[4], int dl) { const uint2 w = lds64(VD + 256 * dl); v[0] = w.x; v[1] = w.y; v[2] = lds32(VD2 + 256 * dl); v[3] = dup(w.x); };
        auto mm4 = [&](const uint32_t (&v)[4], int dl) {
#pragma unroll
            for (int s = dl & 1; s < 10; s += 2) if ((dl + s) / 2 >= 4 && (dl + s) / 2 < 16) mma_bf(acc[(dl + s) / 2], v[0], v[1], v[2], v[3], bd[s].x, bd[s].y);
        };
        const uint32_t KE = kt + (KT_D + g + t) * 4, VE = vt + (VE_BASE - 912 - 16 * t) * 4 + (8 * g ^ 16 * (~t & 2));
        uint32_t b0[8], b1[8];
        auto ld8 = [&](uint32_t (&v)[4], int dl) { const uint2 w = lds64(VE + 512 * dl), z = lds64(VE + 512 * dl - 256); v[0] = w.x; v[1] = w.y; v[2] = z.x; v[3] = z.y; };
        auto mm8 = [&](const uint32_t (&v)[4], int dl, int lo, int hi) {
#pragma unroll
            for (int s = 0; s < 8; s++) if (dl + s >= lo && dl + s < hi) mma_bf(acc[dl + s], v[0], v[1], v[2], v[3], b0[s], b1[s]);
        };
        ld4(x[0][0], 6);
#pragma unroll
        for (int s = 0; s < 10; s++) bd[s] = lds64(kt + (KT_C + 2 * g + 2 * t + 8 * s) * 4);
        mm4(x[0][0], 6);
        uint32_t e[4][4];
#pragma unroll
        for (int k = 1; k < 6; k++) {
#pragma unroll
            for (int j = 0; j < 4; j++) ld4(x[k & 1][j], 4 * k + 3 + j);
            ld_ug(k + 1);
            if (k == 3) {
#pragma unroll
                for (int s = 0; s < 8; s++) { b0[s] = lds32(KE + 32 * s); b1[s] = lds32(KE + 32 * s + 16); }
            }
            if (k > 1) ship(k);
#pragma unroll
            for (int j = 0; j < 4; j++) {
                mm4(x[k & 1][j], 4 * k + 3 + j);
                if (k == 3) { uint32_t v[4], z[4]; ld8(e[j], 8 + j); ld8(v, 12 + j); ld4(z, 30 - j); mm8(v, 12 + j, 12, 16); mm8(e[j], 8 + j, 8, 12); mm4(z, 30 - j); }
                if (k == 5) { ld8(e[j], 8 + j + p.zero); mm8(e[j], 8 + j, 12, 16); }
            }
        }
        ld_ug(7);
        ship(7 - R.value); ship(6 + R.value);
        };
        if (rank) stairs(std::integral_constant<int, 1>()); else stairs(std::integral_constant<int, 0>());
        if ((warp & 3) == 0) TSTAMP(14 + (warp >> 2)); else TSTAMP(21 + warp);
    }
}

constexpr int SF_WD = 73728;
constexpr int SF_RED = 49152;
constexpr int MU_HALF = 640, MU_STRIDE = 1344, SM_RAW = 98304, SM_UT = SM_RAW + 16384, SM_G = SM_UT + 16 * MU_STRIDE, SM_Y = 196608, SM_KT = 138880, SM_KW = SM_G - 49152;
constexpr int SF_XS = 221184;
constexpr int SF_MISC = SF_XS + 8 * 1168;
constexpr int SF_KG = SF_MISC - 10 * KG_STAGE;
constexpr int SF_WR = SF_KG - 2304;
constexpr int FB_X = 64, FB_KDONE = 72, FB_KEYS = 80, FB_FREE = 88  , FB_W = 104, FB_D = FB_W + 72, FB_MU = FB_D + 96, FB_MG = FB_MU + 8, FB_MT = FB_MU + 16, FS_PART = 512, FS_TOK = 896, FS_BM = 1024;
enum { BAR_F = 6, BAR_R = 7, BAR_GU = 8, BAR_RED = 9, BAR_R2 = 10, BAR_X = 11, BAR_G = 12  , BAR_M = 15 };
static_assert(SF_KG % 128 == 0 && NPRE <= 8 && SM_KT + 4 * 2112 <= 147456 && SM_G + MU_STRIDE <= SF_WR - 4 * 9216 && SM_KW + 6 * 2112 >= SM_RAW && SM_KW + 12 * 2112 <= SM_UT, "layout");

__device__ __forceinline__ int mini_ch0(int f) { return f < NW ? 16 * (f - 12) : 32 * (f - NW); }

__device__ __forceinline__ void ffn_front(const Params& p, const CUtensorMap* maps, uint32_t sb, int warp, int lane, int f, unsigned epoch) {
    const unsigned t0 = clock32();
    const int g = lane >> 2, t = lane & 3, mi = lane >> 3, r8 = lane & 7;
    const bool isx = f < NX;
    const int nrw = f < 8 ? 6 : 4, r0 = f < 8 ? 48 * f : 128 + 32 * f;
    const int rw = warp < 12 ? 13 - warp : warp ^ (warp < 14 ? 10 : 15);
    const uint32_t bar_row = sb + SF_MISC  , bar_x = bar_row + FB_X;
    const uint32_t s_part = bar_row + FS_PART  , s_tok = bar_row + FS_TOK  ;
    const uint32_t rows = sb + SF_WR - 9216 * (rw + 1);
    {
#pragma unroll 1
        for (int i = warp < 10 ? 30 : warp - 10; i < 29; i += 6) if (elect()) mbar_init(bar_x + 8 * i, 1 << max(i - 26, 0));
        const uint32_t bytes = rw < 6 ? 9216 : 1152, dst = rw < 6 ? rows : sb + SF_WR + (rw & 1) * 1152;
        const __nv_bfloat16* src = rw < 6 ? p.u + (size_t)(r0 + 8 * rw) * DM : (rw & 1) ? p.gatew : p.wr;
        if (elect()) { mbar_init(bar_row + 8 * rw, 1); mbar_fence(); mbar_expect(bar_row + 8 * rw, bytes); }
        if (rw < nrw) until(t0, RDELAY);
        if (rw < nrw || rw >= 6) { if (elect()) bulk_g2s(dst, src, bytes, bar_row + 8 * rw); }
    }
    uint4* const kdst = p.s->keys + (lane >> 1) * 128 + 2 * f + (lane & 1);
    if (warp == 13) {
        stg128(kdst, 0, 0, 0, 0);
        sts32(s_part + 64 + lane * 4, 0); sts32(bar_row + FS_BM + lane * 4, 0);
        if (lane < 8 && isx && !(f & 1)) st_rlx32(&p.s->sel[32 * f + lane], 0);
    }
    __syncwarp();
    bar_sync(BAR_F, f < 12 ? 256 : 192);
    bar_arrive(0, NTHR);
    if (warp == 15) TSTAMP(1);

    if (warp == 12) {
        if (lane < 22) mbar_expect(bar_row + FB_W + 8 * lane, lane < 9 ? 24576 : lane < 21 ? 12288 : f < NW ? 16384 : 32768);
        if (elect()) { prefetch_map(maps + 1); prefetch_map(maps + 2); prefetch_map(maps + (isx ? 3 : 5)); }
        unsigned tb = t0 + WDELAY;
        auto pieces = [&](int n, int end, uint32_t dst) {
#pragma unroll 1
            for (; n < end; n++, dst += 12288) {
                until(tb, 0); tb += WGAP;
                if (elect()) tma3d(dst, maps + 1 + (n & 1), 0, 64 * (n >> 1), 3 * f, bar_row + FB_W + 8 * (n >> 1));
            }
        };
        if (!isx) {
            until(t0, MDELAY);
#pragma unroll 1
            for (int k = f >= NW; k >= 0; k--) if (elect()) tma4d(sb + SM_RAW - 49152 * k, maps + 5, mini_ch0(f) + 16 * k, 0, 0, 0, bar_row + FB_MU);
            if (f >= NW) return;
        }
#pragma unroll 1
        for (int i = 0; i < 4; i++) {
            if (i == 1) { mbar_wait(bar_row + FB_KEYS); mbar_wait(bar_row + FB_KDONE); tb = clock32() + RESUME; }
            if (i == 3) mbar_wait(bar_row + FB_FREE);
            const int n = ((0x0c080000 + NPRE * 256) >> (8 * i)) & 255;
            pieces(n, ((0x120c0800 + NPRE) >> (8 * i)) & 255, sb + 12288 * (((0x000c0000 + NPRE * 256) >> (8 * i)) & 255));
        }
        TSTAMP(12);
        if (isx) {
#pragma unroll 1
            for (int i = 0; i < 12; i++) {
                const int n = (0x987610ba5432ull >> (4 * i)) & 15;
                if (i == 6) mbar_wait(bar_row + FB_FREE + 8);
                until(tb, 0); tb += DGAP;
                if (elect()) tma2d(sb + SF_WD + n * 12288, maps + 3, 32 * (f >> 1), 2304 * (f & 1) + 192 * n, bar_row + FB_D + 8 * n);
            }
            TSTAMP(13);
        }
    } else if (warp == 13) {
        const uint32_t tag = key_tag(epoch), par = (epoch & 1) ? 0u : 0x8000u;
        bar_sync(BAR_R, 32 * (nrw + 1));
        TSTAMP(3);
        {
            const uint32_t sg = fresh(s_part) + 192 + lane * 4;
            const uint32_t gb = pack_bf16(sigmoidf_(rbf(__uint_as_float(lds32(sg)))), sigmoidf_(rbf(__uint_as_float(lds32(sg + 128))))) | par | (par << 16);
            asm volatile("st.relaxed.gpu.global.u16 [%0], %1;" :: "l"(p.s->gate + r0 + lane), "h"((unsigned short)gb) : "memory");
            if (nrw > 4 && lane < 16) asm volatile("st.relaxed.gpu.global.u16 [%0], %1;" :: "l"(p.s->gate + r0 + 32 + lane), "h"((unsigned short)(gb >> 16)) : "memory");
        }
        bar_sync(BAR_R2, 32 * (nrw + 1));
        {
            const uint4 v = lds128(fresh(s_tok) + (lane & 1) * 16);
            asm volatile("st.relaxed.gpu.global.v4.u32 [%0], {%1,%2,%3,%4};" :: "l"(kdst), "r"(v.x | tag), "r"(v.y | tag), "r"(v.z | tag), "r"(v.w | tag) : "memory");
        }
        TSTAMP(4);
        if (lane == 0) { mbar_arrive(bar_row + FB_KEYS); mbar_expect(bar_x, 8 * 1152); }
        if (f >= NW) return;
        uint32_t k[16];
        const uint4* src = p.s->keys + (f & 15) * 128 + lane;
#pragma unroll 1
        for (int it = 0;; it++) {
            uint32_t bad = 0;
#pragma unroll
            for (int i = 0; i < 4; i++) {
                const uint4 x = ld_rlx128(src + (i < 3 || lane < 24 ? 32 * i : 64));
                k[i] = x.x; k[4 + i] = x.y; k[8 + i] = x.z; k[12 + i] = x.w;
                bad |= x.x ^ tag;
            }
            const bool ok = __all_sync(0xffffffffu, (bad & 0xf800u) == 0);
            if (ok) break;
            if (it > (1 << 20)) give_up();
        }
        TSTAMP(5);
        uint32_t key = 0;
#pragma unroll 2
        for (int r = 0; r < 8; r++) {
            const uint32_t m = __reduce_max_sync(0xffffffffu, max(max(k[0], k[1]), max(k[2], k[3])));
#pragma unroll
            for (int i = 0; i < 4; i++) {
                const bool pop = k[i] == m;
                k[i] = pop ? k[4 + i] : k[i]; k[4 + i] = pop ? k[8 + i] : k[4 + i]; k[8 + i] = pop ? k[12 + i] : k[8 + i]; k[12 + i] = pop ? 0 : k[12 + i];
            }
            if (r8 == r) key = m;
        }
        const int row = key_row(key);
        sts32(s_tok + r8 * 8, row);
        bar_arrive(BAR_X, 160);
        TSTAMP(6);
        if (isx) {
            if (!(f & 1)) {
                __nv_bfloat16* o = p.out + (size_t)row * DM + 16 * f + 8 * mi;
                asm volatile("st.relaxed.gpu.global.v4.u32 [%0], {%1,%1,%1,%1};" :: "l"(o), "r"(0) : "memory");
                if (__any_sync(0xffffffffu, ld_rlx32(o) != 0)) give_up();
                if (lane < 8) st_rlx32(&p.s->sel[32 * f + lane], key);
            } else wait_sel(p, f >> 1, r8, tag);
            uint32_t gb;
#pragma unroll 1
            for (int it = 0;; it++) {
                asm volatile("ld.relaxed.gpu.global.u16 %0, [%1];" : "=r"(gb) : "l"(p.s->gate + row) : "memory");
                gb ^= par;
                if (!(gb & 0x8000u)) break;
                if (it > (1 << 20)) give_up();
            }
            const uint32_t rb = key ^ 0x80000000u, rv = (rb ^ (((int)rb >> 31) & 0x7fff0000u)) & 0xffff0000u;
            sts32(s_tok + r8 * 8 + 4, __float_as_uint(rbf(1.0f - bf_lo(gb)) * rbf(sigmoidf_(__uint_as_float(rv)))));
            __syncwarp();
            TSTAMP(7);
            bar_arrive(BAR_RED, 416);
        }
    } else {
        if (rw < nrw) {
            float c[3][4];
#pragma unroll
            for (int i = 0; i < 3; i++) { c[i][0] = c[i][1] = c[i][2] = c[i][3] = 0.f; }
            mbar_wait(bar_row + 48); mbar_wait(bar_row + 56);
            const uint32_t b = fresh(sb + SF_WR) + (g & 1) * 1152 + (g >> 2) * 64 + t * 16 + (g & 2) * 2;
            uint32_t w[18][2];
#pragma unroll
            for (int kb = 0; kb < 18; kb++) { const uint32_t o = ((kb & 1) ? b ^ 64 : b) + 128 * (kb >> 1); w[kb][0] = lds32(o); w[kb][1] = lds32(o + 8); }
            mbar_wait(bar_row + 8 * rw);
            if (warp == 15) TSTAMP(2);
            const uint32_t a = fresh(rows) + g * 1152 + (g & 1) * 64 + t * 16;
#pragma unroll
            for (int kb = 0; kb < 18; kb++) {
                const uint4 x = lds128(((kb & 1) ? a ^ 64 : a) + 128 * (kb >> 1));
                mma_bf(c[kb % 3], x.x, x.y, x.z, x.w, w[kb][0], w[kb][1]);
            }
            const float sr = c[0][0] + c[1][0] + c[2][0] + __shfl_down_sync(0xffffffffu, c[0][2] + c[1][2] + c[2][2], 1);
            const float sg = c[0][1] + c[1][1] + c[2][1] + __shfl_down_sync(0xffffffffu, c[0][3] + c[1][3] + c[2][3], 1);
            const uint32_t rb = pack_bf16(0.f, sr);
            if (t == 2 * (g & 1)) {
                sts32(s_part + (8 * rw + g) * 4, (rb ^ (((int)rb >> 31) & 0x7fff0000u) ^ 0x80000000u) | (uint32_t)(2047 - r0 - 8 * rw - g));
                sts32(s_part + 192 + (8 * rw + g) * 4, __float_as_uint(sg));
            }
            __syncwarp();
            bar_sync(BAR_R, 32 * (nrw + 1));
            const uint32_t sk = fresh(s_part), kk = lds32(sk + (8 * rw + r8) * 4);
            int n = 0;
#pragma unroll
            for (int i = 0; i < 3; i++) { const uint4 v = lds128(sk + mi * 48 + 16 * i); n += (v.x > kk) + (v.y > kk) + (v.z > kk) + (v.w > kk); }
            n += __shfl_xor_sync(0xffffffffu, n, 8); n += __shfl_xor_sync(0xffffffffu, n, 16);
            if (n < 8) sts32(s_tok + 4 * n, kk);
            __syncwarp();
            bar_arrive(BAR_R2, 32 * (nrw + 1));
        }
    }
}

__device__ __forceinline__ void ffn_work(const Params& p, uint32_t sb, int warp, int lane, int f, unsigned epoch) {
    const int g = lane >> 2, t = lane & 3, mi = lane >> 3, r8 = lane & 7;
    const bool isx = f < NX;
    const uint32_t bar_x = sb + SF_MISC + FB_X, bar_free = sb + SF_MISC + FB_FREE, bar_w = sb + SF_MISC + FB_W, bar_d = sb + SF_MISC + FB_D, s_tok = sb + SF_MISC + FS_TOK;
    uint32_t fr[24][4];
    auto pin = [&] {
#pragma unroll
        for (int i = 0; i < 24; i += 8) asm volatile("" :: "r"(fr[i][0]), "r"(fr[i + 1][0]), "r"(fr[i + 2][0]), "r"(fr[i + 3][0]), "r"(fr[i + 4][0]), "r"(fr[i + 5][0]), "r"(fr[i + 6][0]), "r"(fr[i + 7][0]) : "memory");
    };
    {
        const int j = (unsigned)(warp - 4) < 6, w = warp - (j ? 4 : warp < 4 ? 0 : 6);
        float ag[2][4], au[2][4];
#pragma unroll
        for (int i = 0; i < 2; i++) { ag[i][0] = ag[i][1] = ag[i][2] = ag[i][3] = 0.f; au[i][0] = au[i][1] = au[i][2] = au[i][3] = 0.f; }
        const uint32_t wb = sb + (w >> 1) * 4096 + (r8 + 8 * (mi >> 1)) * 64 + (((2 * (w & 1) + (mi & 1)) ^ (r8 >> 1)) << 4);
        const uint32_t xb = sb + SF_XS + r8 * 1168 + mi * 16;
        auto load = [&](int i, int n, int place) {
            mbar_wait(bar_w + 8 * n);
            const uint32_t wk = fresh(wb) + place * 24576;
#pragma unroll
            for (int s = 0; s < 4; s++) { ldsm4t(fr[8 * i + s], wk + 1024 * s); ldsm4t(fr[8 * i + 4 + s], wk + 1024 * s + 12288); }
        };
        auto mul = [&](int i, uint32_t xk) {
            uint32_t x[2][4];
            ldsm4(x[0], xk); ldsm4(x[1], xk + 64);
#pragma unroll
            for (int s = 0; s < 4; s++) {
                const uint32_t (&a)[4] = fr[8 * i + s], (&b)[4] = fr[8 * i + 4 + s];
                mma_bf(ag[s & 1], a[0], a[1], a[2], a[3], x[s >> 1][2 * (s & 1)], x[s >> 1][2 * (s & 1) + 1]);
                mma_bf(au[s & 1], b[0], b[1], b[2], b[3], x[s >> 1][2 * (s & 1)], x[s >> 1][2 * (s & 1) + 1]);
            }
        };
#pragma unroll
        for (int i = 0; i < 3; i++) load(i, 3 * j + i, (i ? 5 : 3) * j + i);
        pin();
        bar_sync(BAR_G + j, 192);
        if (w == 0 && lane == 0) mbar_arrive(bar_free + 8 * j);
        if (warp < 4) {
            bar_sync(BAR_X, 160);
            const uint32_t rows = lds32(fresh(s_tok) + 8 * r8);
#pragma unroll 1
            for (int i = warp; i < 8; i += 4) {
                const int row = __shfl_sync(0xffffffffu, rows, i);
                if (elect()) bulk_g2s(sb + SF_XS + i * 1168, p.u + (size_t)row * DM, 1152, bar_x);
                __syncwarp();
            }
        }
        mbar_wait(bar_x);
        if (warp == 0) TSTAMP(8);
        {
            const uint32_t xk = fresh(xb) + 384 * j;
#pragma unroll
            for (int i = 0; i < 3; i++) { mul(i, (i ? fresh(xk) : xk) + 128 * i); if (i == 0) { asm volatile("" :: "f"(ag[0][0]), "f"(ag[1][0]), "f"(au[0][0]), "f"(au[1][0])); sts32(s_tok + 64, clock32()); } }
        }
#pragma unroll 1
        for (int n = 6 + j; n < 9; n += 2) { load(0, n, n - 6); mul(0, fresh(xb) + 128 * n); }
#pragma unroll
        for (int c = 0; c < 4; c++) { ag[0][c] += ag[1][c]; au[0][c] += au[1][c]; }
        if (j) {
            sts128(wb + 24576, __float_as_uint(ag[0][0]), __float_as_uint(ag[0][1]), __float_as_uint(ag[0][2]), __float_as_uint(ag[0][3]));
            sts128(wb + 25600, __float_as_uint(au[0][0]), __float_as_uint(au[0][1]), __float_as_uint(au[0][2]), __float_as_uint(au[0][3]));
        }
        bar_sync(BAR_GU, 384);
        if (!j) {
            const uint32_t sf = fresh(wb);
            const uint4 g1 = lds128(sf + 24576), u1 = lds128(sf + 25600);
            const uint32_t gs[4] = {g1.x, g1.y, g1.z, g1.w}, us[4] = {u1.x, u1.y, u1.z, u1.w};
            if (warp == 0) TSTAMP(9);
            float h[4];
#pragma unroll
            for (int c = 0; c < 4; c++) {
                const float gv = rbf(ag[0][c] + __uint_as_float(gs[c]));
                h[c] = rbf(gv * sigmoidf_(gv)) * rbf(au[0][c] + __uint_as_float(us[c]));
            }
            uint32_t h0, h1;
            asm("movmatrix.sync.aligned.m8n8.trans.b16 %0, %1;" : "=r"(h0) : "r"(pack_bf16(h[0], h[1])));
            asm("movmatrix.sync.aligned.m8n8.trans.b16 %0, %1;" : "=r"(h1) : "r"(pack_bf16(h[2], h[3])));
            if (h0 == 0) h0 = 0x8000u;
            asm volatile("{ .reg .b64 v; mov.b64 v, {%1, %2}; st.relaxed.gpu.global.b64 [%0], v; }" :: "l"(p.s->h + ((epoch & 1) * 288 + 6 * f + w) * 32 + lane), "r"(h0), "r"(h1) : "memory");
        }
        if (isx) {
            if (warp == 0) TSTAMP(10);
            const uint2* hsrc = p.s->h + ((epoch & 1) * 288 + 144 * (f & 1) + 12 * warp) * 32 + lane;
            uint2 hb[12];
            auto ldh = [&](int s) { asm volatile("ld.relaxed.gpu.global.v2.u32 {%0, %1}, [%2];" : "=r"(hb[s].x), "=r"(hb[s].y) : "l"(hsrc + 32 * s) : "memory"); };
#pragma unroll
            for (int s = 0; s < 12; s++) ldh(s);
#pragma unroll 1
            for (int it = 0;; it++) {
                bool again = false;
#pragma unroll
                for (int s = 0; s < 12; s += 2) if (__any_sync(0xffffffffu, min(hb[s].x, hb[s + 1].x) == 0)) { ldh(s); ldh(s + 1); again = true; }
                if (!again) break;
                if (it > (1 << 16)) give_up();
            }
            if (warp == 0) TSTAMP(11);
            mbar_wait(bar_d + 8 * warp);
            if (warp == 9) TSTAMP(14);
            float ad[2][2][4];
#pragma unroll
            for (int i = 0; i < 4; i++) { ad[i >> 1][i & 1][0] = ad[i >> 1][i & 1][1] = ad[i >> 1][i & 1][2] = ad[i >> 1][i & 1][3] = 0.f; }
            const uint32_t wd = fresh(sb) + SF_WD + warp * 12288 + (r8 + 8 * (mi >> 1)) * 64 + (((mi & 1) ^ (r8 >> 1)) << 4);
#pragma unroll
            for (int s = 0; s < 12; s++) {
                uint32_t a[4], b[4];
                ldsm4t(a, wd + 1024 * s); ldsm4t(b, (wd ^ 32) + 1024 * s);
                mma_bf(ad[0][s & 1], a[0], a[1], a[2], a[3], hb[s].x, hb[s].y);
                mma_bf(ad[1][s & 1], b[0], b[1], b[2], b[3], hb[s].x, hb[s].y);
            }
            const uint32_t rd = sb + SF_RED + warp * 1152 + (72 * t + g) * 4;
#pragma unroll
            for (int i = 0; i < 8; i++) sts32(rd + (i >> 2) * 64 + (i & 1) * 144 + ((i >> 1) & 1) * 32, __float_as_uint(ad[i >> 2][0][i & 3] + ad[i >> 2][1][i & 3]));
            bar_sync(BAR_RED, 416);
            if (warp < 4) {
                const int tid = 32 * warp + lane;
                const uint32_t rs = fresh(sb + SF_RED) + (tid >> 4) * 144 + (tid & 15) * 8;
                const uint2 tk = lds64(fresh(s_tok) + (tid >> 4) * 8);
                float x = 0.f, y = 0.f;
#pragma unroll
                for (int w = 0; w < 12; w++) { const uint2 v = lds64(rs + w * 1152); x += __uint_as_float(v.x); y += __uint_as_float(v.y); }
                asm volatile("red.relaxed.gpu.global.add.noftz.bf16x2 [%0], %1;" :: "l"(p.out + (size_t)tk.x * DM + 32 * (f >> 1) + 2 * (tid & 15)),
                             "r"(pack_bf16(x * __uint_as_float(tk.y), y * __uint_as_float(tk.y))) : "memory");
            }
            if (warp == 0) { TSTAMP(15); TFLUSH(); }
            asm volatile("exit;"); __builtin_unreachable();
        }
    }
}

__device__ __forceinline__ void fetch_k(const uint4* src, uint64_t (&v)[6], uint32_t a, uint32_t b) {
    asm volatile("{ .reg .pred p; setp.eq.u32 p, %7, %8; @p ld.relaxed.gpu.global.v2.u64 {%0,%1}, [%6]; @p ld.relaxed.gpu.global.v2.u64 {%2,%3}, [%6 + 512]; @p ld.relaxed.gpu.global.v2.u64 {%4,%5}, [%6 + 1024]; }"
                 : "+l"(v[0]), "+l"(v[1]), "+l"(v[2]), "+l"(v[3]), "+l"(v[4]), "+l"(v[5]) : "l"(src), "r"(a), "r"(b));
}
__device__ __forceinline__ uint32_t mini_conv(const Params& p, uint32_t sb, int warp, int lane, int f, unsigned epoch) {
    const int g = lane >> 2, t = lane & 3, mi = lane >> 3, r8 = lane & 7;
    const uint32_t fb = sb + SF_MISC, kt = sb + (warp >= 12 ? SM_KT - 12 * 2112 : f < NW ? SM_KW + 2 * 2112 : SM_KW) + warp * 2112;
    const bool ism = f >= NW;
    const int ch0 = mini_ch0(f);
    uint32_t seq = 128, key;
    uint64_t v[6] = {};
    const uint4* src = p.s->kp + lane;
    auto hi = [&](int i) { return (uint32_t)(v[i] >> 32); };
    if (f >= (warp < 4 ? NW : NX)) {
    {
        const uint32_t c = 36 + (warp & 3) + 2 * (warp & 12), y = (uint32_t)((warp < 8 ? 0xa026802400000000ull : 0x2a2e00280080a22cull) >> ((8 * warp) & 48)) & 0xffff;
        seq = ism ? 0x101 * c - 0x400 : y + (warp & 1) * ((y >> 5) & 0x101);
        src += (ch0 + (seq & 31)) * 96;
    }
    if (warp >= 10 && (warp & 2)) {
        const int q = (warp & 1) + (warp < 12 ? 2 : 0), n0 = ism ? 2 * (q & 1) : q;
        const uint32_t ab = sb - (ism ? 49152 * (q >> 1) : 0);
        mbar_wait(fb + FB_MU);
        if (warp == 15) TSTAMP(16);
        uint32_t a = fresh(ab + SM_RAW) + n0 * 4096 + (8 * mi + 4 * (r8 & 1) + (r8 >> 1)) * 32 + ((r8 & 1) << 4), d = ab + SM_UT + g * MU_STRIDE + (8 + 8 * n0 + t) * 16;
        uint32_t z = ab + SM_UT + (4 * n0 + (mi >> 1)) * MU_STRIDE + (mi & 1) * MU_HALF + r8 * 16;
#pragma unroll 1
        for (int n = 0; n <= ism; n++, a += 4096, d += 128, z += 4 * MU_STRIDE) {
            uint32_t x[8][4];
#pragma unroll
            for (int i = 0; i < 8; i++) ldsm4t(x[i], (i & 4 ? a ^ 16 : a) + 1024 * (i & 3));
            sts128(z, 0, 0, 0, 0); sts128(z + 2 * MU_STRIDE, 0, 0, 0, 0);
#pragma unroll
            for (int i = 0; i < 8; i++) sts128(d + (i & 1) * MU_HALF + (i & 2) * 32 + (i & 4) * 2 * MU_STRIDE, x[i][0], x[i][1], x[i][2], x[i][3]);
        }
        __syncwarp();
        if (lane == 0) mbar_arrive(fb + FB_MT);
    }
    if (seq & 32) {
        mbar_wait(fb + FB_KDONE);
        fetch_k(src, v, 0, 0);
        if ((warp >> 1) == (ism ? 6 : 2)) { fetch_gates(p, warp & 1, lane, epoch, sb + SM_G + (lane & 1) * MU_HALF); __syncwarp(); if (lane == 0) mbar_arrive(fb + FB_MG); }
        mbar_wait(fb + FB_KEYS); mbar_wait(fb + FB_MT);
        sts128(kt + t * 16, 0, 0, 0, 0);
        if (warp == TW) TSTAMP(17);
    }
    }
    const uint32_t lo = (mi & 1) * MU_HALF + (8 + r8) * 16 + (mi >> 1) * 128;
#pragma unroll 1
    do {
        const int c = seq & 31;
        if (seq & 32) {
#pragma unroll 1
        for (int it = 0; !__all_sync(0xffffffffu, ((hi(1) ^ k_tag(epoch)) | (hi(3) ^ k_tag(epoch)) | (hi(5) ^ k_tag(epoch)) | ((uint32_t)v[5] & p.zero)) < 65536); it++) {
            fetch_k(src, v, 0, 0);
            if (it > (1 << 20)) give_up();
        }
        if (warp == TW) TSTAMP(seq >> 8 ? 7 : 10);
        const uint32_t w[12] = {(uint32_t)v[0], hi(0), (uint32_t)v[1], (uint32_t)v[2], hi(2), (uint32_t)v[3], (uint32_t)v[4], hi(4), 0, 0, 0, 0};
        k_tables<false>(fresh(kt), fresh(lane), w);
        }
        __syncwarp();
        if (seq & 128) ffn_work(p, sb, warp, fresh(lane), f, epoch);
        if (!(seq & 32)) return 0;
        const uint32_t ab = sb - 49152 * (c >> 4), kb = fresh(kt) + (16 + g - 2 * t) * 4, ub = fresh(ab + SM_UT + (c & 15) * MU_STRIDE) + lo;
        const uint32_t yd = ab + SM_Y + (c & 15) * 1056 + (c & 8) * 8 + lane * 16;
        uint32_t kp = kb, u1 = ub;
        if (warp == TW && !(seq >> 8)) TSTAMP(13);
        seq >>= 8;
        src += ((int)(seq & 31) - c) * 96;
#pragma unroll
        for (int i = 0; i < 6; i++) v[i] = 0;
        key = 0;
        float acc[6][4];
#pragma unroll
        for (int i = 0; i < 6; i++) { acc[i][0] = acc[i][1] = acc[i][2] = acc[i][3] = 0.f; }
        uint32_t a[4][4], b[2][2][4];
        auto lda = [&](int j, int o) { const uint32_t x = kp + 64 * o + 512 * j; a[j][2] = o ? a[j][1] ^ p.zero : lds32((kp ^ p.zero) + 512 * j - 32); a[j][0] = lds32(x); a[j][1] = lds32(x + 32); a[j][3] = a[j][0] ^ p.zero; };
        auto ldb = [&](int s, int o) { ldsm4(b[s][0], u1 - 16 * o); ldsm4(b[s][1], u1 + 256 - 16 * o); };
        ldb(0, 0);
#pragma unroll
        for (int j = 0; j < 4; j++) lda(j, 0);
#pragma unroll
        for (int s = 0; s < 8; s++) {
            if (s == FPOS) {
                const uint32_t e = seq | (__float_as_uint(acc[0][0]) & p.zero);
                fetch_k(src, v, e & 32, 32);
                if (KEYPF) asm volatile("{ .reg .pred p; setp.eq.u32 p, %2, 0; @p ld.relaxed.gpu.global.u32 %0, [%1]; }" : "+r"(key) : "l"(&p.s->sel[(ch0 >> 5) * 64 + r8]), "r"(e));
            }
            if (s < 7) ldb(~s & 1, s + 1);
#pragma unroll
            for (int i = 0; i < 4; i++) {
                const int j = (i >> 1) + 2 * (i & 1);
#pragma unroll
                for (int mu = 3 - j; mu >= 0; mu--) mma_bf(acc[j + mu + (j & 2)], a[j][0], a[j][1], a[j][2], a[j][3], b[s & 1][mu >> 1][2 * (mu & 1)], b[s & 1][mu >> 1][2 * (mu & 1) + 1]);
                if (s < 7) lda(j, s + 1);
            }
        }
        if (warp == TW && !seq) TSTAMP(14);
        mbar_wait(fb + FB_MG);
#pragma unroll
        for (int e = 0; e < 4; e++) { acc[2][e] += acc[4][e]; acc[3][e] += acc[5][e]; }
        uint32_t ug[4][4];
#pragma unroll
        for (int i = 0; i < 2; i++) { ldsm4t(ug[i], ub + 256 * i); ldsm4t(ug[2 + i], fresh(sb + SM_G) + lo + 256 * i); }
#pragma unroll
        for (int i = 0; i < 2; i++) {
            const uint32_t (&u)[4] = ug[i], (&gg)[4] = ug[2 + i];
            sts128(yd + 512 * i, gmix(gg[0], acc[2 * i][0], acc[2 * i][1], u[0]), gmix(gg[1], acc[2 * i][2], acc[2 * i][3], u[1]),
                   gmix(gg[2], acc[2 * i + 1][0], acc[2 * i + 1][1], u[2]), gmix(gg[3], acc[2 * i + 1][2], acc[2 * i + 1][3], u[3]));
        }
        __syncwarp();
        if (warp == TW) TSTAMP(18 + (seq != 0));
    } while (seq);
    if (warp >= 12) TSTAMP(12 + warp);
    return key;
}
__device__ __forceinline__ void mini_out(const Params& p, const CUtensorMap* maps, uint32_t sb, int warp, int lane, int f, unsigned epoch, uint32_t key) {
    const int g = lane >> 2, t = lane & 3, mi = lane >> 3, r8 = lane & 7;
    const uint32_t fb = sb + SF_MISC;
    const bool ism = f >= NW;
    const int ch0 = mini_ch0(f);
    const int k = ism ? warp >> 3 : 0;
    uint32_t first = 1;
    if (lane == 0) asm volatile("atom.shared.exch.b32 %0, [%1], 1;" : "=r"(first) : "r"(fb + FS_BM + 64 + 4 * k) : "memory");
    if (!__all_sync(0xffffffffu, first)) {
        if (elect()) prefetch_map(maps + 4);
        const int row = key_row(wait_sel(p, ch0 >> 5, r8, key_tag(epoch), key));
        if (row < 512) asm volatile("red.shared.or.b32 [%0], %1;" :: "r"(fb + FS_BM + (row >> 5) * 4), "r"(1u << (row & 31)) : "memory");
    }
    const int m = warp & 7, dr = 128 * (g >> 2) + 32 * (t >> 1) + 16 * (g & 1) + 8 * ((g >> 1) & 1);
    const uint32_t y = SM_Y + ((r8 >> 1) & 1) * 8512 + (2 * mi + (r8 & 1)) * 1056 + (2 * m + (r8 >> 2)) * 16;
    const uint32_t so = (g >> 1) * 256 + (t >> 1) * 64 + (g & 1) * 32 + (t & 1) * 16;
    bar_sync(BAR_M - k, ism ? 256 : NTHR);
#pragma unroll 1
    for (int h = ism ? 0 : warp >> 3;; h++) {
        const int r0 = 256 * h + 64 * (m & 1) + (m >> 1), row = r0 + dr;
        const uint32_t bm = lds32(fresh(fb) + FS_BM + (row >> 5) * 4) >> (row & 31), ab = fresh(sb - 49152 * k + 512 * h), stg = ab + SM_UT + 2048 * m + 512 * h;
        uint32_t x[2][4];
        ldsm4t(x[0], ab + y); ldsm4t(x[1], ab + y + 256);
        if (warp == 0 && x[0][0] != 0x12345) TSTAMP(28);
        if (__any_sync(0xffffffffu, bm & 0x11u)) {
#pragma unroll
            for (int i = 0; i < 2; i++) store_or_add(p.out + (size_t)(row + 4 * i) * DM + ch0 + 16 * k + 8 * (t & 1), x[i], bm & (1u << (4 * i)));
        } else {
#pragma unroll
            for (int i = 0; i < 2; i++) sts128(stg + so + 128 * i, x[i][0], x[i][1], x[i][2], x[i][3]);
            asm volatile("fence.proxy.async.shared::cta;" ::: "memory");
            __syncwarp();
            if (elect()) store_rows(maps + 4, stg, ch0 + 16 * k, r0);
        }
        if (h >= ism) break;
    }
    if (elect()) { asm volatile("cp.async.bulk.commit_group;" ::: "memory"); asm volatile("cp.async.bulk.wait_group.read 0;" ::: "memory"); }
    if (warp == 8) TSTAMP(11);
    if (warp == 0) { TSTAMP(15); TFLUSH(); }
}

constexpr int SMEM_BYTES = 232448;
static_assert(SF_MISC + 1152 <= 232192, "layout");

struct Maps { CUtensorMap m[6]; };

__global__ void __cluster_dims__(2, 1, 1) __launch_bounds__(NTHR, 1)
fused_kernel(const Params p, const __grid_constant__ Maps maps) {
    extern __shared__ __align__(1024) uint8_t smem_raw[];
    uint32_t q[8];
    {
        const int b = blockIdx.x, x = threadIdx.x, rc = 4 * b + max(b - 84, 0) - 288 + (x >> 6);
        const int cv = (b - NCONV) >> 31, ca = 8 * b + ((x >> 5) & 3), cb = 2 * rc - (rc & 3) + 4;
        const uint32_t ch = (ca & cv) | (cb & ~cv), o = NST * ch + 2 * ((x & 31) + ((x >> (cv & 2)) & 32));
        const bool c = x < (b < 84 ? 256 : 320);
        q[6] = ldg16_if(c, p.logdt + ch);
        q[2] = ldg32_if(c, p.Bre + o); q[3] = ldg32_if(c, p.Bim + o); q[4] = ldg32_if(c, p.Cre + o); q[5] = ldg32_if(c, p.Cim + o); q[0] = ldg32_if(c, p.Are + o); q[1] = ldg32_if(c, p.Aim + o);
        q[7] = ldg16_if(c, p.Dskip + ch);
    }
    const unsigned epoch = ld_rlx32(&p.s->epoch[blockIdx.x * 16 + (threadIdx.x >> 5)]);
    const uint32_t sb = __shfl_sync(0xffffffffu, smem_u32(smem_raw), 0);
    const int warp = __shfl_sync(0xffffffffu, threadIdx.x >> 5, 0), bid = __shfl_sync(0xffffffffu, blockIdx.x, 0);
    const int lane = __shfl_sync(0xffffffffu, threadIdx.x & 31, threadIdx.x);
    const bool conv = bid < NCONV;
    const int f = bid - NCONV;
    uint32_t w[12];
    if (warp < (f < 12 ? 8 : 10)) {
        const int half = conv ? warp >> 2 : warp & 1, pr = conv ? warp & 3 : warp >> 1;
        const int rc = 4 * f + max(f - 12, 0) + pr;
        const uint32_t stage = sb + (conv ? SC_KG : SF_KG) + warp * KG_STAGE;
        uint4* const kp = p.s->kp + (conv ? 8 * bid + pr : 2 * rc - (rc & 3) + 4) * 96 + lane;
        kgen(q, sb, half, stage, stage + (conv ? 4 : 1) * KG_STAGE, 1 + pr, lane, p.zero, w, [&] {
            sts128z_if(conv && lane < 20, sb + SC_KT + warp * KT_BYTES + lane * 16 + (lane < 4 ? 0 : lane < 14 ? 2048 : 2288));
            stg128(kp + 64 * half, 0, 0, 0, 0); stg128z_if(!half, kp + 32);
            stg128z_if((unsigned)f < NW && warp < 6, (uint4*)(p.s->h + ((lane >> 4) * 288 + 6 * f + warp) * 32) + (lane & 15));
            if (conv) asm volatile("barrier.cluster.arrive.relaxed.aligned;" ::: "memory");
        });
        if (conv) { conv_main(p, sb, warp, lane, bid, epoch, w); return; }
        {
            if (!half) publish_k(kp, w, epoch, true);
            if (warp == 0) TSTAMP(22);
            if (warp == 2) TSTAMP(23);
            bar_sync(0, NTHR);
            if (warp == 0 && lane == 0) mbar_arrive(sb + SF_MISC + FB_KDONE);
        }
    } else if (conv) {
        conv_aux(p, maps.m, sb, warp - 8, lane, bid, epoch);
        return;
    } else {
        ffn_front(p, maps.m, sb, warp, lane, f, epoch);
    }
    converged();
    next_epoch(p, epoch);
    if (warp >= 12 && f < NX) return;
    mini_out(p, maps.m, sb, warp, lane, f, epoch, mini_conv(p, sb, warp, __shfl_sync(0xffffffffu, lane, lane), f, epoch));
}

typedef CUresult (*EncodeFn)(CUtensorMap*, CUtensorMapDataType, cuuint32_t, void*, const cuuint64_t*, const cuuint64_t*, const cuuint32_t*, const cuuint32_t*,
                             CUtensorMapInterleave, CUtensorMapSwizzle, CUtensorMapL2promotion, CUtensorMapFloatOOBfill);

void make_map(EncodeFn fn, CUtensorMap* m, const void* base, int rank, const cuuint64_t* dims, const cuuint64_t* strides, const cuuint32_t* box, CUtensorMapSwizzle sw) {
    const cuuint32_t es[5] = {1, 1, 1, 1, 1};
    fn(m, CU_TENSOR_MAP_DATA_TYPE_BFLOAT16, rank, (void*)base, dims, strides, box, es, CU_TENSOR_MAP_INTERLEAVE_NONE, sw,
       CU_TENSOR_MAP_L2_PROMOTION_NONE, CU_TENSOR_MAP_FLOAT_OOB_FILL_NONE);
}

}

extern "C" void kernel_launch(void* const* d_in, const int* in_sizes, int n_in, void* d_out, int out_size) {
    (void)in_sizes; (void)n_in; (void)out_size;
    static EncodeFn fn = nullptr;
    static void* scratch = nullptr;
    if (!fn) {
        void* ptr = nullptr; cudaDriverEntryPointQueryResult qr;
        cudaGetDriverEntryPoint("cuTensorMapEncodeTiled", &ptr, cudaEnableDefault, &qr);
        fn = (EncodeFn)ptr;
        cudaGetSymbolAddress(&scratch, g_scratch);
        cudaFuncSetAttribute(fused_kernel, cudaFuncAttributeMaxDynamicSharedMemorySize, SMEM_BYTES);
    }
    typedef const __nv_bfloat16* bp;
    Params p;
    p.u = (bp)d_in[0]; p.Are = (bp)d_in[1]; p.Aim = (bp)d_in[2]; p.Bre = (bp)d_in[3]; p.Bim = (bp)d_in[4]; p.Cre = (bp)d_in[5]; p.Cim = (bp)d_in[6];
    p.logdt = (bp)d_in[7]; p.Dskip = (bp)d_in[8]; p.wr = (bp)d_in[10]; p.gatew = (bp)d_in[14];
    p.out = (__nv_bfloat16*)d_out; p.s = (Scratch*)scratch; p.zero = 0;
    Maps maps;
    {
        const cuuint64_t dims[4] = {DM, 4, 16, 32}, strides[3] = {16 * DM * 2, DM * 2, 64 * DM * 2};
        const cuuint32_t box[4] = {16, 4, 16, 2};
        make_map(fn, &maps.m[0], d_in[0], 4, dims, strides, box, CU_TENSOR_MAP_SWIZZLE_32B);
        const cuuint32_t box2[4] = {16, 4, 16, 8};
        make_map(fn, &maps.m[5], d_in[0], 4, dims, strides, box2, CU_TENSOR_MAP_SWIZZLE_32B);
    }
    for (int i = 0; i < 2; i++) {
        const cuuint64_t dims[3] = {32, DM, FF / 32}, strides[2] = {FF * 2, 64};
        const cuuint32_t box[3] = {32, 64, 3};
        make_map(fn, &maps.m[1 + i], d_in[11 + i], 3, dims, strides, box, CU_TENSOR_MAP_SWIZZLE_64B);
    }
    {
        const cuuint64_t dims[2] = {DM, FF}, strides[1] = {DM * 2};
        const cuuint32_t box[2] = {32, 192};
        make_map(fn, &maps.m[3], d_in[13], 2, dims, strides, box, CU_TENSOR_MAP_SWIZZLE_64B);
    }
    {
        const cuuint64_t dims[5] = {DM, 4, 4, 2, L_SEQ}, strides[4] = {16 * DM * 2, 4 * DM * 2, 128 * DM * 2, DM * 2};
        const cuuint32_t box[5] = {16, 4, 4, 2, 1};
        make_map(fn, &maps.m[4], d_out, 5, dims, strides, box, CU_TENSOR_MAP_SWIZZLE_NONE);
    }
    fused_kernel<<<NCTA, NTHR, SMEM_BYTES>>>(p, maps);
}
```

```cpp
#include <cuda_runtime.h>
#include <cuda_bf16.h>
#include <cuda_fp16.h>
#include <cuda.h>
#include <stdint.h>
#include <type_traits>

#define RESUME 300
#define PUBIT 1
#define FPOS 2
#define PUBY 0
#define KEYPF 1
#define NACC 6
#define EFETCH 0
#define GW 7
#define TW 12
#define MDELAY 2000
#define UDELAY 0
#define RDELAY 900
#define WDELAY 2000
#define WGAP 290
#define NPRE 7
#define DGAP 260

namespace {

constexpr int DM = 576, NST = 128, FF = 4608, L_SEQ = 2048;
constexpr int NCONV = 72, NX = 36, NW = 48, NCTA = 132, NTHR = 512;

struct __align__(128) Scratch {
    unsigned epoch[NCTA * 16];
    uint4 keys[16 * 128];
    uint32_t sel[18 * 64];
    uint16_t gate[L_SEQ];
    uint2 h[2 * 288 * 32];
    uint4 kp[DM * 96];
};
__device__ Scratch g_scratch;
#define TFLUSH()
#define TSTAMP(i)

struct Params {
    const __nv_bfloat16 *Are, *Aim, *Bre, *Bim, *Cre, *Cim, *logdt, *Dskip, *u, *wr, *gatew;
    __nv_bfloat16* out;
    Scratch* s;
    uint32_t zero;
};

__device__ __forceinline__ void give_up() { asm volatile("trap; exit;"); __builtin_unreachable(); }
__device__ __forceinline__ void converged() { __syncwarp(); asm volatile("{ .reg .b32 t; mov.b32 t, 0; movmatrix.sync.aligned.m8n8.trans.b16 t, t; }" ::: "memory"); }
__device__ __forceinline__ bool elect() { uint32_t r; asm volatile("{ .reg .pred p; elect.sync _|p, 0xffffffff; selp.u32 %0, 1, 0, p; }" : "=r"(r)); return r; }
__device__ __forceinline__ uint32_t smem_u32(const void* p) { return (uint32_t)__cvta_generic_to_shared(p); }
__device__ __forceinline__ uint32_t pack_bf16(float lo, float hi) { uint32_t r; asm("cvt.rn.bf16x2.f32 %0, %1, %2;" : "=r"(r) : "f"(hi), "f"(lo)); return r; }
__device__ __forceinline__ uint32_t pack_f16(float lo, float hi) { uint32_t r; asm("cvt.rn.f16x2.f32 %0, %1, %2;" : "=r"(r) : "f"(hi), "f"(lo)); return r; }
__device__ __forceinline__ float bf_lo(uint32_t w) { return __uint_as_float(w << 16); }
__device__ __forceinline__ float bf_hi(uint32_t w) { return __uint_as_float(w & 0xffff0000u); }
__device__ __forceinline__ float rbf(float x) { return bf_lo(pack_bf16(x, 0.f)); }
__device__ __forceinline__ uint32_t badd2(uint32_t a, uint32_t b) { uint32_t r; asm("add.rn.bf16x2 %0, %1, %2;" : "=r"(r) : "r"(a), "r"(b)); return r; }
__device__ __forceinline__ uint32_t bsub2(uint32_t a, uint32_t b) { uint32_t r; asm("sub.rn.bf16x2 %0, %1, %2;" : "=r"(r) : "r"(a), "r"(b)); return r; }
__device__ __forceinline__ uint32_t gmix(uint32_t ng, float ny0, float ny1, uint32_t u) {
    uint32_t r; asm("{ .reg .b32 t; fma.rn.bf16x2 t, %1, %3, %3; fma.rn.bf16x2 %0, %1, %2, t; }" : "=r"(r) : "r"(ng), "r"(pack_bf16(ny0, ny1)), "r"(u)); return r;
}
__device__ __forceinline__ void mma_bf(float (&c)[4], uint32_t a0, uint32_t a1, uint32_t a2, uint32_t a3, uint32_t b0, uint32_t b1) {
    asm("mma.sync.aligned.m16n8k16.row.col.f32.bf16.bf16.f32 {%0,%1,%2,%3}, {%4,%5,%6,%7}, {%8,%9}, {%0,%1,%2,%3};"
        : "+f"(c[0]), "+f"(c[1]), "+f"(c[2]), "+f"(c[3]) : "r"(a0), "r"(a1), "r"(a2), "r"(a3), "r"(b0), "r"(b1));
}
__device__ __forceinline__ void mma_bf8(float (&c)[4], uint32_t a0, uint32_t a1, uint32_t b0) {
    asm("mma.sync.aligned.m16n8k8.row.col.f32.bf16.bf16.f32 {%0,%1,%2,%3}, {%4,%5}, {%6}, {%0,%1,%2,%3};"
        : "+f"(c[0]), "+f"(c[1]), "+f"(c[2]), "+f"(c[3]) : "r"(a0), "r"(a1), "r"(b0));
}
__device__ __forceinline__ void mma_h(float (&c)[4], uint32_t a0, uint32_t a1, uint32_t a2, uint32_t a3, uint32_t b0, uint32_t b1) {
    asm("mma.sync.aligned.m16n8k16.row.col.f32.f16.f16.f32 {%0,%1,%2,%3}, {%4,%5,%6,%7}, {%8,%9}, {%0,%1,%2,%3};"
        : "+f"(c[0]), "+f"(c[1]), "+f"(c[2]), "+f"(c[3]) : "r"(a0), "r"(a1), "r"(a2), "r"(a3), "r"(b0), "r"(b1));
}
__device__ __forceinline__ uint32_t fresh(uint32_t a) { asm volatile("" : "+r"(a) :: "memory"); return a; }
__device__ __forceinline__ uint32_t lds16(uint32_t a) { uint32_t v; asm("ld.shared.u16 %0, [%1];" : "=r"(v) : "r"(a)); return v; }
__device__ __forceinline__ uint32_t lds32(uint32_t a) { uint32_t v; asm("ld.shared.u32 %0, [%1];" : "=r"(v) : "r"(a)); return v; }
__device__ __forceinline__ uint2 lds64(uint32_t a) { uint2 v; asm("ld.shared.v2.u32 {%0,%1}, [%2];" : "=r"(v.x), "=r"(v.y) : "r"(a)); return v; }
__device__ __forceinline__ uint4 lds128(uint32_t a) { uint4 v; asm("ld.shared.v4.u32 {%0,%1,%2,%3}, [%4];" : "=r"(v.x), "=r"(v.y), "=r"(v.z), "=r"(v.w) : "r"(a)); return v; }
__device__ __forceinline__ uint4 lds128v(uint32_t a) { uint4 v; asm volatile("ld.shared.v4.u32 {%0,%1,%2,%3}, [%4];" : "=r"(v.x), "=r"(v.y), "=r"(v.z), "=r"(v.w) : "r"(a) : "memory"); return v; }
__device__ __forceinline__ void ldsm4(uint32_t (&r)[4], uint32_t a) {
    asm("ldmatrix.sync.aligned.m8n8.x4.shared.b16 {%0,%1,%2,%3}, [%4];" : "=r"(r[0]), "=r"(r[1]), "=r"(r[2]), "=r"(r[3]) : "r"(a));
}
__device__ __forceinline__ void ldsm4t(uint32_t (&r)[4], uint32_t a) {
    asm("ldmatrix.sync.aligned.m8n8.x4.trans.shared.b16 {%0,%1,%2,%3}, [%4];" : "=r"(r[0]), "=r"(r[1]), "=r"(r[2]), "=r"(r[3]) : "r"(a));
}
__device__ __forceinline__ void sts16(uint32_t a, uint32_t v) { asm volatile("st.shared.u16 [%0], %1;" :: "r"(a), "h"((unsigned short)v) : "memory"); }
__device__ __forceinline__ void sts32(uint32_t a, uint32_t v) { asm volatile("st.shared.u32 [%0], %1;" :: "r"(a), "r"(v) : "memory"); }
__device__ __forceinline__ void sts64(uint32_t a, uint32_t x, uint32_t y) { asm volatile("st.shared.v2.u32 [%0], {%1,%2};" :: "r"(a), "r"(x), "r"(y) : "memory"); }
__device__ __forceinline__ void sts128(uint32_t a, uint32_t x, uint32_t y, uint32_t z, uint32_t w) {
    asm volatile("st.shared.v4.u32 [%0], {%1,%2,%3,%4};" :: "r"(a), "r"(x), "r"(y), "r"(z), "r"(w) : "memory");
}
__device__ __forceinline__ void st_async128(uint32_t a, uint32_t x, uint32_t y, uint32_t z, uint32_t w, uint32_t bar) {
    asm volatile("st.async.weak.shared::cluster.mbarrier::complete_tx::bytes.v4.b32 [%0], {%1,%2,%3,%4}, [%5];" :: "r"(a), "r"(x), "r"(y), "r"(z), "r"(w), "r"(bar) : "memory");
}
__device__ __forceinline__ void mbar_init(uint32_t b, uint32_t cnt) { asm volatile("mbarrier.init.shared::cta.b64 [%0], %1;" :: "r"(b), "r"(cnt) : "memory"); }
__device__ __forceinline__ void mbar_fence() { asm volatile("fence.mbarrier_init.release.cluster;" ::: "memory"); }
__device__ __forceinline__ void mbar_expect(uint32_t b, uint32_t bytes) { asm volatile("mbarrier.arrive.expect_tx.shared::cta.b64 _, [%0], %1;" :: "r"(b), "r"(bytes) : "memory"); }
__device__ __forceinline__ void mbar_arrive(uint32_t b) { asm volatile("mbarrier.arrive.shared::cta.b64 _, [%0];" :: "r"(b) : "memory"); }
#define CHINT ""
#define HINT ""
__device__ __forceinline__ void mbar_wait(uint32_t b, uint32_t parity = 0) {
    asm volatile("{ .reg .pred p; .reg .u32 n; mov.u32 n, 0;\n"
                 "LW: mbarrier.try_wait.parity.shared::cta.b64 p, [%0], %1" HINT "; @p bra LD; add.u32 n, n, 1; setp.lt.u32 p, n, 65536; @p bra LW; trap;\n"
                 "LD: }" :: "r"(b), "r"(parity) : "memory");
}
__device__ __forceinline__ void mbar_wait_cluster(uint32_t b) {
    asm volatile("{ .reg .pred p; .reg .u32 n; mov.u32 n, 0;\n"
                 "LW: mbarrier.try_wait.parity.acquire.cluster.shared::cta.b64 p, [%0], 0" CHINT "; @p bra LD; add.u32 n, n, 1; setp.lt.u32 p, n, 65536; @p bra LW; trap;\n"
                 "LD: }" :: "r"(b) : "memory");
}
__device__ __forceinline__ void tma2d(uint32_t dst, const CUtensorMap* m, int c0, int c1, uint32_t bar) {
    asm volatile("cp.async.bulk.tensor.2d.shared::cluster.global.mbarrier::complete_tx::bytes [%0], [%1, {%3, %4}], [%2];"
                 :: "r"(dst), "l"(m), "r"(bar), "r"(c0), "r"(c1) : "memory");
}
__device__ __forceinline__ void tma3d(uint32_t dst, const CUtensorMap* m, int c0, int c1, int c2, uint32_t bar) {
    asm volatile("cp.async.bulk.tensor.3d.shared::cluster.global.mbarrier::complete_tx::bytes [%0], [%1, {%3, %4, %5}], [%2];"
                 :: "r"(dst), "l"(m), "r"(bar), "r"(c0), "r"(c1), "r"(c2) : "memory");
}
__device__ __forceinline__ void tma4d(uint32_t dst, const CUtensorMap* m, int c0, int c1, int c2, int c3, uint32_t bar) {
    asm volatile("cp.async.bulk.tensor.4d.shared::cluster.global.mbarrier::complete_tx::bytes [%0], [%1, {%3, %4, %5, %6}], [%2];"
                 :: "r"(dst), "l"(m), "r"(bar), "r"(c0), "r"(c1), "r"(c2), "r"(c3) : "memory");
}
__device__ __forceinline__ void bulk_g2s(uint32_t dst, const void* src, uint32_t bytes, uint32_t bar) {
    asm volatile("cp.async.bulk.shared::cluster.global.mbarrier::complete_tx::bytes [%0], [%1], %2, [%3];"
                 :: "r"(dst), "l"(src), "r"(bytes), "r"(bar) : "memory");
}
__device__ __forceinline__ uint32_t mapa(uint32_t a, uint32_t rank) { uint32_t r; asm("mapa.shared::cluster.u32 %0, %1, %2;" : "=r"(r) : "r"(a), "r"(rank)); return r; }
__device__ __forceinline__ void prefetch_map(const CUtensorMap* m) { asm volatile("prefetch.tensormap [%0];" :: "l"(m) : "memory"); }
__device__ __forceinline__ void bar_sync(int id, int n) { asm volatile("bar.sync %0, %1;" :: "r"(id), "r"(n) : "memory"); }
__device__ __forceinline__ void bar_arrive(int id, int n) { asm volatile("bar.arrive %0, %1;" :: "r"(id), "r"(n) : "memory"); }
__device__ __forceinline__ uint32_t ldg16_if(bool c, const void* p) { uint32_t v; asm volatile("{ .reg .pred p; setp.ne.u32 p, %2, 0; @p ld.global.nc.u16 %0, [%1]; }" : "=r"(v) : "l"(p), "r"((uint32_t)c)); return v; }
__device__ __forceinline__ uint32_t ldg32_if(bool c, const void* p) { uint32_t v; asm volatile("{ .reg .pred p; setp.ne.u32 p, %2, 0; @p ld.global.nc.u32 %0, [%1]; }" : "=r"(v) : "l"(p), "r"((uint32_t)c)); return v; }
__device__ __forceinline__ uint32_t ld_rlx32(const void* p) { uint32_t v; asm volatile("ld.relaxed.gpu.global.u32 %0, [%1];" : "=r"(v) : "l"(p) : "memory"); return v; }
__device__ __forceinline__ uint4 ld_rlx128(const void* p) {
    uint4 v; asm volatile("ld.relaxed.gpu.global.v4.u32 {%0,%1,%2,%3}, [%4];" : "=r"(v.x), "=r"(v.y), "=r"(v.z), "=r"(v.w) : "l"(p) : "memory"); return v;
}
__device__ __forceinline__ void st_rlx32(void* p, uint32_t v) { asm volatile("st.relaxed.gpu.global.u32 [%0], %1;" :: "l"(p), "r"(v) : "memory"); }
__device__ __forceinline__ void stg128(void* p, uint32_t x, uint32_t y, uint32_t z, uint32_t w) {
    asm volatile("st.global.v4.u32 [%0], {%1,%2,%3,%4};" :: "l"(p), "r"(x), "r"(y), "r"(z), "r"(w) : "memory");
}
__device__ __forceinline__ void next_epoch(const Params& p, unsigned e) { if ((threadIdx.x & 31) == 0) p.s->epoch[blockIdx.x * 16 + (threadIdx.x >> 5)] = e + 1; }
__device__ __forceinline__ void sts128z_if(bool c, uint32_t a) { asm volatile("{ .reg .pred p; setp.ne.u32 p, %1, 0; @p st.shared.v4.u32 [%0], {%2,%2,%2,%2}; }" :: "r"(a), "r"((uint32_t)c), "r"(0) : "memory"); }
__device__ __forceinline__ void stg128z_if(bool c, void* a) { asm volatile("{ .reg .pred p; setp.ne.u32 p, %1, 0; @p st.global.v4.u32 [%0], {%2,%2,%2,%2}; }" :: "l"(a), "r"((uint32_t)c), "r"(0) : "memory"); }
__device__ __forceinline__ unsigned clock32() { unsigned c; asm volatile("mov.u32 %0, %clock;" : "=r"(c) :: "memory"); return c; }
__device__ __forceinline__ void until(unsigned t0, int c) { while ((int)(clock32() - t0) < c) { } }
__device__ __forceinline__ float sigmoidf_(float x) { return __fdividef(1.0f, 1.0f + __expf(-x)); }
__device__ __forceinline__ uint32_t key_tag(unsigned epoch) { return ((epoch & 15u) | 16u) << 11; }
__device__ __forceinline__ int key_row(uint32_t key) { return 2047 - (int)(key & 2047u); }
__device__ __forceinline__ uint32_t wait_sel(const Params& p, int s32, int r8, uint32_t tag, uint32_t k = 0) {
#pragma unroll 1
    for (int it = 0; !__all_sync(0xffffffffu, (k & 0xf800u) == tag); it++) {
        k = ld_rlx32(&p.s->sel[s32 * 64 + r8]);
        if (it > (1 << 20)) give_up();
    }
    return k;
}

struct cplx { float re, im; };
__device__ __forceinline__ cplx csq(cplx a) { cplx r; r.re = a.re * a.re - a.im * a.im; r.im = (a.re * a.im) * 2.f; return r; }
__device__ __forceinline__ cplx cexpk(float ar, float ai, float k) {
    float mag, s, c;
    asm("ex2.approx.ftz.f32 %0, %1;" : "=f"(mag) : "f"(ar * (k * 1.4426950408889634f)));
    const float r = ai * k;
    asm("sin.approx.ftz.f32 %0, %1;" : "=f"(s) : "f"(r));
    asm("cos.approx.ftz.f32 %0, %1;" : "=f"(c) : "f"(r));
    cplx o; o.re = mag * c; o.im = mag * s; return o;
}
struct h2c { uint32_t re, im; };
__device__ __forceinline__ h2c cmul_cd(h2c v, __half2 c, __half2 d) {
    const __half2 r = *(const __half2*)&v.re, i = *(const __half2*)&v.im;
    const __half2 x = __hfma2(__hneg2(i), d, __hmul2(r, c)), y = __hfma2(i, c, __hmul2(r, d));
    h2c o; o.re = *(const uint32_t*)&x; o.im = *(const uint32_t*)&y; return o;
}
__device__ __forceinline__ h2c cmul_s(h2c v, uint32_t s) { const __half2 h = *(const __half2*)&s; return cmul_cd(v, __low2half2(h), __high2half2(h)); }
__device__ __forceinline__ h2c cmul_sc(h2c v, uint32_t s) {
    const __half2 h = *(const __half2*)&s, c = __low2half2(h), d = __high2half2(h), r = *(const __half2*)&v.re, i = *(const __half2*)&v.im;
    const __half2 x = __hfma2(i, d, __hmul2(r, c)), y = __hfma2(__hneg2(r), d, __hmul2(i, c));
    h2c o; o.re = *(const uint32_t*)&x; o.im = *(const uint32_t*)&y; return o;
}
__device__ __forceinline__ h2c cmul_vc(h2c v, uint32_t s) {
    const __half2 h = *(const __half2*)&s, c = __low2half2(h), d = __high2half2(h), r = *(const __half2*)&v.re, i = *(const __half2*)&v.im;
    const __half2 x = __hfma2(i, d, __hmul2(r, c)), y = __hfma2(__hneg2(i), c, __hmul2(r, d));
    h2c o; o.re = *(const uint32_t*)&x; o.im = *(const uint32_t*)&y; return o;
}

constexpr int UT_HALF = 2240, UT_STRIDE = 4448;
constexpr int KT_T = 542, KT_C = 552, KT_D = 645, KT_BYTES = 720 * 4;
constexpr int VC_OFF = 80, VE_BASE = 1616;
constexpr int V_STRIDE = (1616 + 1024) * 4 + 80;
constexpr int KG_STAGE = 5248;
constexpr int Y_CS = 2080, Y_RS = 8 * Y_CS + 64;

constexpr int SC_RT = 0;
constexpr int SC_UT = 33408;
constexpr int SC_ST = SC_UT + 8 * UT_STRIDE;
constexpr int SC_KT = SC_ST + 8 * UT_STRIDE;
constexpr int SC_GT = SC_KT + 8 * KT_BYTES;
constexpr int SC_V = SC_GT + UT_STRIDE;
constexpr int SC_KG = SC_V + 4 * V_STRIDE;
constexpr int SC_MISC = SC_V + 8 * V_STRIDE;
static_assert(V_STRIDE % 128 == 16 && 8 * KG_STAGE <= 4 * V_STRIDE && 2 * Y_RS <= SC_UT && SC_UT % 128 == 0 && SC_ST % 128 == 0, "layout");
static_assert(SC_MISC % 16 == 0 && SC_MISC + 512 <= 232192, "layout");

__device__ __forceinline__ void window_task(uint32_t src, uint32_t d0, uint32_t d1, bool withE) {
    float S[35];
    {
        uint32_t w[20];
#pragma unroll
        for (int i = 0; i < 5; i++) {
            const uint4 v = lds128(src + ((i & 1) ? 0 : UT_HALF) + ((i + 1) >> 1) * 16);
            w[4 * i] = v.x; w[4 * i + 1] = v.y; w[4 * i + 2] = v.z; w[4 * i + 3] = v.w;
        }
        float s = 0.f; S[2] = 0.f;
#pragma unroll
        for (int i = 3; i < 26; i++) { s += (i & 1) ? bf_hi(w[i >> 1]) : bf_lo(w[i >> 1]); S[i] = s; }
#pragma unroll
        for (int i = 0; i < 8; i += 2)
            sts128((i & 4 ? d1 : d0) + (VC_OFF - 16) * 4 + 8 * (i & 2), pack_bf16(S[10 + i] - S[5 + i], S[5 + i] - S[2 + i]), pack_bf16(S[18 + i] - S[13 + i], S[13 + i] - S[10 + i]),
                   pack_bf16(S[11 + i] - S[6 + i], S[6 + i] - S[3 + i]), pack_bf16(S[19 + i] - S[14 + i], S[14 + i] - S[11 + i]));
        if (withE) {
#pragma unroll
            for (int i = 26; i < 35; i++) { s += (i & 1) ? bf_hi(w[i >> 1]) : bf_lo(w[i >> 1]); S[i] = s; }
#pragma unroll
            for (int i = 0; i < 8; i += 2)
                sts128((i & 4 ? d1 : d0) + VE_BASE * 4 + 8 * (i & 2), pack_bf16(S[19 + i] - S[12 + i], S[12 + i] - S[3 + i]), pack_bf16(S[27 + i] - S[20 + i], S[20 + i] - S[11 + i]),
                       pack_bf16(S[20 + i] - S[13 + i], S[13 + i] - S[4 + i]), pack_bf16(S[28 + i] - S[21 + i], S[21 + i] - S[12 + i]));
        }
    }
}

template <class F>
__device__ __forceinline__ void kgen(const uint32_t (&q)[8], uint32_t sb, int half, uint32_t stage, uint32_t pstage, int barid, int lane, uint32_t zero, uint32_t (&w)[12], F shadow) {
    const int t = lane & 3, mi = lane >> 3, r8 = lane & 7;
    {
        const uint32_t pAr = q[0], pAi = q[1], pBr = q[2], pBi = q[3], pCr = q[4], pCi = q[5], pDt = q[6], pD = q[7];
        const uint32_t wb = fresh(stage + lane * 16), za = fresh(stage + 5120 + ((lane >> 1) & 3) * 16 + mi * 4 + (lane & 1) * 2), zr = fresh(stage + 5120 + t * 16);
        const uint32_t oA = fresh(stage + (mi & 1) * 1024 + (mi >> 1) * 512 + r8 * 16), oB = fresh(stage + 2048 + mi * 512 + r8 * 16), oC = fresh(stage + 4096 + (mi & 1) * 512 + (mi >> 1) * 128 + r8 * 16);
        float acc[6][4];
#pragma unroll
        for (int a = 0; a < 6; a++) { acc[a][0] = acc[a][1] = acc[a][2] = acc[a][3] = 0.f; asm volatile("" : "+f"(acc[a][0]), "+f"(acc[a][1]), "+f"(acc[a][2]), "+f"(acc[a][3])); }
        shadow();
        sts32(zr, clock32());
        const float dt = rbf(__expf(bf_lo(pDt)));
        float ar = dt * bf_lo(pAr), ai = dt * bf_lo(pAi), ar1 = dt * bf_hi(pAr), ai1 = dt * bf_hi(pAi);
        float wr, wi, wr1, wi1;
        { const float br = dt * bf_lo(pBr), bi = dt * bf_lo(pBi), cr = bf_lo(pCr), ci = bf_lo(pCi); wr = cr * br - ci * bi; wi = cr * bi + ci * br; }
        { const float br = dt * bf_hi(pBr), bi = dt * bf_hi(pBi), cr = bf_hi(pCr), ci = bf_hi(pCi); wr1 = cr * br - ci * bi; wi1 = cr * bi + ci * br; }
        const uint32_t ex = max(__reduce_max_sync(0xffffffffu, __float_as_uint(fmaxf(fmaxf(fabsf(wr), fabsf(wi)), fmaxf(fabsf(wr1), fabsf(wi1))))) >> 23, 14u);
        const float scl = __uint_as_float((267u - ex) << 23);
        uint32_t W = pack_f16(wr * scl, wi * -scl);
        const uint32_t W1 = pack_f16(wr1 * scl, wi1 * -scl);
        if (threadIdx.x < 32) TSTAMP(20);

#pragma unroll 1
        for (int r = 0; r < 2; r++) {
            const cplx z1 = cexpk(ar, ai, 1.f), z64 = cexpk(ar, ai, 64.f);
            const cplx z2 = csq(z1), z4 = csq(z2), z8 = csq(z4), z16 = csq(z8), z32 = csq(z16);
            const cplx z128 = csq(z64), z256 = csq(z128), z512 = csq(z256);
            auto put = [&](int grp, h2c a, h2c b, h2c c, h2c d) { sts128(wb + grp * 1024, a.re, b.re, c.re, d.re); sts128(wb + grp * 1024 + 512, a.im, b.im, c.im, d.im); };
            {
                const uint32_t s4 = pack_f16(z4.re, z4.im), s256 = pack_f16(z256.re, z256.im), s512 = pack_f16(z512.re, z512.im);
                auto mix = [](h2c a, h2c b, uint32_t sel) { return h2c{__byte_perm(a.re, b.re, sel), __byte_perm(a.im, b.im, sel)}; };
                const h2c c10 = cmul_vc(h2c{pack_f16(z1.re, 1.f), pack_f16(z1.im, 0.f)}, W), c32 = cmul_sc(c10, pack_f16(z2.re, z2.im)), c54 = cmul_sc(c10, s4);
                put(2, c10, c32, c54, cmul_sc(c32, s4));
                const h2c d20 = cmul_sc(mix(c32, c10, 0x7632), s256), e04 = cmul_sc(mix(c10, c54, 0x7632), s512), f04 = cmul_sc(e04, s256);
                put(3, d20, cmul_sc(d20, s4), e04, f04);
                const h2c ef = mix(e04, f04, 0x5410), gh = cmul_sc(ef, s512), g8 = cmul_sc(gh, pack_f16(z8.re, z8.im));
                put(4, g8, cmul_sc(g8, s512), gh, ef);
            }
            {
                const uint32_t s32 = pack_f16(z32.re, z32.im), s64 = pack_f16(z64.re, z64.im), s128 = pack_f16(z128.re, z128.im);
                const h2c p0 = {pack_f16(1.f, z8.re), pack_f16(0.f, z8.im)}, p1 = cmul_s(p0, pack_f16(z16.re, z16.im)), p2 = cmul_s(p0, s32), p3 = cmul_s(p1, s32);
                put(0, p0, p1, p2, p3);
                put(1, cmul_s(p0, s64), cmul_s(p1, s64), cmul_s(p2, s64), cmul_s(p3, s64));
                sts16(za, s128); sts16(za + 64, s128 >> 16);
            }
            __syncwarp();
            {
                const uint32_t aA = fresh(oA), aB = fresh(oB), aC = fresh(oC), aZ = fresh(zr);
                const uint4 zc = lds128(aZ), zd = lds128(aZ + 64);
                const uint32_t zcs[4] = {zc.x, zc.y, zc.z, zc.w}, zds[4] = {zd.x, zd.y, zd.z, zd.w};
                uint32_t c[4];
#pragma unroll
                for (int k = 0; k < 4; k++) {
                    uint32_t a[4], b[4];
                    ldsm4t(a, aA + 128 * k); ldsm4t(b, aB + 128 * k);
                    if (!(k & 1)) ldsm4t(c, aC + 128 * k);
                    const h2c x = cmul_cd(h2c{a[0], a[2]}, *(const __half2*)&zcs[k], *(const __half2*)&zds[k]), y = cmul_cd(h2c{a[1], a[3]}, *(const __half2*)&zcs[k], *(const __half2*)&zds[k]);
                    mma_h(acc[0], a[0], a[1], a[2], a[3], b[0], b[1]);
                    mma_h(acc[1], a[0], a[1], a[2], a[3], b[2], b[3]);
                    mma_h(acc[2], a[0], a[1], a[2], a[3], c[2 * (k & 1)], c[2 * (k & 1) + 1]);
                    mma_h(acc[3], x.re, y.re, x.im, y.im, b[0], b[1]);
                    mma_h(acc[4], x.re, y.re, x.im, y.im, b[2], b[3]);
                    mma_h(acc[5], x.re, y.re, x.im, y.im, c[2 * (k & 1)], c[2 * (k & 1) + 1]);
                }
                asm volatile("" :: "f"(acc[0][0]), "f"(acc[1][0]), "f"(acc[2][0]), "f"(acc[3][0]), "f"(acc[4][0]), "f"(acc[5][0]) : "memory");
            }
            __syncwarp();
            ar = ar1; ai = ai1; W = W1;
        }
        if (threadIdx.x < 32) TSTAMP(21);
        const float i0 = __uint_as_float((ex + 243u) << 23);
        if (half) {
#pragma unroll
            for (int a = 0; a < 6; a++) sts128(wb + a * 512, __float_as_uint(acc[a][0]), __float_as_uint(acc[a][1]), __float_as_uint(acc[a][2]), __float_as_uint(acc[a][3]));
            sts32(stage + 3072, __float_as_uint(i0));
            bar_arrive(barid, 64);
        } else {
#pragma unroll
            for (int a = 0; a < 6; a++) { acc[a][0] *= i0; acc[a][1] *= i0; acc[a][2] *= i0; acc[a][3] *= i0; }
            if (lane == 0) acc[0][1] -= bf_lo(pD);
            sts32(zr, clock32());
            bar_sync(barid, 64);
            const uint32_t src = fresh(pstage);
            const float i1 = __uint_as_float(lds32(src + 3072));
#pragma unroll
            for (int a = 0; a < 6; a++) {
                const uint4 y = lds128(src + lane * 16 + a * 512);
                w[4 * (a % 3) + 2 * (a / 3)] = pack_bf16(fmaf(__uint_as_float(y.x), i1, acc[a][0]), fmaf(__uint_as_float(y.y), i1, acc[a][1]));
                w[4 * (a % 3) + 2 * (a / 3) + 1] = pack_bf16(fmaf(__uint_as_float(y.z), i1, acc[a][2]), fmaf(__uint_as_float(y.w), i1, acc[a][3]));
            }
            const uint32_t x0 = __shfl_up_sync(0xffffffffu, w[10], 2), x1 = __shfl_up_sync(0xffffffffu, w[11], 2);
            w[10] = w[8];
            if (t >= 2) { w[8] = x0; w[9] = x1; }
        }
    }
}

__device__ __forceinline__ int swap01(int i) { return (i & ~3) | ((i & 1) << 1) | ((i >> 1) & 1); }
enum { BC_AUX = 0, BC_S = 5, BC_KG = 15 };

__device__ __forceinline__ void fetch_gates(const Params& p, int i, int lane, unsigned epoch, uint32_t dst) {
    const uint32_t par = (epoch & 1) ? 0x80008000u : 0u;
    uint4 v;
#pragma unroll 1
    for (int it = 0;; it++) {
        v = ld_rlx128(p.s->gate + 256 * i + 8 * lane);
        v.x ^= par; v.y ^= par; v.z ^= par; v.w ^= par;
        if (__all_sync(0xffffffffu, (v.x & v.y & v.z & v.w & 0x80008000u) == 0x80008000u)) break;
        if (it > (1 << 20)) give_up();
    }
    sts128(dst + (8 + 16 * i + (lane >> 1)) * 16, v.x, v.y, v.z, v.w);
}
__device__ __forceinline__ void store_rows(const CUtensorMap* m, uint32_t src, int col, int row) {
    asm volatile("cp.async.bulk.tensor.5d.global.shared::cta.bulk_group [%0, {%2, %3, %3, %3, %4}], [%1];" :: "l"(m), "r"(src), "r"(col), "r"(0), "r"(row) : "memory");
}

__device__ __forceinline__ void store_or_add(void* o, const uint32_t (&y)[4], uint32_t add) {
    asm volatile("{ .reg .pred p; setp.ne.u32 p, %5, 0; @!p st.global.v4.u32 [%0], {%1,%2,%3,%4}; @p red.relaxed.gpu.global.add.noftz.v4.bf16x2 [%0], {%1,%2,%3,%4}; }"
                 :: "l"(o), "r"(y[0]), "r"(y[1]), "r"(y[2]), "r"(y[3]), "r"(add) : "memory");
}

__device__ __forceinline__ void conv_aux(const Params& p, const CUtensorMap* mU, uint32_t sb, int aw, int lane, int bid, unsigned epoch) {
    const unsigned t0 = clock32();
    const int g = lane >> 2, t = lane & 3, mi = lane >> 3, r8 = lane & 7;
    const int rank = bid & 1, slab = bid >> 1;
    const uint32_t bar_y = sb + SC_MISC, bar_u = bar_y + 32, bar_v = bar_y + 40, bar_box = bar_y + 64 + 8 * aw, s_bm = bar_y + 128;
    if (elect()) {
        mbar_init(bar_box, 1); mbar_fence();
        mbar_expect(bar_box, 4096);
        if (UDELAY) until(t0, UDELAY);
        tma4d(sb + SC_RT + 4096 * aw, mU, 16 * slab, 0, 0, 16 * rank + 2 * aw, bar_box);
        mbar_init(bar_y + 8 * aw, aw < 4 ? 9 : aw == 5 ? 8 : 1); mbar_fence();
        if (aw < 5) mbar_expect(bar_y + 8 * aw, aw == 4 ? 16384 : 4096);
    }
    __syncwarp();
    asm volatile("barrier.cluster.arrive.relaxed.aligned;" ::: "memory");
    asm volatile("setmaxnreg.dec.sync.aligned.u32 88;");
    const uint32_t ut = sb + SC_UT + aw * UT_STRIDE;
    sts128(ut + (mi >> 1) * (SC_ST - SC_UT) + (mi & 1) * UT_HALF + r8 * 16, 0, 0, 0, 0);
    if (lane < 16) sts128(s_bm + lane * 16, 0, 0, 0, 0);
    {
        const uint32_t dst = sb + SC_UT + swap01(g) * UT_STRIDE + (8 + 64 * rank + 8 * aw + t) * 16;
        const uint32_t rdst = mapa(dst, rank ^ 1), rbar = mapa(bar_u, rank ^ 1);
        asm volatile("barrier.cluster.wait.acquire.aligned;" ::: "memory");
        mbar_wait(bar_box);
        if (aw == 0) TSTAMP(1);
        const uint32_t src = fresh(sb + SC_RT) + aw * 4096 + (8 * mi + 4 * (r8 & 1) + (r8 >> 1)) * 32 + ((rank ^ (r8 & 1)) << 4);
        uint32_t x[8][4];
#pragma unroll
        for (int i = 0; i < 4; i++) { ldsm4t(x[i], src + 1024 * i); ldsm4t(x[4 + i], (src ^ 16) + 1024 * i); }
        asm volatile("" :: "r"(x[0][0]), "r"(x[1][0]), "r"(x[2][0]), "r"(x[3][0]) : "memory");
#pragma unroll
        for (int i = 0; i < 4; i++) st_async128(rdst + (i & 1) * UT_HALF + 32 * (i & 2), x[4 + i][0], x[4 + i][1], x[4 + i][2], x[4 + i][3], rbar);
#pragma unroll
        for (int i = 0; i < 4; i++) sts128(dst + (i & 1) * UT_HALF + 32 * (i & 2), x[i][0], x[i][1], x[i][2], x[i][3]);
    }
    bar_sync(BC_AUX, 256);
    mbar_wait_cluster(bar_u);
    if (aw == 0) TSTAMP(2);
    {
        const uint32_t a = fresh(ut) + (mi & 1) * UT_HALF + (64 * (mi >> 1) + r8) * 16;
        uint4 v = lds128(a);
#pragma unroll
        for (int i = 1; i <= 8; i++) {
            const uint4 w = lds128(a + 128 * i);
            sts128(a + 128 * i + (SC_ST - SC_UT), badd2(v.x, w.x), badd2(v.y, w.y), badd2(v.z, w.z), badd2(v.w, w.w));
            v = w;
        }
    }
    bar_arrive(BC_S + aw, 64);
    if (aw == 0) TSTAMP(3);
    {
        uint32_t ws = sb + SC_UT + t * UT_STRIDE + (g + 6) * 16, wd = sb + SC_V + t * V_STRIDE + 64 * g, sw = 16 * (g & 2);
#pragma unroll 1
        for (int k = aw; k < 25; k += 8) {
            if (k - aw == 8) {
                bar_sync(BC_KG, 384);
                if (lane < 16) sts128(sb + SC_V + aw * V_STRIDE + lane * 16, 0, 0, 0, 0);
            }
            if (k == 24) { ws -= (g & 1) * 4 * UT_STRIDE + 16 * g; wd -= (g & 1) * 4 * V_STRIDE + 64 * g; sw = 0; }
            const int h = k >= 12, a = k - 12 * h;
            const uint32_t d = wd + h * 4 * V_STRIDE + 512 * a;
            window_task(fresh(ws) + h * 4 * UT_STRIDE + 128 * a, d + sw, d + (sw ^ 32), a < 8);
        }
    }
    if (aw == 0) TSTAMP(9);
    {
        if (aw >= 2) fetch_gates(p, aw, lane, epoch, sb + SC_GT + (lane & 1) * UT_HALF);
        __syncwarp();
        if (elect()) { mbar_arrive(bar_v); prefetch_map(mU + 4); }
        next_epoch(p, epoch);
        if (aw == 0) TSTAMP(4);
        if (aw == 7) {
            const int row = key_row(wait_sel(p, slab >> 1, r8, key_tag(epoch)));
            if (lane < 8) asm volatile("red.shared.or.b32 [%0], %1;" :: "r"(s_bm + (row >> 5) * 4), "r"(1u << (row & 31)) : "memory");
            TSTAMP(10);
        }
        bar_sync(BC_AUX, 256);
        const uint32_t src = sb + SC_RT + ((r8 >> 1) & 1) * Y_RS + (2 * mi + (r8 & 1)) * Y_CS + (2 * aw + (r8 >> 2)) * 16;
        const int L = 2 * aw + (t >> 1);
        const int row0 = 256 * rank + 128 * (g >> 2) + 32 * (L & 3) + 16 * (g & 1) + 8 * ((g >> 1) & 1) + (L >> 2);
        __nv_bfloat16* outp = p.out + (size_t)row0 * DM + 16 * slab + 8 * (t & 1);
        const uint32_t stg = sb + SC_ST + 4096 * aw, so = (g >> 1) * 256 + (t >> 1) * 64 + (g & 1) * 32 + (t & 1) * 16;
#pragma unroll 1
        for (int s = 1; s < 4; s++) {
            const uint32_t bm = lds32(fresh(s_bm) + (16 * s + (row0 >> 5)) * 4) >> (row0 & 31);
            const bool routed = __any_sync(0xffffffffu, bm & 0x11u);
            if (aw == s) mbar_wait_cluster(bar_y + 8 * s);
            bar_sync(BC_AUX, 256);
            const uint32_t sf = fresh(src) + 512 * s;
            uint32_t y[2][4];
            ldsm4t(y[0], sf); ldsm4t(y[1], sf + 256);
            if (routed) {
#pragma unroll
                for (int k = 0; k < 2; k++) store_or_add(outp + (size_t)(512 * s + 4 * k) * DM, y[k], bm & (1u << (4 * k)));
            } else {
                sts128(stg + so + 1024 * s, y[0][0], y[0][1], y[0][2], y[0][3]); sts128(stg + so + 1024 * s + 128, y[1][0], y[1][1], y[1][2], y[1][3]);
                asm volatile("fence.proxy.async.shared::cta;" ::: "memory");
                __syncwarp();
                if (elect()) store_rows(mU + 4, stg + 1024 * s, 16 * slab, 512 * s + 256 * rank + 64 * (aw & 1) + (aw >> 1));
            }
            if (aw == 0) TSTAMP(16 + s);
        }
        if (elect()) { asm volatile("cp.async.bulk.commit_group;" ::: "memory"); asm volatile("cp.async.bulk.wait_group.read 0;" ::: "memory"); }
        if (aw == 0) TFLUSH();
    }
}

__device__ __forceinline__ uint32_t k_tag(unsigned epoch) { return epoch << 16 | 0x80000000u; }
__device__ __forceinline__ void publish_k(uint4* kp, const uint32_t (&w)[12], unsigned epoch, bool full) {
#pragma unroll
    for (int i = 0; i < 3; i++)
        asm volatile("st.relaxed.gpu.global.v4.u32 [%0], {%1,%2,%3,%4};" :: "l"(kp + 32 * i), "r"(w[3 * i]), "r"(w[3 * i + 1]), "r"(w[3 * i + 2]),
                     "r"(full ? __byte_perm(w[9 + (i >> 1)], k_tag(epoch), i == 1 ? 0x7632 : 0x7610) : k_tag(epoch)));
}
template <bool FULL>
__device__ __forceinline__ void k_tables(uint32_t kt, int lane, const uint32_t (&w)[12]) {
    const int g = lane >> 2, t = lane & 3, mi = lane >> 3, r8 = lane & 7;
    uint32_t x3 = w[7], re[4], rx[4];
#pragma unroll
    for (int i = 0; i < 4; i++) {
        re[i] = __shfl_sync(0xffffffffu, w[i], lane + 31);
        rx[i] = __shfl_sync(0xffffffffu, w[4 + i], lane + (i == 0 && lane == 29 ? 5 : 1 + 2 * t));
    }
    if (FULL) {
        asm volatile("stmatrix.sync.aligned.m8n8.x2.trans.shared.b16 [%0], {%1,%2};" :: "r"(kt + (KT_D + 7) * 4 + 64 * t + 16 * (mi & 1) + 8 * (r8 & 4)), "r"(w[8]), "r"(w[9]) : "memory");
        if (lane == 2) {
            sts32(kt + (KT_C + 78) * 4, w[10] & 0xffffu);
            sts128(kt + (KT_T + 2) * 4, 0, w[10] & 0xffffu, __byte_perm(w[10], 0, 0x1010), w[10] << 16);
        }
        if (lane == 29) x3 = bsub2(x3, rx[0] & 0xffffu);
    }
#pragma unroll
    for (int i = 0; i < 4; i++) {
        sts64(kt + (16 + 64 * i) * 4 + 8 * lane, __byte_perm(w[i], lane ? re[i] : i ? re[i - 1] : 0, 0x5432), w[i]);
        const uint32_t x = i < 3 ? w[4 + i] : x3, aa = __byte_perm(x, 0, 0x3232);
        if (t < 2) sts128(kt + (272 + 64 * i + 8 * g + 4 * t) * 4, i == 0 && lane == 0 ? __byte_perm(x, re[3], 0x5432) : aa, aa, x,
                          __byte_perm(lane != 29 ? rx[i] : i < 3 ? rx[(i + 1) & 3] : FULL ? 0 : rx[0] << 16, x, 0x5432));
        else if (FULL) sts32(kt + (KT_C - 50 + 8 * i + 32 * t + g) * 4, x);
    }
}

__device__ __forceinline__ void conv_main(const Params& p, uint32_t sb, int warp, int lane0, int bid, unsigned epoch, uint32_t (&w)[12]) {
    asm volatile("setmaxnreg.inc.sync.aligned.u32 168;");
    const int lane = __shfl_sync(0xffffffffu, lane0, lane0);
    const int g = lane >> 2, t = lane & 3, mi = lane >> 3, r8 = lane & 7;
    const int rank = bid & 1;
    const uint32_t bar_y = sb + SC_MISC, bar_v = bar_y + 40;
    next_epoch(p, epoch);
    if (warp < 4) {
        asm volatile("" :: "r"(w[0]), "r"(w[2]), "r"(w[4]), "r"(w[6]), "r"(w[8]), "r"(w[10]) : "memory");
        bar_arrive(BC_KG, 384);
    } else {
        bar_sync(BC_S + swap01(warp), 64);
        const uint4* src = p.s->kp + (8 * bid + warp) * 96 + lane0;
#pragma unroll 1
        for (int it = 0;; it++) {
            uint32_t bad = 0, e[3];
#pragma unroll
            for (int i = 0; i < 3; i++) { const uint4 v = ld_rlx128(src + 32 * i); w[3 * i] = v.x; w[3 * i + 1] = v.y; w[3 * i + 2] = v.z; e[i] = v.w; bad |= v.w ^ k_tag(epoch); }
            w[9] = __byte_perm(e[0], e[1], 0x5410); w[10] = e[2];
            const bool ok = __all_sync(0xffffffffu, bad < 65536);
            if (ok) break;
            if (it > (1 << 20)) give_up();
        }
    }
    if ((warp & 3) == 0) TSTAMP(5 + (warp >> 2));
    k_tables<true>(sb + SC_KT + warp * KT_BYTES, lane0, w);
    asm volatile("barrier.cluster.wait.acquire.aligned;" ::: "memory");
    if (warp < 4)
    bar_sync(BC_S + swap01(warp), 64);
    __syncwarp();
    if ((warp & 3) == 0) TSTAMP(7 + (warp >> 2));
    {
        const uint32_t ut = fresh(sb + SC_UT) + swap01(warp) * UT_STRIDE, kt = fresh(sb + SC_KT) + warp * KT_BYTES;
        uint32_t u1 = ut + (mi & 1) * UT_HALF + (8 + r8) * 16 + (mi >> 1) * 128;
        auto dup = [&](uint32_t v) { return v ^ p.zero; };
        uint32_t kp = kt + (16 + g - 2 * t) * 4;
        float acc[16][4];
        {
            const uint32_t c0 = lds32(kp + 2048), c1 = lds32(kp + 2080), c2 = lds32(kp + 2016), c3 = dup(c0);
            const uint32_t e0 = lds32(kp + (KT_T - 16) * 4), e1 = lds32(kp + (KT_T - 8) * 4), e2 = lds32(kp + (KT_T - 24) * 4), e3 = dup(e0);
            const uint32_t f0 = dup(e1), f1 = lds32(kp + KT_T * 4);
            const uint32_t uo = ut + UT_HALF + (7 + lane) * 16;
#pragma unroll
            for (int i = 0; i < 16; i++) { acc[i][0] = acc[i][1] = acc[i][2] = acc[i][3] = 0.f; }
#pragma unroll
            for (int mu = 0; mu < 8; mu += 4) {
                uint32_t b[4];
                ldsm4(b, uo + 128 * mu);
#pragma unroll
                for (int k = 0; k < 4; k++) mma_bf8(acc[mu + 8 + k], f0, f1, b[k]);
            }
#pragma unroll
            for (int mu = 0; mu < 12; mu += 2) {
                uint32_t b[4];
                ldsm4(b, u1 + 128 * mu);
                mma_bf(acc[mu + 4], c0, c1, c2, c3, b[0], b[1]);
                mma_bf(acc[mu + 5], c0, c1, c2, c3, b[2], b[3]);
                if (mu < 8) { mma_bf(acc[mu + 8], e0, e1, e2, e3, b[0], b[1]); mma_bf(acc[mu + 9], e0, e1, e2, e3, b[2], b[3]); }
            }
        }
        {
            float M[8][4];
#pragma unroll
            for (int i = 0; i < 8; i++) { M[i][0] = M[i][1] = M[i][2] = M[i][3] = 0.f; }
            uint32_t s[8][4], a3[4];
            const uint32_t kb = kp, ub = dup(u1), uc = u1 + (mi >> 1) * 128;
            auto frag = [&](uint32_t (&a)[4], uint32_t x) { a[0] = lds32(x); a[1] = lds32(x + 32); a[2] = lds32(x - 32); a[3] = dup(a[0]); };
            frag(a3, kp + 1536);
#pragma unroll
            for (int i = 1; i < 8; i++) ldsm4(s[i], u1 + (SC_ST - SC_UT) + 256 * i);
            __syncwarp();
            uint32_t ko = 0, uo = 0;
            const uint32_t pub = bid >= 48 ? PUBY : PUBIT;
#pragma unroll 1
            for (uint32_t n = warp < 4 ? pub : 8;; n = 8 - pub) {
#pragma unroll 1
            for (; n; n--) {
                uint32_t a2[4], a1[4], a0[4], b[4][4];
                ko = fresh(ko); uo = fresh(uo);
                kp = kb + ko; u1 = ub + uo;
                const uint32_t up = uc + uo;
                ko += 64; uo -= 16;
                frag(a2, kp + 1024);
#pragma unroll
                for (int i = 1; i < 4; i++) ldsm4(b[i], up + 512 * i);
                asm("ldmatrix.sync.aligned.m8n8.x2.shared.b16 {%0,%1}, [%2];" : "=r"(b[0][2]), "=r"(b[0][3]) : "r"(up + 256));
                frag(a1, kp + 512); frag(a0, kp);
                kp += 64; u1 -= 16;
#pragma unroll
                for (int i = 1; i < 7; i++) mma_bf(acc[2 * i + 2], a3[0], a3[1], a3[2], a3[3], s[i][0], s[i][1]);
#pragma unroll
                for (int e = 0; e < 4; e++) a3[e] = bsub2(a2[e], a3[e]);
#pragma unroll
                for (int i = 1; i < 7; i++) mma_bf(acc[2 * i + 3], a2[0], a2[1], a2[2], a2[3], s[i][2], s[i][3]);
                ldsm4(s[1], u1 + (SC_ST - SC_UT) + 256);
#pragma unroll
                for (int i = 1; i < 7; i++) mma_bf(M[i + 1], a3[0], a3[1], a3[2], a3[3], b[i >> 1][2 * (i & 1)], b[i >> 1][2 * (i & 1) + 1]);
                frag(a3, kp + 1536);
#pragma unroll
                for (int i = 2; i < 8; i++) mma_bf(acc[2 * i], a1[0], a1[1], a1[2], a1[3], s[i][0], s[i][1]);
#pragma unroll
                for (int e = 0; e < 4; e++) a1[e] = bsub2(a0[e], a1[e]);
#pragma unroll
                for (int i = 2; i < 8; i++) { mma_bf(acc[2 * i + 1], a0[0], a0[1], a0[2], a0[3], s[i][2], s[i][3]); ldsm4(s[i], u1 + (SC_ST - SC_UT) + 256 * i); }
#pragma unroll
                for (int i = 2; i < 8; i++) mma_bf(M[i], a1[0], a1[1], a1[2], a1[3], b[i >> 1][2 * (i & 1)], b[i >> 1][2 * (i & 1) + 1]);
            }
            if (ko == 512) break;
            publish_k(p.s->kp + (8 * bid + warp) * 96 + lane, w, epoch, false);
            }
            u1 = ub;
#pragma unroll
            for (int i = 2; i < 8; i++)
#pragma unroll
                for (int c = 0; c < 4; c++) { acc[2 * i][c] += M[i][c]; acc[2 * i + 1][c] -= M[i][c]; }
        }
        if ((warp & 3) == 0) TSTAMP(11 + (warp >> 2));
        mbar_wait(bar_v);
        const uint32_t vt = fresh(sb + SC_V) + swap01(warp) * V_STRIDE;
        const uint32_t g1 = fresh(u1) - ut + sb + SC_GT;
        const uint32_t ydst = sb + SC_RT + rank * Y_RS + warp * Y_CS + lane * 16;
        const uint32_t ydr = mapa(ydst, rank ^ 1), ybr = mapa(bar_y, rank ^ 1);
        auto stairs = [&](auto R) {
        uint32_t ug[2][2][4];
        auto ld_ug = [&](int i) { ldsm4t(ug[i & 1][0], u1 + 256 * i); ldsm4t(ug[i & 1][1], g1 + 256 * i); };
        auto ship = [&](int i) {
            const uint32_t (&u)[4] = ug[i & 1][0], (&gg)[4] = ug[i & 1][1];
            const uint32_t y0 = gmix(gg[0], acc[2 * i][0], acc[2 * i][1], u[0]), y1 = gmix(gg[1], acc[2 * i][2], acc[2 * i][3], u[1]);
            const uint32_t y2 = gmix(gg[2], acc[2 * i + 1][0], acc[2 * i + 1][1], u[2]), y3 = gmix(gg[3], acc[2 * i + 1][2], acc[2 * i + 1][3], u[3]);
            if ((i & 1) != R.value) st_async128(ydr + 512 * (i >> 1), y0, y1, y2, y3, ybr + 8 * (i >> 1));
            else asm volatile("{ .reg .pred q; setp.eq.u32 q, %6, 0; st.shared.v4.u32 [%0], {%2,%3,%4,%5}; bar.warp.sync 0xffffffff; @q mbarrier.arrive.shared::cta.b64 _, [%1]; }"
                              :: "r"(ydst + 512 * (i >> 1)), "r"(bar_y + 8 * (i >> 1)), "r"(y0), "r"(y1), "r"(y2), "r"(y3), "r"(lane) : "memory");
        };
        const uint32_t VD = vt + (VC_OFF - 400 - 16 * t) * 4 + (8 * g ^ 16 * (-t & 2)), VD2 = vt + (VC_OFF - 415 - 16 * t) * 4 + (8 * g ^ 16 * (~t & 2));
        uint2 bd[10];
        uint32_t x[2][4][4];
        auto ld4 = [&](uint32_t (&v)[4], int dl) { const uint2 w = lds64(VD + 256 * dl); v[0] = w.x; v[1] = w.y; v[2] = lds32(VD2 + 256 * dl); v[3] = dup(w.x); };
        auto mm4 = [&](const uint32_t (&v)[4], int dl) {
#pragma unroll
            for (int s = dl & 1; s < 10; s += 2) if ((dl + s) / 2 >= 4 && (dl + s) / 2 < 16) mma_bf(acc[(dl + s) / 2], v[0], v[1], v[2], v[3], bd[s].x, bd[s].y);
        };
        const uint32_t KE = kt + (KT_D + g + t) * 4, VE = vt + (VE_BASE - 912 - 16 * t) * 4 + (8 * g ^ 16 * (~t & 2));
        uint32_t b0[8], b1[8];
        auto ld8 = [&](uint32_t (&v)[4], int dl) { const uint2 w = lds64(VE + 512 * dl), z = lds64(VE + 512 * dl - 256); v[0] = w.x; v[1] = w.y; v[2] = z.x; v[3] = z.y; };
        auto mm8 = [&](const uint32_t (&v)[4], int dl, int lo, int hi) {
#pragma unroll
            for (int s = 0; s < 8; s++) if (dl + s >= lo && dl + s < hi) mma_bf(acc[dl + s], v[0], v[1], v[2], v[3], b0[s], b1[s]);
        };
        ld4(x[0][0], 6);
#pragma unroll
        for (int s = 0; s < 10; s++) bd[s] = lds64(kt + (KT_C + 2 * g + 2 * t + 8 * s) * 4);
        mm4(x[0][0], 6);
        uint32_t e[4][4];
#pragma unroll
        for (int k = 1; k < 6; k++) {
#pragma unroll
            for (int j = 0; j < 4; j++) ld4(x[k & 1][j], 4 * k + 3 + j);
            ld_ug(k + 1);
            if (k == 3) {
#pragma unroll
                for (int s = 0; s < 8; s++) { b0[s] = lds32(KE + 32 * s); b1[s] = lds32(KE + 32 * s + 16); }
            }
            if (k > 1) ship(k);
#pragma unroll
            for (int j = 0; j < 4; j++) {
                mm4(x[k & 1][j], 4 * k + 3 + j);
                if (k == 3) { uint32_t v[4], z[4]; ld8(e[j], 8 + j); ld8(v, 12 + j); ld4(z, 30 - j); mm8(v, 12 + j, 12, 16); mm8(e[j], 8 + j, 8, 12); mm4(z, 30 - j); }
                if (k == 5) { ld8(e[j], 8 + j + p.zero); mm8(e[j], 8 + j, 12, 16); }
            }
        }
        ld_ug(7);
        ship(7 - R.value); ship(6 + R.value);
        };
        if (rank) stairs(std::integral_constant<int, 1>()); else stairs(std::integral_constant<int, 0>());
        if ((warp & 3) == 0) TSTAMP(14 + (warp >> 2)); else TSTAMP(21 + warp);
    }
}

constexpr int SF_WD = 73728;
constexpr int SF_RED = 49152;
constexpr int MU_HALF = 640, MU_STRIDE = 1344, SM_RAW = 98304, SM_UT = SM_RAW + 16384, SM_G = SM_UT + 16 * MU_STRIDE, SM_Y = 196608, SM_KT = 138880, SM_KW = SM_G - 49152;
constexpr int SF_XS = 221184;
constexpr int SF_MISC = SF_XS + 8 * 1168;
constexpr int SF_KG = SF_MISC - 10 * KG_STAGE;
constexpr int SF_WR = SF_KG - 2304;
constexpr int FB_X = 64, FB_KDONE = 72, FB_KEYS = 80, FB_FREE = 88  , FB_W = 104, FB_D = FB_W + 72, FB_MU = FB_D + 96, FB_MG = FB_MU + 8, FB_MT = FB_MU + 16, FS_PART = 512, FS_TOK = 896, FS_BM = 1024;
enum { BAR_R = 7, BAR_GU = 8, BAR_RED = 9, BAR_R2 = 10, BAR_X = 11, BAR_G = 12  , BAR_M = 15 };
static_assert(SF_KG % 128 == 0 && NPRE <= 8 && SM_KT + 4 * 2112 <= 147456 && SM_G + MU_STRIDE <= SF_WR - 4 * 9216 && SM_KW + 6 * 2112 >= SM_RAW && SM_KW + 12 * 2112 <= SM_UT, "layout");

__device__ __forceinline__ int mini_ch0(int f) { return f < NW ? 16 * (f - 12) : 32 * (f - NW); }

__device__ __forceinline__ void ffn_front(const Params& p, const CUtensorMap* maps, uint32_t sb, int warp, int lane, int f, unsigned epoch) {
    const unsigned t0 = clock32();
    const int g = lane >> 2, t = lane & 3, mi = lane >> 3, r8 = lane & 7;
    const bool isx = f < NX;
    const int nrw = f < 8 ? 6 : 4, r0 = f < 8 ? 48 * f : 128 + 32 * f;
    const int rw = warp < 12 ? 13 - warp : warp ^ (warp < 14 ? 10 : 15);
    const uint32_t bar_row = sb + SF_MISC  , bar_x = bar_row + FB_X;
    const uint32_t s_part = bar_row + FS_PART  , s_tok = bar_row + FS_TOK  ;
    const uint32_t rows = sb + SF_WR - 9216 * (rw + 1);
    {
#pragma unroll 1
        for (int i = warp < 10 ? 30 : warp - 10; i < 29; i += 6) if (elect()) mbar_init(bar_x + 8 * i, i == 1 ? 4 + (f >= 12) : i < 27 ? 1 : i == 27 ? 2 : f < NW ? 8 : 16);
        const uint32_t bytes = rw < 6 ? 9216 : 1152, dst = rw < 6 ? rows : sb + SF_WR + (rw & 1) * 1152;
        const __nv_bfloat16* src = rw < 6 ? p.u + (size_t)(r0 + 8 * rw) * DM : (rw & 1) ? p.gatew : p.wr;
        if (elect()) { mbar_init(bar_row + 8 * rw, 1); mbar_fence(); mbar_expect(bar_row + 8 * rw, bytes); }
        if (warp == 13) { sts32(s_part + 64 + lane * 4, 0); sts32(bar_row + FS_BM + lane * 4, 0); }
        bar_sync(0, NTHR);
        if (rw < nrw) until(t0, RDELAY);
        if (rw < nrw || rw >= 6) { if (elect()) bulk_g2s(dst, src, bytes, bar_row + 8 * rw); }
    }
    uint4* const kdst = p.s->keys + (lane >> 1) * 128 + 2 * f + (lane & 1);
    if (warp == 15) TSTAMP(1);

    if (warp == 12) {
        if (lane < 22) mbar_expect(bar_row + FB_W + 8 * lane, lane < 9 ? 24576 : lane < 21 ? 12288 : f < NW ? 16384 : 32768);
        if (elect()) { prefetch_map(maps + 1); prefetch_map(maps + 2); prefetch_map(maps + (isx ? 3 : 5)); }
        unsigned tb = t0 + WDELAY;
        auto pieces = [&](int n, int end, uint32_t dst) {
#pragma unroll 1
            for (; n < end; n++, dst += 12288) {
                until(tb, 0); tb += WGAP;
                if (elect()) tma3d(dst, maps + 1 + (n & 1), 0, 64 * (n >> 1), 3 * f, bar_row + FB_W + 8 * (n >> 1));
            }
        };
        if (!isx) {
            until(t0, MDELAY);
#pragma unroll 1
            for (int k = f >= NW; k >= 0; k--) if (elect()) tma4d(sb + SM_RAW - 49152 * k, maps + 5, mini_ch0(f) + 16 * k, 0, 0, 0, bar_row + FB_MU);
            if (f >= NW) return;
        }
#pragma unroll 1
        for (int i = 0; i < 4; i++) {
            if (i == 1) { mbar_wait(bar_row + FB_KEYS); mbar_wait(bar_row + FB_KDONE); tb = clock32() + RESUME; }
            if (i == 3) mbar_wait(bar_row + FB_FREE);
            const int n = ((0x0c080000 + NPRE * 256) >> (8 * i)) & 255;
            pieces(n, ((0x120c0800 + NPRE) >> (8 * i)) & 255, sb + 12288 * (((0x000c0000 + NPRE * 256) >> (8 * i)) & 255));
        }
        TSTAMP(12);
        if (isx) {
#pragma unroll 1
            for (int i = 0; i < 12; i++) {
                const int n = (0x987610ba5432ull >> (4 * i)) & 15;
                if (i == 6) mbar_wait(bar_row + FB_FREE + 8);
                until(tb, 0); tb += DGAP;
                if (elect()) tma2d(sb + SF_WD + n * 12288, maps + 3, 32 * (f >> 1), 2304 * (f & 1) + 192 * n, bar_row + FB_D + 8 * n);
            }
            TSTAMP(13);
        }
    } else if (warp == 13) {
        const uint32_t tag = key_tag(epoch), par = (epoch & 1) ? 0u : 0x8000u;
        stg128(kdst, 0, 0, 0, 0);
        if (lane < 8 && isx && !(f & 1)) st_rlx32(&p.s->sel[32 * f + lane], 0);
        bar_sync(BAR_R, 32 * (nrw + 1));
        TSTAMP(3);
        {
            const uint32_t sg = fresh(s_part) + 192 + lane * 4;
            const uint32_t gb = pack_bf16(sigmoidf_(rbf(__uint_as_float(lds32(sg)))), sigmoidf_(rbf(__uint_as_float(lds32(sg + 128))))) | par | (par << 16);
            asm volatile("st.relaxed.gpu.global.u16 [%0], %1;" :: "l"(p.s->gate + r0 + lane), "h"((unsigned short)gb) : "memory");
            if (nrw > 4 && lane < 16) asm volatile("st.relaxed.gpu.global.u16 [%0], %1;" :: "l"(p.s->gate + r0 + 32 + lane), "h"((unsigned short)(gb >> 16)) : "memory");
        }
        bar_sync(BAR_R2, 32 * (nrw + 1));
        {
            const uint4 v = lds128(fresh(s_tok) + (lane & 1) * 16);
            asm volatile("st.relaxed.gpu.global.v4.u32 [%0], {%1,%2,%3,%4};" :: "l"(kdst), "r"(v.x | tag), "r"(v.y | tag), "r"(v.z | tag), "r"(v.w | tag) : "memory");
        }
        TSTAMP(4);
        if (lane == 0) { mbar_arrive(bar_row + FB_KEYS); mbar_expect(bar_x, 8 * 1152); }
        if (f >= NW) return;
        uint32_t k[16];
        const uint4* src = p.s->keys + (f & 15) * 128 + lane;
#pragma unroll 1
        for (int it = 0;; it++) {
            uint32_t bad = 0;
#pragma unroll
            for (int i = 0; i < 4; i++) {
                const uint4 x = ld_rlx128(src + (i < 3 || lane < 24 ? 32 * i : 64));
                k[i] = x.x; k[4 + i] = x.y; k[8 + i] = x.z; k[12 + i] = x.w;
                bad |= x.x ^ tag;
            }
            const bool ok = __all_sync(0xffffffffu, (bad & 0xf800u) == 0);
            if (ok) break;
            if (it > (1 << 20)) give_up();
        }
        TSTAMP(5);
        uint32_t key = 0;
#pragma unroll 2
        for (int r = 0; r < 8; r++) {
            const uint32_t m = __reduce_max_sync(0xffffffffu, max(max(k[0], k[1]), max(k[2], k[3])));
#pragma unroll
            for (int i = 0; i < 4; i++) {
                const bool pop = k[i] == m;
                k[i] = pop ? k[4 + i] : k[i]; k[4 + i] = pop ? k[8 + i] : k[4 + i]; k[8 + i] = pop ? k[12 + i] : k[8 + i]; k[12 + i] = pop ? 0 : k[12 + i];
            }
            if (r8 == r) key = m;
        }
        const int row = key_row(key);
        sts32(s_tok + r8 * 8, row);
        bar_arrive(BAR_X, 160);
        TSTAMP(6);
        if (isx) {
            if (!(f & 1)) {
                __nv_bfloat16* o = p.out + (size_t)row * DM + 16 * f + 8 * mi;
                asm volatile("st.relaxed.gpu.global.v4.u32 [%0], {%1,%1,%1,%1};" :: "l"(o), "r"(0) : "memory");
                if (__any_sync(0xffffffffu, ld_rlx32(o) != 0)) give_up();
                if (lane < 8) st_rlx32(&p.s->sel[32 * f + lane], key);
            } else wait_sel(p, f >> 1, r8, tag);
            uint32_t gb;
#pragma unroll 1
            for (int it = 0;; it++) {
                asm volatile("ld.relaxed.gpu.global.u16 %0, [%1];" : "=r"(gb) : "l"(p.s->gate + row) : "memory");
                gb ^= par;
                if (!(gb & 0x8000u)) break;
                if (it > (1 << 20)) give_up();
            }
            const uint32_t rb = key ^ 0x80000000u, rv = (rb ^ (((int)rb >> 31) & 0x7fff0000u)) & 0xffff0000u;
            sts32(s_tok + r8 * 8 + 4, __float_as_uint(rbf(1.0f - bf_lo(gb)) * rbf(sigmoidf_(__uint_as_float(rv)))));
            __syncwarp();
            TSTAMP(7);
            bar_arrive(BAR_RED, 416);
        }
    } else {
        if (rw < nrw) {
            float c[3][4];
#pragma unroll
            for (int i = 0; i < 3; i++) { c[i][0] = c[i][1] = c[i][2] = c[i][3] = 0.f; }
            mbar_wait(bar_row + 48); mbar_wait(bar_row + 56);
            const uint32_t b = fresh(sb + SF_WR) + (g & 1) * 1152 + (g >> 2) * 64 + t * 16 + (g & 2) * 2;
            uint32_t w[18][2];
#pragma unroll
            for (int kb = 0; kb < 18; kb++) { const uint32_t o = ((kb & 1) ? b ^ 64 : b) + 128 * (kb >> 1); w[kb][0] = lds32(o); w[kb][1] = lds32(o + 8); }
            mbar_wait(bar_row + 8 * rw);
            if (warp == 15) TSTAMP(2);
            const uint32_t a = fresh(rows) + g * 1152 + (g & 1) * 64 + t * 16;
#pragma unroll
            for (int kb = 0; kb < 18; kb++) {
                const uint4 x = lds128(((kb & 1) ? a ^ 64 : a) + 128 * (kb >> 1));
                mma_bf(c[kb % 3], x.x, x.y, x.z, x.w, w[kb][0], w[kb][1]);
            }
            const float sr = c[0][0] + c[1][0] + c[2][0] + __shfl_down_sync(0xffffffffu, c[0][2] + c[1][2] + c[2][2], 1);
            const float sg = c[0][1] + c[1][1] + c[2][1] + __shfl_down_sync(0xffffffffu, c[0][3] + c[1][3] + c[2][3], 1);
            const uint32_t rb = pack_bf16(0.f, sr);
            if (t == 2 * (g & 1)) {
                sts32(s_part + (8 * rw + g) * 4, (rb ^ (((int)rb >> 31) & 0x7fff0000u) ^ 0x80000000u) | (uint32_t)(2047 - r0 - 8 * rw - g));
                sts32(s_part + 192 + (8 * rw + g) * 4, __float_as_uint(sg));
            }
            __syncwarp();
            bar_sync(BAR_R, 32 * (nrw + 1));
            const uint32_t sk = fresh(s_part), kk = lds32(sk + (8 * rw + r8) * 4);
            int n = 0;
#pragma unroll
            for (int i = 0; i < 3; i++) { const uint4 v = lds128(sk + mi * 48 + 16 * i); n += (v.x > kk) + (v.y > kk) + (v.z > kk) + (v.w > kk); }
            n += __shfl_xor_sync(0xffffffffu, n, 8); n += __shfl_xor_sync(0xffffffffu, n, 16);
            if (n < 8) sts32(s_tok + 4 * n, kk);
            __syncwarp();
            bar_arrive(BAR_R2, 32 * (nrw + 1));
        }
    }
}

__device__ __forceinline__ void ffn_work(const Params& p, uint32_t sb, int warp, int lane, int f, unsigned epoch) {
    const int g = lane >> 2, t = lane & 3, mi = lane >> 3, r8 = lane & 7;
    const bool isx = f < NX;
    const uint32_t bar_x = sb + SF_MISC + FB_X, bar_free = sb + SF_MISC + FB_FREE, bar_w = sb + SF_MISC + FB_W, bar_d = sb + SF_MISC + FB_D, s_tok = sb + SF_MISC + FS_TOK;
    uint32_t fr[24][4];
    auto pin = [&] {
#pragma unroll
        for (int i = 0; i < 24; i += 8) asm volatile("" :: "r"(fr[i][0]), "r"(fr[i + 1][0]), "r"(fr[i + 2][0]), "r"(fr[i + 3][0]), "r"(fr[i + 4][0]), "r"(fr[i + 5][0]), "r"(fr[i + 6][0]), "r"(fr[i + 7][0]) : "memory");
    };
    {
        const int j = (unsigned)(warp - 4) < 6, w = warp - (j ? 4 : warp < 4 ? 0 : 6);
        float ag[2][4], au[2][4];
#pragma unroll
        for (int i = 0; i < 2; i++) { ag[i][0] = ag[i][1] = ag[i][2] = ag[i][3] = 0.f; au[i][0] = au[i][1] = au[i][2] = au[i][3] = 0.f; }
        const uint32_t wb = sb + (w >> 1) * 4096 + (r8 + 8 * (mi >> 1)) * 64 + (((2 * (w & 1) + (mi & 1)) ^ (r8 >> 1)) << 4);
        const uint32_t xb = sb + SF_XS + r8 * 1168 + mi * 16;
        auto load = [&](int i, int n, int place) {
            mbar_wait(bar_w + 8 * n);
            const uint32_t wk = fresh(wb) + place * 24576;
#pragma unroll
            for (int s = 0; s < 4; s++) { ldsm4t(fr[8 * i + s], wk + 1024 * s); ldsm4t(fr[8 * i + 4 + s], wk + 1024 * s + 12288); }
        };
        auto mul = [&](int i, uint32_t xk) {
            uint32_t x[2][4];
            ldsm4(x[0], xk); ldsm4(x[1], xk + 64);
#pragma unroll
            for (int s = 0; s < 4; s++) {
                const uint32_t (&a)[4] = fr[8 * i + s], (&b)[4] = fr[8 * i + 4 + s];
                mma_bf(ag[s & 1], a[0], a[1], a[2], a[3], x[s >> 1][2 * (s & 1)], x[s >> 1][2 * (s & 1) + 1]);
                mma_bf(au[s & 1], b[0], b[1], b[2], b[3], x[s >> 1][2 * (s & 1)], x[s >> 1][2 * (s & 1) + 1]);
            }
        };
#pragma unroll
        for (int i = 0; i < 3; i++) load(i, 3 * j + i, (i ? 5 : 3) * j + i);
        pin();
        bar_sync(BAR_G + j, 192);
        if (w == 0 && lane == 0) mbar_arrive(bar_free + 8 * j);
        if (warp < 4) {
            bar_sync(BAR_X, 160);
            const uint32_t rows = lds32(fresh(s_tok) + 8 * r8);
#pragma unroll 1
            for (int i = warp; i < 8; i += 4) {
                const int row = __shfl_sync(0xffffffffu, rows, i);
                if (elect()) bulk_g2s(sb + SF_XS + i * 1168, p.u + (size_t)row * DM, 1152, bar_x);
                __syncwarp();
            }
        }
        mbar_wait(bar_x);
        if (warp == 0) TSTAMP(8);
        {
            const uint32_t xk = fresh(xb) + 384 * j;
#pragma unroll
            for (int i = 0; i < 3; i++) { mul(i, (i ? fresh(xk) : xk) + 128 * i); if (i == 0) { asm volatile("" :: "f"(ag[0][0]), "f"(ag[1][0]), "f"(au[0][0]), "f"(au[1][0])); sts32(s_tok + 64, clock32()); } }
        }
#pragma unroll 1
        for (int n = 6 + j; n < 9; n += 2) { load(0, n, n - 6); mul(0, fresh(xb) + 128 * n); }
#pragma unroll
        for (int c = 0; c < 4; c++) { ag[0][c] += ag[1][c]; au[0][c] += au[1][c]; }
        if (j) {
            sts128(wb + 24576, __float_as_uint(ag[0][0]), __float_as_uint(ag[0][1]), __float_as_uint(ag[0][2]), __float_as_uint(ag[0][3]));
            sts128(wb + 25600, __float_as_uint(au[0][0]), __float_as_uint(au[0][1]), __float_as_uint(au[0][2]), __float_as_uint(au[0][3]));
        }
        bar_sync(BAR_GU, 384);
        if (!j) {
            const uint32_t sf = fresh(wb);
            const uint4 g1 = lds128(sf + 24576), u1 = lds128(sf + 25600);
            const uint32_t gs[4] = {g1.x, g1.y, g1.z, g1.w}, us[4] = {u1.x, u1.y, u1.z, u1.w};
            if (warp == 0) TSTAMP(9);
            float h[4];
#pragma unroll
            for (int c = 0; c < 4; c++) {
                const float gv = rbf(ag[0][c] + __uint_as_float(gs[c]));
                h[c] = rbf(gv * sigmoidf_(gv)) * rbf(au[0][c] + __uint_as_float(us[c]));
            }
            uint32_t h0, h1;
            asm("movmatrix.sync.aligned.m8n8.trans.b16 %0, %1;" : "=r"(h0) : "r"(pack_bf16(h[0], h[1])));
            asm("movmatrix.sync.aligned.m8n8.trans.b16 %0, %1;" : "=r"(h1) : "r"(pack_bf16(h[2], h[3])));
            if (h0 == 0) h0 = 0x8000u;
            asm volatile("{ .reg .b64 v; mov.b64 v, {%1, %2}; st.relaxed.gpu.global.b64 [%0], v; }" :: "l"(p.s->h + ((epoch & 1) * 288 + 6 * f + w) * 32 + lane), "r"(h0), "r"(h1) : "memory");
        }
        if (isx) {
            if (warp == 0) TSTAMP(10);
            const uint2* hsrc = p.s->h + ((epoch & 1) * 288 + 144 * (f & 1) + 12 * warp) * 32 + lane;
            uint2 hb[12];
            auto ldh = [&](int s) { asm volatile("ld.relaxed.gpu.global.v2.u32 {%0, %1}, [%2];" : "=r"(hb[s].x), "=r"(hb[s].y) : "l"(hsrc + 32 * s) : "memory"); };
#pragma unroll
            for (int s = 0; s < 12; s++) ldh(s);
#pragma unroll 1
            for (int it = 0;; it++) {
                bool again = false;
#pragma unroll
                for (int s = 0; s < 12; s += 2) if (__any_sync(0xffffffffu, min(hb[s].x, hb[s + 1].x) == 0)) { ldh(s); ldh(s + 1); again = true; }
                if (!again) break;
                if (it > (1 << 16)) give_up();
            }
            if (warp == 0) TSTAMP(11);
            mbar_wait(bar_d + 8 * warp);
            if (warp == 9) TSTAMP(14);
            float ad[2][2][4];
#pragma unroll
            for (int i = 0; i < 4; i++) { ad[i >> 1][i & 1][0] = ad[i >> 1][i & 1][1] = ad[i >> 1][i & 1][2] = ad[i >> 1][i & 1][3] = 0.f; }
            const uint32_t wd = fresh(sb) + SF_WD + warp * 12288 + (r8 + 8 * (mi >> 1)) * 64 + (((mi & 1) ^ (r8 >> 1)) << 4);
#pragma unroll
            for (int s = 0; s < 12; s++) {
                uint32_t a[4], b[4];
                ldsm4t(a, wd + 1024 * s); ldsm4t(b, (wd ^ 32) + 1024 * s);
                mma_bf(ad[0][s & 1], a[0], a[1], a[2], a[3], hb[s].x, hb[s].y);
                mma_bf(ad[1][s & 1], b[0], b[1], b[2], b[3], hb[s].x, hb[s].y);
            }
            const uint32_t rd = sb + SF_RED + warp * 1152 + (72 * t + g) * 4;
#pragma unroll
            for (int i = 0; i < 8; i++) sts32(rd + (i >> 2) * 64 + (i & 1) * 144 + ((i >> 1) & 1) * 32, __float_as_uint(ad[i >> 2][0][i & 3] + ad[i >> 2][1][i & 3]));
            bar_sync(BAR_RED, 416);
            if (warp < 4) {
                const int tid = 32 * warp + lane;
                const uint32_t rs = fresh(sb + SF_RED) + (tid >> 4) * 144 + (tid & 15) * 8;
                const uint2 tk = lds64(fresh(s_tok) + (tid >> 4) * 8);
                float x = 0.f, y = 0.f;
#pragma unroll
                for (int w = 0; w < 12; w++) { const uint2 v = lds64(rs + w * 1152); x += __uint_as_float(v.x); y += __uint_as_float(v.y); }
                asm volatile("red.relaxed.gpu.global.add.noftz.bf16x2 [%0], %1;" :: "l"(p.out + (size_t)tk.x * DM + 32 * (f >> 1) + 2 * (tid & 15)),
                             "r"(pack_bf16(x * __uint_as_float(tk.y), y * __uint_as_float(tk.y))) : "memory");
            }
            if (warp == 0) { TSTAMP(15); TFLUSH(); }
            asm volatile("exit;"); __builtin_unreachable();
        }
    }
}

__device__ __forceinline__ void fetch_k(const uint4* src, uint64_t (&v)[6], uint32_t a, uint32_t b) {
    asm volatile("{ .reg .pred p; setp.eq.u32 p, %7, %8; @p ld.relaxed.gpu.global.v2.u64 {%0,%1}, [%6]; @p ld.relaxed.gpu.global.v2.u64 {%2,%3}, [%6 + 512]; @p ld.relaxed.gpu.global.v2.u64 {%4,%5}, [%6 + 1024]; }"
                 : "+l"(v[0]), "+l"(v[1]), "+l"(v[2]), "+l"(v[3]), "+l"(v[4]), "+l"(v[5]) : "l"(src), "r"(a), "r"(b));
}
__device__ __forceinline__ uint32_t mini_conv(const Params& p, uint32_t sb, int warp, int lane, int f, unsigned epoch) {
    const int g = lane >> 2, t = lane & 3, mi = lane >> 3, r8 = lane & 7;
    const uint32_t fb = sb + SF_MISC, kt = sb + (warp >= 12 ? SM_KT - 12 * 2112 : f < NW ? SM_KW + 2 * 2112 : SM_KW) + warp * 2112;
    const bool ism = f >= NW;
    const int ch0 = mini_ch0(f);
    uint32_t seq = 128, key;
    uint64_t v[6] = {};
    const uint4* src = p.s->kp + lane;
    auto hi = [&](int i) { return (uint32_t)(v[i] >> 32); };
    if (f >= (warp < 4 ? NW : NX)) {
    {
        const uint32_t c = 36 + (warp & 3) + 2 * (warp & 12), y = (uint32_t)((warp < 8 ? 0xa026802400000000ull : 0x2a2e00280080a22cull) >> ((8 * warp) & 48)) & 0xffff;
        seq = ism ? 0x101 * c - 0x400 : y + (warp & 1) * ((y >> 5) & 0x101);
        src += (ch0 + (seq & 31)) * 96;
    }
    if (seq & 32) {
        if (seq & 4) {
            const int q = (seq & 3) + ((seq >> 1) & 4);
            const uint32_t ab = sb - 3072 * (seq & 16), d = ab + SM_UT + g * MU_STRIDE + (8 + 4 * q + t) * 16;
            sts128(ab + SM_UT + (2 * q + (mi >> 1)) * MU_STRIDE + (mi & 1) * MU_HALF + r8 * 16, 0, 0, 0, 0);
            mbar_wait(fb + FB_MU);
            if (warp == 15) TSTAMP(16);
            const uint32_t a = fresh(ab + SM_RAW) + q * 2048 + (8 * mi + 4 * (r8 & 1) + (r8 >> 1)) * 32 + ((r8 & 1) << 4);
            uint32_t x[4][4];
#pragma unroll
            for (int i = 0; i < 4; i++) ldsm4t(x[i], (i & 2 ? a ^ 16 : a) + 1024 * (i & 1));
#pragma unroll
            for (int i = 0; i < 4; i++) sts128(d + (i & 1) * MU_HALF + (i & 2) * 4 * MU_STRIDE, x[i][0], x[i][1], x[i][2], x[i][3]);
            __syncwarp();
            if (lane == 0) mbar_arrive(fb + FB_MT);
        }
        if (!EFETCH) mbar_wait(fb + FB_KDONE);
        fetch_k(src, v, 0, 0);
        if (EFETCH) mbar_wait(fb + FB_KDONE);
        if ((warp | 2) == GW) { fetch_gates(p, (warp >> 1) & 1, lane, epoch, sb + SM_G + (lane & 1) * MU_HALF); __syncwarp(); if (lane == 0) mbar_arrive(fb + FB_MG); }
        mbar_wait(fb + FB_KEYS);
        if (warp == TW) TSTAMP(17);
    }
    }
    const uint32_t lo = (mi & 1) * MU_HALF + (8 + r8) * 16 + (mi >> 1) * 128;
#pragma unroll 1
    do {
        const int c = seq & 31;
        if (seq & 32) {
#pragma unroll 1
        for (int it = 0; !__all_sync(0xffffffffu, ((hi(1) ^ k_tag(epoch)) | (hi(3) ^ k_tag(epoch)) | (hi(5) ^ k_tag(epoch)) | ((uint32_t)v[5] & p.zero)) < 65536); it++) {
            fetch_k(src, v, 0, 0);
            if (it > (1 << 20)) give_up();
        }
        mbar_wait(fb + FB_MT);
        sts128(kt + t * 16, 0, 0, 0, 0);
        if (warp == TW) TSTAMP(seq >> 8 ? 7 : 10);
        const uint32_t w[12] = {(uint32_t)v[0], hi(0), (uint32_t)v[1], (uint32_t)v[2], hi(2), (uint32_t)v[3], (uint32_t)v[4], hi(4), 0, 0, 0, 0};
        k_tables<false>(fresh(kt), fresh(lane), w);
        }
        __syncwarp();
        if (seq & 128) ffn_work(p, sb, warp, fresh(lane), f, epoch);
        if (!(seq & 32)) return 0;
        const uint32_t ab = sb - 49152 * (c >> 4), kb = fresh(kt) + (16 + g - 2 * t) * 4, ub = fresh(ab + SM_UT + (c & 15) * MU_STRIDE) + lo;
        const uint32_t yd = ab + SM_Y + (c & 15) * 1056 + (c & 8) * 8 + lane * 16;
        uint32_t kp = kb, u1 = ub;
        if (warp == TW && !(seq >> 8)) TSTAMP(13);
        seq >>= 8;
        src += ((int)(seq & 31) - c) * 96;
#pragma unroll
        for (int i = 0; i < 6; i++) v[i] = 0;
        key = 0;
        float acc[8][4];
#pragma unroll
        for (int i = 0; i < 8; i++) { acc[i][0] = acc[i][1] = acc[i][2] = acc[i][3] = 0.f; }
        uint32_t a[4][4], b[2][2][4];
        auto lda = [&](int j, int o) { const uint32_t x = kp + 64 * o + 512 * j; a[j][2] = o ? a[j][1] ^ p.zero : lds32((kp ^ p.zero) + 512 * j - 32); a[j][0] = lds32(x); a[j][1] = lds32(x + 32); a[j][3] = a[j][0] ^ p.zero; };
        auto ldb = [&](int s, int o) { ldsm4(b[s][0], u1 - 16 * o); ldsm4(b[s][1], u1 + 256 - 16 * o); };
        ldb(0, 0);
#pragma unroll
        for (int j = 0; j < 4; j++) lda(j, 0);
#pragma unroll
        for (int s = 0; s < 8; s++) {
            if (s == FPOS) {
                const uint32_t e = seq | (__float_as_uint(acc[0][0]) & p.zero);
                fetch_k(src, v, e & 32, 32);
                if (KEYPF) asm volatile("{ .reg .pred p; setp.eq.u32 p, %2, 0; @p ld.relaxed.gpu.global.u32 %0, [%1]; }" : "+r"(key) : "l"(&p.s->sel[(ch0 >> 5) * 64 + r8]), "r"(e));
            }
            if (s < 7) ldb(~s & 1, s + 1);
#pragma unroll
            for (int i = 0; i < 4; i++) {
                const int j = (i >> 1) + 2 * (i & 1);
#pragma unroll
                for (int mu = 3 - j; mu >= 0; mu--) mma_bf(acc[NACC == 8 && j + mu == 3 && (j & 1) ? 6 + (j >> 1) : j + mu + (j & 2)], a[j][0], a[j][1], a[j][2], a[j][3], b[s & 1][mu >> 1][2 * (mu & 1)], b[s & 1][mu >> 1][2 * (mu & 1) + 1]);
                if (s < 7) lda(j, s + 1);
            }
        }
        if (warp == TW && !seq) TSTAMP(14);
        mbar_wait(fb + FB_MG);
#pragma unroll
        for (int e = 0; e < 4; e++) { acc[2][e] += acc[4][e]; acc[3][e] += acc[5][e]; if (NACC == 8) acc[3][e] += acc[6][e] + acc[7][e]; }
        uint32_t ug[4][4];
#pragma unroll
        for (int i = 0; i < 2; i++) { ldsm4t(ug[i], ub + 256 * i); ldsm4t(ug[2 + i], fresh(sb + SM_G) + lo + 256 * i); }
#pragma unroll
        for (int i = 0; i < 2; i++) {
            const uint32_t (&u)[4] = ug[i], (&gg)[4] = ug[2 + i];
            sts128(yd + 512 * i, gmix(gg[0], acc[2 * i][0], acc[2 * i][1], u[0]), gmix(gg[1], acc[2 * i][2], acc[2 * i][3], u[1]),
                   gmix(gg[2], acc[2 * i + 1][0], acc[2 * i + 1][1], u[2]), gmix(gg[3], acc[2 * i + 1][2], acc[2 * i + 1][3], u[3]));
        }
        __syncwarp();
        if (warp == TW) TSTAMP(18 + (seq != 0));
    } while (seq);
    if (warp >= 12) TSTAMP(12 + warp);
    return key;
}
__device__ __forceinline__ void mini_out(const Params& p, const CUtensorMap* maps, uint32_t sb, int warp, int lane, int f, unsigned epoch, uint32_t key) {
    const int g = lane >> 2, t = lane & 3, mi = lane >> 3, r8 = lane & 7;
    const uint32_t fb = sb + SF_MISC;
    const bool ism = f >= NW;
    const int ch0 = mini_ch0(f);
    const int k = ism ? warp >> 3 : 0;
    uint32_t first = 1;
    if (lane == 0) asm volatile("atom.shared.exch.b32 %0, [%1], 1;" : "=r"(first) : "r"(fb + FS_BM + 64 + 4 * k) : "memory");
    if (!__all_sync(0xffffffffu, first)) {
        if (elect()) prefetch_map(maps + 4);
        const int row = key_row(wait_sel(p, ch0 >> 5, r8, key_tag(epoch), key));
        if (row < 512) asm volatile("red.shared.or.b32 [%0], %1;" :: "r"(fb + FS_BM + (row >> 5) * 4), "r"(1u << (row & 31)) : "memory");
    }
    const int m = warp & 7, dr = 128 * (g >> 2) + 32 * (t >> 1) + 16 * (g & 1) + 8 * ((g >> 1) & 1);
    const uint32_t y = SM_Y + ((r8 >> 1) & 1) * 8512 + (2 * mi + (r8 & 1)) * 1056 + (2 * m + (r8 >> 2)) * 16;
    const uint32_t so = (g >> 1) * 256 + (t >> 1) * 64 + (g & 1) * 32 + (t & 1) * 16;
    bar_sync(BAR_M - k, ism ? 256 : NTHR);
#pragma unroll 1
    for (int h = ism ? 0 : warp >> 3;; h++) {
        const int r0 = 256 * h + 64 * (m & 1) + (m >> 1), row = r0 + dr;
        const uint32_t bm = lds32(fresh(fb) + FS_BM + (row >> 5) * 4) >> (row & 31), ab = fresh(sb - 49152 * k + 512 * h), stg = ab + SM_UT + 2048 * m + 512 * h;
        uint32_t x[2][4];
        ldsm4t(x[0], ab + y); ldsm4t(x[1], ab + y + 256);
        if (warp == 0 && x[0][0] != 0x12345) TSTAMP(28);
        if (__any_sync(0xffffffffu, bm & 0x11u)) {
#pragma unroll
            for (int i = 0; i < 2; i++) store_or_add(p.out + (size_t)(row + 4 * i) * DM + ch0 + 16 * k + 8 * (t & 1), x[i], bm & (1u << (4 * i)));
        } else {
#pragma unroll
            for (int i = 0; i < 2; i++) sts128(stg + so + 128 * i, x[i][0], x[i][1], x[i][2], x[i][3]);
            asm volatile("fence.proxy.async.shared::cta;" ::: "memory");
            __syncwarp();
            if (elect()) store_rows(maps + 4, stg, ch0 + 16 * k, r0);
        }
        if (h >= ism) break;
    }
    if (elect()) { asm volatile("cp.async.bulk.commit_group;" ::: "memory"); asm volatile("cp.async.bulk.wait_group.read 0;" ::: "memory"); }
    if (warp == 8) TSTAMP(11);
    if (warp == 0) { TSTAMP(15); TFLUSH(); }
}

constexpr int SMEM_BYTES = 232448;
static_assert(SF_MISC + 1152 <= 232192, "layout");

struct Maps { CUtensorMap m[6]; };

__global__ void __cluster_dims__(2, 1, 1) __launch_bounds__(NTHR, 1)
fused_kernel(const Params p, const __grid_constant__ Maps maps) {
    extern __shared__ __align__(1024) uint8_t smem_raw[];
    uint32_t q[8];
    {
        const int b = blockIdx.x, x = threadIdx.x, rc = 4 * b + max(b - 84, 0) - 288 + (x >> 6);
        const int cv = (b - NCONV) >> 31, ca = 8 * b + ((x >> 5) & 3), cb = 2 * rc - (rc & 3) + 4;
        const uint32_t ch = (ca & cv) | (cb & ~cv), o = NST * ch + 2 * ((x & 31) + ((x >> (cv & 2)) & 32));
        const bool c = x < (b < 84 ? 256 : 320);
        q[6] = ldg16_if(c, p.logdt + ch);
        q[2] = ldg32_if(c, p.Bre + o); q[3] = ldg32_if(c, p.Bim + o); q[4] = ldg32_if(c, p.Cre + o); q[5] = ldg32_if(c, p.Cim + o); q[0] = ldg32_if(c, p.Are + o); q[1] = ldg32_if(c, p.Aim + o);
        q[7] = ldg16_if(c, p.Dskip + ch);
    }
    const unsigned epoch = ld_rlx32(&p.s->epoch[blockIdx.x * 16 + (threadIdx.x >> 5)]);
    const uint32_t sb = __shfl_sync(0xffffffffu, smem_u32(smem_raw), 0);
    const int warp = __shfl_sync(0xffffffffu, threadIdx.x >> 5, 0), bid = __shfl_sync(0xffffffffu, blockIdx.x, 0);
    const int lane = __shfl_sync(0xffffffffu, threadIdx.x & 31, threadIdx.x);
    const bool conv = bid < NCONV;
    const int f = bid - NCONV;
    uint32_t w[12];
    if (warp < (f < 12 ? 8 : 10)) {
        const int half = conv ? warp >> 2 : warp & 1, pr = conv ? warp & 3 : warp >> 1;
        const int rc = 4 * f + max(f - 12, 0) + pr;
        const uint32_t stage = sb + (conv ? SC_KG : SF_KG) + warp * KG_STAGE;
        uint4* const kp = p.s->kp + (conv ? 8 * bid + pr : 2 * rc - (rc & 3) + 4) * 96 + lane;
        kgen(q, sb, half, stage, stage + (conv ? 4 : 1) * KG_STAGE, 1 + pr, lane, p.zero, w, [&] {
            sts128z_if(conv && lane < 20, sb + SC_KT + warp * KT_BYTES + lane * 16 + (lane < 4 ? 0 : lane < 14 ? 2048 : 2288));
            stg128(kp + 64 * half, 0, 0, 0, 0); stg128z_if(!half, kp + 32);
            stg128z_if((unsigned)f < NW && warp < 6, (uint4*)(p.s->h + ((lane >> 4) * 288 + 6 * f + warp) * 32) + (lane & 15));
            if (conv) asm volatile("barrier.cluster.arrive.relaxed.aligned;" ::: "memory"); else bar_sync(0, NTHR);
        });
        if (conv) { conv_main(p, sb, warp, lane, bid, epoch, w); return; }
        {
            if (!half) { publish_k(kp, w, epoch, true); if (lane == 0) mbar_arrive(sb + SF_MISC + FB_KDONE); }
            if (warp == 0) TSTAMP(22);
            if (warp == 2) TSTAMP(23);
        }
    } else if (conv) {
        conv_aux(p, maps.m, sb, warp - 8, lane, bid, epoch);
        return;
    } else {
        ffn_front(p, maps.m, sb, warp, lane, f, epoch);
    }
    converged();
    next_epoch(p, epoch);
    if (warp >= 12 && f < NX) return;
    mini_out(p, maps.m, sb, warp, lane, f, epoch, mini_conv(p, sb, warp, __shfl_sync(0xffffffffu, lane, lane), f, epoch));
}

typedef CUresult (*EncodeFn)(CUtensorMap*, CUtensorMapDataType, cuuint32_t, void*, const cuuint64_t*, const cuuint64_t*, const cuuint32_t*, const cuuint32_t*,
                             CUtensorMapInterleave, CUtensorMapSwizzle, CUtensorMapL2promotion, CUtensorMapFloatOOBfill);

void make_map(EncodeFn fn, CUtensorMap* m, const void* base, int rank, const cuuint64_t* dims, const cuuint64_t* strides, const cuuint32_t* box, CUtensorMapSwizzle sw) {
    const cuuint32_t es[5] = {1, 1, 1, 1, 1};
    fn(m, CU_TENSOR_MAP_DATA_TYPE_BFLOAT16, rank, (void*)base, dims, strides, box, es, CU_TENSOR_MAP_INTERLEAVE_NONE, sw,
       CU_TENSOR_MAP_L2_PROMOTION_NONE, CU_TENSOR_MAP_FLOAT_OOB_FILL_NONE);
}

}

extern "C" void kernel_launch(void* const* d_in, const int* in_sizes, int n_in, void* d_out, int out_size) {
    (void)in_sizes; (void)n_in; (void)out_size;
    static EncodeFn fn = nullptr;
    static void* scratch = nullptr;
    if (!fn) {
        void* ptr = nullptr; cudaDriverEntryPointQueryResult qr;
        cudaGetDriverEntryPoint("cuTensorMapEncodeTiled", &ptr, cudaEnableDefault, &qr);
        fn = (EncodeFn)ptr;
        cudaGetSymbolAddress(&scratch, g_scratch);
        cudaFuncSetAttribute(fused_kernel, cudaFuncAttributeMaxDynamicSharedMemorySize, SMEM_BYTES);
    }
    typedef const __nv_bfloat16* bp;
    Params p;
    p.u = (bp)d_in[0]; p.Are = (bp)d_in[1]; p.Aim = (bp)d_in[2]; p.Bre = (bp)d_in[3]; p.Bim = (bp)d_in[4]; p.Cre = (bp)d_in[5]; p.Cim = (bp)d_in[6];
    p.logdt = (bp)d_in[7]; p.Dskip = (bp)d_in[8]; p.wr = (bp)d_in[10]; p.gatew = (bp)d_in[14];
    p.out = (__nv_bfloat16*)d_out; p.s = (Scratch*)scratch; p.zero = 0;
    Maps maps;
    {
        const cuuint64_t dims[4] = {DM, 4, 16, 32}, strides[3] = {16 * DM * 2, DM * 2, 64 * DM * 2};
        const cuuint32_t box[4] = {16, 4, 16, 2};
        make_map(fn, &maps.m[0], d_in[0], 4, dims, strides, box, CU_TENSOR_MAP_SWIZZLE_32B);
        const cuuint32_t box2[4] = {16, 4, 16, 8};
        make_map(fn, &maps.m[5], d_in[0], 4, dims, strides, box2, CU_TENSOR_MAP_SWIZZLE_32B);
    }
    for (int i = 0; i < 2; i++) {
        const cuuint64_t dims[3] = {32, DM, FF / 32}, strides[2] = {FF * 2, 64};
        const cuuint32_t box[3] = {32, 64, 3};
        make_map(fn, &maps.m[1 + i], d_in[11 + i], 3, dims, strides, box, CU_TENSOR_MAP_SWIZZLE_64B);
    }
    {
        const cuuint64_t dims[2] = {DM, FF}, strides[1] = {DM * 2};
        const cuuint32_t box[2] = {32, 192};
        make_map(fn, &maps.m[3], d_in[13], 2, dims, strides, box, CU_TENSOR_MAP_SWIZZLE_64B);
    }
    {
        const cuuint64_t dims[5] = {DM, 4, 4, 2, L_SEQ}, strides[4] = {16 * DM * 2, 4 * DM * 2, 128 * DM * 2, DM * 2};
        const cuuint32_t box[5] = {16, 4, 4, 2, 1};
        make_map(fn, &maps.m[4], d_out, 5, dims, strides, box, CU_TENSOR_MAP_SWIZZLE_NONE);
    }
    fused_kernel<<<NCTA, NTHR, SMEM_BYTES>>>(p, maps);
}
```

```cpp
#include <cuda_runtime.h>
#include <cuda_bf16.h>
#include <cuda_fp16.h>
#include <cuda.h>
#include <stdint.h>
#include <type_traits>

#define RESUME 450
#define FPOS 4
#define KEYPF 1
#define NACC 6
#define EFETCH 0
#define GW 7
#define TW 12
#define MDELAY 2000
#define UDELAY 0
#define RDELAY 900
#define WDELAY 2000
#define WGAP 290
#define NPRE 7
#define DGAP 260

namespace {

constexpr int DM = 576, NST = 128, FF = 4608, L_SEQ = 2048;
constexpr int NCONV = 72, NX = 36, NW = 48, NCTA = 132, NTHR = 512;

struct __align__(128) Scratch {
    unsigned epoch[NCTA * 16];
    uint4 keys[16 * 128];
    uint32_t sel[18 * 64];
    uint16_t gate[L_SEQ];
    uint2 h[2 * 288 * 32];
    uint4 kp[DM * 96];
};
__device__ Scratch g_scratch;
#define TFLUSH()
#define TSTAMP(i)

struct Params {
    const __nv_bfloat16 *Are, *Aim, *Bre, *Bim, *Cre, *Cim, *logdt, *Dskip, *u, *wr, *gatew;
    __nv_bfloat16* out;
    Scratch* s;
    uint32_t zero;
};

__device__ __forceinline__ void give_up() { asm volatile("trap; exit;"); __builtin_unreachable(); }
__device__ __forceinline__ void converged() { __syncwarp(); asm volatile("{ .reg .b32 t; mov.b32 t, 0; movmatrix.sync.aligned.m8n8.trans.b16 t, t; }" ::: "memory"); }
__device__ __forceinline__ bool elect() { uint32_t r; asm volatile("{ .reg .pred p; elect.sync _|p, 0xffffffff; selp.u32 %0, 1, 0, p; }" : "=r"(r)); return r; }
__device__ __forceinline__ uint32_t smem_u32(const void* p) { return (uint32_t)__cvta_generic_to_shared(p); }
__device__ __forceinline__ uint32_t pack_bf16(float lo, float hi) { uint32_t r; asm("cvt.rn.bf16x2.f32 %0, %1, %2;" : "=r"(r) : "f"(hi), "f"(lo)); return r; }
__device__ __forceinline__ uint32_t pack_f16(float lo, float hi) { uint32_t r; asm("cvt.rn.f16x2.f32 %0, %1, %2;" : "=r"(r) : "f"(hi), "f"(lo)); return r; }
__device__ __forceinline__ float bf_lo(uint32_t w) { return __uint_as_float(w << 16); }
__device__ __forceinline__ float bf_hi(uint32_t w) { return __uint_as_float(w & 0xffff0000u); }
__device__ __forceinline__ float rbf(float x) { return bf_lo(pack_bf16(x, 0.f)); }
__device__ __forceinline__ uint32_t badd2(uint32_t a, uint32_t b) { uint32_t r; asm("add.rn.bf16x2 %0, %1, %2;" : "=r"(r) : "r"(a), "r"(b)); return r; }
__device__ __forceinline__ uint32_t bsub2(uint32_t a, uint32_t b) { uint32_t r; asm("sub.rn.bf16x2 %0, %1, %2;" : "=r"(r) : "r"(a), "r"(b)); return r; }
__device__ __forceinline__ uint32_t gmix(uint32_t ng, float ny0, float ny1, uint32_t u) {
    uint32_t r; asm("{ .reg .b32 t; fma.rn.bf16x2 t, %1, %3, %3; fma.rn.bf16x2 %0, %1, %2, t; }" : "=r"(r) : "r"(ng), "r"(pack_bf16(ny0, ny1)), "r"(u)); return r;
}
__device__ __forceinline__ void mma_bf(float (&c)[4], uint32_t a0, uint32_t a1, uint32_t a2, uint32_t a3, uint32_t b0, uint32_t b1) {
    asm("mma.sync.aligned.m16n8k16.row.col.f32.bf16.bf16.f32 {%0,%1,%2,%3}, {%4,%5,%6,%7}, {%8,%9}, {%0,%1,%2,%3};"
        : "+f"(c[0]), "+f"(c[1]), "+f"(c[2]), "+f"(c[3]) : "r"(a0), "r"(a1), "r"(a2), "r"(a3), "r"(b0), "r"(b1));
}
__device__ __forceinline__ void mma_bf8(float (&c)[4], uint32_t a0, uint32_t a1, uint32_t b0) {
    asm("mma.sync.aligned.m16n8k8.row.col.f32.bf16.bf16.f32 {%0,%1,%2,%3}, {%4,%5}, {%6}, {%0,%1,%2,%3};"
        : "+f"(c[0]), "+f"(c[1]), "+f"(c[2]), "+f"(c[3]) : "r"(a0), "r"(a1), "r"(b0));
}
__device__ __forceinline__ void mma_h(float (&c)[4], uint32_t a0, uint32_t a1, uint32_t a2, uint32_t a3, uint32_t b0, uint32_t b1) {
    asm("mma.sync.aligned.m16n8k16.row.col.f32.f16.f16.f32 {%0,%1,%2,%3}, {%4,%5,%6,%7}, {%8,%9}, {%0,%1,%2,%3};"
        : "+f"(c[0]), "+f"(c[1]), "+f"(c[2]), "+f"(c[3]) : "r"(a0), "r"(a1), "r"(a2), "r"(a3), "r"(b0), "r"(b1));
}
__device__ __forceinline__ uint32_t fresh(uint32_t a) { asm volatile("" : "+r"(a) :: "memory"); return a; }
__device__ __forceinline__ uint32_t lds16(uint32_t a) { uint32_t v; asm("ld.shared.u16 %0, [%1];" : "=r"(v) : "r"(a)); return v; }
__device__ __forceinline__ uint32_t lds32(uint32_t a) { uint32_t v; asm("ld.shared.u32 %0, [%1];" : "=r"(v) : "r"(a)); return v; }
__device__ __forceinline__ uint2 lds64(uint32_t a) { uint2 v; asm("ld.shared.v2.u32 {%0,%1}, [%2];" : "=r"(v.x), "=r"(v.y) : "r"(a)); return v; }
__device__ __forceinline__ uint4 lds128(uint32_t a) { uint4 v; asm("ld.shared.v4.u32 {%0,%1,%2,%3}, [%4];" : "=r"(v.x), "=r"(v.y), "=r"(v.z), "=r"(v.w) : "r"(a)); return v; }
__device__ __forceinline__ uint4 lds128v(uint32_t a) { uint4 v; asm volatile("ld.shared.v4.u32 {%0,%1,%2,%3}, [%4];" : "=r"(v.x), "=r"(v.y), "=r"(v.z), "=r"(v.w) : "r"(a) : "memory"); return v; }
__device__ __forceinline__ void ldsm4(uint32_t (&r)[4], uint32_t a) {
    asm("ldmatrix.sync.aligned.m8n8.x4.shared.b16 {%0,%1,%2,%3}, [%4];" : "=r"(r[0]), "=r"(r[1]), "=r"(r[2]), "=r"(r[3]) : "r"(a));
}
__device__ __forceinline__ void ldsm4t(uint32_t (&r)[4], uint32_t a) {
    asm("ldmatrix.sync.aligned.m8n8.x4.trans.shared.b16 {%0,%1,%2,%3}, [%4];" : "=r"(r[0]), "=r"(r[1]), "=r"(r[2]), "=r"(r[3]) : "r"(a));
}
__device__ __forceinline__ void sts16(uint32_t a, uint32_t v) { asm volatile("st.shared.u16 [%0], %1;" :: "r"(a), "h"((unsigned short)v) : "memory"); }
__device__ __forceinline__ void sts32(uint32_t a, uint32_t v) { asm volatile("st.shared.u32 [%0], %1;" :: "r"(a), "r"(v) : "memory"); }
__device__ __forceinline__ void sts64(uint32_t a, uint32_t x, uint32_t y) { asm volatile("st.shared.v2.u32 [%0], {%1,%2};" :: "r"(a), "r"(x), "r"(y) : "memory"); }
__device__ __forceinline__ void sts128(uint32_t a, uint32_t x, uint32_t y, uint32_t z, uint32_t w) {
    asm volatile("st.shared.v4.u32 [%0], {%1,%2,%3,%4};" :: "r"(a), "r"(x), "r"(y), "r"(z), "r"(w) : "memory");
}
__device__ __forceinline__ void st_async128(uint32_t a, uint32_t x, uint32_t y, uint32_t z, uint32_t w, uint32_t bar) {
    asm volatile("st.async.weak.shared::cluster.mbarrier::complete_tx::bytes.v4.b32 [%0], {%1,%2,%3,%4}, [%5];" :: "r"(a), "r"(x), "r"(y), "r"(z), "r"(w), "r"(bar) : "memory");
}
__device__ __forceinline__ void mbar_init(uint32_t b, uint32_t cnt) { asm volatile("mbarrier.init.shared::cta.b64 [%0], %1;" :: "r"(b), "r"(cnt) : "memory"); }
__device__ __forceinline__ void mbar_fence() { asm volatile("fence.mbarrier_init.release.cluster;" ::: "memory"); }
__device__ __forceinline__ void mbar_expect(uint32_t b, uint32_t bytes) { asm volatile("mbarrier.arrive.expect_tx.shared::cta.b64 _, [%0], %1;" :: "r"(b), "r"(bytes) : "memory"); }
__device__ __forceinline__ void mbar_arrive(uint32_t b) { asm volatile("mbarrier.arrive.shared::cta.b64 _, [%0];" :: "r"(b) : "memory"); }
#define CHINT ""
#define HINT ""
__device__ __forceinline__ void mbar_wait(uint32_t b, uint32_t parity = 0) {
    asm volatile("{ .reg .pred p; .reg .u32 n; mov.u32 n, 0;\n"
                 "LW: mbarrier.try_wait.parity.shared::cta.b64 p, [%0], %1" HINT "; @p bra LD; add.u32 n, n, 1; setp.lt.u32 p, n, 65536; @p bra LW; trap;\n"
                 "LD: }" :: "r"(b), "r"(parity) : "memory");
}
__device__ __forceinline__ void mbar_wait_cluster(uint32_t b) {
    asm volatile("{ .reg .pred p; .reg .u32 n; mov.u32 n, 0;\n"
                 "LW: mbarrier.try_wait.parity.acquire.cluster.shared::cta.b64 p, [%0], 0" CHINT "; @p bra LD; add.u32 n, n, 1; setp.lt.u32 p, n, 65536; @p bra LW; trap;\n"
                 "LD: }" :: "r"(b) : "memory");
}
__device__ __forceinline__ void tma2d(uint32_t dst, const CUtensorMap* m, int c0, int c1, uint32_t bar) {
    asm volatile("cp.async.bulk.tensor.2d.shared::cluster.global.mbarrier::complete_tx::bytes [%0], [%1, {%3, %4}], [%2];"
                 :: "r"(dst), "l"(m), "r"(bar), "r"(c0), "r"(c1) : "memory");
}
__device__ __forceinline__ void tma3d(uint32_t dst, const CUtensorMap* m, int c0, int c1, int c2, uint32_t bar) {
    asm volatile("cp.async.bulk.tensor.3d.shared::cluster.global.mbarrier::complete_tx::bytes [%0], [%1, {%3, %4, %5}], [%2];"
                 :: "r"(dst), "l"(m), "r"(bar), "r"(c0), "r"(c1), "r"(c2) : "memory");
}
__device__ __forceinline__ void tma4d(uint32_t dst, const CUtensorMap* m, int c0, int c1, int c2, int c3, uint32_t bar) {
    asm volatile("cp.async.bulk.tensor.4d.shared::cluster.global.mbarrier::complete_tx::bytes [%0], [%1, {%3, %4, %5, %6}], [%2];"
                 :: "r"(dst), "l"(m), "r"(bar), "r"(c0), "r"(c1), "r"(c2), "r"(c3) : "memory");
}
__device__ __forceinline__ void bulk_g2s(uint32_t dst, const void* src, uint32_t bytes, uint32_t bar) {
    asm volatile("cp.async.bulk.shared::cluster.global.mbarrier::complete_tx::bytes [%0], [%1], %2, [%3];"
                 :: "r"(dst), "l"(src), "r"(bytes), "r"(bar) : "memory");
}
__device__ __forceinline__ uint32_t mapa(uint32_t a, uint32_t rank) { uint32_t r; asm("mapa.shared::cluster.u32 %0, %1, %2;" : "=r"(r) : "r"(a), "r"(rank)); return r; }
__device__ __forceinline__ void prefetch_map(const CUtensorMap* m) { asm volatile("prefetch.tensormap [%0];" :: "l"(m) : "memory"); }
__device__ __forceinline__ void bar_sync(int id, int n) { asm volatile("bar.sync %0, %1;" :: "r"(id), "r"(n) : "memory"); }
__device__ __forceinline__ void bar_arrive(int id, int n) { asm volatile("bar.arrive %0, %1;" :: "r"(id), "r"(n) : "memory"); }
__device__ __forceinline__ uint32_t ldg16_if(bool c, const void* p) { uint32_t v; asm volatile("{ .reg .pred p; setp.ne.u32 p, %2, 0; @p ld.global.nc.u16 %0, [%1]; }" : "=r"(v) : "l"(p), "r"((uint32_t)c)); return v; }
__device__ __forceinline__ uint32_t ldg32_if(bool c, const void* p) { uint32_t v; asm volatile("{ .reg .pred p; setp.ne.u32 p, %2, 0; @p ld.global.nc.u32 %0, [%1]; }" : "=r"(v) : "l"(p), "r"((uint32_t)c)); return v; }
__device__ __forceinline__ uint32_t ld_rlx32(const void* p) { uint32_t v; asm volatile("ld.relaxed.gpu.global.u32 %0, [%1];" : "=r"(v) : "l"(p) : "memory"); return v; }
__device__ __forceinline__ uint4 ld_rlx128(const void* p) {
    uint4 v; asm volatile("ld.relaxed.gpu.global.v4.u32 {%0,%1,%2,%3}, [%4];" : "=r"(v.x), "=r"(v.y), "=r"(v.z), "=r"(v.w) : "l"(p) : "memory"); return v;
}
__device__ __forceinline__ void st_rlx32(void* p, uint32_t v) { asm volatile("st.relaxed.gpu.global.u32 [%0], %1;" :: "l"(p), "r"(v) : "memory"); }
__device__ __forceinline__ void stg128(void* p, uint32_t x, uint32_t y, uint32_t z, uint32_t w) {
    asm volatile("st.global.v4.u32 [%0], {%1,%2,%3,%4};" :: "l"(p), "r"(x), "r"(y), "r"(z), "r"(w) : "memory");
}
__device__ __forceinline__ void next_epoch(const Params& p, unsigned e) { if ((threadIdx.x & 31) == 0) p.s->epoch[blockIdx.x * 16 + (threadIdx.x >> 5)] = e + 1; }
__device__ __forceinline__ void sts128z_if(bool c, uint32_t a) { asm volatile("{ .reg .pred p; setp.ne.u32 p, %1, 0; @p st.shared.v4.u32 [%0], {%2,%2,%2,%2}; }" :: "r"(a), "r"((uint32_t)c), "r"(0) : "memory"); }
__device__ __forceinline__ void stg128z_if(bool c, void* a) { asm volatile("{ .reg .pred p; setp.ne.u32 p, %1, 0; @p st.global.v4.u32 [%0], {%2,%2,%2,%2}; }" :: "l"(a), "r"((uint32_t)c), "r"(0) : "memory"); }
__device__ __forceinline__ unsigned clock32() { unsigned c; asm volatile("mov.u32 %0, %clock;" : "=r"(c) :: "memory"); return c; }
__device__ __forceinline__ void until(unsigned t0, int c) { while ((int)(clock32() - t0) < c) { } }
__device__ __forceinline__ float sigmoidf_(float x) { return __fdividef(1.0f, 1.0f + __expf(-x)); }
__device__ __forceinline__ uint32_t key_tag(unsigned epoch) { return ((epoch & 15u) | 16u) << 11; }
__device__ __forceinline__ int key_row(uint32_t key) { return 2047 - (int)(key & 2047u); }
__device__ __forceinline__ uint32_t wait_sel(const Params& p, int s32, int r8, uint32_t tag, uint32_t k = 0) {
#pragma unroll 1
    for (int it = 0; !__all_sync(0xffffffffu, (k & 0xf800u) == tag); it++) {
        k = ld_rlx32(&p.s->sel[s32 * 64 + r8]);
        if (it > (1 << 20)) give_up();
    }
    return k;
}

struct cplx { float re, im; };
__device__ __forceinline__ cplx csq(cplx a) { cplx r; r.re = a.re * a.re - a.im * a.im; r.im = (a.re * a.im) * 2.f; return r; }
__device__ __forceinline__ cplx cexpk(float ar, float ai, float k) {
    float mag, s, c;
    asm("ex2.approx.ftz.f32 %0, %1;" : "=f"(mag) : "f"(ar * (k * 1.4426950408889634f)));
    const float r = ai * k;
    asm("sin.approx.ftz.f32 %0, %1;" : "=f"(s) : "f"(r));
    asm("cos.approx.ftz.f32 %0, %1;" : "=f"(c) : "f"(r));
    cplx o; o.re = mag * c; o.im = mag * s; return o;
}
struct h2c { uint32_t re, im; };
__device__ __forceinline__ h2c cmul_cd(h2c v, __half2 c, __half2 d) {
    const __half2 r = *(const __half2*)&v.re, i = *(const __half2*)&v.im;
    const __half2 x = __hfma2(__hneg2(i), d, __hmul2(r, c)), y = __hfma2(i, c, __hmul2(r, d));
    h2c o; o.re = *(const uint32_t*)&x; o.im = *(const uint32_t*)&y; return o;
}
__device__ __forceinline__ h2c cmul_s(h2c v, uint32_t s) { const __half2 h = *(const __half2*)&s; return cmul_cd(v, __low2half2(h), __high2half2(h)); }
__device__ __forceinline__ h2c cmul_sc(h2c v, uint32_t s) {
    const __half2 h = *(const __half2*)&s, c = __low2half2(h), d = __high2half2(h), r = *(const __half2*)&v.re, i = *(const __half2*)&v.im;
    const __half2 x = __hfma2(i, d, __hmul2(r, c)), y = __hfma2(__hneg2(r), d, __hmul2(i, c));
    h2c o; o.re = *(const uint32_t*)&x; o.im = *(const uint32_t*)&y; return o;
}
__device__ __forceinline__ h2c cmul_vc(h2c v, uint32_t s) {
    const __half2 h = *(const __half2*)&s, c = __low2half2(h), d = __high2half2(h), r = *(const __half2*)&v.re, i = *(const __half2*)&v.im;
    const __half2 x = __hfma2(i, d, __hmul2(r, c)), y = __hfma2(__hneg2(i), c, __hmul2(r, d));
    h2c o; o.re = *(const uint32_t*)&x; o.im = *(const uint32_t*)&y; return o;
}

constexpr int UT_HALF = 2240, UT_STRIDE = 4448;
constexpr int KT_T = 542, KT_C = 552, KT_D = 645, KT_BYTES = 720 * 4;
constexpr int VC_OFF = 80, VE_BASE = 1616;
constexpr int V_STRIDE = (1616 + 1024) * 4 + 80;
constexpr int KG_STAGE = 5248;
constexpr int Y_CS = 2080, Y_RS = 8 * Y_CS + 64;

constexpr int SC_RT = 0;
constexpr int SC_UT = 33408;
constexpr int SC_ST = SC_UT + 8 * UT_STRIDE;
constexpr int SC_KT = SC_ST + 8 * UT_STRIDE;
constexpr int SC_GT = SC_KT + 8 * KT_BYTES;
constexpr int SC_V = SC_GT + UT_STRIDE;
constexpr int SC_KG = SC_V + 4 * V_STRIDE;
constexpr int SC_MISC = SC_V + 8 * V_STRIDE;
static_assert(V_STRIDE % 128 == 16 && 8 * KG_STAGE <= 4 * V_STRIDE && 2 * Y_RS <= SC_UT && SC_UT % 128 == 0 && SC_ST % 128 == 0, "layout");
static_assert(SC_MISC % 16 == 0 && SC_MISC + 512 <= 232192, "layout");

__device__ __forceinline__ void window_task(uint32_t src, uint32_t d0, uint32_t d1, bool withE) {
    float S[35];
    {
        uint32_t w[20];
#pragma unroll
        for (int i = 0; i < 5; i++) {
            const uint4 v = lds128(src + ((i & 1) ? 0 : UT_HALF) + ((i + 1) >> 1) * 16);
            w[4 * i] = v.x; w[4 * i + 1] = v.y; w[4 * i + 2] = v.z; w[4 * i + 3] = v.w;
        }
        float s = 0.f; S[2] = 0.f;
#pragma unroll
        for (int i = 3; i < 26; i++) { s += (i & 1) ? bf_hi(w[i >> 1]) : bf_lo(w[i >> 1]); S[i] = s; }
#pragma unroll
        for (int i = 0; i < 8; i += 2)
            sts128((i & 4 ? d1 : d0) + (VC_OFF - 16) * 4 + 8 * (i & 2), pack_bf16(S[10 + i] - S[5 + i], S[5 + i] - S[2 + i]), pack_bf16(S[18 + i] - S[13 + i], S[13 + i] - S[10 + i]),
                   pack_bf16(S[11 + i] - S[6 + i], S[6 + i] - S[3 + i]), pack_bf16(S[19 + i] - S[14 + i], S[14 + i] - S[11 + i]));
        if (withE) {
#pragma unroll
            for (int i = 26; i < 35; i++) { s += (i & 1) ? bf_hi(w[i >> 1]) : bf_lo(w[i >> 1]); S[i] = s; }
#pragma unroll
            for (int i = 0; i < 8; i += 2)
                sts128((i & 4 ? d1 : d0) + VE_BASE * 4 + 8 * (i & 2), pack_bf16(S[19 + i] - S[12 + i], S[12 + i] - S[3 + i]), pack_bf16(S[27 + i] - S[20 + i], S[20 + i] - S[11 + i]),
                       pack_bf16(S[20 + i] - S[13 + i], S[13 + i] - S[4 + i]), pack_bf16(S[28 + i] - S[21 + i], S[21 + i] - S[12 + i]));
        }
    }
}

template <class F>
__device__ __forceinline__ void kgen(const uint32_t (&q)[8], uint32_t sb, int half, uint32_t stage, uint32_t pstage, int barid, int lane, uint32_t zero, uint32_t (&w)[12], F shadow) {
    const int t = lane & 3, mi = lane >> 3, r8 = lane & 7;
    {
        const uint32_t pAr = q[0], pAi = q[1], pBr = q[2], pBi = q[3], pCr = q[4], pCi = q[5], pDt = q[6], pD = q[7];
        const uint32_t wb = fresh(stage + lane * 16), za = fresh(stage + 5120 + ((lane >> 1) & 3) * 16 + mi * 4 + (lane & 1) * 2), zr = fresh(stage + 5120 + t * 16);
        const uint32_t oA = fresh(stage + (mi & 1) * 1024 + (mi >> 1) * 512 + r8 * 16), oB = fresh(stage + 2048 + mi * 512 + r8 * 16), oC = fresh(stage + 4096 + (mi & 1) * 512 + (mi >> 1) * 128 + r8 * 16);
        float acc[6][4];
#pragma unroll
        for (int a = 0; a < 6; a++) { acc[a][0] = acc[a][1] = acc[a][2] = acc[a][3] = 0.f; asm volatile("" : "+f"(acc[a][0]), "+f"(acc[a][1]), "+f"(acc[a][2]), "+f"(acc[a][3])); }
        shadow();
        sts32(zr, clock32());
        const float dt = rbf(__expf(bf_lo(pDt)));
        float ar = dt * bf_lo(pAr), ai = dt * bf_lo(pAi), ar1 = dt * bf_hi(pAr), ai1 = dt * bf_hi(pAi);
        float wr, wi, wr1, wi1;
        { const float br = dt * bf_lo(pBr), bi = dt * bf_lo(pBi), cr = bf_lo(pCr), ci = bf_lo(pCi); wr = cr * br - ci * bi; wi = cr * bi + ci * br; }
        { const float br = dt * bf_hi(pBr), bi = dt * bf_hi(pBi), cr = bf_hi(pCr), ci = bf_hi(pCi); wr1 = cr * br - ci * bi; wi1 = cr * bi + ci * br; }
        const uint32_t ex = max(__reduce_max_sync(0xffffffffu, __float_as_uint(fmaxf(fmaxf(fabsf(wr), fabsf(wi)), fmaxf(fabsf(wr1), fabsf(wi1))))) >> 23, 14u);
        const float scl = __uint_as_float((267u - ex) << 23);
        uint32_t W = pack_f16(wr * scl, wi * -scl);
        const uint32_t W1 = pack_f16(wr1 * scl, wi1 * -scl);
        if (threadIdx.x < 32) TSTAMP(20);

#pragma unroll 1
        for (int r = 0; r < 2; r++) {
            const cplx z1 = cexpk(ar, ai, 1.f), z64 = cexpk(ar, ai, 64.f);
            const cplx z2 = csq(z1), z4 = csq(z2), z8 = csq(z4), z16 = csq(z8), z32 = csq(z16);
            const cplx z128 = csq(z64), z256 = csq(z128), z512 = csq(z256);
            auto put = [&](int grp, h2c a, h2c b, h2c c, h2c d) { sts128(wb + grp * 1024, a.re, b.re, c.re, d.re); sts128(wb + grp * 1024 + 512, a.im, b.im, c.im, d.im); };
            {
                const uint32_t s4 = pack_f16(z4.re, z4.im), s256 = pack_f16(z256.re, z256.im), s512 = pack_f16(z512.re, z512.im);
                auto mix = [](h2c a, h2c b, uint32_t sel) { return h2c{__byte_perm(a.re, b.re, sel), __byte_perm(a.im, b.im, sel)}; };
                const h2c c10 = cmul_vc(h2c{pack_f16(z1.re, 1.f), pack_f16(z1.im, 0.f)}, W), c32 = cmul_sc(c10, pack_f16(z2.re, z2.im)), c54 = cmul_sc(c10, s4);
                put(2, c10, c32, c54, cmul_sc(c32, s4));
                const h2c d20 = cmul_sc(mix(c32, c10, 0x7632), s256), e04 = cmul_sc(mix(c10, c54, 0x7632), s512), f04 = cmul_sc(e04, s256);
                put(3, d20, cmul_sc(d20, s4), e04, f04);
                const h2c ef = mix(e04, f04, 0x5410), gh = cmul_sc(ef, s512), g8 = cmul_sc(gh, pack_f16(z8.re, z8.im));
                put(4, g8, cmul_sc(g8, s512), gh, ef);
            }
            {
                const uint32_t s32 = pack_f16(z32.re, z32.im), s64 = pack_f16(z64.re, z64.im), s128 = pack_f16(z128.re, z128.im);
                const h2c p0 = {pack_f16(1.f, z8.re), pack_f16(0.f, z8.im)}, p1 = cmul_s(p0, pack_f16(z16.re, z16.im)), p2 = cmul_s(p0, s32), p3 = cmul_s(p1, s32);
                put(0, p0, p1, p2, p3);
                put(1, cmul_s(p0, s64), cmul_s(p1, s64), cmul_s(p2, s64), cmul_s(p3, s64));
                sts16(za, s128); sts16(za + 64, s128 >> 16);
            }
            __syncwarp();
            {
                const uint32_t aA = fresh(oA), aB = fresh(oB), aC = fresh(oC), aZ = fresh(zr);
                const uint4 zc = lds128(aZ), zd = lds128(aZ + 64);
                const uint32_t zcs[4] = {zc.x, zc.y, zc.z, zc.w}, zds[4] = {zd.x, zd.y, zd.z, zd.w};
                uint32_t c[4];
#pragma unroll
                for (int k = 0; k < 4; k++) {
                    uint32_t a[4], b[4];
                    ldsm4t(a, aA + 128 * k); ldsm4t(b, aB + 128 * k);
                    if (!(k & 1)) ldsm4t(c, aC + 128 * k);
                    const h2c x = cmul_cd(h2c{a[0], a[2]}, *(const __half2*)&zcs[k], *(const __half2*)&zds[k]), y = cmul_cd(h2c{a[1], a[3]}, *(const __half2*)&zcs[k], *(const __half2*)&zds[k]);
                    mma_h(acc[0], a[0], a[1], a[2], a[3], b[0], b[1]);
                    mma_h(acc[1], a[0], a[1], a[2], a[3], b[2], b[3]);
                    mma_h(acc[2], a[0], a[1], a[2], a[3], c[2 * (k & 1)], c[2 * (k & 1) + 1]);
                    mma_h(acc[3], x.re, y.re, x.im, y.im, b[0], b[1]);
                    mma_h(acc[4], x.re, y.re, x.im, y.im, b[2], b[3]);
                    mma_h(acc[5], x.re, y.re, x.im, y.im, c[2 * (k & 1)], c[2 * (k & 1) + 1]);
                }
                asm volatile("" :: "f"(acc[0][0]), "f"(acc[1][0]), "f"(acc[2][0]), "f"(acc[3][0]), "f"(acc[4][0]), "f"(acc[5][0]) : "memory");
            }
            __syncwarp();
            ar = ar1; ai = ai1; W = W1;
        }
        if (threadIdx.x < 32) TSTAMP(21);
        const float i0 = __uint_as_float((ex + 243u) << 23);
        if (half) {
#pragma unroll
            for (int a = 0; a < 6; a++) sts128(wb + a * 512, __float_as_uint(acc[a][0]), __float_as_uint(acc[a][1]), __float_as_uint(acc[a][2]), __float_as_uint(acc[a][3]));
            sts32(stage + 3072, __float_as_uint(i0));
            bar_arrive(barid, 64);
        } else {
#pragma unroll
            for (int a = 0; a < 6; a++) { acc[a][0] *= i0; acc[a][1] *= i0; acc[a][2] *= i0; acc[a][3] *= i0; }
            if (lane == 0) acc[0][1] -= bf_lo(pD);
            sts32(zr, clock32());
            bar_sync(barid, 64);
            const uint32_t src = fresh(pstage);
            const float i1 = __uint_as_float(lds32(src + 3072));
#pragma unroll
            for (int a = 0; a < 6; a++) {
                const uint4 y = lds128(src + lane * 16 + a * 512);
                w[4 * (a % 3) + 2 * (a / 3)] = pack_bf16(fmaf(__uint_as_float(y.x), i1, acc[a][0]), fmaf(__uint_as_float(y.y), i1, acc[a][1]));
                w[4 * (a % 3) + 2 * (a / 3) + 1] = pack_bf16(fmaf(__uint_as_float(y.z), i1, acc[a][2]), fmaf(__uint_as_float(y.w), i1, acc[a][3]));
            }
            const uint32_t x0 = __shfl_up_sync(0xffffffffu, w[10], 2), x1 = __shfl_up_sync(0xffffffffu, w[11], 2);
            w[10] = w[8];
            if (t >= 2) { w[8] = x0; w[9] = x1; }
        }
    }
}

__device__ __forceinline__ int swap01(int i) { return (i & ~3) | ((i & 1) << 1) | ((i >> 1) & 1); }
enum { BC_AUX = 0, BC_S = 5, BC_KG = 15 };

__device__ __forceinline__ void fetch_gates(const Params& p, int i, int lane, unsigned epoch, uint32_t dst) {
    const uint32_t par = (epoch & 1) ? 0x80008000u : 0u;
    uint4 v;
#pragma unroll 1
    for (int it = 0;; it++) {
        v = ld_rlx128(p.s->gate + 256 * i + 8 * lane);
        v.x ^= par; v.y ^= par; v.z ^= par; v.w ^= par;
        if (__all_sync(0xffffffffu, (v.x & v.y & v.z & v.w & 0x80008000u) == 0x80008000u)) break;
        if (it > (1 << 20)) give_up();
    }
    sts128(dst + (8 + 16 * i + (lane >> 1)) * 16, v.x, v.y, v.z, v.w);
}
__device__ __forceinline__ void store_rows(const CUtensorMap* m, uint32_t src, int col, int row) {
    asm volatile("cp.async.bulk.tensor.5d.global.shared::cta.bulk_group [%0, {%2, %3, %3, %3, %4}], [%1];" :: "l"(m), "r"(src), "r"(col), "r"(0), "r"(row) : "memory");
}

__device__ __forceinline__ void store_or_add(void* o, const uint32_t (&y)[4], uint32_t add) {
    asm volatile("{ .reg .pred p; setp.ne.u32 p, %5, 0; @!p st.global.v4.u32 [%0], {%1,%2,%3,%4}; @p red.relaxed.gpu.global.add.noftz.v4.bf16x2 [%0], {%1,%2,%3,%4}; }"
                 :: "l"(o), "r"(y[0]), "r"(y[1]), "r"(y[2]), "r"(y[3]), "r"(add) : "memory");
}

__device__ __forceinline__ void conv_aux(const Params& p, const CUtensorMap* mU, uint32_t sb, int aw, int lane, int bid, unsigned epoch) {
    const unsigned t0 = clock32();
    const int g = lane >> 2, t = lane & 3, mi = lane >> 3, r8 = lane & 7;
    const int rank = bid & 1, slab = bid >> 1;
    const uint32_t bar_y = sb + SC_MISC, bar_u = bar_y + 32, bar_v = bar_y + 40, bar_box = bar_y + 64 + 8 * aw, s_bm = bar_y + 128;
    if (elect()) {
        mbar_init(bar_box, 1); mbar_fence();
        mbar_expect(bar_box, 4096);
        if (UDELAY) until(t0, UDELAY);
        tma4d(sb + SC_RT + 4096 * aw, mU, 16 * slab, 0, 0, 16 * rank + 2 * aw, bar_box);
        mbar_init(bar_y + 8 * aw, aw < 4 ? 9 : aw == 5 ? 8 : 1); mbar_fence();
        if (aw < 5) mbar_expect(bar_y + 8 * aw, aw == 4 ? 16384 : 4096);
    }
    __syncwarp();
    asm volatile("barrier.cluster.arrive.relaxed.aligned;" ::: "memory");
    asm volatile("setmaxnreg.dec.sync.aligned.u32 88;");
    const uint32_t ut = sb + SC_UT + aw * UT_STRIDE;
    sts128(ut + (mi >> 1) * (SC_ST - SC_UT) + (mi & 1) * UT_HALF + r8 * 16, 0, 0, 0, 0);
    if (lane < 16) sts128(s_bm + lane * 16, 0, 0, 0, 0);
    {
        const uint32_t dst = sb + SC_UT + swap01(g) * UT_STRIDE + (8 + 64 * rank + 8 * aw + t) * 16;
        const uint32_t rdst = mapa(dst, rank ^ 1), rbar = mapa(bar_u, rank ^ 1);
        asm volatile("barrier.cluster.wait.acquire.aligned;" ::: "memory");
        mbar_wait(bar_box);
        if (aw == 0) TSTAMP(1);
        const uint32_t src = fresh(sb + SC_RT) + aw * 4096 + (8 * mi + 4 * (r8 & 1) + (r8 >> 1)) * 32 + ((rank ^ (r8 & 1)) << 4);
        uint32_t x[8][4];
#pragma unroll
        for (int i = 0; i < 4; i++) { ldsm4t(x[i], src + 1024 * i); ldsm4t(x[4 + i], (src ^ 16) + 1024 * i); }
        asm volatile("" :: "r"(x[0][0]), "r"(x[1][0]), "r"(x[2][0]), "r"(x[3][0]) : "memory");
#pragma unroll
        for (int i = 0; i < 4; i++) st_async128(rdst + (i & 1) * UT_HALF + 32 * (i & 2), x[4 + i][0], x[4 + i][1], x[4 + i][2], x[4 + i][3], rbar);
#pragma unroll
        for (int i = 0; i < 4; i++) sts128(dst + (i & 1) * UT_HALF + 32 * (i & 2), x[i][0], x[i][1], x[i][2], x[i][3]);
    }
    bar_sync(BC_AUX, 256);
    mbar_wait_cluster(bar_u);
    if (aw == 0) TSTAMP(2);
    {
        const uint32_t a = fresh(ut) + (mi & 1) * UT_HALF + (64 * (mi >> 1) + r8) * 16;
        uint4 v = lds128(a);
#pragma unroll
        for (int i = 1; i <= 8; i++) {
            const uint4 w = lds128(a + 128 * i);
            sts128(a + 128 * i + (SC_ST - SC_UT), badd2(v.x, w.x), badd2(v.y, w.y), badd2(v.z, w.z), badd2(v.w, w.w));
            v = w;
        }
    }
    bar_arrive(BC_S + aw, 64);
    if (aw == 0) TSTAMP(3);
    {
        uint32_t ws = sb + SC_UT + t * UT_STRIDE + (g + 6) * 16, wd = sb + SC_V + t * V_STRIDE + 64 * g, sw = 16 * (g & 2);
#pragma unroll 1
        for (int k = aw; k < 25; k += 8) {
            if (k - aw == 8) {
                bar_sync(BC_KG, 384);
                if (lane < 16) sts128(sb + SC_V + aw * V_STRIDE + lane * 16, 0, 0, 0, 0);
            }
            if (k == 24) { ws -= (g & 1) * 4 * UT_STRIDE + 16 * g; wd -= (g & 1) * 4 * V_STRIDE + 64 * g; sw = 0; }
            const int h = k >= 12, a = k - 12 * h;
            const uint32_t d = wd + h * 4 * V_STRIDE + 512 * a;
            window_task(fresh(ws) + h * 4 * UT_STRIDE + 128 * a, d + sw, d + (sw ^ 32), a < 8);
        }
    }
    if (aw == 0) TSTAMP(9);
    {
        if (aw >= 2) fetch_gates(p, aw, lane, epoch, sb + SC_GT + (lane & 1) * UT_HALF);
        __syncwarp();
        if (elect()) { mbar_arrive(bar_v); prefetch_map(mU + 4); }
        next_epoch(p, epoch);
        if (aw == 0) TSTAMP(4);
        if (aw == 7) {
            const int row = key_row(wait_sel(p, slab >> 1, r8, key_tag(epoch)));
            if (lane < 8) asm volatile("red.shared.or.b32 [%0], %1;" :: "r"(s_bm + (row >> 5) * 4), "r"(1u << (row & 31)) : "memory");
            TSTAMP(10);
        }
        bar_sync(BC_AUX, 256);
        const uint32_t src = sb + SC_RT + ((r8 >> 1) & 1) * Y_RS + (2 * mi + (r8 & 1)) * Y_CS + (2 * aw + (r8 >> 2)) * 16;
        const int L = 2 * aw + (t >> 1);
        const int row0 = 256 * rank + 128 * (g >> 2) + 32 * (L & 3) + 16 * (g & 1) + 8 * ((g >> 1) & 1) + (L >> 2);
        __nv_bfloat16* outp = p.out + (size_t)row0 * DM + 16 * slab + 8 * (t & 1);
        const uint32_t stg = sb + SC_ST + 4096 * aw, so = (g >> 1) * 256 + (t >> 1) * 64 + (g & 1) * 32 + (t & 1) * 16;
#pragma unroll 1
        for (int s = 1; s < 4; s++) {
            const uint32_t bm = lds32(fresh(s_bm) + (16 * s + (row0 >> 5)) * 4) >> (row0 & 31);
            const bool routed = __any_sync(0xffffffffu, bm & 0x11u);
            if (aw == s) mbar_wait_cluster(bar_y + 8 * s);
            bar_sync(BC_AUX, 256);
            const uint32_t sf = fresh(src) + 512 * s;
            uint32_t y[2][4];
            ldsm4t(y[0], sf); ldsm4t(y[1], sf + 256);
            if (routed) {
#pragma unroll
                for (int k = 0; k < 2; k++) store_or_add(outp + (size_t)(512 * s + 4 * k) * DM, y[k], bm & (1u << (4 * k)));
            } else {
                sts128(stg + so + 1024 * s, y[0][0], y[0][1], y[0][2], y[0][3]); sts128(stg + so + 1024 * s + 128, y[1][0], y[1][1], y[1][2], y[1][3]);
                asm volatile("fence.proxy.async.shared::cta;" ::: "memory");
                __syncwarp();
                if (elect()) store_rows(mU + 4, stg + 1024 * s, 16 * slab, 512 * s + 256 * rank + 64 * (aw & 1) + (aw >> 1));
            }
            if (aw == 0) TSTAMP(16 + s);
        }
        if (elect()) { asm volatile("cp.async.bulk.commit_group;" ::: "memory"); asm volatile("cp.async.bulk.wait_group.read 0;" ::: "memory"); }
        if (aw == 0) TFLUSH();
    }
}

__device__ __forceinline__ uint32_t k_tag(unsigned epoch) { return epoch << 16 | 0x80000000u; }
__device__ __forceinline__ void publish_k(uint4* kp, const uint32_t (&w)[12], unsigned epoch) {
#pragma unroll
    for (int i = 0; i < 3; i++)
        asm volatile("st.relaxed.gpu.global.v4.u32 [%0], {%1,%2,%3,%4};" :: "l"(kp + 32 * i), "r"(w[3 * i]), "r"(w[3 * i + 1]), "r"(w[3 * i + 2]),
                     "r"(__byte_perm(w[9 + (i >> 1)], k_tag(epoch), i == 1 ? 0x7632 : 0x7610)));
}
template <bool FULL>
__device__ __forceinline__ void k_tables(uint32_t kt, int lane, const uint32_t (&w)[12]) {
    const int g = lane >> 2, t = lane & 3, mi = lane >> 3, r8 = lane & 7;
    uint32_t x3 = w[7], re[4], rx[4];
#pragma unroll
    for (int i = 0; i < 4; i++) {
        re[i] = __shfl_sync(0xffffffffu, w[i], lane + 31);
        rx[i] = __shfl_sync(0xffffffffu, w[4 + i], lane + (i == 0 && lane == 29 ? 5 : 1 + 2 * t));
    }
    if (FULL) {
        asm volatile("stmatrix.sync.aligned.m8n8.x2.trans.shared.b16 [%0], {%1,%2};" :: "r"(kt + (KT_D + 7) * 4 + 64 * t + 16 * (mi & 1) + 8 * (r8 & 4)), "r"(w[8]), "r"(w[9]) : "memory");
        if (lane == 2) {
            sts32(kt + (KT_C + 78) * 4, w[10] & 0xffffu);
            sts128(kt + (KT_T + 2) * 4, 0, w[10] & 0xffffu, __byte_perm(w[10], 0, 0x1010), w[10] << 16);
        }
        if (lane == 29) x3 = bsub2(x3, rx[0] & 0xffffu);
    }
#pragma unroll
    for (int i = 0; i < 4; i++) {
        sts64(kt + (16 + 64 * i) * 4 + 8 * lane, __byte_perm(w[i], lane ? re[i] : i ? re[i - 1] : 0, 0x5432), w[i]);
        const uint32_t x = i < 3 ? w[4 + i] : x3, aa = __byte_perm(x, 0, 0x3232);
        if (t < 2) sts128(kt + (272 + 64 * i + 8 * g + 4 * t) * 4, i == 0 && lane == 0 ? __byte_perm(x, re[3], 0x5432) : aa, aa, x,
                          __byte_perm(lane != 29 ? rx[i] : i < 3 ? rx[(i + 1) & 3] : FULL ? 0 : rx[0] << 16, x, 0x5432));
        else if (FULL) sts32(kt + (KT_C - 50 + 8 * i + 32 * t + g) * 4, x);
    }
}

__device__ __forceinline__ void conv_main(const Params& p, uint32_t sb, int warp, int lane0, int bid, unsigned epoch, uint32_t (&w)[12]) {
    asm volatile("setmaxnreg.inc.sync.aligned.u32 168;");
    const int lane = __shfl_sync(0xffffffffu, lane0, lane0);
    const int g = lane >> 2, t = lane & 3, mi = lane >> 3, r8 = lane & 7;
    const int rank = bid & 1;
    const uint32_t bar_y = sb + SC_MISC, bar_v = bar_y + 40;
    next_epoch(p, epoch);
    if (warp < 4) {
        asm volatile("" :: "r"(w[0]), "r"(w[2]), "r"(w[4]), "r"(w[6]), "r"(w[8]), "r"(w[10]) : "memory");
        bar_arrive(BC_KG, 384);
    } else {
        bar_sync(BC_S + swap01(warp), 64);
        const uint4* src = p.s->kp + (8 * bid + warp) * 96 + lane0;
#pragma unroll 1
        for (int it = 0;; it++) {
            uint32_t bad = 0, e[3];
#pragma unroll
            for (int i = 0; i < 3; i++) { const uint4 v = ld_rlx128(src + 32 * i); w[3 * i] = v.x; w[3 * i + 1] = v.y; w[3 * i + 2] = v.z; e[i] = v.w; bad |= v.w ^ k_tag(epoch); }
            w[9] = __byte_perm(e[0], e[1], 0x5410); w[10] = e[2];
            const bool ok = __all_sync(0xffffffffu, bad < 65536);
            if (ok) break;
            if (it > (1 << 20)) give_up();
        }
    }
    if ((warp & 3) == 0) TSTAMP(5 + (warp >> 2));
    k_tables<true>(sb + SC_KT + warp * KT_BYTES, lane0, w);
    asm volatile("barrier.cluster.wait.acquire.aligned;" ::: "memory");
    if (warp < 4)
    bar_sync(BC_S + swap01(warp), 64);
    __syncwarp();
    if ((warp & 3) == 0) TSTAMP(7 + (warp >> 2));
    {
        const uint32_t ut = fresh(sb + SC_UT) + swap01(warp) * UT_STRIDE, kt = fresh(sb + SC_KT) + warp * KT_BYTES;
        uint32_t u1 = ut + (mi & 1) * UT_HALF + (8 + r8) * 16 + (mi >> 1) * 128;
        auto dup = [&](uint32_t v) { return v ^ p.zero; };
        uint32_t kp = kt + (16 + g - 2 * t) * 4;
        float acc[16][4];
        {
            const uint32_t c0 = lds32(kp + 2048), c1 = lds32(kp + 2080), c2 = lds32(kp + 2016), c3 = dup(c0);
            const uint32_t e0 = lds32(kp + (KT_T - 16) * 4), e1 = lds32(kp + (KT_T - 8) * 4), e2 = lds32(kp + (KT_T - 24) * 4), e3 = dup(e0);
            const uint32_t f0 = dup(e1), f1 = lds32(kp + KT_T * 4);
            const uint32_t uo = ut + UT_HALF + (7 + lane) * 16;
#pragma unroll
            for (int i = 0; i < 16; i++) { acc[i][0] = acc[i][1] = acc[i][2] = acc[i][3] = 0.f; }
#pragma unroll
            for (int mu = 0; mu < 8; mu += 4) {
                uint32_t b[4];
                ldsm4(b, uo + 128 * mu);
#pragma unroll
                for (int k = 0; k < 4; k++) mma_bf8(acc[mu + 8 + k], f0, f1, b[k]);
            }
#pragma unroll
            for (int mu = 0; mu < 12; mu += 2) {
                uint32_t b[4];
                ldsm4(b, u1 + 128 * mu);
                mma_bf(acc[mu + 4], c0, c1, c2, c3, b[0], b[1]);
                mma_bf(acc[mu + 5], c0, c1, c2, c3, b[2], b[3]);
                if (mu < 8) { mma_bf(acc[mu + 8], e0, e1, e2, e3, b[0], b[1]); mma_bf(acc[mu + 9], e0, e1, e2, e3, b[2], b[3]); }
            }
        }
        {
            float M[8][4];
#pragma unroll
            for (int i = 0; i < 8; i++) { M[i][0] = M[i][1] = M[i][2] = M[i][3] = 0.f; }
            uint32_t s[8][4], a3[4];
            const uint32_t kb = kp, ub = dup(u1), uc = u1 + (mi >> 1) * 128;
            auto frag = [&](uint32_t (&a)[4], uint32_t x) { a[0] = lds32(x); a[1] = lds32(x + 32); a[2] = lds32(x - 32); a[3] = dup(a[0]); };
            frag(a3, kp + 1536);
#pragma unroll
            for (int i = 1; i < 8; i++) ldsm4(s[i], u1 + (SC_ST - SC_UT) + 256 * i);
            __syncwarp();
#pragma unroll 1
            for (uint32_t ko = 0, uo = 0; ko != 512;) {
                uint32_t a2[4], a1[4], a0[4], b[4][4];
                ko = fresh(ko); uo = fresh(uo);
                kp = kb + ko; u1 = ub + uo;
                const uint32_t up = uc + uo;
                ko += 64; uo -= 16;
                frag(a2, kp + 1024);
#pragma unroll
                for (int i = 1; i < 4; i++) ldsm4(b[i], up + 512 * i);
                asm("ldmatrix.sync.aligned.m8n8.x2.shared.b16 {%0,%1}, [%2];" : "=r"(b[0][2]), "=r"(b[0][3]) : "r"(up + 256));
                frag(a1, kp + 512); frag(a0, kp);
                kp += 64; u1 -= 16;
#pragma unroll
                for (int i = 1; i < 7; i++) mma_bf(acc[2 * i + 2], a3[0], a3[1], a3[2], a3[3], s[i][0], s[i][1]);
#pragma unroll
                for (int e = 0; e < 4; e++) a3[e] = bsub2(a2[e], a3[e]);
#pragma unroll
                for (int i = 1; i < 7; i++) mma_bf(acc[2 * i + 3], a2[0], a2[1], a2[2], a2[3], s[i][2], s[i][3]);
                ldsm4(s[1], u1 + (SC_ST - SC_UT) + 256);
#pragma unroll
                for (int i = 1; i < 7; i++) mma_bf(M[i + 1], a3[0], a3[1], a3[2], a3[3], b[i >> 1][2 * (i & 1)], b[i >> 1][2 * (i & 1) + 1]);
                frag(a3, kp + 1536);
#pragma unroll
                for (int i = 2; i < 8; i++) mma_bf(acc[2 * i], a1[0], a1[1], a1[2], a1[3], s[i][0], s[i][1]);
#pragma unroll
                for (int e = 0; e < 4; e++) a1[e] = bsub2(a0[e], a1[e]);
#pragma unroll
                for (int i = 2; i < 8; i++) { mma_bf(acc[2 * i + 1], a0[0], a0[1], a0[2], a0[3], s[i][2], s[i][3]); ldsm4(s[i], u1 + (SC_ST - SC_UT) + 256 * i); }
#pragma unroll
                for (int i = 2; i < 8; i++) mma_bf(M[i], a1[0], a1[1], a1[2], a1[3], b[i >> 1][2 * (i & 1)], b[i >> 1][2 * (i & 1) + 1]);
            }
            u1 = ub;
#pragma unroll
            for (int i = 2; i < 8; i++)
#pragma unroll
                for (int c = 0; c < 4; c++) { acc[2 * i][c] += M[i][c]; acc[2 * i + 1][c] -= M[i][c]; }
        }
        if ((warp & 3) == 0) TSTAMP(11 + (warp >> 2));
        mbar_wait(bar_v);
        const uint32_t vt = fresh(sb + SC_V) + swap01(warp) * V_STRIDE;
        const uint32_t g1 = fresh(u1) - ut + sb + SC_GT;
        const uint32_t ydst = sb + SC_RT + rank * Y_RS + warp * Y_CS + lane * 16;
        const uint32_t ydr = mapa(ydst, rank ^ 1), ybr = mapa(bar_y, rank ^ 1);
        auto stairs = [&](auto R) {
        uint32_t ug[2][2][4];
        auto ld_ug = [&](int i) { ldsm4t(ug[i & 1][0], u1 + 256 * i); ldsm4t(ug[i & 1][1], g1 + 256 * i); };
        auto ship = [&](int i) {
            const uint32_t (&u)[4] = ug[i & 1][0], (&gg)[4] = ug[i & 1][1];
            const uint32_t y0 = gmix(gg[0], acc[2 * i][0], acc[2 * i][1], u[0]), y1 = gmix(gg[1], acc[2 * i][2], acc[2 * i][3], u[1]);
            const uint32_t y2 = gmix(gg[2], acc[2 * i + 1][0], acc[2 * i + 1][1], u[2]), y3 = gmix(gg[3], acc[2 * i + 1][2], acc[2 * i + 1][3], u[3]);
            if ((i & 1) != R.value) st_async128(ydr + 512 * (i >> 1), y0, y1, y2, y3, ybr + 8 * (i >> 1));
            else asm volatile("{ .reg .pred q; setp.eq.u32 q, %6, 0; st.shared.v4.u32 [%0], {%2,%3,%4,%5}; bar.warp.sync 0xffffffff; @q mbarrier.arrive.shared::cta.b64 _, [%1]; }"
                              :: "r"(ydst + 512 * (i >> 1)), "r"(bar_y + 8 * (i >> 1)), "r"(y0), "r"(y1), "r"(y2), "r"(y3), "r"(lane) : "memory");
        };
        const uint32_t VD = vt + (VC_OFF - 400 - 16 * t) * 4 + (8 * g ^ 16 * (-t & 2)), VD2 = vt + (VC_OFF - 415 - 16 * t) * 4 + (8 * g ^ 16 * (~t & 2));
        uint2 bd[10];
        uint32_t x[2][4][4];
        auto ld4 = [&](uint32_t (&v)[4], int dl) { const uint2 w = lds64(VD + 256 * dl); v[0] = w.x; v[1] = w.y; v[2] = lds32(VD2 + 256 * dl); v[3] = dup(w.x); };
        auto mm4 = [&](const uint32_t (&v)[4], int dl) {
#pragma unroll
            for (int s = dl & 1; s < 10; s += 2) if ((dl + s) / 2 >= 4 && (dl + s) / 2 < 16) mma_bf(acc[(dl + s) / 2], v[0], v[1], v[2], v[3], bd[s].x, bd[s].y);
        };
        const uint32_t KE = kt + (KT_D + g + t) * 4, VE = vt + (VE_BASE - 912 - 16 * t) * 4 + (8 * g ^ 16 * (~t & 2));
        uint32_t b0[8], b1[8];
        auto ld8 = [&](uint32_t (&v)[4], int dl) { const uint2 w = lds64(VE + 512 * dl), z = lds64(VE + 512 * dl - 256); v[0] = w.x; v[1] = w.y; v[2] = z.x; v[3] = z.y; };
        auto mm8 = [&](const uint32_t (&v)[4], int dl, int lo, int hi) {
#pragma unroll
            for (int s = 0; s < 8; s++) if (dl + s >= lo && dl + s < hi) mma_bf(acc[dl + s], v[0], v[1], v[2], v[3], b0[s], b1[s]);
        };
        ld4(x[0][0], 6);
#pragma unroll
        for (int s = 0; s < 10; s++) bd[s] = lds64(kt + (KT_C + 2 * g + 2 * t + 8 * s) * 4);
        mm4(x[0][0], 6);
        uint32_t e[4][4];
#pragma unroll
        for (int k = 1; k < 6; k++) {
#pragma unroll
            for (int j = 0; j < 4; j++) ld4(x[k & 1][j], 4 * k + 3 + j);
            ld_ug(k + 1);
            if (k == 3) {
#pragma unroll
                for (int s = 0; s < 8; s++) { b0[s] = lds32(KE + 32 * s); b1[s] = lds32(KE + 32 * s + 16); }
            }
            if (k > 1) ship(k);
#pragma unroll
            for (int j = 0; j < 4; j++) {
                mm4(x[k & 1][j], 4 * k + 3 + j);
                if (k == 3) { uint32_t v[4], z[4]; ld8(e[j], 8 + j); ld8(v, 12 + j); ld4(z, 30 - j); mm8(v, 12 + j, 12, 16); mm8(e[j], 8 + j, 8, 12); mm4(z, 30 - j); }
                if (k == 5) { ld8(e[j], 8 + j + p.zero); mm8(e[j], 8 + j, 12, 16); }
            }
        }
        ld_ug(7);
        ship(7 - R.value); ship(6 + R.value);
        };
        if (rank) stairs(std::integral_constant<int, 1>()); else stairs(std::integral_constant<int, 0>());
        if ((warp & 3) == 0) TSTAMP(14 + (warp >> 2)); else TSTAMP(21 + warp);
    }
}

constexpr int SF_WD = 73728;
constexpr int SF_RED = 49152;
constexpr int MU_HALF = 640, MU_STRIDE = 1344, SM_RAW = 98304, SM_UT = SM_RAW + 16384, SM_G = SM_UT + 16 * MU_STRIDE, SM_Y = 196608, SM_KT = 138880, SM_KW = SM_G - 49152;
constexpr int SF_XS = 221184;
constexpr int SF_MISC = SF_XS + 8 * 1168;
constexpr int SF_KG = SF_MISC - 10 * KG_STAGE;
constexpr int SF_WR = SF_KG - 2304;
constexpr int FB_X = 64, FB_KDONE = 72, FB_KEYS = 80, FB_FREE = 88  , FB_W = 104, FB_D = FB_W + 72, FB_MU = FB_D + 96, FB_MG = FB_MU + 8, FB_MT = FB_MU + 16, FS_PART = 512, FS_TOK = 896, FS_BM = 1024;
enum { BAR_R = 7, BAR_GU = 8, BAR_RED = 9, BAR_R2 = 10, BAR_X = 11, BAR_G = 12  , BAR_M = 15 };
static_assert(SF_KG % 128 == 0 && NPRE <= 8 && SM_KT + 4 * 2112 <= 147456 && SM_G + MU_STRIDE <= SF_WR - 4 * 9216 && SM_KW + 6 * 2112 >= SM_RAW && SM_KW + 12 * 2112 <= SM_UT, "layout");

__device__ __forceinline__ int mini_ch0(int f) { return f < NW ? 16 * (f - 12) : 32 * (f - NW); }

__device__ __forceinline__ void ffn_front(const Params& p, const CUtensorMap* maps, uint32_t sb, int warp, int lane, int f, unsigned epoch) {
    const unsigned t0 = clock32();
    const int g = lane >> 2, t = lane & 3, mi = lane >> 3, r8 = lane & 7;
    const bool isx = f < NX;
    const int nrw = f < 8 ? 6 : 4, r0 = f < 8 ? 48 * f : 128 + 32 * f;
    const int rw = warp < 12 ? 13 - warp : warp ^ (warp < 14 ? 10 : 15);
    const uint32_t bar_row = sb + SF_MISC  , bar_x = bar_row + FB_X;
    const uint32_t s_part = bar_row + FS_PART  , s_tok = bar_row + FS_TOK  ;
    const uint32_t rows = sb + SF_WR - 9216 * (rw + 1);
    {
#pragma unroll 1
        for (int i = warp < 10 ? 30 : warp - 10; i < 29; i += 6) if (elect()) mbar_init(bar_x + 8 * i, i == 1 ? 4 + (f >= 12) : i < 27 ? 1 : i == 27 ? 2 : f < NW ? 8 : 16);
        const uint32_t bytes = rw < 6 ? 9216 : 1152, dst = rw < 6 ? rows : sb + SF_WR + (rw & 1) * 1152;
        const __nv_bfloat16* src = rw < 6 ? p.u + (size_t)(r0 + 8 * rw) * DM : (rw & 1) ? p.gatew : p.wr;
        if (elect()) { mbar_init(bar_row + 8 * rw, 1); mbar_fence(); mbar_expect(bar_row + 8 * rw, bytes); }
        if (warp == 13) { sts32(s_part + 64 + lane * 4, 0); sts32(bar_row + FS_BM + lane * 4, 0); }
        bar_sync(0, NTHR);
        if (rw < nrw) until(t0, RDELAY);
        if (rw < nrw || rw >= 6) { if (elect()) bulk_g2s(dst, src, bytes, bar_row + 8 * rw); }
    }
    uint4* const kdst = p.s->keys + (lane >> 1) * 128 + 2 * f + (lane & 1);
    if (warp == 15) TSTAMP(1);

    if (warp == 12) {
        if (lane < 22) mbar_expect(bar_row + FB_W + 8 * lane, lane < 9 ? 24576 : lane < 21 ? 12288 : f < NW ? 16384 : 32768);
        if (elect()) { prefetch_map(maps + 1); prefetch_map(maps + 2); prefetch_map(maps + (isx ? 3 : 5)); }
        unsigned tb = t0 + WDELAY;
        auto pieces = [&](int n, int end, uint32_t dst) {
#pragma unroll 1
            for (; n < end; n++, dst += 12288) {
                until(tb, 0); tb += WGAP;
                if (elect()) tma3d(dst, maps + 1 + (n & 1), 0, 64 * (n >> 1), 3 * f, bar_row + FB_W + 8 * (n >> 1));
            }
        };
        if (!isx) {
            until(t0, MDELAY);
#pragma unroll 1
            for (int k = f >= NW; k >= 0; k--) if (elect()) tma4d(sb + SM_RAW - 49152 * k, maps + 5, mini_ch0(f) + 16 * k, 0, 0, 0, bar_row + FB_MU);
            if (f >= NW) return;
        }
#pragma unroll 1
        for (int i = 0; i < 4; i++) {
            if (i == 1) { mbar_wait(bar_row + FB_KEYS); mbar_wait(bar_row + FB_KDONE); tb = clock32() + RESUME; }
            if (i == 3) mbar_wait(bar_row + FB_FREE);
            const int n = ((0x0c080000 + NPRE * 256) >> (8 * i)) & 255;
            pieces(n, ((0x120c0800 + NPRE) >> (8 * i)) & 255, sb + 12288 * (((0x000c0000 + NPRE * 256) >> (8 * i)) & 255));
        }
        TSTAMP(12);
        if (isx) {
#pragma unroll 1
            for (int i = 0; i < 12; i++) {
                const int n = (0x987610ba5432ull >> (4 * i)) & 15;
                if (i == 6) mbar_wait(bar_row + FB_FREE + 8);
                until(tb, 0); tb += DGAP;
                if (elect()) tma2d(sb + SF_WD + n * 12288, maps + 3, 32 * (f >> 1), 2304 * (f & 1) + 192 * n, bar_row + FB_D + 8 * n);
            }
            TSTAMP(13);
        }
    } else if (warp == 13) {
        const uint32_t tag = key_tag(epoch), par = (epoch & 1) ? 0u : 0x8000u;
        stg128(kdst, 0, 0, 0, 0);
        if (lane < 8 && isx && !(f & 1)) st_rlx32(&p.s->sel[32 * f + lane], 0);
        bar_sync(BAR_R, 32 * (nrw + 1));
        TSTAMP(3);
        {
            const uint32_t sg = fresh(s_part) + 192 + lane * 4;
            const uint32_t gb = pack_bf16(sigmoidf_(rbf(__uint_as_float(lds32(sg)))), sigmoidf_(rbf(__uint_as_float(lds32(sg + 128))))) | par | (par << 16);
            asm volatile("st.relaxed.gpu.global.u16 [%0], %1;" :: "l"(p.s->gate + r0 + lane), "h"((unsigned short)gb) : "memory");
            if (nrw > 4 && lane < 16) asm volatile("st.relaxed.gpu.global.u16 [%0], %1;" :: "l"(p.s->gate + r0 + 32 + lane), "h"((unsigned short)(gb >> 16)) : "memory");
        }
        bar_sync(BAR_R2, 32 * (nrw + 1));
        {
            const uint4 v = lds128(fresh(s_tok) + (lane & 1) * 16);
            asm volatile("st.relaxed.gpu.global.v4.u32 [%0], {%1,%2,%3,%4};" :: "l"(kdst), "r"(v.x | tag), "r"(v.y | tag), "r"(v.z | tag), "r"(v.w | tag) : "memory");
        }
        TSTAMP(4);
        if (lane == 0) { mbar_arrive(bar_row + FB_KEYS); mbar_expect(bar_x, 8 * 1152); }
        if (f >= NW) return;
        uint32_t k[16];
        const uint4* src = p.s->keys + (f & 15) * 128 + lane;
#pragma unroll 1
        for (int it = 0;; it++) {
            uint32_t bad = 0;
#pragma unroll
            for (int i = 0; i < 4; i++) {
                const uint4 x = ld_rlx128(src + (i < 3 || lane < 24 ? 32 * i : 64));
                k[i] = x.x; k[4 + i] = x.y; k[8 + i] = x.z; k[12 + i] = x.w;
                bad |= x.x ^ tag;
            }
            const bool ok = __all_sync(0xffffffffu, (bad & 0xf800u) == 0);
            if (ok) break;
            if (it > (1 << 20)) give_up();
        }
        TSTAMP(5);
        uint32_t key = 0;
#pragma unroll 2
        for (int r = 0; r < 8; r++) {
            const uint32_t m = __reduce_max_sync(0xffffffffu, max(max(k[0], k[1]), max(k[2], k[3])));
#pragma unroll
            for (int i = 0; i < 4; i++) {
                const bool pop = k[i] == m;
                k[i] = pop ? k[4 + i] : k[i]; k[4 + i] = pop ? k[8 + i] : k[4 + i]; k[8 + i] = pop ? k[12 + i] : k[8 + i]; k[12 + i] = pop ? 0 : k[12 + i];
            }
            if (r8 == r) key = m;
        }
        const int row = key_row(key);
        sts32(s_tok + r8 * 8, row);
        bar_arrive(BAR_X, 160);
        TSTAMP(6);
        if (isx) {
            if (!(f & 1)) {
                __nv_bfloat16* o = p.out + (size_t)row * DM + 16 * f + 8 * mi;
                asm volatile("st.relaxed.gpu.global.v4.u32 [%0], {%1,%1,%1,%1};" :: "l"(o), "r"(0) : "memory");
                if (__any_sync(0xffffffffu, ld_rlx32(o) != 0)) give_up();
                if (lane < 8) st_rlx32(&p.s->sel[32 * f + lane], key);
            } else wait_sel(p, f >> 1, r8, tag);
            uint32_t gb;
#pragma unroll 1
            for (int it = 0;; it++) {
                asm volatile("ld.relaxed.gpu.global.u16 %0, [%1];" : "=r"(gb) : "l"(p.s->gate + row) : "memory");
                gb ^= par;
                if (!(gb & 0x8000u)) break;
                if (it > (1 << 20)) give_up();
            }
            const uint32_t rb = key ^ 0x80000000u, rv = (rb ^ (((int)rb >> 31) & 0x7fff0000u)) & 0xffff0000u;
            sts32(s_tok + r8 * 8 + 4, __float_as_uint(rbf(1.0f - bf_lo(gb)) * rbf(sigmoidf_(__uint_as_float(rv)))));
            __syncwarp();
            TSTAMP(7);
            bar_arrive(BAR_RED, 416);
        }
    } else {
        if (rw < nrw) {
            float c[3][4];
#pragma unroll
            for (int i = 0; i < 3; i++) { c[i][0] = c[i][1] = c[i][2] = c[i][3] = 0.f; }
            mbar_wait(bar_row + 48); mbar_wait(bar_row + 56);
            const uint32_t b = fresh(sb + SF_WR) + (g & 1) * 1152 + (g >> 2) * 64 + t * 16 + (g & 2) * 2;
            uint32_t w[18][2];
#pragma unroll
            for (int kb = 0; kb < 18; kb++) { const uint32_t o = ((kb & 1) ? b ^ 64 : b) + 128 * (kb >> 1); w[kb][0] = lds32(o); w[kb][1] = lds32(o + 8); }
            mbar_wait(bar_row + 8 * rw);
            if (warp == 15) TSTAMP(2);
            const uint32_t a = fresh(rows) + g * 1152 + (g & 1) * 64 + t * 16;
#pragma unroll
            for (int kb = 0; kb < 18; kb++) {
                const uint4 x = lds128(((kb & 1) ? a ^ 64 : a) + 128 * (kb >> 1));
                mma_bf(c[kb % 3], x.x, x.y, x.z, x.w, w[kb][0], w[kb][1]);
            }
            const float sr = c[0][0] + c[1][0] + c[2][0] + __shfl_down_sync(0xffffffffu, c[0][2] + c[1][2] + c[2][2], 1);
            const float sg = c[0][1] + c[1][1] + c[2][1] + __shfl_down_sync(0xffffffffu, c[0][3] + c[1][3] + c[2][3], 1);
            const uint32_t rb = pack_bf16(0.f, sr);
            if (t == 2 * (g & 1)) {
                sts32(s_part + (8 * rw + g) * 4, (rb ^ (((int)rb >> 31) & 0x7fff0000u) ^ 0x80000000u) | (uint32_t)(2047 - r0 - 8 * rw - g));
                sts32(s_part + 192 + (8 * rw + g) * 4, __float_as_uint(sg));
            }
            __syncwarp();
            bar_sync(BAR_R, 32 * (nrw + 1));
            const uint32_t sk = fresh(s_part), kk = lds32(sk + (8 * rw + r8) * 4);
            int n = 0;
#pragma unroll
            for (int i = 0; i < 3; i++) { const uint4 v = lds128(sk + mi * 48 + 16 * i); n += (v.x > kk) + (v.y > kk) + (v.z > kk) + (v.w > kk); }
            n += __shfl_xor_sync(0xffffffffu, n, 8); n += __shfl_xor_sync(0xffffffffu, n, 16);
            if (n < 8) sts32(s_tok + 4 * n, kk);
            __syncwarp();
            bar_arrive(BAR_R2, 32 * (nrw + 1));
        }
    }
}

__device__ __forceinline__ void ffn_work(const Params& p, uint32_t sb, int warp, int lane, int f, unsigned epoch) {
    const int g = lane >> 2, t = lane & 3, mi = lane >> 3, r8 = lane & 7;
    const bool isx = f < NX;
    const uint32_t bar_x = sb + SF_MISC + FB_X, bar_free = sb + SF_MISC + FB_FREE, bar_w = sb + SF_MISC + FB_W, bar_d = sb + SF_MISC + FB_D, s_tok = sb + SF_MISC + FS_TOK;
    uint32_t fr[24][4];
    auto pin = [&] {
#pragma unroll
        for (int i = 0; i < 24; i += 8) asm volatile("" :: "r"(fr[i][0]), "r"(fr[i + 1][0]), "r"(fr[i + 2][0]), "r"(fr[i + 3][0]), "r"(fr[i + 4][0]), "r"(fr[i + 5][0]), "r"(fr[i + 6][0]), "r"(fr[i + 7][0]) : "memory");
    };
    {
        const int j = (unsigned)(warp - 4) < 6, w = warp - (j ? 4 : warp < 4 ? 0 : 6);
        float ag[2][4], au[2][4];
#pragma unroll
        for (int i = 0; i < 2; i++) { ag[i][0] = ag[i][1] = ag[i][2] = ag[i][3] = 0.f; au[i][0] = au[i][1] = au[i][2] = au[i][3] = 0.f; }
        const uint32_t wb = sb + (w >> 1) * 4096 + (r8 + 8 * (mi >> 1)) * 64 + (((2 * (w & 1) + (mi & 1)) ^ (r8 >> 1)) << 4);
        const uint32_t xb = sb + SF_XS + r8 * 1168 + mi * 16;
        auto load = [&](int i, int n, int place) {
            mbar_wait(bar_w + 8 * n);
            const uint32_t wk = fresh(wb) + place * 24576;
#pragma unroll
            for (int s = 0; s < 4; s++) { ldsm4t(fr[8 * i + s], wk + 1024 * s); ldsm4t(fr[8 * i + 4 + s], wk + 1024 * s + 12288); }
        };
        auto mul = [&](int i, uint32_t xk) {
            uint32_t x[2][4];
            ldsm4(x[0], xk); ldsm4(x[1], xk + 64);
#pragma unroll
            for (int s = 0; s < 4; s++) {
                const uint32_t (&a)[4] = fr[8 * i + s], (&b)[4] = fr[8 * i + 4 + s];
                mma_bf(ag[s & 1], a[0], a[1], a[2], a[3], x[s >> 1][2 * (s & 1)], x[s >> 1][2 * (s & 1) + 1]);
                mma_bf(au[s & 1], b[0], b[1], b[2], b[3], x[s >> 1][2 * (s & 1)], x[s >> 1][2 * (s & 1) + 1]);
            }
        };
#pragma unroll
        for (int i = 0; i < 3; i++) load(i, 3 * j + i, (i ? 5 : 3) * j + i);
        pin();
        bar_sync(BAR_G + j, 192);
        if (w == 0 && lane == 0) mbar_arrive(bar_free + 8 * j);
        if (warp < 4) {
            bar_sync(BAR_X, 160);
            const uint32_t rows = lds32(fresh(s_tok) + 8 * r8);
#pragma unroll 1
            for (int i = warp; i < 8; i += 4) {
                const int row = __shfl_sync(0xffffffffu, rows, i);
                if (elect()) bulk_g2s(sb + SF_XS + i * 1168, p.u + (size_t)row * DM, 1152, bar_x);
                __syncwarp();
            }
        }
        mbar_wait(bar_x);
        if (warp == 0) TSTAMP(8);
        {
            const uint32_t xk = fresh(xb) + 384 * j;
#pragma unroll
            for (int i = 0; i < 3; i++) { mul(i, (i ? fresh(xk) : xk) + 128 * i); if (i == 0) { asm volatile("" :: "f"(ag[0][0]), "f"(ag[1][0]), "f"(au[0][0]), "f"(au[1][0])); sts32(s_tok + 64, clock32()); } }
        }
#pragma unroll 1
        for (int n = 6 + j; n < 9; n += 2) { load(0, n, n - 6); mul(0, fresh(xb) + 128 * n); }
#pragma unroll
        for (int c = 0; c < 4; c++) { ag[0][c] += ag[1][c]; au[0][c] += au[1][c]; }
        if (j) {
            sts128(wb + 24576, __float_as_uint(ag[0][0]), __float_as_uint(ag[0][1]), __float_as_uint(ag[0][2]), __float_as_uint(ag[0][3]));
            sts128(wb + 25600, __float_as_uint(au[0][0]), __float_as_uint(au[0][1]), __float_as_uint(au[0][2]), __float_as_uint(au[0][3]));
        }
        bar_sync(BAR_GU, 384);
        if (!j) {
            const uint32_t sf = fresh(wb);
            const uint4 g1 = lds128(sf + 24576), u1 = lds128(sf + 25600);
            const uint32_t gs[4] = {g1.x, g1.y, g1.z, g1.w}, us[4] = {u1.x, u1.y, u1.z, u1.w};
            if (warp == 0) TSTAMP(9);
            float h[4];
#pragma unroll
            for (int c = 0; c < 4; c++) {
                const float gv = rbf(ag[0][c] + __uint_as_float(gs[c]));
                h[c] = rbf(gv * sigmoidf_(gv)) * rbf(au[0][c] + __uint_as_float(us[c]));
            }
            uint32_t h0, h1;
            asm("movmatrix.sync.aligned.m8n8.trans.b16 %0, %1;" : "=r"(h0) : "r"(pack_bf16(h[0], h[1])));
            asm("movmatrix.sync.aligned.m8n8.trans.b16 %0, %1;" : "=r"(h1) : "r"(pack_bf16(h[2], h[3])));
            if (h0 == 0) h0 = 0x8000u;
            asm volatile("{ .reg .b64 v; mov.b64 v, {%1, %2}; st.relaxed.gpu.global.b64 [%0], v; }" :: "l"(p.s->h + ((epoch & 1) * 288 + 6 * f + w) * 32 + lane), "r"(h0), "r"(h1) : "memory");
        }
        if (isx) {
            if (warp == 0) TSTAMP(10);
            const uint2* hsrc = p.s->h + ((epoch & 1) * 288 + 144 * (f & 1) + 12 * warp) * 32 + lane;
            uint2 hb[12];
            auto ldh = [&](int s) { asm volatile("ld.relaxed.gpu.global.v2.u32 {%0, %1}, [%2];" : "=r"(hb[s].x), "=r"(hb[s].y) : "l"(hsrc + 32 * s) : "memory"); };
#pragma unroll
            for (int s = 0; s < 12; s++) ldh(s);
#pragma unroll 1
            for (int it = 0;; it++) {
                bool again = false;
#pragma unroll
                for (int s = 0; s < 12; s += 2) if (__any_sync(0xffffffffu, min(hb[s].x, hb[s + 1].x) == 0)) { ldh(s); ldh(s + 1); again = true; }
                if (!again) break;
                if (it > (1 << 16)) give_up();
            }
            if (warp == 0) TSTAMP(11);
            mbar_wait(bar_d + 8 * warp);
            if (warp == 9) TSTAMP(14);
            float ad[2][2][4];
#pragma unroll
            for (int i = 0; i < 4; i++) { ad[i >> 1][i & 1][0] = ad[i >> 1][i & 1][1] = ad[i >> 1][i & 1][2] = ad[i >> 1][i & 1][3] = 0.f; }
            const uint32_t wd = fresh(sb) + SF_WD + warp * 12288 + (r8 + 8 * (mi >> 1)) * 64 + (((mi & 1) ^ (r8 >> 1)) << 4);
#pragma unroll
            for (int s = 0; s < 12; s++) {
                uint32_t a[4], b[4];
                ldsm4t(a, wd + 1024 * s); ldsm4t(b, (wd ^ 32) + 1024 * s);
                mma_bf(ad[0][s & 1], a[0], a[1], a[2], a[3], hb[s].x, hb[s].y);
                mma_bf(ad[1][s & 1], b[0], b[1], b[2], b[3], hb[s].x, hb[s].y);
            }
            const uint32_t rd = sb + SF_RED + warp * 1152 + (72 * t + g) * 4;
#pragma unroll
            for (int i = 0; i < 8; i++) sts32(rd + (i >> 2) * 64 + (i & 1) * 144 + ((i >> 1) & 1) * 32, __float_as_uint(ad[i >> 2][0][i & 3] + ad[i >> 2][1][i & 3]));
            bar_sync(BAR_RED, 416);
            if (warp < 4) {
                const int tid = 32 * warp + lane;
                const uint32_t rs = fresh(sb + SF_RED) + (tid >> 4) * 144 + (tid & 15) * 8;
                const uint2 tk = lds64(fresh(s_tok) + (tid >> 4) * 8);
                float x = 0.f, y = 0.f;
#pragma unroll
                for (int w = 0; w < 12; w++) { const uint2 v = lds64(rs + w * 1152); x += __uint_as_float(v.x); y += __uint_as_float(v.y); }
                asm volatile("red.relaxed.gpu.global.add.noftz.bf16x2 [%0], %1;" :: "l"(p.out + (size_t)tk.x * DM + 32 * (f >> 1) + 2 * (tid & 15)),
                             "r"(pack_bf16(x * __uint_as_float(tk.y), y * __uint_as_float(tk.y))) : "memory");
            }
            if (warp == 0) { TSTAMP(15); TFLUSH(); }
            asm volatile("exit;"); __builtin_unreachable();
        }
    }
}

__device__ __forceinline__ void fetch_k(const uint4* src, uint64_t (&v)[6], uint32_t a, uint32_t b) {
    asm volatile("{ .reg .pred p; setp.eq.u32 p, %7, %8; @p ld.relaxed.gpu.global.v2.u64 {%0,%1}, [%6]; @p ld.relaxed.gpu.global.v2.u64 {%2,%3}, [%6 + 512]; @p ld.relaxed.gpu.global.v2.u64 {%4,%5}, [%6 + 1024]; }"
                 : "+l"(v[0]), "+l"(v[1]), "+l"(v[2]), "+l"(v[3]), "+l"(v[4]), "+l"(v[5]) : "l"(src), "r"(a), "r"(b));
}
__device__ __forceinline__ uint32_t mini_conv(const Params& p, uint32_t sb, int warp, int lane, int f, unsigned epoch) {
    const int g = lane >> 2, t = lane & 3, mi = lane >> 3, r8 = lane & 7;
    const uint32_t fb = sb + SF_MISC, kt = sb + (warp >= 12 ? SM_KT - 12 * 2112 : f < NW ? SM_KW + 2 * 2112 : SM_KW) + warp * 2112;
    const bool ism = f >= NW;
    const int ch0 = mini_ch0(f);
    uint32_t seq = 128, key;
    uint64_t v[6] = {};
    const uint4* src = p.s->kp + lane;
    auto hi = [&](int i) { return (uint32_t)(v[i] >> 32); };
    if (f >= (warp < 4 ? NW : NX)) {
    {
        const uint32_t c = 36 + (warp & 3) + 2 * (warp & 12), y = (uint32_t)((warp < 8 ? 0xa026802400000000ull : 0x2a2e00280080a22cull) >> ((8 * warp) & 48)) & 0xffff;
        seq = ism ? 0x101 * c - 0x400 : y + (warp & 1) * ((y >> 5) & 0x101);
        src += (ch0 + (seq & 31)) * 96;
    }
    if (seq & 32) {
        if (seq & 4) {
            const int q = (seq & 3) + ((seq >> 1) & 4);
            const uint32_t ab = sb - 3072 * (seq & 16), d = ab + SM_UT + g * MU_STRIDE + (8 + 4 * q + t) * 16;
            sts128(ab + SM_UT + (2 * q + (mi >> 1)) * MU_STRIDE + (mi & 1) * MU_HALF + r8 * 16, 0, 0, 0, 0);
            mbar_wait(fb + FB_MU);
            if (warp == 15) TSTAMP(16);
            const uint32_t a = fresh(ab + SM_RAW) + q * 2048 + (8 * mi + 4 * (r8 & 1) + (r8 >> 1)) * 32 + ((r8 & 1) << 4);
            uint32_t x[4][4];
#pragma unroll
            for (int i = 0; i < 4; i++) ldsm4t(x[i], (i & 2 ? a ^ 16 : a) + 1024 * (i & 1));
#pragma unroll
            for (int i = 0; i < 4; i++) sts128(d + (i & 1) * MU_HALF + (i & 2) * 4 * MU_STRIDE, x[i][0], x[i][1], x[i][2], x[i][3]);
            __syncwarp();
            if (lane == 0) mbar_arrive(fb + FB_MT);
        }
        if (!EFETCH) mbar_wait(fb + FB_KDONE);
        fetch_k(src, v, 0, 0);
        if (EFETCH) mbar_wait(fb + FB_KDONE);
        if ((warp | 2) == GW) { fetch_gates(p, (warp >> 1) & 1, lane, epoch, sb + SM_G + (lane & 1) * MU_HALF); __syncwarp(); if (lane == 0) mbar_arrive(fb + FB_MG); }
        mbar_wait(fb + FB_KEYS);
        if (warp == TW) TSTAMP(17);
    }
    }
    const uint32_t lo = (mi & 1) * MU_HALF + (8 + r8) * 16 + (mi >> 1) * 128;
#pragma unroll 1
    do {
        const int c = seq & 31;
        if (seq & 32) {
#pragma unroll 1
        for (int it = 0; !__all_sync(0xffffffffu, ((hi(1) ^ k_tag(epoch)) | (hi(3) ^ k_tag(epoch)) | (hi(5) ^ k_tag(epoch)) | ((uint32_t)v[5] & p.zero)) < 65536); it++) {
            fetch_k(src, v, 0, 0);
            if (it > (1 << 20)) give_up();
        }
        mbar_wait(fb + FB_MT);
        sts128(kt + t * 16, 0, 0, 0, 0);
        if (warp == TW) TSTAMP(seq >> 8 ? 7 : 10);
        const uint32_t w[12] = {(uint32_t)v[0], hi(0), (uint32_t)v[1], (uint32_t)v[2], hi(2), (uint32_t)v[3], (uint32_t)v[4], hi(4), 0, 0, 0, 0};
        k_tables<false>(fresh(kt), fresh(lane), w);
        }
        __syncwarp();
        if (seq & 128) ffn_work(p, sb, warp, fresh(lane), f, epoch);
        if (!(seq & 32)) return 0;
        const uint32_t ab = sb - 49152 * (c >> 4), kb = fresh(kt) + (16 + g - 2 * t) * 4, ub = fresh(ab + SM_UT + (c & 15) * MU_STRIDE) + lo;
        const uint32_t yd = ab + SM_Y + (c & 15) * 1056 + (c & 8) * 8 + lane * 16;
        uint32_t kp = kb, u1 = ub;
        if (warp == TW && !(seq >> 8)) TSTAMP(13);
        seq >>= 8;
        src += ((int)(seq & 31) - c) * 96;
#pragma unroll
        for (int i = 0; i < 6; i++) v[i] = 0;
        key = 0;
        float acc[8][4];
#pragma unroll
        for (int i = 0; i < 8; i++) { acc[i][0] = acc[i][1] = acc[i][2] = acc[i][3] = 0.f; }
        uint32_t a[4][4], b[2][2][4];
        auto lda = [&](int j, int o) { const uint32_t x = kp + 64 * o + 512 * j; a[j][2] = o ? a[j][1] ^ p.zero : lds32((kp ^ p.zero) + 512 * j - 32); a[j][0] = lds32(x); a[j][1] = lds32(x + 32); a[j][3] = a[j][0] ^ p.zero; };
        auto ldb = [&](int s, int o) { ldsm4(b[s][0], u1 - 16 * o); ldsm4(b[s][1], u1 + 256 - 16 * o); };
        ldb(0, 0);
#pragma unroll
        for (int j = 0; j < 4; j++) lda(j, 0);
#pragma unroll
        for (int s = 0; s < 8; s++) {
            if (s == FPOS) {
                const uint32_t e = seq | (__float_as_uint(acc[0][0]) & p.zero);
                fetch_k(src, v, e & 32, 32);
                if (KEYPF) asm volatile("{ .reg .pred p; setp.eq.u32 p, %2, 0; @p ld.relaxed.gpu.global.u32 %0, [%1]; }" : "+r"(key) : "l"(&p.s->sel[(ch0 >> 5) * 64 + r8]), "r"(e));
            }
            if (s < 7) ldb(~s & 1, s + 1);
#pragma unroll
            for (int i = 0; i < 4; i++) {
                const int j = (i >> 1) + 2 * (i & 1);
#pragma unroll
                for (int mu = 3 - j; mu >= 0; mu--) mma_bf(acc[NACC == 8 && j + mu == 3 && (j & 1) ? 6 + (j >> 1) : j + mu + (j & 2)], a[j][0], a[j][1], a[j][2], a[j][3], b[s & 1][mu >> 1][2 * (mu & 1)], b[s & 1][mu >> 1][2 * (mu & 1) + 1]);
                if (s < 7) lda(j, s + 1);
            }
        }
        if (warp == TW && !seq) TSTAMP(14);
        mbar_wait(fb + FB_MG);
#pragma unroll
        for (int e = 0; e < 4; e++) { acc[2][e] += acc[4][e]; acc[3][e] += acc[5][e]; if (NACC == 8) acc[3][e] += acc[6][e] + acc[7][e]; }
        uint32_t ug[4][4];
#pragma unroll
        for (int i = 0; i < 2; i++) { ldsm4t(ug[i], ub + 256 * i); ldsm4t(ug[2 + i], fresh(sb + SM_G) + lo + 256 * i); }
#pragma unroll
        for (int i = 0; i < 2; i++) {
            const uint32_t (&u)[4] = ug[i], (&gg)[4] = ug[2 + i];
            sts128(yd + 512 * i, gmix(gg[0], acc[2 * i][0], acc[2 * i][1], u[0]), gmix(gg[1], acc[2 * i][2], acc[2 * i][3], u[1]),
                   gmix(gg[2], acc[2 * i + 1][0], acc[2 * i + 1][1], u[2]), gmix(gg[3], acc[2 * i + 1][2], acc[2 * i + 1][3], u[3]));
        }
        __syncwarp();
        if (warp == TW) TSTAMP(18 + (seq != 0));
    } while (seq);
    if (warp >= 12) TSTAMP(12 + warp);
    return key;
}
__device__ __forceinline__ void mini_out(const Params& p, const CUtensorMap* maps, uint32_t sb, int warp, int lane, int f, unsigned epoch, uint32_t key) {
    const int g = lane >> 2, t = lane & 3, mi = lane >> 3, r8 = lane & 7;
    const uint32_t fb = sb + SF_MISC;
    const bool ism = f >= NW;
    const int ch0 = mini_ch0(f);
    const int k = ism ? warp >> 3 : 0;
    uint32_t first = 1;
    if (lane == 0) asm volatile("atom.shared.exch.b32 %0, [%1], 1;" : "=r"(first) : "r"(fb + FS_BM + 64 + 4 * k) : "memory");
    if (!__all_sync(0xffffffffu, first)) {
        if (elect()) prefetch_map(maps + 4);
        const int row = key_row(wait_sel(p, ch0 >> 5, r8, key_tag(epoch), key));
        if (row < 512) asm volatile("red.shared.or.b32 [%0], %1;" :: "r"(fb + FS_BM + (row >> 5) * 4), "r"(1u << (row & 31)) : "memory");
    }
    const int m = warp & 7, dr = 128 * (g >> 2) + 32 * (t >> 1) + 16 * (g & 1) + 8 * ((g >> 1) & 1);
    const uint32_t y = SM_Y + ((r8 >> 1) & 1) * 8512 + (2 * mi + (r8 & 1)) * 1056 + (2 * m + (r8 >> 2)) * 16;
    const uint32_t so = (g >> 1) * 256 + (t >> 1) * 64 + (g & 1) * 32 + (t & 1) * 16;
    bar_sync(BAR_M - k, ism ? 256 : NTHR);
#pragma unroll 1
    for (int h = ism ? 0 : warp >> 3;; h++) {
        const int r0 = 256 * h + 64 * (m & 1) + (m >> 1), row = r0 + dr;
        const uint32_t bm = lds32(fresh(fb) + FS_BM + (row >> 5) * 4) >> (row & 31), ab = fresh(sb - 49152 * k + 512 * h), stg = ab + SM_UT + 2048 * m + 512 * h;
        uint32_t x[2][4];
        ldsm4t(x[0], ab + y); ldsm4t(x[1], ab + y + 256);
        if (warp == 0 && x[0][0] != 0x12345) TSTAMP(28);
        if (__any_sync(0xffffffffu, bm & 0x11u)) {
#pragma unroll
            for (int i = 0; i < 2; i++) store_or_add(p.out + (size_t)(row + 4 * i) * DM + ch0 + 16 * k + 8 * (t & 1), x[i], bm & (1u << (4 * i)));
        } else {
#pragma unroll
            for (int i = 0; i < 2; i++) sts128(stg + so + 128 * i, x[i][0], x[i][1], x[i][2], x[i][3]);
            asm volatile("fence.proxy.async.shared::cta;" ::: "memory");
            __syncwarp();
            if (elect()) store_rows(maps + 4, stg, ch0 + 16 * k, r0);
        }
        if (h >= ism) break;
    }
    if (elect()) { asm volatile("cp.async.bulk.commit_group;" ::: "memory"); asm volatile("cp.async.bulk.wait_group.read 0;" ::: "memory"); }
    if (warp == 8) TSTAMP(11);
    if (warp == 0) { TSTAMP(15); TFLUSH(); }
}

constexpr int SMEM_BYTES = 232448;
static_assert(SF_MISC + 1152 <= 232192, "layout");

struct Maps { CUtensorMap m[6]; };

__global__ void __cluster_dims__(2, 1, 1) __launch_bounds__(NTHR, 1)
fused_kernel(const Params p, const __grid_constant__ Maps maps) {
    extern __shared__ __align__(1024) uint8_t smem_raw[];
    uint32_t q[8];
    {
        const int b = blockIdx.x, x = threadIdx.x, rc = 4 * b + max(b - 84, 0) - 288 + (x >> 6);
        const int cv = (b - NCONV) >> 31, ca = 8 * b + ((x >> 5) & 3), cb = 2 * rc - (rc & 3) + 4;
        const uint32_t ch = (ca & cv) | (cb & ~cv), o = NST * ch + 2 * ((x & 31) + ((x >> (cv & 2)) & 32));
        const bool c = x < (b < 84 ? 256 : 320);
        q[6] = ldg16_if(c, p.logdt + ch);
        q[2] = ldg32_if(c, p.Bre + o); q[3] = ldg32_if(c, p.Bim + o); q[4] = ldg32_if(c, p.Cre + o); q[5] = ldg32_if(c, p.Cim + o); q[0] = ldg32_if(c, p.Are + o); q[1] = ldg32_if(c, p.Aim + o);
        q[7] = ldg16_if(c, p.Dskip + ch);
    }
    const unsigned epoch = ld_rlx32(&p.s->epoch[blockIdx.x * 16 + (threadIdx.x >> 5)]);
    const uint32_t sb = __shfl_sync(0xffffffffu, smem_u32(smem_raw), 0);
    const int warp = __shfl_sync(0xffffffffu, threadIdx.x >> 5, 0), bid = __shfl_sync(0xffffffffu, blockIdx.x, 0);
    const int lane = __shfl_sync(0xffffffffu, threadIdx.x & 31, threadIdx.x);
    const bool conv = bid < NCONV;
    const int f = bid - NCONV;
    uint32_t w[12];
    if (warp < (f < 12 ? 8 : 10)) {
        const int half = conv ? warp >> 2 : warp & 1, pr = conv ? warp & 3 : warp >> 1;
        const int rc = 4 * f + max(f - 12, 0) + pr;
        const uint32_t stage = sb + (conv ? SC_KG : SF_KG) + warp * KG_STAGE;
        uint4* const kp = p.s->kp + (conv ? 8 * bid + pr : 2 * rc - (rc & 3) + 4) * 96 + lane;
        kgen(q, sb, half, stage, stage + (conv ? 4 : 1) * KG_STAGE, 1 + pr, lane, p.zero, w, [&] {
            sts128z_if(conv && lane < 20, sb + SC_KT + warp * KT_BYTES + lane * 16 + (lane < 4 ? 0 : lane < 14 ? 2048 : 2288));
            stg128z_if(!conv, kp + 64 * half); stg128z_if(!half && !conv, kp + 32);
            stg128z_if((unsigned)f < NW && warp < 6, (uint4*)(p.s->h + ((lane >> 4) * 288 + 6 * f + warp) * 32) + (lane & 15));
            if (conv) asm volatile("barrier.cluster.arrive.relaxed.aligned;" ::: "memory"); else bar_sync(0, NTHR);
        });
        if (!half) publish_k(kp, w, epoch);
        if (conv) { conv_main(p, sb, warp, lane, bid, epoch, w); return; }
        {
            if (!half && lane == 0) mbar_arrive(sb + SF_MISC + FB_KDONE);
            if (warp == 0) TSTAMP(22);
            if (warp == 2) TSTAMP(23);
        }
    } else if (conv) {
        conv_aux(p, maps.m, sb, warp - 8, lane, bid, epoch);
        return;
    } else {
        ffn_front(p, maps.m, sb, warp, lane, f, epoch);
    }
    converged();
    next_epoch(p, epoch);
    if (warp >= 12 && f < NX) return;
    mini_out(p, maps.m, sb, warp, lane, f, epoch, mini_conv(p, sb, warp, __shfl_sync(0xffffffffu, lane, lane), f, epoch));
}

typedef CUresult (*EncodeFn)(CUtensorMap*, CUtensorMapDataType, cuuint32_t, void*, const cuuint64_t*, const cuuint64_t*, const cuuint32_t*, const cuuint32_t*,
                             CUtensorMapInterleave, CUtensorMapSwizzle, CUtensorMapL2promotion, CUtensorMapFloatOOBfill);

void make_map(EncodeFn fn, CUtensorMap* m, const void* base, int rank, const cuuint64_t* dims, const cuuint64_t* strides, const cuuint32_t* box, CUtensorMapSwizzle sw) {
    const cuuint32_t es[5] = {1, 1, 1, 1, 1};
    fn(m, CU_TENSOR_MAP_DATA_TYPE_BFLOAT16, rank, (void*)base, dims, strides, box, es, CU_TENSOR_MAP_INTERLEAVE_NONE, sw,
       CU_TENSOR_MAP_L2_PROMOTION_NONE, CU_TENSOR_MAP_FLOAT_OOB_FILL_NONE);
}

}

extern "C" void kernel_launch(void* const* d_in, const int* in_sizes, int n_in, void* d_out, int out_size) {
    (void)in_sizes; (void)n_in; (void)out_size;
    static EncodeFn fn = nullptr;
    static void* scratch = nullptr;
    if (!fn) {
        void* ptr = nullptr; cudaDriverEntryPointQueryResult qr;
        cudaGetDriverEntryPoint("cuTensorMapEncodeTiled", &ptr, cudaEnableDefault, &qr);
        fn = (EncodeFn)ptr;
        cudaGetSymbolAddress(&scratch, g_scratch);
        cudaFuncSetAttribute(fused_kernel, cudaFuncAttributeMaxDynamicSharedMemorySize, SMEM_BYTES);
    }
    typedef const __nv_bfloat16* bp;
    Params p;
    p.u = (bp)d_in[0]; p.Are = (bp)d_in[1]; p.Aim = (bp)d_in[2]; p.Bre = (bp)d_in[3]; p.Bim = (bp)d_in[4]; p.Cre = (bp)d_in[5]; p.Cim = (bp)d_in[6];
    p.logdt = (bp)d_in[7]; p.Dskip = (bp)d_in[8]; p.wr = (bp)d_in[10]; p.gatew = (bp)d_in[14];
    p.out = (__nv_bfloat16*)d_out; p.s = (Scratch*)scratch; p.zero = 0;
    Maps maps;
    {
        const cuuint64_t dims[4] = {DM, 4, 16, 32}, strides[3] = {16 * DM * 2, DM * 2, 64 * DM * 2};
        const cuuint32_t box[4] = {16, 4, 16, 2};
        make_map(fn, &maps.m[0], d_in[0], 4, dims, strides, box, CU_TENSOR_MAP_SWIZZLE_32B);
        const cuuint32_t box2[4] = {16, 4, 16, 8};
        make_map(fn, &maps.m[5], d_in[0], 4, dims, strides, box2, CU_TENSOR_MAP_SWIZZLE_32B);
    }
    for (int i = 0; i < 2; i++) {
        const cuuint64_t dims[3] = {32, DM, FF / 32}, strides[2] = {FF * 2, 64};
        const cuuint32_t box[3] = {32, 64, 3};
        make_map(fn, &maps.m[1 + i], d_in[11 + i], 3, dims, strides, box, CU_TENSOR_MAP_SWIZZLE_64B);
    }
    {
        const cuuint64_t dims[2] = {DM, FF}, strides[1] = {DM * 2};
        const cuuint32_t box[2] = {32, 192};
        make_map(fn, &maps.m[3], d_in[13], 2, dims, strides, box, CU_TENSOR_MAP_SWIZZLE_64B);
    }
    {
        const cuuint64_t dims[5] = {DM, 4, 4, 2, L_SEQ}, strides[4] = {16 * DM * 2, 4 * DM * 2, 128 * DM * 2, DM * 2};
        const cuuint32_t box[5] = {16, 4, 4, 2, 1};
        make_map(fn, &maps.m[4], d_out, 5, dims, strides, box, CU_TENSOR_MAP_SWIZZLE_NONE);
    }
    fused_kernel<<<NCTA, NTHR, SMEM_BYTES>>>(p, maps);
}
```

```cpp
#include <cuda_runtime.h>
#include <cuda_bf16.h>
#include <cuda_fp16.h>
#include <cuda.h>
#include <stdint.h>
#include <type_traits>

#define RESUME 300
#define FPOS 4
#define KEYPF 1
#define NACC 6
#define EFETCH 0
#define GW 7
#define TW 12
#define MDELAY 2000
#define UDELAY 0
#define RDELAY 900
#define WDELAY 2000
#define WGAP 290
#define NPRE 7
#define DGAP 260

#define TUNR 2
namespace {
constexpr int TUN = TUNR;

constexpr int DM = 576, NST = 128, FF = 4608, L_SEQ = 2048;
constexpr int NCONV = 72, NX = 36, NW = 48, NCTA = 132, NTHR = 512;

struct __align__(128) Scratch {
    unsigned epoch[NCTA * 16];
    uint4 keys[16 * 128];
    uint32_t sel[18 * 64];
    uint16_t gate[L_SEQ];
    uint2 h[2 * 288 * 32];
    uint4 kp[DM * 96];
};
__device__ Scratch g_scratch;
#define TFLUSH()
#define TSTAMP(i)

struct Params {
    const __nv_bfloat16 *Are, *Aim, *Bre, *Bim, *Cre, *Cim, *logdt, *Dskip, *u, *wr, *gatew;
    __nv_bfloat16* out;
    Scratch* s;
    uint32_t zero;
};

__device__ __forceinline__ void give_up() { asm volatile("trap; exit;"); __builtin_unreachable(); }
__device__ __forceinline__ void converged() { __syncwarp(); asm volatile("{ .reg .b32 t; mov.b32 t, 0; movmatrix.sync.aligned.m8n8.trans.b16 t, t; }" ::: "memory"); }
__device__ __forceinline__ bool elect() { uint32_t r; asm volatile("{ .reg .pred p; elect.sync _|p, 0xffffffff; selp.u32 %0, 1, 0, p; }" : "=r"(r)); return r; }
__device__ __forceinline__ uint32_t smem_u32(const void* p) { return (uint32_t)__cvta_generic_to_shared(p); }
__device__ __forceinline__ uint32_t pack_bf16(float lo, float hi) { uint32_t r; asm("cvt.rn.bf16x2.f32 %0, %1, %2;" : "=r"(r) : "f"(hi), "f"(lo)); return r; }
__device__ __forceinline__ uint32_t pack_f16(float lo, float hi) { uint32_t r; asm("cvt.rn.f16x2.f32 %0, %1, %2;" : "=r"(r) : "f"(hi), "f"(lo)); return r; }
__device__ __forceinline__ float bf_lo(uint32_t w) { return __uint_as_float(w << 16); }
__device__ __forceinline__ float bf_hi(uint32_t w) { return __uint_as_float(w & 0xffff0000u); }
__device__ __forceinline__ float rbf(float x) { return bf_lo(pack_bf16(x, 0.f)); }
__device__ __forceinline__ uint32_t badd2(uint32_t a, uint32_t b) { uint32_t r; asm("add.rn.bf16x2 %0, %1, %2;" : "=r"(r) : "r"(a), "r"(b)); return r; }
__device__ __forceinline__ uint32_t bsub2(uint32_t a, uint32_t b) { uint32_t r; asm("sub.rn.bf16x2 %0, %1, %2;" : "=r"(r) : "r"(a), "r"(b)); return r; }
__device__ __forceinline__ uint32_t gmix(uint32_t ng, float ny0, float ny1, uint32_t u) {
    uint32_t r; asm("{ .reg .b32 t; fma.rn.bf16x2 t, %1, %3, %3; fma.rn.bf16x2 %0, %1, %2, t; }" : "=r"(r) : "r"(ng), "r"(pack_bf16(ny0, ny1)), "r"(u)); return r;
}
__device__ __forceinline__ void mma_bf(float (&c)[4], uint32_t a0, uint32_t a1, uint32_t a2, uint32_t a3, uint32_t b0, uint32_t b1) {
    asm("mma.sync.aligned.m16n8k16.row.col.f32.bf16.bf16.f32 {%0,%1,%2,%3}, {%4,%5,%6,%7}, {%8,%9}, {%0,%1,%2,%3};"
        : "+f"(c[0]), "+f"(c[1]), "+f"(c[2]), "+f"(c[3]) : "r"(a0), "r"(a1), "r"(a2), "r"(a3), "r"(b0), "r"(b1));
}
__device__ __forceinline__ void mma_bf8(float (&c)[4], uint32_t a0, uint32_t a1, uint32_t b0) {
    asm("mma.sync.aligned.m16n8k8.row.col.f32.bf16.bf16.f32 {%0,%1,%2,%3}, {%4,%5}, {%6}, {%0,%1,%2,%3};"
        : "+f"(c[0]), "+f"(c[1]), "+f"(c[2]), "+f"(c[3]) : "r"(a0), "r"(a1), "r"(b0));
}
__device__ __forceinline__ void mma_h(float (&c)[4], uint32_t a0, uint32_t a1, uint32_t a2, uint32_t a3, uint32_t b0, uint32_t b1) {
    asm("mma.sync.aligned.m16n8k16.row.col.f32.f16.f16.f32 {%0,%1,%2,%3}, {%4,%5,%6,%7}, {%8,%9}, {%0,%1,%2,%3};"
        : "+f"(c[0]), "+f"(c[1]), "+f"(c[2]), "+f"(c[3]) : "r"(a0), "r"(a1), "r"(a2), "r"(a3), "r"(b0), "r"(b1));
}
__device__ __forceinline__ uint32_t fresh(uint32_t a) { asm volatile("" : "+r"(a) :: "memory"); return a; }
__device__ __forceinline__ uint32_t lds16(uint32_t a) { uint32_t v; asm("ld.shared.u16 %0, [%1];" : "=r"(v) : "r"(a)); return v; }
__device__ __forceinline__ uint32_t lds32(uint32_t a) { uint32_t v; asm("ld.shared.u32 %0, [%1];" : "=r"(v) : "r"(a)); return v; }
__device__ __forceinline__ uint2 lds64(uint32_t a) { uint2 v; asm("ld.shared.v2.u32 {%0,%1}, [%2];" : "=r"(v.x), "=r"(v.y) : "r"(a)); return v; }
__device__ __forceinline__ uint4 lds128(uint32_t a) { uint4 v; asm("ld.shared.v4.u32 {%0,%1,%2,%3}, [%4];" : "=r"(v.x), "=r"(v.y), "=r"(v.z), "=r"(v.w) : "r"(a)); return v; }
__device__ __forceinline__ uint4 lds128v(uint32_t a) { uint4 v; asm volatile("ld.shared.v4.u32 {%0,%1,%2,%3}, [%4];" : "=r"(v.x), "=r"(v.y), "=r"(v.z), "=r"(v.w) : "r"(a) : "memory"); return v; }
__device__ __forceinline__ void ldsm4(uint32_t (&r)[4], uint32_t a) {
    asm("ldmatrix.sync.aligned.m8n8.x4.shared.b16 {%0,%1,%2,%3}, [%4];" : "=r"(r[0]), "=r"(r[1]), "=r"(r[2]), "=r"(r[3]) : "r"(a));
}
__device__ __forceinline__ void ldsm4t(uint32_t (&r)[4], uint32_t a) {
    asm("ldmatrix.sync.aligned.m8n8.x4.trans.shared.b16 {%0,%1,%2,%3}, [%4];" : "=r"(r[0]), "=r"(r[1]), "=r"(r[2]), "=r"(r[3]) : "r"(a));
}
__device__ __forceinline__ void sts16(uint32_t a, uint32_t v) { asm volatile("st.shared.u16 [%0], %1;" :: "r"(a), "h"((unsigned short)v) : "memory"); }
__device__ __forceinline__ void sts32(uint32_t a, uint32_t v) { asm volatile("st.shared.u32 [%0], %1;" :: "r"(a), "r"(v) : "memory"); }
__device__ __forceinline__ void sts64(uint32_t a, uint32_t x, uint32_t y) { asm volatile("st.shared.v2.u32 [%0], {%1,%2};" :: "r"(a), "r"(x), "r"(y) : "memory"); }
__device__ __forceinline__ void sts128(uint32_t a, uint32_t x, uint32_t y, uint32_t z, uint32_t w) {
    asm volatile("st.shared.v4.u32 [%0], {%1,%2,%3,%4};" :: "r"(a), "r"(x), "r"(y), "r"(z), "r"(w) : "memory");
}
__device__ __forceinline__ void st_async128(uint32_t a, uint32_t x, uint32_t y, uint32_t z, uint32_t w, uint32_t bar) {
    asm volatile("st.async.weak.shared::cluster.mbarrier::complete_tx::bytes.v4.b32 [%0], {%1,%2,%3,%4}, [%5];" :: "r"(a), "r"(x), "r"(y), "r"(z), "r"(w), "r"(bar) : "memory");
}
__device__ __forceinline__ void mbar_init(uint32_t b, uint32_t cnt) { asm volatile("mbarrier.init.shared::cta.b64 [%0], %1;" :: "r"(b), "r"(cnt) : "memory"); }
__device__ __forceinline__ void mbar_fence() { asm volatile("fence.mbarrier_init.release.cluster;" ::: "memory"); }
__device__ __forceinline__ void mbar_expect(uint32_t b, uint32_t bytes) { asm volatile("mbarrier.arrive.expect_tx.shared::cta.b64 _, [%0], %1;" :: "r"(b), "r"(bytes) : "memory"); }
__device__ __forceinline__ void mbar_arrive(uint32_t b) { asm volatile("mbarrier.arrive.shared::cta.b64 _, [%0];" :: "r"(b) : "memory"); }
#define CHINT ""
#define HINT ""
__device__ __forceinline__ void mbar_wait(uint32_t b, uint32_t parity = 0) {
    asm volatile("{ .reg .pred p; .reg .u32 n; mov.u32 n, 0;\n"
                 "LW: mbarrier.try_wait.parity.shared::cta.b64 p, [%0], %1" HINT "; @p bra LD; add.u32 n, n, 1; setp.lt.u32 p, n, 65536; @p bra LW; trap;\n"
                 "LD: }" :: "r"(b), "r"(parity) : "memory");
}
__device__ __forceinline__ void mbar_wait_cluster(uint32_t b) {
    asm volatile("{ .reg .pred p; .reg .u32 n; mov.u32 n, 0;\n"
                 "LW: mbarrier.try_wait.parity.acquire.cluster.shared::cta.b64 p, [%0], 0" CHINT "; @p bra LD; add.u32 n, n, 1; setp.lt.u32 p, n, 65536; @p bra LW; trap;\n"
                 "LD: }" :: "r"(b) : "memory");
}
__device__ __forceinline__ void tma2d(uint32_t dst, const CUtensorMap* m, int c0, int c1, uint32_t bar) {
    asm volatile("cp.async.bulk.tensor.2d.shared::cluster.global.mbarrier::complete_tx::bytes [%0], [%1, {%3, %4}], [%2];"
                 :: "r"(dst), "l"(m), "r"(bar), "r"(c0), "r"(c1) : "memory");
}
__device__ __forceinline__ void tma3d(uint32_t dst, const CUtensorMap* m, int c0, int c1, int c2, uint32_t bar) {
    asm volatile("cp.async.bulk.tensor.3d.shared::cluster.global.mbarrier::complete_tx::bytes [%0], [%1, {%3, %4, %5}], [%2];"
                 :: "r"(dst), "l"(m), "r"(bar), "r"(c0), "r"(c1), "r"(c2) : "memory");
}
__device__ __forceinline__ void tma4d(uint32_t dst, const CUtensorMap* m, int c0, int c1, int c2, int c3, uint32_t bar) {
    asm volatile("cp.async.bulk.tensor.4d.shared::cluster.global.mbarrier::complete_tx::bytes [%0], [%1, {%3, %4, %5, %6}], [%2];"
                 :: "r"(dst), "l"(m), "r"(bar), "r"(c0), "r"(c1), "r"(c2), "r"(c3) : "memory");
}
__device__ __forceinline__ void bulk_g2s(uint32_t dst, const void* src, uint32_t bytes, uint32_t bar) {
    asm volatile("cp.async.bulk.shared::cluster.global.mbarrier::complete_tx::bytes [%0], [%1], %2, [%3];"
                 :: "r"(dst), "l"(src), "r"(bytes), "r"(bar) : "memory");
}
__device__ __forceinline__ uint32_t mapa(uint32_t a, uint32_t rank) { uint32_t r; asm("mapa.shared::cluster.u32 %0, %1, %2;" : "=r"(r) : "r"(a), "r"(rank)); return r; }
__device__ __forceinline__ void prefetch_map(const CUtensorMap* m) { asm volatile("prefetch.tensormap [%0];" :: "l"(m) : "memory"); }
__device__ __forceinline__ void bar_sync(int id, int n) { asm volatile("bar.sync %0, %1;" :: "r"(id), "r"(n) : "memory"); }
__device__ __forceinline__ void bar_arrive(int id, int n) { asm volatile("bar.arrive %0, %1;" :: "r"(id), "r"(n) : "memory"); }
__device__ __forceinline__ uint32_t ldg16_if(bool c, const void* p) { uint32_t v; asm volatile("{ .reg .pred p; setp.ne.u32 p, %2, 0; @p ld.global.nc.u16 %0, [%1]; }" : "=r"(v) : "l"(p), "r"((uint32_t)c)); return v; }
__device__ __forceinline__ uint32_t ldg32_if(bool c, const void* p) { uint32_t v; asm volatile("{ .reg .pred p; setp.ne.u32 p, %2, 0; @p ld.global.nc.u32 %0, [%1]; }" : "=r"(v) : "l"(p), "r"((uint32_t)c)); return v; }
__device__ __forceinline__ uint32_t ld_rlx32(const void* p) { uint32_t v; asm volatile("ld.relaxed.gpu.global.u32 %0, [%1];" : "=r"(v) : "l"(p) : "memory"); return v; }
__device__ __forceinline__ uint4 ld_rlx128(const void* p) {
    uint4 v; asm volatile("ld.relaxed.gpu.global.v4.u32 {%0,%1,%2,%3}, [%4];" : "=r"(v.x), "=r"(v.y), "=r"(v.z), "=r"(v.w) : "l"(p) : "memory"); return v;
}
__device__ __forceinline__ void st_rlx32(void* p, uint32_t v) { asm volatile("st.relaxed.gpu.global.u32 [%0], %1;" :: "l"(p), "r"(v) : "memory"); }
__device__ __forceinline__ void stg128(void* p, uint32_t x, uint32_t y, uint32_t z, uint32_t w) {
    asm volatile("st.global.v4.u32 [%0], {%1,%2,%3,%4};" :: "l"(p), "r"(x), "r"(y), "r"(z), "r"(w) : "memory");
}
__device__ __forceinline__ void next_epoch(const Params& p, unsigned e) { if ((threadIdx.x & 31) == 0) p.s->epoch[blockIdx.x * 16 + (threadIdx.x >> 5)] = e + 1; }
__device__ __forceinline__ void sts128z_if(bool c, uint32_t a) { asm volatile("{ .reg .pred p; setp.ne.u32 p, %1, 0; @p st.shared.v4.u32 [%0], {%2,%2,%2,%2}; }" :: "r"(a), "r"((uint32_t)c), "r"(0) : "memory"); }
__device__ __forceinline__ void stg128z_if(bool c, void* a) { asm volatile("{ .reg .pred p; setp.ne.u32 p, %1, 0; @p st.global.v4.u32 [%0], {%2,%2,%2,%2}; }" :: "l"(a), "r"((uint32_t)c), "r"(0) : "memory"); }
__device__ __forceinline__ unsigned clock32() { unsigned c; asm volatile("mov.u32 %0, %clock;" : "=r"(c) :: "memory"); return c; }
__device__ __forceinline__ void until(unsigned t0, int c) { while ((int)(clock32() - t0) < c) { } }
__device__ __forceinline__ float sigmoidf_(float x) { return __fdividef(1.0f, 1.0f + __expf(-x)); }
__device__ __forceinline__ uint32_t key_tag(unsigned epoch) { return ((epoch & 15u) | 16u) << 11; }
__device__ __forceinline__ int key_row(uint32_t key) { return 2047 - (int)(key & 2047u); }
__device__ __forceinline__ uint32_t wait_sel(const Params& p, int s32, int r8, uint32_t tag, uint32_t k = 0) {
#pragma unroll 1
    for (int it = 0; !__all_sync(0xffffffffu, (k & 0xf800u) == tag); it++) {
        k = ld_rlx32(&p.s->sel[s32 * 64 + r8]);
        if (it > (1 << 20)) give_up();
    }
    return k;
}

struct cplx { float re, im; };
__device__ __forceinline__ cplx csq(cplx a) { cplx r; r.re = a.re * a.re - a.im * a.im; r.im = (a.re * a.im) * 2.f; return r; }
__device__ __forceinline__ cplx cexpk(float ar, float ai, float k) {
    float mag, s, c;
    asm("ex2.approx.ftz.f32 %0, %1;" : "=f"(mag) : "f"(ar * (k * 1.4426950408889634f)));
    const float r = ai * k;
    asm("sin.approx.ftz.f32 %0, %1;" : "=f"(s) : "f"(r));
    asm("cos.approx.ftz.f32 %0, %1;" : "=f"(c) : "f"(r));
    cplx o; o.re = mag * c; o.im = mag * s; return o;
}
struct h2c { uint32_t re, im; };
__device__ __forceinline__ h2c cmul_cd(h2c v, __half2 c, __half2 d) {
    const __half2 r = *(const __half2*)&v.re, i = *(const __half2*)&v.im;
    const __half2 x = __hfma2(__hneg2(i), d, __hmul2(r, c)), y = __hfma2(i, c, __hmul2(r, d));
    h2c o; o.re = *(const uint32_t*)&x; o.im = *(const uint32_t*)&y; return o;
}
__device__ __forceinline__ h2c cmul_s(h2c v, uint32_t s) { const __half2 h = *(const __half2*)&s; return cmul_cd(v, __low2half2(h), __high2half2(h)); }
__device__ __forceinline__ h2c cmul_sc(h2c v, uint32_t s) {
    const __half2 h = *(const __half2*)&s, c = __low2half2(h), d = __high2half2(h), r = *(const __half2*)&v.re, i = *(const __half2*)&v.im;
    const __half2 x = __hfma2(i, d, __hmul2(r, c)), y = __hfma2(__hneg2(r), d, __hmul2(i, c));
    h2c o; o.re = *(const uint32_t*)&x; o.im = *(const uint32_t*)&y; return o;
}
__device__ __forceinline__ h2c cmul_vc(h2c v, uint32_t s) {
    const __half2 h = *(const __half2*)&s, c = __low2half2(h), d = __high2half2(h), r = *(const __half2*)&v.re, i = *(const __half2*)&v.im;
    const __half2 x = __hfma2(i, d, __hmul2(r, c)), y = __hfma2(__hneg2(i), c, __hmul2(r, d));
    h2c o; o.re = *(const uint32_t*)&x; o.im = *(const uint32_t*)&y; return o;
}

constexpr int UT_HALF = 2240, UT_STRIDE = 4448;
constexpr int KT_T = 542, KT_C = 552, KT_D = 645, KT_BYTES = 720 * 4;
constexpr int VC_OFF = 80, VE_BASE = 1616;
constexpr int V_STRIDE = (1616 + 1024) * 4 + 80;
constexpr int KG_STAGE = 5248;
constexpr int Y_CS = 2080, Y_RS = 8 * Y_CS + 64;

constexpr int SC_RT = 0;
constexpr int SC_UT = 33408;
constexpr int SC_ST = SC_UT + 8 * UT_STRIDE;
constexpr int SC_KT = SC_ST + 8 * UT_STRIDE;
constexpr int SC_GT = SC_KT + 8 * KT_BYTES;
constexpr int SC_V = SC_GT + UT_STRIDE;
constexpr int SC_KG = SC_V + 4 * V_STRIDE;
constexpr int SC_MISC = SC_V + 8 * V_STRIDE;
static_assert(V_STRIDE % 128 == 16 && 8 * KG_STAGE <= 4 * V_STRIDE && 2 * Y_RS <= SC_UT && SC_UT % 128 == 0 && SC_ST % 128 == 0, "layout");
static_assert(SC_MISC % 16 == 0 && SC_MISC + 512 <= 232192, "layout");

__device__ __forceinline__ void window_task(uint32_t src, uint32_t d0, uint32_t d1, bool withE) {
    float S[35];
    {
        uint32_t w[20];
#pragma unroll
        for (int i = 0; i < 5; i++) {
            const uint4 v = lds128(src + ((i & 1) ? 0 : UT_HALF) + ((i + 1) >> 1) * 16);
            w[4 * i] = v.x; w[4 * i + 1] = v.y; w[4 * i + 2] = v.z; w[4 * i + 3] = v.w;
        }
        float s = 0.f; S[2] = 0.f;
#pragma unroll
        for (int i = 3; i < 26; i++) { s += (i & 1) ? bf_hi(w[i >> 1]) : bf_lo(w[i >> 1]); S[i] = s; }
#pragma unroll
        for (int i = 0; i < 8; i += 2)
            sts128((i & 4 ? d1 : d0) + (VC_OFF - 16) * 4 + 8 * (i & 2), pack_bf16(S[10 + i] - S[5 + i], S[5 + i] - S[2 + i]), pack_bf16(S[18 + i] - S[13 + i], S[13 + i] - S[10 + i]),
                   pack_bf16(S[11 + i] - S[6 + i], S[6 + i] - S[3 + i]), pack_bf16(S[19 + i] - S[14 + i], S[14 + i] - S[11 + i]));
        if (withE) {
#pragma unroll
            for (int i = 26; i < 35; i++) { s += (i & 1) ? bf_hi(w[i >> 1]) : bf_lo(w[i >> 1]); S[i] = s; }
#pragma unroll
            for (int i = 0; i < 8; i += 2)
                sts128((i & 4 ? d1 : d0) + VE_BASE * 4 + 8 * (i & 2), pack_bf16(S[19 + i] - S[12 + i], S[12 + i] - S[3 + i]), pack_bf16(S[27 + i] - S[20 + i], S[20 + i] - S[11 + i]),
                       pack_bf16(S[20 + i] - S[13 + i], S[13 + i] - S[4 + i]), pack_bf16(S[28 + i] - S[21 + i], S[21 + i] - S[12 + i]));
        }
    }
}

template <class F>
__device__ __forceinline__ void kgen(const uint32_t (&q)[8], uint32_t sb, int half, uint32_t stage, uint32_t pstage, int barid, int lane, uint32_t zero, uint32_t (&w)[12], F shadow) {
    const int t = lane & 3, mi = lane >> 3, r8 = lane & 7;
    {
        const uint32_t pAr = q[0], pAi = q[1], pBr = q[2], pBi = q[3], pCr = q[4], pCi = q[5], pDt = q[6], pD = q[7];
        const uint32_t wb = fresh(stage + lane * 16), za = fresh(stage + 5120 + ((lane >> 1) & 3) * 16 + mi * 4 + (lane & 1) * 2), zr = fresh(stage + 5120 + t * 16);
        const uint32_t oA = fresh(stage + (mi & 1) * 1024 + (mi >> 1) * 512 + r8 * 16), oB = fresh(stage + 2048 + mi * 512 + r8 * 16), oC = fresh(stage + 4096 + (mi & 1) * 512 + (mi >> 1) * 128 + r8 * 16);
        float acc[6][4];
#pragma unroll
        for (int a = 0; a < 6; a++) { acc[a][0] = acc[a][1] = acc[a][2] = acc[a][3] = 0.f; asm volatile("" : "+f"(acc[a][0]), "+f"(acc[a][1]), "+f"(acc[a][2]), "+f"(acc[a][3])); }
        shadow();
        sts32(zr, clock32());
        const float dt = rbf(__expf(bf_lo(pDt)));
        float ar = dt * bf_lo(pAr), ai = dt * bf_lo(pAi), ar1 = dt * bf_hi(pAr), ai1 = dt * bf_hi(pAi);
        float wr, wi, wr1, wi1;
        { const float br = dt * bf_lo(pBr), bi = dt * bf_lo(pBi), cr = bf_lo(pCr), ci = bf_lo(pCi); wr = cr * br - ci * bi; wi = cr * bi + ci * br; }
        { const float br = dt * bf_hi(pBr), bi = dt * bf_hi(pBi), cr = bf_hi(pCr), ci = bf_hi(pCi); wr1 = cr * br - ci * bi; wi1 = cr * bi + ci * br; }
        const uint32_t ex = max(__reduce_max_sync(0xffffffffu, __float_as_uint(fmaxf(fmaxf(fabsf(wr), fabsf(wi)), fmaxf(fabsf(wr1), fabsf(wi1))))) >> 23, 14u);
        const float scl = __uint_as_float((267u - ex) << 23);
        uint32_t W = pack_f16(wr * scl, wi * -scl);
        const uint32_t W1 = pack_f16(wr1 * scl, wi1 * -scl);
        if (threadIdx.x < 32) TSTAMP(20);

#pragma unroll 1
        for (int r = 0; r < 2; r++) {
            const cplx z1 = cexpk(ar, ai, 1.f), z64 = cexpk(ar, ai, 64.f);
            const cplx z2 = csq(z1), z4 = csq(z2), z8 = csq(z4), z16 = csq(z8), z32 = csq(z16);
            const cplx z128 = csq(z64), z256 = csq(z128), z512 = csq(z256);
            auto put = [&](int grp, h2c a, h2c b, h2c c, h2c d) { sts128(wb + grp * 1024, a.re, b.re, c.re, d.re); sts128(wb + grp * 1024 + 512, a.im, b.im, c.im, d.im); };
            {
                const uint32_t s4 = pack_f16(z4.re, z4.im), s256 = pack_f16(z256.re, z256.im), s512 = pack_f16(z512.re, z512.im);
                auto mix = [](h2c a, h2c b, uint32_t sel) { return h2c{__byte_perm(a.re, b.re, sel), __byte_perm(a.im, b.im, sel)}; };
                const h2c c10 = cmul_vc(h2c{pack_f16(z1.re, 1.f), pack_f16(z1.im, 0.f)}, W), c32 = cmul_sc(c10, pack_f16(z2.re, z2.im)), c54 = cmul_sc(c10, s4);
                put(2, c10, c32, c54, cmul_sc(c32, s4));
                const h2c d20 = cmul_sc(mix(c32, c10, 0x7632), s256), e04 = cmul_sc(mix(c10, c54, 0x7632), s512), f04 = cmul_sc(e04, s256);
                put(3, d20, cmul_sc(d20, s4), e04, f04);
                const h2c ef = mix(e04, f04, 0x5410), gh = cmul_sc(ef, s512), g8 = cmul_sc(gh, pack_f16(z8.re, z8.im));
                put(4, g8, cmul_sc(g8, s512), gh, ef);
            }
            {
                const uint32_t s32 = pack_f16(z32.re, z32.im), s64 = pack_f16(z64.re, z64.im), s128 = pack_f16(z128.re, z128.im);
                const h2c p0 = {pack_f16(1.f, z8.re), pack_f16(0.f, z8.im)}, p1 = cmul_s(p0, pack_f16(z16.re, z16.im)), p2 = cmul_s(p0, s32), p3 = cmul_s(p1, s32);
                put(0, p0, p1, p2, p3);
                put(1, cmul_s(p0, s64), cmul_s(p1, s64), cmul_s(p2, s64), cmul_s(p3, s64));
                sts16(za, s128); sts16(za + 64, s128 >> 16);
            }
            __syncwarp();
            {
                const uint32_t aA = fresh(oA), aB = fresh(oB), aC = fresh(oC), aZ = fresh(zr);
                const uint4 zc = lds128(aZ), zd = lds128(aZ + 64);
                const uint32_t zcs[4] = {zc.x, zc.y, zc.z, zc.w}, zds[4] = {zd.x, zd.y, zd.z, zd.w};
                uint32_t c[4];
#pragma unroll
                for (int k = 0; k < 4; k++) {
                    uint32_t a[4], b[4];
                    ldsm4t(a, aA + 128 * k); ldsm4t(b, aB + 128 * k);
                    if (!(k & 1)) ldsm4t(c, aC + 128 * k);
                    const h2c x = cmul_cd(h2c{a[0], a[2]}, *(const __half2*)&zcs[k], *(const __half2*)&zds[k]), y = cmul_cd(h2c{a[1], a[3]}, *(const __half2*)&zcs[k], *(const __half2*)&zds[k]);
                    mma_h(acc[0], a[0], a[1], a[2], a[3], b[0], b[1]);
                    mma_h(acc[1], a[0], a[1], a[2], a[3], b[2], b[3]);
                    mma_h(acc[2], a[0], a[1], a[2], a[3], c[2 * (k & 1)], c[2 * (k & 1) + 1]);
                    mma_h(acc[3], x.re, y.re, x.im, y.im, b[0], b[1]);
                    mma_h(acc[4], x.re, y.re, x.im, y.im, b[2], b[3]);
                    mma_h(acc[5], x.re, y.re, x.im, y.im, c[2 * (k & 1)], c[2 * (k & 1) + 1]);
                }
                asm volatile("" :: "f"(acc[0][0]), "f"(acc[1][0]), "f"(acc[2][0]), "f"(acc[3][0]), "f"(acc[4][0]), "f"(acc[5][0]) : "memory");
            }
            __syncwarp();
            ar = ar1; ai = ai1; W = W1;
        }
        if (threadIdx.x < 32) TSTAMP(21);
        const float i0 = __uint_as_float((ex + 243u) << 23);
        if (half) {
#pragma unroll
            for (int a = 0; a < 6; a++) sts128(wb + a * 512, __float_as_uint(acc[a][0]), __float_as_uint(acc[a][1]), __float_as_uint(acc[a][2]), __float_as_uint(acc[a][3]));
            sts32(stage + 3072, __float_as_uint(i0));
            bar_arrive(barid, 64);
        } else {
#pragma unroll
            for (int a = 0; a < 6; a++) { acc[a][0] *= i0; acc[a][1] *= i0; acc[a][2] *= i0; acc[a][3] *= i0; }
            if (lane == 0) acc[0][1] -= bf_lo(pD);
            sts32(zr, clock32());
            bar_sync(barid, 64);
            const uint32_t src = fresh(pstage);
            const float i1 = __uint_as_float(lds32(src + 3072));
#pragma unroll
            for (int a = 0; a < 6; a++) {
                const uint4 y = lds128(src + lane * 16 + a * 512);
                w[4 * (a % 3) + 2 * (a / 3)] = pack_bf16(fmaf(__uint_as_float(y.x), i1, acc[a][0]), fmaf(__uint_as_float(y.y), i1, acc[a][1]));
                w[4 * (a % 3) + 2 * (a / 3) + 1] = pack_bf16(fmaf(__uint_as_float(y.z), i1, acc[a][2]), fmaf(__uint_as_float(y.w), i1, acc[a][3]));
            }
            const uint32_t x0 = __shfl_up_sync(0xffffffffu, w[10], 2), x1 = __shfl_up_sync(0xffffffffu, w[11], 2);
            w[10] = w[8];
            if (t >= 2) { w[8] = x0; w[9] = x1; }
        }
    }
}

__device__ __forceinline__ int swap01(int i) { return (i & ~3) | ((i & 1) << 1) | ((i >> 1) & 1); }
enum { BC_AUX = 0, BC_S = 5, BC_KG = 15 };

__device__ __forceinline__ void fetch_gates(const Params& p, int i, int lane, unsigned epoch, uint32_t dst) {
    const uint32_t par = (epoch & 1) ? 0x80008000u : 0u;
    uint4 v;
#pragma unroll 1
    for (int it = 0;; it++) {
        v = ld_rlx128(p.s->gate + 256 * i + 8 * lane);
        v.x ^= par; v.y ^= par; v.z ^= par; v.w ^= par;
        if (__all_sync(0xffffffffu, (v.x & v.y & v.z & v.w & 0x80008000u) == 0x80008000u)) break;
        if (it > (1 << 20)) give_up();
    }
    sts128(dst + (8 + 16 * i + (lane >> 1)) * 16, v.x, v.y, v.z, v.w);
}
__device__ __forceinline__ void store_rows(const CUtensorMap* m, uint32_t src, int col, int row) {
    asm volatile("cp.async.bulk.tensor.5d.global.shared::cta.bulk_group [%0, {%2, %3, %3, %3, %4}], [%1];" :: "l"(m), "r"(src), "r"(col), "r"(0), "r"(row) : "memory");
}

__device__ __forceinline__ void store_or_add(void* o, const uint32_t (&y)[4], uint32_t add) {
    asm volatile("{ .reg .pred p; setp.ne.u32 p, %5, 0; @!p st.global.v4.u32 [%0], {%1,%2,%3,%4}; @p red.relaxed.gpu.global.add.noftz.v4.bf16x2 [%0], {%1,%2,%3,%4}; }"
                 :: "l"(o), "r"(y[0]), "r"(y[1]), "r"(y[2]), "r"(y[3]), "r"(add) : "memory");
}

__device__ __forceinline__ void conv_aux(const Params& p, const CUtensorMap* mU, uint32_t sb, int aw, int lane, int bid, unsigned epoch) {
    const unsigned t0 = clock32();
    const int g = lane >> 2, t = lane & 3, mi = lane >> 3, r8 = lane & 7;
    const int rank = bid & 1, slab = bid >> 1;
    const uint32_t bar_y = sb + SC_MISC, bar_u = bar_y + 32, bar_v = bar_y + 40, bar_box = bar_y + 64 + 8 * aw, s_bm = bar_y + 128;
    if (elect()) {
        mbar_init(bar_box, 1); mbar_fence();
        mbar_expect(bar_box, 4096);
        if (UDELAY) until(t0, UDELAY);
        tma4d(sb + SC_RT + 4096 * aw, mU, 16 * slab, 0, 0, 16 * rank + 2 * aw, bar_box);
        mbar_init(bar_y + 8 * aw, aw < 4 ? 9 : aw == 5 ? 8 : 1); mbar_fence();
        if (aw < 5) mbar_expect(bar_y + 8 * aw, aw == 4 ? 16384 : 4096);
    }
    __syncwarp();
    asm volatile("barrier.cluster.arrive.relaxed.aligned;" ::: "memory");
    asm volatile("setmaxnreg.dec.sync.aligned.u32 88;");
    const uint32_t ut = sb + SC_UT + aw * UT_STRIDE;
    sts128(ut + (mi >> 1) * (SC_ST - SC_UT) + (mi & 1) * UT_HALF + r8 * 16, 0, 0, 0, 0);
    if (lane < 16) sts128(s_bm + lane * 16, 0, 0, 0, 0);
    {
        const uint32_t dst = sb + SC_UT + swap01(g) * UT_STRIDE + (8 + 64 * rank + 8 * aw + t) * 16;
        const uint32_t rdst = mapa(dst, rank ^ 1), rbar = mapa(bar_u, rank ^ 1);
        asm volatile("barrier.cluster.wait.acquire.aligned;" ::: "memory");
        mbar_wait(bar_box);
        if (aw == 0) TSTAMP(1);
        const uint32_t src = fresh(sb + SC_RT) + aw * 4096 + (8 * mi + 4 * (r8 & 1) + (r8 >> 1)) * 32 + ((rank ^ (r8 & 1)) << 4);
        uint32_t x[8][4];
#pragma unroll
        for (int i = 0; i < 4; i++) { ldsm4t(x[i], src + 1024 * i); ldsm4t(x[4 + i], (src ^ 16) + 1024 * i); }
        asm volatile("" :: "r"(x[0][0]), "r"(x[1][0]), "r"(x[2][0]), "r"(x[3][0]) : "memory");
#pragma unroll
        for (int i = 0; i < 4; i++) st_async128(rdst + (i & 1) * UT_HALF + 32 * (i & 2), x[4 + i][0], x[4 + i][1], x[4 + i][2], x[4 + i][3], rbar);
#pragma unroll
        for (int i = 0; i < 4; i++) sts128(dst + (i & 1) * UT_HALF + 32 * (i & 2), x[i][0], x[i][1], x[i][2], x[i][3]);
    }
    bar_sync(BC_AUX, 256);
    mbar_wait_cluster(bar_u);
    if (aw == 0) TSTAMP(2);
    {
        const uint32_t a = fresh(ut) + (mi & 1) * UT_HALF + (64 * (mi >> 1) + r8) * 16;
        uint4 v = lds128(a);
#pragma unroll
        for (int i = 1; i <= 8; i++) {
            const uint4 w = lds128(a + 128 * i);
            sts128(a + 128 * i + (SC_ST - SC_UT), badd2(v.x, w.x), badd2(v.y, w.y), badd2(v.z, w.z), badd2(v.w, w.w));
            v = w;
        }
    }
    bar_arrive(BC_S + aw, 64);
    if (aw == 0) TSTAMP(3);
    {
        uint32_t ws = sb + SC_UT + t * UT_STRIDE + (g + 6) * 16, wd = sb + SC_V + t * V_STRIDE + 64 * g, sw = 16 * (g & 2);
#pragma unroll 1
        for (int k = aw; k < 25; k += 8) {
            if (k - aw == 8) {
                bar_sync(BC_KG, 384);
                if (lane < 16) sts128(sb + SC_V + aw * V_STRIDE + lane * 16, 0, 0, 0, 0);
            }
            if (k == 24) { ws -= (g & 1) * 4 * UT_STRIDE + 16 * g; wd -= (g & 1) * 4 * V_STRIDE + 64 * g; sw = 0; }
            const int h = k >= 12, a = k - 12 * h;
            const uint32_t d = wd + h * 4 * V_STRIDE + 512 * a;
            window_task(fresh(ws) + h * 4 * UT_STRIDE + 128 * a, d + sw, d + (sw ^ 32), a < 8);
        }
    }
    if (aw == 0) TSTAMP(9);
    {
        if (aw >= 2) fetch_gates(p, aw, lane, epoch, sb + SC_GT + (lane & 1) * UT_HALF);
        __syncwarp();
        if (elect()) { mbar_arrive(bar_v); prefetch_map(mU + 4); }
        next_epoch(p, epoch);
        if (aw == 0) TSTAMP(4);
        if (aw == 7) {
            const int row = key_row(wait_sel(p, slab >> 1, r8, key_tag(epoch)));
            if (lane < 8) asm volatile("red.shared.or.b32 [%0], %1;" :: "r"(s_bm + (row >> 5) * 4), "r"(1u << (row & 31)) : "memory");
            TSTAMP(10);
        }
        bar_sync(BC_AUX, 256);
        const uint32_t src = sb + SC_RT + ((r8 >> 1) & 1) * Y_RS + (2 * mi + (r8 & 1)) * Y_CS + (2 * aw + (r8 >> 2)) * 16;
        const int L = 2 * aw + (t >> 1);
        const int row0 = 256 * rank + 128 * (g >> 2) + 32 * (L & 3) + 16 * (g & 1) + 8 * ((g >> 1) & 1) + (L >> 2);
        __nv_bfloat16* outp = p.out + (size_t)row0 * DM + 16 * slab + 8 * (t & 1);
        const uint32_t stg = sb + SC_ST + 4096 * aw, so = (g >> 1) * 256 + (t >> 1) * 64 + (g & 1) * 32 + (t & 1) * 16;
#pragma unroll 1
        for (int s = 1; s < 4; s++) {
            const uint32_t bm = lds32(fresh(s_bm) + (16 * s + (row0 >> 5)) * 4) >> (row0 & 31);
            const bool routed = __any_sync(0xffffffffu, bm & 0x11u);
            if (aw == s) mbar_wait_cluster(bar_y + 8 * s);
            bar_sync(BC_AUX, 256);
            const uint32_t sf = fresh(src) + 512 * s;
            uint32_t y[2][4];
            ldsm4t(y[0], sf); ldsm4t(y[1], sf + 256);
            if (routed) {
#pragma unroll
                for (int k = 0; k < 2; k++) store_or_add(outp + (size_t)(512 * s + 4 * k) * DM, y[k], bm & (1u << (4 * k)));
            } else {
                sts128(stg + so + 1024 * s, y[0][0], y[0][1], y[0][2], y[0][3]); sts128(stg + so + 1024 * s + 128, y[1][0], y[1][1], y[1][2], y[1][3]);
                asm volatile("fence.proxy.async.shared::cta;" ::: "memory");
                __syncwarp();
                if (elect()) store_rows(mU + 4, stg + 1024 * s, 16 * slab, 512 * s + 256 * rank + 64 * (aw & 1) + (aw >> 1));
            }
            if (aw == 0) TSTAMP(16 + s);
        }
        if (elect()) { asm volatile("cp.async.bulk.commit_group;" ::: "memory"); asm volatile("cp.async.bulk.wait_group.read 0;" ::: "memory"); }
        if (aw == 0) TFLUSH();
    }
}

__device__ __forceinline__ uint32_t k_tag(unsigned epoch) { return epoch << 16 | 0x80000000u; }
__device__ __forceinline__ void publish_k(uint4* kp, const uint32_t (&w)[12], unsigned epoch) {
#pragma unroll
    for (int i = 0; i < 3; i++)
        asm volatile("st.relaxed.gpu.global.v4.u32 [%0], {%1,%2,%3,%4};" :: "l"(kp + 32 * i), "r"(w[3 * i]), "r"(w[3 * i + 1]), "r"(w[3 * i + 2]),
                     "r"(__byte_perm(w[9 + (i >> 1)], k_tag(epoch), i == 1 ? 0x7632 : 0x7610)));
}
template <bool FULL>
__device__ __forceinline__ void k_tables(uint32_t kt, int lane, const uint32_t (&w)[12]) {
    const int g = lane >> 2, t = lane & 3, mi = lane >> 3, r8 = lane & 7;
    uint32_t x3 = w[7], re[4], rx[4];
#pragma unroll
    for (int i = 0; i < 4; i++) {
        re[i] = __shfl_sync(0xffffffffu, w[i], lane + 31);
        rx[i] = __shfl_sync(0xffffffffu, w[4 + i], lane + (i == 0 && lane == 29 ? 5 : 1 + 2 * t));
    }
    if (FULL) {
        asm volatile("stmatrix.sync.aligned.m8n8.x2.trans.shared.b16 [%0], {%1,%2};" :: "r"(kt + (KT_D + 7) * 4 + 64 * t + 16 * (mi & 1) + 8 * (r8 & 4)), "r"(w[8]), "r"(w[9]) : "memory");
        if (lane == 2) {
            sts32(kt + (KT_C + 78) * 4, w[10] & 0xffffu);
            sts128(kt + (KT_T + 2) * 4, 0, w[10] & 0xffffu, __byte_perm(w[10], 0, 0x1010), w[10] << 16);
        }
        if (lane == 29) x3 = bsub2(x3, rx[0] & 0xffffu);
    }
#pragma unroll
    for (int i = 0; i < 4; i++) {
        sts64(kt + (16 + 64 * i) * 4 + 8 * lane, __byte_perm(w[i], lane ? re[i] : i ? re[i - 1] : 0, 0x5432), w[i]);
        const uint32_t x = i < 3 ? w[4 + i] : x3, aa = __byte_perm(x, 0, 0x3232);
        if (t < 2) sts128(kt + (272 + 64 * i + 8 * g + 4 * t) * 4, i == 0 && lane == 0 ? __byte_perm(x, re[3], 0x5432) : aa, aa, x,
                          __byte_perm(lane != 29 ? rx[i] : i < 3 ? rx[(i + 1) & 3] : FULL ? 0 : rx[0] << 16, x, 0x5432));
        else if (FULL) sts32(kt + (KT_C - 50 + 8 * i + 32 * t + g) * 4, x);
    }
}

__device__ __forceinline__ void conv_main(const Params& p, uint32_t sb, int warp, int lane0, int bid, unsigned epoch, uint32_t (&w)[12]) {
    asm volatile("setmaxnreg.inc.sync.aligned.u32 168;");
    const int lane = __shfl_sync(0xffffffffu, lane0, lane0);
    const int g = lane >> 2, t = lane & 3, mi = lane >> 3, r8 = lane & 7;
    const int rank = bid & 1;
    const uint32_t bar_y = sb + SC_MISC, bar_v = bar_y + 40;
    next_epoch(p, epoch);
    if (warp < 4) {
        asm volatile("" :: "r"(w[0]), "r"(w[2]), "r"(w[4]), "r"(w[6]), "r"(w[8]), "r"(w[10]) : "memory");
        bar_arrive(BC_KG, 384);
    } else {
        bar_sync(BC_S + swap01(warp), 64);
        const uint4* src = p.s->kp + (8 * bid + warp) * 96 + lane0;
#pragma unroll 1
        for (int it = 0;; it++) {
            uint32_t bad = 0, e[3];
#pragma unroll
            for (int i = 0; i < 3; i++) { const uint4 v = ld_rlx128(src + 32 * i); w[3 * i] = v.x; w[3 * i + 1] = v.y; w[3 * i + 2] = v.z; e[i] = v.w; bad |= v.w ^ k_tag(epoch); }
            w[9] = __byte_perm(e[0], e[1], 0x5410); w[10] = e[2];
            const bool ok = __all_sync(0xffffffffu, bad < 65536);
            if (ok) break;
            if (it > (1 << 20)) give_up();
        }
    }
    if ((warp & 3) == 0) TSTAMP(5 + (warp >> 2));
    k_tables<true>(sb + SC_KT + warp * KT_BYTES, lane0, w);
    asm volatile("barrier.cluster.wait.acquire.aligned;" ::: "memory");
    if (warp < 4)
    bar_sync(BC_S + swap01(warp), 64);
    __syncwarp();
    if ((warp & 3) == 0) TSTAMP(7 + (warp >> 2));
    {
        const uint32_t ut = fresh(sb + SC_UT) + swap01(warp) * UT_STRIDE, kt = fresh(sb + SC_KT) + warp * KT_BYTES;
        uint32_t u1 = ut + (mi & 1) * UT_HALF + (8 + r8) * 16 + (mi >> 1) * 128;
        auto dup = [&](uint32_t v) { return v ^ p.zero; };
        uint32_t kp = kt + (16 + g - 2 * t) * 4;
        float acc[16][4];
        {
            const uint32_t c0 = lds32(kp + 2048), c1 = lds32(kp + 2080), c2 = lds32(kp + 2016), c3 = dup(c0);
            const uint32_t e0 = lds32(kp + (KT_T - 16) * 4), e1 = lds32(kp + (KT_T - 8) * 4), e2 = lds32(kp + (KT_T - 24) * 4), e3 = dup(e0);
            const uint32_t f0 = dup(e1), f1 = lds32(kp + KT_T * 4);
            const uint32_t uo = ut + UT_HALF + (7 + lane) * 16;
#pragma unroll
            for (int i = 0; i < 16; i++) { acc[i][0] = acc[i][1] = acc[i][2] = acc[i][3] = 0.f; }
#pragma unroll
            for (int mu = 0; mu < 8; mu += 4) {
                uint32_t b[4];
                ldsm4(b, uo + 128 * mu);
#pragma unroll
                for (int k = 0; k < 4; k++) mma_bf8(acc[mu + 8 + k], f0, f1, b[k]);
            }
#pragma unroll
            for (int mu = 0; mu < 12; mu += 2) {
                uint32_t b[4];
                ldsm4(b, u1 + 128 * mu);
                mma_bf(acc[mu + 4], c0, c1, c2, c3, b[0], b[1]);
                mma_bf(acc[mu + 5], c0, c1, c2, c3, b[2], b[3]);
                if (mu < 8) { mma_bf(acc[mu + 8], e0, e1, e2, e3, b[0], b[1]); mma_bf(acc[mu + 9], e0, e1, e2, e3, b[2], b[3]); }
            }
        }
        {
            float M[8][4];
#pragma unroll
            for (int i = 0; i < 8; i++) { M[i][0] = M[i][1] = M[i][2] = M[i][3] = 0.f; }
            uint32_t s[8][4], a3[4];
            const uint32_t kb = kp, ub = dup(u1), uc = u1 + (mi >> 1) * 128;
            auto frag = [&](uint32_t (&a)[4], uint32_t x) { a[0] = lds32(x); a[1] = lds32(x + 32); a[2] = lds32(x - 32); a[3] = dup(a[0]); };
            frag(a3, kp + 1536);
#pragma unroll
            for (int i = 1; i < 8; i++) ldsm4(s[i], u1 + (SC_ST - SC_UT) + 256 * i);
            __syncwarp();
#pragma unroll 1
            for (uint32_t ko = 0, uo = 0; ko != 512;) {
                uint32_t a2[4], a1[4], a0[4], b[4][4];
                ko = fresh(ko); uo = fresh(uo);
                kp = kb + ko; u1 = ub + uo;
                const uint32_t up = uc + uo;
                ko += 64; uo -= 16;
                frag(a2, kp + 1024);
#pragma unroll
                for (int i = 1; i < 4; i++) ldsm4(b[i], up + 512 * i);
                asm("ldmatrix.sync.aligned.m8n8.x2.shared.b16 {%0,%1}, [%2];" : "=r"(b[0][2]), "=r"(b[0][3]) : "r"(up + 256));
                frag(a1, kp + 512); frag(a0, kp);
                kp += 64; u1 -= 16;
#pragma unroll
                for (int i = 1; i < 7; i++) mma_bf(acc[2 * i + 2], a3[0], a3[1], a3[2], a3[3], s[i][0], s[i][1]);
#pragma unroll
                for (int e = 0; e < 4; e++) a3[e] = bsub2(a2[e], a3[e]);
#pragma unroll
                for (int i = 1; i < 7; i++) mma_bf(acc[2 * i + 3], a2[0], a2[1], a2[2], a2[3], s[i][2], s[i][3]);
                ldsm4(s[1], u1 + (SC_ST - SC_UT) + 256);
#pragma unroll
                for (int i = 1; i < 7; i++) mma_bf(M[i + 1], a3[0], a3[1], a3[2], a3[3], b[i >> 1][2 * (i & 1)], b[i >> 1][2 * (i & 1) + 1]);
                frag(a3, kp + 1536);
#pragma unroll
                for (int i = 2; i < 8; i++) mma_bf(acc[2 * i], a1[0], a1[1], a1[2], a1[3], s[i][0], s[i][1]);
#pragma unroll
                for (int e = 0; e < 4; e++) a1[e] = bsub2(a0[e], a1[e]);
#pragma unroll
                for (int i = 2; i < 8; i++) { mma_bf(acc[2 * i + 1], a0[0], a0[1], a0[2], a0[3], s[i][2], s[i][3]); ldsm4(s[i], u1 + (SC_ST - SC_UT) + 256 * i); }
#pragma unroll
                for (int i = 2; i < 8; i++) mma_bf(M[i], a1[0], a1[1], a1[2], a1[3], b[i >> 1][2 * (i & 1)], b[i >> 1][2 * (i & 1) + 1]);
            }
            u1 = ub;
#pragma unroll
            for (int i = 2; i < 8; i++)
#pragma unroll
                for (int c = 0; c < 4; c++) { acc[2 * i][c] += M[i][c]; acc[2 * i + 1][c] -= M[i][c]; }
        }
        if ((warp & 3) == 0) TSTAMP(11 + (warp >> 2));
        mbar_wait(bar_v);
        const uint32_t vt = fresh(sb + SC_V) + swap01(warp) * V_STRIDE;
        const uint32_t g1 = fresh(u1) - ut + sb + SC_GT;
        const uint32_t ydst = sb + SC_RT + rank * Y_RS + warp * Y_CS + lane * 16;
        const uint32_t ydr = mapa(ydst, rank ^ 1), ybr = mapa(bar_y, rank ^ 1);
        auto stairs = [&](auto R) {
        uint32_t ug[2][2][4];
        auto ld_ug = [&](int i) { ldsm4t(ug[i & 1][0], u1 + 256 * i); ldsm4t(ug[i & 1][1], g1 + 256 * i); };
        auto ship = [&](int i) {
            const uint32_t (&u)[4] = ug[i & 1][0], (&gg)[4] = ug[i & 1][1];
            const uint32_t y0 = gmix(gg[0], acc[2 * i][0], acc[2 * i][1], u[0]), y1 = gmix(gg[1], acc[2 * i][2], acc[2 * i][3], u[1]);
            const uint32_t y2 = gmix(gg[2], acc[2 * i + 1][0], acc[2 * i + 1][1], u[2]), y3 = gmix(gg[3], acc[2 * i + 1][2], acc[2 * i + 1][3], u[3]);
            if ((i & 1) != R.value) st_async128(ydr + 512 * (i >> 1), y0, y1, y2, y3, ybr + 8 * (i >> 1));
            else asm volatile("{ .reg .pred q; setp.eq.u32 q, %6, 0; st.shared.v4.u32 [%0], {%2,%3,%4,%5}; bar.warp.sync 0xffffffff; @q mbarrier.arrive.shared::cta.b64 _, [%1]; }"
                              :: "r"(ydst + 512 * (i >> 1)), "r"(bar_y + 8 * (i >> 1)), "r"(y0), "r"(y1), "r"(y2), "r"(y3), "r"(lane) : "memory");
        };
        const uint32_t VD = vt + (VC_OFF - 400 - 16 * t) * 4 + (8 * g ^ 16 * (-t & 2)), VD2 = vt + (VC_OFF - 415 - 16 * t) * 4 + (8 * g ^ 16 * (~t & 2));
        uint2 bd[10];
        uint32_t x[2][4][4];
        auto ld4 = [&](uint32_t (&v)[4], int dl) { const uint2 w = lds64(VD + 256 * dl); v[0] = w.x; v[1] = w.y; v[2] = lds32(VD2 + 256 * dl); v[3] = dup(w.x); };
        auto mm4 = [&](const uint32_t (&v)[4], int dl) {
#pragma unroll
            for (int s = dl & 1; s < 10; s += 2) if ((dl + s) / 2 >= 4 && (dl + s) / 2 < 16) mma_bf(acc[(dl + s) / 2], v[0], v[1], v[2], v[3], bd[s].x, bd[s].y);
        };
        const uint32_t KE = kt + (KT_D + g + t) * 4, VE = vt + (VE_BASE - 912 - 16 * t) * 4 + (8 * g ^ 16 * (~t & 2));
        uint32_t b0[8], b1[8];
        auto ld8 = [&](uint32_t (&v)[4], int dl) { const uint2 w = lds64(VE + 512 * dl), z = lds64(VE + 512 * dl - 256); v[0] = w.x; v[1] = w.y; v[2] = z.x; v[3] = z.y; };
        auto mm8 = [&](const uint32_t (&v)[4], int dl, int lo, int hi) {
#pragma unroll
            for (int s = 0; s < 8; s++) if (dl + s >= lo && dl + s < hi) mma_bf(acc[dl + s], v[0], v[1], v[2], v[3], b0[s], b1[s]);
        };
        ld4(x[0][0], 6);
#pragma unroll
        for (int s = 0; s < 10; s++) bd[s] = lds64(kt + (KT_C + 2 * g + 2 * t + 8 * s) * 4);
        mm4(x[0][0], 6);
        uint32_t e[4][4];
#pragma unroll
        for (int k = 1; k < 6; k++) {
#pragma unroll
            for (int j = 0; j < 4; j++) ld4(x[k & 1][j], 4 * k + 3 + j);
            ld_ug(k + 1);
            if (k == 3) {
#pragma unroll
                for (int s = 0; s < 8; s++) { b0[s] = lds32(KE + 32 * s); b1[s] = lds32(KE + 32 * s + 16); }
            }
            if (k > 1) ship(k);
#pragma unroll
            for (int j = 0; j < 4; j++) {
                mm4(x[k & 1][j], 4 * k + 3 + j);
                if (k == 3) { uint32_t v[4], z[4]; ld8(e[j], 8 + j); ld8(v, 12 + j); ld4(z, 30 - j); mm8(v, 12 + j, 12, 16); mm8(e[j], 8 + j, 8, 12); mm4(z, 30 - j); }
                if (k == 5) { ld8(e[j], 8 + j + p.zero); mm8(e[j], 8 + j, 12, 16); }
            }
        }
        ld_ug(7);
        ship(7 - R.value); ship(6 + R.value);
        };
        if (rank) stairs(std::integral_constant<int, 1>()); else stairs(std::integral_constant<int, 0>());
        if ((warp & 3) == 0) TSTAMP(14 + (warp >> 2)); else TSTAMP(21 + warp);
    }
}

constexpr int SF_WD = 73728;
constexpr int SF_RED = 49152;
constexpr int MU_HALF = 640, MU_STRIDE = 1344, SM_RAW = 98304, SM_UT = SM_RAW + 16384, SM_G = SM_UT + 16 * MU_STRIDE, SM_Y = 196608, SM_KT = 138880, SM_KW = SM_G - 49152;
constexpr int SF_XS = 221184;
constexpr int SF_MISC = SF_XS + 8 * 1168;
constexpr int SF_KG = SF_MISC - 10 * KG_STAGE;
constexpr int SF_WR = SF_KG - 2304;
constexpr int FB_X = 64, FB_KDONE = 72, FB_KEYS = 80, FB_FREE = 88  , FB_W = 104, FB_D = FB_W + 72, FB_MU = FB_D + 96, FB_MG = FB_MU + 8, FB_MT = FB_MU + 16, FS_PART = 512, FS_TOK = 896, FS_BM = 1024;
enum { BAR_R = 7, BAR_GU = 8, BAR_RED = 9, BAR_R2 = 10, BAR_G = 12  , BAR_M = 15 };
static_assert(SF_KG % 128 == 0 && NPRE <= 8 && SM_KT + 4 * 2112 <= 147456 && SM_G + MU_STRIDE <= SF_WR - 4 * 9216 && SM_KW + 6 * 2112 >= SM_RAW && SM_KW + 12 * 2112 <= SM_UT, "layout");

__device__ __forceinline__ int mini_ch0(int f) { return f < NW ? 16 * (f - 12) : 32 * (f - NW); }

__device__ __forceinline__ void ffn_front(const Params& p, const CUtensorMap* maps, uint32_t sb, int warp, int lane, int f, unsigned epoch) {
    const unsigned t0 = clock32();
    const int g = lane >> 2, t = lane & 3, mi = lane >> 3, r8 = lane & 7;
    const bool isx = f < NX;
    const int nrw = f < 8 ? 6 : 4, r0 = f < 8 ? 48 * f : 128 + 32 * f;
    const int rw = warp < 12 ? 13 - warp : warp ^ (warp < 14 ? 10 : 15);
    const uint32_t bar_row = sb + SF_MISC  , bar_x = bar_row + FB_X;
    const uint32_t s_part = bar_row + FS_PART  , s_tok = bar_row + FS_TOK  ;
    const uint32_t rows = sb + SF_WR - 9216 * (rw + 1);
    {
#pragma unroll 1
        for (int i = warp < 10 ? 30 : warp - 10; i < 29; i += 6) if (elect()) mbar_init(bar_x + 8 * i, i == 1 ? 4 + (f >= 12) : i < 27 ? 1 : i == 27 ? 2 : f < NW ? 8 : 16);
        const uint32_t bytes = rw < 6 ? 9216 : 1152, dst = rw < 6 ? rows : sb + SF_WR + (rw & 1) * 1152;
        const __nv_bfloat16* src = rw < 6 ? p.u + (size_t)(r0 + 8 * rw) * DM : (rw & 1) ? p.gatew : p.wr;
        if (elect()) { mbar_init(bar_row + 8 * rw, 1); mbar_fence(); mbar_expect(bar_row + 8 * rw, bytes); }
        if (warp == 13) { sts32(s_part + 64 + lane * 4, 0); sts32(bar_row + FS_BM + lane * 4, 0); }
        bar_sync(0, NTHR);
        if (rw < nrw) until(t0, RDELAY);
        if (rw < nrw || rw >= 6) { if (elect()) bulk_g2s(dst, src, bytes, bar_row + 8 * rw); }
    }
    uint4* const kdst = p.s->keys + (lane >> 1) * 128 + 2 * f + (lane & 1);
    if (warp == 15) TSTAMP(1);

    if (warp == 12) {
        if (lane < 22) mbar_expect(bar_row + FB_W + 8 * lane, lane < 9 ? 24576 : lane < 21 ? 12288 : f < NW ? 16384 : 32768);
        if (elect()) { prefetch_map(maps + 1); prefetch_map(maps + 2); prefetch_map(maps + (isx ? 3 : 5)); }
        unsigned tb = t0 + WDELAY;
        auto pieces = [&](int n, int end, uint32_t dst) {
#pragma unroll 1
            for (; n < end; n++, dst += 12288) {
                until(tb, 0); tb += WGAP;
                if (elect()) tma3d(dst, maps + 1 + (n & 1), 0, 64 * (n >> 1), 3 * f, bar_row + FB_W + 8 * (n >> 1));
            }
        };
        if (!isx) {
            until(t0, MDELAY);
#pragma unroll 1
            for (int k = f >= NW; k >= 0; k--) if (elect()) tma4d(sb + SM_RAW - 49152 * k, maps + 5, mini_ch0(f) + 16 * k, 0, 0, 0, bar_row + FB_MU);
            if (f >= NW) return;
        }
#pragma unroll 1
        for (int i = 0; i < 4; i++) {
            if (i == 1) { mbar_wait(bar_row + FB_KEYS); mbar_wait(bar_row + FB_KDONE); tb = clock32() + RESUME; }
            if (i == 3) mbar_wait(bar_row + FB_FREE);
            const int n = ((0x0c080000 + NPRE * 256) >> (8 * i)) & 255;
            pieces(n, ((0x120c0800 + NPRE) >> (8 * i)) & 255, sb + 12288 * (((0x000c0000 + NPRE * 256) >> (8 * i)) & 255));
        }
        TSTAMP(12);
        if (isx) {
#pragma unroll 1
            for (int i = 0; i < 12; i++) {
                const int n = (0x987610ba5432ull >> (4 * i)) & 15;
                if (i == 6) mbar_wait(bar_row + FB_FREE + 8);
                until(tb, 0); tb += DGAP;
                if (elect()) tma2d(sb + SF_WD + n * 12288, maps + 3, 32 * (f >> 1), 2304 * (f & 1) + 192 * n, bar_row + FB_D + 8 * n);
            }
            TSTAMP(13);
        }
    } else if (warp == 13) {
        const uint32_t tag = key_tag(epoch), par = (epoch & 1) ? 0u : 0x8000u;
        stg128(kdst, 0, 0, 0, 0);
        if (lane < 8 && isx && !(f & 1)) st_rlx32(&p.s->sel[32 * f + lane], 0);
        bar_sync(BAR_R, 32 * (nrw + 1));
        TSTAMP(3);
        {
            const uint32_t sg = fresh(s_part) + 192 + lane * 4;
            const uint32_t gb = pack_bf16(sigmoidf_(rbf(__uint_as_float(lds32(sg)))), sigmoidf_(rbf(__uint_as_float(lds32(sg + 128))))) | par | (par << 16);
            asm volatile("st.relaxed.gpu.global.u16 [%0], %1;" :: "l"(p.s->gate + r0 + lane), "h"((unsigned short)gb) : "memory");
            if (nrw > 4 && lane < 16) asm volatile("st.relaxed.gpu.global.u16 [%0], %1;" :: "l"(p.s->gate + r0 + 32 + lane), "h"((unsigned short)(gb >> 16)) : "memory");
        }
        bar_sync(BAR_R2, 32 * (nrw + 1));
        {
            const uint4 v = lds128(fresh(s_tok) + (lane & 1) * 16);
            asm volatile("st.relaxed.gpu.global.v4.u32 [%0], {%1,%2,%3,%4};" :: "l"(kdst), "r"(v.x | tag), "r"(v.y | tag), "r"(v.z | tag), "r"(v.w | tag) : "memory");
        }
        TSTAMP(4);
        if (lane == 0) { mbar_arrive(bar_row + FB_KEYS); mbar_expect(bar_x, 8 * 1152); }
        if (f >= NW) return;
        mbar_wait(bar_row + FB_KDONE);
        uint32_t k[16];
        const uint4* src = p.s->keys + (f & 15) * 128 + lane;
#pragma unroll 1
        for (int it = 0;; it++) {
            uint32_t bad = 0;
#pragma unroll
            for (int i = 0; i < 4; i++) {
                const uint4 x = ld_rlx128(src + (i < 3 || lane < 24 ? 32 * i : 64));
                k[i] = x.x; k[4 + i] = x.y; k[8 + i] = x.z; k[12 + i] = x.w;
                bad |= x.x ^ tag;
            }
            const bool ok = __all_sync(0xffffffffu, (bad & 0xf800u) == 0);
            if (ok) break;
            if (it > (1 << 20)) give_up();
        }
        TSTAMP(5);
        uint32_t key = 0, m = __reduce_max_sync(0xffffffffu, max(max(k[0], k[1]), max(k[2], k[3])));
#pragma unroll TUN
        for (int r = 0; r < 8; r++) {
            bool pop[4];
#pragma unroll
            for (int i = 0; i < 4; i++) { pop[i] = k[i] == m; k[i] = pop[i] ? k[4 + i] : k[i]; }
            const uint32_t mn = __reduce_max_sync(0xffffffffu, max(max(k[0], k[1]), max(k[2], k[3])));
            if (elect()) bulk_g2s(sb + SF_XS + r * 1168, p.u + (size_t)key_row(m) * DM, 1152, bar_x);
#pragma unroll
            for (int i = 0; i < 4; i++) { k[4 + i] = pop[i] ? k[8 + i] : k[4 + i]; k[8 + i] = pop[i] ? k[12 + i] : k[8 + i]; k[12 + i] = pop[i] ? 0 : k[12 + i]; }
            if (r8 == r) key = m;
            m = mn;
        }
        const int row = key_row(key);
        sts32(s_tok + r8 * 8, row);
        TSTAMP(6);
        if (isx) {
            if (!(f & 1)) {
                __nv_bfloat16* o = p.out + (size_t)row * DM + 16 * f + 8 * mi;
                asm volatile("st.relaxed.gpu.global.v4.u32 [%0], {%1,%1,%1,%1};" :: "l"(o), "r"(0) : "memory");
                if (__any_sync(0xffffffffu, ld_rlx32(o) != 0)) give_up();
                if (lane < 8) st_rlx32(&p.s->sel[32 * f + lane], key);
            } else wait_sel(p, f >> 1, r8, tag);
            uint32_t gb;
#pragma unroll 1
            for (int it = 0;; it++) {
                asm volatile("ld.relaxed.gpu.global.u16 %0, [%1];" : "=r"(gb) : "l"(p.s->gate + row) : "memory");
                gb ^= par;
                if (!(gb & 0x8000u)) break;
                if (it > (1 << 20)) give_up();
            }
            const uint32_t rb = key ^ 0x80000000u, rv = (rb ^ (((int)rb >> 31) & 0x7fff0000u)) & 0xffff0000u;
            sts32(s_tok + r8 * 8 + 4, __float_as_uint(rbf(1.0f - bf_lo(gb)) * rbf(sigmoidf_(__uint_as_float(rv)))));
            __syncwarp();
            TSTAMP(7);
            bar_arrive(BAR_RED, 416);
        }
    } else {
        if (rw < nrw) {
            float c[3][4];
#pragma unroll
            for (int i = 0; i < 3; i++) { c[i][0] = c[i][1] = c[i][2] = c[i][3] = 0.f; }
            mbar_wait(bar_row + 48); mbar_wait(bar_row + 56);
            const uint32_t b = fresh(sb + SF_WR) + (g & 1) * 1152 + (g >> 2) * 64 + t * 16 + (g & 2) * 2;
            uint32_t w[18][2];
#pragma unroll
            for (int kb = 0; kb < 18; kb++) { const uint32_t o = ((kb & 1) ? b ^ 64 : b) + 128 * (kb >> 1); w[kb][0] = lds32(o); w[kb][1] = lds32(o + 8); }
            mbar_wait(bar_row + 8 * rw);
            if (warp == 15) TSTAMP(2);
            const uint32_t a = fresh(rows) + g * 1152 + (g & 1) * 64 + t * 16;
#pragma unroll
            for (int kb = 0; kb < 18; kb++) {
                const uint4 x = lds128(((kb & 1) ? a ^ 64 : a) + 128 * (kb >> 1));
                mma_bf(c[kb % 3], x.x, x.y, x.z, x.w, w[kb][0], w[kb][1]);
            }
            const float sr = c[0][0] + c[1][0] + c[2][0] + __shfl_down_sync(0xffffffffu, c[0][2] + c[1][2] + c[2][2], 1);
            const float sg = c[0][1] + c[1][1] + c[2][1] + __shfl_down_sync(0xffffffffu, c[0][3] + c[1][3] + c[2][3], 1);
            const uint32_t rb = pack_bf16(0.f, sr);
            if (t == 2 * (g & 1)) {
                sts32(s_part + (8 * rw + g) * 4, (rb ^ (((int)rb >> 31) & 0x7fff0000u) ^ 0x80000000u) | (uint32_t)(2047 - r0 - 8 * rw - g));
                sts32(s_part + 192 + (8 * rw + g) * 4, __float_as_uint(sg));
            }
            __syncwarp();
            bar_sync(BAR_R, 32 * (nrw + 1));
            const uint32_t sk = fresh(s_part), kk = lds32(sk + (8 * rw + r8) * 4);
            int n = 0;
#pragma unroll
            for (int i = 0; i < 3; i++) { const uint4 v = lds128(sk + mi * 48 + 16 * i); n += (v.x > kk) + (v.y > kk) + (v.z > kk) + (v.w > kk); }
            n += __shfl_xor_sync(0xffffffffu, n, 8); n += __shfl_xor_sync(0xffffffffu, n, 16);
            if (n < 8) sts32(s_tok + 4 * n, kk);
            __syncwarp();
            bar_arrive(BAR_R2, 32 * (nrw + 1));
        }
    }
}

__device__ __forceinline__ void ffn_work(const Params& p, uint32_t sb, int warp, int lane, int f, unsigned epoch) {
    const int g = lane >> 2, t = lane & 3, mi = lane >> 3, r8 = lane & 7;
    const bool isx = f < NX;
    const uint32_t bar_x = sb + SF_MISC + FB_X, bar_free = sb + SF_MISC + FB_FREE, bar_w = sb + SF_MISC + FB_W, bar_d = sb + SF_MISC + FB_D, s_tok = sb + SF_MISC + FS_TOK;
    uint32_t fr[24][4];
    auto pin = [&] {
#pragma unroll
        for (int i = 0; i < 24; i += 8) asm volatile("" :: "r"(fr[i][0]), "r"(fr[i + 1][0]), "r"(fr[i + 2][0]), "r"(fr[i + 3][0]), "r"(fr[i + 4][0]), "r"(fr[i + 5][0]), "r"(fr[i + 6][0]), "r"(fr[i + 7][0]) : "memory");
    };
    {
        const int j = (unsigned)(warp - 4) < 6, w = warp - (j ? 4 : warp < 4 ? 0 : 6);
        float ag[2][4], au[2][4];
#pragma unroll
        for (int i = 0; i < 2; i++) { ag[i][0] = ag[i][1] = ag[i][2] = ag[i][3] = 0.f; au[i][0] = au[i][1] = au[i][2] = au[i][3] = 0.f; }
        const uint32_t wb = sb + (w >> 1) * 4096 + (r8 + 8 * (mi >> 1)) * 64 + (((2 * (w & 1) + (mi & 1)) ^ (r8 >> 1)) << 4);
        const uint32_t xb = sb + SF_XS + r8 * 1168 + mi * 16;
        auto load = [&](int i, int n, int place) {
            mbar_wait(bar_w + 8 * n);
            const uint32_t wk = fresh(wb) + place * 24576;
#pragma unroll
            for (int s = 0; s < 4; s++) { ldsm4t(fr[8 * i + s], wk + 1024 * s); ldsm4t(fr[8 * i + 4 + s], wk + 1024 * s + 12288); }
        };
        auto mul = [&](int i, uint32_t xk) {
            uint32_t x[2][4];
            ldsm4(x[0], xk); ldsm4(x[1], xk + 64);
#pragma unroll
            for (int s = 0; s < 4; s++) {
                const uint32_t (&a)[4] = fr[8 * i + s], (&b)[4] = fr[8 * i + 4 + s];
                mma_bf(ag[s & 1], a[0], a[1], a[2], a[3], x[s >> 1][2 * (s & 1)], x[s >> 1][2 * (s & 1) + 1]);
                mma_bf(au[s & 1], b[0], b[1], b[2], b[3], x[s >> 1][2 * (s & 1)], x[s >> 1][2 * (s & 1) + 1]);
            }
        };
#pragma unroll
        for (int i = 0; i < 3; i++) load(i, 3 * j + i, (i ? 5 : 3) * j + i);
        pin();
        bar_sync(BAR_G + j, 192);
        if (w == 0 && lane == 0) mbar_arrive(bar_free + 8 * j);
        mbar_wait(bar_x);
        if (warp == 0) TSTAMP(8);
        {
            const uint32_t xk = fresh(xb) + 384 * j;
#pragma unroll
            for (int i = 0; i < 3; i++) { mul(i, (i ? fresh(xk) : xk) + 128 * i); if (i == 0) { asm volatile("" :: "f"(ag[0][0]), "f"(ag[1][0]), "f"(au[0][0]), "f"(au[1][0])); sts32(s_tok + 64, clock32()); } }
        }
#pragma unroll 1
        for (int n = 6 + j; n < 9; n += 2) { load(0, n, n - 6); mul(0, fresh(xb) + 128 * n); }
#pragma unroll
        for (int c = 0; c < 4; c++) { ag[0][c] += ag[1][c]; au[0][c] += au[1][c]; }
        if (j) {
            sts128(wb + 24576, __float_as_uint(ag[0][0]), __float_as_uint(ag[0][1]), __float_as_uint(ag[0][2]), __float_as_uint(ag[0][3]));
            sts128(wb + 25600, __float_as_uint(au[0][0]), __float_as_uint(au[0][1]), __float_as_uint(au[0][2]), __float_as_uint(au[0][3]));
        }
        bar_sync(BAR_GU, 384);
        if (!j) {
            const uint32_t sf = fresh(wb);
            const uint4 g1 = lds128(sf + 24576), u1 = lds128(sf + 25600);
            const uint32_t gs[4] = {g1.x, g1.y, g1.z, g1.w}, us[4] = {u1.x, u1.y, u1.z, u1.w};
            if (warp == 0) TSTAMP(9);
            float h[4];
#pragma unroll
            for (int c = 0; c < 4; c++) {
                const float gv = rbf(ag[0][c] + __uint_as_float(gs[c]));
                h[c] = rbf(gv * sigmoidf_(gv)) * rbf(au[0][c] + __uint_as_float(us[c]));
            }
            uint32_t h0, h1;
            asm("movmatrix.sync.aligned.m8n8.trans.b16 %0, %1;" : "=r"(h0) : "r"(pack_bf16(h[0], h[1])));
            asm("movmatrix.sync.aligned.m8n8.trans.b16 %0, %1;" : "=r"(h1) : "r"(pack_bf16(h[2], h[3])));
            if (h0 == 0) h0 = 0x8000u;
            asm volatile("{ .reg .b64 v; mov.b64 v, {%1, %2}; st.relaxed.gpu.global.b64 [%0], v; }" :: "l"(p.s->h + ((epoch & 1) * 288 + 6 * f + w) * 32 + lane), "r"(h0), "r"(h1) : "memory");
        }
        if (isx) {
            if (warp == 0) TSTAMP(10);
            const uint2* hsrc = p.s->h + ((epoch & 1) * 288 + 144 * (f & 1) + 12 * warp) * 32 + lane;
            uint2 hb[12];
            auto ldh = [&](int s) { asm volatile("ld.relaxed.gpu.global.v2.u32 {%0, %1}, [%2];" : "=r"(hb[s].x), "=r"(hb[s].y) : "l"(hsrc + 32 * s) : "memory"); };
#pragma unroll
            for (int s = 0; s < 12; s++) ldh(s);
#pragma unroll 1
            for (int it = 0;; it++) {
                bool again = false;
#pragma unroll
                for (int s = 0; s < 12; s += 2) if (__any_sync(0xffffffffu, min(hb[s].x, hb[s + 1].x) == 0)) { ldh(s); ldh(s + 1); again = true; }
                if (!again) break;
                if (it > (1 << 16)) give_up();
            }
            if (warp == 0) TSTAMP(11);
            mbar_wait(bar_d + 8 * warp);
            if (warp == 9) TSTAMP(14);
            float ad[2][2][4];
#pragma unroll
            for (int i = 0; i < 4; i++) { ad[i >> 1][i & 1][0] = ad[i >> 1][i & 1][1] = ad[i >> 1][i & 1][2] = ad[i >> 1][i & 1][3] = 0.f; }
            const uint32_t wd = fresh(sb) + SF_WD + warp * 12288 + (r8 + 8 * (mi >> 1)) * 64 + (((mi & 1) ^ (r8 >> 1)) << 4);
#pragma unroll
            for (int s = 0; s < 12; s++) {
                uint32_t a[4], b[4];
                ldsm4t(a, wd + 1024 * s); ldsm4t(b, (wd ^ 32) + 1024 * s);
                mma_bf(ad[0][s & 1], a[0], a[1], a[2], a[3], hb[s].x, hb[s].y);
                mma_bf(ad[1][s & 1], b[0], b[1], b[2], b[3], hb[s].x, hb[s].y);
            }
            const uint32_t rd = sb + SF_RED + warp * 1152 + (72 * t + g) * 4;
#pragma unroll
            for (int i = 0; i < 8; i++) sts32(rd + (i >> 2) * 64 + (i & 1) * 144 + ((i >> 1) & 1) * 32, __float_as_uint(ad[i >> 2][0][i & 3] + ad[i >> 2][1][i & 3]));
            bar_sync(BAR_RED, 416);
            if (warp < 4) {
                const int tid = 32 * warp + lane;
                const uint32_t rs = fresh(sb + SF_RED) + (tid >> 4) * 144 + (tid & 15) * 8;
                const uint2 tk = lds64(fresh(s_tok) + (tid >> 4) * 8);
                float x = 0.f, y = 0.f;
#pragma unroll
                for (int w = 0; w < 12; w++) { const uint2 v = lds64(rs + w * 1152); x += __uint_as_float(v.x); y += __uint_as_float(v.y); }
                asm volatile("red.relaxed.gpu.global.add.noftz.bf16x2 [%0], %1;" :: "l"(p.out + (size_t)tk.x * DM + 32 * (f >> 1) + 2 * (tid & 15)),
                             "r"(pack_bf16(x * __uint_as_float(tk.y), y * __uint_as_float(tk.y))) : "memory");
            }
            if (warp == 0) { TSTAMP(15); TFLUSH(); }
            asm volatile("exit;"); __builtin_unreachable();
        }
    }
}

__device__ __forceinline__ void fetch_k(const uint4* src, uint64_t (&v)[6], uint32_t a, uint32_t b) {
    asm volatile("{ .reg .pred p; setp.eq.u32 p, %7, %8; @p ld.relaxed.gpu.global.v2.u64 {%0,%1}, [%6]; @p ld.relaxed.gpu.global.v2.u64 {%2,%3}, [%6 + 512]; @p ld.relaxed.gpu.global.v2.u64 {%4,%5}, [%6 + 1024]; }"
                 : "+l"(v[0]), "+l"(v[1]), "+l"(v[2]), "+l"(v[3]), "+l"(v[4]), "+l"(v[5]) : "l"(src), "r"(a), "r"(b));
}
__device__ __forceinline__ uint32_t mini_conv(const Params& p, uint32_t sb, int warp, int lane, int f, unsigned epoch) {
    const int g = lane >> 2, t = lane & 3, mi = lane >> 3, r8 = lane & 7;
    const uint32_t fb = sb + SF_MISC, kt = sb + (warp >= 12 ? SM_KT - 12 * 2112 : f < NW ? SM_KW + 2 * 2112 : SM_KW) + warp * 2112;
    const bool ism = f >= NW;
    const int ch0 = mini_ch0(f);
    uint32_t seq = 128, key;
    uint64_t v[6] = {};
    const uint4* src = p.s->kp + lane;
    auto hi = [&](int i) { return (uint32_t)(v[i] >> 32); };
    if (f >= (warp < 4 ? NW : NX)) {
    {
        const uint32_t c = 36 + (warp & 3) + 2 * (warp & 12), y = (uint32_t)((warp < 8 ? 0xa026802400000000ull : 0x2a2e00280080a22cull) >> ((8 * warp) & 48)) & 0xffff;
        seq = ism ? 0x101 * c - 0x400 : y + (warp & 1) * ((y >> 5) & 0x101);
        src += (ch0 + (seq & 31)) * 96;
    }
    if (seq & 32) {
        if (seq & 4) {
            const int q = (seq & 3) + ((seq >> 1) & 4);
            const uint32_t ab = sb - 3072 * (seq & 16), d = ab + SM_UT + g * MU_STRIDE + (8 + 4 * q + t) * 16;
            sts128(ab + SM_UT + (2 * q + (mi >> 1)) * MU_STRIDE + (mi & 1) * MU_HALF + r8 * 16, 0, 0, 0, 0);
            mbar_wait(fb + FB_MU);
            if (warp == 15) TSTAMP(16);
            const uint32_t a = fresh(ab + SM_RAW) + q * 2048 + (8 * mi + 4 * (r8 & 1) + (r8 >> 1)) * 32 + ((r8 & 1) << 4);
            uint32_t x[4][4];
#pragma unroll
            for (int i = 0; i < 4; i++) ldsm4t(x[i], (i & 2 ? a ^ 16 : a) + 1024 * (i & 1));
#pragma unroll
            for (int i = 0; i < 4; i++) sts128(d + (i & 1) * MU_HALF + (i & 2) * 4 * MU_STRIDE, x[i][0], x[i][1], x[i][2], x[i][3]);
            __syncwarp();
            if (lane == 0) mbar_arrive(fb + FB_MT);
        }
        if (!EFETCH) mbar_wait(fb + FB_KDONE);
        fetch_k(src, v, 0, 0);
        if (EFETCH) mbar_wait(fb + FB_KDONE);
        if ((warp | 2) == GW) { fetch_gates(p, (warp >> 1) & 1, lane, epoch, sb + SM_G + (lane & 1) * MU_HALF); __syncwarp(); if (lane == 0) mbar_arrive(fb + FB_MG); }
        mbar_wait(fb + FB_KEYS);
        if (warp == TW) TSTAMP(17);
    }
    }
    const uint32_t lo = (mi & 1) * MU_HALF + (8 + r8) * 16 + (mi >> 1) * 128;
#pragma unroll 1
    do {
        const int c = seq & 31;
        if (seq & 32) {
#pragma unroll 1
        for (int it = 0; !__all_sync(0xffffffffu, ((hi(1) ^ k_tag(epoch)) | (hi(3) ^ k_tag(epoch)) | (hi(5) ^ k_tag(epoch)) | ((uint32_t)v[5] & p.zero)) < 65536); it++) {
            fetch_k(src, v, 0, 0);
            if (it > (1 << 20)) give_up();
        }
        mbar_wait(fb + FB_MT);
        sts128(kt + t * 16, 0, 0, 0, 0);
        if (warp == TW) TSTAMP(seq >> 8 ? 7 : 10);
        const uint32_t w[12] = {(uint32_t)v[0], hi(0), (uint32_t)v[1], (uint32_t)v[2], hi(2), (uint32_t)v[3], (uint32_t)v[4], hi(4), 0, 0, 0, 0};
        k_tables<false>(fresh(kt), fresh(lane), w);
        }
        __syncwarp();
        if (seq & 128) ffn_work(p, sb, warp, fresh(lane), f, epoch);
        if (!(seq & 32)) return 0;
        const uint32_t ab = sb - 49152 * (c >> 4), kb = fresh(kt) + (16 + g - 2 * t) * 4, ub = fresh(ab + SM_UT + (c & 15) * MU_STRIDE) + lo;
        const uint32_t yd = ab + SM_Y + (c & 15) * 1056 + (c & 8) * 8 + lane * 16;
        uint32_t kp = kb, u1 = ub;
        if (warp == TW && !(seq >> 8)) TSTAMP(13);
        seq >>= 8;
        src += ((int)(seq & 31) - c) * 96;
#pragma unroll
        for (int i = 0; i < 6; i++) v[i] = 0;
        key = 0;
        float acc[8][4];
#pragma unroll
        for (int i = 0; i < 8; i++) { acc[i][0] = acc[i][1] = acc[i][2] = acc[i][3] = 0.f; }
        uint32_t a[4][4], b[2][2][4];
        auto lda = [&](int j, int o) { const uint32_t x = kp + 64 * o + 512 * j; a[j][2] = o ? a[j][1] ^ p.zero : lds32((kp ^ p.zero) + 512 * j - 32); a[j][0] = lds32(x); a[j][1] = lds32(x + 32); a[j][3] = a[j][0] ^ p.zero; };
        auto ldb = [&](int s, int o) { ldsm4(b[s][0], u1 - 16 * o); ldsm4(b[s][1], u1 + 256 - 16 * o); };
        ldb(0, 0);
#pragma unroll
        for (int j = 0; j < 4; j++) lda(j, 0);
#pragma unroll
        for (int s = 0; s < 8; s++) {
            if (s == FPOS) {
                const uint32_t e = seq | (__float_as_uint(acc[0][0]) & p.zero);
                fetch_k(src, v, e & 32, 32);
                if (KEYPF) asm volatile("{ .reg .pred p; setp.eq.u32 p, %2, 0; @p ld.relaxed.gpu.global.u32 %0, [%1]; }" : "+r"(key) : "l"(&p.s->sel[(ch0 >> 5) * 64 + r8]), "r"(e));
            }
            if (s < 7) ldb(~s & 1, s + 1);
#pragma unroll
            for (int i = 0; i < 4; i++) {
                const int j = (i >> 1) + 2 * (i & 1);
#pragma unroll
                for (int mu = 3 - j; mu >= 0; mu--) mma_bf(acc[NACC == 8 && j + mu == 3 && (j & 1) ? 6 + (j >> 1) : j + mu + (j & 2)], a[j][0], a[j][1], a[j][2], a[j][3], b[s & 1][mu >> 1][2 * (mu & 1)], b[s & 1][mu >> 1][2 * (mu & 1) + 1]);
                if (s < 7) lda(j, s + 1);
            }
        }
        if (warp == TW && !seq) TSTAMP(14);
        mbar_wait(fb + FB_MG);
#pragma unroll
        for (int e = 0; e < 4; e++) { acc[2][e] += acc[4][e]; acc[3][e] += acc[5][e]; if (NACC == 8) acc[3][e] += acc[6][e] + acc[7][e]; }
        uint32_t ug[4][4];
#pragma unroll
        for (int i = 0; i < 2; i++) { ldsm4t(ug[i], ub + 256 * i); ldsm4t(ug[2 + i], fresh(sb + SM_G) + lo + 256 * i); }
#pragma unroll
        for (int i = 0; i < 2; i++) {
            const uint32_t (&u)[4] = ug[i], (&gg)[4] = ug[2 + i];
            sts128(yd + 512 * i, gmix(gg[0], acc[2 * i][0], acc[2 * i][1], u[0]), gmix(gg[1], acc[2 * i][2], acc[2 * i][3], u[1]),
                   gmix(gg[2], acc[2 * i + 1][0], acc[2 * i + 1][1], u[2]), gmix(gg[3], acc[2 * i + 1][2], acc[2 * i + 1][3], u[3]));
        }
        __syncwarp();
        if (warp == TW) TSTAMP(18 + (seq != 0));
    } while (seq);
    if (warp >= 12) TSTAMP(12 + warp);
    return key;
}
__device__ __forceinline__ void mini_out(const Params& p, const CUtensorMap* maps, uint32_t sb, int warp, int lane, int f, unsigned epoch, uint32_t key) {
    const int g = lane >> 2, t = lane & 3, mi = lane >> 3, r8 = lane & 7;
    const uint32_t fb = sb + SF_MISC;
    const bool ism = f >= NW;
    const int ch0 = mini_ch0(f);
    const int k = ism ? warp >> 3 : 0;
    uint32_t first = 1;
    if (lane == 0) asm volatile("atom.shared.exch.b32 %0, [%1], 1;" : "=r"(first) : "r"(fb + FS_BM + 64 + 4 * k) : "memory");
    if (!__all_sync(0xffffffffu, first)) {
        if (elect()) prefetch_map(maps + 4);
        const int row = key_row(wait_sel(p, ch0 >> 5, r8, key_tag(epoch), key));
        if (row < 512) asm volatile("red.shared.or.b32 [%0], %1;" :: "r"(fb + FS_BM + (row >> 5) * 4), "r"(1u << (row & 31)) : "memory");
    }
    const int m = warp & 7, dr = 128 * (g >> 2) + 32 * (t >> 1) + 16 * (g & 1) + 8 * ((g >> 1) & 1);
    const uint32_t y = SM_Y + ((r8 >> 1) & 1) * 8512 + (2 * mi + (r8 & 1)) * 1056 + (2 * m + (r8 >> 2)) * 16;
    const uint32_t so = (g >> 1) * 256 + (t >> 1) * 64 + (g & 1) * 32 + (t & 1) * 16;
    bar_sync(BAR_M - k, ism ? 256 : NTHR);
#pragma unroll 1
    for (int h = ism ? 0 : warp >> 3;; h++) {
        const int r0 = 256 * h + 64 * (m & 1) + (m >> 1), row = r0 + dr;
        const uint32_t bm = lds32(fresh(fb) + FS_BM + (row >> 5) * 4) >> (row & 31), ab = fresh(sb - 49152 * k + 512 * h), stg = ab + SM_UT + 2048 * m + 512 * h;
        uint32_t x[2][4];
        ldsm4t(x[0], ab + y); ldsm4t(x[1], ab + y + 256);
        if (warp == 0 && x[0][0] != 0x12345) TSTAMP(28);
        if (__any_sync(0xffffffffu, bm & 0x11u)) {
#pragma unroll
            for (int i = 0; i < 2; i++) store_or_add(p.out + (size_t)(row + 4 * i) * DM + ch0 + 16 * k + 8 * (t & 1), x[i], bm & (1u << (4 * i)));
        } else {
#pragma unroll
            for (int i = 0; i < 2; i++) sts128(stg + so + 128 * i, x[i][0], x[i][1], x[i][2], x[i][3]);
            asm volatile("fence.proxy.async.shared::cta;" ::: "memory");
            __syncwarp();
            if (elect()) store_rows(maps + 4, stg, ch0 + 16 * k, r0);
        }
        if (h >= ism) break;
    }
    if (elect()) { asm volatile("cp.async.bulk.commit_group;" ::: "memory"); asm volatile("cp.async.bulk.wait_group.read 0;" ::: "memory"); }
    if (warp == 8) TSTAMP(11);
    if (warp == 0) { TSTAMP(15); TFLUSH(); }
}

constexpr int SMEM_BYTES = 232448;
static_assert(SF_MISC + 1152 <= 232192, "layout");

struct Maps { CUtensorMap m[6]; };

__global__ void __cluster_dims__(2, 1, 1) __launch_bounds__(NTHR, 1)
fused_kernel(const Params p, const __grid_constant__ Maps maps) {
    extern __shared__ __align__(1024) uint8_t smem_raw[];
    uint32_t q[8];
    {
        const int b = blockIdx.x, x = threadIdx.x, rc = 4 * b + max(b - 84, 0) - 288 + (x >> 6);
        const int cv = (b - NCONV) >> 31, ca = 8 * b + ((x >> 5) & 3), cb = 2 * rc - (rc & 3) + 4;
        const uint32_t ch = (ca & cv) | (cb & ~cv), o = NST * ch + 2 * ((x & 31) + ((x >> (cv & 2)) & 32));
        const bool c = x < (b < 84 ? 256 : 320);
        q[6] = ldg16_if(c, p.logdt + ch);
        q[2] = ldg32_if(c, p.Bre + o); q[3] = ldg32_if(c, p.Bim + o); q[4] = ldg32_if(c, p.Cre + o); q[5] = ldg32_if(c, p.Cim + o); q[0] = ldg32_if(c, p.Are + o); q[1] = ldg32_if(c, p.Aim + o);
        q[7] = ldg16_if(c, p.Dskip + ch);
    }
    const unsigned epoch = ld_rlx32(&p.s->epoch[blockIdx.x * 16 + (threadIdx.x >> 5)]);
    const uint32_t sb = __shfl_sync(0xffffffffu, smem_u32(smem_raw), 0);
    const int warp = __shfl_sync(0xffffffffu, threadIdx.x >> 5, 0), bid = __shfl_sync(0xffffffffu, blockIdx.x, 0);
    const int lane = __shfl_sync(0xffffffffu, threadIdx.x & 31, threadIdx.x);
    const bool conv = bid < NCONV;
    const int f = bid - NCONV;
    uint32_t w[12];
    if (warp < (f < 12 ? 8 : 10)) {
        const int half = conv ? warp >> 2 : warp & 1, pr = conv ? warp & 3 : warp >> 1;
        const int rc = 4 * f + max(f - 12, 0) + pr;
        const uint32_t stage = sb + (conv ? SC_KG : SF_KG) + warp * KG_STAGE;
        uint4* const kp = p.s->kp + (conv ? 8 * bid + pr : 2 * rc - (rc & 3) + 4) * 96 + lane;
        kgen(q, sb, half, stage, stage + (conv ? 4 : 1) * KG_STAGE, 1 + pr, lane, p.zero, w, [&] {
            sts128z_if(conv && lane < 20, sb + SC_KT + warp * KT_BYTES + lane * 16 + (lane < 4 ? 0 : lane < 14 ? 2048 : 2288));
            stg128z_if(!conv, kp + 64 * half); stg128z_if(!half && !conv, kp + 32);
            stg128z_if((unsigned)f < NW && warp < 6, (uint4*)(p.s->h + ((lane >> 4) * 288 + 6 * f + warp) * 32) + (lane & 15));
            if (conv) asm volatile("barrier.cluster.arrive.relaxed.aligned;" ::: "memory"); else bar_sync(0, NTHR);
        });
        if (!half) publish_k(kp, w, epoch);
        if (conv) { conv_main(p, sb, warp, lane, bid, epoch, w); return; }
        {
            if (!half && lane == 0) mbar_arrive(sb + SF_MISC + FB_KDONE);
            if (warp == 0) TSTAMP(22);
            if (warp == 2) TSTAMP(23);
        }
    } else if (conv) {
        conv_aux(p, maps.m, sb, warp - 8, lane, bid, epoch);
        return;
    } else {
        ffn_front(p, maps.m, sb, warp, lane, f, epoch);
    }
    converged();
    next_epoch(p, epoch);
    if (warp >= 12 && f < NX) return;
    mini_out(p, maps.m, sb, warp, lane, f, epoch, mini_conv(p, sb, warp, __shfl_sync(0xffffffffu, lane, lane), f, epoch));
}

typedef CUresult (*EncodeFn)(CUtensorMap*, CUtensorMapDataType, cuuint32_t, void*, const cuuint64_t*, const cuuint64_t*, const cuuint32_t*, const cuuint32_t*,
                             CUtensorMapInterleave, CUtensorMapSwizzle, CUtensorMapL2promotion, CUtensorMapFloatOOBfill);

void make_map(EncodeFn fn, CUtensorMap* m, const void* base, int rank, const cuuint64_t* dims, const cuuint64_t* strides, const cuuint32_t* box, CUtensorMapSwizzle sw) {
    const cuuint32_t es[5] = {1, 1, 1, 1, 1};
    fn(m, CU_TENSOR_MAP_DATA_TYPE_BFLOAT16, rank, (void*)base, dims, strides, box, es, CU_TENSOR_MAP_INTERLEAVE_NONE, sw,
       CU_TENSOR_MAP_L2_PROMOTION_NONE, CU_TENSOR_MAP_FLOAT_OOB_FILL_NONE);
}

}

extern "C" void kernel_launch(void* const* d_in, const int* in_sizes, int n_in, void* d_out, int out_size) {
    (void)in_sizes; (void)n_in; (void)out_size;
    static EncodeFn fn = nullptr;
    static void* scratch = nullptr;
    if (!fn) {
        void* ptr = nullptr; cudaDriverEntryPointQueryResult qr;
        cudaGetDriverEntryPoint("cuTensorMapEncodeTiled", &ptr, cudaEnableDefault, &qr);
        fn = (EncodeFn)ptr;
        cudaGetSymbolAddress(&scratch, g_scratch);
        cudaFuncSetAttribute(fused_kernel, cudaFuncAttributeMaxDynamicSharedMemorySize, SMEM_BYTES);
    }
    typedef const __nv_bfloat16* bp;
    Params p;
    p.u = (bp)d_in[0]; p.Are = (bp)d_in[1]; p.Aim = (bp)d_in[2]; p.Bre = (bp)d_in[3]; p.Bim = (bp)d_in[4]; p.Cre = (bp)d_in[5]; p.Cim = (bp)d_in[6];
    p.logdt = (bp)d_in[7]; p.Dskip = (bp)d_in[8]; p.wr = (bp)d_in[10]; p.gatew = (bp)d_in[14];
    p.out = (__nv_bfloat16*)d_out; p.s = (Scratch*)scratch; p.zero = 0;
    Maps maps;
    {
        const cuuint64_t dims[4] = {DM, 4, 16, 32}, strides[3] = {16 * DM * 2, DM * 2, 64 * DM * 2};
        const cuuint32_t box[4] = {16, 4, 16, 2};
        make_map(fn, &maps.m[0], d_in[0], 4, dims, strides, box, CU_TENSOR_MAP_SWIZZLE_32B);
        const cuuint32_t box2[4] = {16, 4, 16, 8};
        make_map(fn, &maps.m[5], d_in[0], 4, dims, strides, box2, CU_TENSOR_MAP_SWIZZLE_32B);
    }
    for (int i = 0; i < 2; i++) {
        const cuuint64_t dims[3] = {32, DM, FF / 32}, strides[2] = {FF * 2, 64};
        const cuuint32_t box[3] = {32, 64, 3};
        make_map(fn, &maps.m[1 + i], d_in[11 + i], 3, dims, strides, box, CU_TENSOR_MAP_SWIZZLE_64B);
    }
    {
        const cuuint64_t dims[2] = {DM, FF}, strides[1] = {DM * 2};
        const cuuint32_t box[2] = {32, 192};
        make_map(fn, &maps.m[3], d_in[13], 2, dims, strides, box, CU_TENSOR_MAP_SWIZZLE_64B);
    }
    {
        const cuuint64_t dims[5] = {DM, 4, 4, 2, L_SEQ}, strides[4] = {16 * DM * 2, 4 * DM * 2, 128 * DM * 2, DM * 2};
        const cuuint32_t box[5] = {16, 4, 4, 2, 1};
        make_map(fn, &maps.m[4], d_out, 5, dims, strides, box, CU_TENSOR_MAP_SWIZZLE_NONE);
    }
    fused_kernel<<<NCTA, NTHR, SMEM_BYTES>>>(p, maps);
}
```

```cpp
#include <cuda_runtime.h>
#include <cuda_bf16.h>
#include <cuda_fp16.h>
#include <cuda.h>
#include <stdint.h>
#include <type_traits>

#define RESUME 300
#define MDELAY 2000
#define RDELAY 900
#define WDELAY 2000
#define WGAP 290
#define NPRE 7
#define DGAP 260
namespace {

constexpr int DM = 576, NST = 128, FF = 4608, L_SEQ = 2048;
constexpr int NCONV = 72, NX = 36, NW = 48, NCTA = 132, NTHR = 512;

struct __align__(128) Scratch {
    unsigned epoch[NCTA * 16];
    uint4 keys[16 * 128];
    uint32_t sel[18 * 64];
    uint16_t gate[L_SEQ];
    uint2 h[2 * 288 * 32];
    uint4 kp[DM * 96];
};
__device__ Scratch g_scratch;
#define TFLUSH()
#define TSTAMP(i)
#define TW 12

struct Params {
    const __nv_bfloat16 *Are, *Aim, *Bre, *Bim, *Cre, *Cim, *logdt, *Dskip, *u, *wr, *gatew;
    __nv_bfloat16* out;
    Scratch* s;
    uint32_t zero;
};

__device__ __forceinline__ void give_up() { asm volatile("trap; exit;"); __builtin_unreachable(); }
__device__ __forceinline__ void converged() { __syncwarp(); asm volatile("{ .reg .b32 t; mov.b32 t, 0; movmatrix.sync.aligned.m8n8.trans.b16 t, t; }" ::: "memory"); }
__device__ __forceinline__ bool elect() { uint32_t r; asm volatile("{ .reg .pred p; elect.sync _|p, 0xffffffff; selp.u32 %0, 1, 0, p; }" : "=r"(r)); return r; }
__device__ __forceinline__ uint32_t smem_u32(const void* p) { return (uint32_t)__cvta_generic_to_shared(p); }
__device__ __forceinline__ uint32_t pack_bf16(float lo, float hi) { uint32_t r; asm("cvt.rn.bf16x2.f32 %0, %1, %2;" : "=r"(r) : "f"(hi), "f"(lo)); return r; }
__device__ __forceinline__ uint32_t pack_f16(float lo, float hi) { uint32_t r; asm("cvt.rn.f16x2.f32 %0, %1, %2;" : "=r"(r) : "f"(hi), "f"(lo)); return r; }
__device__ __forceinline__ float bf_lo(uint32_t w) { return __uint_as_float(w << 16); }
__device__ __forceinline__ float bf_hi(uint32_t w) { return __uint_as_float(w & 0xffff0000u); }
__device__ __forceinline__ float rbf(float x) { return bf_lo(pack_bf16(x, 0.f)); }
__device__ __forceinline__ uint32_t badd2(uint32_t a, uint32_t b) { uint32_t r; asm("add.rn.bf16x2 %0, %1, %2;" : "=r"(r) : "r"(a), "r"(b)); return r; }
__device__ __forceinline__ uint32_t bsub2(uint32_t a, uint32_t b) { uint32_t r; asm("sub.rn.bf16x2 %0, %1, %2;" : "=r"(r) : "r"(a), "r"(b)); return r; }
__device__ __forceinline__ uint32_t gmix(uint32_t ng, float ny0, float ny1, uint32_t u) {
    uint32_t r; asm("{ .reg .b32 t; fma.rn.bf16x2 t, %1, %3, %3; fma.rn.bf16x2 %0, %1, %2, t; }" : "=r"(r) : "r"(ng), "r"(pack_bf16(ny0, ny1)), "r"(u)); return r;
}
__device__ __forceinline__ void mma_bf(float (&c)[4], uint32_t a0, uint32_t a1, uint32_t a2, uint32_t a3, uint32_t b0, uint32_t b1) {
    asm("mma.sync.aligned.m16n8k16.row.col.f32.bf16.bf16.f32 {%0,%1,%2,%3}, {%4,%5,%6,%7}, {%8,%9}, {%0,%1,%2,%3};"
        : "+f"(c[0]), "+f"(c[1]), "+f"(c[2]), "+f"(c[3]) : "r"(a0), "r"(a1), "r"(a2), "r"(a3), "r"(b0), "r"(b1));
}
__device__ __forceinline__ void mma_bf8(float (&c)[4], uint32_t a0, uint32_t a1, uint32_t b0) {
    asm("mma.sync.aligned.m16n8k8.row.col.f32.bf16.bf16.f32 {%0,%1,%2,%3}, {%4,%5}, {%6}, {%0,%1,%2,%3};"
        : "+f"(c[0]), "+f"(c[1]), "+f"(c[2]), "+f"(c[3]) : "r"(a0), "r"(a1), "r"(b0));
}
__device__ __forceinline__ void mma_h(float (&c)[4], uint32_t a0, uint32_t a1, uint32_t a2, uint32_t a3, uint32_t b0, uint32_t b1) {
    asm("mma.sync.aligned.m16n8k16.row.col.f32.f16.f16.f32 {%0,%1,%2,%3}, {%4,%5,%6,%7}, {%8,%9}, {%0,%1,%2,%3};"
        : "+f"(c[0]), "+f"(c[1]), "+f"(c[2]), "+f"(c[3]) : "r"(a0), "r"(a1), "r"(a2), "r"(a3), "r"(b0), "r"(b1));
}
__device__ __forceinline__ uint32_t fresh(uint32_t a) { asm volatile("" : "+r"(a) :: "memory"); return a; }
__device__ __forceinline__ uint32_t lds32(uint32_t a) { uint32_t v; asm("ld.shared.u32 %0, [%1];" : "=r"(v) : "r"(a)); return v; }
__device__ __forceinline__ uint2 lds64(uint32_t a) { uint2 v; asm("ld.shared.v2.u32 {%0,%1}, [%2];" : "=r"(v.x), "=r"(v.y) : "r"(a)); return v; }
__device__ __forceinline__ uint4 lds128(uint32_t a) { uint4 v; asm("ld.shared.v4.u32 {%0,%1,%2,%3}, [%4];" : "=r"(v.x), "=r"(v.y), "=r"(v.z), "=r"(v.w) : "r"(a)); return v; }
__device__ __forceinline__ void ldsm4(uint32_t (&r)[4], uint32_t a) {
    asm("ldmatrix.sync.aligned.m8n8.x4.shared.b16 {%0,%1,%2,%3}, [%4];" : "=r"(r[0]), "=r"(r[1]), "=r"(r[2]), "=r"(r[3]) : "r"(a));
}
__device__ __forceinline__ void ldsm4t(uint32_t (&r)[4], uint32_t a) {
    asm("ldmatrix.sync.aligned.m8n8.x4.trans.shared.b16 {%0,%1,%2,%3}, [%4];" : "=r"(r[0]), "=r"(r[1]), "=r"(r[2]), "=r"(r[3]) : "r"(a));
}
__device__ __forceinline__ void sts16(uint32_t a, uint32_t v) { asm volatile("st.shared.u16 [%0], %1;" :: "r"(a), "h"((unsigned short)v) : "memory"); }
__device__ __forceinline__ void sts32(uint32_t a, uint32_t v) { asm volatile("st.shared.u32 [%0], %1;" :: "r"(a), "r"(v) : "memory"); }
__device__ __forceinline__ void sts64(uint32_t a, uint32_t x, uint32_t y) { asm volatile("st.shared.v2.u32 [%0], {%1,%2};" :: "r"(a), "r"(x), "r"(y) : "memory"); }
__device__ __forceinline__ void sts128(uint32_t a, uint32_t x, uint32_t y, uint32_t z, uint32_t w) {
    asm volatile("st.shared.v4.u32 [%0], {%1,%2,%3,%4};" :: "r"(a), "r"(x), "r"(y), "r"(z), "r"(w) : "memory");
}
__device__ __forceinline__ void st_async128(uint32_t a, uint32_t x, uint32_t y, uint32_t z, uint32_t w, uint32_t bar) {
    asm volatile("st.async.weak.shared::cluster.mbarrier::complete_tx::bytes.v4.b32 [%0], {%1,%2,%3,%4}, [%5];" :: "r"(a), "r"(x), "r"(y), "r"(z), "r"(w), "r"(bar) : "memory");
}
__device__ __forceinline__ void mbar_init(uint32_t b, uint32_t cnt) { asm volatile("mbarrier.init.shared::cta.b64 [%0], %1;" :: "r"(b), "r"(cnt) : "memory"); }
__device__ __forceinline__ void mbar_fence() { asm volatile("fence.mbarrier_init.release.cluster;" ::: "memory"); }
__device__ __forceinline__ void mbar_expect(uint32_t b, uint32_t bytes) { asm volatile("mbarrier.arrive.expect_tx.shared::cta.b64 _, [%0], %1;" :: "r"(b), "r"(bytes) : "memory"); }
__device__ __forceinline__ void mbar_arrive(uint32_t b) { asm volatile("mbarrier.arrive.shared::cta.b64 _, [%0];" :: "r"(b) : "memory"); }
__device__ __forceinline__ void mbar_wait(uint32_t b, uint32_t parity = 0) {
    asm volatile("{ .reg .pred p; .reg .u32 n; mov.u32 n, 0;\n"
                 "LW: mbarrier.try_wait.parity.shared::cta.b64 p, [%0], %1; @p bra LD; add.u32 n, n, 1; setp.lt.u32 p, n, 65536; @p bra LW; trap;\n"
                 "LD: }" :: "r"(b), "r"(parity) : "memory");
}
__device__ __forceinline__ void mbar_wait_cluster(uint32_t b) {
    asm volatile("{ .reg .pred p; .reg .u32 n; mov.u32 n, 0;\n"
                 "LW: mbarrier.try_wait.parity.acquire.cluster.shared::cta.b64 p, [%0], 0; @p bra LD; add.u32 n, n, 1; setp.lt.u32 p, n, 65536; @p bra LW; trap;\n"
                 "LD: }" :: "r"(b) : "memory");
}
__device__ __forceinline__ void tma2d(uint32_t dst, const CUtensorMap* m, int c0, int c1, uint32_t bar) {
    asm volatile("cp.async.bulk.tensor.2d.shared::cluster.global.mbarrier::complete_tx::bytes [%0], [%1, {%3, %4}], [%2];"
                 :: "r"(dst), "l"(m), "r"(bar), "r"(c0), "r"(c1) : "memory");
}
__device__ __forceinline__ void tma3d(uint32_t dst, const CUtensorMap* m, int c0, int c1, int c2, uint32_t bar) {
    asm volatile("cp.async.bulk.tensor.3d.shared::cluster.global.mbarrier::complete_tx::bytes [%0], [%1, {%3, %4, %5}], [%2];"
                 :: "r"(dst), "l"(m), "r"(bar), "r"(c0), "r"(c1), "r"(c2) : "memory");
}
__device__ __forceinline__ void tma4d(uint32_t dst, const CUtensorMap* m, int c0, int c1, int c2, int c3, uint32_t bar) {
    asm volatile("cp.async.bulk.tensor.4d.shared::cluster.global.mbarrier::complete_tx::bytes [%0], [%1, {%3, %4, %5, %6}], [%2];"
                 :: "r"(dst), "l"(m), "r"(bar), "r"(c0), "r"(c1), "r"(c2), "r"(c3) : "memory");
}
__device__ __forceinline__ void bulk_g2s(uint32_t dst, const void* src, uint32_t bytes, uint32_t bar) {
    asm volatile("cp.async.bulk.shared::cluster.global.mbarrier::complete_tx::bytes [%0], [%1], %2, [%3];"
                 :: "r"(dst), "l"(src), "r"(bytes), "r"(bar) : "memory");
}
__device__ __forceinline__ uint32_t mapa(uint32_t a, uint32_t rank) { uint32_t r; asm("mapa.shared::cluster.u32 %0, %1, %2;" : "=r"(r) : "r"(a), "r"(rank)); return r; }
__device__ __forceinline__ void prefetch_map(const CUtensorMap* m) { asm volatile("prefetch.tensormap [%0];" :: "l"(m) : "memory"); }
__device__ __forceinline__ void bar_sync(int id, int n) { asm volatile("bar.sync %0, %1;" :: "r"(id), "r"(n) : "memory"); }
__device__ __forceinline__ void bar_arrive(int id, int n) { asm volatile("bar.arrive %0, %1;" :: "r"(id), "r"(n) : "memory"); }
__device__ __forceinline__ uint32_t ldg16_if(bool c, const void* p) { uint32_t v; asm volatile("{ .reg .pred p; setp.ne.u32 p, %2, 0; @p ld.global.nc.u16 %0, [%1]; }" : "=r"(v) : "l"(p), "r"((uint32_t)c)); return v; }
__device__ __forceinline__ uint32_t ldg32_if(bool c, const void* p) { uint32_t v; asm volatile("{ .reg .pred p; setp.ne.u32 p, %2, 0; @p ld.global.nc.u32 %0, [%1]; }" : "=r"(v) : "l"(p), "r"((uint32_t)c)); return v; }
__device__ __forceinline__ uint32_t ld_rlx32(const void* p) { uint32_t v; asm volatile("ld.relaxed.gpu.global.u32 %0, [%1];" : "=r"(v) : "l"(p) : "memory"); return v; }
__device__ __forceinline__ uint4 ld_rlx128(const void* p) {
    uint4 v; asm volatile("ld.relaxed.gpu.global.v4.u32 {%0,%1,%2,%3}, [%4];" : "=r"(v.x), "=r"(v.y), "=r"(v.z), "=r"(v.w) : "l"(p) : "memory"); return v;
}
__device__ __forceinline__ void st_rlx32(void* p, uint32_t v) { asm volatile("st.relaxed.gpu.global.u32 [%0], %1;" :: "l"(p), "r"(v) : "memory"); }
__device__ __forceinline__ void stg128(void* p, uint32_t x, uint32_t y, uint32_t z, uint32_t w) {
    asm volatile("st.global.v4.u32 [%0], {%1,%2,%3,%4};" :: "l"(p), "r"(x), "r"(y), "r"(z), "r"(w) : "memory");
}
__device__ __forceinline__ void next_epoch(const Params& p, unsigned e) { if ((threadIdx.x & 31) == 0) p.s->epoch[blockIdx.x * 16 + (threadIdx.x >> 5)] = e + 1; }
__device__ __forceinline__ void sts128z_if(bool c, uint32_t a) { asm volatile("{ .reg .pred p; setp.ne.u32 p, %1, 0; @p st.shared.v4.u32 [%0], {%2,%2,%2,%2}; }" :: "r"(a), "r"((uint32_t)c), "r"(0) : "memory"); }
__device__ __forceinline__ void stg128z_if(bool c, void* a) { asm volatile("{ .reg .pred p; setp.ne.u32 p, %1, 0; @p st.global.v4.u32 [%0], {%2,%2,%2,%2}; }" :: "l"(a), "r"((uint32_t)c), "r"(0) : "memory"); }
__device__ __forceinline__ unsigned clock32() { unsigned c; asm volatile("mov.u32 %0, %clock;" : "=r"(c) :: "memory"); return c; }
__device__ __forceinline__ void until(unsigned t0, int c) { while ((int)(clock32() - t0) < c) { } }
__device__ __forceinline__ float sigmoidf_(float x) { return __fdividef(1.0f, 1.0f + __expf(-x)); }
__device__ __forceinline__ uint32_t key_tag(unsigned epoch) { return ((epoch & 15u) | 16u) << 11; }
__device__ __forceinline__ int key_row(uint32_t key) { return 2047 - (int)(key & 2047u); }
__device__ __forceinline__ uint32_t wait_sel(const Params& p, int s32, int r8, uint32_t tag, uint32_t k = 0) {
#pragma unroll 1
    for (int it = 0; !__all_sync(0xffffffffu, (k & 0xf800u) == tag); it++) {
        k = ld_rlx32(&p.s->sel[s32 * 64 + r8]);
        if (it > (1 << 20)) give_up();
    }
    return k;
}

struct cplx { float re, im; };
__device__ __forceinline__ cplx csq(cplx a) { cplx r; r.re = a.re * a.re - a.im * a.im; r.im = (a.re * a.im) * 2.f; return r; }
__device__ __forceinline__ cplx cexpk(float ar, float ai, float k) {
    float mag, s, c;
    asm("ex2.approx.ftz.f32 %0, %1;" : "=f"(mag) : "f"(ar * (k * 1.4426950408889634f)));
    const float r = ai * k;
    asm("sin.approx.ftz.f32 %0, %1;" : "=f"(s) : "f"(r));
    asm("cos.approx.ftz.f32 %0, %1;" : "=f"(c) : "f"(r));
    cplx o; o.re = mag * c; o.im = mag * s; return o;
}
struct h2c { uint32_t re, im; };
__device__ __forceinline__ h2c cmul_cd(h2c v, __half2 c, __half2 d) {
    const __half2 r = *(const __half2*)&v.re, i = *(const __half2*)&v.im;
    const __half2 x = __hfma2(__hneg2(i), d, __hmul2(r, c)), y = __hfma2(i, c, __hmul2(r, d));
    h2c o; o.re = *(const uint32_t*)&x; o.im = *(const uint32_t*)&y; return o;
}
__device__ __forceinline__ h2c cmul_s(h2c v, uint32_t s) { const __half2 h = *(const __half2*)&s; return cmul_cd(v, __low2half2(h), __high2half2(h)); }
__device__ __forceinline__ h2c cmul_sc(h2c v, uint32_t s) {
    const __half2 h = *(const __half2*)&s, c = __low2half2(h), d = __high2half2(h), r = *(const __half2*)&v.re, i = *(const __half2*)&v.im;
    const __half2 x = __hfma2(i, d, __hmul2(r, c)), y = __hfma2(__hneg2(r), d, __hmul2(i, c));
    h2c o; o.re = *(const uint32_t*)&x; o.im = *(const uint32_t*)&y; return o;
}
__device__ __forceinline__ h2c cmul_vc(h2c v, uint32_t s) {
    const __half2 h = *(const __half2*)&s, c = __low2half2(h), d = __high2half2(h), r = *(const __half2*)&v.re, i = *(const __half2*)&v.im;
    const __half2 x = __hfma2(i, d, __hmul2(r, c)), y = __hfma2(__hneg2(i), c, __hmul2(r, d));
    h2c o; o.re = *(const uint32_t*)&x; o.im = *(const uint32_t*)&y; return o;
}

constexpr int UT_HALF = 2240, UT_STRIDE = 4448;
constexpr int KT_T = 542, KT_C = 552, KT_D = 645, KT_BYTES = 720 * 4;
constexpr int VC_OFF = 80, VE_BASE = 1616;
constexpr int V_STRIDE = (1616 + 1024) * 4 + 80;
constexpr int KG_STAGE = 5248;
constexpr int Y_CS = 2080, Y_RS = 8 * Y_CS + 64;

constexpr int SC_RT = 0;
constexpr int SC_UT = 33408;
constexpr int SC_ST = SC_UT + 8 * UT_STRIDE;
constexpr int SC_KT = SC_ST + 8 * UT_STRIDE;
constexpr int SC_GT = SC_KT + 8 * KT_BYTES;
constexpr int SC_V = SC_GT + UT_STRIDE;
constexpr int SC_KG = SC_V + 4 * V_STRIDE;
constexpr int SC_MISC = SC_V + 8 * V_STRIDE;
static_assert(V_STRIDE % 128 == 16 && 8 * KG_STAGE <= 4 * V_STRIDE && 2 * Y_RS <= SC_UT && SC_UT % 128 == 0 && SC_ST % 128 == 0, "layout");
static_assert(SC_MISC % 16 == 0 && SC_MISC + 512 <= 232192, "layout");

__device__ __forceinline__ void window_task(uint32_t src, uint32_t d0, uint32_t d1, bool withE) {
    float S[35];
    {
        uint32_t w[20];
#pragma unroll
        for (int i = 0; i < 5; i++) {
            const uint4 v = lds128(src + ((i & 1) ? 0 : UT_HALF) + ((i + 1) >> 1) * 16);
            w[4 * i] = v.x; w[4 * i + 1] = v.y; w[4 * i + 2] = v.z; w[4 * i + 3] = v.w;
        }
        float s = 0.f; S[2] = 0.f;
#pragma unroll
        for (int i = 3; i < 26; i++) { s += (i & 1) ? bf_hi(w[i >> 1]) : bf_lo(w[i >> 1]); S[i] = s; }
#pragma unroll
        for (int i = 0; i < 8; i += 2)
            sts128((i & 4 ? d1 : d0) + (VC_OFF - 16) * 4 + 8 * (i & 2), pack_bf16(S[10 + i] - S[5 + i], S[5 + i] - S[2 + i]), pack_bf16(S[18 + i] - S[13 + i], S[13 + i] - S[10 + i]),
                   pack_bf16(S[11 + i] - S[6 + i], S[6 + i] - S[3 + i]), pack_bf16(S[19 + i] - S[14 + i], S[14 + i] - S[11 + i]));
        if (withE) {
#pragma unroll
            for (int i = 26; i < 35; i++) { s += (i & 1) ? bf_hi(w[i >> 1]) : bf_lo(w[i >> 1]); S[i] = s; }
#pragma unroll
            for (int i = 0; i < 8; i += 2)
                sts128((i & 4 ? d1 : d0) + VE_BASE * 4 + 8 * (i & 2), pack_bf16(S[19 + i] - S[12 + i], S[12 + i] - S[3 + i]), pack_bf16(S[27 + i] - S[20 + i], S[20 + i] - S[11 + i]),
                       pack_bf16(S[20 + i] - S[13 + i], S[13 + i] - S[4 + i]), pack_bf16(S[28 + i] - S[21 + i], S[21 + i] - S[12 + i]));
        }
    }
}

template <class F>
__device__ __forceinline__ void kgen(const uint32_t (&q)[8], uint32_t sb, int half, uint32_t stage, uint32_t pstage, int barid, int lane, uint32_t (&w)[12], F shadow) {
    const int t = lane & 3, mi = lane >> 3, r8 = lane & 7;
    {
        const uint32_t pAr = q[0], pAi = q[1], pBr = q[2], pBi = q[3], pCr = q[4], pCi = q[5], pDt = q[6], pD = q[7];
        const uint32_t wb = fresh(stage + lane * 16), za = fresh(stage + 5120 + ((lane >> 1) & 3) * 16 + mi * 4 + (lane & 1) * 2), zr = fresh(stage + 5120 + t * 16);
        const uint32_t oA = fresh(stage + (mi & 1) * 1024 + (mi >> 1) * 512 + r8 * 16), oB = fresh(stage + 2048 + mi * 512 + r8 * 16), oC = fresh(stage + 4096 + (mi & 1) * 512 + (mi >> 1) * 128 + r8 * 16);
        float acc[6][4];
#pragma unroll
        for (int a = 0; a < 6; a++) { acc[a][0] = acc[a][1] = acc[a][2] = acc[a][3] = 0.f; asm volatile("" : "+f"(acc[a][0]), "+f"(acc[a][1]), "+f"(acc[a][2]), "+f"(acc[a][3])); }
        shadow();
        sts32(zr, clock32());
        const float dt = rbf(__expf(bf_lo(pDt)));
        float ar = dt * bf_lo(pAr), ai = dt * bf_lo(pAi), ar1 = dt * bf_hi(pAr), ai1 = dt * bf_hi(pAi);
        float wr, wi, wr1, wi1;
        { const float br = dt * bf_lo(pBr), bi = dt * bf_lo(pBi), cr = bf_lo(pCr), ci = bf_lo(pCi); wr = cr * br - ci * bi; wi = cr * bi + ci * br; }
        { const float br = dt * bf_hi(pBr), bi = dt * bf_hi(pBi), cr = bf_hi(pCr), ci = bf_hi(pCi); wr1 = cr * br - ci * bi; wi1 = cr * bi + ci * br; }
        const uint32_t ex = max(__reduce_max_sync(0xffffffffu, __float_as_uint(fmaxf(fmaxf(fabsf(wr), fabsf(wi)), fmaxf(fabsf(wr1), fabsf(wi1))))) >> 23, 14u);
        const float scl = __uint_as_float((267u - ex) << 23);
        uint32_t W = pack_f16(wr * scl, wi * -scl);
        const uint32_t W1 = pack_f16(wr1 * scl, wi1 * -scl);
        if (threadIdx.x < 32) TSTAMP(20);

#pragma unroll 1
        for (int r = 0; r < 2; r++) {
            const cplx z1 = cexpk(ar, ai, 1.f), z64 = cexpk(ar, ai, 64.f);
            const cplx z2 = csq(z1), z4 = csq(z2), z8 = csq(z4), z16 = csq(z8), z32 = csq(z16);
            const cplx z128 = csq(z64), z256 = csq(z128), z512 = csq(z256);
            auto put = [&](int grp, h2c a, h2c b, h2c c, h2c d) { sts128(wb + grp * 1024, a.re, b.re, c.re, d.re); sts128(wb + grp * 1024 + 512, a.im, b.im, c.im, d.im); };
            {
                const uint32_t s4 = pack_f16(z4.re, z4.im), s256 = pack_f16(z256.re, z256.im), s512 = pack_f16(z512.re, z512.im);
                auto mix = [](h2c a, h2c b, uint32_t sel) { return h2c{__byte_perm(a.re, b.re, sel), __byte_perm(a.im, b.im, sel)}; };
                const h2c c10 = cmul_vc(h2c{pack_f16(z1.re, 1.f), pack_f16(z1.im, 0.f)}, W), c32 = cmul_sc(c10, pack_f16(z2.re, z2.im)), c54 = cmul_sc(c10, s4);
                put(2, c10, c32, c54, cmul_sc(c32, s4));
                const h2c d20 = cmul_sc(mix(c32, c10, 0x7632), s256), e04 = cmul_sc(mix(c10, c54, 0x7632), s512), f04 = cmul_sc(e04, s256);
                put(3, d20, cmul_sc(d20, s4), e04, f04);
                const h2c ef = mix(e04, f04, 0x5410), gh = cmul_sc(ef, s512), g8 = cmul_sc(gh, pack_f16(z8.re, z8.im));
                put(4, g8, cmul_sc(g8, s512), gh, ef);
            }
            {
                const uint32_t s32 = pack_f16(z32.re, z32.im), s64 = pack_f16(z64.re, z64.im), s128 = pack_f16(z128.re, z128.im);
                const h2c p0 = {pack_f16(1.f, z8.re), pack_f16(0.f, z8.im)}, p1 = cmul_s(p0, pack_f16(z16.re, z16.im)), p2 = cmul_s(p0, s32), p3 = cmul_s(p1, s32);
                put(0, p0, p1, p2, p3);
                put(1, cmul_s(p0, s64), cmul_s(p1, s64), cmul_s(p2, s64), cmul_s(p3, s64));
                sts16(za, s128); sts16(za + 64, s128 >> 16);
            }
            __syncwarp();
            {
                const uint32_t aA = fresh(oA), aB = fresh(oB), aC = fresh(oC), aZ = fresh(zr);
                const uint4 zc = lds128(aZ), zd = lds128(aZ + 64);
                const uint32_t zcs[4] = {zc.x, zc.y, zc.z, zc.w}, zds[4] = {zd.x, zd.y, zd.z, zd.w};
                uint32_t c[4];
#pragma unroll
                for (int k = 0; k < 4; k++) {
                    uint32_t a[4], b[4];
                    ldsm4t(a, aA + 128 * k); ldsm4t(b, aB + 128 * k);
                    if (!(k & 1)) ldsm4t(c, aC + 128 * k);
                    const h2c x = cmul_cd(h2c{a[0], a[2]}, *(const __half2*)&zcs[k], *(const __half2*)&zds[k]), y = cmul_cd(h2c{a[1], a[3]}, *(const __half2*)&zcs[k], *(const __half2*)&zds[k]);
                    mma_h(acc[0], a[0], a[1], a[2], a[3], b[0], b[1]);
                    mma_h(acc[1], a[0], a[1], a[2], a[3], b[2], b[3]);
                    mma_h(acc[2], a[0], a[1], a[2], a[3], c[2 * (k & 1)], c[2 * (k & 1) + 1]);
                    mma_h(acc[3], x.re, y.re, x.im, y.im, b[0], b[1]);
                    mma_h(acc[4], x.re, y.re, x.im, y.im, b[2], b[3]);
                    mma_h(acc[5], x.re, y.re, x.im, y.im, c[2 * (k & 1)], c[2 * (k & 1) + 1]);
                }
                asm volatile("" :: "f"(acc[0][0]), "f"(acc[1][0]), "f"(acc[2][0]), "f"(acc[3][0]), "f"(acc[4][0]), "f"(acc[5][0]) : "memory");
            }
            __syncwarp();
            ar = ar1; ai = ai1; W = W1;
        }
        if (threadIdx.x < 32) TSTAMP(21);
        const float i0 = __uint_as_float((ex + 243u) << 23);
        if (half) {
#pragma unroll
            for (int a = 0; a < 6; a++) sts128(wb + a * 512, __float_as_uint(acc[a][0]), __float_as_uint(acc[a][1]), __float_as_uint(acc[a][2]), __float_as_uint(acc[a][3]));
            sts32(stage + 3072, __float_as_uint(i0));
            bar_arrive(barid, 64);
        } else {
#pragma unroll
            for (int a = 0; a < 6; a++) { acc[a][0] *= i0; acc[a][1] *= i0; acc[a][2] *= i0; acc[a][3] *= i0; }
            if (lane == 0) acc[0][1] -= bf_lo(pD);
            sts32(zr, clock32());
            bar_sync(barid, 64);
            const uint32_t src = fresh(pstage);
            const float i1 = __uint_as_float(lds32(src + 3072));
#pragma unroll
            for (int a = 0; a < 6; a++) {
                const uint4 y = lds128(src + lane * 16 + a * 512);
                w[4 * (a % 3) + 2 * (a / 3)] = pack_bf16(fmaf(__uint_as_float(y.x), i1, acc[a][0]), fmaf(__uint_as_float(y.y), i1, acc[a][1]));
                w[4 * (a % 3) + 2 * (a / 3) + 1] = pack_bf16(fmaf(__uint_as_float(y.z), i1, acc[a][2]), fmaf(__uint_as_float(y.w), i1, acc[a][3]));
            }
            const uint32_t x0 = __shfl_up_sync(0xffffffffu, w[10], 2), x1 = __shfl_up_sync(0xffffffffu, w[11], 2);
            w[10] = w[8];
            if (t >= 2) { w[8] = x0; w[9] = x1; }
        }
    }
}

__device__ __forceinline__ int swap01(int i) { return (i & ~3) | ((i & 1) << 1) | ((i >> 1) & 1); }
enum { BC_AUX = 0, BC_S = 5, BC_KG = 15 };

__device__ __forceinline__ void fetch_gates(const Params& p, int i, int lane, unsigned epoch, uint32_t dst) {
    const uint32_t par = (epoch & 1) ? 0x80008000u : 0u;
    uint4 v;
#pragma unroll 1
    for (int it = 0;; it++) {
        v = ld_rlx128(p.s->gate + 256 * i + 8 * lane);
        v.x ^= par; v.y ^= par; v.z ^= par; v.w ^= par;
        if (__all_sync(0xffffffffu, (v.x & v.y & v.z & v.w & 0x80008000u) == 0x80008000u)) break;
        if (it > (1 << 20)) give_up();
    }
    sts128(dst + (8 + 16 * i + (lane >> 1)) * 16, v.x, v.y, v.z, v.w);
}
__device__ __forceinline__ void store_rows(const CUtensorMap* m, uint32_t src, int col, int row) {
    asm volatile("cp.async.bulk.tensor.5d.global.shared::cta.bulk_group [%0, {%2, %3, %3, %3, %4}], [%1];" :: "l"(m), "r"(src), "r"(col), "r"(0), "r"(row) : "memory");
}

__device__ __forceinline__ void store_or_add(void* o, const uint32_t (&y)[4], uint32_t add) {
    asm volatile("{ .reg .pred p; setp.ne.u32 p, %5, 0; @!p st.global.v4.u32 [%0], {%1,%2,%3,%4}; @p red.relaxed.gpu.global.add.noftz.v4.bf16x2 [%0], {%1,%2,%3,%4}; }"
                 :: "l"(o), "r"(y[0]), "r"(y[1]), "r"(y[2]), "r"(y[3]), "r"(add) : "memory");
}

__device__ __forceinline__ void conv_aux(const Params& p, const CUtensorMap* mU, uint32_t sb, int aw, int lane, int bid, unsigned epoch) {
    const int g = lane >> 2, t = lane & 3, mi = lane >> 3, r8 = lane & 7;
    const int rank = bid & 1, slab = bid >> 1;
    const uint32_t bar_y = sb + SC_MISC, bar_u = bar_y + 32, bar_v = bar_y + 40, bar_box = bar_y + 64 + 8 * aw, s_bm = bar_y + 128;
    if (elect()) {
        mbar_init(bar_box, 1); mbar_fence();
        mbar_expect(bar_box, 4096);
        tma4d(sb + SC_RT + 4096 * aw, mU, 16 * slab, 0, 0, 16 * rank + 2 * aw, bar_box);
        mbar_init(bar_y + 8 * aw, aw < 4 ? 9 : aw == 5 ? 8 : 1); mbar_fence();
        if (aw < 5) mbar_expect(bar_y + 8 * aw, aw == 4 ? 16384 : 4096);
    }
    __syncwarp();
    asm volatile("barrier.cluster.arrive.relaxed.aligned;" ::: "memory");
    asm volatile("setmaxnreg.dec.sync.aligned.u32 88;");
    const uint32_t ut = sb + SC_UT + aw * UT_STRIDE;
    sts128(ut + (mi >> 1) * (SC_ST - SC_UT) + (mi & 1) * UT_HALF + r8 * 16, 0, 0, 0, 0);
    if (lane < 16) sts128(s_bm + lane * 16, 0, 0, 0, 0);
    {
        const uint32_t dst = sb + SC_UT + swap01(g) * UT_STRIDE + (8 + 64 * rank + 8 * aw + t) * 16;
        const uint32_t rdst = mapa(dst, rank ^ 1), rbar = mapa(bar_u, rank ^ 1);
        asm volatile("barrier.cluster.wait.acquire.aligned;" ::: "memory");
        mbar_wait(bar_box);
        if (aw == 0) TSTAMP(1);
        const uint32_t src = fresh(sb + SC_RT) + aw * 4096 + (8 * mi + 4 * (r8 & 1) + (r8 >> 1)) * 32 + ((rank ^ (r8 & 1)) << 4);
        uint32_t x[8][4];
#pragma unroll
        for (int i = 0; i < 4; i++) { ldsm4t(x[i], src + 1024 * i); ldsm4t(x[4 + i], (src ^ 16) + 1024 * i); }
        asm volatile("" :: "r"(x[0][0]), "r"(x[1][0]), "r"(x[2][0]), "r"(x[3][0]) : "memory");
#pragma unroll
        for (int i = 0; i < 4; i++) st_async128(rdst + (i & 1) * UT_HALF + 32 * (i & 2), x[4 + i][0], x[4 + i][1], x[4 + i][2], x[4 + i][3], rbar);
#pragma unroll
        for (int i = 0; i < 4; i++) sts128(dst + (i & 1) * UT_HALF + 32 * (i & 2), x[i][0], x[i][1], x[i][2], x[i][3]);
    }
    bar_sync(BC_AUX, 256);
    mbar_wait_cluster(bar_u);
    if (aw == 0) TSTAMP(2);
    {
        const uint32_t a = fresh(ut) + (mi & 1) * UT_HALF + (64 * (mi >> 1) + r8) * 16;
        uint4 v = lds128(a);
#pragma unroll
        for (int i = 1; i <= 8; i++) {
            const uint4 w = lds128(a + 128 * i);
            sts128(a + 128 * i + (SC_ST - SC_UT), badd2(v.x, w.x), badd2(v.y, w.y), badd2(v.z, w.z), badd2(v.w, w.w));
            v = w;
        }
    }
    bar_arrive(BC_S + aw, 64);
    if (aw == 0) TSTAMP(3);
    {
        uint32_t ws = sb + SC_UT + t * UT_STRIDE + (g + 6) * 16, wd = sb + SC_V + t * V_STRIDE + 64 * g, sw = 16 * (g & 2);
#pragma unroll 1
        for (int k = aw; k < 25; k += 8) {
            if (k - aw == 8) {
                bar_sync(BC_KG, 384);
                if (lane < 16) sts128(sb + SC_V + aw * V_STRIDE + lane * 16, 0, 0, 0, 0);
            }
            if (k == 24) { ws -= (g & 1) * 4 * UT_STRIDE + 16 * g; wd -= (g & 1) * 4 * V_STRIDE + 64 * g; sw = 0; }
            const int h = k >= 12, a = k - 12 * h;
            const uint32_t d = wd + h * 4 * V_STRIDE + 512 * a;
            window_task(fresh(ws) + h * 4 * UT_STRIDE + 128 * a, d + sw, d + (sw ^ 32), a < 8);
        }
    }
    if (aw == 0) TSTAMP(9);
    {
        if (aw >= 2) fetch_gates(p, aw, lane, epoch, sb + SC_GT + (lane & 1) * UT_HALF);
        __syncwarp();
        if (elect()) { mbar_arrive(bar_v); prefetch_map(mU + 4); }
        next_epoch(p, epoch);
        if (aw == 0) TSTAMP(4);
        if (aw == 7) {
            const int row = key_row(wait_sel(p, slab >> 1, r8, key_tag(epoch)));
            if (lane < 8) asm volatile("red.shared.or.b32 [%0], %1;" :: "r"(s_bm + (row >> 5) * 4), "r"(1u << (row & 31)) : "memory");
            TSTAMP(10);
        }
        bar_sync(BC_AUX, 256);
        const uint32_t src = sb + SC_RT + ((r8 >> 1) & 1) * Y_RS + (2 * mi + (r8 & 1)) * Y_CS + (2 * aw + (r8 >> 2)) * 16;
        const int L = 2 * aw + (t >> 1);
        const int row0 = 256 * rank + 128 * (g >> 2) + 32 * (L & 3) + 16 * (g & 1) + 8 * ((g >> 1) & 1) + (L >> 2);
        __nv_bfloat16* outp = p.out + (size_t)row0 * DM + 16 * slab + 8 * (t & 1);
        const uint32_t stg = sb + SC_ST + 4096 * aw, so = (g >> 1) * 256 + (t >> 1) * 64 + (g & 1) * 32 + (t & 1) * 16;
#pragma unroll 1
        for (int s = 1; s < 4; s++) {
            const uint32_t bm = lds32(fresh(s_bm) + (16 * s + (row0 >> 5)) * 4) >> (row0 & 31);
            const bool routed = __any_sync(0xffffffffu, bm & 0x11u);
            if (aw == s) mbar_wait_cluster(bar_y + 8 * s);
            bar_sync(BC_AUX, 256);
            const uint32_t sf = fresh(src) + 512 * s;
            uint32_t y[2][4];
            ldsm4t(y[0], sf); ldsm4t(y[1], sf + 256);
            if (routed) {
#pragma unroll
                for (int k = 0; k < 2; k++) store_or_add(outp + (size_t)(512 * s + 4 * k) * DM, y[k], bm & (1u << (4 * k)));
            } else {
                sts128(stg + so + 1024 * s, y[0][0], y[0][1], y[0][2], y[0][3]); sts128(stg + so + 1024 * s + 128, y[1][0], y[1][1], y[1][2], y[1][3]);
                asm volatile("fence.proxy.async.shared::cta;" ::: "memory");
                __syncwarp();
                if (elect()) store_rows(mU + 4, stg + 1024 * s, 16 * slab, 512 * s + 256 * rank + 64 * (aw & 1) + (aw >> 1));
            }
            if (aw == 0) TSTAMP(16 + s);
        }
        if (elect()) { asm volatile("cp.async.bulk.commit_group;" ::: "memory"); asm volatile("cp.async.bulk.wait_group.read 0;" ::: "memory"); }
        if (aw == 0) TFLUSH();
    }
}

__device__ __forceinline__ uint32_t k_tag(unsigned epoch) { return epoch << 16 | 0x80000000u; }
__device__ __forceinline__ void publish_k(uint4* kp, const uint32_t (&w)[12], unsigned epoch) {
#pragma unroll
    for (int i = 0; i < 3; i++)
        asm volatile("st.relaxed.gpu.global.v4.u32 [%0], {%1,%2,%3,%4};" :: "l"(kp + 32 * i), "r"(w[3 * i]), "r"(w[3 * i + 1]), "r"(w[3 * i + 2]),
                     "r"(__byte_perm(w[9 + (i >> 1)], k_tag(epoch), i == 1 ? 0x7632 : 0x7610)));
}
template <bool FULL>
__device__ __forceinline__ void k_tables(uint32_t kt, int lane, const uint32_t (&w)[12]) {
    const int g = lane >> 2, t = lane & 3, mi = lane >> 3, r8 = lane & 7;
    uint32_t x3 = w[7], re[4], rx[4];
#pragma unroll
    for (int i = 0; i < 4; i++) {
        re[i] = __shfl_sync(0xffffffffu, w[i], lane + 31);
        rx[i] = __shfl_sync(0xffffffffu, w[4 + i], lane + (i == 0 && lane == 29 ? 5 : 1 + 2 * t));
    }
    if (FULL) {
        asm volatile("stmatrix.sync.aligned.m8n8.x2.trans.shared.b16 [%0], {%1,%2};" :: "r"(kt + (KT_D + 7) * 4 + 64 * t + 16 * (mi & 1) + 8 * (r8 & 4)), "r"(w[8]), "r"(w[9]) : "memory");
        if (lane == 2) {
            sts32(kt + (KT_C + 78) * 4, w[10] & 0xffffu);
            sts128(kt + (KT_T + 2) * 4, 0, w[10] & 0xffffu, __byte_perm(w[10], 0, 0x1010), w[10] << 16);
        }
        if (lane == 29) x3 = bsub2(x3, rx[0] & 0xffffu);
    }
#pragma unroll
    for (int i = 0; i < 4; i++) {
        sts64(kt + (16 + 64 * i) * 4 + 8 * lane, __byte_perm(w[i], lane ? re[i] : i ? re[i - 1] : 0, 0x5432), w[i]);
        const uint32_t x = i < 3 ? w[4 + i] : x3, aa = __byte_perm(x, 0, 0x3232);
        if (t < 2) sts128(kt + (272 + 64 * i + 8 * g + 4 * t) * 4, i == 0 && lane == 0 ? __byte_perm(x, re[3], 0x5432) : aa, aa, x,
                          __byte_perm(lane != 29 ? rx[i] : i < 3 ? rx[(i + 1) & 3] : FULL ? 0 : rx[0] << 16, x, 0x5432));
        else if (FULL) sts32(kt + (KT_C - 50 + 8 * i + 32 * t + g) * 4, x);
    }
}

__device__ __forceinline__ void conv_main(const Params& p, uint32_t sb, int warp, int lane0, int bid, unsigned epoch, uint32_t (&w)[12]) {
    asm volatile("setmaxnreg.inc.sync.aligned.u32 168;");
    const int lane = __shfl_sync(0xffffffffu, lane0, lane0);
    const int g = lane >> 2, t = lane & 3, mi = lane >> 3, r8 = lane & 7;
    const int rank = bid & 1;
    const uint32_t bar_y = sb + SC_MISC, bar_v = bar_y + 40;
    next_epoch(p, epoch);
    if (warp < 4) {
        asm volatile("" :: "r"(w[0]), "r"(w[2]), "r"(w[4]), "r"(w[6]), "r"(w[8]), "r"(w[10]) : "memory");
        bar_arrive(BC_KG, 384);
    } else {
        bar_sync(BC_S + swap01(warp), 64);
        const uint4* src = p.s->kp + (8 * bid + warp) * 96 + lane0;
#pragma unroll 1
        for (int it = 0;; it++) {
            uint32_t bad = 0, e[3];
#pragma unroll
            for (int i = 0; i < 3; i++) { const uint4 v = ld_rlx128(src + 32 * i); w[3 * i] = v.x; w[3 * i + 1] = v.y; w[3 * i + 2] = v.z; e[i] = v.w; bad |= v.w ^ k_tag(epoch); }
            w[9] = __byte_perm(e[0], e[1], 0x5410); w[10] = e[2];
            const bool ok = __all_sync(0xffffffffu, bad < 65536);
            if (ok) break;
            if (it > (1 << 20)) give_up();
        }
    }
    if ((warp & 3) == 0) TSTAMP(5 + (warp >> 2));
    k_tables<true>(sb + SC_KT + warp * KT_BYTES, lane0, w);
    asm volatile("barrier.cluster.wait.acquire.aligned;" ::: "memory");
    if (warp < 4) bar_sync(BC_S + swap01(warp), 64);
    __syncwarp();
    if ((warp & 3) == 0) TSTAMP(7 + (warp >> 2));
    {
        const uint32_t ut = fresh(sb + SC_UT) + swap01(warp) * UT_STRIDE, kt = fresh(sb + SC_KT) + warp * KT_BYTES;
        uint32_t u1 = ut + (mi & 1) * UT_HALF + (8 + r8) * 16 + (mi >> 1) * 128;
        auto dup = [&](uint32_t v) { return v ^ p.zero; };
        uint32_t kp = kt + (16 + g - 2 * t) * 4;
        float acc[16][4];
        {
            const uint32_t c0 = lds32(kp + 2048), c1 = lds32(kp + 2080), c2 = lds32(kp + 2016), c3 = dup(c0);
            const uint32_t e0 = lds32(kp + (KT_T - 16) * 4), e1 = lds32(kp + (KT_T - 8) * 4), e2 = lds32(kp + (KT_T - 24) * 4), e3 = dup(e0);
            const uint32_t f0 = dup(e1), f1 = lds32(kp + KT_T * 4);
            const uint32_t uo = ut + UT_HALF + (7 + lane) * 16;
#pragma unroll
            for (int i = 0; i < 16; i++) { acc[i][0] = acc[i][1] = acc[i][2] = acc[i][3] = 0.f; }
#pragma unroll
            for (int mu = 0; mu < 8; mu += 4) {
                uint32_t b[4];
                ldsm4(b, uo + 128 * mu);
#pragma unroll
                for (int k = 0; k < 4; k++) mma_bf8(acc[mu + 8 + k], f0, f1, b[k]);
            }
#pragma unroll
            for (int mu = 0; mu < 12; mu += 2) {
                uint32_t b[4];
                ldsm4(b, u1 + 128 * mu);
                mma_bf(acc[mu + 4], c0, c1, c2, c3, b[0], b[1]);
                mma_bf(acc[mu + 5], c0, c1, c2, c3, b[2], b[3]);
                if (mu < 8) { mma_bf(acc[mu + 8], e0, e1, e2, e3, b[0], b[1]); mma_bf(acc[mu + 9], e0, e1, e2, e3, b[2], b[3]); }
            }
        }
        {
            float M[8][4];
#pragma unroll
            for (int i = 0; i < 8; i++) { M[i][0] = M[i][1] = M[i][2] = M[i][3] = 0.f; }
            uint32_t s[8][4], a3[4];
            const uint32_t kb = kp, ub = dup(u1), uc = u1 + (mi >> 1) * 128;
            auto frag = [&](uint32_t (&a)[4], uint32_t x) { a[0] = lds32(x); a[1] = lds32(x + 32); a[2] = lds32(x - 32); a[3] = dup(a[0]); };
            frag(a3, kp + 1536);
#pragma unroll
            for (int i = 1; i < 8; i++) ldsm4(s[i], u1 + (SC_ST - SC_UT) + 256 * i);
            __syncwarp();
#pragma unroll 1
            for (uint32_t ko = 0, uo = 0; ko != 512;) {
                uint32_t a2[4], a1[4], a0[4], b[4][4];
                ko = fresh(ko); uo = fresh(uo);
                kp = kb + ko; u1 = ub + uo;
                const uint32_t up = uc + uo;
                ko += 64; uo -= 16;
                frag(a2, kp + 1024);
#pragma unroll
                for (int i = 1; i < 4; i++) ldsm4(b[i], up + 512 * i);
                asm("ldmatrix.sync.aligned.m8n8.x2.shared.b16 {%0,%1}, [%2];" : "=r"(b[0][2]), "=r"(b[0][3]) : "r"(up + 256));
                frag(a1, kp + 512); frag(a0, kp);
                kp += 64; u1 -= 16;
#pragma unroll
                for (int i = 1; i < 7; i++) mma_bf(acc[2 * i + 2], a3[0], a3[1], a3[2], a3[3], s[i][0], s[i][1]);
#pragma unroll
                for (int e = 0; e < 4; e++) a3[e] = bsub2(a2[e], a3[e]);
#pragma unroll
                for (int i = 1; i < 7; i++) mma_bf(acc[2 * i + 3], a2[0], a2[1], a2[2], a2[3], s[i][2], s[i][3]);
                ldsm4(s[1], u1 + (SC_ST - SC_UT) + 256);
#pragma unroll
                for (int i = 1; i < 7; i++) mma_bf(M[i + 1], a3[0], a3[1], a3[2], a3[3], b[i >> 1][2 * (i & 1)], b[i >> 1][2 * (i & 1) + 1]);
                frag(a3, kp + 1536);
#pragma unroll
                for (int i = 2; i < 8; i++) mma_bf(acc[2 * i], a1[0], a1[1], a1[2], a1[3], s[i][0], s[i][1]);
#pragma unroll
                for (int e = 0; e < 4; e++) a1[e] = bsub2(a0[e], a1[e]);
#pragma unroll
                for (int i = 2; i < 8; i++) { mma_bf(acc[2 * i + 1], a0[0], a0[1], a0[2], a0[3], s[i][2], s[i][3]); ldsm4(s[i], u1 + (SC_ST - SC_UT) + 256 * i); }
#pragma unroll
                for (int i = 2; i < 8; i++) mma_bf(M[i], a1[0], a1[1], a1[2], a1[3], b[i >> 1][2 * (i & 1)], b[i >> 1][2 * (i & 1) + 1]);
            }
            u1 = ub;
#pragma unroll
            for (int i = 2; i < 8; i++)
#pragma unroll
                for (int c = 0; c < 4; c++) { acc[2 * i][c] += M[i][c]; acc[2 * i + 1][c] -= M[i][c]; }
        }
        if ((warp & 3) == 0) TSTAMP(11 + (warp >> 2));
        mbar_wait(bar_v);
        const uint32_t vt = fresh(sb + SC_V) + swap01(warp) * V_STRIDE;
        const uint32_t g1 = fresh(u1) - ut + sb + SC_GT;
        const uint32_t ydst = sb + SC_RT + rank * Y_RS + warp * Y_CS + lane * 16;
        const uint32_t ydr = mapa(ydst, rank ^ 1), ybr = mapa(bar_y, rank ^ 1);
        auto stairs = [&](auto R) {
        uint32_t ug[2][2][4];
        auto ld_ug = [&](int i) { ldsm4t(ug[i & 1][0], u1 + 256 * i); ldsm4t(ug[i & 1][1], g1 + 256 * i); };
        auto ship = [&](int i) {
            const uint32_t (&u)[4] = ug[i & 1][0], (&gg)[4] = ug[i & 1][1];
            const uint32_t y0 = gmix(gg[0], acc[2 * i][0], acc[2 * i][1], u[0]), y1 = gmix(gg[1], acc[2 * i][2], acc[2 * i][3], u[1]);
            const uint32_t y2 = gmix(gg[2], acc[2 * i + 1][0], acc[2 * i + 1][1], u[2]), y3 = gmix(gg[3], acc[2 * i + 1][2], acc[2 * i + 1][3], u[3]);
            if ((i & 1) != R.value) st_async128(ydr + 512 * (i >> 1), y0, y1, y2, y3, ybr + 8 * (i >> 1));
            else asm volatile("{ .reg .pred q; setp.eq.u32 q, %6, 0; st.shared.v4.u32 [%0], {%2,%3,%4,%5}; bar.warp.sync 0xffffffff; @q mbarrier.arrive.shared::cta.b64 _, [%1]; }"
                              :: "r"(ydst + 512 * (i >> 1)), "r"(bar_y + 8 * (i >> 1)), "r"(y0), "r"(y1), "r"(y2), "r"(y3), "r"(lane) : "memory");
        };
        const uint32_t VD = vt + (VC_OFF - 400 - 16 * t) * 4 + (8 * g ^ 16 * (-t & 2)), VD2 = vt + (VC_OFF - 415 - 16 * t) * 4 + (8 * g ^ 16 * (~t & 2));
        uint2 bd[10];
        uint32_t x[2][4][4];
        auto ld4 = [&](uint32_t (&v)[4], int dl) { const uint2 w = lds64(VD + 256 * dl); v[0] = w.x; v[1] = w.y; v[2] = lds32(VD2 + 256 * dl); v[3] = dup(w.x); };
        auto mm4 = [&](const uint32_t (&v)[4], int dl) {
#pragma unroll
            for (int s = dl & 1; s < 10; s += 2) if ((dl + s) / 2 >= 4 && (dl + s) / 2 < 16) mma_bf(acc[(dl + s) / 2], v[0], v[1], v[2], v[3], bd[s].x, bd[s].y);
        };
        const uint32_t KE = kt + (KT_D + g + t) * 4, VE = vt + (VE_BASE - 912 - 16 * t) * 4 + (8 * g ^ 16 * (~t & 2));
        uint32_t b0[8], b1[8];
        auto ld8 = [&](uint32_t (&v)[4], int dl) { const uint2 w = lds64(VE + 512 * dl), z = lds64(VE + 512 * dl - 256); v[0] = w.x; v[1] = w.y; v[2] = z.x; v[3] = z.y; };
        auto mm8 = [&](const uint32_t (&v)[4], int dl, int lo, int hi) {
#pragma unroll
            for (int s = 0; s < 8; s++) if (dl + s >= lo && dl + s < hi) mma_bf(acc[dl + s], v[0], v[1], v[2], v[3], b0[s], b1[s]);
        };
        ld4(x[0][0], 6);
#pragma unroll
        for (int s = 0; s < 10; s++) bd[s] = lds64(kt + (KT_C + 2 * g + 2 * t + 8 * s) * 4);
        mm4(x[0][0], 6);
        uint32_t e[4][4];
#pragma unroll
        for (int k = 1; k < 6; k++) {
#pragma unroll
            for (int j = 0; j < 4; j++) ld4(x[k & 1][j], 4 * k + 3 + j);
            ld_ug(k + 1);
            if (k == 3) {
#pragma unroll
                for (int s = 0; s < 8; s++) { b0[s] = lds32(KE + 32 * s); b1[s] = lds32(KE + 32 * s + 16); }
            }
            if (k > 1) ship(k);
#pragma unroll
            for (int j = 0; j < 4; j++) {
                mm4(x[k & 1][j], 4 * k + 3 + j);
                if (k == 3) { uint32_t v[4], z[4]; ld8(e[j], 8 + j); ld8(v, 12 + j); ld4(z, 30 - j); mm8(v, 12 + j, 12, 16); mm8(e[j], 8 + j, 8, 12); mm4(z, 30 - j); }
                if (k == 5) { ld8(e[j], 8 + j + p.zero); mm8(e[j], 8 + j, 12, 16); }
            }
        }
        ld_ug(7);
        ship(7 - R.value); ship(6 + R.value);
        };
        if (rank) stairs(std::integral_constant<int, 1>()); else stairs(std::integral_constant<int, 0>());
        if ((warp & 3) == 0) TSTAMP(14 + (warp >> 2)); else TSTAMP(21 + warp);
    }
}

constexpr int SF_WD = 73728;
constexpr int SF_RED = 49152;
constexpr int MU_HALF = 640, MU_STRIDE = 1344, SM_RAW = 98304, SM_UT = SM_RAW + 16384, SM_G = SM_UT + 16 * MU_STRIDE, SM_Y = 196608, SM_KT = 138880, SM_KW = SM_G - 49152;
constexpr int SF_XS = 221184;
constexpr int SF_MISC = SF_XS + 8 * 1168;
constexpr int SF_KG = SF_MISC - 10 * KG_STAGE;
constexpr int SF_WR = SF_KG - 2304;
constexpr int FB_X = 64, FB_KDONE = 72, FB_KEYS = 80, FB_FREE = 88  , FB_W = 104, FB_D = FB_W + 72, FB_MU = FB_D + 96, FB_MG = FB_MU + 8, FB_MT = FB_MU + 16, FS_PART = 512, FS_TOK = 896, FS_BM = 1024;
enum { BAR_R = 7, BAR_GU = 8, BAR_RED = 9, BAR_R2 = 10, BAR_G = 12  , BAR_M = 15 };
static_assert(SF_KG % 128 == 0 && NPRE <= 8 && SM_KT + 4 * 2112 <= 147456 && SM_G + MU_STRIDE <= SF_WR - 4 * 9216 && SM_KW + 6 * 2112 >= SM_RAW && SM_KW + 12 * 2112 <= SM_UT, "layout");

__device__ __forceinline__ int mini_ch0(int f) { return f < NW ? 16 * (f - 12) : 32 * (f - NW); }

__device__ __forceinline__ void ffn_front(const Params& p, const CUtensorMap* maps, uint32_t sb, int warp, int lane, int f, unsigned epoch) {
    const unsigned t0 = clock32();
    const int g = lane >> 2, t = lane & 3, mi = lane >> 3, r8 = lane & 7;
    const bool isx = f < NX;
    const int nrw = f < 8 ? 6 : 4, r0 = f < 8 ? 48 * f : 128 + 32 * f;
    const int rw = warp < 12 ? 13 - warp : warp ^ (warp < 14 ? 10 : 15);
    const uint32_t bar_row = sb + SF_MISC  , bar_x = bar_row + FB_X;
    const uint32_t s_part = bar_row + FS_PART  , s_tok = bar_row + FS_TOK  ;
    const uint32_t rows = sb + SF_WR - 9216 * (rw + 1);
    {
#pragma unroll 1
        for (int i = warp < 10 ? 30 : warp - 10; i < 29; i += 6) if (elect()) mbar_init(bar_x + 8 * i, i == 1 ? 4 + (f >= 12) : i < 27 ? 1 : i == 27 ? 2 : f < NW ? 8 : 16);
        const uint32_t bytes = rw < 6 ? 9216 : 1152, dst = rw < 6 ? rows : sb + SF_WR + (rw & 1) * 1152;
        const __nv_bfloat16* src = rw < 6 ? p.u + (size_t)(r0 + 8 * rw) * DM : (rw & 1) ? p.gatew : p.wr;
        if (elect()) { mbar_init(bar_row + 8 * rw, 1); mbar_fence(); mbar_expect(bar_row + 8 * rw, bytes); }
        if (warp == 13) { sts32(s_part + 64 + lane * 4, 0); sts32(bar_row + FS_BM + lane * 4, 0); }
        bar_sync(0, NTHR);
        if (rw < nrw) until(t0, RDELAY);
        if (rw < nrw || rw >= 6) { if (elect()) bulk_g2s(dst, src, bytes, bar_row + 8 * rw); }
    }
    uint4* const kdst = p.s->keys + (lane >> 1) * 128 + 2 * f + (lane & 1);
    if (warp == 15) TSTAMP(1);

    if (warp == 12) {
        if (lane < 22) mbar_expect(bar_row + FB_W + 8 * lane, lane < 9 ? 24576 : lane < 21 ? 12288 : f < NW ? 16384 : 32768);
        if (elect()) { prefetch_map(maps + 1); prefetch_map(maps + 2); prefetch_map(maps + (isx ? 3 : 5)); }
        unsigned tb = t0 + WDELAY;
        auto pieces = [&](int n, int end, uint32_t dst) {
#pragma unroll 1
            for (; n < end; n++, dst += 12288) {
                until(tb, 0); tb += WGAP;
                if (elect()) tma3d(dst, maps + 1 + (n & 1), 0, 64 * (n >> 1), 3 * f, bar_row + FB_W + 8 * (n >> 1));
            }
        };
        if (!isx) {
            until(t0, MDELAY);
#pragma unroll 1
            for (int k = f >= NW; k >= 0; k--) if (elect()) tma4d(sb + SM_RAW - 49152 * k, maps + 5, mini_ch0(f) + 16 * k, 0, 0, 0, bar_row + FB_MU);
            if (f >= NW) return;
        }
#pragma unroll 1
        for (int i = 0; i < 4; i++) {
            if (i == 1) { mbar_wait(bar_row + FB_KEYS); mbar_wait(bar_row + FB_KDONE); tb = clock32() + RESUME; }
            if (i == 3) mbar_wait(bar_row + FB_FREE);
            const int n = ((0x0c080000 + NPRE * 256) >> (8 * i)) & 255;
            pieces(n, ((0x120c0800 + NPRE) >> (8 * i)) & 255, sb + 12288 * (((0x000c0000 + NPRE * 256) >> (8 * i)) & 255));
        }
        TSTAMP(12);
        if (isx) {
#pragma unroll 1
            for (int i = 0; i < 12; i++) {
                const int n = (0x987610ba5432ull >> (4 * i)) & 15;
                if (i == 6) mbar_wait(bar_row + FB_FREE + 8);
                until(tb, 0); tb += DGAP;
                if (elect()) tma2d(sb + SF_WD + n * 12288, maps + 3, 32 * (f >> 1), 2304 * (f & 1) + 192 * n, bar_row + FB_D + 8 * n);
            }
            TSTAMP(13);
        }
    } else if (warp == 13) {
        const uint32_t tag = key_tag(epoch), par = (epoch & 1) ? 0u : 0x8000u;
        stg128(kdst, 0, 0, 0, 0);
        if (lane < 8 && isx && !(f & 1)) st_rlx32(&p.s->sel[32 * f + lane], 0);
        bar_sync(BAR_R, 32 * (nrw + 1));
        TSTAMP(3);
        {
            const uint32_t sg = fresh(s_part) + 192 + lane * 4;
            const uint32_t gb = pack_bf16(sigmoidf_(rbf(__uint_as_float(lds32(sg)))), sigmoidf_(rbf(__uint_as_float(lds32(sg + 128))))) | par | (par << 16);
            asm volatile("st.relaxed.gpu.global.u16 [%0], %1;" :: "l"(p.s->gate + r0 + lane), "h"((unsigned short)gb) : "memory");
            if (nrw > 4 && lane < 16) asm volatile("st.relaxed.gpu.global.u16 [%0], %1;" :: "l"(p.s->gate + r0 + 32 + lane), "h"((unsigned short)(gb >> 16)) : "memory");
        }
        bar_sync(BAR_R2, 32 * (nrw + 1));
        {
            const uint4 v = lds128(fresh(s_tok) + (lane & 1) * 16);
            asm volatile("st.relaxed.gpu.global.v4.u32 [%0], {%1,%2,%3,%4};" :: "l"(kdst), "r"(v.x | tag), "r"(v.y | tag), "r"(v.z | tag), "r"(v.w | tag) : "memory");
        }
        TSTAMP(4);
        if (lane == 0) { mbar_arrive(bar_row + FB_KEYS); mbar_expect(bar_x, 8 * 1152); }
        if (f >= NW) return;
        mbar_wait(bar_row + FB_KDONE);
        uint32_t k[16];
        const uint4* src = p.s->keys + (f & 15) * 128 + lane;
#pragma unroll 1
        for (int it = 0;; it++) {
            uint32_t bad = 0;
#pragma unroll
            for (int i = 0; i < 4; i++) {
                const uint4 x = ld_rlx128(src + (i < 3 || lane < 24 ? 32 * i : 64));
                k[i] = x.x; k[4 + i] = x.y; k[8 + i] = x.z; k[12 + i] = x.w;
                bad |= x.x ^ tag;
            }
            const bool ok = __all_sync(0xffffffffu, (bad & 0xf800u) == 0);
            if (ok) break;
            if (it > (1 << 20)) give_up();
        }
        TSTAMP(5);
        uint32_t key = 0, m = __reduce_max_sync(0xffffffffu, max(max(k[0], k[1]), max(k[2], k[3])));
#pragma unroll 2
        for (int r = 0; r < 8; r++) {
            bool pop[4];
#pragma unroll
            for (int i = 0; i < 4; i++) { pop[i] = k[i] == m; k[i] = pop[i] ? k[4 + i] : k[i]; }
            const uint32_t mn = __reduce_max_sync(0xffffffffu, max(max(k[0], k[1]), max(k[2], k[3])));
            if (elect()) bulk_g2s(sb + SF_XS + r * 1168, p.u + (size_t)key_row(m) * DM, 1152, bar_x);
#pragma unroll
            for (int i = 0; i < 4; i++) { k[4 + i] = pop[i] ? k[8 + i] : k[4 + i]; k[8 + i] = pop[i] ? k[12 + i] : k[8 + i]; k[12 + i] = pop[i] ? 0 : k[12 + i]; }
            if (r8 == r) key = m;
            m = mn;
        }
        const int row = key_row(key);
        sts32(s_tok + r8 * 8, row);
        TSTAMP(6);
        if (isx) {
            if (!(f & 1)) {
                __nv_bfloat16* o = p.out + (size_t)row * DM + 16 * f + 8 * mi;
                asm volatile("st.relaxed.gpu.global.v4.u32 [%0], {%1,%1,%1,%1};" :: "l"(o), "r"(0) : "memory");
                if (__any_sync(0xffffffffu, ld_rlx32(o) != 0)) give_up();
                if (lane < 8) st_rlx32(&p.s->sel[32 * f + lane], key);
            } else wait_sel(p, f >> 1, r8, tag);
            uint32_t gb;
#pragma unroll 1
            for (int it = 0;; it++) {
                asm volatile("ld.relaxed.gpu.global.u16 %0, [%1];" : "=r"(gb) : "l"(p.s->gate + row) : "memory");
                gb ^= par;
                if (!(gb & 0x8000u)) break;
                if (it > (1 << 20)) give_up();
            }
            const uint32_t rb = key ^ 0x80000000u, rv = (rb ^ (((int)rb >> 31) & 0x7fff0000u)) & 0xffff0000u;
            sts32(s_tok + r8 * 8 + 4, __float_as_uint(rbf(1.0f - bf_lo(gb)) * rbf(sigmoidf_(__uint_as_float(rv)))));
            __syncwarp();
            TSTAMP(7);
            bar_arrive(BAR_RED, 416);
        }
    } else {
        if (rw < nrw) {
            float c[3][4];
#pragma unroll
            for (int i = 0; i < 3; i++) { c[i][0] = c[i][1] = c[i][2] = c[i][3] = 0.f; }
            mbar_wait(bar_row + 48); mbar_wait(bar_row + 56);
            const uint32_t b = fresh(sb + SF_WR) + (g & 1) * 1152 + (g >> 2) * 64 + t * 16 + (g & 2) * 2;
            uint32_t w[18][2];
#pragma unroll
            for (int kb = 0; kb < 18; kb++) { const uint32_t o = ((kb & 1) ? b ^ 64 : b) + 128 * (kb >> 1); w[kb][0] = lds32(o); w[kb][1] = lds32(o + 8); }
            mbar_wait(bar_row + 8 * rw);
            if (warp == 15) TSTAMP(2);
            const uint32_t a = fresh(rows) + g * 1152 + (g & 1) * 64 + t * 16;
#pragma unroll
            for (int kb = 0; kb < 18; kb++) {
                const uint4 x = lds128(((kb & 1) ? a ^ 64 : a) + 128 * (kb >> 1));
                mma_bf(c[kb % 3], x.x, x.y, x.z, x.w, w[kb][0], w[kb][1]);
            }
            const float sr = c[0][0] + c[1][0] + c[2][0] + __shfl_down_sync(0xffffffffu, c[0][2] + c[1][2] + c[2][2], 1);
            const float sg = c[0][1] + c[1][1] + c[2][1] + __shfl_down_sync(0xffffffffu, c[0][3] + c[1][3] + c[2][3], 1);
            const uint32_t rb = pack_bf16(0.f, sr);
            if (t == 2 * (g & 1)) {
                sts32(s_part + (8 * rw + g) * 4, (rb ^ (((int)rb >> 31) & 0x7fff0000u) ^ 0x80000000u) | (uint32_t)(2047 - r0 - 8 * rw - g));
                sts32(s_part + 192 + (8 * rw + g) * 4, __float_as_uint(sg));
            }
            __syncwarp();
            bar_sync(BAR_R, 32 * (nrw + 1));
            const uint32_t sk = fresh(s_part), kk = lds32(sk + (8 * rw + r8) * 4);
            int n = 0;
#pragma unroll
            for (int i = 0; i < 3; i++) { const uint4 v = lds128(sk + mi * 48 + 16 * i); n += (v.x > kk) + (v.y > kk) + (v.z > kk) + (v.w > kk); }
            n += __shfl_xor_sync(0xffffffffu, n, 8); n += __shfl_xor_sync(0xffffffffu, n, 16);
            if (n < 8) sts32(s_tok + 4 * n, kk);
            __syncwarp();
            bar_arrive(BAR_R2, 32 * (nrw + 1));
        }
    }
}

__device__ __forceinline__ void ffn_work(const Params& p, uint32_t sb, int warp, int lane, int f, unsigned epoch) {
    const int g = lane >> 2, t = lane & 3, mi = lane >> 3, r8 = lane & 7;
    const bool isx = f < NX;
    const uint32_t bar_x = sb + SF_MISC + FB_X, bar_free = sb + SF_MISC + FB_FREE, bar_w = sb + SF_MISC + FB_W, bar_d = sb + SF_MISC + FB_D, s_tok = sb + SF_MISC + FS_TOK;
    uint32_t fr[24][4];
    auto pin = [&] {
#pragma unroll
        for (int i = 0; i < 24; i += 8) asm volatile("" :: "r"(fr[i][0]), "r"(fr[i + 1][0]), "r"(fr[i + 2][0]), "r"(fr[i + 3][0]), "r"(fr[i + 4][0]), "r"(fr[i + 5][0]), "r"(fr[i + 6][0]), "r"(fr[i + 7][0]) : "memory");
    };
    {
        const int j = (unsigned)(warp - 4) < 6, w = warp - (j ? 4 : warp < 4 ? 0 : 6);
        float ag[2][4], au[2][4];
#pragma unroll
        for (int i = 0; i < 2; i++) { ag[i][0] = ag[i][1] = ag[i][2] = ag[i][3] = 0.f; au[i][0] = au[i][1] = au[i][2] = au[i][3] = 0.f; }
        const uint32_t wb = sb + (w >> 1) * 4096 + (r8 + 8 * (mi >> 1)) * 64 + (((2 * (w & 1) + (mi & 1)) ^ (r8 >> 1)) << 4);
        const uint32_t xb = sb + SF_XS + r8 * 1168 + mi * 16;
        auto load = [&](int i, int n, int place) {
            mbar_wait(bar_w + 8 * n);
            const uint32_t wk = fresh(wb) + place * 24576;
#pragma unroll
            for (int s = 0; s < 4; s++) { ldsm4t(fr[8 * i + s], wk + 1024 * s); ldsm4t(fr[8 * i + 4 + s], wk + 1024 * s + 12288); }
        };
        auto mul = [&](int i, uint32_t xk) {
            uint32_t x[2][4];
            ldsm4(x[0], xk); ldsm4(x[1], xk + 64);
#pragma unroll
            for (int s = 0; s < 4; s++) {
                const uint32_t (&a)[4] = fr[8 * i + s], (&b)[4] = fr[8 * i + 4 + s];
                mma_bf(ag[s & 1], a[0], a[1], a[2], a[3], x[s >> 1][2 * (s & 1)], x[s >> 1][2 * (s & 1) + 1]);
                mma_bf(au[s & 1], b[0], b[1], b[2], b[3], x[s >> 1][2 * (s & 1)], x[s >> 1][2 * (s & 1) + 1]);
            }
        };
#pragma unroll
        for (int i = 0; i < 3; i++) load(i, 3 * j + i, (i ? 5 : 3) * j + i);
        pin();
        bar_sync(BAR_G + j, 192);
        if (w == 0 && lane == 0) mbar_arrive(bar_free + 8 * j);
        mbar_wait(bar_x);
        if (warp == 0) TSTAMP(8);
        {
            const uint32_t xk = fresh(xb) + 384 * j;
#pragma unroll
            for (int i = 0; i < 3; i++) { mul(i, (i ? fresh(xk) : xk) + 128 * i); if (i == 0) { asm volatile("" :: "f"(ag[0][0]), "f"(ag[1][0]), "f"(au[0][0]), "f"(au[1][0])); sts32(s_tok + 64, clock32()); } }
        }
#pragma unroll 1
        for (int n = 6 + j; n < 9; n += 2) { load(0, n, n - 6); mul(0, fresh(xb) + 128 * n); }
#pragma unroll
        for (int c = 0; c < 4; c++) { ag[0][c] += ag[1][c]; au[0][c] += au[1][c]; }
        if (j) {
            sts128(wb + 24576, __float_as_uint(ag[0][0]), __float_as_uint(ag[0][1]), __float_as_uint(ag[0][2]), __float_as_uint(ag[0][3]));
            sts128(wb + 25600, __float_as_uint(au[0][0]), __float_as_uint(au[0][1]), __float_as_uint(au[0][2]), __float_as_uint(au[0][3]));
        }
        bar_sync(BAR_GU, 384);
        if (!j) {
            const uint32_t sf = fresh(wb);
            const uint4 g1 = lds128(sf + 24576), u1 = lds128(sf + 25600);
            const uint32_t gs[4] = {g1.x, g1.y, g1.z, g1.w}, us[4] = {u1.x, u1.y, u1.z, u1.w};
            if (warp == 0) TSTAMP(9);
            float h[4];
#pragma unroll
            for (int c = 0; c < 4; c++) {
                const float gv = rbf(ag[0][c] + __uint_as_float(gs[c]));
                h[c] = rbf(gv * sigmoidf_(gv)) * rbf(au[0][c] + __uint_as_float(us[c]));
            }
            uint32_t h0, h1;
            asm("movmatrix.sync.aligned.m8n8.trans.b16 %0, %1;" : "=r"(h0) : "r"(pack_bf16(h[0], h[1])));
            asm("movmatrix.sync.aligned.m8n8.trans.b16 %0, %1;" : "=r"(h1) : "r"(pack_bf16(h[2], h[3])));
            if (h0 == 0) h0 = 0x8000u;
            asm volatile("{ .reg .b64 v; mov.b64 v, {%1, %2}; st.relaxed.gpu.global.b64 [%0], v; }" :: "l"(p.s->h + ((epoch & 1) * 288 + 6 * f + w) * 32 + lane), "r"(h0), "r"(h1) : "memory");
        }
        if (isx) {
            if (warp == 0) TSTAMP(10);
            const uint2* hsrc = p.s->h + ((epoch & 1) * 288 + 144 * (f & 1) + 12 * warp) * 32 + lane;
            uint2 hb[12];
            auto ldh = [&](int s) { asm volatile("ld.relaxed.gpu.global.v2.u32 {%0, %1}, [%2];" : "=r"(hb[s].x), "=r"(hb[s].y) : "l"(hsrc + 32 * s) : "memory"); };
#pragma unroll
            for (int s = 0; s < 12; s++) ldh(s);
#pragma unroll 1
            for (int it = 0;; it++) {
                bool again = false;
#pragma unroll
                for (int s = 0; s < 12; s += 2) if (__any_sync(0xffffffffu, min(hb[s].x, hb[s + 1].x) == 0)) { ldh(s); ldh(s + 1); again = true; }
                if (!again) break;
                if (it > (1 << 16)) give_up();
            }
            if (warp == 0) TSTAMP(11);
            mbar_wait(bar_d + 8 * warp);
            if (warp == 9) TSTAMP(14);
            float ad[2][2][4];
#pragma unroll
            for (int i = 0; i < 4; i++) { ad[i >> 1][i & 1][0] = ad[i >> 1][i & 1][1] = ad[i >> 1][i & 1][2] = ad[i >> 1][i & 1][3] = 0.f; }
            const uint32_t wd = fresh(sb) + SF_WD + warp * 12288 + (r8 + 8 * (mi >> 1)) * 64 + (((mi & 1) ^ (r8 >> 1)) << 4);
#pragma unroll
            for (int s = 0; s < 12; s++) {
                uint32_t a[4], b[4];
                ldsm4t(a, wd + 1024 * s); ldsm4t(b, (wd ^ 32) + 1024 * s);
                mma_bf(ad[0][s & 1], a[0], a[1], a[2], a[3], hb[s].x, hb[s].y);
                mma_bf(ad[1][s & 1], b[0], b[1], b[2], b[3], hb[s].x, hb[s].y);
            }
            const uint32_t rd = sb + SF_RED + warp * 1152 + (72 * t + g) * 4;
#pragma unroll
            for (int i = 0; i < 8; i++) sts32(rd + (i >> 2) * 64 + (i & 1) * 144 + ((i >> 1) & 1) * 32, __float_as_uint(ad[i >> 2][0][i & 3] + ad[i >> 2][1][i & 3]));
            bar_sync(BAR_RED, 416);
            if (warp < 4) {
                const int tid = 32 * warp + lane;
                const uint32_t rs = fresh(sb + SF_RED) + (tid >> 4) * 144 + (tid & 15) * 8;
                const uint2 tk = lds64(fresh(s_tok) + (tid >> 4) * 8);
                float x = 0.f, y = 0.f;
#pragma unroll
                for (int w = 0; w < 12; w++) { const uint2 v = lds64(rs + w * 1152); x += __uint_as_float(v.x); y += __uint_as_float(v.y); }
                asm volatile("red.relaxed.gpu.global.add.noftz.bf16x2 [%0], %1;" :: "l"(p.out + (size_t)tk.x * DM + 32 * (f >> 1) + 2 * (tid & 15)),
                             "r"(pack_bf16(x * __uint_as_float(tk.y), y * __uint_as_float(tk.y))) : "memory");
            }
            if (warp == 0) { TSTAMP(15); TFLUSH(); }
            asm volatile("exit;"); __builtin_unreachable();
        }
    }
}

__device__ __forceinline__ void fetch_k(const uint4* src, uint64_t (&v)[6], uint32_t a, uint32_t b) {
    asm volatile("{ .reg .pred p; setp.eq.u32 p, %7, %8; @p ld.relaxed.gpu.global.v2.u64 {%0,%1}, [%6]; @p ld.relaxed.gpu.global.v2.u64 {%2,%3}, [%6 + 512]; @p ld.relaxed.gpu.global.v2.u64 {%4,%5}, [%6 + 1024]; }"
                 : "+l"(v[0]), "+l"(v[1]), "+l"(v[2]), "+l"(v[3]), "+l"(v[4]), "+l"(v[5]) : "l"(src), "r"(a), "r"(b));
}
__device__ __forceinline__ uint32_t mini_conv(const Params& p, uint32_t sb, int warp, int lane, int f, unsigned epoch) {
    const int g = lane >> 2, t = lane & 3, mi = lane >> 3, r8 = lane & 7;
    const uint32_t fb = sb + SF_MISC, kt = sb + (warp >= 12 ? SM_KT - 12 * 2112 : f < NW ? SM_KW + 2 * 2112 : SM_KW) + warp * 2112;
    const bool ism = f >= NW;
    const int ch0 = mini_ch0(f);
    uint32_t seq = 128, key;
    uint64_t v[6] = {};
    const uint4* src = p.s->kp + lane;
    auto hi = [&](int i) { return (uint32_t)(v[i] >> 32); };
    if (f >= (warp < 4 ? NW : NX)) {
    {
        const uint32_t c = 36 + (warp & 3) + 2 * (warp & 12), y = (uint32_t)((warp < 8 ? 0xa026802400000000ull : 0x2a2e00280080a22cull) >> ((8 * warp) & 48)) & 0xffff;
        seq = ism ? 0x101 * c - 0x400 : y + (warp & 1) * ((y >> 5) & 0x101);
        src += (ch0 + (seq & 31)) * 96;
    }
    if (seq & 32) {
        if (seq & 4) {
            const int q = (seq & 3) + ((seq >> 1) & 4);
            const uint32_t ab = sb - 3072 * (seq & 16), d = ab + SM_UT + g * MU_STRIDE + (8 + 4 * q + t) * 16;
            sts128(ab + SM_UT + (2 * q + (mi >> 1)) * MU_STRIDE + (mi & 1) * MU_HALF + r8 * 16, 0, 0, 0, 0);
            mbar_wait(fb + FB_MU);
            if (warp == 15) TSTAMP(16);
            const uint32_t a = fresh(ab + SM_RAW) + q * 2048 + (8 * mi + 4 * (r8 & 1) + (r8 >> 1)) * 32 + ((r8 & 1) << 4);
            uint32_t x[4][4];
#pragma unroll
            for (int i = 0; i < 4; i++) ldsm4t(x[i], (i & 2 ? a ^ 16 : a) + 1024 * (i & 1));
#pragma unroll
            for (int i = 0; i < 4; i++) sts128(d + (i & 1) * MU_HALF + (i & 2) * 4 * MU_STRIDE, x[i][0], x[i][1], x[i][2], x[i][3]);
            __syncwarp();
            if (lane == 0) mbar_arrive(fb + FB_MT);
        }
        mbar_wait(fb + FB_KDONE);
        fetch_k(src, v, 0, 0);
        if ((warp | 2) == 7) { fetch_gates(p, (warp >> 1) & 1, lane, epoch, sb + SM_G + (lane & 1) * MU_HALF); __syncwarp(); if (lane == 0) mbar_arrive(fb + FB_MG); }
        mbar_wait(fb + FB_KEYS);
        if (warp == TW) TSTAMP(17);
    }
    }
    const uint32_t lo = (mi & 1) * MU_HALF + (8 + r8) * 16 + (mi >> 1) * 128;
#pragma unroll 1
    do {
        const int c = seq & 31;
        if (seq & 32) {
#pragma unroll 1
        for (int it = 0; !__all_sync(0xffffffffu, ((hi(1) ^ k_tag(epoch)) | (hi(3) ^ k_tag(epoch)) | (hi(5) ^ k_tag(epoch)) | ((uint32_t)v[5] & p.zero)) < 65536); it++) {
            fetch_k(src, v, 0, 0);
            if (it > (1 << 20)) give_up();
        }
        mbar_wait(fb + FB_MT);
        sts128(kt + t * 16, 0, 0, 0, 0);
        if (warp == TW) TSTAMP(seq >> 8 ? 7 : 10);
        const uint32_t w[12] = {(uint32_t)v[0], hi(0), (uint32_t)v[1], (uint32_t)v[2], hi(2), (uint32_t)v[3], (uint32_t)v[4], hi(4), 0, 0, 0, 0};
        k_tables<false>(fresh(kt), fresh(lane), w);
        }
        __syncwarp();
        if (seq & 128) ffn_work(p, sb, warp, fresh(lane), f, epoch);
        if (!(seq & 32)) return 0;
        const uint32_t ab = sb - 49152 * (c >> 4), kb = fresh(kt) + (16 + g - 2 * t) * 4, ub = fresh(ab + SM_UT + (c & 15) * MU_STRIDE) + lo;
        const uint32_t yd = ab + SM_Y + (c & 15) * 1056 + (c & 8) * 8 + lane * 16;
        uint32_t kp = kb, u1 = ub;
        if (warp == TW && !(seq >> 8)) TSTAMP(13);
        seq >>= 8;
        src += ((int)(seq & 31) - c) * 96;
#pragma unroll
        for (int i = 0; i < 6; i++) v[i] = 0;
        key = 0;
        float acc[6][4];
#pragma unroll
        for (int i = 0; i < 6; i++) { acc[i][0] = acc[i][1] = acc[i][2] = acc[i][3] = 0.f; }
        uint32_t a[4][4], b[2][2][4];
        auto lda = [&](int j, int o) { const uint32_t x = kp + 64 * o + 512 * j; a[j][2] = o ? a[j][1] ^ p.zero : lds32((kp ^ p.zero) + 512 * j - 32); a[j][0] = lds32(x); a[j][1] = lds32(x + 32); a[j][3] = a[j][0] ^ p.zero; };
        auto ldb = [&](int s, int o) { ldsm4(b[s][0], u1 - 16 * o); ldsm4(b[s][1], u1 + 256 - 16 * o); };
        ldb(0, 0);
#pragma unroll
        for (int j = 0; j < 4; j++) lda(j, 0);
#pragma unroll
        for (int s = 0; s < 8; s++) {
            if (s == 4) {
                const uint32_t e = seq | (__float_as_uint(acc[0][0]) & p.zero);
                fetch_k(src, v, e & 32, 32);
                asm volatile("{ .reg .pred p; setp.eq.u32 p, %2, 0; @p ld.relaxed.gpu.global.u32 %0, [%1]; }" : "+r"(key) : "l"(&p.s->sel[(ch0 >> 5) * 64 + r8]), "r"(e));
            }
            if (s < 7) ldb(~s & 1, s + 1);
#pragma unroll
            for (int i = 0; i < 4; i++) {
                const int j = (i >> 1) + 2 * (i & 1);
#pragma unroll
                for (int mu = 3 - j; mu >= 0; mu--) mma_bf(acc[j + mu + (j & 2)], a[j][0], a[j][1], a[j][2], a[j][3], b[s & 1][mu >> 1][2 * (mu & 1)], b[s & 1][mu >> 1][2 * (mu & 1) + 1]);
                if (s < 7) lda(j, s + 1);
            }
        }
        if (warp == TW && !seq) TSTAMP(14);
        mbar_wait(fb + FB_MG);
#pragma unroll
        for (int e = 0; e < 4; e++) { acc[2][e] += acc[4][e]; acc[3][e] += acc[5][e]; }
        uint32_t ug[4][4];
#pragma unroll
        for (int i = 0; i < 2; i++) { ldsm4t(ug[i], ub + 256 * i); ldsm4t(ug[2 + i], fresh(sb + SM_G) + lo + 256 * i); }
#pragma unroll
        for (int i = 0; i < 2; i++) {
            const uint32_t (&u)[4] = ug[i], (&gg)[4] = ug[2 + i];
            sts128(yd + 512 * i, gmix(gg[0], acc[2 * i][0], acc[2 * i][1], u[0]), gmix(gg[1], acc[2 * i][2], acc[2 * i][3], u[1]),
                   gmix(gg[2], acc[2 * i + 1][0], acc[2 * i + 1][1], u[2]), gmix(gg[3], acc[2 * i + 1][2], acc[2 * i + 1][3], u[3]));
        }
        __syncwarp();
        if (warp == TW) TSTAMP(18 + (seq != 0));
    } while (seq);
    if (warp >= 12) TSTAMP(12 + warp);
    return key;
}
__device__ __forceinline__ void mini_out(const Params& p, const CUtensorMap* maps, uint32_t sb, int warp, int lane, int f, unsigned epoch, uint32_t key) {
    const int g = lane >> 2, t = lane & 3, mi = lane >> 3, r8 = lane & 7;
    const uint32_t fb = sb + SF_MISC;
    const bool ism = f >= NW;
    const int ch0 = mini_ch0(f);
    const int k = ism ? warp >> 3 : 0;
    uint32_t first = 1;
    if (lane == 0) asm volatile("atom.shared.exch.b32 %0, [%1], 1;" : "=r"(first) : "r"(fb + FS_BM + 64 + 4 * k) : "memory");
    if (!__all_sync(0xffffffffu, first)) {
        if (elect()) prefetch_map(maps + 4);
        const int row = key_row(wait_sel(p, ch0 >> 5, r8, key_tag(epoch), key));
        if (row < 512) asm volatile("red.shared.or.b32 [%0], %1;" :: "r"(fb + FS_BM + (row >> 5) * 4), "r"(1u << (row & 31)) : "memory");
    }
    const int m = warp & 7, dr = 128 * (g >> 2) + 32 * (t >> 1) + 16 * (g & 1) + 8 * ((g >> 1) & 1);
    const uint32_t y = SM_Y + ((r8 >> 1) & 1) * 8512 + (2 * mi + (r8 & 1)) * 1056 + (2 * m + (r8 >> 2)) * 16;
    const uint32_t so = (g >> 1) * 256 + (t >> 1) * 64 + (g & 1) * 32 + (t & 1) * 16;
    bar_sync(BAR_M - k, ism ? 256 : NTHR);
#pragma unroll 1
    for (int h = ism ? 0 : warp >> 3;; h++) {
        const int r0 = 256 * h + 64 * (m & 1) + (m >> 1), row = r0 + dr;
        const uint32_t bm = lds32(fresh(fb) + FS_BM + (row >> 5) * 4) >> (row & 31), ab = fresh(sb - 49152 * k + 512 * h), stg = ab + SM_UT + 2048 * m + 512 * h;
        uint32_t x[2][4];
        ldsm4t(x[0], ab + y); ldsm4t(x[1], ab + y + 256);
        if (warp == 0 && x[0][0] != 0x12345) TSTAMP(28);
        if (__any_sync(0xffffffffu, bm & 0x11u)) {
#pragma unroll
            for (int i = 0; i < 2; i++) store_or_add(p.out + (size_t)(row + 4 * i) * DM + ch0 + 16 * k + 8 * (t & 1), x[i], bm & (1u << (4 * i)));
        } else {
#pragma unroll
            for (int i = 0; i < 2; i++) sts128(stg + so + 128 * i, x[i][0], x[i][1], x[i][2], x[i][3]);
            asm volatile("fence.proxy.async.shared::cta;" ::: "memory");
            __syncwarp();
            if (elect()) store_rows(maps + 4, stg, ch0 + 16 * k, r0);
        }
        if (h >= ism) break;
    }
    if (elect()) { asm volatile("cp.async.bulk.commit_group;" ::: "memory"); asm volatile("cp.async.bulk.wait_group.read 0;" ::: "memory"); }
    if (warp == 8) TSTAMP(11);
    if (warp == 0) { TSTAMP(15); TFLUSH(); }
}

constexpr int SMEM_BYTES = 232448;
static_assert(SF_MISC + 1152 <= 232192, "layout");

struct Maps { CUtensorMap m[6]; };

__global__ void __cluster_dims__(2, 1, 1) __launch_bounds__(NTHR, 1)
fused_kernel(const Params p, const __grid_constant__ Maps maps) {
    extern __shared__ __align__(1024) uint8_t smem_raw[];
    uint32_t q[8];
    {
        const int b = blockIdx.x, x = threadIdx.x, rc = 4 * b + max(b - 84, 0) - 288 + (x >> 6);
        const int cv = (b - NCONV) >> 31, ca = 8 * b + ((x >> 5) & 3), cb = 2 * rc - (rc & 3) + 4;
        const uint32_t ch = (ca & cv) | (cb & ~cv), o = NST * ch + 2 * ((x & 31) + ((x >> (cv & 2)) & 32));
        const bool c = x < (b < 84 ? 256 : 320);
        q[6] = ldg16_if(c, p.logdt + ch);
        q[2] = ldg32_if(c, p.Bre + o); q[3] = ldg32_if(c, p.Bim + o); q[4] = ldg32_if(c, p.Cre + o); q[5] = ldg32_if(c, p.Cim + o); q[0] = ldg32_if(c, p.Are + o); q[1] = ldg32_if(c, p.Aim + o);
        q[7] = ldg16_if(c, p.Dskip + ch);
    }
    const unsigned epoch = ld_rlx32(&p.s->epoch[blockIdx.x * 16 + (threadIdx.x >> 5)]);
    const uint32_t sb = __shfl_sync(0xffffffffu, smem_u32(smem_raw), 0);
    const int warp = __shfl_sync(0xffffffffu, threadIdx.x >> 5, 0), bid = __shfl_sync(0xffffffffu, blockIdx.x, 0);
    const int lane = __shfl_sync(0xffffffffu, threadIdx.x & 31, threadIdx.x);
    const bool conv = bid < NCONV;
    const int f = bid - NCONV;
    uint32_t w[12];
    if (warp < (f < 12 ? 8 : 10)) {
        const int half = conv ? warp >> 2 : warp & 1, pr = conv ? warp & 3 : warp >> 1;
        const int rc = 4 * f + max(f - 12, 0) + pr;
        const uint32_t stage = sb + (conv ? SC_KG : SF_KG) + warp * KG_STAGE;
        uint4* const kp = p.s->kp + (conv ? 8 * bid + pr : 2 * rc - (rc & 3) + 4) * 96 + lane;
        kgen(q, sb, half, stage, stage + (conv ? 4 : 1) * KG_STAGE, 1 + pr, lane, w, [&] {
            sts128z_if(conv && lane < 20, sb + SC_KT + warp * KT_BYTES + lane * 16 + (lane < 4 ? 0 : lane < 14 ? 2048 : 2288));
            stg128z_if(!conv, kp + 64 * half); stg128z_if(!half && !conv, kp + 32);
            stg128z_if((unsigned)f < NW && warp < 6, (uint4*)(p.s->h + ((lane >> 4) * 288 + 6 * f + warp) * 32) + (lane & 15));
            if (conv) asm volatile("barrier.cluster.arrive.relaxed.aligned;" ::: "memory"); else bar_sync(0, NTHR);
        });
        if (!half) publish_k(kp, w, epoch);
        if (conv) { conv_main(p, sb, warp, lane, bid, epoch, w); return; }
        {
            if (!half && lane == 0) mbar_arrive(sb + SF_MISC + FB_KDONE);
            if (warp == 0) TSTAMP(22);
            if (warp == 2) TSTAMP(23);
        }
    } else if (conv) {
        conv_aux(p, maps.m, sb, warp - 8, lane, bid, epoch);
        return;
    } else {
        ffn_front(p, maps.m, sb, warp, lane, f, epoch);
    }
    converged();
    next_epoch(p, epoch);
    if (warp >= 12 && f < NX) return;
    mini_out(p, maps.m, sb, warp, lane, f, epoch, mini_conv(p, sb, warp, __shfl_sync(0xffffffffu, lane, lane), f, epoch));
}

typedef CUresult (*EncodeFn)(CUtensorMap*, CUtensorMapDataType, cuuint32_t, void*, const cuuint64_t*, const cuuint64_t*, const cuuint32_t*, const cuuint32_t*,
                             CUtensorMapInterleave, CUtensorMapSwizzle, CUtensorMapL2promotion, CUtensorMapFloatOOBfill);

void make_map(EncodeFn fn, CUtensorMap* m, const void* base, int rank, const cuuint64_t* dims, const cuuint64_t* strides, const cuuint32_t* box, CUtensorMapSwizzle sw) {
    const cuuint32_t es[5] = {1, 1, 1, 1, 1};
    fn(m, CU_TENSOR_MAP_DATA_TYPE_BFLOAT16, rank, (void*)base, dims, strides, box, es, CU_TENSOR_MAP_INTERLEAVE_NONE, sw,
       CU_TENSOR_MAP_L2_PROMOTION_NONE, CU_TENSOR_MAP_FLOAT_OOB_FILL_NONE);
}

}

extern "C" void kernel_launch(void* const* d_in, const int* in_sizes, int n_in, void* d_out, int out_size) {
    (void)in_sizes; (void)n_in; (void)out_size;
    static EncodeFn fn = nullptr;
    static void* scratch = nullptr;
    if (!fn) {
        void* ptr = nullptr; cudaDriverEntryPointQueryResult qr;
        cudaGetDriverEntryPoint("cuTensorMapEncodeTiled", &ptr, cudaEnableDefault, &qr);
        fn = (EncodeFn)ptr;
        cudaGetSymbolAddress(&scratch, g_scratch);
        cudaFuncSetAttribute(fused_kernel, cudaFuncAttributeMaxDynamicSharedMemorySize, SMEM_BYTES);
    }
    typedef const __nv_bfloat16* bp;
    Params p;
    p.u = (bp)d_in[0]; p.Are = (bp)d_in[1]; p.Aim = (bp)d_in[2]; p.Bre = (bp)d_in[3]; p.Bim = (bp)d_in[4]; p.Cre = (bp)d_in[5]; p.Cim = (bp)d_in[6];
    p.logdt = (bp)d_in[7]; p.Dskip = (bp)d_in[8]; p.wr = (bp)d_in[10]; p.gatew = (bp)d_in[14];
    p.out = (__nv_bfloat16*)d_out; p.s = (Scratch*)scratch; p.zero = 0;
    Maps maps;
    {
        const cuuint64_t dims[4] = {DM, 4, 16, 32}, strides[3] = {16 * DM * 2, DM * 2, 64 * DM * 2};
        const cuuint32_t box[4] = {16, 4, 16, 2};
        make_map(fn, &maps.m[0], d_in[0], 4, dims, strides, box, CU_TENSOR_MAP_SWIZZLE_32B);
        const cuuint32_t box2[4] = {16, 4, 16, 8};
        make_map(fn, &maps.m[5], d_in[0], 4, dims, strides, box2, CU_TENSOR_MAP_SWIZZLE_32B);
    }
    for (int i = 0; i < 2; i++) {
        const cuuint64_t dims[3] = {32, DM, FF / 32}, strides[2] = {FF * 2, 64};
        const cuuint32_t box[3] = {32, 64, 3};
        make_map(fn, &maps.m[1 + i], d_in[11 + i], 3, dims, strides, box, CU_TENSOR_MAP_SWIZZLE_64B);
    }
    {
        const cuuint64_t dims[2] = {DM, FF}, strides[1] = {DM * 2};
        const cuuint32_t box[2] = {32, 192};
        make_map(fn, &maps.m[3], d_in[13], 2, dims, strides, box, CU_TENSOR_MAP_SWIZZLE_64B);
    }
    {
        const cuuint64_t dims[5] = {DM, 4, 4, 2, L_SEQ}, strides[4] = {16 * DM * 2, 4 * DM * 2, 128 * DM * 2, DM * 2};
        const cuuint32_t box[5] = {16, 4, 4, 2, 1};
        make_map(fn, &maps.m[4], d_out, 5, dims, strides, box, CU_TENSOR_MAP_SWIZZLE_NONE);
    }
    fused_kernel<<<NCTA, NTHR, SMEM_BYTES>>>(p, maps);
}
```

```cpp
#include <cuda_runtime.h>
#include <cuda_bf16.h>
#include <cuda_fp16.h>
#include <cuda.h>
#include <stdint.h>
#include <type_traits>

#define RESUME 300
#define MDELAY 2000
#define MGAP 0
#define RDELAY 900
#define WDELAY 2000
#define WGAP 290
#define NPRE 7
#define DGAP 260
namespace {

constexpr int DM = 576, NST = 128, FF = 4608, L_SEQ = 2048;
constexpr int NCONV = 72, NX = 36, NW = 48, NCTA = 132, NTHR = 512;

struct __align__(128) Scratch {
    unsigned epoch[NCTA * 16];
    uint4 keys[16 * 128];
    uint32_t sel[18 * 64];
    uint16_t gate[L_SEQ];
    uint2 h[2 * 288 * 32];
    uint4 kp[DM * 96];
};
__device__ Scratch g_scratch;
#define TFLUSH()
#define TSTAMP(i)
#define TW 12

struct Params {
    const __nv_bfloat16 *Are, *Aim, *Bre, *Bim, *Cre, *Cim, *logdt, *Dskip, *u, *wr, *gatew;
    __nv_bfloat16* out;
    Scratch* s;
    uint32_t zero;
};

__device__ __forceinline__ void give_up() { asm volatile("trap; exit;"); __builtin_unreachable(); }
__device__ __forceinline__ void converged() { __syncwarp(); asm volatile("{ .reg .b32 t; mov.b32 t, 0; movmatrix.sync.aligned.m8n8.trans.b16 t, t; }" ::: "memory"); }
__device__ __forceinline__ bool elect() { uint32_t r; asm volatile("{ .reg .pred p; elect.sync _|p, 0xffffffff; selp.u32 %0, 1, 0, p; }" : "=r"(r)); return r; }
__device__ __forceinline__ uint32_t smem_u32(const void* p) { return (uint32_t)__cvta_generic_to_shared(p); }
__device__ __forceinline__ uint32_t pack_bf16(float lo, float hi) { uint32_t r; asm("cvt.rn.bf16x2.f32 %0, %1, %2;" : "=r"(r) : "f"(hi), "f"(lo)); return r; }
__device__ __forceinline__ uint32_t pack_f16(float lo, float hi) { uint32_t r; asm("cvt.rn.f16x2.f32 %0, %1, %2;" : "=r"(r) : "f"(hi), "f"(lo)); return r; }
__device__ __forceinline__ float bf_lo(uint32_t w) { return __uint_as_float(w << 16); }
__device__ __forceinline__ float bf_hi(uint32_t w) { return __uint_as_float(w & 0xffff0000u); }
__device__ __forceinline__ float rbf(float x) { return bf_lo(pack_bf16(x, 0.f)); }
__device__ __forceinline__ uint32_t badd2(uint32_t a, uint32_t b) { uint32_t r; asm("add.rn.bf16x2 %0, %1, %2;" : "=r"(r) : "r"(a), "r"(b)); return r; }
__device__ __forceinline__ uint32_t bsub2(uint32_t a, uint32_t b) { uint32_t r; asm("sub.rn.bf16x2 %0, %1, %2;" : "=r"(r) : "r"(a), "r"(b)); return r; }
__device__ __forceinline__ uint32_t gmix(uint32_t ng, float ny0, float ny1, uint32_t u) {
    uint32_t r; asm("{ .reg .b32 t; fma.rn.bf16x2 t, %1, %3, %3; fma.rn.bf16x2 %0, %1, %2, t; }" : "=r"(r) : "r"(ng), "r"(pack_bf16(ny0, ny1)), "r"(u)); return r;
}
__device__ __forceinline__ void mma_bf(float (&c)[4], uint32_t a0, uint32_t a1, uint32_t a2, uint32_t a3, uint32_t b0, uint32_t b1) {
    asm("mma.sync.aligned.m16n8k16.row.col.f32.bf16.bf16.f32 {%0,%1,%2,%3}, {%4,%5,%6,%7}, {%8,%9}, {%0,%1,%2,%3};"
        : "+f"(c[0]), "+f"(c[1]), "+f"(c[2]), "+f"(c[3]) : "r"(a0), "r"(a1), "r"(a2), "r"(a3), "r"(b0), "r"(b1));
}
__device__ __forceinline__ void mma_bf8(float (&c)[4], uint32_t a0, uint32_t a1, uint32_t b0) {
    asm("mma.sync.aligned.m16n8k8.row.col.f32.bf16.bf16.f32 {%0,%1,%2,%3}, {%4,%5}, {%6}, {%0,%1,%2,%3};"
        : "+f"(c[0]), "+f"(c[1]), "+f"(c[2]), "+f"(c[3]) : "r"(a0), "r"(a1), "r"(b0));
}
__device__ __forceinline__ void mma_h(float (&c)[4], uint32_t a0, uint32_t a1, uint32_t a2, uint32_t a3, uint32_t b0, uint32_t b1) {
    asm("mma.sync.aligned.m16n8k16.row.col.f32.f16.f16.f32 {%0,%1,%2,%3}, {%4,%5,%6,%7}, {%8,%9}, {%0,%1,%2,%3};"
        : "+f"(c[0]), "+f"(c[1]), "+f"(c[2]), "+f"(c[3]) : "r"(a0), "r"(a1), "r"(a2), "r"(a3), "r"(b0), "r"(b1));
}
__device__ __forceinline__ uint32_t fresh(uint32_t a) { asm volatile("" : "+r"(a) :: "memory"); return a; }
__device__ __forceinline__ uint32_t lds32(uint32_t a) { uint32_t v; asm("ld.shared.u32 %0, [%1];" : "=r"(v) : "r"(a)); return v; }
__device__ __forceinline__ uint2 lds64(uint32_t a) { uint2 v; asm("ld.shared.v2.u32 {%0,%1}, [%2];" : "=r"(v.x), "=r"(v.y) : "r"(a)); return v; }
__device__ __forceinline__ uint4 lds128(uint32_t a) { uint4 v; asm("ld.shared.v4.u32 {%0,%1,%2,%3}, [%4];" : "=r"(v.x), "=r"(v.y), "=r"(v.z), "=r"(v.w) : "r"(a)); return v; }
__device__ __forceinline__ void ldsm4(uint32_t (&r)[4], uint32_t a) {
    asm("ldmatrix.sync.aligned.m8n8.x4.shared.b16 {%0,%1,%2,%3}, [%4];" : "=r"(r[0]), "=r"(r[1]), "=r"(r[2]), "=r"(r[3]) : "r"(a));
}
__device__ __forceinline__ void ldsm4t(uint32_t (&r)[4], uint32_t a) {
    asm("ldmatrix.sync.aligned.m8n8.x4.trans.shared.b16 {%0,%1,%2,%3}, [%4];" : "=r"(r[0]), "=r"(r[1]), "=r"(r[2]), "=r"(r[3]) : "r"(a));
}
__device__ __forceinline__ void sts16(uint32_t a, uint32_t v) { asm volatile("st.shared.u16 [%0], %1;" :: "r"(a), "h"((unsigned short)v) : "memory"); }
__device__ __forceinline__ void sts32(uint32_t a, uint32_t v) { asm volatile("st.shared.u32 [%0], %1;" :: "r"(a), "r"(v) : "memory"); }
__device__ __forceinline__ void sts64(uint32_t a, uint32_t x, uint32_t y) { asm volatile("st.shared.v2.u32 [%0], {%1,%2};" :: "r"(a), "r"(x), "r"(y) : "memory"); }
__device__ __forceinline__ void sts128(uint32_t a, uint32_t x, uint32_t y, uint32_t z, uint32_t w) {
    asm volatile("st.shared.v4.u32 [%0], {%1,%2,%3,%4};" :: "r"(a), "r"(x), "r"(y), "r"(z), "r"(w) : "memory");
}
__device__ __forceinline__ void st_async128(uint32_t a, uint32_t x, uint32_t y, uint32_t z, uint32_t w, uint32_t bar) {
    asm volatile("st.async.weak.shared::cluster.mbarrier::complete_tx::bytes.v4.b32 [%0], {%1,%2,%3,%4}, [%5];" :: "r"(a), "r"(x), "r"(y), "r"(z), "r"(w), "r"(bar) : "memory");
}
__device__ __forceinline__ void mbar_init(uint32_t b, uint32_t cnt) { asm volatile("mbarrier.init.shared::cta.b64 [%0], %1;" :: "r"(b), "r"(cnt) : "memory"); }
__device__ __forceinline__ void mbar_fence() { asm volatile("fence.mbarrier_init.release.cluster;" ::: "memory"); }
__device__ __forceinline__ void mbar_expect(uint32_t b, uint32_t bytes) { asm volatile("mbarrier.arrive.expect_tx.shared::cta.b64 _, [%0], %1;" :: "r"(b), "r"(bytes) : "memory"); }
__device__ __forceinline__ void mbar_arrive(uint32_t b) { asm volatile("mbarrier.arrive.shared::cta.b64 _, [%0];" :: "r"(b) : "memory"); }
__device__ __forceinline__ void mbar_wait(uint32_t b, uint32_t parity = 0) {
    asm volatile("{ .reg .pred p; .reg .u32 n; mov.u32 n, 0;\n"
                 "LW: mbarrier.try_wait.parity.shared::cta.b64 p, [%0], %1; @p bra LD; add.u32 n, n, 1; setp.lt.u32 p, n, 65536; @p bra LW; trap;\n"
                 "LD: }" :: "r"(b), "r"(parity) : "memory");
}
__device__ __forceinline__ void mbar_wait_cluster(uint32_t b) {
    asm volatile("{ .reg .pred p; .reg .u32 n; mov.u32 n, 0;\n"
                 "LW: mbarrier.try_wait.parity.acquire.cluster.shared::cta.b64 p, [%0], 0; @p bra LD; add.u32 n, n, 1; setp.lt.u32 p, n, 65536; @p bra LW; trap;\n"
                 "LD: }" :: "r"(b) : "memory");
}
__device__ __forceinline__ void tma2d(uint32_t dst, const CUtensorMap* m, int c0, int c1, uint32_t bar) {
    asm volatile("cp.async.bulk.tensor.2d.shared::cluster.global.mbarrier::complete_tx::bytes [%0], [%1, {%3, %4}], [%2];"
                 :: "r"(dst), "l"(m), "r"(bar), "r"(c0), "r"(c1) : "memory");
}
__device__ __forceinline__ void tma3d(uint32_t dst, const CUtensorMap* m, int c0, int c1, int c2, uint32_t bar) {
    asm volatile("cp.async.bulk.tensor.3d.shared::cluster.global.mbarrier::complete_tx::bytes [%0], [%1, {%3, %4, %5}], [%2];"
                 :: "r"(dst), "l"(m), "r"(bar), "r"(c0), "r"(c1), "r"(c2) : "memory");
}
__device__ __forceinline__ void tma4d(uint32_t dst, const CUtensorMap* m, int c0, int c1, int c2, int c3, uint32_t bar) {
    asm volatile("cp.async.bulk.tensor.4d.shared::cluster.global.mbarrier::complete_tx::bytes [%0], [%1, {%3, %4, %5, %6}], [%2];"
                 :: "r"(dst), "l"(m), "r"(bar), "r"(c0), "r"(c1), "r"(c2), "r"(c3) : "memory");
}
__device__ __forceinline__ void bulk_g2s(uint32_t dst, const void* src, uint32_t bytes, uint32_t bar) {
    asm volatile("cp.async.bulk.shared::cluster.global.mbarrier::complete_tx::bytes [%0], [%1], %2, [%3];"
                 :: "r"(dst), "l"(src), "r"(bytes), "r"(bar) : "memory");
}
__device__ __forceinline__ uint32_t mapa(uint32_t a, uint32_t rank) { uint32_t r; asm("mapa.shared::cluster.u32 %0, %1, %2;" : "=r"(r) : "r"(a), "r"(rank)); return r; }
__device__ __forceinline__ void prefetch_map(const CUtensorMap* m) { asm volatile("prefetch.tensormap [%0];" :: "l"(m) : "memory"); }
__device__ __forceinline__ void bar_sync(int id, int n) { asm volatile("bar.sync %0, %1;" :: "r"(id), "r"(n) : "memory"); }
__device__ __forceinline__ void bar_arrive(int id, int n) { asm volatile("bar.arrive %0, %1;" :: "r"(id), "r"(n) : "memory"); }
__device__ __forceinline__ uint32_t ldg16_if(bool c, const void* p) { uint32_t v; asm volatile("{ .reg .pred p; setp.ne.u32 p, %2, 0; @p ld.global.nc.u16 %0, [%1]; }" : "=r"(v) : "l"(p), "r"((uint32_t)c)); return v; }
__device__ __forceinline__ uint32_t ldg32_if(bool c, const void* p) { uint32_t v; asm volatile("{ .reg .pred p; setp.ne.u32 p, %2, 0; @p ld.global.nc.u32 %0, [%1]; }" : "=r"(v) : "l"(p), "r"((uint32_t)c)); return v; }
__device__ __forceinline__ uint32_t ld_rlx32(const void* p) { uint32_t v; asm volatile("ld.relaxed.gpu.global.u32 %0, [%1];" : "=r"(v) : "l"(p) : "memory"); return v; }
__device__ __forceinline__ uint4 ld_rlx128(const void* p) {
    uint4 v; asm volatile("ld.relaxed.gpu.global.v4.u32 {%0,%1,%2,%3}, [%4];" : "=r"(v.x), "=r"(v.y), "=r"(v.z), "=r"(v.w) : "l"(p) : "memory"); return v;
}
__device__ __forceinline__ void st_rlx32(void* p, uint32_t v) { asm volatile("st.relaxed.gpu.global.u32 [%0], %1;" :: "l"(p), "r"(v) : "memory"); }
__device__ __forceinline__ void stg128(void* p, uint32_t x, uint32_t y, uint32_t z, uint32_t w) {
    asm volatile("st.global.v4.u32 [%0], {%1,%2,%3,%4};" :: "l"(p), "r"(x), "r"(y), "r"(z), "r"(w) : "memory");
}
__device__ __forceinline__ void next_epoch(const Params& p, unsigned e) { if ((threadIdx.x & 31) == 0) p.s->epoch[blockIdx.x * 16 + (threadIdx.x >> 5)] = e + 1; }
__device__ __forceinline__ void sts128z_if(bool c, uint32_t a) { asm volatile("{ .reg .pred p; setp.ne.u32 p, %1, 0; @p st.shared.v4.u32 [%0], {%2,%2,%2,%2}; }" :: "r"(a), "r"((uint32_t)c), "r"(0) : "memory"); }
__device__ __forceinline__ void stg128z_if(bool c, void* a) { asm volatile("{ .reg .pred p; setp.ne.u32 p, %1, 0; @p st.global.v4.u32 [%0], {%2,%2,%2,%2}; }" :: "l"(a), "r"((uint32_t)c), "r"(0) : "memory"); }
__device__ __forceinline__ unsigned clock32() { unsigned c; asm volatile("mov.u32 %0, %clock;" : "=r"(c) :: "memory"); return c; }
__device__ __forceinline__ void until(unsigned t0, int c) { while ((int)(clock32() - t0) < c) { } }
__device__ __forceinline__ float sigmoidf_(float x) { return __fdividef(1.0f, 1.0f + __expf(-x)); }
__device__ __forceinline__ uint32_t key_tag(unsigned epoch) { return ((epoch & 15u) | 16u) << 11; }
__device__ __forceinline__ int key_row(uint32_t key) { return 2047 - (int)(key & 2047u); }
__device__ __forceinline__ uint32_t wait_sel(const Params& p, int s32, int r8, uint32_t tag, uint32_t k = 0) {
#pragma unroll 1
    for (int it = 0; !__all_sync(0xffffffffu, (k & 0xf800u) == tag); it++) {
        k = ld_rlx32(&p.s->sel[s32 * 64 + r8]);
        if (it > (1 << 20)) give_up();
    }
    return k;
}

struct cplx { float re, im; };
__device__ __forceinline__ cplx csq(cplx a) { cplx r; r.re = a.re * a.re - a.im * a.im; r.im = (a.re * a.im) * 2.f; return r; }
__device__ __forceinline__ cplx cexpk(float ar, float ai, float k) {
    float mag, s, c;
    asm("ex2.approx.ftz.f32 %0, %1;" : "=f"(mag) : "f"(ar * (k * 1.4426950408889634f)));
    const float r = ai * k;
    asm("sin.approx.ftz.f32 %0, %1;" : "=f"(s) : "f"(r));
    asm("cos.approx.ftz.f32 %0, %1;" : "=f"(c) : "f"(r));
    cplx o; o.re = mag * c; o.im = mag * s; return o;
}
struct h2c { uint32_t re, im; };
__device__ __forceinline__ h2c cmul_cd(h2c v, __half2 c, __half2 d) {
    const __half2 r = *(const __half2*)&v.re, i = *(const __half2*)&v.im;
    const __half2 x = __hfma2(__hneg2(i), d, __hmul2(r, c)), y = __hfma2(i, c, __hmul2(r, d));
    h2c o; o.re = *(const uint32_t*)&x; o.im = *(const uint32_t*)&y; return o;
}
__device__ __forceinline__ h2c cmul_s(h2c v, uint32_t s) { const __half2 h = *(const __half2*)&s; return cmul_cd(v, __low2half2(h), __high2half2(h)); }
__device__ __forceinline__ h2c cmul_sc(h2c v, uint32_t s) {
    const __half2 h = *(const __half2*)&s, c = __low2half2(h), d = __high2half2(h), r = *(const __half2*)&v.re, i = *(const __half2*)&v.im;
    const __half2 x = __hfma2(i, d, __hmul2(r, c)), y = __hfma2(__hneg2(r), d, __hmul2(i, c));
    h2c o; o.re = *(const uint32_t*)&x; o.im = *(const uint32_t*)&y; return o;
}
__device__ __forceinline__ h2c cmul_vc(h2c v, uint32_t s) {
    const __half2 h = *(const __half2*)&s, c = __low2half2(h), d = __high2half2(h), r = *(const __half2*)&v.re, i = *(const __half2*)&v.im;
    const __half2 x = __hfma2(i, d, __hmul2(r, c)), y = __hfma2(__hneg2(i), c, __hmul2(r, d));
    h2c o; o.re = *(const uint32_t*)&x; o.im = *(const uint32_t*)&y; return o;
}

constexpr int UT_HALF = 2240, UT_STRIDE = 4448;
constexpr int KT_T = 542, KT_C = 552, KT_D = 645, KT_BYTES = 720 * 4;
constexpr int VC_OFF = 80, VE_BASE = 1616;
constexpr int V_STRIDE = (1616 + 1024) * 4 + 80;
constexpr int KG_STAGE = 5248;
constexpr int Y_CS = 2080, Y_RS = 8 * Y_CS + 64;

constexpr int SC_RT = 0;
constexpr int SC_UT = 33408;
constexpr int SC_ST = SC_UT + 8 * UT_STRIDE;
constexpr int SC_KT = SC_ST + 8 * UT_STRIDE;
constexpr int SC_GT = SC_KT + 8 * KT_BYTES;
constexpr int SC_V = SC_GT + UT_STRIDE;
constexpr int SC_KG = SC_V + 4 * V_STRIDE;
constexpr int SC_MISC = SC_V + 8 * V_STRIDE;
static_assert(V_STRIDE % 128 == 16 && 8 * KG_STAGE <= 4 * V_STRIDE && 2 * Y_RS <= SC_UT && SC_UT % 128 == 0 && SC_ST % 128 == 0, "layout");
static_assert(SC_MISC % 16 == 0 && SC_MISC + 512 <= 232192, "layout");

__device__ __forceinline__ void window_task(uint32_t src, uint32_t d0, uint32_t d1, bool withE) {
    float S[35];
    {
        uint32_t w[20];
#pragma unroll
        for (int i = 0; i < 5; i++) {
            const uint4 v = lds128(src + ((i & 1) ? 0 : UT_HALF) + ((i + 1) >> 1) * 16);
            w[4 * i] = v.x; w[4 * i + 1] = v.y; w[4 * i + 2] = v.z; w[4 * i + 3] = v.w;
        }
        float s = 0.f; S[2] = 0.f;
#pragma unroll
        for (int i = 3; i < 26; i++) { s += (i & 1) ? bf_hi(w[i >> 1]) : bf_lo(w[i >> 1]); S[i] = s; }
#pragma unroll
        for (int i = 0; i < 8; i += 2)
            sts128((i & 4 ? d1 : d0) + (VC_OFF - 16) * 4 + 8 * (i & 2), pack_bf16(S[10 + i] - S[5 + i], S[5 + i] - S[2 + i]), pack_bf16(S[18 + i] - S[13 + i], S[13 + i] - S[10 + i]),
                   pack_bf16(S[11 + i] - S[6 + i], S[6 + i] - S[3 + i]), pack_bf16(S[19 + i] - S[14 + i], S[14 + i] - S[11 + i]));
        if (withE) {
#pragma unroll
            for (int i = 26; i < 35; i++) { s += (i & 1) ? bf_hi(w[i >> 1]) : bf_lo(w[i >> 1]); S[i] = s; }
#pragma unroll
            for (int i = 0; i < 8; i += 2)
                sts128((i & 4 ? d1 : d0) + VE_BASE * 4 + 8 * (i & 2), pack_bf16(S[19 + i] - S[12 + i], S[12 + i] - S[3 + i]), pack_bf16(S[27 + i] - S[20 + i], S[20 + i] - S[11 + i]),
                       pack_bf16(S[20 + i] - S[13 + i], S[13 + i] - S[4 + i]), pack_bf16(S[28 + i] - S[21 + i], S[21 + i] - S[12 + i]));
        }
    }
}

template <class F>
__device__ __forceinline__ void kgen(const uint32_t (&q)[8], uint32_t sb, int half, uint32_t stage, uint32_t pstage, int barid, int lane, uint32_t (&w)[12], F shadow) {
    const int t = lane & 3, mi = lane >> 3, r8 = lane & 7;
    {
        const uint32_t pAr = q[0], pAi = q[1], pBr = q[2], pBi = q[3], pCr = q[4], pCi = q[5], pDt = q[6], pD = q[7];
        const uint32_t wb = fresh(stage + lane * 16), za = fresh(stage + 5120 + ((lane >> 1) & 3) * 16 + mi * 4 + (lane & 1) * 2), zr = fresh(stage + 5120 + t * 16);
        const uint32_t oA = fresh(stage + (mi & 1) * 1024 + (mi >> 1) * 512 + r8 * 16), oB = fresh(stage + 2048 + mi * 512 + r8 * 16), oC = fresh(stage + 4096 + (mi & 1) * 512 + (mi >> 1) * 128 + r8 * 16);
        float acc[6][4];
#pragma unroll
        for (int a = 0; a < 6; a++) { acc[a][0] = acc[a][1] = acc[a][2] = acc[a][3] = 0.f; asm volatile("" : "+f"(acc[a][0]), "+f"(acc[a][1]), "+f"(acc[a][2]), "+f"(acc[a][3])); }
        shadow();
        sts32(zr, clock32());
        const float dt = rbf(__expf(bf_lo(pDt)));
        float ar = dt * bf_lo(pAr), ai = dt * bf_lo(pAi), ar1 = dt * bf_hi(pAr), ai1 = dt * bf_hi(pAi);
        float wr, wi, wr1, wi1;
        { const float br = dt * bf_lo(pBr), bi = dt * bf_lo(pBi), cr = bf_lo(pCr), ci = bf_lo(pCi); wr = cr * br - ci * bi; wi = cr * bi + ci * br; }
        { const float br = dt * bf_hi(pBr), bi = dt * bf_hi(pBi), cr = bf_hi(pCr), ci = bf_hi(pCi); wr1 = cr * br - ci * bi; wi1 = cr * bi + ci * br; }
        const uint32_t ex = max(__reduce_max_sync(0xffffffffu, __float_as_uint(fmaxf(fmaxf(fabsf(wr), fabsf(wi)), fmaxf(fabsf(wr1), fabsf(wi1))))) >> 23, 14u);
        const float scl = __uint_as_float((267u - ex) << 23);
        uint32_t W = pack_f16(wr * scl, wi * -scl);
        const uint32_t W1 = pack_f16(wr1 * scl, wi1 * -scl);
        if (threadIdx.x < 32) TSTAMP(20);

#pragma unroll 1
        for (int r = 0; r < 2; r++) {
            const cplx z1 = cexpk(ar, ai, 1.f), z64 = cexpk(ar, ai, 64.f);
            const cplx z2 = csq(z1), z4 = csq(z2), z8 = csq(z4), z16 = csq(z8), z32 = csq(z16);
            const cplx z128 = csq(z64), z256 = csq(z128), z512 = csq(z256);
            auto put = [&](int grp, h2c a, h2c b, h2c c, h2c d) { sts128(wb + grp * 1024, a.re, b.re, c.re, d.re); sts128(wb + grp * 1024 + 512, a.im, b.im, c.im, d.im); };
            {
                const uint32_t s4 = pack_f16(z4.re, z4.im), s256 = pack_f16(z256.re, z256.im), s512 = pack_f16(z512.re, z512.im);
                auto mix = [](h2c a, h2c b, uint32_t sel) { return h2c{__byte_perm(a.re, b.re, sel), __byte_perm(a.im, b.im, sel)}; };
                const h2c c10 = cmul_vc(h2c{pack_f16(z1.re, 1.f), pack_f16(z1.im, 0.f)}, W), c32 = cmul_sc(c10, pack_f16(z2.re, z2.im)), c54 = cmul_sc(c10, s4);
                put(2, c10, c32, c54, cmul_sc(c32, s4));
                const h2c d20 = cmul_sc(mix(c32, c10, 0x7632), s256), e04 = cmul_sc(mix(c10, c54, 0x7632), s512), f04 = cmul_sc(e04, s256);
                put(3, d20, cmul_sc(d20, s4), e04, f04);
                const h2c ef = mix(e04, f04, 0x5410), gh = cmul_sc(ef, s512), g8 = cmul_sc(gh, pack_f16(z8.re, z8.im));
                put(4, g8, cmul_sc(g8, s512), gh, ef);
            }
            {
                const uint32_t s32 = pack_f16(z32.re, z32.im), s64 = pack_f16(z64.re, z64.im), s128 = pack_f16(z128.re, z128.im);
                const h2c p0 = {pack_f16(1.f, z8.re), pack_f16(0.f, z8.im)}, p1 = cmul_s(p0, pack_f16(z16.re, z16.im)), p2 = cmul_s(p0, s32), p3 = cmul_s(p1, s32);
                put(0, p0, p1, p2, p3);
                put(1, cmul_s(p0, s64), cmul_s(p1, s64), cmul_s(p2, s64), cmul_s(p3, s64));
                sts16(za, s128); sts16(za + 64, s128 >> 16);
            }
            __syncwarp();
            {
                const uint32_t aA = fresh(oA), aB = fresh(oB), aC = fresh(oC), aZ = fresh(zr);
                const uint4 zc = lds128(aZ), zd = lds128(aZ + 64);
                const uint32_t zcs[4] = {zc.x, zc.y, zc.z, zc.w}, zds[4] = {zd.x, zd.y, zd.z, zd.w};
                uint32_t c[4];
#pragma unroll
                for (int k = 0; k < 4; k++) {
                    uint32_t a[4], b[4];
                    ldsm4t(a, aA + 128 * k); ldsm4t(b, aB + 128 * k);
                    if (!(k & 1)) ldsm4t(c, aC + 128 * k);
                    const h2c x = cmul_cd(h2c{a[0], a[2]}, *(const __half2*)&zcs[k], *(const __half2*)&zds[k]), y = cmul_cd(h2c{a[1], a[3]}, *(const __half2*)&zcs[k], *(const __half2*)&zds[k]);
                    mma_h(acc[0], a[0], a[1], a[2], a[3], b[0], b[1]);
                    mma_h(acc[1], a[0], a[1], a[2], a[3], b[2], b[3]);
                    mma_h(acc[2], a[0], a[1], a[2], a[3], c[2 * (k & 1)], c[2 * (k & 1) + 1]);
                    mma_h(acc[3], x.re, y.re, x.im, y.im, b[0], b[1]);
                    mma_h(acc[4], x.re, y.re, x.im, y.im, b[2], b[3]);
                    mma_h(acc[5], x.re, y.re, x.im, y.im, c[2 * (k & 1)], c[2 * (k & 1) + 1]);
                }
                asm volatile("" :: "f"(acc[0][0]), "f"(acc[1][0]), "f"(acc[2][0]), "f"(acc[3][0]), "f"(acc[4][0]), "f"(acc[5][0]) : "memory");
            }
            __syncwarp();
            ar = ar1; ai = ai1; W = W1;
        }
        if (threadIdx.x < 32) TSTAMP(21);
        const float i0 = __uint_as_float((ex + 243u) << 23);
        if (half) {
#pragma unroll
            for (int a = 0; a < 6; a++) sts128(wb + a * 512, __float_as_uint(acc[a][0]), __float_as_uint(acc[a][1]), __float_as_uint(acc[a][2]), __float_as_uint(acc[a][3]));
            sts32(stage + 3072, __float_as_uint(i0));
            bar_arrive(barid, 64);
        } else {
#pragma unroll
            for (int a = 0; a < 6; a++) { acc[a][0] *= i0; acc[a][1] *= i0; acc[a][2] *= i0; acc[a][3] *= i0; }
            if (lane == 0) acc[0][1] -= bf_lo(pD);
            sts32(zr, clock32());
            bar_sync(barid, 64);
            const uint32_t src = fresh(pstage);
            const float i1 = __uint_as_float(lds32(src + 3072));
#pragma unroll
            for (int a = 0; a < 6; a++) {
                const uint4 y = lds128(src + lane * 16 + a * 512);
                w[4 * (a % 3) + 2 * (a / 3)] = pack_bf16(fmaf(__uint_as_float(y.x), i1, acc[a][0]), fmaf(__uint_as_float(y.y), i1, acc[a][1]));
                w[4 * (a % 3) + 2 * (a / 3) + 1] = pack_bf16(fmaf(__uint_as_float(y.z), i1, acc[a][2]), fmaf(__uint_as_float(y.w), i1, acc[a][3]));
            }
            const uint32_t x0 = __shfl_up_sync(0xffffffffu, w[10], 2), x1 = __shfl_up_sync(0xffffffffu, w[11], 2);
            w[10] = w[8];
            if (t >= 2) { w[8] = x0; w[9] = x1; }
        }
    }
}

__device__ __forceinline__ int swap01(int i) { return (i & ~3) | ((i & 1) << 1) | ((i >> 1) & 1); }
enum { BC_AUX = 0, BC_S = 5, BC_KG = 15 };

__device__ __forceinline__ void fetch_gates(const Params& p, int i, int lane, unsigned epoch, uint32_t dst) {
    const uint32_t par = (epoch & 1) ? 0x80008000u : 0u;
    uint4 v;
#pragma unroll 1
    for (int it = 0;; it++) {
        v = ld_rlx128(p.s->gate + 256 * i + 8 * lane);
        v.x ^= par; v.y ^= par; v.z ^= par; v.w ^= par;
        if (__all_sync(0xffffffffu, (v.x & v.y & v.z & v.w & 0x80008000u) == 0x80008000u)) break;
        if (it > (1 << 20)) give_up();
    }
    sts128(dst + (8 + 16 * i + (lane >> 1)) * 16, v.x, v.y, v.z, v.w);
}
__device__ __forceinline__ void store_rows(const CUtensorMap* m, uint32_t src, int col, int row) {
    asm volatile("cp.async.bulk.tensor.5d.global.shared::cta.bulk_group [%0, {%2, %3, %3, %3, %4}], [%1];" :: "l"(m), "r"(src), "r"(col), "r"(0), "r"(row) : "memory");
}

__device__ __forceinline__ void store_or_add(void* o, const uint32_t (&y)[4], uint32_t add) {
    asm volatile("{ .reg .pred p; setp.ne.u32 p, %5, 0; @!p st.global.v4.u32 [%0], {%1,%2,%3,%4}; @p red.relaxed.gpu.global.add.noftz.v4.bf16x2 [%0], {%1,%2,%3,%4}; }"
                 :: "l"(o), "r"(y[0]), "r"(y[1]), "r"(y[2]), "r"(y[3]), "r"(add) : "memory");
}

__device__ __forceinline__ void conv_aux(const Params& p, const CUtensorMap* mU, uint32_t sb, int aw, int lane, int bid, unsigned epoch) {
    const int g = lane >> 2, t = lane & 3, mi = lane >> 3, r8 = lane & 7;
    const int rank = bid & 1, slab = bid >> 1;
    const uint32_t bar_y = sb + SC_MISC, bar_u = bar_y + 32, bar_v = bar_y + 40, bar_box = bar_y + 64 + 8 * aw, s_bm = bar_y + 128;
    if (elect()) {
        mbar_init(bar_box, 1); mbar_fence();
        mbar_expect(bar_box, 4096);
        tma4d(sb + SC_RT + 4096 * aw, mU, 16 * slab, 0, 0, 16 * rank + 2 * aw, bar_box);
        mbar_init(bar_y + 8 * aw, aw < 4 ? 9 : aw == 5 ? 8 : 1); mbar_fence();
        if (aw < 5) mbar_expect(bar_y + 8 * aw, aw == 4 ? 16384 : 4096);
    }
    __syncwarp();
    asm volatile("barrier.cluster.arrive.relaxed.aligned;" ::: "memory");
    asm volatile("setmaxnreg.dec.sync.aligned.u32 88;");
    const uint32_t ut = sb + SC_UT + aw * UT_STRIDE;
    sts128(ut + (mi >> 1) * (SC_ST - SC_UT) + (mi & 1) * UT_HALF + r8 * 16, 0, 0, 0, 0);
    if (lane < 16) sts128(s_bm + lane * 16, 0, 0, 0, 0);
    {
        const uint32_t dst = sb + SC_UT + swap01(g) * UT_STRIDE + (8 + 64 * rank + 8 * aw + t) * 16;
        const uint32_t rdst = mapa(dst, rank ^ 1), rbar = mapa(bar_u, rank ^ 1);
        asm volatile("barrier.cluster.wait.acquire.aligned;" ::: "memory");
        mbar_wait(bar_box);
        if (aw == 0) TSTAMP(1);
        const uint32_t src = fresh(sb + SC_RT) + aw * 4096 + (8 * mi + 4 * (r8 & 1) + (r8 >> 1)) * 32 + ((rank ^ (r8 & 1)) << 4);
        uint32_t x[8][4];
#pragma unroll
        for (int i = 0; i < 4; i++) { ldsm4t(x[i], src + 1024 * i); ldsm4t(x[4 + i], (src ^ 16) + 1024 * i); }
        asm volatile("" :: "r"(x[0][0]), "r"(x[1][0]), "r"(x[2][0]), "r"(x[3][0]) : "memory");
#pragma unroll
        for (int i = 0; i < 4; i++) st_async128(rdst + (i & 1) * UT_HALF + 32 * (i & 2), x[4 + i][0], x[4 + i][1], x[4 + i][2], x[4 + i][3], rbar);
#pragma unroll
        for (int i = 0; i < 4; i++) sts128(dst + (i & 1) * UT_HALF + 32 * (i & 2), x[i][0], x[i][1], x[i][2], x[i][3]);
    }
    bar_sync(BC_AUX, 256);
    mbar_wait_cluster(bar_u);
    if (aw == 0) TSTAMP(2);
    {
        const uint32_t a = fresh(ut) + (mi & 1) * UT_HALF + (64 * (mi >> 1) + r8) * 16;
        uint4 v = lds128(a);
#pragma unroll
        for (int i = 1; i <= 8; i++) {
            const uint4 w = lds128(a + 128 * i);
            sts128(a + 128 * i + (SC_ST - SC_UT), badd2(v.x, w.x), badd2(v.y, w.y), badd2(v.z, w.z), badd2(v.w, w.w));
            v = w;
        }
    }
    bar_arrive(BC_S + aw, 64);
    if (aw == 0) TSTAMP(3);
    {
        uint32_t ws = sb + SC_UT + t * UT_STRIDE + (g + 6) * 16, wd = sb + SC_V + t * V_STRIDE + 64 * g, sw = 16 * (g & 2);
#pragma unroll 1
        for (int k = aw; k < 25; k += 8) {
            if (k - aw == 8) {
                bar_sync(BC_KG, 384);
                if (lane < 16) sts128(sb + SC_V + aw * V_STRIDE + lane * 16, 0, 0, 0, 0);
            }
            if (k == 24) { ws -= (g & 1) * 4 * UT_STRIDE + 16 * g; wd -= (g & 1) * 4 * V_STRIDE + 64 * g; sw = 0; }
            const int h = k >= 12, a = k - 12 * h;
            const uint32_t d = wd + h * 4 * V_STRIDE + 512 * a;
            window_task(fresh(ws) + h * 4 * UT_STRIDE + 128 * a, d + sw, d + (sw ^ 32), a < 8);
        }
    }
    if (aw == 0) TSTAMP(9);
    {
        if (aw >= 2) fetch_gates(p, aw, lane, epoch, sb + SC_GT + (lane & 1) * UT_HALF);
        __syncwarp();
        if (elect()) { mbar_arrive(bar_v); prefetch_map(mU + 4); }
        next_epoch(p, epoch);
        if (aw == 0) TSTAMP(4);
        if (aw == 7) {
            const int row = key_row(wait_sel(p, slab >> 1, r8, key_tag(epoch)));
            if (lane < 8) asm volatile("red.shared.or.b32 [%0], %1;" :: "r"(s_bm + (row >> 5) * 4), "r"(1u << (row & 31)) : "memory");
            TSTAMP(10);
        }
        bar_sync(BC_AUX, 256);
        const uint32_t src = sb + SC_RT + ((r8 >> 1) & 1) * Y_RS + (2 * mi + (r8 & 1)) * Y_CS + (2 * aw + (r8 >> 2)) * 16;
        const int L = 2 * aw + (t >> 1);
        const int row0 = 256 * rank + 128 * (g >> 2) + 32 * (L & 3) + 16 * (g & 1) + 8 * ((g >> 1) & 1) + (L >> 2);
        __nv_bfloat16* outp = p.out + (size_t)row0 * DM + 16 * slab + 8 * (t & 1);
        const uint32_t stg = sb + SC_ST + 4096 * aw, so = (g >> 1) * 256 + (t >> 1) * 64 + (g & 1) * 32 + (t & 1) * 16;
#pragma unroll 1
        for (int s = 1; s < 4; s++) {
            const uint32_t bm = lds32(fresh(s_bm) + (16 * s + (row0 >> 5)) * 4) >> (row0 & 31);
            const bool routed = __any_sync(0xffffffffu, bm & 0x11u);
            if (aw == s) mbar_wait_cluster(bar_y + 8 * s);
            bar_sync(BC_AUX, 256);
            const uint32_t sf = fresh(src) + 512 * s;
            uint32_t y[2][4];
            ldsm4t(y[0], sf); ldsm4t(y[1], sf + 256);
            if (routed) {
#pragma unroll
                for (int k = 0; k < 2; k++) store_or_add(outp + (size_t)(512 * s + 4 * k) * DM, y[k], bm & (1u << (4 * k)));
            } else {
                sts128(stg + so + 1024 * s, y[0][0], y[0][1], y[0][2], y[0][3]); sts128(stg + so + 1024 * s + 128, y[1][0], y[1][1], y[1][2], y[1][3]);
                asm volatile("fence.proxy.async.shared::cta;" ::: "memory");
                __syncwarp();
                if (elect()) store_rows(mU + 4, stg + 1024 * s, 16 * slab, 512 * s + 256 * rank + 64 * (aw & 1) + (aw >> 1));
            }
            if (aw == 0) TSTAMP(16 + s);
        }
        if (elect()) { asm volatile("cp.async.bulk.commit_group;" ::: "memory"); asm volatile("cp.async.bulk.wait_group.read 0;" ::: "memory"); }
        if (aw == 0) TFLUSH();
    }
}

__device__ __forceinline__ uint32_t k_tag(unsigned epoch) { return epoch << 16 | 0x80000000u; }
__device__ __forceinline__ void publish_k(uint4* kp, const uint32_t (&w)[12], unsigned epoch, uint64_t (&v)[6]) {
#pragma unroll
    for (int i = 0; i < 3; i++) {
        v[2 * i] = w[3 * i] | (uint64_t)w[3 * i + 1] << 32; v[2 * i + 1] = w[3 * i + 2] | (uint64_t)__byte_perm(w[9 + (i >> 1)], k_tag(epoch), i == 1 ? 0x7632 : 0x7610) << 32;
        asm volatile("st.relaxed.gpu.global.v2.u64 [%0], {%1,%2};" :: "l"(kp + 32 * i), "l"(v[2 * i]), "l"(v[2 * i + 1]));
    }
}
template <bool FULL>
__device__ __forceinline__ void k_tables(uint32_t kt, int lane, const uint32_t (&w)[12]) {
    const int g = lane >> 2, t = lane & 3, mi = lane >> 3, r8 = lane & 7;
    uint32_t x3 = w[7], re[4], rx[4];
#pragma unroll
    for (int i = 0; i < 4; i++) {
        re[i] = __shfl_sync(0xffffffffu, w[i], lane + 31);
        rx[i] = __shfl_sync(0xffffffffu, w[4 + i], lane + (i == 0 && lane == 29 ? 5 : 1 + 2 * t));
    }
    if (FULL) {
        asm volatile("stmatrix.sync.aligned.m8n8.x2.trans.shared.b16 [%0], {%1,%2};" :: "r"(kt + (KT_D + 7) * 4 + 64 * t + 16 * (mi & 1) + 8 * (r8 & 4)), "r"(w[8]), "r"(w[9]) : "memory");
        if (lane == 2) {
            sts32(kt + (KT_C + 78) * 4, w[10] & 0xffffu);
            sts128(kt + (KT_T + 2) * 4, 0, w[10] & 0xffffu, __byte_perm(w[10], 0, 0x1010), w[10] << 16);
        }
        if (lane == 29) x3 = bsub2(x3, rx[0] & 0xffffu);
    }
#pragma unroll
    for (int i = 0; i < 4; i++) {
        sts64(kt + (16 + 64 * i) * 4 + 8 * lane, __byte_perm(w[i], lane ? re[i] : i ? re[i - 1] : 0, 0x5432), w[i]);
        const uint32_t x = i < 3 ? w[4 + i] : x3, aa = __byte_perm(x, 0, 0x3232);
        if (t < 2) sts128(kt + (272 + 64 * i + 8 * g + 4 * t) * 4, i == 0 && lane == 0 ? __byte_perm(x, re[3], 0x5432) : aa, aa, x,
                          __byte_perm(lane != 29 ? rx[i] : i < 3 ? rx[(i + 1) & 3] : FULL ? 0 : rx[0] << 16, x, 0x5432));
        else if (FULL) sts32(kt + (KT_C - 50 + 8 * i + 32 * t + g) * 4, x);
    }
}

__device__ __forceinline__ void conv_main(const Params& p, uint32_t sb, int warp, int lane0, int bid, unsigned epoch, uint32_t (&w)[12]) {
    asm volatile("setmaxnreg.inc.sync.aligned.u32 168;");
    const int lane = __shfl_sync(0xffffffffu, lane0, lane0);
    const int g = lane >> 2, t = lane & 3, mi = lane >> 3, r8 = lane & 7;
    const int rank = bid & 1;
    const uint32_t bar_y = sb + SC_MISC, bar_v = bar_y + 40;
    next_epoch(p, epoch);
    if (warp < 4) {
        asm volatile("" :: "r"(w[0]), "r"(w[2]), "r"(w[4]), "r"(w[6]), "r"(w[8]), "r"(w[10]) : "memory");
        bar_arrive(BC_KG, 384);
    } else {
        bar_sync(BC_S + swap01(warp), 64);
        const uint4* src = p.s->kp + (8 * bid + warp) * 96 + lane0;
#pragma unroll 1
        for (int it = 0;; it++) {
            uint32_t bad = 0, e[3];
#pragma unroll
            for (int i = 0; i < 3; i++) { const uint4 v = ld_rlx128(src + 32 * i); w[3 * i] = v.x; w[3 * i + 1] = v.y; w[3 * i + 2] = v.z; e[i] = v.w; bad |= v.w ^ k_tag(epoch); }
            w[9] = __byte_perm(e[0], e[1], 0x5410); w[10] = e[2];
            const bool ok = __all_sync(0xffffffffu, bad < 65536);
            if (ok) break;
            if (it > (1 << 20)) give_up();
        }
    }
    if ((warp & 3) == 0) TSTAMP(5 + (warp >> 2));
    k_tables<true>(sb + SC_KT + warp * KT_BYTES, lane0, w);
    asm volatile("barrier.cluster.wait.acquire.aligned;" ::: "memory");
    if (warp < 4) bar_sync(BC_S + swap01(warp), 64);
    __syncwarp();
    if ((warp & 3) == 0) TSTAMP(7 + (warp >> 2));
    {
        const uint32_t ut = fresh(sb + SC_UT) + swap01(warp) * UT_STRIDE, kt = fresh(sb + SC_KT) + warp * KT_BYTES;
        uint32_t u1 = ut + (mi & 1) * UT_HALF + (8 + r8) * 16 + (mi >> 1) * 128;
        auto dup = [&](uint32_t v) { return v ^ p.zero; };
        uint32_t kp = kt + (16 + g - 2 * t) * 4;
        float acc[16][4];
        {
            const uint32_t c0 = lds32(kp + 2048), c1 = lds32(kp + 2080), c2 = lds32(kp + 2016), c3 = dup(c0);
            const uint32_t e0 = lds32(kp + (KT_T - 16) * 4), e1 = lds32(kp + (KT_T - 8) * 4), e2 = lds32(kp + (KT_T - 24) * 4), e3 = dup(e0);
            const uint32_t f0 = dup(e1), f1 = lds32(kp + KT_T * 4);
            const uint32_t uo = ut + UT_HALF + (7 + lane) * 16;
#pragma unroll
            for (int i = 0; i < 16; i++) { acc[i][0] = acc[i][1] = acc[i][2] = acc[i][3] = 0.f; }
#pragma unroll
            for (int mu = 0; mu < 8; mu += 4) {
                uint32_t b[4];
                ldsm4(b, uo + 128 * mu);
#pragma unroll
                for (int k = 0; k < 4; k++) mma_bf8(acc[mu + 8 + k], f0, f1, b[k]);
            }
#pragma unroll
            for (int mu = 0; mu < 12; mu += 2) {
                uint32_t b[4];
                ldsm4(b, u1 + 128 * mu);
                mma_bf(acc[mu + 4], c0, c1, c2, c3, b[0], b[1]);
                mma_bf(acc[mu + 5], c0, c1, c2, c3, b[2], b[3]);
                if (mu < 8) { mma_bf(acc[mu + 8], e0, e1, e2, e3, b[0], b[1]); mma_bf(acc[mu + 9], e0, e1, e2, e3, b[2], b[3]); }
            }
        }
        {
            float M[8][4];
#pragma unroll
            for (int i = 0; i < 8; i++) { M[i][0] = M[i][1] = M[i][2] = M[i][3] = 0.f; }
            uint32_t s[8][4], a3[4];
            const uint32_t kb = kp, ub = dup(u1), uc = u1 + (mi >> 1) * 128;
            auto frag = [&](uint32_t (&a)[4], uint32_t x) { a[0] = lds32(x); a[1] = lds32(x + 32); a[2] = lds32(x - 32); a[3] = dup(a[0]); };
            frag(a3, kp + 1536);
#pragma unroll
            for (int i = 1; i < 8; i++) ldsm4(s[i], u1 + (SC_ST - SC_UT) + 256 * i);
            __syncwarp();
#pragma unroll 1
            for (uint32_t ko = 0, uo = 0; ko != 512;) {
                uint32_t a2[4], a1[4], a0[4], b[4][4];
                ko = fresh(ko); uo = fresh(uo);
                kp = kb + ko; u1 = ub + uo;
                const uint32_t up = uc + uo;
                ko += 64; uo -= 16;
                frag(a2, kp + 1024);
#pragma unroll
                for (int i = 1; i < 4; i++) ldsm4(b[i], up + 512 * i);
                asm("ldmatrix.sync.aligned.m8n8.x2.shared.b16 {%0,%1}, [%2];" : "=r"(b[0][2]), "=r"(b[0][3]) : "r"(up + 256));
                frag(a1, kp + 512); frag(a0, kp);
                kp += 64; u1 -= 16;
#pragma unroll
                for (int i = 1; i < 7; i++) mma_bf(acc[2 * i + 2], a3[0], a3[1], a3[2], a3[3], s[i][0], s[i][1]);
#pragma unroll
                for (int e = 0; e < 4; e++) a3[e] = bsub2(a2[e], a3[e]);
#pragma unroll
                for (int i = 1; i < 7; i++) mma_bf(acc[2 * i + 3], a2[0], a2[1], a2[2], a2[3], s[i][2], s[i][3]);
                ldsm4(s[1], u1 + (SC_ST - SC_UT) + 256);
#pragma unroll
                for (int i = 1; i < 7; i++) mma_bf(M[i + 1], a3[0], a3[1], a3[2], a3[3], b[i >> 1][2 * (i & 1)], b[i >> 1][2 * (i & 1) + 1]);
                frag(a3, kp + 1536);
#pragma unroll
                for (int i = 2; i < 8; i++) mma_bf(acc[2 * i], a1[0], a1[1], a1[2], a1[3], s[i][0], s[i][1]);
#pragma unroll
                for (int e = 0; e < 4; e++) a1[e] = bsub2(a0[e], a1[e]);
#pragma unroll
                for (int i = 2; i < 8; i++) { mma_bf(acc[2 * i + 1], a0[0], a0[1], a0[2], a0[3], s[i][2], s[i][3]); ldsm4(s[i], u1 + (SC_ST - SC_UT) + 256 * i); }
#pragma unroll
                for (int i = 2; i < 8; i++) mma_bf(M[i], a1[0], a1[1], a1[2], a1[3], b[i >> 1][2 * (i & 1)], b[i >> 1][2 * (i & 1) + 1]);
            }
            u1 = ub;
#pragma unroll
            for (int i = 2; i < 8; i++)
#pragma unroll
                for (int c = 0; c < 4; c++) { acc[2 * i][c] += M[i][c]; acc[2 * i + 1][c] -= M[i][c]; }
        }
        if ((warp & 3) == 0) TSTAMP(11 + (warp >> 2));
        mbar_wait(bar_v);
        const uint32_t vt = fresh(sb + SC_V) + swap01(warp) * V_STRIDE;
        const uint32_t g1 = fresh(u1) - ut + sb + SC_GT;
        const uint32_t ydst = sb + SC_RT + rank * Y_RS + warp * Y_CS + lane * 16;
        const uint32_t ydr = mapa(ydst, rank ^ 1), ybr = mapa(bar_y, rank ^ 1);
        auto stairs = [&](auto R) {
        uint32_t ug[2][2][4];
        auto ld_ug = [&](int i) { ldsm4t(ug[i & 1][0], u1 + 256 * i); ldsm4t(ug[i & 1][1], g1 + 256 * i); };
        auto ship = [&](int i) {
            const uint32_t (&u)[4] = ug[i & 1][0], (&gg)[4] = ug[i & 1][1];
            const uint32_t y0 = gmix(gg[0], acc[2 * i][0], acc[2 * i][1], u[0]), y1 = gmix(gg[1], acc[2 * i][2], acc[2 * i][3], u[1]);
            const uint32_t y2 = gmix(gg[2], acc[2 * i + 1][0], acc[2 * i + 1][1], u[2]), y3 = gmix(gg[3], acc[2 * i + 1][2], acc[2 * i + 1][3], u[3]);
            if ((i & 1) != R.value) st_async128(ydr + 512 * (i >> 1), y0, y1, y2, y3, ybr + 8 * (i >> 1));
            else asm volatile("{ .reg .pred q; setp.eq.u32 q, %6, 0; st.shared.v4.u32 [%0], {%2,%3,%4,%5}; bar.warp.sync 0xffffffff; @q mbarrier.arrive.shared::cta.b64 _, [%1]; }"
                              :: "r"(ydst + 512 * (i >> 1)), "r"(bar_y + 8 * (i >> 1)), "r"(y0), "r"(y1), "r"(y2), "r"(y3), "r"(lane) : "memory");
        };
        const uint32_t VD = vt + (VC_OFF - 400 - 16 * t) * 4 + (8 * g ^ 16 * (-t & 2)), VD2 = vt + (VC_OFF - 415 - 16 * t) * 4 + (8 * g ^ 16 * (~t & 2));
        uint2 bd[10];
        uint32_t x[2][4][4];
        auto ld4 = [&](uint32_t (&v)[4], int dl) { const uint2 w = lds64(VD + 256 * dl); v[0] = w.x; v[1] = w.y; v[2] = lds32(VD2 + 256 * dl); v[3] = dup(w.x); };
        auto mm4 = [&](const uint32_t (&v)[4], int dl) {
#pragma unroll
            for (int s = dl & 1; s < 10; s += 2) if ((dl + s) / 2 >= 4 && (dl + s) / 2 < 16) mma_bf(acc[(dl + s) / 2], v[0], v[1], v[2], v[3], bd[s].x, bd[s].y);
        };
        const uint32_t KE = kt + (KT_D + g + t) * 4, VE = vt + (VE_BASE - 912 - 16 * t) * 4 + (8 * g ^ 16 * (~t & 2));
        uint32_t b0[8], b1[8];
        auto ld8 = [&](uint32_t (&v)[4], int dl) { const uint2 w = lds64(VE + 512 * dl), z = lds64(VE + 512 * dl - 256); v[0] = w.x; v[1] = w.y; v[2] = z.x; v[3] = z.y; };
        auto mm8 = [&](const uint32_t (&v)[4], int dl, int lo, int hi) {
#pragma unroll
            for (int s = 0; s < 8; s++) if (dl + s >= lo && dl + s < hi) mma_bf(acc[dl + s], v[0], v[1], v[2], v[3], b0[s], b1[s]);
        };
        ld4(x[0][0], 6);
#pragma unroll
        for (int s = 0; s < 10; s++) bd[s] = lds64(kt + (KT_C + 2 * g + 2 * t + 8 * s) * 4);
        mm4(x[0][0], 6);
        uint32_t e[4][4];
#pragma unroll
        for (int k = 1; k < 6; k++) {
#pragma unroll
            for (int j = 0; j < 4; j++) ld4(x[k & 1][j], 4 * k + 3 + j);
            ld_ug(k + 1);
            if (k == 3) {
#pragma unroll
                for (int s = 0; s < 8; s++) { b0[s] = lds32(KE + 32 * s); b1[s] = lds32(KE + 32 * s + 16); }
            }
            if (k > 1) ship(k);
#pragma unroll
            for (int j = 0; j < 4; j++) {
                mm4(x[k & 1][j], 4 * k + 3 + j);
                if (k == 3) { uint32_t v[4], z[4]; ld8(e[j], 8 + j); ld8(v, 12 + j); ld4(z, 30 - j); mm8(v, 12 + j, 12, 16); mm8(e[j], 8 + j, 8, 12); mm4(z, 30 - j); }
                if (k == 5) { ld8(e[j], 8 + j + p.zero); mm8(e[j], 8 + j, 12, 16); }
            }
        }
        ld_ug(7);
        ship(7 - R.value); ship(6 + R.value);
        };
        if (rank) stairs(std::integral_constant<int, 1>()); else stairs(std::integral_constant<int, 0>());
        if ((warp & 3) == 0) TSTAMP(14 + (warp >> 2)); else TSTAMP(21 + warp);
    }
}

constexpr int SF_WD = 73728;
constexpr int SF_RED = 49152;
constexpr int MU_HALF = 640, MU_STRIDE = 1344, SM_RAW = 98304, SM_UT = SM_RAW + 16384, SM_G = SM_UT + 16 * MU_STRIDE, SM_Y = 196608, SM_KT = 138880, SM_KW = SM_G - 49152;
constexpr int SF_XS = 221184;
constexpr int SF_MISC = SF_XS + 8 * 1168;
constexpr int SF_KG = SF_MISC - 10 * KG_STAGE;
constexpr int SF_WR = SF_KG - 2304;
constexpr int FB_X = 64, FB_KDONE = 72, FB_KEYS = 80, FB_FREE = 88  , FB_W = 104, FB_D = FB_W + 72, FB_MU = FB_D + 96, FB_MG = FB_MU + 8, FB_MT = FB_MU + 16  , FS_PART = 512, FS_TOK = 896, FS_BM = 1024;
enum { BAR_R = 7, BAR_GU = 8, BAR_RED = 9, BAR_R2 = 10, BAR_G = 12  , BAR_M = 15 };
static_assert(SF_KG % 128 == 0 && NPRE <= 8 && SM_KT + 4 * 2112 <= 147456 && SM_G + MU_STRIDE <= SF_WR - 4 * 9216 && SM_KW + 6 * 2112 >= SM_RAW && SM_KW + 12 * 2112 <= SM_UT, "layout");

__device__ __forceinline__ int mini_ch0(int f) { return 48 * f - (f < NW ? 1696 : 2304); }

__device__ __forceinline__ void ffn_front(const Params& p, const CUtensorMap* maps, uint32_t sb, int warp, int lane, int f, unsigned epoch) {
    const unsigned t0 = clock32();
    const int g = lane >> 2, t = lane & 3, mi = lane >> 3, r8 = lane & 7;
    const bool isx = f < NX;
    const int nrw = f < 52 ? 4 : 6, r0 = f < 52 ? 32 * f : 48 * f - 832;
    const int rw = warp < 12 ? 13 - warp : warp ^ (warp < 14 ? 10 : 15);
    const uint32_t bar_row = sb + SF_MISC  , bar_x = bar_row + FB_X;
    const uint32_t s_part = bar_row + FS_PART  , s_tok = bar_row + FS_TOK  ;
    const uint32_t rows = sb + SF_WR - 9216 * (rw + 1) - (rw & 4) * ((SF_WR - 6 * 9216) / 4);
    {
#pragma unroll 1
        for (int i = warp < 10 ? 30 : warp - 10; i < 30; i += 6) if (elect()) mbar_init(bar_x + 8 * i, i == 1 ? 4 + (f < NW) : i < 27 ? 1 : i == 27 ? 2 : 8);
        const uint32_t bytes = rw < 6 ? 9216 : 1152, dst = rw < 6 ? rows : sb + SF_WR + (rw & 1) * 1152;
        const __nv_bfloat16* src = rw < 6 ? p.u + (size_t)(r0 + 8 * rw) * DM : (rw & 1) ? p.gatew : p.wr;
        if (elect()) { mbar_init(bar_row + 8 * rw, 1); mbar_fence(); mbar_expect(bar_row + 8 * rw, bytes); }
        if (warp == 13) { sts32(s_part + 64 + lane * 4, 0); sts32(bar_row + FS_BM + lane * 4, 0); }
        bar_sync(0, NTHR);
        if (rw < nrw) until(t0, RDELAY);
        if (rw < nrw || rw >= 6) { if (elect()) bulk_g2s(dst, src, bytes, bar_row + 8 * rw); }
    }
    uint4* const kdst = p.s->keys + (lane >> 1) * 128 + 2 * f + (lane & 1);
    if (warp == 15) TSTAMP(1);

    if (warp == 12) {
        if (lane < 22) mbar_expect(bar_row + FB_W + 8 * lane, lane < 9 ? 24576 : isx ? 12288 : 16384);
        if (elect()) { prefetch_map(maps + 1); prefetch_map(maps + 2); prefetch_map(maps + (isx ? 3 : 5)); }
        unsigned tb = t0 + WDELAY;
        auto pieces = [&](int n, int end, uint32_t dst) {
#pragma unroll 1
            for (; n < end; n++, dst += 12288) {
                until(tb, 0); tb += WGAP;
                if (elect()) tma3d(dst, maps + 1 + (n & 1), 0, 64 * (n >> 1), 3 * f, bar_row + FB_W + 8 * (n >> 1));
            }
        };
        if (!isx) {
#pragma unroll 1
            for (int k = 0; k <= (f >= NW); k++) { until(t0, MDELAY + k * MGAP); if (elect()) tma4d(sb + SM_RAW - 49152 * k, maps + 5, mini_ch0(f) + 16 * k, 0, 0, 0, bar_row + FB_MU - 8 * k); }
            if (f >= NW) return;
        }
#pragma unroll 1
        for (int i = 0; i < 4; i++) {
            if (i == 1) { mbar_wait(bar_row + FB_KEYS); mbar_wait(bar_row + FB_KDONE); tb = clock32() + RESUME; }
            if (i == 3) mbar_wait(bar_row + FB_FREE);
            const int n = ((0x0c080000 + NPRE * 256) >> (8 * i)) & 255;
            pieces(n, ((0x120c0800 + NPRE) >> (8 * i)) & 255, sb + 12288 * (((0x000c0000 + NPRE * 256) >> (8 * i)) & 255));
        }
        TSTAMP(12);
        if (isx) {
#pragma unroll 1
            for (int i = 0; i < 12; i++) {
                const int n = (0x987610ba5432ull >> (4 * i)) & 15;
                if (i == 6) mbar_wait(bar_row + FB_FREE + 8);
                until(tb, 0); tb += DGAP;
                if (elect()) tma2d(sb + SF_WD + n * 12288, maps + 3, 32 * (f >> 1), 2304 * (f & 1) + 192 * n, bar_row + FB_D + 8 * n);
            }
            TSTAMP(13);
        }
    } else if (warp == 13) {
        const uint32_t tag = key_tag(epoch), par = (epoch & 1) ? 0u : 0x8000u;
        stg128(kdst, 0, 0, 0, 0);
        if (lane < 8 && isx && !(f & 1)) st_rlx32(&p.s->sel[32 * f + lane], 0);
        bar_sync(BAR_R, 32 * (nrw + 1));
        TSTAMP(3);
        {
            const uint32_t sg = fresh(s_part) + 192 + lane * 4;
            const uint32_t gb = pack_bf16(sigmoidf_(rbf(__uint_as_float(lds32(sg)))), sigmoidf_(rbf(__uint_as_float(lds32(sg + 128))))) | par | (par << 16);
            asm volatile("st.relaxed.gpu.global.u16 [%0], %1;" :: "l"(p.s->gate + r0 + lane), "h"((unsigned short)gb) : "memory");
            if (nrw > 4 && lane < 16) asm volatile("st.relaxed.gpu.global.u16 [%0], %1;" :: "l"(p.s->gate + r0 + 32 + lane), "h"((unsigned short)(gb >> 16)) : "memory");
        }
        bar_sync(BAR_R2, 32 * (nrw + 1));
        {
            const uint4 v = lds128(fresh(s_tok) + (lane & 1) * 16);
            asm volatile("st.relaxed.gpu.global.v4.u32 [%0], {%1,%2,%3,%4};" :: "l"(kdst), "r"(v.x | tag), "r"(v.y | tag), "r"(v.z | tag), "r"(v.w | tag) : "memory");
        }
        TSTAMP(4);
        if (lane == 0) { mbar_arrive(bar_row + FB_KEYS); mbar_expect(bar_x, 8 * 1152); }
        if (f >= NW) return;
        mbar_wait(bar_row + FB_KDONE);
        uint32_t k[16];
        const uint4* src = p.s->keys + (f & 15) * 128 + lane;
#pragma unroll 1
        for (int it = 0;; it++) {
            uint32_t bad = 0;
#pragma unroll
            for (int i = 0; i < 4; i++) {
                const uint4 x = ld_rlx128(src + (i < 3 || lane < 24 ? 32 * i : 64));
                k[i] = x.x; k[4 + i] = x.y; k[8 + i] = x.z; k[12 + i] = x.w;
                bad |= x.x ^ tag;
            }
            const bool ok = __all_sync(0xffffffffu, (bad & 0xf800u) == 0);
            if (ok) break;
            if (it > (1 << 20)) give_up();
        }
        TSTAMP(5);
        uint32_t key = 0, m = __reduce_max_sync(0xffffffffu, max(max(k[0], k[1]), max(k[2], k[3])));
#pragma unroll 2
        for (int r = 0; r < 8; r++) {
            bool pop[4];
#pragma unroll
            for (int i = 0; i < 4; i++) { pop[i] = k[i] == m; k[i] = pop[i] ? k[4 + i] : k[i]; }
            const uint32_t mn = __reduce_max_sync(0xffffffffu, max(max(k[0], k[1]), max(k[2], k[3])));
            if (elect()) bulk_g2s(sb + SF_XS + r * 1168, p.u + (size_t)key_row(m) * DM, 1152, bar_x);
#pragma unroll
            for (int i = 0; i < 4; i++) { k[4 + i] = pop[i] ? k[8 + i] : k[4 + i]; k[8 + i] = pop[i] ? k[12 + i] : k[8 + i]; k[12 + i] = pop[i] ? 0 : k[12 + i]; }
            if (r8 == r) key = m;
            m = mn;
        }
        const int row = key_row(key);
        sts32(s_tok + r8 * 8, row);
        TSTAMP(6);
        if (isx) {
            if (!(f & 1)) {
                __nv_bfloat16* o = p.out + (size_t)row * DM + 16 * f + 8 * mi;
                asm volatile("st.relaxed.gpu.global.v4.u32 [%0], {%1,%1,%1,%1};" :: "l"(o), "r"(0) : "memory");
                if (__any_sync(0xffffffffu, ld_rlx32(o) != 0)) give_up();
                if (lane < 8) st_rlx32(&p.s->sel[32 * f + lane], key);
            } else wait_sel(p, f >> 1, r8, tag);
            uint32_t gb;
#pragma unroll 1
            for (int it = 0;; it++) {
                asm volatile("ld.relaxed.gpu.global.u16 %0, [%1];" : "=r"(gb) : "l"(p.s->gate + row) : "memory");
                gb ^= par;
                if (!(gb & 0x8000u)) break;
                if (it > (1 << 20)) give_up();
            }
            const uint32_t rb = key ^ 0x80000000u, rv = (rb ^ (((int)rb >> 31) & 0x7fff0000u)) & 0xffff0000u;
            sts32(s_tok + r8 * 8 + 4, __float_as_uint(rbf(1.0f - bf_lo(gb)) * rbf(sigmoidf_(__uint_as_float(rv)))));
            __syncwarp();
            TSTAMP(7);
            bar_arrive(BAR_RED, 416);
        }
    } else {
        if (rw < nrw) {
            float c[3][4];
#pragma unroll
            for (int i = 0; i < 3; i++) { c[i][0] = c[i][1] = c[i][2] = c[i][3] = 0.f; }
            mbar_wait(bar_row + 48); mbar_wait(bar_row + 56);
            const uint32_t b = fresh(sb + SF_WR) + (g & 1) * 1152 + (g >> 2) * 64 + t * 16 + (g & 2) * 2;
            uint32_t w[18][2];
#pragma unroll
            for (int kb = 0; kb < 18; kb++) { const uint32_t o = ((kb & 1) ? b ^ 64 : b) + 128 * (kb >> 1); w[kb][0] = lds32(o); w[kb][1] = lds32(o + 8); }
            mbar_wait(bar_row + 8 * rw);
            if (warp == 15) TSTAMP(2);
            const uint32_t a = fresh(rows) + g * 1152 + (g & 1) * 64 + t * 16;
#pragma unroll
            for (int kb = 0; kb < 18; kb++) {
                const uint4 x = lds128(((kb & 1) ? a ^ 64 : a) + 128 * (kb >> 1));
                mma_bf(c[kb % 3], x.x, x.y, x.z, x.w, w[kb][0], w[kb][1]);
            }
            const float sr = c[0][0] + c[1][0] + c[2][0] + __shfl_down_sync(0xffffffffu, c[0][2] + c[1][2] + c[2][2], 1);
            const float sg = c[0][1] + c[1][1] + c[2][1] + __shfl_down_sync(0xffffffffu, c[0][3] + c[1][3] + c[2][3], 1);
            const uint32_t rb = pack_bf16(0.f, sr);
            if (t == 2 * (g & 1)) {
                sts32(s_part + (8 * rw + g) * 4, (rb ^ (((int)rb >> 31) & 0x7fff0000u) ^ 0x80000000u) | (uint32_t)(2047 - r0 - 8 * rw - g));
                sts32(s_part + 192 + (8 * rw + g) * 4, __float_as_uint(sg));
            }
            __syncwarp();
            bar_sync(BAR_R, 32 * (nrw + 1));
            const uint32_t sk = fresh(s_part), kk = lds32(sk + (8 * rw + r8) * 4);
            int n = 0;
#pragma unroll
            for (int i = 0; i < 3; i++) { const uint4 v = lds128(sk + mi * 48 + 16 * i); n += (v.x > kk) + (v.y > kk) + (v.z > kk) + (v.w > kk); }
            n += __shfl_xor_sync(0xffffffffu, n, 8); n += __shfl_xor_sync(0xffffffffu, n, 16);
            if (n < 8) sts32(s_tok + 4 * n, kk);
            __syncwarp();
            bar_arrive(BAR_R2, 32 * (nrw + 1));
        }
    }
}

__device__ __forceinline__ void ffn_work(const Params& p, uint32_t sb, int warp, int lane, int f, unsigned epoch) {
    const int g = lane >> 2, t = lane & 3, mi = lane >> 3, r8 = lane & 7;
    const bool isx = f < NX;
    const uint32_t bar_x = sb + SF_MISC + FB_X, bar_free = sb + SF_MISC + FB_FREE, bar_w = sb + SF_MISC + FB_W, bar_d = sb + SF_MISC + FB_D, s_tok = sb + SF_MISC + FS_TOK;
    uint32_t fr[24][4];
    auto pin = [&] {
#pragma unroll
        for (int i = 0; i < 24; i += 8) asm volatile("" :: "r"(fr[i][0]), "r"(fr[i + 1][0]), "r"(fr[i + 2][0]), "r"(fr[i + 3][0]), "r"(fr[i + 4][0]), "r"(fr[i + 5][0]), "r"(fr[i + 6][0]), "r"(fr[i + 7][0]) : "memory");
    };
    {
        const int j = (unsigned)(warp - 4) < 6, w = warp - (j ? 4 : warp < 4 ? 0 : 6);
        float ag[2][4], au[2][4];
#pragma unroll
        for (int i = 0; i < 2; i++) { ag[i][0] = ag[i][1] = ag[i][2] = ag[i][3] = 0.f; au[i][0] = au[i][1] = au[i][2] = au[i][3] = 0.f; }
        const uint32_t wb = sb + (w >> 1) * 4096 + (r8 + 8 * (mi >> 1)) * 64 + (((2 * (w & 1) + (mi & 1)) ^ (r8 >> 1)) << 4);
        const uint32_t xb = sb + SF_XS + r8 * 1168 + mi * 16;
        auto load = [&](int i, int n, int place) {
            mbar_wait(bar_w + 8 * n);
            const uint32_t wk = fresh(wb) + place * 24576;
#pragma unroll
            for (int s = 0; s < 4; s++) { ldsm4t(fr[8 * i + s], wk + 1024 * s); ldsm4t(fr[8 * i + 4 + s], wk + 1024 * s + 12288); }
        };
        auto mul = [&](int i, uint32_t xk) {
            uint32_t x[2][4];
            ldsm4(x[0], xk); ldsm4(x[1], xk + 64);
#pragma unroll
            for (int s = 0; s < 4; s++) {
                const uint32_t (&a)[4] = fr[8 * i + s], (&b)[4] = fr[8 * i + 4 + s];
                mma_bf(ag[s & 1], a[0], a[1], a[2], a[3], x[s >> 1][2 * (s & 1)], x[s >> 1][2 * (s & 1) + 1]);
                mma_bf(au[s & 1], b[0], b[1], b[2], b[3], x[s >> 1][2 * (s & 1)], x[s >> 1][2 * (s & 1) + 1]);
            }
        };
#pragma unroll
        for (int i = 0; i < 3; i++) load(i, 3 * j + i, (i ? 5 : 3) * j + i);
        pin();
        bar_sync(BAR_G + j, 192);
        if (w == 0 && lane == 0) mbar_arrive(bar_free + 8 * j);
        mbar_wait(bar_x);
        if (warp == 0) TSTAMP(8);
        {
            const uint32_t xk = fresh(xb) + 384 * j;
#pragma unroll
            for (int i = 0; i < 3; i++) { mul(i, (i ? fresh(xk) : xk) + 128 * i); if (i == 0) { asm volatile("" :: "f"(ag[0][0]), "f"(ag[1][0]), "f"(au[0][0]), "f"(au[1][0])); sts32(s_tok + 64, clock32()); } }
        }
#pragma unroll 1
        for (int n = 6 + j; n < 9; n += 2) { load(0, n, n - 6); mul(0, fresh(xb) + 128 * n); }
#pragma unroll
        for (int c = 0; c < 4; c++) { ag[0][c] += ag[1][c]; au[0][c] += au[1][c]; }
        if (j) {
            sts128(wb + 24576, __float_as_uint(ag[0][0]), __float_as_uint(ag[0][1]), __float_as_uint(ag[0][2]), __float_as_uint(ag[0][3]));
            sts128(wb + 25600, __float_as_uint(au[0][0]), __float_as_uint(au[0][1]), __float_as_uint(au[0][2]), __float_as_uint(au[0][3]));
        }
        bar_sync(BAR_GU, 384);
        if (!j) {
            const uint32_t sf = fresh(wb);
            const uint4 g1 = lds128(sf + 24576), u1 = lds128(sf + 25600);
            const uint32_t gs[4] = {g1.x, g1.y, g1.z, g1.w}, us[4] = {u1.x, u1.y, u1.z, u1.w};
            if (warp == 0) TSTAMP(9);
            float h[4];
#pragma unroll
            for (int c = 0; c < 4; c++) {
                const float gv = rbf(ag[0][c] + __uint_as_float(gs[c]));
                h[c] = rbf(gv * sigmoidf_(gv)) * rbf(au[0][c] + __uint_as_float(us[c]));
            }
            uint32_t h0, h1;
            asm("movmatrix.sync.aligned.m8n8.trans.b16 %0, %1;" : "=r"(h0) : "r"(pack_bf16(h[0], h[1])));
            asm("movmatrix.sync.aligned.m8n8.trans.b16 %0, %1;" : "=r"(h1) : "r"(pack_bf16(h[2], h[3])));
            if (h0 == 0) h0 = 0x8000u;
            asm volatile("{ .reg .b64 v; mov.b64 v, {%1, %2}; st.relaxed.gpu.global.b64 [%0], v; }" :: "l"(p.s->h + ((epoch & 1) * 288 + 6 * f + w) * 32 + lane), "r"(h0), "r"(h1) : "memory");
        }
        if (isx) {
            if (warp == 0) TSTAMP(10);
            const uint2* hsrc = p.s->h + ((epoch & 1) * 288 + 144 * (f & 1) + 12 * warp) * 32 + lane;
            uint2 hb[12];
            auto ldh = [&](int s) { asm volatile("ld.relaxed.gpu.global.v2.u32 {%0, %1}, [%2];" : "=r"(hb[s].x), "=r"(hb[s].y) : "l"(hsrc + 32 * s) : "memory"); };
#pragma unroll
            for (int s = 0; s < 12; s++) ldh(s);
#pragma unroll 1
            for (int it = 0;; it++) {
                bool again = false;
#pragma unroll
                for (int s = 0; s < 12; s += 2) if (__any_sync(0xffffffffu, min(hb[s].x, hb[s + 1].x) == 0)) { ldh(s); ldh(s + 1); again = true; }
                if (!again) break;
                if (it > (1 << 16)) give_up();
            }
            if (warp == 0) TSTAMP(11);
            mbar_wait(bar_d + 8 * warp);
            if (warp == 9) TSTAMP(14);
            float ad[2][2][4];
#pragma unroll
            for (int i = 0; i < 4; i++) { ad[i >> 1][i & 1][0] = ad[i >> 1][i & 1][1] = ad[i >> 1][i & 1][2] = ad[i >> 1][i & 1][3] = 0.f; }
            const uint32_t wd = fresh(sb) + SF_WD + warp * 12288 + (r8 + 8 * (mi >> 1)) * 64 + (((mi & 1) ^ (r8 >> 1)) << 4);
#pragma unroll
            for (int s = 0; s < 12; s++) {
                uint32_t a[4], b[4];
                ldsm4t(a, wd + 1024 * s); ldsm4t(b, (wd ^ 32) + 1024 * s);
                mma_bf(ad[0][s & 1], a[0], a[1], a[2], a[3], hb[s].x, hb[s].y);
                mma_bf(ad[1][s & 1], b[0], b[1], b[2], b[3], hb[s].x, hb[s].y);
            }
            const uint32_t rd = sb + SF_RED + warp * 1152 + (72 * t + g) * 4;
#pragma unroll
            for (int i = 0; i < 8; i++) sts32(rd + (i >> 2) * 64 + (i & 1) * 144 + ((i >> 1) & 1) * 32, __float_as_uint(ad[i >> 2][0][i & 3] + ad[i >> 2][1][i & 3]));
            bar_sync(BAR_RED, 416);
            if (warp < 4) {
                const int tid = 32 * warp + lane;
                const uint32_t rs = fresh(sb + SF_RED) + (tid >> 4) * 144 + (tid & 15) * 8;
                const uint2 tk = lds64(fresh(s_tok) + (tid >> 4) * 8);
                float x = 0.f, y = 0.f;
#pragma unroll
                for (int w = 0; w < 12; w++) { const uint2 v = lds64(rs + w * 1152); x += __uint_as_float(v.x); y += __uint_as_float(v.y); }
                asm volatile("red.relaxed.gpu.global.add.noftz.bf16x2 [%0], %1;" :: "l"(p.out + (size_t)tk.x * DM + 32 * (f >> 1) + 2 * (tid & 15)),
                             "r"(pack_bf16(x * __uint_as_float(tk.y), y * __uint_as_float(tk.y))) : "memory");
            }
            if (warp == 0) { TSTAMP(15); TFLUSH(); }
            asm volatile("exit;"); __builtin_unreachable();
        }
    }
}

__device__ __forceinline__ void fetch_k(const uint4* src, uint64_t (&v)[6], uint32_t a, uint32_t b) {
    asm volatile("{ .reg .pred p; setp.eq.u32 p, %7, %8; @p ld.relaxed.gpu.global.v2.u64 {%0,%1}, [%6]; @p ld.relaxed.gpu.global.v2.u64 {%2,%3}, [%6 + 512]; @p ld.relaxed.gpu.global.v2.u64 {%4,%5}, [%6 + 1024]; }"
                 : "+l"(v[0]), "+l"(v[1]), "+l"(v[2]), "+l"(v[3]), "+l"(v[4]), "+l"(v[5]) : "l"(src), "r"(a), "r"(b));
}
__device__ __forceinline__ uint32_t mini_conv(const Params& p, uint32_t sb, int warp, int lane, int f, unsigned epoch, uint64_t (&v)[6]) {
    const int g = lane >> 2, t = lane & 3, mi = lane >> 3, r8 = lane & 7;
    const uint32_t fb = sb + SF_MISC, kt = sb + (warp >= 12 ? SM_KT - 12 * 2112 : f < NW ? SM_KW + 2 * 2112 : SM_KW) + warp * 2112;
    const bool ism = f >= NW;
    const int ch0 = mini_ch0(f);
    uint32_t seq = 128, key;
    const uint4* src = p.s->kp + lane;
    auto hi = [&](int i) { return (uint32_t)(v[i] >> 32); };
    if (f >= (warp < 4 ? NW : NX)) {
    {
        const uint32_t c = 36 + (warp & 3) + 2 * (warp & 12), y = (uint32_t)((warp < 8 ? 0xa026802400000000ull : 0x2a2e00280080a22cull) >> ((8 * warp) & 48)) & 0xffff;
        seq = ism ? 0x101 * c - 0x400 : y + (warp & 1) * ((y >> 5) & 0x101);
        src += (ch0 + (seq & 31)) * 96;
    }
    if (seq & 32) {
        if (seq & 4) {
            const int q = (seq & 3) + ((seq >> 1) & 4);
            const uint32_t ab = sb - 3072 * (seq & 16), d = ab + SM_UT + g * MU_STRIDE + (8 + 4 * q + t) * 16;
            sts128(ab + SM_UT + (2 * q + (mi >> 1)) * MU_STRIDE + (mi & 1) * MU_HALF + r8 * 16, 0, 0, 0, 0);
            mbar_wait(fb + FB_MU - (seq & 16) / 2);
            if (warp == 15) TSTAMP(16);
            const uint32_t a = fresh(ab + SM_RAW) + q * 2048 + (8 * mi + 4 * (r8 & 1) + (r8 >> 1)) * 32 + ((r8 & 1) << 4);
            uint32_t x[4][4];
#pragma unroll
            for (int i = 0; i < 4; i++) ldsm4t(x[i], (i & 2 ? a ^ 16 : a) + 1024 * (i & 1));
#pragma unroll
            for (int i = 0; i < 4; i++) sts128(d + (i & 1) * MU_HALF + (i & 2) * 4 * MU_STRIDE, x[i][0], x[i][1], x[i][2], x[i][3]);
            __syncwarp();
            if (lane == 0) mbar_arrive(fb + FB_MT + (seq & 16) / 2);
        }
        mbar_wait(fb + FB_KDONE);
        fetch_k(src, v, warp < 4, 0);
        if ((warp | 2) == 7) { fetch_gates(p, (warp >> 1) & 1, lane, epoch, sb + SM_G + (lane & 1) * MU_HALF); __syncwarp(); if (lane == 0) mbar_arrive(fb + FB_MG); }
        if (warp >= 8) { mbar_wait(fb + FB_KEYS); mbar_wait(fb + FB_MT); }
        if (warp == TW) TSTAMP(17);
    }
    }
    const uint32_t lo = (mi & 1) * MU_HALF + (8 + r8) * 16 + (mi >> 1) * 128;
#pragma unroll 1
    do {
        const int c = seq & 31;
        if (seq & 32) {
#pragma unroll 1
        for (int it = 0; !__all_sync(0xffffffffu, ((hi(1) ^ k_tag(epoch)) | (hi(3) ^ k_tag(epoch)) | (hi(5) ^ k_tag(epoch)) | ((uint32_t)v[5] & p.zero)) < 65536); it++) {
            fetch_k(src, v, 0, 0);
            if (it > (1 << 20)) give_up();
        }
        mbar_wait(fb + FB_MT + (seq & 16) / 2);
        sts128(kt + t * 16, 0, 0, 0, 0);
        if (warp == TW) TSTAMP(seq >> 8 ? 7 : 10);
        const uint32_t w[12] = {(uint32_t)v[0], hi(0), (uint32_t)v[1], (uint32_t)v[2], hi(2), (uint32_t)v[3], (uint32_t)v[4], hi(4), 0, 0, 0, 0};
        k_tables<false>(fresh(kt), fresh(lane), w);
        }
        __syncwarp();
        if (seq & 128) ffn_work(p, sb, warp, fresh(lane), f, epoch);
        if (!(seq & 32)) return 0;
        const uint32_t ab = sb - 49152 * (c >> 4), kb = fresh(kt) + (16 + g - 2 * t) * 4, ub = fresh(ab + SM_UT + (c & 15) * MU_STRIDE) + lo;
        const uint32_t yd = ab + SM_Y + (c & 15) * 1056 + (c & 8) * 8 + lane * 16;
        uint32_t kp = kb, u1 = ub;
        if (warp == TW && !(seq >> 8)) TSTAMP(13);
        seq >>= 8;
        src += ((int)(seq & 31) - c) * 96;
#pragma unroll
        for (int i = 0; i < 6; i++) v[i] = 0;
        key = 0;
        float acc[6][4];
#pragma unroll
        for (int i = 0; i < 6; i++) { acc[i][0] = acc[i][1] = acc[i][2] = acc[i][3] = 0.f; }
        uint32_t a[4][4], b[2][2][4];
        auto lda = [&](int j, int o) { const uint32_t x = kp + 64 * o + 512 * j; a[j][2] = o ? a[j][1] ^ p.zero : lds32((kp ^ p.zero) + 512 * j - 32); a[j][0] = lds32(x); a[j][1] = lds32(x + 32); a[j][3] = a[j][0] ^ p.zero; };
        auto ldb = [&](int s, int o) { ldsm4(b[s][0], u1 - 16 * o); ldsm4(b[s][1], u1 + 256 - 16 * o); };
        ldb(0, 0);
#pragma unroll
        for (int j = 0; j < 4; j++) lda(j, 0);
#pragma unroll
        for (int s = 0; s < 8; s++) {
            if (s == 4) {
                const uint32_t e = seq | (__float_as_uint(acc[0][0]) & p.zero);
                fetch_k(src, v, e & 32, 32);
                asm volatile("{ .reg .pred p; setp.eq.u32 p, %2, 0; @p ld.relaxed.gpu.global.u32 %0, [%1]; }" : "+r"(key) : "l"(&p.s->sel[((ch0 + c) >> 5) * 64 + r8]), "r"(e));
            }
            if (s < 7) ldb(~s & 1, s + 1);
#pragma unroll
            for (int i = 0; i < 4; i++) {
                const int j = (i >> 1) + 2 * (i & 1);
#pragma unroll
                for (int mu = 3 - j; mu >= 0; mu--) mma_bf(acc[j + mu + (j & 2)], a[j][0], a[j][1], a[j][2], a[j][3], b[s & 1][mu >> 1][2 * (mu & 1)], b[s & 1][mu >> 1][2 * (mu & 1) + 1]);
                if (s < 7) lda(j, s + 1);
            }
        }
        if (warp == TW && !seq) TSTAMP(14);
        mbar_wait(fb + FB_MG);
#pragma unroll
        for (int e = 0; e < 4; e++) { acc[2][e] += acc[4][e]; acc[3][e] += acc[5][e]; }
        uint32_t ug[4][4];
#pragma unroll
        for (int i = 0; i < 2; i++) { ldsm4t(ug[i], ub + 256 * i); ldsm4t(ug[2 + i], fresh(sb + SM_G) + lo + 256 * i); }
#pragma unroll
        for (int i = 0; i < 2; i++) {
            const uint32_t (&u)[4] = ug[i], (&gg)[4] = ug[2 + i];
            sts128(yd + 512 * i, gmix(gg[0], acc[2 * i][0], acc[2 * i][1], u[0]), gmix(gg[1], acc[2 * i][2], acc[2 * i][3], u[1]),
                   gmix(gg[2], acc[2 * i + 1][0], acc[2 * i + 1][1], u[2]), gmix(gg[3], acc[2 * i + 1][2], acc[2 * i + 1][3], u[3]));
        }
        __syncwarp();
        if (warp == TW) TSTAMP(18 + (seq != 0));
    } while (seq);
    if (warp >= 12) TSTAMP(12 + warp);
    return key;
}
__device__ __forceinline__ void mini_out(const Params& p, const CUtensorMap* maps, uint32_t sb, int warp, int lane, int f, unsigned epoch, uint32_t key) {
    const int g = lane >> 2, t = lane & 3, mi = lane >> 3, r8 = lane & 7;
    const uint32_t fb = sb + SF_MISC;
    const bool ism = f >= NW;
    const int ch0 = mini_ch0(f);
    const int k = ism ? warp >> 3 : 0;
    uint32_t first = 1;
    if (lane == 0) asm volatile("atom.shared.exch.b32 %0, [%1], 1;" : "=r"(first) : "r"(fb + FS_BM + 64 + 4 * k) : "memory");
    if (!__all_sync(0xffffffffu, first)) {
        if (elect()) prefetch_map(maps + 4);
        const int row = key_row(wait_sel(p, (ch0 + 16 * k) >> 5, r8, key_tag(epoch), key));
        if (row < 512) asm volatile("red.shared.or.b32 [%0], %1;" :: "r"(fb + FS_BM + (row >> 5) * 4), "r"(1u << (row & 31)) : "memory");
    }
    const int m = warp & 7, dr = 128 * (g >> 2) + 32 * (t >> 1) + 16 * (g & 1) + 8 * ((g >> 1) & 1);
    const uint32_t y = SM_Y + ((r8 >> 1) & 1) * 8512 + (2 * mi + (r8 & 1)) * 1056 + (2 * m + (r8 >> 2)) * 16;
    const uint32_t so = (g >> 1) * 256 + (t >> 1) * 64 + (g & 1) * 32 + (t & 1) * 16;
    bar_sync(BAR_M - k, ism ? 256 : NTHR);
#pragma unroll 1
    for (int h = ism ? 0 : warp >> 3;; h++) {
        const int r0 = 256 * h + 64 * (m & 1) + (m >> 1), row = r0 + dr;
        const uint32_t bm = lds32(fresh(fb) + FS_BM + (row >> 5) * 4) >> (row & 31), ab = fresh(sb - 49152 * k + 512 * h), stg = ab + SM_UT + 2048 * m + 512 * h;
        uint32_t x[2][4];
        ldsm4t(x[0], ab + y); ldsm4t(x[1], ab + y + 256);
        if (warp == 0 && x[0][0] != 0x12345) TSTAMP(28);
        if (__any_sync(0xffffffffu, bm & 0x11u)) {
#pragma unroll
            for (int i = 0; i < 2; i++) store_or_add(p.out + (size_t)(row + 4 * i) * DM + ch0 + 16 * k + 8 * (t & 1), x[i], bm & (1u << (4 * i)));
        } else {
#pragma unroll
            for (int i = 0; i < 2; i++) sts128(stg + so + 128 * i, x[i][0], x[i][1], x[i][2], x[i][3]);
            asm volatile("fence.proxy.async.shared::cta;" ::: "memory");
            __syncwarp();
            if (elect()) store_rows(maps + 4, stg, ch0 + 16 * k, r0);
        }
        if (h >= ism) break;
    }
    if (elect()) { asm volatile("cp.async.bulk.commit_group;" ::: "memory"); asm volatile("cp.async.bulk.wait_group.read 0;" ::: "memory"); }
    if (warp == 8) TSTAMP(11);
    if (warp == 0) { TSTAMP(15); TFLUSH(); }
}

constexpr int SMEM_BYTES = 232448;
static_assert(SF_MISC + 1152 <= 232192, "layout");

struct Maps { CUtensorMap m[6]; };

__global__ void __cluster_dims__(2, 1, 1) __launch_bounds__(NTHR, 1)
fused_kernel(const Params p, const __grid_constant__ Maps maps) {
    extern __shared__ __align__(1024) uint8_t smem_raw[];
    uint32_t q[8];
    {
        const int b = blockIdx.x - NCONV, x = threadIdx.x, rc = 5 * b + (b & ~3) + 4 + (x >> 6);
        const int cv = (unsigned)b < NW ? 0 : -1, ca = (b < 0 ? 8 * b + DM : 48 * b - 2300) + ((x >> 5) & 3), cb = 2 * rc - (rc & 3) + 4;
        const uint32_t ch = (ca & cv) | (cb & ~cv), o = NST * ch + 2 * ((x & 31) + ((x >> (cv & 2)) & 32));
        const bool c = x < (cv ? 256 : 320);
        q[6] = ldg16_if(c, p.logdt + ch);
        q[2] = ldg32_if(c, p.Bre + o); q[3] = ldg32_if(c, p.Bim + o); q[4] = ldg32_if(c, p.Cre + o); q[5] = ldg32_if(c, p.Cim + o); q[0] = ldg32_if(c, p.Are + o); q[1] = ldg32_if(c, p.Aim + o);
        q[7] = ldg16_if(c, p.Dskip + ch);
    }
    const unsigned epoch = ld_rlx32(&p.s->epoch[blockIdx.x * 16 + (threadIdx.x >> 5)]);
    const uint32_t sb = __shfl_sync(0xffffffffu, smem_u32(smem_raw), 0);
    const int warp = __shfl_sync(0xffffffffu, threadIdx.x >> 5, 0), bid = __shfl_sync(0xffffffffu, blockIdx.x, 0);
    const int lane = __shfl_sync(0xffffffffu, threadIdx.x & 31, threadIdx.x);
    const bool conv = bid < NCONV;
    const int f = bid - NCONV;
    uint32_t w[12];
    uint64_t v[6];
    const bool four = (unsigned)f >= NW;
    if (warp < (four ? 8 : 10)) {
        const int half = four ? warp >> 2 : warp & 1, pr = four ? warp & 3 : warp >> 1;
        const int rc = 5 * f + (f & ~3) + 4 + pr;
        const uint32_t stage = sb + (conv ? SC_KG : SF_KG) + warp * KG_STAGE;
        uint4* const kp = p.s->kp + (four ? (conv ? 8 * bid : 48 * f - 2300) + pr : 2 * rc - (rc & 3) + 4) * 96 + lane;
        kgen(q, sb, half, stage, stage + (four ? 4 : 1) * KG_STAGE, 1 + pr, lane, w, [&] {
            sts128z_if(conv && lane < 20, sb + SC_KT + warp * KT_BYTES + lane * 16 + (lane < 4 ? 0 : lane < 14 ? 2048 : 2288));
            stg128z_if(!conv, kp + 64 * half); stg128z_if(!half && !conv, kp + 32);
            stg128z_if((unsigned)f < NW && warp < 6, (uint4*)(p.s->h + ((lane >> 4) * 288 + 6 * f + warp) * 32) + (lane & 15));
            if (conv) asm volatile("barrier.cluster.arrive.relaxed.aligned;" ::: "memory"); else bar_sync(0, NTHR);
        });
        if (!half) publish_k(kp, w, epoch, v);
        else for (int i = 0; i < 6; i++) v[i] = 0;
        if (conv) { conv_main(p, sb, warp, lane, bid, epoch, w); return; }
        {
            if (!half && lane == 0) mbar_arrive(sb + SF_MISC + FB_KDONE);
            if (warp == 0) TSTAMP(22);
            if (warp == 2) TSTAMP(23);
        }
    } else if (conv) {
        conv_aux(p, maps.m, sb, warp - 8, lane, bid, epoch);
        return;
    } else {
        ffn_front(p, maps.m, sb, warp, lane, f, epoch);
        for (int i = 0; i < 6; i++) v[i] = 0;
    }
    converged();
    next_epoch(p, epoch);
    if (warp >= 12 && f < NX) return;
    mini_out(p, maps.m, sb, warp, lane, f, epoch, mini_conv(p, sb, warp, __shfl_sync(0xffffffffu, lane, lane), f, epoch, v));
}

typedef CUresult (*EncodeFn)(CUtensorMap*, CUtensorMapDataType, cuuint32_t, void*, const cuuint64_t*, const cuuint64_t*, const cuuint32_t*, const cuuint32_t*,
                             CUtensorMapInterleave, CUtensorMapSwizzle, CUtensorMapL2promotion, CUtensorMapFloatOOBfill);

void make_map(EncodeFn fn, CUtensorMap* m, const void* base, int rank, const cuuint64_t* dims, const cuuint64_t* strides, const cuuint32_t* box, CUtensorMapSwizzle sw) {
    const cuuint32_t es[5] = {1, 1, 1, 1, 1};
    fn(m, CU_TENSOR_MAP_DATA_TYPE_BFLOAT16, rank, (void*)base, dims, strides, box, es, CU_TENSOR_MAP_INTERLEAVE_NONE, sw,
       CU_TENSOR_MAP_L2_PROMOTION_NONE, CU_TENSOR_MAP_FLOAT_OOB_FILL_NONE);
}

}

extern "C" void kernel_launch(void* const* d_in, const int* in_sizes, int n_in, void* d_out, int out_size) {
    (void)in_sizes; (void)n_in; (void)out_size;
    static EncodeFn fn = nullptr;
    static void* scratch = nullptr;
    if (!fn) {
        void* ptr = nullptr; cudaDriverEntryPointQueryResult qr;
        cudaGetDriverEntryPoint("cuTensorMapEncodeTiled", &ptr, cudaEnableDefault, &qr);
        fn = (EncodeFn)ptr;
        cudaGetSymbolAddress(&scratch, g_scratch);
        cudaFuncSetAttribute(fused_kernel, cudaFuncAttributeMaxDynamicSharedMemorySize, SMEM_BYTES);
    }
    typedef const __nv_bfloat16* bp;
    Params p;
    p.u = (bp)d_in[0]; p.Are = (bp)d_in[1]; p.Aim = (bp)d_in[2]; p.Bre = (bp)d_in[3]; p.Bim = (bp)d_in[4]; p.Cre = (bp)d_in[5]; p.Cim = (bp)d_in[6];
    p.logdt = (bp)d_in[7]; p.Dskip = (bp)d_in[8]; p.wr = (bp)d_in[10]; p.gatew = (bp)d_in[14];
    p.out = (__nv_bfloat16*)d_out; p.s = (Scratch*)scratch; p.zero = 0;
    Maps maps;
    {
        const cuuint64_t dims[4] = {DM, 4, 16, 32}, strides[3] = {16 * DM * 2, DM * 2, 64 * DM * 2};
        const cuuint32_t box[4] = {16, 4, 16, 2};
        make_map(fn, &maps.m[0], d_in[0], 4, dims, strides, box, CU_TENSOR_MAP_SWIZZLE_32B);
        const cuuint32_t box2[4] = {16, 4, 16, 8};
        make_map(fn, &maps.m[5], d_in[0], 4, dims, strides, box2, CU_TENSOR_MAP_SWIZZLE_32B);
    }
    for (int i = 0; i < 2; i++) {
        const cuuint64_t dims[3] = {32, DM, FF / 32}, strides[2] = {FF * 2, 64};
        const cuuint32_t box[3] = {32, 64, 3};
        make_map(fn, &maps.m[1 + i], d_in[11 + i], 3, dims, strides, box, CU_TENSOR_MAP_SWIZZLE_64B);
    }
    {
        const cuuint64_t dims[2] = {DM, FF}, strides[1] = {DM * 2};
        const cuuint32_t box[2] = {32, 192};
        make_map(fn, &maps.m[3], d_in[13], 2, dims, strides, box, CU_TENSOR_MAP_SWIZZLE_64B);
    }
    {
        const cuuint64_t dims[5] = {DM, 4, 4, 2, L_SEQ}, strides[4] = {16 * DM * 2, 4 * DM * 2, 128 * DM * 2, DM * 2};
        const cuuint32_t box[5] = {16, 4, 4, 2, 1};
        make_map(fn, &maps.m[4], d_out, 5, dims, strides, box, CU_TENSOR_MAP_SWIZZLE_NONE);
    }
    fused_kernel<<<NCTA, NTHR, SMEM_BYTES>>>(p, maps);
}
```

```cpp
#include <cuda_runtime.h>
#include <cuda_bf16.h>
#include <cuda_fp16.h>
#include <cuda.h>
#include <stdint.h>
#include <type_traits>

#define RESUME 300
#define MDELAY 2000
#define MGAP 0
#define USKEW 4
#define RDELAY 900
#define WDELAY 2000
#define WGAP 290
#define NPRE 7
#define DGAP 260
namespace {

constexpr int DM = 576, NST = 128, FF = 4608, L_SEQ = 2048;
constexpr int NCONV = 72, NX = 36, NW = 48, NCTA = 132, NTHR = 512;

struct __align__(128) Scratch {
    unsigned epoch[NCTA * 16];
    uint4 keys[16 * 128];
    uint32_t sel[18 * 64];
    uint16_t gate[L_SEQ];
    uint2 h[2 * 288 * 32];
    uint4 kp[DM * 96];
};
__device__ Scratch g_scratch;
#define TFLUSH()
#define TSTAMP(i)
#define TW 12

struct Params {
    const __nv_bfloat16 *Are, *Aim, *Bre, *Bim, *Cre, *Cim, *logdt, *Dskip, *u, *wr, *gatew;
    __nv_bfloat16* out;
    Scratch* s;
    uint32_t zero;
};

__device__ __forceinline__ void give_up() { asm volatile("trap; exit;"); __builtin_unreachable(); }
__device__ __forceinline__ void converged() { __syncwarp(); asm volatile("{ .reg .b32 t; mov.b32 t, 0; movmatrix.sync.aligned.m8n8.trans.b16 t, t; }" ::: "memory"); }
__device__ __forceinline__ bool elect() { uint32_t r; asm volatile("{ .reg .pred p; elect.sync _|p, 0xffffffff; selp.u32 %0, 1, 0, p; }" : "=r"(r)); return r; }
__device__ __forceinline__ uint32_t smem_u32(const void* p) { return (uint32_t)__cvta_generic_to_shared(p); }
__device__ __forceinline__ uint32_t pack_bf16(float lo, float hi) { uint32_t r; asm("cvt.rn.bf16x2.f32 %0, %1, %2;" : "=r"(r) : "f"(hi), "f"(lo)); return r; }
__device__ __forceinline__ uint32_t pack_f16(float lo, float hi) { uint32_t r; asm("cvt.rn.f16x2.f32 %0, %1, %2;" : "=r"(r) : "f"(hi), "f"(lo)); return r; }
__device__ __forceinline__ float bf_lo(uint32_t w) { return __uint_as_float(w << 16); }
__device__ __forceinline__ float bf_hi(uint32_t w) { return __uint_as_float(w & 0xffff0000u); }
__device__ __forceinline__ float rbf(float x) { return bf_lo(pack_bf16(x, 0.f)); }
__device__ __forceinline__ uint32_t badd2(uint32_t a, uint32_t b) { uint32_t r; asm("add.rn.bf16x2 %0, %1, %2;" : "=r"(r) : "r"(a), "r"(b)); return r; }
__device__ __forceinline__ uint32_t bsub2(uint32_t a, uint32_t b) { uint32_t r; asm("sub.rn.bf16x2 %0, %1, %2;" : "=r"(r) : "r"(a), "r"(b)); return r; }
__device__ __forceinline__ uint32_t gmix(uint32_t ng, float ny0, float ny1, uint32_t u) {
    uint32_t r; asm("{ .reg .b32 t; fma.rn.bf16x2 t, %1, %3, %3; fma.rn.bf16x2 %0, %1, %2, t; }" : "=r"(r) : "r"(ng), "r"(pack_bf16(ny0, ny1)), "r"(u)); return r;
}
__device__ __forceinline__ void mma_bf(float (&c)[4], uint32_t a0, uint32_t a1, uint32_t a2, uint32_t a3, uint32_t b0, uint32_t b1) {
    asm("mma.sync.aligned.m16n8k16.row.col.f32.bf16.bf16.f32 {%0,%1,%2,%3}, {%4,%5,%6,%7}, {%8,%9}, {%0,%1,%2,%3};"
        : "+f"(c[0]), "+f"(c[1]), "+f"(c[2]), "+f"(c[3]) : "r"(a0), "r"(a1), "r"(a2), "r"(a3), "r"(b0), "r"(b1));
}
__device__ __forceinline__ void mma_bf8(float (&c)[4], uint32_t a0, uint32_t a1, uint32_t b0) {
    asm("mma.sync.aligned.m16n8k8.row.col.f32.bf16.bf16.f32 {%0,%1,%2,%3}, {%4,%5}, {%6}, {%0,%1,%2,%3};"
        : "+f"(c[0]), "+f"(c[1]), "+f"(c[2]), "+f"(c[3]) : "r"(a0), "r"(a1), "r"(b0));
}
__device__ __forceinline__ void mma_h(float (&c)[4], uint32_t a0, uint32_t a1, uint32_t a2, uint32_t a3, uint32_t b0, uint32_t b1) {
    asm("mma.sync.aligned.m16n8k16.row.col.f32.f16.f16.f32 {%0,%1,%2,%3}, {%4,%5,%6,%7}, {%8,%9}, {%0,%1,%2,%3};"
        : "+f"(c[0]), "+f"(c[1]), "+f"(c[2]), "+f"(c[3]) : "r"(a0), "r"(a1), "r"(a2), "r"(a3), "r"(b0), "r"(b1));
}
__device__ __forceinline__ uint32_t fresh(uint32_t a) { asm volatile("" : "+r"(a) :: "memory"); return a; }
__device__ __forceinline__ uint32_t lds32(uint32_t a) { uint32_t v; asm("ld.shared.u32 %0, [%1];" : "=r"(v) : "r"(a)); return v; }
__device__ __forceinline__ uint2 lds64(uint32_t a) { uint2 v; asm("ld.shared.v2.u32 {%0,%1}, [%2];" : "=r"(v.x), "=r"(v.y) : "r"(a)); return v; }
__device__ __forceinline__ uint4 lds128(uint32_t a) { uint4 v; asm("ld.shared.v4.u32 {%0,%1,%2,%3}, [%4];" : "=r"(v.x), "=r"(v.y), "=r"(v.z), "=r"(v.w) : "r"(a)); return v; }
__device__ __forceinline__ void ldsm4(uint32_t (&r)[4], uint32_t a) {
    asm("ldmatrix.sync.aligned.m8n8.x4.shared.b16 {%0,%1,%2,%3}, [%4];" : "=r"(r[0]), "=r"(r[1]), "=r"(r[2]), "=r"(r[3]) : "r"(a));
}
__device__ __forceinline__ void ldsm4t(uint32_t (&r)[4], uint32_t a) {
    asm("ldmatrix.sync.aligned.m8n8.x4.trans.shared.b16 {%0,%1,%2,%3}, [%4];" : "=r"(r[0]), "=r"(r[1]), "=r"(r[2]), "=r"(r[3]) : "r"(a));
}
__device__ __forceinline__ void sts16(uint32_t a, uint32_t v) { asm volatile("st.shared.u16 [%0], %1;" :: "r"(a), "h"((unsigned short)v) : "memory"); }
__device__ __forceinline__ void sts32(uint32_t a, uint32_t v) { asm volatile("st.shared.u32 [%0], %1;" :: "r"(a), "r"(v) : "memory"); }
__device__ __forceinline__ void sts64(uint32_t a, uint32_t x, uint32_t y) { asm volatile("st.shared.v2.u32 [%0], {%1,%2};" :: "r"(a), "r"(x), "r"(y) : "memory"); }
__device__ __forceinline__ void sts128(uint32_t a, uint32_t x, uint32_t y, uint32_t z, uint32_t w) {
    asm volatile("st.shared.v4.u32 [%0], {%1,%2,%3,%4};" :: "r"(a), "r"(x), "r"(y), "r"(z), "r"(w) : "memory");
}
__device__ __forceinline__ void st_async128(uint32_t a, uint32_t x, uint32_t y, uint32_t z, uint32_t w, uint32_t bar) {
    asm volatile("st.async.weak.shared::cluster.mbarrier::complete_tx::bytes.v4.b32 [%0], {%1,%2,%3,%4}, [%5];" :: "r"(a), "r"(x), "r"(y), "r"(z), "r"(w), "r"(bar) : "memory");
}
__device__ __forceinline__ void mbar_init(uint32_t b, uint32_t cnt) { asm volatile("mbarrier.init.shared::cta.b64 [%0], %1;" :: "r"(b), "r"(cnt) : "memory"); }
__device__ __forceinline__ void mbar_fence() { asm volatile("fence.mbarrier_init.release.cluster;" ::: "memory"); }
__device__ __forceinline__ void mbar_expect(uint32_t b, uint32_t bytes) { asm volatile("mbarrier.arrive.expect_tx.shared::cta.b64 _, [%0], %1;" :: "r"(b), "r"(bytes) : "memory"); }
__device__ __forceinline__ void mbar_arrive(uint32_t b) { asm volatile("mbarrier.arrive.shared::cta.b64 _, [%0];" :: "r"(b) : "memory"); }
__device__ __forceinline__ void mbar_wait(uint32_t b, uint32_t parity = 0) {
    asm volatile("{ .reg .pred p; .reg .u32 n; mov.u32 n, 0;\n"
                 "LW: mbarrier.try_wait.parity.shared::cta.b64 p, [%0], %1; @p bra LD; add.u32 n, n, 1; setp.lt.u32 p, n, 65536; @p bra LW; trap;\n"
                 "LD: }" :: "r"(b), "r"(parity) : "memory");
}
__device__ __forceinline__ void mbar_wait_cluster(uint32_t b) {
    asm volatile("{ .reg .pred p; .reg .u32 n; mov.u32 n, 0;\n"
                 "LW: mbarrier.try_wait.parity.acquire.cluster.shared::cta.b64 p, [%0], 0; @p bra LD; add.u32 n, n, 1; setp.lt.u32 p, n, 65536; @p bra LW; trap;\n"
                 "LD: }" :: "r"(b) : "memory");
}
__device__ __forceinline__ void tma2d(uint32_t dst, const CUtensorMap* m, int c0, int c1, uint32_t bar) {
    asm volatile("cp.async.bulk.tensor.2d.shared::cluster.global.mbarrier::complete_tx::bytes [%0], [%1, {%3, %4}], [%2];"
                 :: "r"(dst), "l"(m), "r"(bar), "r"(c0), "r"(c1) : "memory");
}
__device__ __forceinline__ void tma3d(uint32_t dst, const CUtensorMap* m, int c0, int c1, int c2, uint32_t bar) {
    asm volatile("cp.async.bulk.tensor.3d.shared::cluster.global.mbarrier::complete_tx::bytes [%0], [%1, {%3, %4, %5}], [%2];"
                 :: "r"(dst), "l"(m), "r"(bar), "r"(c0), "r"(c1), "r"(c2) : "memory");
}
__device__ __forceinline__ void tma4d(uint32_t dst, const CUtensorMap* m, int c0, int c1, int c2, int c3, uint32_t bar) {
    asm volatile("cp.async.bulk.tensor.4d.shared::cluster.global.mbarrier::complete_tx::bytes [%0], [%1, {%3, %4, %5, %6}], [%2];"
                 :: "r"(dst), "l"(m), "r"(bar), "r"(c0), "r"(c1), "r"(c2), "r"(c3) : "memory");
}
__device__ __forceinline__ void bulk_g2s(uint32_t dst, const void* src, uint32_t bytes, uint32_t bar) {
    asm volatile("cp.async.bulk.shared::cluster.global.mbarrier::complete_tx::bytes [%0], [%1], %2, [%3];"
                 :: "r"(dst), "l"(src), "r"(bytes), "r"(bar) : "memory");
}
__device__ __forceinline__ uint32_t mapa(uint32_t a, uint32_t rank) { uint32_t r; asm("mapa.shared::cluster.u32 %0, %1, %2;" : "=r"(r) : "r"(a), "r"(rank)); return r; }
__device__ __forceinline__ void prefetch_map(const CUtensorMap* m) { asm volatile("prefetch.tensormap [%0];" :: "l"(m) : "memory"); }
__device__ __forceinline__ void bar_sync(int id, int n) { asm volatile("bar.sync %0, %1;" :: "r"(id), "r"(n) : "memory"); }
__device__ __forceinline__ void bar_arrive(int id, int n) { asm volatile("bar.arrive %0, %1;" :: "r"(id), "r"(n) : "memory"); }
__device__ __forceinline__ uint32_t ldg16_if(bool c, const void* p) { uint32_t v; asm volatile("{ .reg .pred p; setp.ne.u32 p, %2, 0; @p ld.global.nc.u16 %0, [%1]; }" : "=r"(v) : "l"(p), "r"((uint32_t)c)); return v; }
__device__ __forceinline__ uint32_t ldg32_if(bool c, const void* p) { uint32_t v; asm volatile("{ .reg .pred p; setp.ne.u32 p, %2, 0; @p ld.global.nc.u32 %0, [%1]; }" : "=r"(v) : "l"(p), "r"((uint32_t)c)); return v; }
__device__ __forceinline__ uint32_t ld_rlx32(const void* p) { uint32_t v; asm volatile("ld.relaxed.gpu.global.u32 %0, [%1];" : "=r"(v) : "l"(p) : "memory"); return v; }
__device__ __forceinline__ uint4 ld_rlx128(const void* p) {
    uint4 v; asm volatile("ld.relaxed.gpu.global.v4.u32 {%0,%1,%2,%3}, [%4];" : "=r"(v.x), "=r"(v.y), "=r"(v.z), "=r"(v.w) : "l"(p) : "memory"); return v;
}
__device__ __forceinline__ void st_rlx32(void* p, uint32_t v) { asm volatile("st.relaxed.gpu.global.u32 [%0], %1;" :: "l"(p), "r"(v) : "memory"); }
__device__ __forceinline__ void stg128(void* p, uint32_t x, uint32_t y, uint32_t z, uint32_t w) {
    asm volatile("st.global.v4.u32 [%0], {%1,%2,%3,%4};" :: "l"(p), "r"(x), "r"(y), "r"(z), "r"(w) : "memory");
}
__device__ __forceinline__ void next_epoch(const Params& p, unsigned e) { if ((threadIdx.x & 31) == 0) p.s->epoch[blockIdx.x * 16 + (threadIdx.x >> 5)] = e + 1; }
__device__ __forceinline__ void sts128z_if(bool c, uint32_t a) { asm volatile("{ .reg .pred p; setp.ne.u32 p, %1, 0; @p st.shared.v4.u32 [%0], {%2,%2,%2,%2}; }" :: "r"(a), "r"((uint32_t)c), "r"(0) : "memory"); }
__device__ __forceinline__ void stg128z_if(bool c, void* a) { asm volatile("{ .reg .pred p; setp.ne.u32 p, %1, 0; @p st.global.v4.u32 [%0], {%2,%2,%2,%2}; }" :: "l"(a), "r"((uint32_t)c), "r"(0) : "memory"); }
__device__ __forceinline__ unsigned clock32() { unsigned c; asm volatile("mov.u32 %0, %clock;" : "=r"(c) :: "memory"); return c; }
__device__ __forceinline__ void until(unsigned t0, int c) { while ((int)(clock32() - t0) < c) { } }
__device__ __forceinline__ float sigmoidf_(float x) { return __fdividef(1.0f, 1.0f + __expf(-x)); }
__device__ __forceinline__ uint32_t key_tag(unsigned epoch) { return ((epoch & 15u) | 16u) << 11; }
__device__ __forceinline__ int key_row(uint32_t key) { return 2047 - (int)(key & 2047u); }
__device__ __forceinline__ uint32_t wait_sel(const Params& p, int s32, int r8, uint32_t tag, uint32_t k = 0) {
#pragma unroll 1
    for (int it = 0; !__all_sync(0xffffffffu, (k & 0xf800u) == tag); it++) {
        k = ld_rlx32(&p.s->sel[s32 * 64 + r8]);
        if (it > (1 << 20)) give_up();
    }
    return k;
}

struct cplx { float re, im; };
__device__ __forceinline__ cplx csq(cplx a) { cplx r; r.re = a.re * a.re - a.im * a.im; r.im = (a.re * a.im) * 2.f; return r; }
__device__ __forceinline__ cplx cexpk(float ar, float ai, float k) {
    float mag, s, c;
    asm("ex2.approx.ftz.f32 %0, %1;" : "=f"(mag) : "f"(ar * (k * 1.4426950408889634f)));
    const float r = ai * k;
    asm("sin.approx.ftz.f32 %0, %1;" : "=f"(s) : "f"(r));
    asm("cos.approx.ftz.f32 %0, %1;" : "=f"(c) : "f"(r));
    cplx o; o.re = mag * c; o.im = mag * s; return o;
}
struct h2c { uint32_t re, im; };
__device__ __forceinline__ h2c cmul_cd(h2c v, __half2 c, __half2 d) {
    const __half2 r = *(const __half2*)&v.re, i = *(const __half2*)&v.im;
    const __half2 x = __hfma2(__hneg2(i), d, __hmul2(r, c)), y = __hfma2(i, c, __hmul2(r, d));
    h2c o; o.re = *(const uint32_t*)&x; o.im = *(const uint32_t*)&y; return o;
}
__device__ __forceinline__ h2c cmul_s(h2c v, uint32_t s) { const __half2 h = *(const __half2*)&s; return cmul_cd(v, __low2half2(h), __high2half2(h)); }
__device__ __forceinline__ h2c cmul_sc(h2c v, uint32_t s) {
    const __half2 h = *(const __half2*)&s, c = __low2half2(h), d = __high2half2(h), r = *(const __half2*)&v.re, i = *(const __half2*)&v.im;
    const __half2 x = __hfma2(i, d, __hmul2(r, c)), y = __hfma2(__hneg2(r), d, __hmul2(i, c));
    h2c o; o.re = *(const uint32_t*)&x; o.im = *(const uint32_t*)&y; return o;
}
__device__ __forceinline__ h2c cmul_vc(h2c v, uint32_t s) {
    const __half2 h = *(const __half2*)&s, c = __low2half2(h), d = __high2half2(h), r = *(const __half2*)&v.re, i = *(const __half2*)&v.im;
    const __half2 x = __hfma2(i, d, __hmul2(r, c)), y = __hfma2(__hneg2(i), c, __hmul2(r, d));
    h2c o; o.re = *(const uint32_t*)&x; o.im = *(const uint32_t*)&y; return o;
}

constexpr int UT_HALF = 2240, UT_STRIDE = 4448;
constexpr int KT_T = 542, KT_C = 552, KT_D = 645, KT_BYTES = 720 * 4;
constexpr int VC_OFF = 80, VE_BASE = 1616;
constexpr int V_STRIDE = (1616 + 1024) * 4 + 80;
constexpr int KG_STAGE = 5248;
constexpr int Y_CS = 2080, Y_RS = 8 * Y_CS + 64;

constexpr int SC_RT = 0;
constexpr int SC_UT = 33408;
constexpr int SC_ST = SC_UT + 8 * UT_STRIDE;
constexpr int SC_KT = SC_ST + 8 * UT_STRIDE;
constexpr int SC_GT = SC_KT + 8 * KT_BYTES;
constexpr int SC_V = SC_GT + UT_STRIDE;
constexpr int SC_KG = SC_V + 4 * V_STRIDE;
constexpr int SC_MISC = SC_V + 8 * V_STRIDE;
static_assert(V_STRIDE % 128 == 16 && 8 * KG_STAGE <= 4 * V_STRIDE && 2 * Y_RS <= SC_UT && SC_UT % 128 == 0 && SC_ST % 128 == 0, "layout");
static_assert(SC_MISC % 16 == 0 && SC_MISC + 512 <= 232192, "layout");

__device__ __forceinline__ void window_task(uint32_t src, uint32_t d0, uint32_t d1, int k) {
    float S[51], s = 0.f;
    uint32_t w[28];
#pragma unroll
    for (int i = 0; i < 7; i++) {
        const uint4 v = lds128(src + ((i & 1) ? 0 : UT_HALF) + ((i + 1) >> 1) * 16);
        w[4 * i] = v.x; w[4 * i + 1] = v.y; w[4 * i + 2] = v.z; w[4 * i + 3] = v.w;
    }
    auto sums = [&](int lo, int hi) {
#pragma unroll
        for (int i = lo; i < hi; i++) { const float x = (i & 1) ? bf_hi(w[i >> 1]) : bf_lo(w[i >> 1]); s = i > 3 ? s + x : x; S[i] = s; }
    };
    auto put = [&](int off, int b, int o0, int o1, int o2) {
        auto v = [&](int i) { i += 16 * b; return pack_bf16(S[o0 + i] - S[o1 + i], S[o1 + i] - S[o2 + i]); };
#pragma unroll
        for (int i = 0; i < 8; i += 2) sts128((i & 4 ? d1 : d0) + 4 * off + 64 * b + 8 * (i & 2), v(i), v(i + 8), v(i + 1), v(i + 9));
    };
    S[2] = 0.f;
    sums(3, 26); put(VC_OFF - 16, 0, 10, 5, 2);
    if (k == 12) return;
    sums(26, 42); put(VC_OFF - 16, 1, 10, 5, 2);
    if (k < 8) { put(VE_BASE, 0, 19, 12, 3); sums(42, 51); put(VE_BASE, 1, 19, 12, 3); }
}

template <class F>
__device__ __forceinline__ void kgen(const uint32_t (&q)[8], uint32_t sb, int half, uint32_t stage, uint32_t pstage, int barid, int lane, uint32_t (&w)[12], F shadow) {
    const int t = lane & 3, mi = lane >> 3, r8 = lane & 7;
    {
        const uint32_t pAr = q[0], pAi = q[1], pBr = q[2], pBi = q[3], pCr = q[4], pCi = q[5], pDt = q[6], pD = q[7];
        const uint32_t wb = fresh(stage + lane * 16), za = fresh(stage + 5120 + ((lane >> 1) & 3) * 16 + mi * 4 + (lane & 1) * 2), zr = fresh(stage + 5120 + t * 16);
        const uint32_t oA = fresh(stage + (mi & 1) * 1024 + (mi >> 1) * 512 + r8 * 16), oB = fresh(stage + 2048 + mi * 512 + r8 * 16), oC = fresh(stage + 4096 + (mi & 1) * 512 + (mi >> 1) * 128 + r8 * 16);
        float acc[6][4];
#pragma unroll
        for (int a = 0; a < 6; a++) { acc[a][0] = acc[a][1] = acc[a][2] = acc[a][3] = 0.f; asm volatile("" : "+f"(acc[a][0]), "+f"(acc[a][1]), "+f"(acc[a][2]), "+f"(acc[a][3])); }
        shadow();
        sts32(zr, clock32());
        const float dt = rbf(__expf(bf_lo(pDt)));
        float ar = dt * bf_lo(pAr), ai = dt * bf_lo(pAi), ar1 = dt * bf_hi(pAr), ai1 = dt * bf_hi(pAi);
        float wr, wi, wr1, wi1;
        { const float br = dt * bf_lo(pBr), bi = dt * bf_lo(pBi), cr = bf_lo(pCr), ci = bf_lo(pCi); wr = cr * br - ci * bi; wi = cr * bi + ci * br; }
        { const float br = dt * bf_hi(pBr), bi = dt * bf_hi(pBi), cr = bf_hi(pCr), ci = bf_hi(pCi); wr1 = cr * br - ci * bi; wi1 = cr * bi + ci * br; }
        const uint32_t ex = max(__reduce_max_sync(0xffffffffu, __float_as_uint(fmaxf(fmaxf(fabsf(wr), fabsf(wi)), fmaxf(fabsf(wr1), fabsf(wi1))))) >> 23, 14u);
        const float scl = __uint_as_float((267u - ex) << 23);
        uint32_t W = pack_f16(wr * scl, wi * -scl);
        const uint32_t W1 = pack_f16(wr1 * scl, wi1 * -scl);
        if (threadIdx.x < 32) TSTAMP(20);

#pragma unroll 1
        for (int r = 0; r < 2; r++) {
            const cplx z1 = cexpk(ar, ai, 1.f), z64 = cexpk(ar, ai, 64.f);
            const cplx z2 = csq(z1), z4 = csq(z2), z8 = csq(z4), z16 = csq(z8), z32 = csq(z16);
            const cplx z128 = csq(z64), z256 = csq(z128), z512 = csq(z256);
            auto put = [&](int grp, h2c a, h2c b, h2c c, h2c d) { sts128(wb + grp * 1024, a.re, b.re, c.re, d.re); sts128(wb + grp * 1024 + 512, a.im, b.im, c.im, d.im); };
            {
                const uint32_t s4 = pack_f16(z4.re, z4.im), s256 = pack_f16(z256.re, z256.im), s512 = pack_f16(z512.re, z512.im);
                auto mix = [](h2c a, h2c b, uint32_t sel) { return h2c{__byte_perm(a.re, b.re, sel), __byte_perm(a.im, b.im, sel)}; };
                const h2c c10 = cmul_vc(h2c{pack_f16(z1.re, 1.f), pack_f16(z1.im, 0.f)}, W), c32 = cmul_sc(c10, pack_f16(z2.re, z2.im)), c54 = cmul_sc(c10, s4);
                put(2, c10, c32, c54, cmul_sc(c32, s4));
                const h2c d20 = cmul_sc(mix(c32, c10, 0x7632), s256), e04 = cmul_sc(mix(c10, c54, 0x7632), s512), f04 = cmul_sc(e04, s256);
                put(3, d20, cmul_sc(d20, s4), e04, f04);
                const h2c ef = mix(e04, f04, 0x5410), gh = cmul_sc(ef, s512), g8 = cmul_sc(gh, pack_f16(z8.re, z8.im));
                put(4, g8, cmul_sc(g8, s512), gh, ef);
            }
            {
                const uint32_t s32 = pack_f16(z32.re, z32.im), s64 = pack_f16(z64.re, z64.im), s128 = pack_f16(z128.re, z128.im);
                const h2c p0 = {pack_f16(1.f, z8.re), pack_f16(0.f, z8.im)}, p1 = cmul_s(p0, pack_f16(z16.re, z16.im)), p2 = cmul_s(p0, s32), p3 = cmul_s(p1, s32);
                put(0, p0, p1, p2, p3);
                put(1, cmul_s(p0, s64), cmul_s(p1, s64), cmul_s(p2, s64), cmul_s(p3, s64));
                sts16(za, s128); sts16(za + 64, s128 >> 16);
            }
            __syncwarp();
            {
                const uint32_t aA = fresh(oA), aB = fresh(oB), aC = fresh(oC), aZ = fresh(zr);
                const uint4 zc = lds128(aZ), zd = lds128(aZ + 64);
                const uint32_t zcs[4] = {zc.x, zc.y, zc.z, zc.w}, zds[4] = {zd.x, zd.y, zd.z, zd.w};
                uint32_t c[4];
#pragma unroll
                for (int k = 0; k < 4; k++) {
                    uint32_t a[4], b[4];
                    ldsm4t(a, aA + 128 * k); ldsm4t(b, aB + 128 * k);
                    if (!(k & 1)) ldsm4t(c, aC + 128 * k);
                    const h2c x = cmul_cd(h2c{a[0], a[2]}, *(const __half2*)&zcs[k], *(const __half2*)&zds[k]), y = cmul_cd(h2c{a[1], a[3]}, *(const __half2*)&zcs[k], *(const __half2*)&zds[k]);
                    mma_h(acc[0], a[0], a[1], a[2], a[3], b[0], b[1]);
                    mma_h(acc[1], a[0], a[1], a[2], a[3], b[2], b[3]);
                    mma_h(acc[2], a[0], a[1], a[2], a[3], c[2 * (k & 1)], c[2 * (k & 1) + 1]);
                    mma_h(acc[3], x.re, y.re, x.im, y.im, b[0], b[1]);
                    mma_h(acc[4], x.re, y.re, x.im, y.im, b[2], b[3]);
                    mma_h(acc[5], x.re, y.re, x.im, y.im, c[2 * (k & 1)], c[2 * (k & 1) + 1]);
                }
                asm volatile("" :: "f"(acc[0][0]), "f"(acc[1][0]), "f"(acc[2][0]), "f"(acc[3][0]), "f"(acc[4][0]), "f"(acc[5][0]) : "memory");
            }
            __syncwarp();
            ar = ar1; ai = ai1; W = W1;
        }
        if (threadIdx.x < 32) TSTAMP(21);
        const float i0 = __uint_as_float((ex + 243u) << 23);
        if (half) {
#pragma unroll
            for (int a = 0; a < 6; a++) sts128(wb + a * 512, __float_as_uint(acc[a][0]), __float_as_uint(acc[a][1]), __float_as_uint(acc[a][2]), __float_as_uint(acc[a][3]));
            sts32(stage + 3072, __float_as_uint(i0));
            bar_arrive(barid, 64);
        } else {
#pragma unroll
            for (int a = 0; a < 6; a++) { acc[a][0] *= i0; acc[a][1] *= i0; acc[a][2] *= i0; acc[a][3] *= i0; }
            if (lane == 0) acc[0][1] -= bf_lo(pD);
            sts32(zr, clock32());
            bar_sync(barid, 64);
            const uint32_t src = fresh(pstage);
            const float i1 = __uint_as_float(lds32(src + 3072));
#pragma unroll
            for (int a = 0; a < 6; a++) {
                const uint4 y = lds128(src + lane * 16 + a * 512);
                w[4 * (a % 3) + 2 * (a / 3)] = pack_bf16(fmaf(__uint_as_float(y.x), i1, acc[a][0]), fmaf(__uint_as_float(y.y), i1, acc[a][1]));
                w[4 * (a % 3) + 2 * (a / 3) + 1] = pack_bf16(fmaf(__uint_as_float(y.z), i1, acc[a][2]), fmaf(__uint_as_float(y.w), i1, acc[a][3]));
            }
            const uint32_t x0 = __shfl_up_sync(0xffffffffu, w[10], 2), x1 = __shfl_up_sync(0xffffffffu, w[11], 2);
            w[10] = w[8];
            if (t >= 2) { w[8] = x0; w[9] = x1; }
        }
    }
}

__device__ __forceinline__ int swap01(int i) { return (i & ~3) | ((i & 1) << 1) | ((i >> 1) & 1); }
__device__ __forceinline__ int ut_off(int i) { return i * UT_STRIDE + (i & 4) * USKEW; }
enum { BC_AUX = 0, BC_S = 5, BC_KG = 15 };

__device__ __forceinline__ void fetch_gates(const Params& p, int i, int lane, unsigned epoch, uint32_t dst) {
    const uint32_t par = (epoch & 1) ? 0x80008000u : 0u;
    uint4 v;
#pragma unroll 1
    for (int it = 0;; it++) {
        v = ld_rlx128(p.s->gate + 256 * i + 8 * lane);
        v.x ^= par; v.y ^= par; v.z ^= par; v.w ^= par;
        if (__all_sync(0xffffffffu, (v.x & v.y & v.z & v.w & 0x80008000u) == 0x80008000u)) break;
        if (it > (1 << 20)) give_up();
    }
    sts128(dst + (8 + 16 * i + (lane >> 1)) * 16, v.x, v.y, v.z, v.w);
}
__device__ __forceinline__ void store_rows(const CUtensorMap* m, uint32_t src, int col, int row) {
    asm volatile("cp.async.bulk.tensor.5d.global.shared::cta.bulk_group [%0, {%2, %3, %3, %3, %4}], [%1];" :: "l"(m), "r"(src), "r"(col), "r"(0), "r"(row) : "memory");
}

__device__ __forceinline__ void store_or_add(void* o, const uint32_t (&y)[4], uint32_t add) {
    asm volatile("{ .reg .pred p; setp.ne.u32 p, %5, 0; @!p st.global.v4.u32 [%0], {%1,%2,%3,%4}; @p red.relaxed.gpu.global.add.noftz.v4.bf16x2 [%0], {%1,%2,%3,%4}; }"
                 :: "l"(o), "r"(y[0]), "r"(y[1]), "r"(y[2]), "r"(y[3]), "r"(add) : "memory");
}

__device__ __forceinline__ void conv_aux(const Params& p, const CUtensorMap* mU, uint32_t sb, int aw, int lane, int bid, unsigned epoch) {
    const int g = lane >> 2, t = lane & 3, mi = lane >> 3, r8 = lane & 7;
    const int rank = bid & 1, slab = bid >> 1;
    const uint32_t bar_y = sb + SC_MISC, bar_u = bar_y + 32, bar_v = bar_y + 40, bar_box = bar_y + 64 + 8 * aw, s_bm = bar_y + 128;
    if (elect()) {
        mbar_init(bar_box, 1); mbar_fence();
        mbar_expect(bar_box, 4096);
        tma4d(sb + SC_RT + 4096 * aw, mU, 16 * slab, 0, 0, 16 * rank + 2 * aw, bar_box);
        mbar_init(bar_y + 8 * aw, aw < 4 ? 9 : aw == 5 ? 8 : 1); mbar_fence();
        if (aw < 5) mbar_expect(bar_y + 8 * aw, aw == 4 ? 16384 : 4096);
    }
    __syncwarp();
    asm volatile("barrier.cluster.arrive.relaxed.aligned;" ::: "memory");
    asm volatile("setmaxnreg.dec.sync.aligned.u32 88;");
    const uint32_t ut = sb + SC_UT + ut_off(aw);
    sts128(ut + (mi >> 1) * (SC_ST - SC_UT) + (mi & 1) * UT_HALF + r8 * 16, 0, 0, 0, 0);
    if (lane < 16) sts128(s_bm + lane * 16, 0, 0, 0, 0);
    {
        const uint32_t dst = sb + SC_UT + ut_off(swap01(g)) + (8 + 64 * rank + 8 * aw + t) * 16;
        const uint32_t rdst = mapa(dst, rank ^ 1), rbar = mapa(bar_u, rank ^ 1);
        asm volatile("barrier.cluster.wait.acquire.aligned;" ::: "memory");
        mbar_wait(bar_box);
        if (aw == 0) TSTAMP(1);
        const uint32_t src = fresh(sb + SC_RT) + aw * 4096 + (8 * mi + 4 * (r8 & 1) + (r8 >> 1)) * 32 + ((rank ^ (r8 & 1)) << 4);
        uint32_t x[8][4];
#pragma unroll
        for (int i = 0; i < 4; i++) { ldsm4t(x[i], src + 1024 * i); ldsm4t(x[4 + i], (src ^ 16) + 1024 * i); }
        asm volatile("" :: "r"(x[0][0]), "r"(x[1][0]), "r"(x[2][0]), "r"(x[3][0]) : "memory");
#pragma unroll
        for (int i = 0; i < 4; i++) st_async128(rdst + (i & 1) * UT_HALF + 32 * (i & 2), x[4 + i][0], x[4 + i][1], x[4 + i][2], x[4 + i][3], rbar);
#pragma unroll
        for (int i = 0; i < 4; i++) sts128(dst + (i & 1) * UT_HALF + 32 * (i & 2), x[i][0], x[i][1], x[i][2], x[i][3]);
    }
    bar_sync(BC_AUX, 256);
    mbar_wait_cluster(bar_u);
    if (aw == 0) TSTAMP(2);
    {
        const uint32_t a = fresh(ut) + (mi & 1) * UT_HALF + (64 * (mi >> 1) + r8) * 16;
        uint4 v = lds128(a);
#pragma unroll
        for (int i = 1; i <= 8; i++) {
            const uint4 w = lds128(a + 128 * i);
            sts128(a + 128 * i + (SC_ST - SC_UT), badd2(v.x, w.x), badd2(v.y, w.y), badd2(v.z, w.z), badd2(v.w, w.w));
            v = w;
        }
    }
    bar_arrive(BC_S + aw, 64);
    if (aw == 0) TSTAMP(3);
    {
        const int c = t + 4 * (g & 1);
        uint32_t ws = sb + SC_UT + ut_off(c) + 96, wd = sb + SC_V + c * V_STRIDE;
        bar_sync(BC_KG, 384);
        if (lane < 16) sts128(sb + SC_V + aw * V_STRIDE + lane * 16, 0, 0, 0, 0);
#pragma unroll 1
        for (int k = aw; k < 13; k += 8) {
            const int a = 8 * k + (k < 12 ? g & 6 : 0);
            const uint32_t d = wd + 64 * a, sw = 16 * (a & 2);
            window_task(fresh(ws) + 16 * a, d + sw, d + (sw ^ 32), k);
        }
    }
    if (aw == 0) TSTAMP(9);
    {
        if (aw >= 2) fetch_gates(p, aw, lane, epoch, sb + SC_GT + (lane & 1) * UT_HALF);
        __syncwarp();
        if (elect()) { mbar_arrive(bar_v); prefetch_map(mU + 4); }
        next_epoch(p, epoch);
        if (aw == 0) TSTAMP(4);
        if (aw == 7) {
            const int row = key_row(wait_sel(p, slab >> 1, r8, key_tag(epoch)));
            if (lane < 8) asm volatile("red.shared.or.b32 [%0], %1;" :: "r"(s_bm + (row >> 5) * 4), "r"(1u << (row & 31)) : "memory");
            TSTAMP(10);
        }
        bar_sync(BC_AUX, 256);
        const uint32_t src = sb + SC_RT + ((r8 >> 1) & 1) * Y_RS + (2 * mi + (r8 & 1)) * Y_CS + (2 * aw + (r8 >> 2)) * 16;
        const int L = 2 * aw + (t >> 1);
        const int row0 = 256 * rank + 128 * (g >> 2) + 32 * (L & 3) + 16 * (g & 1) + 8 * ((g >> 1) & 1) + (L >> 2);
        __nv_bfloat16* outp = p.out + (size_t)row0 * DM + 16 * slab + 8 * (t & 1);
        const uint32_t stg = sb + SC_ST + 4096 * aw, so = (g >> 1) * 256 + (t >> 1) * 64 + (g & 1) * 32 + (t & 1) * 16;
#pragma unroll 1
        for (int s = 1; s < 4; s++) {
            const uint32_t bm = lds32(fresh(s_bm) + (16 * s + (row0 >> 5)) * 4) >> (row0 & 31);
            const bool routed = __any_sync(0xffffffffu, bm & 0x11u);
            if (aw == s) mbar_wait_cluster(bar_y + 8 * s);
            bar_sync(BC_AUX, 256);
            const uint32_t sf = fresh(src) + 512 * s;
            uint32_t y[2][4];
            ldsm4t(y[0], sf); ldsm4t(y[1], sf + 256);
            if (routed) {
#pragma unroll
                for (int k = 0; k < 2; k++) store_or_add(outp + (size_t)(512 * s + 4 * k) * DM, y[k], bm & (1u << (4 * k)));
            } else {
                sts128(stg + so + 1024 * s, y[0][0], y[0][1], y[0][2], y[0][3]); sts128(stg + so + 1024 * s + 128, y[1][0], y[1][1], y[1][2], y[1][3]);
                asm volatile("fence.proxy.async.shared::cta;" ::: "memory");
                __syncwarp();
                if (elect()) store_rows(mU + 4, stg + 1024 * s, 16 * slab, 512 * s + 256 * rank + 64 * (aw & 1) + (aw >> 1));
            }
            if (aw == 0) TSTAMP(16 + s);
        }
        if (elect()) { asm volatile("cp.async.bulk.commit_group;" ::: "memory"); asm volatile("cp.async.bulk.wait_group.read 0;" ::: "memory"); }
        if (aw == 0) TFLUSH();
    }
}

__device__ __forceinline__ uint32_t k_tag(unsigned epoch) { return epoch << 16 | 0x80000000u; }
__device__ __forceinline__ void publish_k(uint4* kp, const uint32_t (&w)[12], unsigned epoch, uint64_t (&v)[6]) {
#pragma unroll
    for (int i = 0; i < 3; i++) {
        v[2 * i] = w[3 * i] | (uint64_t)w[3 * i + 1] << 32; v[2 * i + 1] = w[3 * i + 2] | (uint64_t)__byte_perm(w[9 + (i >> 1)], k_tag(epoch), i == 1 ? 0x7632 : 0x7610) << 32;
        asm volatile("st.relaxed.gpu.global.v2.u64 [%0], {%1,%2};" :: "l"(kp + 32 * i), "l"(v[2 * i]), "l"(v[2 * i + 1]));
    }
}
template <bool FULL>
__device__ __forceinline__ void k_tables(uint32_t kt, int lane, const uint32_t (&w)[12]) {
    const int g = lane >> 2, t = lane & 3, mi = lane >> 3, r8 = lane & 7;
    uint32_t x3 = w[7], re[4], rx[4];
#pragma unroll
    for (int i = 0; i < 4; i++) {
        re[i] = __shfl_sync(0xffffffffu, w[i], lane + 31);
        rx[i] = __shfl_sync(0xffffffffu, w[4 + i], lane + (i == 0 && lane == 29 ? 5 : 1 + 2 * t));
    }
    if (FULL) {
        asm volatile("stmatrix.sync.aligned.m8n8.x2.trans.shared.b16 [%0], {%1,%2};" :: "r"(kt + (KT_D + 7) * 4 + 64 * t + 16 * (mi & 1) + 8 * (r8 & 4)), "r"(w[8]), "r"(w[9]) : "memory");
        if (lane == 2) {
            sts32(kt + (KT_C + 78) * 4, w[10] & 0xffffu);
            sts128(kt + (KT_T + 2) * 4, 0, w[10] & 0xffffu, __byte_perm(w[10], 0, 0x1010), w[10] << 16);
        }
        if (lane == 29) x3 = bsub2(x3, rx[0] & 0xffffu);
    }
#pragma unroll
    for (int i = 0; i < 4; i++) {
        sts64(kt + (16 + 64 * i) * 4 + 8 * lane, __byte_perm(w[i], lane ? re[i] : i ? re[i - 1] : 0, 0x5432), w[i]);
        const uint32_t x = i < 3 ? w[4 + i] : x3, aa = __byte_perm(x, 0, 0x3232);
        if (t < 2) sts128(kt + (272 + 64 * i + 8 * g + 4 * t) * 4, i == 0 && lane == 0 ? __byte_perm(x, re[3], 0x5432) : aa, aa, x,
                          __byte_perm(lane != 29 ? rx[i] : i < 3 ? rx[(i + 1) & 3] : FULL ? 0 : rx[0] << 16, x, 0x5432));
        else if (FULL) sts32(kt + (KT_C - 50 + 8 * i + 32 * t + g) * 4, x);
    }
}

__device__ __forceinline__ void conv_main(const Params& p, uint32_t sb, int warp, int lane0, int bid, unsigned epoch, uint32_t (&w)[12]) {
    asm volatile("setmaxnreg.inc.sync.aligned.u32 168;");
    const int lane = __shfl_sync(0xffffffffu, lane0, lane0);
    const int g = lane >> 2, t = lane & 3, mi = lane >> 3, r8 = lane & 7;
    const int rank = bid & 1;
    const uint32_t bar_y = sb + SC_MISC, bar_v = bar_y + 40;
    next_epoch(p, epoch);
    if (warp < 4) {
        asm volatile("" :: "r"(w[0]), "r"(w[2]), "r"(w[4]), "r"(w[6]), "r"(w[8]), "r"(w[10]) : "memory");
        bar_arrive(BC_KG, 384);
    } else {
        bar_sync(BC_S + swap01(warp), 64);
        const uint4* src = p.s->kp + (8 * bid + warp) * 96 + lane0;
#pragma unroll 1
        for (int it = 0;; it++) {
            uint32_t bad = 0, e[3];
#pragma unroll
            for (int i = 0; i < 3; i++) { const uint4 v = ld_rlx128(src + 32 * i); w[3 * i] = v.x; w[3 * i + 1] = v.y; w[3 * i + 2] = v.z; e[i] = v.w; bad |= v.w ^ k_tag(epoch); }
            w[9] = __byte_perm(e[0], e[1], 0x5410); w[10] = e[2];
            const bool ok = __all_sync(0xffffffffu, bad < 65536);
            if (ok) break;
            if (it > (1 << 20)) give_up();
        }
    }
    if ((warp & 3) == 0) TSTAMP(5 + (warp >> 2));
    k_tables<true>(sb + SC_KT + warp * KT_BYTES, lane0, w);
    asm volatile("barrier.cluster.wait.acquire.aligned;" ::: "memory");
    if (warp < 4) bar_sync(BC_S + swap01(warp), 64);
    __syncwarp();
    if ((warp & 3) == 0) TSTAMP(7 + (warp >> 2));
    {
        const uint32_t ut = fresh(sb + SC_UT) + ut_off(swap01(warp)), kt = fresh(sb + SC_KT) + warp * KT_BYTES;
        uint32_t u1 = ut + (mi & 1) * UT_HALF + (8 + r8) * 16 + (mi >> 1) * 128;
        auto dup = [&](uint32_t v) { return v ^ p.zero; };
        uint32_t kp = kt + (16 + g - 2 * t) * 4;
        float acc[16][4];
        {
            const uint32_t c0 = lds32(kp + 2048), c1 = lds32(kp + 2080), c2 = lds32(kp + 2016), c3 = dup(c0);
            const uint32_t e0 = lds32(kp + (KT_T - 16) * 4), e1 = lds32(kp + (KT_T - 8) * 4), e2 = lds32(kp + (KT_T - 24) * 4), e3 = dup(e0);
            const uint32_t f0 = dup(e1), f1 = lds32(kp + KT_T * 4);
            const uint32_t uo = ut + UT_HALF + (7 + lane) * 16;
#pragma unroll
            for (int i = 0; i < 16; i++) { acc[i][0] = acc[i][1] = acc[i][2] = acc[i][3] = 0.f; }
#pragma unroll
            for (int mu = 0; mu < 8; mu += 4) {
                uint32_t b[4];
                ldsm4(b, uo + 128 * mu);
#pragma unroll
                for (int k = 0; k < 4; k++) mma_bf8(acc[mu + 8 + k], f0, f1, b[k]);
            }
#pragma unroll
            for (int mu = 0; mu < 12; mu += 2) {
                uint32_t b[4];
                ldsm4(b, u1 + 128 * mu);
                mma_bf(acc[mu + 4], c0, c1, c2, c3, b[0], b[1]);
                mma_bf(acc[mu + 5], c0, c1, c2, c3, b[2], b[3]);
                if (mu < 8) { mma_bf(acc[mu + 8], e0, e1, e2, e3, b[0], b[1]); mma_bf(acc[mu + 9], e0, e1, e2, e3, b[2], b[3]); }
            }
        }
        {
            float M[8][4];
#pragma unroll
            for (int i = 0; i < 8; i++) { M[i][0] = M[i][1] = M[i][2] = M[i][3] = 0.f; }
            uint32_t s[8][4], a3[4];
            const uint32_t kb = kp, ub = dup(u1), uc = u1 + (mi >> 1) * 128;
            auto frag = [&](uint32_t (&a)[4], uint32_t x) { a[0] = lds32(x); a[1] = lds32(x + 32); a[2] = lds32(x - 32); a[3] = dup(a[0]); };
            frag(a3, kp + 1536);
#pragma unroll
            for (int i = 1; i < 8; i++) ldsm4(s[i], u1 + (SC_ST - SC_UT) + 256 * i);
            __syncwarp();
#pragma unroll 1
            for (uint32_t ko = 0, uo = 0; ko != 512;) {
                uint32_t a2[4], a1[4], a0[4], b[4][4];
                ko = fresh(ko); uo = fresh(uo);
                kp = kb + ko; u1 = ub + uo;
                const uint32_t up = uc + uo;
                ko += 64; uo -= 16;
                frag(a2, kp + 1024);
#pragma unroll
                for (int i = 1; i < 4; i++) ldsm4(b[i], up + 512 * i);
                asm("ldmatrix.sync.aligned.m8n8.x2.shared.b16 {%0,%1}, [%2];" : "=r"(b[0][2]), "=r"(b[0][3]) : "r"(up + 256));
                frag(a1, kp + 512); frag(a0, kp);
                kp += 64; u1 -= 16;
#pragma unroll
                for (int i = 1; i < 7; i++) mma_bf(acc[2 * i + 2], a3[0], a3[1], a3[2], a3[3], s[i][0], s[i][1]);
#pragma unroll
                for (int e = 0; e < 4; e++) a3[e] = bsub2(a2[e], a3[e]);
#pragma unroll
                for (int i = 1; i < 7; i++) mma_bf(acc[2 * i + 3], a2[0], a2[1], a2[2], a2[3], s[i][2], s[i][3]);
                ldsm4(s[1], u1 + (SC_ST - SC_UT) + 256);
#pragma unroll
                for (int i = 1; i < 7; i++) mma_bf(M[i + 1], a3[0], a3[1], a3[2], a3[3], b[i >> 1][2 * (i & 1)], b[i >> 1][2 * (i & 1) + 1]);
                frag(a3, kp + 1536);
#pragma unroll
                for (int i = 2; i < 8; i++) mma_bf(acc[2 * i], a1[0], a1[1], a1[2], a1[3], s[i][0], s[i][1]);
#pragma unroll
                for (int e = 0; e < 4; e++) a1[e] = bsub2(a0[e], a1[e]);
#pragma unroll
                for (int i = 2; i < 8; i++) { mma_bf(acc[2 * i + 1], a0[0], a0[1], a0[2], a0[3], s[i][2], s[i][3]); ldsm4(s[i], u1 + (SC_ST - SC_UT) + 256 * i); }
#pragma unroll
                for (int i = 2; i < 8; i++) mma_bf(M[i], a1[0], a1[1], a1[2], a1[3], b[i >> 1][2 * (i & 1)], b[i >> 1][2 * (i & 1) + 1]);
            }
            u1 = ub;
#pragma unroll
            for (int i = 2; i < 8; i++)
#pragma unroll
                for (int c = 0; c < 4; c++) { acc[2 * i][c] += M[i][c]; acc[2 * i + 1][c] -= M[i][c]; }
        }
        if ((warp & 3) == 0) TSTAMP(11 + (warp >> 2));
        mbar_wait(bar_v);
        const uint32_t vt = fresh(sb + SC_V) + swap01(warp) * V_STRIDE;
        const uint32_t g1 = fresh(u1) - ut + sb + SC_GT;
        const uint32_t ydst = sb + SC_RT + rank * Y_RS + warp * Y_CS + lane * 16;
        const uint32_t ydr = mapa(ydst, rank ^ 1), ybr = mapa(bar_y, rank ^ 1);
        auto stairs = [&](auto R) {
        uint32_t ug[2][2][4];
        auto ld_ug = [&](int i) { ldsm4t(ug[i & 1][0], u1 + 256 * i); ldsm4t(ug[i & 1][1], g1 + 256 * i); };
        auto ship = [&](int i) {
            const uint32_t (&u)[4] = ug[i & 1][0], (&gg)[4] = ug[i & 1][1];
            const uint32_t y0 = gmix(gg[0], acc[2 * i][0], acc[2 * i][1], u[0]), y1 = gmix(gg[1], acc[2 * i][2], acc[2 * i][3], u[1]);
            const uint32_t y2 = gmix(gg[2], acc[2 * i + 1][0], acc[2 * i + 1][1], u[2]), y3 = gmix(gg[3], acc[2 * i + 1][2], acc[2 * i + 1][3], u[3]);
            if ((i & 1) != R.value) st_async128(ydr + 512 * (i >> 1), y0, y1, y2, y3, ybr + 8 * (i >> 1));
            else asm volatile("{ .reg .pred q; setp.eq.u32 q, %6, 0; st.shared.v4.u32 [%0], {%2,%3,%4,%5}; bar.warp.sync 0xffffffff; @q mbarrier.arrive.shared::cta.b64 _, [%1]; }"
                              :: "r"(ydst + 512 * (i >> 1)), "r"(bar_y + 8 * (i >> 1)), "r"(y0), "r"(y1), "r"(y2), "r"(y3), "r"(lane) : "memory");
        };
        const uint32_t VD = vt + (VC_OFF - 400 - 16 * t) * 4 + (8 * g ^ 16 * (-t & 2)), VD2 = vt + (VC_OFF - 415 - 16 * t) * 4 + (8 * g ^ 16 * (~t & 2));
        uint2 bd[10];
        uint32_t x[2][4][4];
        auto ld4 = [&](uint32_t (&v)[4], int dl) { const uint2 w = lds64(VD + 256 * dl); v[0] = w.x; v[1] = w.y; v[2] = lds32(VD2 + 256 * dl); v[3] = dup(w.x); };
        auto mm4 = [&](const uint32_t (&v)[4], int dl) {
#pragma unroll
            for (int s = dl & 1; s < 10; s += 2) if ((dl + s) / 2 >= 4 && (dl + s) / 2 < 16) mma_bf(acc[(dl + s) / 2], v[0], v[1], v[2], v[3], bd[s].x, bd[s].y);
        };
        const uint32_t KE = kt + (KT_D + g + t) * 4, VE = vt + (VE_BASE - 912 - 16 * t) * 4 + (8 * g ^ 16 * (~t & 2));
        uint32_t b0[8], b1[8];
        auto ld8 = [&](uint32_t (&v)[4], int dl) { const uint2 w = lds64(VE + 512 * dl), z = lds64(VE + 512 * dl - 256); v[0] = w.x; v[1] = w.y; v[2] = z.x; v[3] = z.y; };
        auto mm8 = [&](const uint32_t (&v)[4], int dl, int lo, int hi) {
#pragma unroll
            for (int s = 0; s < 8; s++) if (dl + s >= lo && dl + s < hi) mma_bf(acc[dl + s], v[0], v[1], v[2], v[3], b0[s], b1[s]);
        };
        ld4(x[0][0], 6);
#pragma unroll
        for (int s = 0; s < 10; s++) bd[s] = lds64(kt + (KT_C + 2 * g + 2 * t + 8 * s) * 4);
        mm4(x[0][0], 6);
        uint32_t e[4][4];
#pragma unroll
        for (int k = 1; k < 6; k++) {
#pragma unroll
            for (int j = 0; j < 4; j++) ld4(x[k & 1][j], 4 * k + 3 + j);
            ld_ug(k + 1);
            if (k == 3) {
#pragma unroll
                for (int s = 0; s < 8; s++) { b0[s] = lds32(KE + 32 * s); b1[s] = lds32(KE + 32 * s + 16); }
            }
            if (k > 1) ship(k);
#pragma unroll
            for (int j = 0; j < 4; j++) {
                mm4(x[k & 1][j], 4 * k + 3 + j);
                if (k == 3) { uint32_t v[4], z[4]; ld8(e[j], 8 + j); ld8(v, 12 + j); ld4(z, 30 - j); mm8(v, 12 + j, 12, 16); mm8(e[j], 8 + j, 8, 12); mm4(z, 30 - j); }
                if (k == 5) { ld8(e[j], 8 + j + p.zero); mm8(e[j], 8 + j, 12, 16); }
            }
        }
        ld_ug(7);
        ship(7 - R.value); ship(6 + R.value);
        };
        if (rank) stairs(std::integral_constant<int, 1>()); else stairs(std::integral_constant<int, 0>());
        if ((warp & 3) == 0) TSTAMP(14 + (warp >> 2)); else TSTAMP(21 + warp);
    }
}

constexpr int SF_WD = 73728;
constexpr int SF_RED = 49152;
constexpr int MU_HALF = 640, MU_STRIDE = 1344, SM_RAW = 98304, SM_UT = SM_RAW + 16384, SM_G = SM_UT + 16 * MU_STRIDE, SM_Y = 196608, SM_KT = 138880, SM_KW = SM_G - 49152;
constexpr int SF_XS = 221184;
constexpr int SF_MISC = SF_XS + 8 * 1168;
constexpr int SF_KG = SF_MISC - 10 * KG_STAGE;
constexpr int SF_WR = SF_KG - 2304;
constexpr int FB_X = 64, FB_KDONE = 72, FB_KEYS = 80, FB_FREE = 88  , FB_W = 104, FB_D = FB_W + 72, FB_MU = FB_D + 96, FB_MG = FB_MU + 8, FB_MT = FB_MU + 16  , FS_PART = 512, FS_TOK = 896, FS_BM = 1024;
enum { BAR_R = 7, BAR_GU = 8, BAR_RED = 9, BAR_R2 = 10, BAR_G = 12  , BAR_M = 15 };
static_assert(SF_KG % 128 == 0 && NPRE <= 8 && SM_KT + 4 * 2112 <= 147456 && SM_G + MU_STRIDE <= SF_WR - 4 * 9216 && SM_KW + 6 * 2112 >= SM_RAW && SM_KW + 12 * 2112 <= SM_UT, "layout");

__device__ __forceinline__ int mini_ch0(int f) { return 48 * f - (f < NW ? 1696 : 2304); }

__device__ __forceinline__ void ffn_front(const Params& p, const CUtensorMap* maps, uint32_t sb, int warp, int lane, int f, unsigned epoch) {
    const unsigned t0 = clock32();
    const int g = lane >> 2, t = lane & 3, mi = lane >> 3, r8 = lane & 7;
    const bool isx = f < NX;
    const int nrw = f < 52 ? 4 : 6, r0 = f < 52 ? 32 * f : 48 * f - 832;
    const int rw = warp < 12 ? 13 - warp : warp ^ (warp < 14 ? 10 : 15);
    const uint32_t bar_row = sb + SF_MISC  , bar_x = bar_row + FB_X;
    const uint32_t s_part = bar_row + FS_PART  , s_tok = bar_row + FS_TOK  ;
    const uint32_t rows = sb + SF_WR - 9216 * (rw + 1) - (rw & 4) * ((SF_WR - 6 * 9216) / 4);
    {
#pragma unroll 1
        for (int i = warp < 10 ? 30 : warp - 10; i < 30; i += 6) if (elect()) mbar_init(bar_x + 8 * i, i == 1 ? 4 + (f < NW) : i < 27 ? 1 : i == 27 ? 2 : 8);
        const uint32_t bytes = rw < 6 ? 9216 : 1152, dst = rw < 6 ? rows : sb + SF_WR + (rw & 1) * 1152;
        const __nv_bfloat16* src = rw < 6 ? p.u + (size_t)(r0 + 8 * rw) * DM : (rw & 1) ? p.gatew : p.wr;
        if (elect()) { mbar_init(bar_row + 8 * rw, 1); mbar_fence(); mbar_expect(bar_row + 8 * rw, bytes); }
        if (warp == 13) { sts32(s_part + 64 + lane * 4, 0); sts32(bar_row + FS_BM + lane * 4, 0); }
        bar_sync(0, NTHR);
        if (rw < nrw) until(t0, RDELAY);
        if (rw < nrw || rw >= 6) { if (elect()) bulk_g2s(dst, src, bytes, bar_row + 8 * rw); }
    }
    uint4* const kdst = p.s->keys + (lane >> 1) * 128 + 2 * f + (lane & 1);
    if (warp == 15) TSTAMP(1);

    if (warp == 12) {
        if (lane < 22) mbar_expect(bar_row + FB_W + 8 * lane, lane < 9 ? 24576 : isx ? 12288 : 16384);
        if (elect()) { prefetch_map(maps + 1); prefetch_map(maps + 2); prefetch_map(maps + (isx ? 3 : 5)); }
        unsigned tb = t0 + WDELAY;
        auto pieces = [&](int n, int end, uint32_t dst) {
#pragma unroll 1
            for (; n < end; n++, dst += 12288) {
                until(tb, 0); tb += WGAP;
                if (elect()) tma3d(dst, maps + 1 + (n & 1), 0, 64 * (n >> 1), 3 * f, bar_row + FB_W + 8 * (n >> 1));
            }
        };
        if (!isx) {
#pragma unroll 1
            for (int k = 0; k <= (f >= NW); k++) { until(t0, MDELAY + k * MGAP); if (elect()) tma4d(sb + SM_RAW - 49152 * k, maps + 5, mini_ch0(f) + 16 * k, 0, 0, 0, bar_row + FB_MU - 8 * k); }
            if (f >= NW) return;
        }
#pragma unroll 1
        for (int i = 0; i < 4; i++) {
            if (i == 1) { mbar_wait(bar_row + FB_KEYS); mbar_wait(bar_row + FB_KDONE); tb = clock32() + RESUME; }
            if (i == 3) mbar_wait(bar_row + FB_FREE);
            const int n = ((0x0c080000 + NPRE * 256) >> (8 * i)) & 255;
            pieces(n, ((0x120c0800 + NPRE) >> (8 * i)) & 255, sb + 12288 * (((0x000c0000 + NPRE * 256) >> (8 * i)) & 255));
        }
        TSTAMP(12);
        if (isx) {
#pragma unroll 1
            for (int i = 0; i < 12; i++) {
                const int n = (0x987610ba5432ull >> (4 * i)) & 15;
                if (i == 6) mbar_wait(bar_row + FB_FREE + 8);
                until(tb, 0); tb += DGAP;
                if (elect()) tma2d(sb + SF_WD + n * 12288, maps + 3, 32 * (f >> 1), 2304 * (f & 1) + 192 * n, bar_row + FB_D + 8 * n);
            }
            TSTAMP(13);
        }
    } else if (warp == 13) {
        const uint32_t tag = key_tag(epoch), par = (epoch & 1) ? 0u : 0x8000u;
        stg128(kdst, 0, 0, 0, 0);
        if (lane < 8 && isx && !(f & 1)) st_rlx32(&p.s->sel[32 * f + lane], 0);
        bar_sync(BAR_R, 32 * (nrw + 1));
        TSTAMP(3);
        {
            const uint32_t sg = fresh(s_part) + 192 + lane * 4;
            const uint32_t gb = pack_bf16(sigmoidf_(rbf(__uint_as_float(lds32(sg)))), sigmoidf_(rbf(__uint_as_float(lds32(sg + 128))))) | par | (par << 16);
            asm volatile("st.relaxed.gpu.global.u16 [%0], %1;" :: "l"(p.s->gate + r0 + lane), "h"((unsigned short)gb) : "memory");
            if (nrw > 4 && lane < 16) asm volatile("st.relaxed.gpu.global.u16 [%0], %1;" :: "l"(p.s->gate + r0 + 32 + lane), "h"((unsigned short)(gb >> 16)) : "memory");
        }
        bar_sync(BAR_R2, 32 * (nrw + 1));
        {
            const uint4 v = lds128(fresh(s_tok) + (lane & 1) * 16);
            asm volatile("st.relaxed.gpu.global.v4.u32 [%0], {%1,%2,%3,%4};" :: "l"(kdst), "r"(v.x | tag), "r"(v.y | tag), "r"(v.z | tag), "r"(v.w | tag) : "memory");
        }
        TSTAMP(4);
        if (lane == 0) { mbar_arrive(bar_row + FB_KEYS); mbar_expect(bar_x, 8 * 1152); }
        if (f >= NW) return;
        mbar_wait(bar_row + FB_KDONE);
        uint32_t k[16];
        const uint4* src = p.s->keys + (f & 15) * 128 + lane;
#pragma unroll 1
        for (int it = 0;; it++) {
            uint32_t bad = 0;
#pragma unroll
            for (int i = 0; i < 4; i++) {
                const uint4 x = ld_rlx128(src + (i < 3 || lane < 24 ? 32 * i : 64));
                k[i] = x.x; k[4 + i] = x.y; k[8 + i] = x.z; k[12 + i] = x.w;
                bad |= x.x ^ tag;
            }
            const bool ok = __all_sync(0xffffffffu, (bad & 0xf800u) == 0);
            if (ok) break;
            if (it > (1 << 20)) give_up();
        }
        TSTAMP(5);
        uint32_t key = 0, m = __reduce_max_sync(0xffffffffu, max(max(k[0], k[1]), max(k[2], k[3])));
#pragma unroll 2
        for (int r = 0; r < 8; r++) {
            bool pop[4];
#pragma unroll
            for (int i = 0; i < 4; i++) { pop[i] = k[i] == m; k[i] = pop[i] ? k[4 + i] : k[i]; }
            const uint32_t mn = __reduce_max_sync(0xffffffffu, max(max(k[0], k[1]), max(k[2], k[3])));
            if (elect()) bulk_g2s(sb + SF_XS + r * 1168, p.u + (size_t)key_row(m) * DM, 1152, bar_x);
#pragma unroll
            for (int i = 0; i < 4; i++) { k[4 + i] = pop[i] ? k[8 + i] : k[4 + i]; k[8 + i] = pop[i] ? k[12 + i] : k[8 + i]; k[12 + i] = pop[i] ? 0 : k[12 + i]; }
            if (r8 == r) key = m;
            m = mn;
        }
        const int row = key_row(key);
        sts32(s_tok + r8 * 8, row);
        TSTAMP(6);
        if (isx) {
            if (!(f & 1)) {
                __nv_bfloat16* o = p.out + (size_t)row * DM + 16 * f + 8 * mi;
                asm volatile("st.relaxed.gpu.global.v4.u32 [%0], {%1,%1,%1,%1};" :: "l"(o), "r"(0) : "memory");
                if (__any_sync(0xffffffffu, ld_rlx32(o) != 0)) give_up();
                if (lane < 8) st_rlx32(&p.s->sel[32 * f + lane], key);
            } else wait_sel(p, f >> 1, r8, tag);
            uint32_t gb;
#pragma unroll 1
            for (int it = 0;; it++) {
                asm volatile("ld.relaxed.gpu.global.u16 %0, [%1];" : "=r"(gb) : "l"(p.s->gate + row) : "memory");
                gb ^= par;
                if (!(gb & 0x8000u)) break;
                if (it > (1 << 20)) give_up();
            }
            const uint32_t rb = key ^ 0x80000000u, rv = (rb ^ (((int)rb >> 31) & 0x7fff0000u)) & 0xffff0000u;
            sts32(s_tok + r8 * 8 + 4, __float_as_uint(rbf(1.0f - bf_lo(gb)) * rbf(sigmoidf_(__uint_as_float(rv)))));
            __syncwarp();
            TSTAMP(7);
            bar_arrive(BAR_RED, 416);
        }
    } else {
        if (rw < nrw) {
            float c[3][4];
#pragma unroll
            for (int i = 0; i < 3; i++) { c[i][0] = c[i][1] = c[i][2] = c[i][3] = 0.f; }
            mbar_wait(bar_row + 48); mbar_wait(bar_row + 56);
            const uint32_t b = fresh(sb + SF_WR) + (g & 1) * 1152 + (g >> 2) * 64 + t * 16 + (g & 2) * 2;
            uint32_t w[18][2];
#pragma unroll
            for (int kb = 0; kb < 18; kb++) { const uint32_t o = ((kb & 1) ? b ^ 64 : b) + 128 * (kb >> 1); w[kb][0] = lds32(o); w[kb][1] = lds32(o + 8); }
            mbar_wait(bar_row + 8 * rw);
            if (warp == 15) TSTAMP(2);
            const uint32_t a = fresh(rows) + g * 1152 + (g & 1) * 64 + t * 16;
#pragma unroll
            for (int kb = 0; kb < 18; kb++) {
                const uint4 x = lds128(((kb & 1) ? a ^ 64 : a) + 128 * (kb >> 1));
                mma_bf(c[kb % 3], x.x, x.y, x.z, x.w, w[kb][0], w[kb][1]);
            }
            const float sr = c[0][0] + c[1][0] + c[2][0] + __shfl_down_sync(0xffffffffu, c[0][2] + c[1][2] + c[2][2], 1);
            const float sg = c[0][1] + c[1][1] + c[2][1] + __shfl_down_sync(0xffffffffu, c[0][3] + c[1][3] + c[2][3], 1);
            const uint32_t rb = pack_bf16(0.f, sr);
            if (t == 2 * (g & 1)) {
                sts32(s_part + (8 * rw + g) * 4, (rb ^ (((int)rb >> 31) & 0x7fff0000u) ^ 0x80000000u) | (uint32_t)(2047 - r0 - 8 * rw - g));
                sts32(s_part + 192 + (8 * rw + g) * 4, __float_as_uint(sg));
            }
            __syncwarp();
            bar_sync(BAR_R, 32 * (nrw + 1));
            const uint32_t sk = fresh(s_part), kk = lds32(sk + (8 * rw + r8) * 4);
            int n = 0;
#pragma unroll
            for (int i = 0; i < 3; i++) { const uint4 v = lds128(sk + mi * 48 + 16 * i); n += (v.x > kk) + (v.y > kk) + (v.z > kk) + (v.w > kk); }
            n += __shfl_xor_sync(0xffffffffu, n, 8); n += __shfl_xor_sync(0xffffffffu, n, 16);
            if (n < 8) sts32(s_tok + 4 * n, kk);
            __syncwarp();
            bar_arrive(BAR_R2, 32 * (nrw + 1));
        }
    }
}

__device__ __forceinline__ void ffn_work(const Params& p, uint32_t sb, int warp, int lane, int f, unsigned epoch) {
    const int g = lane >> 2, t = lane & 3, mi = lane >> 3, r8 = lane & 7;
    const bool isx = f < NX;
    const uint32_t bar_x = sb + SF_MISC + FB_X, bar_free = sb + SF_MISC + FB_FREE, bar_w = sb + SF_MISC + FB_W, bar_d = sb + SF_MISC + FB_D, s_tok = sb + SF_MISC + FS_TOK;
    uint32_t fr[24][4];
    auto pin = [&] {
#pragma unroll
        for (int i = 0; i < 24; i += 8) asm volatile("" :: "r"(fr[i][0]), "r"(fr[i + 1][0]), "r"(fr[i + 2][0]), "r"(fr[i + 3][0]), "r"(fr[i + 4][0]), "r"(fr[i + 5][0]), "r"(fr[i + 6][0]), "r"(fr[i + 7][0]) : "memory");
    };
    {
        const int j = (unsigned)(warp - 4) < 6, w = warp - (j ? 4 : warp < 4 ? 0 : 6);
        float ag[2][4], au[2][4];
#pragma unroll
        for (int i = 0; i < 2; i++) { ag[i][0] = ag[i][1] = ag[i][2] = ag[i][3] = 0.f; au[i][0] = au[i][1] = au[i][2] = au[i][3] = 0.f; }
        const uint32_t wb = sb + (w >> 1) * 4096 + (r8 + 8 * (mi >> 1)) * 64 + (((2 * (w & 1) + (mi & 1)) ^ (r8 >> 1)) << 4);
        const uint32_t xb = sb + SF_XS + r8 * 1168 + mi * 16;
        auto load = [&](int i, int n, int place) {
            mbar_wait(bar_w + 8 * n);
            const uint32_t wk = fresh(wb) + place * 24576;
#pragma unroll
            for (int s = 0; s < 4; s++) { ldsm4t(fr[8 * i + s], wk + 1024 * s); ldsm4t(fr[8 * i + 4 + s], wk + 1024 * s + 12288); }
        };
        auto mul = [&](int i, uint32_t xk) {
            uint32_t x[2][4];
            ldsm4(x[0], xk); ldsm4(x[1], xk + 64);
#pragma unroll
            for (int s = 0; s < 4; s++) {
                const uint32_t (&a)[4] = fr[8 * i + s], (&b)[4] = fr[8 * i + 4 + s];
                mma_bf(ag[s & 1], a[0], a[1], a[2], a[3], x[s >> 1][2 * (s & 1)], x[s >> 1][2 * (s & 1) + 1]);
                mma_bf(au[s & 1], b[0], b[1], b[2], b[3], x[s >> 1][2 * (s & 1)], x[s >> 1][2 * (s & 1) + 1]);
            }
        };
#pragma unroll
        for (int i = 0; i < 3; i++) load(i, 3 * j + i, (i ? 5 : 3) * j + i);
        pin();
        bar_sync(BAR_G + j, 192);
        if (w == 0 && lane == 0) mbar_arrive(bar_free + 8 * j);
        mbar_wait(bar_x);
        if (warp == 0) TSTAMP(8);
        {
            const uint32_t xk = fresh(xb) + 384 * j;
#pragma unroll
            for (int i = 0; i < 3; i++) { mul(i, (i ? fresh(xk) : xk) + 128 * i); if (i == 0) { asm volatile("" :: "f"(ag[0][0]), "f"(ag[1][0]), "f"(au[0][0]), "f"(au[1][0])); sts32(s_tok + 64, clock32()); } }
        }
#pragma unroll 1
        for (int n = 6 + j; n < 9; n += 2) { load(0, n, n - 6); mul(0, fresh(xb) + 128 * n); }
#pragma unroll
        for (int c = 0; c < 4; c++) { ag[0][c] += ag[1][c]; au[0][c] += au[1][c]; }
        if (j) {
            sts128(wb + 24576, __float_as_uint(ag[0][0]), __float_as_uint(ag[0][1]), __float_as_uint(ag[0][2]), __float_as_uint(ag[0][3]));
            sts128(wb + 25600, __float_as_uint(au[0][0]), __float_as_uint(au[0][1]), __float_as_uint(au[0][2]), __float_as_uint(au[0][3]));
        }
        bar_sync(BAR_GU, 384);
        if (!j) {
            const uint32_t sf = fresh(wb);
            const uint4 g1 = lds128(sf + 24576), u1 = lds128(sf + 25600);
            const uint32_t gs[4] = {g1.x, g1.y, g1.z, g1.w}, us[4] = {u1.x, u1.y, u1.z, u1.w};
            if (warp == 0) TSTAMP(9);
            float h[4];
#pragma unroll
            for (int c = 0; c < 4; c++) {
                const float gv = rbf(ag[0][c] + __uint_as_float(gs[c]));
                h[c] = rbf(gv * sigmoidf_(gv)) * rbf(au[0][c] + __uint_as_float(us[c]));
            }
            uint32_t h0, h1;
            asm("movmatrix.sync.aligned.m8n8.trans.b16 %0, %1;" : "=r"(h0) : "r"(pack_bf16(h[0], h[1])));
            asm("movmatrix.sync.aligned.m8n8.trans.b16 %0, %1;" : "=r"(h1) : "r"(pack_bf16(h[2], h[3])));
            if (h0 == 0) h0 = 0x8000u;
            asm volatile("{ .reg .b64 v; mov.b64 v, {%1, %2}; st.relaxed.gpu.global.b64 [%0], v; }" :: "l"(p.s->h + ((epoch & 1) * 288 + 6 * f + w) * 32 + lane), "r"(h0), "r"(h1) : "memory");
        }
        if (isx) {
            if (warp == 0) TSTAMP(10);
            const uint2* hsrc = p.s->h + ((epoch & 1) * 288 + 144 * (f & 1) + 12 * warp) * 32 + lane;
            uint2 hb[12];
            auto ldh = [&](int s) { asm volatile("ld.relaxed.gpu.global.v2.u32 {%0, %1}, [%2];" : "=r"(hb[s].x), "=r"(hb[s].y) : "l"(hsrc + 32 * s) : "memory"); };
#pragma unroll
            for (int s = 0; s < 12; s++) ldh(s);
#pragma unroll 1
            for (int it = 0;; it++) {
                bool again = false;
#pragma unroll
                for (int s = 0; s < 12; s += 2) if (__any_sync(0xffffffffu, min(hb[s].x, hb[s + 1].x) == 0)) { ldh(s); ldh(s + 1); again = true; }
                if (!again) break;
                if (it > (1 << 16)) give_up();
            }
            if (warp == 0) TSTAMP(11);
            mbar_wait(bar_d + 8 * warp);
            if (warp == 9) TSTAMP(14);
            float ad[2][2][4];
#pragma unroll
            for (int i = 0; i < 4; i++) { ad[i >> 1][i & 1][0] = ad[i >> 1][i & 1][1] = ad[i >> 1][i & 1][2] = ad[i >> 1][i & 1][3] = 0.f; }
            const uint32_t wd = fresh(sb) + SF_WD + warp * 12288 + (r8 + 8 * (mi >> 1)) * 64 + (((mi & 1) ^ (r8 >> 1)) << 4);
#pragma unroll
            for (int s = 0; s < 12; s++) {
                uint32_t a[4], b[4];
                ldsm4t(a, wd + 1024 * s); ldsm4t(b, (wd ^ 32) + 1024 * s);
                mma_bf(ad[0][s & 1], a[0], a[1], a[2], a[3], hb[s].x, hb[s].y);
                mma_bf(ad[1][s & 1], b[0], b[1], b[2], b[3], hb[s].x, hb[s].y);
            }
            const uint32_t rd = sb + SF_RED + warp * 1152 + (72 * t + g) * 4;
#pragma unroll
            for (int i = 0; i < 8; i++) sts32(rd + (i >> 2) * 64 + (i & 1) * 144 + ((i >> 1) & 1) * 32, __float_as_uint(ad[i >> 2][0][i & 3] + ad[i >> 2][1][i & 3]));
            bar_sync(BAR_RED, 416);
            if (warp < 4) {
                const int tid = 32 * warp + lane;
                const uint32_t rs = fresh(sb + SF_RED) + (tid >> 4) * 144 + (tid & 15) * 8;
                const uint2 tk = lds64(fresh(s_tok) + (tid >> 4) * 8);
                float x = 0.f, y = 0.f;
#pragma unroll
                for (int w = 0; w < 12; w++) { const uint2 v = lds64(rs + w * 1152); x += __uint_as_float(v.x); y += __uint_as_float(v.y); }
                asm volatile("red.relaxed.gpu.global.add.noftz.bf16x2 [%0], %1;" :: "l"(p.out + (size_t)tk.x * DM + 32 * (f >> 1) + 2 * (tid & 15)),
                             "r"(pack_bf16(x * __uint_as_float(tk.y), y * __uint_as_float(tk.y))) : "memory");
            }
            if (warp == 0) { TSTAMP(15); TFLUSH(); }
            asm volatile("exit;"); __builtin_unreachable();
        }
    }
}

__device__ __forceinline__ void fetch_k(const uint4* src, uint64_t (&v)[6], uint32_t a, uint32_t b) {
    asm volatile("{ .reg .pred p; setp.eq.u32 p, %7, %8; @p ld.relaxed.gpu.global.v2.u64 {%0,%1}, [%6]; @p ld.relaxed.gpu.global.v2.u64 {%2,%3}, [%6 + 512]; @p ld.relaxed.gpu.global.v2.u64 {%4,%5}, [%6 + 1024]; }"
                 : "+l"(v[0]), "+l"(v[1]), "+l"(v[2]), "+l"(v[3]), "+l"(v[4]), "+l"(v[5]) : "l"(src), "r"(a), "r"(b));
}
__device__ __forceinline__ uint32_t mini_conv(const Params& p, uint32_t sb, int warp, int lane, int f, unsigned epoch, uint64_t (&v)[6]) {
    const int g = lane >> 2, t = lane & 3, mi = lane >> 3, r8 = lane & 7;
    const uint32_t fb = sb + SF_MISC, kt = sb + (warp >= 12 ? SM_KT - 12 * 2112 : f < NW ? SM_KW + 2 * 2112 : SM_KW) + warp * 2112;
    const bool ism = f >= NW;
    const int ch0 = mini_ch0(f);
    uint32_t seq = 128, key;
    const uint4* src = p.s->kp + lane;
    auto hi = [&](int i) { return (uint32_t)(v[i] >> 32); };
    if (f >= (warp < 4 ? NW : NX)) {
    {
        const uint32_t c = 36 + (warp & 3) + 2 * (warp & 12), y = (uint32_t)((warp < 8 ? 0xa026802400000000ull : 0x2a2e00280080a22cull) >> ((8 * warp) & 48)) & 0xffff;
        seq = ism ? 0x101 * c - 0x400 : y + (warp & 1) * ((y >> 5) & 0x101);
        src += (ch0 + (seq & 31)) * 96;
    }
    if (seq & 32) {
        if (seq & 4) {
            const int q = (seq & 3) + ((seq >> 1) & 4);
            const uint32_t ab = sb - 3072 * (seq & 16), d = ab + SM_UT + g * MU_STRIDE + (8 + 4 * q + t) * 16;
            sts128(ab + SM_UT + (2 * q + (mi >> 1)) * MU_STRIDE + (mi & 1) * MU_HALF + r8 * 16, 0, 0, 0, 0);
            mbar_wait(fb + FB_MU - (seq & 16) / 2);
            if (warp == 15) TSTAMP(16);
            const uint32_t a = fresh(ab + SM_RAW) + q * 2048 + (8 * mi + 4 * (r8 & 1) + (r8 >> 1)) * 32 + ((r8 & 1) << 4);
            uint32_t x[4][4];
#pragma unroll
            for (int i = 0; i < 4; i++) ldsm4t(x[i], (i & 2 ? a ^ 16 : a) + 1024 * (i & 1));
#pragma unroll
            for (int i = 0; i < 4; i++) sts128(d + (i & 1) * MU_HALF + (i & 2) * 4 * MU_STRIDE, x[i][0], x[i][1], x[i][2], x[i][3]);
            __syncwarp();
            if (lane == 0) mbar_arrive(fb + FB_MT + (seq & 16) / 2);
        }
        mbar_wait(fb + FB_KDONE);
        fetch_k(src, v, warp < 4, 0);
        if ((warp | 2) == 7) { fetch_gates(p, (warp >> 1) & 1, lane, epoch, sb + SM_G + (lane & 1) * MU_HALF); __syncwarp(); if (lane == 0) mbar_arrive(fb + FB_MG); }
        if (warp >= 8) { mbar_wait(fb + FB_KEYS); mbar_wait(fb + FB_MT); }
        if (warp == TW) TSTAMP(17);
    }
    }
    const uint32_t lo = (mi & 1) * MU_HALF + (8 + r8) * 16 + (mi >> 1) * 128;
#pragma unroll 1
    do {
        const int c = seq & 31;
        if (seq & 32) {
#pragma unroll 1
        for (int it = 0; !__all_sync(0xffffffffu, ((hi(1) ^ k_tag(epoch)) | (hi(3) ^ k_tag(epoch)) | (hi(5) ^ k_tag(epoch)) | ((uint32_t)v[5] & p.zero)) < 65536); it++) {
            fetch_k(src, v, 0, 0);
            if (it > (1 << 20)) give_up();
        }
        mbar_wait(fb + FB_MT + (seq & 16) / 2);
        sts128(kt + t * 16, 0, 0, 0, 0);
        if (warp == TW) TSTAMP(seq >> 8 ? 7 : 10);
        const uint32_t w[12] = {(uint32_t)v[0], hi(0), (uint32_t)v[1], (uint32_t)v[2], hi(2), (uint32_t)v[3], (uint32_t)v[4], hi(4), 0, 0, 0, 0};
        k_tables<false>(fresh(kt), fresh(lane), w);
        }
        __syncwarp();
        if (seq & 128) ffn_work(p, sb, warp, fresh(lane), f, epoch);
        if (!(seq & 32)) return 0;
        const uint32_t ab = sb - 49152 * (c >> 4), kb = fresh(kt) + (16 + g - 2 * t) * 4, ub = fresh(ab + SM_UT + (c & 15) * MU_STRIDE) + lo;
        const uint32_t yd = ab + SM_Y + (c & 15) * 1056 + (c & 8) * 8 + lane * 16;
        uint32_t kp = kb, u1 = ub;
        if (warp == TW && !(seq >> 8)) TSTAMP(13);
        seq >>= 8;
        src += ((int)(seq & 31) - c) * 96;
#pragma unroll
        for (int i = 0; i < 6; i++) v[i] = 0;
        key = 0;
        float acc[6][4];
#pragma unroll
        for (int i = 0; i < 6; i++) { acc[i][0] = acc[i][1] = acc[i][2] = acc[i][3] = 0.f; }
        uint32_t a[4][4], b[2][2][4];
        auto lda = [&](int j, int o) { const uint32_t x = kp + 64 * o + 512 * j; a[j][2] = o ? a[j][1] ^ p.zero : lds32((kp ^ p.zero) + 512 * j - 32); a[j][0] = lds32(x); a[j][1] = lds32(x + 32); a[j][3] = a[j][0] ^ p.zero; };
        auto ldb = [&](int s, int o) { ldsm4(b[s][0], u1 - 16 * o); ldsm4(b[s][1], u1 + 256 - 16 * o); };
        ldb(0, 0);
#pragma unroll
        for (int j = 0; j < 4; j++) lda(j, 0);
#pragma unroll
        for (int s = 0; s < 8; s++) {
            if (s == 4) {
                const uint32_t e = seq | (__float_as_uint(acc[0][0]) & p.zero);
                fetch_k(src, v, e & 32, 32);
                asm volatile("{ .reg .pred p; setp.eq.u32 p, %2, 0; @p ld.relaxed.gpu.global.u32 %0, [%1]; }" : "+r"(key) : "l"(&p.s->sel[((ch0 + c) >> 5) * 64 + r8]), "r"(e));
            }
            if (s < 7) ldb(~s & 1, s + 1);
#pragma unroll
            for (int i = 0; i < 4; i++) {
                const int j = (i >> 1) + 2 * (i & 1);
#pragma unroll
                for (int mu = 3 - j; mu >= 0; mu--) mma_bf(acc[j + mu + (j & 2)], a[j][0], a[j][1], a[j][2], a[j][3], b[s & 1][mu >> 1][2 * (mu & 1)], b[s & 1][mu >> 1][2 * (mu & 1) + 1]);
                if (s < 7) lda(j, s + 1);
            }
        }
        if (warp == TW && !seq) TSTAMP(14);
        mbar_wait(fb + FB_MG);
#pragma unroll
        for (int e = 0; e < 4; e++) { acc[2][e] += acc[4][e]; acc[3][e] += acc[5][e]; }
        uint32_t ug[4][4];
#pragma unroll
        for (int i = 0; i < 2; i++) { ldsm4t(ug[i], ub + 256 * i); ldsm4t(ug[2 + i], fresh(sb + SM_G) + lo + 256 * i); }
#pragma unroll
        for (int i = 0; i < 2; i++) {
            const uint32_t (&u)[4] = ug[i], (&gg)[4] = ug[2 + i];
            sts128(yd + 512 * i, gmix(gg[0], acc[2 * i][0], acc[2 * i][1], u[0]), gmix(gg[1], acc[2 * i][2], acc[2 * i][3], u[1]),
                   gmix(gg[2], acc[2 * i + 1][0], acc[2 * i + 1][1], u[2]), gmix(gg[3], acc[2 * i + 1][2], acc[2 * i + 1][3], u[3]));
        }
        __syncwarp();
        if (warp == TW) TSTAMP(18 + (seq != 0));
    } while (seq);
    if (warp >= 12) TSTAMP(12 + warp);
    return key;
}
__device__ __forceinline__ void mini_out(const Params& p, const CUtensorMap* maps, uint32_t sb, int warp, int lane, int f, unsigned epoch, uint32_t key) {
    const int g = lane >> 2, t = lane & 3, mi = lane >> 3, r8 = lane & 7;
    const uint32_t fb = sb + SF_MISC;
    const bool ism = f >= NW;
    const int ch0 = mini_ch0(f);
    const int k = ism ? warp >> 3 : 0;
    uint32_t first = 1;
    if (lane == 0) asm volatile("atom.shared.exch.b32 %0, [%1], 1;" : "=r"(first) : "r"(fb + FS_BM + 64 + 4 * k) : "memory");
    if (!__all_sync(0xffffffffu, first)) {
        if (elect()) prefetch_map(maps + 4);
        const int row = key_row(wait_sel(p, (ch0 + 16 * k) >> 5, r8, key_tag(epoch), key));
        if (row < 512) asm volatile("red.shared.or.b32 [%0], %1;" :: "r"(fb + FS_BM + (row >> 5) * 4), "r"(1u << (row & 31)) : "memory");
    }
    const int m = warp & 7, dr = 128 * (g >> 2) + 32 * (t >> 1) + 16 * (g & 1) + 8 * ((g >> 1) & 1);
    const uint32_t y = SM_Y + ((r8 >> 1) & 1) * 8512 + (2 * mi + (r8 & 1)) * 1056 + (2 * m + (r8 >> 2)) * 16;
    const uint32_t so = (g >> 1) * 256 + (t >> 1) * 64 + (g & 1) * 32 + (t & 1) * 16;
    bar_sync(BAR_M - k, ism ? 256 : NTHR);
#pragma unroll 1
    for (int h = ism ? 0 : warp >> 3;; h++) {
        const int r0 = 256 * h + 64 * (m & 1) + (m >> 1), row = r0 + dr;
        const uint32_t bm = lds32(fresh(fb) + FS_BM + (row >> 5) * 4) >> (row & 31), ab = fresh(sb - 49152 * k + 512 * h), stg = ab + SM_UT + 2048 * m + 512 * h;
        uint32_t x[2][4];
        ldsm4t(x[0], ab + y); ldsm4t(x[1], ab + y + 256);
        if (warp == 0 && x[0][0] != 0x12345) TSTAMP(28);
        if (__any_sync(0xffffffffu, bm & 0x11u)) {
#pragma unroll
            for (int i = 0; i < 2; i++) store_or_add(p.out + (size_t)(row + 4 * i) * DM + ch0 + 16 * k + 8 * (t & 1), x[i], bm & (1u << (4 * i)));
        } else {
#pragma unroll
            for (int i = 0; i < 2; i++) sts128(stg + so + 128 * i, x[i][0], x[i][1], x[i][2], x[i][3]);
            asm volatile("fence.proxy.async.shared::cta;" ::: "memory");
            __syncwarp();
            if (elect()) store_rows(maps + 4, stg, ch0 + 16 * k, r0);
        }
        if (h >= ism) break;
    }
    if (elect()) { asm volatile("cp.async.bulk.commit_group;" ::: "memory"); asm volatile("cp.async.bulk.wait_group.read 0;" ::: "memory"); }
    if (warp == 8) TSTAMP(11);
    if (warp == 0) { TSTAMP(15); TFLUSH(); }
}

constexpr int SMEM_BYTES = 232448;
static_assert(SF_MISC + 1152 <= 232192, "layout");

struct Maps { CUtensorMap m[6]; };

__global__ void __cluster_dims__(2, 1, 1) __launch_bounds__(NTHR, 1)
fused_kernel(const Params p, const __grid_constant__ Maps maps) {
    extern __shared__ __align__(1024) uint8_t smem_raw[];
    uint32_t q[8];
    {
        const int b = blockIdx.x - NCONV, x = threadIdx.x, rc = 5 * b + (b & ~3) + 4 + (x >> 6);
        const int cv = (unsigned)b < NW ? 0 : -1, ca = (b < 0 ? 8 * b + DM : 48 * b - 2300) + ((x >> 5) & 3), cb = 2 * rc - (rc & 3) + 4;
        const uint32_t ch = (ca & cv) | (cb & ~cv), o = NST * ch + 2 * ((x & 31) + ((x >> (cv & 2)) & 32));
        const bool c = x < (cv ? 256 : 320);
        q[6] = ldg16_if(c, p.logdt + ch);
        q[2] = ldg32_if(c, p.Bre + o); q[3] = ldg32_if(c, p.Bim + o); q[4] = ldg32_if(c, p.Cre + o); q[5] = ldg32_if(c, p.Cim + o); q[0] = ldg32_if(c, p.Are + o); q[1] = ldg32_if(c, p.Aim + o);
        q[7] = ldg16_if(c, p.Dskip + ch);
    }
    const unsigned epoch = ld_rlx32(&p.s->epoch[blockIdx.x * 16 + (threadIdx.x >> 5)]);
    const uint32_t sb = __shfl_sync(0xffffffffu, smem_u32(smem_raw), 0);
    const int warp = __shfl_sync(0xffffffffu, threadIdx.x >> 5, 0), bid = __shfl_sync(0xffffffffu, blockIdx.x, 0);
    const int lane = __shfl_sync(0xffffffffu, threadIdx.x & 31, threadIdx.x);
    const bool conv = bid < NCONV;
    const int f = bid - NCONV;
    uint32_t w[12];
    uint64_t v[6];
    const bool four = (unsigned)f >= NW;
    if (warp < (four ? 8 : 10)) {
        const int half = four ? warp >> 2 : warp & 1, pr = four ? warp & 3 : warp >> 1;
        const int rc = 5 * f + (f & ~3) + 4 + pr;
        const uint32_t stage = sb + (conv ? SC_KG : SF_KG) + warp * KG_STAGE;
        uint4* const kp = p.s->kp + (four ? (conv ? 8 * bid : 48 * f - 2300) + pr : 2 * rc - (rc & 3) + 4) * 96 + lane;
        kgen(q, sb, half, stage, stage + (four ? 4 : 1) * KG_STAGE, 1 + pr, lane, w, [&] {
            sts128z_if(conv && lane < 20, sb + SC_KT + warp * KT_BYTES + lane * 16 + (lane < 4 ? 0 : lane < 14 ? 2048 : 2288));
            stg128z_if(!conv, kp + 64 * half); stg128z_if(!half && !conv, kp + 32);
            stg128z_if((unsigned)f < NW && warp < 6, (uint4*)(p.s->h + ((lane >> 4) * 288 + 6 * f + warp) * 32) + (lane & 15));
            if (conv) asm volatile("barrier.cluster.arrive.relaxed.aligned;" ::: "memory"); else bar_sync(0, NTHR);
        });
        if (!half) publish_k(kp, w, epoch, v);
        else for (int i = 0; i < 6; i++) v[i] = 0;
        if (conv) { conv_main(p, sb, warp, lane, bid, epoch, w); return; }
        {
            if (!half && lane == 0) mbar_arrive(sb + SF_MISC + FB_KDONE);
            if (warp == 0) TSTAMP(22);
            if (warp == 2) TSTAMP(23);
        }
    } else if (conv) {
        conv_aux(p, maps.m, sb, warp - 8, lane, bid, epoch);
        return;
    } else {
        ffn_front(p, maps.m, sb, warp, lane, f, epoch);
        for (int i = 0; i < 6; i++) v[i] = 0;
    }
    converged();
    next_epoch(p, epoch);
    if (warp >= 12 && f < NX) return;
    mini_out(p, maps.m, sb, warp, lane, f, epoch, mini_conv(p, sb, warp, __shfl_sync(0xffffffffu, lane, lane), f, epoch, v));
}

typedef CUresult (*EncodeFn)(CUtensorMap*, CUtensorMapDataType, cuuint32_t, void*, const cuuint64_t*, const cuuint64_t*, const cuuint32_t*, const cuuint32_t*,
                             CUtensorMapInterleave, CUtensorMapSwizzle, CUtensorMapL2promotion, CUtensorMapFloatOOBfill);

void make_map(EncodeFn fn, CUtensorMap* m, const void* base, int rank, const cuuint64_t* dims, const cuuint64_t* strides, const cuuint32_t* box, CUtensorMapSwizzle sw) {
    const cuuint32_t es[5] = {1, 1, 1, 1, 1};
    fn(m, CU_TENSOR_MAP_DATA_TYPE_BFLOAT16, rank, (void*)base, dims, strides, box, es, CU_TENSOR_MAP_INTERLEAVE_NONE, sw,
       CU_TENSOR_MAP_L2_PROMOTION_NONE, CU_TENSOR_MAP_FLOAT_OOB_FILL_NONE);
}

}

extern "C" void kernel_launch(void* const* d_in, const int* in_sizes, int n_in, void* d_out, int out_size) {
    (void)in_sizes; (void)n_in; (void)out_size;
    static EncodeFn fn = nullptr;
    static void* scratch = nullptr;
    if (!fn) {
        void* ptr = nullptr; cudaDriverEntryPointQueryResult qr;
        cudaGetDriverEntryPoint("cuTensorMapEncodeTiled", &ptr, cudaEnableDefault, &qr);
        fn = (EncodeFn)ptr;
        cudaGetSymbolAddress(&scratch, g_scratch);
        cudaFuncSetAttribute(fused_kernel, cudaFuncAttributeMaxDynamicSharedMemorySize, SMEM_BYTES);
    }
    typedef const __nv_bfloat16* bp;
    Params p;
    p.u = (bp)d_in[0]; p.Are = (bp)d_in[1]; p.Aim = (bp)d_in[2]; p.Bre = (bp)d_in[3]; p.Bim = (bp)d_in[4]; p.Cre = (bp)d_in[5]; p.Cim = (bp)d_in[6];
    p.logdt = (bp)d_in[7]; p.Dskip = (bp)d_in[8]; p.wr = (bp)d_in[10]; p.gatew = (bp)d_in[14];
    p.out = (__nv_bfloat16*)d_out; p.s = (Scratch*)scratch; p.zero = 0;
    Maps maps;
    {
        const cuuint64_t dims[4] = {DM, 4, 16, 32}, strides[3] = {16 * DM * 2, DM * 2, 64 * DM * 2};
        const cuuint32_t box[4] = {16, 4, 16, 2};
        make_map(fn, &maps.m[0], d_in[0], 4, dims, strides, box, CU_TENSOR_MAP_SWIZZLE_32B);
        const cuuint32_t box2[4] = {16, 4, 16, 8};
        make_map(fn, &maps.m[5], d_in[0], 4, dims, strides, box2, CU_TENSOR_MAP_SWIZZLE_32B);
    }
    for (int i = 0; i < 2; i++) {
        const cuuint64_t dims[3] = {32, DM, FF / 32}, strides[2] = {FF * 2, 64};
        const cuuint32_t box[3] = {32, 64, 3};
        make_map(fn, &maps.m[1 + i], d_in[11 + i], 3, dims, strides, box, CU_TENSOR_MAP_SWIZZLE_64B);
    }
    {
        const cuuint64_t dims[2] = {DM, FF}, strides[1] = {DM * 2};
        const cuuint32_t box[2] = {32, 192};
        make_map(fn, &maps.m[3], d_in[13], 2, dims, strides, box, CU_TENSOR_MAP_SWIZZLE_64B);
    }
    {
        const cuuint64_t dims[5] = {DM, 4, 4, 2, L_SEQ}, strides[4] = {16 * DM * 2, 4 * DM * 2, 128 * DM * 2, DM * 2};
        const cuuint32_t box[5] = {16, 4, 4, 2, 1};
        make_map(fn, &maps.m[4], d_out, 5, dims, strides, box, CU_TENSOR_MAP_SWIZZLE_NONE);
    }
    fused_kernel<<<NCTA, NTHR, SMEM_BYTES>>>(p, maps);
}
```

```cpp
#include <cuda_runtime.h>
#include <cuda_bf16.h>
#include <cuda_fp16.h>
#include <cuda.h>
#include <stdint.h>
#include <type_traits>

#define RESUME 300
#define MDELAY 2000
#define MGAP 0
#define DUN 1
#define KPOLL 500
#define DPA 7
#define DPB 9
#define RDELAY 900
#define WDELAY 2000
#define WGAP 290
#define NPRE 7
#define DGAP 260
namespace {
constexpr int DUNR = DUN;

constexpr int DM = 576, NST = 128, FF = 4608, L_SEQ = 2048;
constexpr int NCONV = 72, NX = 36, NW = 48, NCTA = 132, NTHR = 512;

struct __align__(128) Scratch {
    unsigned epoch[NCTA * 16];
    uint4 keys[16 * 128];
    uint32_t sel[18 * 64];
    uint16_t gate[L_SEQ];
    uint2 h[2 * 288 * 32];
    uint4 kp[DM * 96];
};
__device__ Scratch g_scratch;
#define TFLUSH()
#define TSTAMP(i)
#define TW 12

struct Params {
    const __nv_bfloat16 *Are, *Aim, *Bre, *Bim, *Cre, *Cim, *logdt, *Dskip, *u, *wr, *gatew;
    __nv_bfloat16* out;
    Scratch* s;
    uint32_t zero;
};

__device__ __forceinline__ void give_up() { asm volatile("trap; exit;"); __builtin_unreachable(); }
__device__ __forceinline__ void converged() { __syncwarp(); asm volatile("{ .reg .b32 t; mov.b32 t, 0; movmatrix.sync.aligned.m8n8.trans.b16 t, t; }" ::: "memory"); }
__device__ __forceinline__ bool elect() { uint32_t r; asm volatile("{ .reg .pred p; elect.sync _|p, 0xffffffff; selp.u32 %0, 1, 0, p; }" : "=r"(r)); return r; }
__device__ __forceinline__ uint32_t smem_u32(const void* p) { return (uint32_t)__cvta_generic_to_shared(p); }
__device__ __forceinline__ uint32_t pack_bf16(float lo, float hi) { uint32_t r; asm("cvt.rn.bf16x2.f32 %0, %1, %2;" : "=r"(r) : "f"(hi), "f"(lo)); return r; }
__device__ __forceinline__ uint32_t pack_f16(float lo, float hi) { uint32_t r; asm("cvt.rn.f16x2.f32 %0, %1, %2;" : "=r"(r) : "f"(hi), "f"(lo)); return r; }
__device__ __forceinline__ float bf_lo(uint32_t w) { return __uint_as_float(w << 16); }
__device__ __forceinline__ float bf_hi(uint32_t w) { return __uint_as_float(w & 0xffff0000u); }
__device__ __forceinline__ float rbf(float x) { return bf_lo(pack_bf16(x, 0.f)); }
__device__ __forceinline__ uint32_t badd2(uint32_t a, uint32_t b) { uint32_t r; asm("add.rn.bf16x2 %0, %1, %2;" : "=r"(r) : "r"(a), "r"(b)); return r; }
__device__ __forceinline__ uint32_t bsub2(uint32_t a, uint32_t b) { uint32_t r; asm("sub.rn.bf16x2 %0, %1, %2;" : "=r"(r) : "r"(a), "r"(b)); return r; }
__device__ __forceinline__ uint32_t gmix(uint32_t ng, float ny0, float ny1, uint32_t u) {
    uint32_t r; asm("{ .reg .b32 t; fma.rn.bf16x2 t, %1, %3, %3; fma.rn.bf16x2 %0, %1, %2, t; }" : "=r"(r) : "r"(ng), "r"(pack_bf16(ny0, ny1)), "r"(u)); return r;
}
__device__ __forceinline__ void mma_bf(float (&c)[4], uint32_t a0, uint32_t a1, uint32_t a2, uint32_t a3, uint32_t b0, uint32_t b1) {
    asm("mma.sync.aligned.m16n8k16.row.col.f32.bf16.bf16.f32 {%0,%1,%2,%3}, {%4,%5,%6,%7}, {%8,%9}, {%0,%1,%2,%3};"
        : "+f"(c[0]), "+f"(c[1]), "+f"(c[2]), "+f"(c[3]) : "r"(a0), "r"(a1), "r"(a2), "r"(a3), "r"(b0), "r"(b1));
}
__device__ __forceinline__ void mma_bf8(float (&c)[4], uint32_t a0, uint32_t a1, uint32_t b0) {
    asm("mma.sync.aligned.m16n8k8.row.col.f32.bf16.bf16.f32 {%0,%1,%2,%3}, {%4,%5}, {%6}, {%0,%1,%2,%3};"
        : "+f"(c[0]), "+f"(c[1]), "+f"(c[2]), "+f"(c[3]) : "r"(a0), "r"(a1), "r"(b0));
}
__device__ __forceinline__ void mma_h(float (&c)[4], uint32_t a0, uint32_t a1, uint32_t a2, uint32_t a3, uint32_t b0, uint32_t b1) {
    asm("mma.sync.aligned.m16n8k16.row.col.f32.f16.f16.f32 {%0,%1,%2,%3}, {%4,%5,%6,%7}, {%8,%9}, {%0,%1,%2,%3};"
        : "+f"(c[0]), "+f"(c[1]), "+f"(c[2]), "+f"(c[3]) : "r"(a0), "r"(a1), "r"(a2), "r"(a3), "r"(b0), "r"(b1));
}
__device__ __forceinline__ uint32_t fresh(uint32_t a) { asm volatile("" : "+r"(a) :: "memory"); return a; }
__device__ __forceinline__ uint32_t lds32(uint32_t a) { uint32_t v; asm("ld.shared.u32 %0, [%1];" : "=r"(v) : "r"(a)); return v; }
__device__ __forceinline__ uint2 lds64(uint32_t a) { uint2 v; asm("ld.shared.v2.u32 {%0,%1}, [%2];" : "=r"(v.x), "=r"(v.y) : "r"(a)); return v; }
__device__ __forceinline__ uint4 lds128(uint32_t a) { uint4 v; asm("ld.shared.v4.u32 {%0,%1,%2,%3}, [%4];" : "=r"(v.x), "=r"(v.y), "=r"(v.z), "=r"(v.w) : "r"(a)); return v; }
__device__ __forceinline__ void ldsm4(uint32_t (&r)[4], uint32_t a) {
    asm("ldmatrix.sync.aligned.m8n8.x4.shared.b16 {%0,%1,%2,%3}, [%4];" : "=r"(r[0]), "=r"(r[1]), "=r"(r[2]), "=r"(r[3]) : "r"(a));
}
__device__ __forceinline__ void ldsm4t(uint32_t (&r)[4], uint32_t a) {
    asm("ldmatrix.sync.aligned.m8n8.x4.trans.shared.b16 {%0,%1,%2,%3}, [%4];" : "=r"(r[0]), "=r"(r[1]), "=r"(r[2]), "=r"(r[3]) : "r"(a));
}
__device__ __forceinline__ void sts16(uint32_t a, uint32_t v) { asm volatile("st.shared.u16 [%0], %1;" :: "r"(a), "h"((unsigned short)v) : "memory"); }
__device__ __forceinline__ void sts32(uint32_t a, uint32_t v) { asm volatile("st.shared.u32 [%0], %1;" :: "r"(a), "r"(v) : "memory"); }
__device__ __forceinline__ void sts64(uint32_t a, uint32_t x, uint32_t y) { asm volatile("st.shared.v2.u32 [%0], {%1,%2};" :: "r"(a), "r"(x), "r"(y) : "memory"); }
__device__ __forceinline__ void sts128(uint32_t a, uint32_t x, uint32_t y, uint32_t z, uint32_t w) {
    asm volatile("st.shared.v4.u32 [%0], {%1,%2,%3,%4};" :: "r"(a), "r"(x), "r"(y), "r"(z), "r"(w) : "memory");
}
__device__ __forceinline__ void st_async128(uint32_t a, uint32_t x, uint32_t y, uint32_t z, uint32_t w, uint32_t bar) {
    asm volatile("st.async.weak.shared::cluster.mbarrier::complete_tx::bytes.v4.b32 [%0], {%1,%2,%3,%4}, [%5];" :: "r"(a), "r"(x), "r"(y), "r"(z), "r"(w), "r"(bar) : "memory");
}
__device__ __forceinline__ void mbar_init(uint32_t b, uint32_t cnt) { asm volatile("mbarrier.init.shared::cta.b64 [%0], %1;" :: "r"(b), "r"(cnt) : "memory"); }
__device__ __forceinline__ void mbar_fence() { asm volatile("fence.mbarrier_init.release.cluster;" ::: "memory"); }
__device__ __forceinline__ void mbar_expect(uint32_t b, uint32_t bytes) { asm volatile("mbarrier.arrive.expect_tx.shared::cta.b64 _, [%0], %1;" :: "r"(b), "r"(bytes) : "memory"); }
__device__ __forceinline__ void mbar_arrive(uint32_t b) { asm volatile("mbarrier.arrive.shared::cta.b64 _, [%0];" :: "r"(b) : "memory"); }
__device__ __forceinline__ void mbar_wait(uint32_t b, uint32_t parity = 0) {
    asm volatile("{ .reg .pred p; .reg .u32 n; mov.u32 n, 0;\n"
                 "LW: mbarrier.try_wait.parity.shared::cta.b64 p, [%0], %1; @p bra LD; add.u32 n, n, 1; setp.lt.u32 p, n, 65536; @p bra LW; trap;\n"
                 "LD: }" :: "r"(b), "r"(parity) : "memory");
}
__device__ __forceinline__ void mbar_wait_cluster(uint32_t b) {
    asm volatile("{ .reg .pred p; .reg .u32 n; mov.u32 n, 0;\n"
                 "LW: mbarrier.try_wait.parity.acquire.cluster.shared::cta.b64 p, [%0], 0; @p bra LD; add.u32 n, n, 1; setp.lt.u32 p, n, 65536; @p bra LW; trap;\n"
                 "LD: }" :: "r"(b) : "memory");
}
__device__ __forceinline__ void tma2d(uint32_t dst, const CUtensorMap* m, int c0, int c1, uint32_t bar) {
    asm volatile("cp.async.bulk.tensor.2d.shared::cluster.global.mbarrier::complete_tx::bytes [%0], [%1, {%3, %4}], [%2];"
                 :: "r"(dst), "l"(m), "r"(bar), "r"(c0), "r"(c1) : "memory");
}
__device__ __forceinline__ void tma3d(uint32_t dst, const CUtensorMap* m, int c0, int c1, int c2, uint32_t bar) {
    asm volatile("cp.async.bulk.tensor.3d.shared::cluster.global.mbarrier::complete_tx::bytes [%0], [%1, {%3, %4, %5}], [%2];"
                 :: "r"(dst), "l"(m), "r"(bar), "r"(c0), "r"(c1), "r"(c2) : "memory");
}
__device__ __forceinline__ void tma4d(uint32_t dst, const CUtensorMap* m, int c0, int c1, int c2, int c3, uint32_t bar) {
    asm volatile("cp.async.bulk.tensor.4d.shared::cluster.global.mbarrier::complete_tx::bytes [%0], [%1, {%3, %4, %5, %6}], [%2];"
                 :: "r"(dst), "l"(m), "r"(bar), "r"(c0), "r"(c1), "r"(c2), "r"(c3) : "memory");
}
__device__ __forceinline__ void bulk_g2s(uint32_t dst, const void* src, uint32_t bytes, uint32_t bar) {
    asm volatile("cp.async.bulk.shared::cluster.global.mbarrier::complete_tx::bytes [%0], [%1], %2, [%3];"
                 :: "r"(dst), "l"(src), "r"(bytes), "r"(bar) : "memory");
}
__device__ __forceinline__ uint32_t mapa(uint32_t a, uint32_t rank) { uint32_t r; asm("mapa.shared::cluster.u32 %0, %1, %2;" : "=r"(r) : "r"(a), "r"(rank)); return r; }
__device__ __forceinline__ void prefetch_map(const CUtensorMap* m) { asm volatile("prefetch.tensormap [%0];" :: "l"(m) : "memory"); }
__device__ __forceinline__ void bar_sync(int id, int n) { asm volatile("bar.sync %0, %1;" :: "r"(id), "r"(n) : "memory"); }
__device__ __forceinline__ void bar_arrive(int id, int n) { asm volatile("bar.arrive %0, %1;" :: "r"(id), "r"(n) : "memory"); }
__device__ __forceinline__ uint32_t ldg16_if(bool c, const void* p) { uint32_t v; asm volatile("{ .reg .pred p; setp.ne.u32 p, %2, 0; @p ld.global.nc.u16 %0, [%1]; }" : "=r"(v) : "l"(p), "r"((uint32_t)c)); return v; }
__device__ __forceinline__ uint32_t ldg32_if(bool c, const void* p) { uint32_t v; asm volatile("{ .reg .pred p; setp.ne.u32 p, %2, 0; @p ld.global.nc.u32 %0, [%1]; }" : "=r"(v) : "l"(p), "r"((uint32_t)c)); return v; }
__device__ __forceinline__ uint32_t ld_rlx32(const void* p) { uint32_t v; asm volatile("ld.relaxed.gpu.global.u32 %0, [%1];" : "=r"(v) : "l"(p) : "memory"); return v; }
__device__ __forceinline__ uint4 ld_rlx128(const void* p) {
    uint4 v; asm volatile("ld.relaxed.gpu.global.v4.u32 {%0,%1,%2,%3}, [%4];" : "=r"(v.x), "=r"(v.y), "=r"(v.z), "=r"(v.w) : "l"(p) : "memory"); return v;
}
__device__ __forceinline__ void st_rlx32(void* p, uint32_t v) { asm volatile("st.relaxed.gpu.global.u32 [%0], %1;" :: "l"(p), "r"(v) : "memory"); }
__device__ __forceinline__ void stg128(void* p, uint32_t x, uint32_t y, uint32_t z, uint32_t w) {
    asm volatile("st.global.v4.u32 [%0], {%1,%2,%3,%4};" :: "l"(p), "r"(x), "r"(y), "r"(z), "r"(w) : "memory");
}
__device__ __forceinline__ void next_epoch(const Params& p, unsigned e) { if ((threadIdx.x & 31) == 0) p.s->epoch[blockIdx.x * 16 + (threadIdx.x >> 5)] = e + 1; }
__device__ __forceinline__ void sts128z_if(bool c, uint32_t a) { asm volatile("{ .reg .pred p; setp.ne.u32 p, %1, 0; @p st.shared.v4.u32 [%0], {%2,%2,%2,%2}; }" :: "r"(a), "r"((uint32_t)c), "r"(0) : "memory"); }
__device__ __forceinline__ void stg128z_if(bool c, void* a) { asm volatile("{ .reg .pred p; setp.ne.u32 p, %1, 0; @p st.global.v4.u32 [%0], {%2,%2,%2,%2}; }" :: "l"(a), "r"((uint32_t)c), "r"(0) : "memory"); }
__device__ __forceinline__ unsigned clock32() { unsigned c; asm volatile("mov.u32 %0, %clock;" : "=r"(c) :: "memory"); return c; }
__device__ __forceinline__ void until(unsigned t0, int c) { while ((int)(clock32() - t0) < c) { } }
__device__ __forceinline__ float sigmoidf_(float x) { return __fdividef(1.0f, 1.0f + __expf(-x)); }
__device__ __forceinline__ uint32_t key_tag(unsigned epoch) { return ((epoch & 15u) | 16u) << 11; }
__device__ __forceinline__ int key_row(uint32_t key) { return 2047 - (int)(key & 2047u); }
__device__ __forceinline__ uint32_t wait_sel(const Params& p, int s32, int r8, uint32_t tag, uint32_t k = 0) {
#pragma unroll 1
    for (int it = 0; !__all_sync(0xffffffffu, (k & 0xf800u) == tag); it++) {
        k = ld_rlx32(&p.s->sel[s32 * 64 + r8]);
        if (it > (1 << 20)) give_up();
    }
    return k;
}

struct cplx { float re, im; };
__device__ __forceinline__ cplx csq(cplx a) { cplx r; r.re = a.re * a.re - a.im * a.im; r.im = (a.re * a.im) * 2.f; return r; }
__device__ __forceinline__ cplx cexpk(float ar, float ai, float k) {
    float mag, s, c;
    asm("ex2.approx.ftz.f32 %0, %1;" : "=f"(mag) : "f"(ar * (k * 1.4426950408889634f)));
    const float r = ai * k;
    asm("sin.approx.ftz.f32 %0, %1;" : "=f"(s) : "f"(r));
    asm("cos.approx.ftz.f32 %0, %1;" : "=f"(c) : "f"(r));
    cplx o; o.re = mag * c; o.im = mag * s; return o;
}
struct h2c { uint32_t re, im; };
__device__ __forceinline__ h2c cmul_cd(h2c v, __half2 c, __half2 d) {
    const __half2 r = *(const __half2*)&v.re, i = *(const __half2*)&v.im;
    const __half2 x = __hfma2(__hneg2(i), d, __hmul2(r, c)), y = __hfma2(i, c, __hmul2(r, d));
    h2c o; o.re = *(const uint32_t*)&x; o.im = *(const uint32_t*)&y; return o;
}
__device__ __forceinline__ h2c cmul_s(h2c v, uint32_t s) { const __half2 h = *(const __half2*)&s; return cmul_cd(v, __low2half2(h), __high2half2(h)); }
__device__ __forceinline__ h2c cmul_sc(h2c v, uint32_t s) {
    const __half2 h = *(const __half2*)&s, c = __low2half2(h), d = __high2half2(h), r = *(const __half2*)&v.re, i = *(const __half2*)&v.im;
    const __half2 x = __hfma2(i, d, __hmul2(r, c)), y = __hfma2(__hneg2(r), d, __hmul2(i, c));
    h2c o; o.re = *(const uint32_t*)&x; o.im = *(const uint32_t*)&y; return o;
}
__device__ __forceinline__ h2c cmul_vc(h2c v, uint32_t s) {
    const __half2 h = *(const __half2*)&s, c = __low2half2(h), d = __high2half2(h), r = *(const __half2*)&v.re, i = *(const __half2*)&v.im;
    const __half2 x = __hfma2(i, d, __hmul2(r, c)), y = __hfma2(__hneg2(i), c, __hmul2(r, d));
    h2c o; o.re = *(const uint32_t*)&x; o.im = *(const uint32_t*)&y; return o;
}

constexpr int UT_HALF = 2560, UT_STRIDE = 4768, GT_HALF = 2240;
__device__ __forceinline__ uint32_t swz(uint32_t x) { return x ^ ((x >> 2) & 64); }
__device__ __forceinline__ int col(int n) { return (n >> 1) + 4 * (n & 1); }
constexpr int KT_T = 542, KT_C = 552, KT_D = 645, KT_BYTES = 720 * 4;
constexpr int VC_OFF = 80, VE_BASE = 1616;
constexpr int V_STRIDE = (1616 + 1024) * 4 + 80;
constexpr int KG_STAGE = 5248;
constexpr int Y_CS = 2080, Y_RS = 8 * Y_CS + 64;

constexpr int SC_RT = 0;
constexpr int SC_UT = 33408;
constexpr int SC_KG = SC_UT + 8 * UT_STRIDE;
constexpr int SC_KT = SC_KG + 8 * KG_STAGE;
constexpr int SC_GT = SC_KT + 8 * KT_BYTES;
constexpr int SC_V = SC_GT + 4448;
constexpr int SC_MISC = SC_V + 8 * V_STRIDE;
static_assert(V_STRIDE % 128 == 16 && 2 * Y_RS <= SC_UT && SC_UT % 128 == 0 && SC_KG % 128 == 0, "layout");
static_assert(SC_MISC % 16 == 0 && SC_MISC + 512 <= 232192, "layout");

__device__ __forceinline__ void window_task(uint32_t s0, uint32_t s1, uint32_t d0, uint32_t d1, int k) {
    float S[51], s = 0.f;
    uint32_t w[28];
#pragma unroll
    for (int i = 0; i < 7; i++) {
        const uint4 v = lds128((i < 3 ? s0 : s1 - 32) + ((i & 1) ? 0 : UT_HALF) + ((i + 1) >> 1) * 16);
        w[4 * i] = v.x; w[4 * i + 1] = v.y; w[4 * i + 2] = v.z; w[4 * i + 3] = v.w;
    }
    auto sums = [&](int lo, int hi) {
#pragma unroll
        for (int i = lo; i < hi; i++) { const float x = (i & 1) ? bf_hi(w[i >> 1]) : bf_lo(w[i >> 1]); s = i > 3 ? s + x : x; S[i] = s; }
    };
    auto put = [&](int off, int b, int o0, int o1, int o2) {
        auto v = [&](int i) { i += 16 * b; return pack_bf16(S[o0 + i] - S[o1 + i], S[o1 + i] - S[o2 + i]); };
#pragma unroll
        for (int i = 0; i < 8; i += 2) sts128((i & 4 ? d1 : d0) + 4 * off + 64 * b + 8 * (i & 2), v(i), v(i + 8), v(i + 1), v(i + 9));
    };
    S[2] = 0.f;
    sums(3, 26); put(VC_OFF - 16, 0, 10, 5, 2);
    if (k == 12) return;
    sums(26, 42); put(VC_OFF - 16, 1, 10, 5, 2);
    if (k < 8) { put(VE_BASE, 0, 19, 12, 3); sums(42, 51); put(VE_BASE, 1, 19, 12, 3); }
}

template <class F>
__device__ __forceinline__ void kgen(const uint32_t (&q)[8], uint32_t sb, int half, uint32_t stage, uint32_t pstage, int barid, int lane, uint32_t (&w)[12], F shadow) {
    const int t = lane & 3, mi = lane >> 3, r8 = lane & 7;
    {
        const uint32_t pAr = q[0], pAi = q[1], pBr = q[2], pBi = q[3], pCr = q[4], pCi = q[5], pDt = q[6], pD = q[7];
        const uint32_t wb = fresh(stage + lane * 16), za = fresh(stage + 5120 + ((lane >> 1) & 3) * 16 + mi * 4 + (lane & 1) * 2), zr = fresh(stage + 5120 + t * 16);
        const uint32_t oA = fresh(stage + (mi & 1) * 1024 + (mi >> 1) * 512 + r8 * 16), oB = fresh(stage + 2048 + mi * 512 + r8 * 16), oC = fresh(stage + 4096 + (mi & 1) * 512 + (mi >> 1) * 128 + r8 * 16);
        float acc[6][4];
#pragma unroll
        for (int a = 0; a < 6; a++) { acc[a][0] = acc[a][1] = acc[a][2] = acc[a][3] = 0.f; asm volatile("" : "+f"(acc[a][0]), "+f"(acc[a][1]), "+f"(acc[a][2]), "+f"(acc[a][3])); }
        shadow();
        sts32(zr, clock32());
        const float dt = rbf(__expf(bf_lo(pDt)));
        float ar = dt * bf_lo(pAr), ai = dt * bf_lo(pAi), ar1 = dt * bf_hi(pAr), ai1 = dt * bf_hi(pAi);
        float wr, wi, wr1, wi1;
        { const float br = dt * bf_lo(pBr), bi = dt * bf_lo(pBi), cr = bf_lo(pCr), ci = bf_lo(pCi); wr = cr * br - ci * bi; wi = cr * bi + ci * br; }
        { const float br = dt * bf_hi(pBr), bi = dt * bf_hi(pBi), cr = bf_hi(pCr), ci = bf_hi(pCi); wr1 = cr * br - ci * bi; wi1 = cr * bi + ci * br; }
        const uint32_t ex = max(__reduce_max_sync(0xffffffffu, __float_as_uint(fmaxf(fmaxf(fabsf(wr), fabsf(wi)), fmaxf(fabsf(wr1), fabsf(wi1))))) >> 23, 14u);
        const float scl = __uint_as_float((267u - ex) << 23);
        uint32_t W = pack_f16(wr * scl, wi * -scl);
        const uint32_t W1 = pack_f16(wr1 * scl, wi1 * -scl);
        if (threadIdx.x < 32) TSTAMP(20);

#pragma unroll 1
        for (int r = 0; r < 2; r++) {
            const cplx z1 = cexpk(ar, ai, 1.f), z64 = cexpk(ar, ai, 64.f);
            const cplx z2 = csq(z1), z4 = csq(z2), z8 = csq(z4), z16 = csq(z8), z32 = csq(z16);
            const cplx z128 = csq(z64), z256 = csq(z128), z512 = csq(z256);
            auto put = [&](int grp, h2c a, h2c b, h2c c, h2c d) { sts128(wb + grp * 1024, a.re, b.re, c.re, d.re); sts128(wb + grp * 1024 + 512, a.im, b.im, c.im, d.im); };
            {
                const uint32_t s4 = pack_f16(z4.re, z4.im), s256 = pack_f16(z256.re, z256.im), s512 = pack_f16(z512.re, z512.im);
                auto mix = [](h2c a, h2c b, uint32_t sel) { return h2c{__byte_perm(a.re, b.re, sel), __byte_perm(a.im, b.im, sel)}; };
                const h2c c10 = cmul_vc(h2c{pack_f16(z1.re, 1.f), pack_f16(z1.im, 0.f)}, W), c32 = cmul_sc(c10, pack_f16(z2.re, z2.im)), c54 = cmul_sc(c10, s4);
                put(2, c10, c32, c54, cmul_sc(c32, s4));
                const h2c d20 = cmul_sc(mix(c32, c10, 0x7632), s256), e04 = cmul_sc(mix(c10, c54, 0x7632), s512), f04 = cmul_sc(e04, s256);
                put(3, d20, cmul_sc(d20, s4), e04, f04);
                const h2c ef = mix(e04, f04, 0x5410), gh = cmul_sc(ef, s512), g8 = cmul_sc(gh, pack_f16(z8.re, z8.im));
                put(4, g8, cmul_sc(g8, s512), gh, ef);
            }
            {
                const uint32_t s32 = pack_f16(z32.re, z32.im), s64 = pack_f16(z64.re, z64.im), s128 = pack_f16(z128.re, z128.im);
                const h2c p0 = {pack_f16(1.f, z8.re), pack_f16(0.f, z8.im)}, p1 = cmul_s(p0, pack_f16(z16.re, z16.im)), p2 = cmul_s(p0, s32), p3 = cmul_s(p1, s32);
                put(0, p0, p1, p2, p3);
                put(1, cmul_s(p0, s64), cmul_s(p1, s64), cmul_s(p2, s64), cmul_s(p3, s64));
                sts16(za, s128); sts16(za + 64, s128 >> 16);
            }
            __syncwarp();
            {
                const uint32_t aA = fresh(oA), aB = fresh(oB), aC = fresh(oC), aZ = fresh(zr);
                const uint4 zc = lds128(aZ), zd = lds128(aZ + 64);
                const uint32_t zcs[4] = {zc.x, zc.y, zc.z, zc.w}, zds[4] = {zd.x, zd.y, zd.z, zd.w};
                uint32_t c[4];
#pragma unroll
                for (int k = 0; k < 4; k++) {
                    uint32_t a[4], b[4];
                    ldsm4t(a, aA + 128 * k); ldsm4t(b, aB + 128 * k);
                    if (!(k & 1)) ldsm4t(c, aC + 128 * k);
                    const h2c x = cmul_cd(h2c{a[0], a[2]}, *(const __half2*)&zcs[k], *(const __half2*)&zds[k]), y = cmul_cd(h2c{a[1], a[3]}, *(const __half2*)&zcs[k], *(const __half2*)&zds[k]);
                    mma_h(acc[0], a[0], a[1], a[2], a[3], b[0], b[1]);
                    mma_h(acc[1], a[0], a[1], a[2], a[3], b[2], b[3]);
                    mma_h(acc[2], a[0], a[1], a[2], a[3], c[2 * (k & 1)], c[2 * (k & 1) + 1]);
                    mma_h(acc[3], x.re, y.re, x.im, y.im, b[0], b[1]);
                    mma_h(acc[4], x.re, y.re, x.im, y.im, b[2], b[3]);
                    mma_h(acc[5], x.re, y.re, x.im, y.im, c[2 * (k & 1)], c[2 * (k & 1) + 1]);
                }
                asm volatile("" :: "f"(acc[0][0]), "f"(acc[1][0]), "f"(acc[2][0]), "f"(acc[3][0]), "f"(acc[4][0]), "f"(acc[5][0]) : "memory");
            }
            __syncwarp();
            ar = ar1; ai = ai1; W = W1;
        }
        if (threadIdx.x < 32) TSTAMP(21);
        const float i0 = __uint_as_float((ex + 243u) << 23);
        if (half) {
#pragma unroll
            for (int a = 0; a < 6; a++) sts128(wb + a * 512, __float_as_uint(acc[a][0]), __float_as_uint(acc[a][1]), __float_as_uint(acc[a][2]), __float_as_uint(acc[a][3]));
            sts32(stage + 3072, __float_as_uint(i0));
            bar_arrive(barid, 64);
        } else {
#pragma unroll
            for (int a = 0; a < 6; a++) { acc[a][0] *= i0; acc[a][1] *= i0; acc[a][2] *= i0; acc[a][3] *= i0; }
            if (lane == 0) acc[0][1] -= bf_lo(pD);
            sts32(zr, clock32());
            bar_sync(barid, 64);
            const uint32_t src = fresh(pstage);
            const float i1 = __uint_as_float(lds32(src + 3072));
#pragma unroll
            for (int a = 0; a < 6; a++) {
                const uint4 y = lds128(src + lane * 16 + a * 512);
                w[4 * (a % 3) + 2 * (a / 3)] = pack_bf16(fmaf(__uint_as_float(y.x), i1, acc[a][0]), fmaf(__uint_as_float(y.y), i1, acc[a][1]));
                w[4 * (a % 3) + 2 * (a / 3) + 1] = pack_bf16(fmaf(__uint_as_float(y.z), i1, acc[a][2]), fmaf(__uint_as_float(y.w), i1, acc[a][3]));
            }
            const uint32_t x0 = __shfl_up_sync(0xffffffffu, w[10], 2), x1 = __shfl_up_sync(0xffffffffu, w[11], 2);
            w[10] = w[8];
            if (t >= 2) { w[8] = x0; w[9] = x1; }
        }
    }
}

__device__ __forceinline__ int swap01(int i) { return (i & ~3) | ((i & 1) << 1) | ((i >> 1) & 1); }
__device__ __forceinline__ int ut_off(int i) { return i * UT_STRIDE + (i & 4) * 4; }
enum { BC_AUX = 0, BC_U = 5 };

__device__ __forceinline__ void fetch_gates(const Params& p, int i, int lane, unsigned epoch, uint32_t dst) {
    const uint32_t par = (epoch & 1) ? 0x80008000u : 0u;
    uint4 v;
#pragma unroll 1
    for (int it = 0;; it++) {
        v = ld_rlx128(p.s->gate + 256 * i + 8 * lane);
        v.x ^= par; v.y ^= par; v.z ^= par; v.w ^= par;
        if (__all_sync(0xffffffffu, (v.x & v.y & v.z & v.w & 0x80008000u) == 0x80008000u)) break;
        if (it > (1 << 20)) give_up();
    }
    sts128(dst + (8 + 16 * i + (lane >> 1)) * 16, v.x, v.y, v.z, v.w);
}
__device__ __forceinline__ void store_rows(const CUtensorMap* m, uint32_t src, int col, int row) {
    asm volatile("cp.async.bulk.tensor.5d.global.shared::cta.bulk_group [%0, {%2, %3, %3, %3, %4}], [%1];" :: "l"(m), "r"(src), "r"(col), "r"(0), "r"(row) : "memory");
}

__device__ __forceinline__ void store_or_add(void* o, const uint32_t (&y)[4], uint32_t add) {
    asm volatile("{ .reg .pred p; setp.ne.u32 p, %5, 0; @!p st.global.v4.u32 [%0], {%1,%2,%3,%4}; @p red.relaxed.gpu.global.add.noftz.v4.bf16x2 [%0], {%1,%2,%3,%4}; }"
                 :: "l"(o), "r"(y[0]), "r"(y[1]), "r"(y[2]), "r"(y[3]), "r"(add) : "memory");
}

__device__ __forceinline__ void conv_aux(const Params& p, const CUtensorMap* mU, uint32_t sb, int aw, int lane, int bid, unsigned epoch) {
    const int g = lane >> 2, t = lane & 3, mi = lane >> 3, r8 = lane & 7;
    const int rank = bid & 1, slab = bid >> 1;
    const uint32_t bar_y = sb + SC_MISC, bar_u = bar_y + 32, bar_v = bar_y + 40, bar_box = bar_y + 64 + 8 * aw, s_bm = bar_y + 128;
    if (elect()) {
        mbar_init(bar_box, 1); mbar_fence();
        mbar_expect(bar_box, 4096);
        tma4d(sb + SC_RT + 4096 * aw, mU, 16 * slab, 0, 0, 16 * rank + 2 * aw, bar_box);
        mbar_init(bar_y + 8 * aw, aw < 4 ? 9 : aw == 5 ? 8 : 1); mbar_fence();
        if (aw < 5) mbar_expect(bar_y + 8 * aw, aw == 4 ? 16384 : 4096);
    }
    __syncwarp();
    asm volatile("barrier.cluster.arrive.relaxed.aligned;" ::: "memory");
    asm volatile("setmaxnreg.dec.sync.aligned.u32 88;");
    sts128(sb + (lane < 16 ? SC_UT + ut_off(aw) + mi * (UT_HALF - 128) : SC_V - 256 + aw * V_STRIDE) + lane * 16, 0, 0, 0, 0);
    if (lane < 16) sts128(s_bm + lane * 16, 0, 0, 0, 0);
    {
        const uint32_t dst = sb + SC_UT + ut_off(swap01(g)) + swz((8 + 64 * rank + 8 * aw) * 16) + 16 * t, dn = 64 - 64 * ((aw + 1) & 2);
        const uint32_t rdst = mapa(dst, rank ^ 1), rbar = mapa(bar_u, rank ^ 1);
        asm volatile("barrier.cluster.wait.acquire.aligned;" ::: "memory");
        mbar_wait(bar_box);
        if (aw == 0) TSTAMP(1);
        const uint32_t src = fresh(sb + SC_RT) + aw * 4096 + (8 * mi + 4 * (r8 & 1) + (r8 >> 1)) * 32 + ((rank ^ (r8 & 1)) << 4);
        uint32_t x[8][4];
#pragma unroll
        for (int i = 0; i < 4; i++) { ldsm4t(x[i], src + 1024 * i); ldsm4t(x[4 + i], (src ^ 16) + 1024 * i); }
        asm volatile("" :: "r"(x[0][0]), "r"(x[1][0]), "r"(x[2][0]), "r"(x[3][0]) : "memory");
#pragma unroll
        for (int i = 0; i < 4; i++) st_async128(rdst + (i & 1) * UT_HALF + (i & 2 ? dn : 0), x[4 + i][0], x[4 + i][1], x[4 + i][2], x[4 + i][3], rbar);
#pragma unroll
        for (int i = 0; i < 4; i++) sts128(dst + (i & 1) * UT_HALF + (i & 2 ? dn : 0), x[i][0], x[i][1], x[i][2], x[i][3]);
    }
    bar_sync(BC_AUX, 256);
    mbar_wait_cluster(bar_u);
    if (aw == 0) TSTAMP(2);
    if (aw >= 4) bar_arrive(BC_U + aw, 64); else bar_sync(BC_U + aw, 64);
    if (aw == 0) TSTAMP(3);
    {
        const int c = t + 4 * (g & 1);
        const uint32_t ws = fresh(sb + SC_UT) + ut_off(c), wd = sb + SC_V + c * V_STRIDE;
#pragma unroll 1
        for (int k = aw; k < 13; k += 8) {
            const int a = 8 * k + (k < 12 ? g & 6 : 0);
            const uint32_t d = wd + 64 * a, sw = 16 * (a & 2);
            window_task(ws + swz(16 * a + 96), ws + swz(16 * a + 128), d + sw, d + (sw ^ 32), k);
        }
    }
    if (aw == 0) TSTAMP(9);
    {
        if (aw >= 2) fetch_gates(p, aw, lane, epoch, sb + SC_GT + (lane & 1) * GT_HALF);
        __syncwarp();
        if (elect()) { mbar_arrive(bar_v); prefetch_map(mU + 4); }
        next_epoch(p, epoch);
        if (aw == 0) TSTAMP(4);
        if (aw == 7) {
            const int row = key_row(wait_sel(p, slab >> 1, r8, key_tag(epoch)));
            if (lane < 8) asm volatile("red.shared.or.b32 [%0], %1;" :: "r"(s_bm + (row >> 5) * 4), "r"(1u << (row & 31)) : "memory");
            TSTAMP(10);
        }
        bar_sync(BC_AUX, 256);
        const uint32_t src = sb + SC_RT + ((r8 >> 1) & 1) * Y_RS + (2 * mi + (r8 & 1)) * Y_CS + (2 * aw + (r8 >> 2)) * 16;
        const int L = 2 * aw + (t >> 1);
        const int row0 = 256 * rank + 128 * (g >> 2) + 16 * (L & 3) + 64 * (g & 1) + 8 * ((g >> 1) & 1) + (L >> 2);
        __nv_bfloat16* outp = p.out + (size_t)row0 * DM + 16 * slab + 8 * (t & 1);
        const uint32_t stg = sb + SC_KG + 4096 * aw, so = (g & 2) * 256 + (g >> 2) * 128 + r8 * 16;
#pragma unroll 1
        for (int s = 1; s < 4; s++) {
            const uint32_t bm = lds32(fresh(s_bm) + (16 * s + (row0 >> 5)) * 4) >> (row0 & 31);
            const bool routed = __any_sync(0xffffffffu, bm & 0x11u);
            if (aw == s) mbar_wait_cluster(bar_y + 8 * s);
            bar_sync(BC_AUX, 256);
            const uint32_t sf = fresh(src) + 512 * s;
            uint32_t y[2][4];
            ldsm4t(y[0], sf); ldsm4t(y[1], sf + 256);
            if (routed) {
#pragma unroll
                for (int k = 0; k < 2; k++) store_or_add(outp + (size_t)(512 * s + 4 * k) * DM, y[k], bm & (1u << (4 * k)));
            } else {
                sts128(stg + so + 1024 * s, y[0][0], y[0][1], y[0][2], y[0][3]); sts128(stg + so + 1024 * s + 256, y[1][0], y[1][1], y[1][2], y[1][3]);
                asm volatile("fence.proxy.async.shared::cta;" ::: "memory");
                __syncwarp();
                if (elect()) store_rows(mU + 4, stg + 1024 * s, 16 * slab, 512 * s + 256 * rank + 32 * (aw & 1) + (aw >> 1));
            }
            if (aw == 0) TSTAMP(16 + s);
        }
        if (elect()) { asm volatile("cp.async.bulk.commit_group;" ::: "memory"); asm volatile("cp.async.bulk.wait_group.read 0;" ::: "memory"); }
        if (aw == 0) TFLUSH();
    }
}

__device__ __forceinline__ uint32_t k_tag(unsigned epoch) { return epoch << 16 | 0x80000000u; }
__device__ __forceinline__ void publish_k(uint4* kp, const uint32_t (&w)[12], unsigned epoch, uint64_t (&v)[6]) {
#pragma unroll
    for (int i = 0; i < 3; i++) {
        v[2 * i] = w[3 * i] | (uint64_t)w[3 * i + 1] << 32; v[2 * i + 1] = w[3 * i + 2] | (uint64_t)__byte_perm(w[9 + (i >> 1)], k_tag(epoch), i == 1 ? 0x7632 : 0x7610) << 32;
        asm volatile("st.relaxed.gpu.global.v2.u64 [%0], {%1,%2};" :: "l"(kp + 32 * i), "l"(v[2 * i]), "l"(v[2 * i + 1]));
    }
}
template <bool FULL>
__device__ __forceinline__ void k_tables(uint32_t kt, int lane, const uint32_t (&w)[12]) {
    const int g = lane >> 2, t = lane & 3, mi = lane >> 3, r8 = lane & 7;
    uint32_t x3 = w[7], re[4], rx[4];
#pragma unroll
    for (int i = 0; i < 4; i++) {
        re[i] = __shfl_sync(0xffffffffu, w[i], lane + 31);
        rx[i] = __shfl_sync(0xffffffffu, w[4 + i], lane + (i == 0 && lane == 29 ? 5 : 1 + 2 * t));
    }
    if (FULL) {
        asm volatile("stmatrix.sync.aligned.m8n8.x2.trans.shared.b16 [%0], {%1,%2};" :: "r"(kt + (KT_D + 7) * 4 + 64 * t + 16 * (mi & 1) + 8 * (r8 & 4)), "r"(w[8]), "r"(w[9]) : "memory");
        if (lane == 2) {
            sts32(kt + (KT_C + 78) * 4, w[10] & 0xffffu);
            sts128(kt + (KT_T + 2) * 4, 0, w[10] & 0xffffu, __byte_perm(w[10], 0, 0x1010), w[10] << 16);
        }
        if (lane == 29) x3 = bsub2(x3, rx[0] & 0xffffu);
    }
#pragma unroll
    for (int i = 0; i < 4; i++) {
        sts64(kt + (16 + 64 * i) * 4 + 8 * lane, __byte_perm(w[i], lane ? re[i] : i ? re[i - 1] : 0, 0x5432), w[i]);
        const uint32_t x = i < 3 ? w[4 + i] : x3, aa = __byte_perm(x, 0, 0x3232);
        if (t < 2) sts128(kt + (272 + 64 * i + 8 * g + 4 * t) * 4, i == 0 && lane == 0 ? __byte_perm(x, re[3], 0x5432) : aa, aa, x,
                          __byte_perm(lane != 29 ? rx[i] : i < 3 ? rx[(i + 1) & 3] : FULL ? 0 : rx[0] << 16, x, 0x5432));
        else if (FULL) sts32(kt + (KT_C - 50 + 8 * i + 32 * t + g) * 4, x);
    }
}

__device__ __forceinline__ void conv_main(const Params& p, uint32_t sb, int warp, int lane0, int bid, unsigned epoch, uint32_t (&w)[12]) {
    asm volatile("setmaxnreg.inc.sync.aligned.u32 168;");
    const int lane = __shfl_sync(0xffffffffu, lane0, lane0);
    const int g = lane >> 2, t = lane & 3, mi = lane >> 3, r8 = lane & 7;
    const int rank = bid & 1;
    const uint32_t bar_y = sb + SC_MISC, bar_v = bar_y + 40;
    next_epoch(p, epoch);
    if (warp >= 4) {
        bar_sync(BC_U + warp, 64);
        if (KPOLL) until(clock32(), KPOLL);
        const uint4* src = p.s->kp + (8 * bid + warp) * 96 + lane0;
#pragma unroll 1
        for (int it = 0;; it++) {
            uint32_t bad = 0, e[3];
#pragma unroll
            for (int i = 0; i < 3; i++) { const uint4 v = ld_rlx128(src + 32 * i); w[3 * i] = v.x; w[3 * i + 1] = v.y; w[3 * i + 2] = v.z; e[i] = v.w; bad |= v.w ^ k_tag(epoch); }
            w[9] = __byte_perm(e[0], e[1], 0x5410); w[10] = e[2];
            const bool ok = __all_sync(0xffffffffu, bad < 65536);
            if (ok) break;
            if (it > (1 << 20)) give_up();
        }
    }
    if ((warp & 3) == 0) TSTAMP(5 + (warp >> 2));
    k_tables<true>(sb + SC_KT + warp * KT_BYTES, lane0, w);
    asm volatile("barrier.cluster.wait.acquire.aligned;" ::: "memory");
    if (warp < 4) bar_sync(BC_U + warp, 64);
    __syncwarp();
    if ((warp & 3) == 0) TSTAMP(7 + (warp >> 2));
    {
        const uint32_t ut = fresh(sb + SC_UT) + ut_off(swap01(warp)), kt = fresh(sb + SC_KT) + warp * KT_BYTES;
        auto dup = [&](uint32_t v) { return v ^ p.zero; };
        auto frag = [&](uint32_t (&a)[4], uint32_t x) { a[0] = lds32(x); a[1] = lds32(x + 32); a[2] = lds32(x - 32); a[3] = dup(a[0]); };
        const uint32_t kb = kt + (16 + g - 2 * t) * 4;
        float acc[16][4];
        {
            float y[12][4], M[6][4];
#pragma unroll
            for (int i = 0; i < 12; i++) { y[i][0] = y[i][1] = y[i][2] = y[i][3] = 0.f; M[i >> 1][0] = M[i >> 1][1] = M[i >> 1][2] = M[i >> 1][3] = 0.f; }
            uint32_t U[10][4], a1[4], ad[4], R = (mi & 1) * UT_HALF + (8 + (r8 >> 1) + 48 * (r8 & 1)) * 16 + 64 * (mi >> 1);
            auto places = [&] { ad[0] = swz(R); ad[1] = swz(R + 128); ad[2] = ad[0] ^ 64; ad[3] = ad[1] ^ 64; };
            auto ldu = [&](int k) { ldsm4(U[k], ut + ad[k & 3] + 256 * (k >> 1)); };
            places();
            frag(a1, kb + 2048);
#pragma unroll
            for (int k = 0; k < 7; k++) ldu(k);
#pragma unroll
            for (int i = 0; i < 12; i++) mma_bf(y[i], a1[0], a1[1], a1[2], a1[3], U[i >> 1][2 * (i & 1)], U[i >> 1][2 * (i & 1) + 1]);
            frag(a1, kb + 1792);
            __syncwarp();
#pragma unroll DUNR
            for (uint32_t ko = 0; ko != 256;) {
                if (DUN == 1) ko = fresh(ko);
                const uint32_t kp = kb + ko;
                ko += 64;
                uint32_t se[10][2], so[10][2], ue[10][2];
                auto sums = [&](int k) {
#pragma unroll
                    for (int e = 0; e < 2; e++) { ue[k][e] = U[k][e]; se[k][e] = badd2(U[k][e], U[k - 1][2 + e]); so[k][e] = badd2(U[k][e], U[k][2 + e]); }
                };
#pragma unroll
                for (int k = 1; k < 6; k++) sums(k);
#pragma unroll
                for (int m = 3; m >= 0; m--) {
                    uint32_t a0[4];
                    frag(a0, kp + 512 * m);
                    sums(9 - m);
                    if (m) ldu(10 - m); else { R -= 16; places(); }
#pragma unroll
                    for (int i = 0; i < 6; i++) mma_bf(y[2 * i], a1[0], a1[1], a1[2], a1[3], se[i - m + 4][0], se[i - m + 4][1]);
#pragma unroll
                    for (int e = 0; e < 4; e++) a1[e] = bsub2(a0[e], a1[e]);
#pragma unroll
                    for (int i = 0; i < 6; i++) { mma_bf(M[i], a1[0], a1[1], a1[2], a1[3], ue[i - m + 4][0], ue[i - m + 4][1]); if (!m) ldu(i); }
                    frag(a1, m ? kp + 512 * m - 256 : kp + 1792 + 64);
                    if (!m) ldu(6);
#pragma unroll
                    for (int i = 0; i < 6; i++) mma_bf(y[2 * i + 1], a0[0], a0[1], a0[2], a0[3], so[i - m + 4][0], so[i - m + 4][1]);
                }
            }
#pragma unroll
            for (int i = 0; i < 6; i++)
#pragma unroll
                for (int c = 0; c < 4; c++) { acc[4 + i + 6 * (c & 1)][c & 2] = y[2 * i][c] + M[i][c]; acc[4 + i + 6 * (c & 1)][c | 1] = y[2 * i + 1][c] - M[i][c]; }
        }
        const uint32_t lo = (8 + col(r8)) * 16 + (mi >> 1) * 128, ua = fresh(ut) + (mi & 1) * UT_HALF, u1[2] = {ua + swz(lo), ua + (swz(lo) ^ 64)};
        {
            uint32_t e[4];
            frag(e, kb + (KT_T - 16) * 4);
            const uint32_t f0 = dup(e[1]), f1 = lds32(kb + KT_T * 4), uo = fresh(ut) + UT_HALF + swz((7 + 8 * mi + col(r8)) * 16);
#pragma unroll
            for (int i = 0; i < 4; i++) {
                uint32_t b[4];
                if (i < 2) {
                    ldsm4(b, uo + 512 * i);
#pragma unroll
                    for (int k = 0; k < 4; k++) mma_bf8(acc[8 + 4 * i + k], f0, f1, b[k]);
                }
                ldsm4(b, u1[i & 1] + 256 * i);
                mma_bf(acc[2 * i + 8], e[0], e[1], e[2], e[3], b[0], b[1]); mma_bf(acc[2 * i + 9], e[0], e[1], e[2], e[3], b[2], b[3]);
            }
        }
        if ((warp & 3) == 0) TSTAMP(11 + (warp >> 2));
        mbar_wait(bar_v);
        const uint32_t vt = fresh(sb + SC_V) + swap01(warp) * V_STRIDE;
        const uint32_t g1 = fresh(sb + SC_GT) + (mi & 1) * GT_HALF + lo;
        const uint32_t ydst = sb + SC_RT + rank * Y_RS + warp * Y_CS + lane * 16;
        const uint32_t ydr = mapa(ydst, rank ^ 1), ybr = mapa(bar_y, rank ^ 1);
        auto stairs = [&](auto R) {
        uint32_t ug[2][2][4];
        auto ld_ug = [&](int i) { ldsm4t(ug[i & 1][0], u1[i & 1] + 256 * i); ldsm4t(ug[i & 1][1], g1 + 256 * i); };
        auto ship = [&](int i) {
            const uint32_t (&u)[4] = ug[i & 1][0], (&gg)[4] = ug[i & 1][1];
            const uint32_t y0 = gmix(gg[0], acc[2 * i][0], acc[2 * i][1], u[0]), y1 = gmix(gg[1], acc[2 * i][2], acc[2 * i][3], u[1]);
            const uint32_t y2 = gmix(gg[2], acc[2 * i + 1][0], acc[2 * i + 1][1], u[2]), y3 = gmix(gg[3], acc[2 * i + 1][2], acc[2 * i + 1][3], u[3]);
            if ((i & 1) != R.value) st_async128(ydr + 512 * (i >> 1), y0, y1, y2, y3, ybr + 8 * (i >> 1));
            else asm volatile("{ .reg .pred q; setp.eq.u32 q, %6, 0; st.shared.v4.u32 [%0], {%2,%3,%4,%5}; bar.warp.sync 0xffffffff; @q mbarrier.arrive.shared::cta.b64 _, [%1]; }"
                              :: "r"(ydst + 512 * (i >> 1)), "r"(bar_y + 8 * (i >> 1)), "r"(y0), "r"(y1), "r"(y2), "r"(y3), "r"(lane) : "memory");
        };
        const uint32_t VD = vt + (VC_OFF - 400 - 16 * t) * 4 + (8 * g ^ 16 * (-t & 2)), VD2 = vt + (VC_OFF - 415 - 16 * t) * 4 + (8 * g ^ 16 * (~t & 2));
        uint2 bd[10];
        uint32_t x[2][4][4];
        auto ld4 = [&](uint32_t (&v)[4], int dl) { const uint2 w = lds64(VD + 256 * dl); v[0] = w.x; v[1] = w.y; v[2] = lds32(VD2 + 256 * dl); v[3] = dup(w.x); };
        auto mm4 = [&](const uint32_t (&v)[4], int dl) {
#pragma unroll
            for (int s = dl & 1; s < 10; s += 2) if ((dl + s) / 2 >= 4 && (dl + s) / 2 < 16) mma_bf(acc[(dl + s) / 2], v[0], v[1], v[2], v[3], bd[s].x, bd[s].y);
        };
        const uint32_t KE = kt + (KT_D + col(g) + t) * 4, VE = vt + (VE_BASE - 912 - 16 * t) * 4 + (8 * g ^ 16 * (~t & 2));
        uint32_t b0[8], b1[8];
        auto ld8 = [&](uint32_t (&v)[4], int dl) { const uint2 w = lds64(VE + 512 * dl), z = lds64(VE + 512 * dl - 256); v[0] = w.x; v[1] = w.y; v[2] = z.x; v[3] = z.y; };
        auto mm8 = [&](const uint32_t (&v)[4], int dl, int lo, int hi) {
#pragma unroll
            for (int s = 0; s < 8; s++) if (dl + s >= lo && dl + s < hi) mma_bf(acc[dl + s], v[0], v[1], v[2], v[3], b0[s], b1[s]);
        };
        ld4(x[0][0], 6);
#pragma unroll
        for (int s = 0; s < 10; s++) bd[s] = lds64(kt + (KT_C + 2 * col(g) + 2 * t + 8 * s) * 4);
        mm4(x[0][0], 6);
        uint32_t e[4][4];
#pragma unroll
        for (int k = 1; k < 6; k++) {
#pragma unroll
            for (int j = 0; j < 4; j++) ld4(x[k & 1][j], 4 * k + 3 + j);
            ld_ug(k + 1);
            if (k == 3) {
#pragma unroll
                for (int s = 0; s < 8; s++) { b0[s] = lds32(KE + 32 * s); b1[s] = lds32(KE + 32 * s + 16); }
            }
            if (k > 1) ship(k);
#pragma unroll
            for (int j = 0; j < 4; j++) {
                mm4(x[k & 1][j], 4 * k + 3 + j);
                if (k == 3) { uint32_t v[4], z[4]; ld8(e[j], 8 + j); ld8(v, 12 + j); ld4(z, 30 - j); mm8(v, 12 + j, 12, 16); mm8(e[j], 8 + j, 8, 12); mm4(z, 30 - j); }
                if (k == 5) { ld8(e[j], 8 + j + p.zero); mm8(e[j], 8 + j, 12, 16); }
            }
        }
        ld_ug(7);
        ship(7 - R.value); ship(6 + R.value);
        };
        if (rank) stairs(std::integral_constant<int, 1>()); else stairs(std::integral_constant<int, 0>());
        if ((warp & 3) == 0) TSTAMP(14 + (warp >> 2)); else TSTAMP(21 + warp);
    }
}

constexpr int SF_WD = 73728;
constexpr int SF_RED = 49152;
constexpr int MU_HALF = 640, MU_STRIDE = 1344, SM_RAW = 98304, SM_UT = SM_RAW + 16384, SM_G = SM_UT + 16 * MU_STRIDE, SM_Y = 196608, SM_KT = 138880, SM_KW = SM_G - 49152;
constexpr int SF_XS = 221184;
constexpr int SF_MISC = SF_XS + 8 * 1168;
constexpr int SF_KG = SF_MISC - 10 * KG_STAGE;
constexpr int SF_WR = SF_KG - 2304;
constexpr int FB_X = 64, FB_KDONE = 72, FB_KEYS = 80, FB_FREE = 88  , FB_W = 104, FB_D = FB_W + 72, FB_MU = FB_D + 96, FB_MG = FB_MU + 8, FB_MT = FB_MU + 16  , FS_PART = 512, FS_TOK = 896, FS_BM = 1024;
enum { BAR_R = 7, BAR_GU = 8, BAR_RED = 9, BAR_R2 = 10, BAR_G = 12  , BAR_M = 15 };
static_assert(SF_KG % 128 == 0 && NPRE <= 8 && SM_KT + 4 * 2112 <= 147456 && SM_G + MU_STRIDE <= SF_WR - 4 * 9216 && SM_KW + 6 * 2112 >= SM_RAW && SM_KW + 12 * 2112 <= SM_UT, "layout");

__device__ __forceinline__ constexpr int box_no(int i) { return (0x987610ba5432ull >> (4 * i)) & 15; }
__device__ __forceinline__ int mini_ch0(int f) { return 48 * f - (f < NW ? 1696 : 2304); }

__device__ __forceinline__ void ffn_front(const Params& p, const CUtensorMap* maps, uint32_t sb, int warp, int lane, int f, unsigned epoch) {
    const unsigned t0 = clock32();
    const int g = lane >> 2, t = lane & 3, mi = lane >> 3, r8 = lane & 7;
    const bool isx = f < NX;
    const int nrw = f < 52 ? 4 : 6, r0 = f < 52 ? 32 * f : 48 * f - 832;
    const int rw = warp < 12 ? 13 - warp : warp ^ (warp < 14 ? 10 : 15);
    const uint32_t bar_row = sb + SF_MISC  , bar_x = bar_row + FB_X;
    const uint32_t s_part = bar_row + FS_PART  , s_tok = bar_row + FS_TOK  ;
    const uint32_t rows = sb + SF_WR - 9216 * (rw + 1) - (rw & 4) * ((SF_WR - 6 * 9216) / 4);
    {
#pragma unroll 1
        for (int i = warp < 10 ? 30 : warp - 10; i < 30; i += 6) if (elect()) mbar_init(bar_x + 8 * i, i == 1 ? 4 + (f < NW) : i < 27 ? 1 : i == 27 ? 2 : 8);
        const uint32_t bytes = rw < 6 ? 9216 : 1152, dst = rw < 6 ? rows : sb + SF_WR + (rw & 1) * 1152;
        const __nv_bfloat16* src = rw < 6 ? p.u + (size_t)(r0 + 8 * rw) * DM : (rw & 1) ? p.gatew : p.wr;
        if (elect()) { mbar_init(bar_row + 8 * rw, 1); mbar_fence(); mbar_expect(bar_row + 8 * rw, bytes); }
        if (warp == 13) { sts32(s_part + 64 + lane * 4, 0); sts32(bar_row + FS_BM + lane * 4, 0); }
        bar_sync(0, NTHR);
        if (rw < nrw) until(t0, RDELAY);
        if (rw < nrw || rw >= 6) { if (elect()) bulk_g2s(dst, src, bytes, bar_row + 8 * rw); }
    }
    uint4* const kdst = p.s->keys + (lane >> 1) * 128 + 2 * f + (lane & 1);
    if (warp == 15) TSTAMP(1);

    if (warp == 12) {
        if (lane < 22) mbar_expect(bar_row + FB_W + 8 * lane, lane < 9 ? 24576 : isx ? 12288 : 16384);
        if (elect()) { prefetch_map(maps + 1); prefetch_map(maps + 2); prefetch_map(maps + (isx ? 3 : 5)); }
        unsigned tb = t0 + WDELAY;
        auto pieces = [&](int n, int end, uint32_t dst) {
#pragma unroll 1
            for (; n < end; n++, dst += 12288) {
                until(tb, 0); tb += WGAP;
                if (elect()) tma3d(dst, maps + 1 + (n & 1), 0, 64 * (n >> 1), 3 * f, bar_row + FB_W + 8 * (n >> 1));
            }
        };
        if (!isx) {
#pragma unroll 1
            for (int k = 0; k <= (f >= NW); k++) { until(t0, MDELAY + k * MGAP); if (elect()) tma4d(sb + SM_RAW - 49152 * k, maps + 5, mini_ch0(f) + 16 * k, 0, 0, 0, bar_row + FB_MU - 8 * k); }
            if (f >= NW) return;
        }
#pragma unroll 1
        for (int i = 0; i < 4; i++) {
            if (i == 1) { mbar_wait(bar_row + FB_KEYS); mbar_wait(bar_row + FB_KDONE); tb = clock32() + RESUME; }
            if (i == 3) mbar_wait(bar_row + FB_FREE);
            const int n = ((0x0c080000 + NPRE * 256) >> (8 * i)) & 255;
            pieces(n, ((0x120c0800 + NPRE) >> (8 * i)) & 255, sb + 12288 * (((0x000c0000 + NPRE * 256) >> (8 * i)) & 255));
        }
        TSTAMP(12);
        if (isx) {
#pragma unroll 1
            for (int i = 0; i < 12; i++) {
                const int n = box_no(i);
                if (i == 6) mbar_wait(bar_row + FB_FREE + 8);
                until(tb, 0); tb += DGAP;
                if (elect()) tma2d(sb + SF_WD + n * 12288, maps + 3, 32 * (f >> 1), 2304 * (f & 1) + 192 * n, bar_row + FB_D + 8 * n);
            }
            TSTAMP(13);
        }
    } else if (warp == 13) {
        const uint32_t tag = key_tag(epoch), par = (epoch & 1) ? 0u : 0x8000u;
        stg128(kdst, 0, 0, 0, 0);
        if (lane < 8 && isx && !(f & 1)) st_rlx32(&p.s->sel[32 * f + lane], 0);
        bar_sync(BAR_R, 32 * (nrw + 1));
        TSTAMP(3);
        {
            const uint32_t sg = fresh(s_part) + 192 + lane * 4;
            const uint32_t gb = pack_bf16(sigmoidf_(rbf(__uint_as_float(lds32(sg)))), sigmoidf_(rbf(__uint_as_float(lds32(sg + 128))))) | par | (par << 16);
            asm volatile("st.relaxed.gpu.global.u16 [%0], %1;" :: "l"(p.s->gate + r0 + lane), "h"((unsigned short)gb) : "memory");
            if (nrw > 4 && lane < 16) asm volatile("st.relaxed.gpu.global.u16 [%0], %1;" :: "l"(p.s->gate + r0 + 32 + lane), "h"((unsigned short)(gb >> 16)) : "memory");
        }
        bar_sync(BAR_R2, 32 * (nrw + 1));
        {
            const uint4 v = lds128(fresh(s_tok) + (lane & 1) * 16);
            asm volatile("st.relaxed.gpu.global.v4.u32 [%0], {%1,%2,%3,%4};" :: "l"(kdst), "r"(v.x | tag), "r"(v.y | tag), "r"(v.z | tag), "r"(v.w | tag) : "memory");
        }
        TSTAMP(4);
        if (lane == 0) { mbar_arrive(bar_row + FB_KEYS); mbar_expect(bar_x, 8 * 1152); }
        if (f >= NW) return;
        mbar_wait(bar_row + FB_KDONE);
        uint32_t k[16];
        const uint4* src = p.s->keys + (f & 15) * 128 + lane;
#pragma unroll 1
        for (int it = 0;; it++) {
            uint32_t bad = 0;
#pragma unroll
            for (int i = 0; i < 4; i++) {
                const uint4 x = ld_rlx128(src + (i < 3 || lane < 24 ? 32 * i : 64));
                k[i] = x.x; k[4 + i] = x.y; k[8 + i] = x.z; k[12 + i] = x.w;
                bad |= x.x ^ tag;
            }
            const bool ok = __all_sync(0xffffffffu, (bad & 0xf800u) == 0);
            if (ok) break;
            if (it > (1 << 20)) give_up();
        }
        TSTAMP(5);
        uint32_t key = 0, m = __reduce_max_sync(0xffffffffu, max(max(k[0], k[1]), max(k[2], k[3])));
#pragma unroll 2
        for (int r = 0; r < 8; r++) {
            bool pop[4];
#pragma unroll
            for (int i = 0; i < 4; i++) { pop[i] = k[i] == m; k[i] = pop[i] ? k[4 + i] : k[i]; }
            const uint32_t mn = __reduce_max_sync(0xffffffffu, max(max(k[0], k[1]), max(k[2], k[3])));
            if (elect()) bulk_g2s(sb + SF_XS + r * 1168, p.u + (size_t)key_row(m) * DM, 1152, bar_x);
#pragma unroll
            for (int i = 0; i < 4; i++) { k[4 + i] = pop[i] ? k[8 + i] : k[4 + i]; k[8 + i] = pop[i] ? k[12 + i] : k[8 + i]; k[12 + i] = pop[i] ? 0 : k[12 + i]; }
            if (r8 == r) key = m;
            m = mn;
        }
        const int row = key_row(key);
        sts32(s_tok + r8 * 8, row);
        TSTAMP(6);
        if (isx) {
            if (!(f & 1)) {
                __nv_bfloat16* o = p.out + (size_t)row * DM + 16 * f + 8 * mi;
                asm volatile("st.relaxed.gpu.global.v4.u32 [%0], {%1,%1,%1,%1};" :: "l"(o), "r"(0) : "memory");
                if (__any_sync(0xffffffffu, ld_rlx32(o) != 0)) give_up();
                if (lane < 8) st_rlx32(&p.s->sel[32 * f + lane], key);
            } else wait_sel(p, f >> 1, r8, tag);
            uint32_t gb;
#pragma unroll 1
            for (int it = 0;; it++) {
                asm volatile("ld.relaxed.gpu.global.u16 %0, [%1];" : "=r"(gb) : "l"(p.s->gate + row) : "memory");
                gb ^= par;
                if (!(gb & 0x8000u)) break;
                if (it > (1 << 20)) give_up();
            }
            const uint32_t rb = key ^ 0x80000000u, rv = (rb ^ (((int)rb >> 31) & 0x7fff0000u)) & 0xffff0000u;
            sts32(s_tok + r8 * 8 + 4, __float_as_uint(rbf(1.0f - bf_lo(gb)) * rbf(sigmoidf_(__uint_as_float(rv)))));
            __syncwarp();
            TSTAMP(7);
            bar_arrive(BAR_RED, 416);
        }
    } else {
        if (rw < nrw) {
            float c[3][4];
#pragma unroll
            for (int i = 0; i < 3; i++) { c[i][0] = c[i][1] = c[i][2] = c[i][3] = 0.f; }
            mbar_wait(bar_row + 48); mbar_wait(bar_row + 56);
            const uint32_t b = fresh(sb + SF_WR) + (g & 1) * 1152 + (g >> 2) * 64 + t * 16 + (g & 2) * 2;
            uint32_t w[18][2];
#pragma unroll
            for (int kb = 0; kb < 18; kb++) { const uint32_t o = ((kb & 1) ? b ^ 64 : b) + 128 * (kb >> 1); w[kb][0] = lds32(o); w[kb][1] = lds32(o + 8); }
            mbar_wait(bar_row + 8 * rw);
            if (warp == 15) TSTAMP(2);
            const uint32_t a = fresh(rows) + g * 1152 + (g & 1) * 64 + t * 16;
#pragma unroll
            for (int kb = 0; kb < 18; kb++) {
                const uint4 x = lds128(((kb & 1) ? a ^ 64 : a) + 128 * (kb >> 1));
                mma_bf(c[kb % 3], x.x, x.y, x.z, x.w, w[kb][0], w[kb][1]);
            }
            const float sr = c[0][0] + c[1][0] + c[2][0] + __shfl_down_sync(0xffffffffu, c[0][2] + c[1][2] + c[2][2], 1);
            const float sg = c[0][1] + c[1][1] + c[2][1] + __shfl_down_sync(0xffffffffu, c[0][3] + c[1][3] + c[2][3], 1);
            const uint32_t rb = pack_bf16(0.f, sr);
            if (t == 2 * (g & 1)) {
                sts32(s_part + (8 * rw + g) * 4, (rb ^ (((int)rb >> 31) & 0x7fff0000u) ^ 0x80000000u) | (uint32_t)(2047 - r0 - 8 * rw - g));
                sts32(s_part + 192 + (8 * rw + g) * 4, __float_as_uint(sg));
            }
            __syncwarp();
            bar_sync(BAR_R, 32 * (nrw + 1));
            const uint32_t sk = fresh(s_part), kk = lds32(sk + (8 * rw + r8) * 4);
            int n = 0;
#pragma unroll
            for (int i = 0; i < 3; i++) { const uint4 v = lds128(sk + mi * 48 + 16 * i); n += (v.x > kk) + (v.y > kk) + (v.z > kk) + (v.w > kk); }
            n += __shfl_xor_sync(0xffffffffu, n, 8); n += __shfl_xor_sync(0xffffffffu, n, 16);
            if (n < 8) sts32(s_tok + 4 * n, kk);
            __syncwarp();
            bar_arrive(BAR_R2, 32 * (nrw + 1));
        }
    }
}

__device__ __forceinline__ void ffn_work(const Params& p, uint32_t sb, int warp, int lane, int f, unsigned epoch) {
    const int g = lane >> 2, t = lane & 3, mi = lane >> 3, r8 = lane & 7;
    const bool isx = f < NX;
    const uint32_t bar_x = sb + SF_MISC + FB_X, bar_free = sb + SF_MISC + FB_FREE, bar_w = sb + SF_MISC + FB_W, bar_d = sb + SF_MISC + FB_D, s_tok = sb + SF_MISC + FS_TOK;
    uint32_t fr[24][4];
    auto pin = [&] {
#pragma unroll
        for (int i = 0; i < 24; i += 8) asm volatile("" :: "r"(fr[i][0]), "r"(fr[i + 1][0]), "r"(fr[i + 2][0]), "r"(fr[i + 3][0]), "r"(fr[i + 4][0]), "r"(fr[i + 5][0]), "r"(fr[i + 6][0]), "r"(fr[i + 7][0]) : "memory");
    };
    {
        const int j = (unsigned)(warp - 4) < 6, w = warp - (j ? 4 : warp < 4 ? 0 : 6);
        float ag[2][4], au[2][4];
#pragma unroll
        for (int i = 0; i < 2; i++) { ag[i][0] = ag[i][1] = ag[i][2] = ag[i][3] = 0.f; au[i][0] = au[i][1] = au[i][2] = au[i][3] = 0.f; }
        const uint32_t wb = sb + (w >> 1) * 4096 + (r8 + 8 * (mi >> 1)) * 64 + (((2 * (w & 1) + (mi & 1)) ^ (r8 >> 1)) << 4);
        const uint32_t xb = sb + SF_XS + r8 * 1168 + mi * 16;
        auto load = [&](int i, int n, int place) {
            mbar_wait(bar_w + 8 * n);
            const uint32_t wk = fresh(wb) + place * 24576;
#pragma unroll
            for (int s = 0; s < 4; s++) { ldsm4t(fr[8 * i + s], wk + 1024 * s); ldsm4t(fr[8 * i + 4 + s], wk + 1024 * s + 12288); }
        };
        auto mul = [&](int i, uint32_t xk) {
            uint32_t x[2][4];
            ldsm4(x[0], xk); ldsm4(x[1], xk + 64);
#pragma unroll
            for (int s = 0; s < 4; s++) {
                const uint32_t (&a)[4] = fr[8 * i + s], (&b)[4] = fr[8 * i + 4 + s];
                mma_bf(ag[s & 1], a[0], a[1], a[2], a[3], x[s >> 1][2 * (s & 1)], x[s >> 1][2 * (s & 1) + 1]);
                mma_bf(au[s & 1], b[0], b[1], b[2], b[3], x[s >> 1][2 * (s & 1)], x[s >> 1][2 * (s & 1) + 1]);
            }
        };
#pragma unroll
        for (int i = 0; i < 3; i++) load(i, 3 * j + i, (i ? 5 : 3) * j + i);
        pin();
        bar_sync(BAR_G + j, 192);
        if (w == 0 && lane == 0) mbar_arrive(bar_free + 8 * j);
        mbar_wait(bar_x);
        if (warp == 0) TSTAMP(8);
        {
            const uint32_t xk = fresh(xb) + 384 * j;
#pragma unroll
            for (int i = 0; i < 3; i++) { mul(i, (i ? fresh(xk) : xk) + 128 * i); if (i == 0) { asm volatile("" :: "f"(ag[0][0]), "f"(ag[1][0]), "f"(au[0][0]), "f"(au[1][0])); sts32(s_tok + 64, clock32()); } }
        }
#pragma unroll 1
        for (int n = 6 + j; n < 9; n += 2) { load(0, n, n - 6); mul(0, fresh(xb) + 128 * n); }
#pragma unroll
        for (int c = 0; c < 4; c++) { ag[0][c] += ag[1][c]; au[0][c] += au[1][c]; }
        if (j) {
            sts128(wb + 24576, __float_as_uint(ag[0][0]), __float_as_uint(ag[0][1]), __float_as_uint(ag[0][2]), __float_as_uint(ag[0][3]));
            sts128(wb + 25600, __float_as_uint(au[0][0]), __float_as_uint(au[0][1]), __float_as_uint(au[0][2]), __float_as_uint(au[0][3]));
        }
        bar_sync(BAR_GU, 384);
        if (!j) {
            const uint32_t sf = fresh(wb);
            const uint4 g1 = lds128(sf + 24576), u1 = lds128(sf + 25600);
            const uint32_t gs[4] = {g1.x, g1.y, g1.z, g1.w}, us[4] = {u1.x, u1.y, u1.z, u1.w};
            if (warp == 0) TSTAMP(9);
            float h[4];
#pragma unroll
            for (int c = 0; c < 4; c++) {
                const float gv = rbf(ag[0][c] + __uint_as_float(gs[c]));
                h[c] = rbf(gv * sigmoidf_(gv)) * rbf(au[0][c] + __uint_as_float(us[c]));
            }
            uint32_t h0, h1;
            asm("movmatrix.sync.aligned.m8n8.trans.b16 %0, %1;" : "=r"(h0) : "r"(pack_bf16(h[0], h[1])));
            asm("movmatrix.sync.aligned.m8n8.trans.b16 %0, %1;" : "=r"(h1) : "r"(pack_bf16(h[2], h[3])));
            if (h0 == 0) h0 = 0x8000u;
            asm volatile("{ .reg .b64 v; mov.b64 v, {%1, %2}; st.relaxed.gpu.global.b64 [%0], v; }" :: "l"(p.s->h + ((epoch & 1) * 288 + 6 * f + w) * 32 + lane), "r"(h0), "r"(h1) : "memory");
        }
        if (isx) {
            if (warp == 0) TSTAMP(10);
            const uint2* hsrc = p.s->h + ((epoch & 1) * 288 + 144 * (f & 1) + warp) * 32 + lane;
            const uint32_t wd = sb + SF_WD + warp * 1024 + (r8 + 8 * (mi >> 1)) * 64 + (((mi & 1) ^ (r8 >> 1)) << 4), we = wd ^ 32;
            uint2 hb[12];
            auto ldh = [&](int i) { asm volatile("ld.relaxed.gpu.global.v2.u32 {%0, %1}, [%2];" : "=r"(hb[i].x), "=r"(hb[i].y) : "l"(hsrc + 384 * box_no(i)) : "memory"); };
            auto ldw = [&](int i) { mbar_wait(bar_d + 8 * box_no(i)); ldsm4t(fr[2 * i], fresh(wd) + 12288 * box_no(i)); ldsm4t(fr[2 * i + 1], fresh(we) + 12288 * box_no(i)); };
#pragma unroll
            for (int i = 0; i < DPA; i++) ldw(i);
#pragma unroll
            for (int i = 0; i < 12; i++) ldh(i);
#pragma unroll
            for (int i = DPA; i < DPB; i++) ldw(i);
#pragma unroll
            for (int i = 0; i < DPB; i++) asm volatile("" :: "r"(fr[2 * i][0]), "r"(fr[2 * i + 1][0]) : "memory");
#pragma unroll 1
            for (int it = 0;; it++) {
                bool again = false;
#pragma unroll
                for (int s = 0; s < 12; s += 2) if (__any_sync(0xffffffffu, min(hb[s].x, hb[s + 1].x) == 0)) { ldh(s); ldh(s + 1); again = true; }
                if (!again) break;
                if (it > (1 << 16)) give_up();
            }
            if (warp == 0) TSTAMP(11);
            float ad[2][2][4];
#pragma unroll
            for (int i = 0; i < 4; i++) { ad[i >> 1][i & 1][0] = ad[i >> 1][i & 1][1] = ad[i >> 1][i & 1][2] = ad[i >> 1][i & 1][3] = 0.f; }
#pragma unroll
            for (int i = 0; i < 12; i++) {
                if (i >= DPB) ldw(i);
                if (i == 11 && warp == 9) TSTAMP(14);
#pragma unroll
                for (int c = 0; c < 2; c++) mma_bf(ad[c][i & 1], fr[2 * i + c][0], fr[2 * i + c][1], fr[2 * i + c][2], fr[2 * i + c][3], hb[i].x, hb[i].y);
                if (i >= DPB - 1) asm volatile("" :: "f"(ad[0][i & 1][0]), "f"(ad[1][i & 1][0]) : "memory");
            }
            const uint32_t rd = sb + SF_RED + warp * 1152 + (72 * t + g) * 4;
#pragma unroll
            for (int i = 0; i < 8; i++) sts32(rd + (i >> 2) * 64 + (i & 1) * 144 + ((i >> 1) & 1) * 32, __float_as_uint(ad[i >> 2][0][i & 3] + ad[i >> 2][1][i & 3]));
            bar_sync(BAR_RED, 416);
            if (warp < 4) {
                const int tid = 32 * warp + lane;
                const uint32_t rs = fresh(sb + SF_RED) + (tid >> 4) * 144 + (tid & 15) * 8;
                const uint2 tk = lds64(fresh(s_tok) + (tid >> 4) * 8);
                float x = 0.f, y = 0.f;
#pragma unroll
                for (int w = 0; w < 12; w++) { const uint2 v = lds64(rs + w * 1152); x += __uint_as_float(v.x); y += __uint_as_float(v.y); }
                asm volatile("red.relaxed.gpu.global.add.noftz.bf16x2 [%0], %1;" :: "l"(p.out + (size_t)tk.x * DM + 32 * (f >> 1) + 2 * (tid & 15)),
                             "r"(pack_bf16(x * __uint_as_float(tk.y), y * __uint_as_float(tk.y))) : "memory");
            }
            if (warp == 0) { TSTAMP(15); TFLUSH(); }
            asm volatile("exit;"); __builtin_unreachable();
        }
    }
}

__device__ __forceinline__ void fetch_k(const uint4* src, uint64_t (&v)[6], uint32_t a, uint32_t b) {
    asm volatile("{ .reg .pred p; setp.eq.u32 p, %7, %8; @p ld.relaxed.gpu.global.v2.u64 {%0,%1}, [%6]; @p ld.relaxed.gpu.global.v2.u64 {%2,%3}, [%6 + 512]; @p ld.relaxed.gpu.global.v2.u64 {%4,%5}, [%6 + 1024]; }"
                 : "+l"(v[0]), "+l"(v[1]), "+l"(v[2]), "+l"(v[3]), "+l"(v[4]), "+l"(v[5]) : "l"(src), "r"(a), "r"(b));
}
__device__ __forceinline__ uint32_t mini_conv(const Params& p, uint32_t sb, int warp, int lane, int f, unsigned epoch, uint64_t (&v)[6]) {
    const int g = lane >> 2, t = lane & 3, mi = lane >> 3, r8 = lane & 7;
    const uint32_t fb = sb + SF_MISC, kt = sb + (warp >= 12 ? SM_KT - 12 * 2112 : f < NW ? SM_KW + 2 * 2112 : SM_KW) + warp * 2112;
    const bool ism = f >= NW;
    const int ch0 = mini_ch0(f);
    uint32_t seq = 128, key;
    const uint4* src = p.s->kp + lane;
    auto hi = [&](int i) { return (uint32_t)(v[i] >> 32); };
    if (f >= (warp < 4 ? NW : NX)) {
    {
        const uint32_t c = 36 + (warp & 3) + 2 * (warp & 12), y = (uint32_t)((warp < 8 ? 0xa026802400000000ull : 0x2a2e00280080a22cull) >> ((8 * warp) & 48)) & 0xffff;
        seq = ism ? 0x101 * c - 0x400 : y + (warp & 1) * ((y >> 5) & 0x101);
        src += (ch0 + (seq & 31)) * 96;
    }
    if (seq & 32) {
        if (seq & 4) {
            const int q = (seq & 3) + ((seq >> 1) & 4);
            const uint32_t ab = sb - 3072 * (seq & 16), d = ab + SM_UT + g * MU_STRIDE + (8 + 4 * q + t) * 16;
            sts128(ab + SM_UT + (2 * q + (mi >> 1)) * MU_STRIDE + (mi & 1) * MU_HALF + r8 * 16, 0, 0, 0, 0);
            mbar_wait(fb + FB_MU - (seq & 16) / 2);
            if (warp == 15) TSTAMP(16);
            const uint32_t a = fresh(ab + SM_RAW) + q * 2048 + (8 * mi + 4 * (r8 & 1) + (r8 >> 1)) * 32 + ((r8 & 1) << 4);
            uint32_t x[4][4];
#pragma unroll
            for (int i = 0; i < 4; i++) ldsm4t(x[i], (i & 2 ? a ^ 16 : a) + 1024 * (i & 1));
#pragma unroll
            for (int i = 0; i < 4; i++) sts128(d + (i & 1) * MU_HALF + (i & 2) * 4 * MU_STRIDE, x[i][0], x[i][1], x[i][2], x[i][3]);
            __syncwarp();
            if (lane == 0) mbar_arrive(fb + FB_MT + (seq & 16) / 2);
        }
        mbar_wait(fb + FB_KDONE);
        fetch_k(src, v, warp < 4, 0);
        if ((warp | 2) == 7) { fetch_gates(p, (warp >> 1) & 1, lane, epoch, sb + SM_G + (lane & 1) * MU_HALF); __syncwarp(); if (lane == 0) mbar_arrive(fb + FB_MG); }
        if (warp >= 8) { mbar_wait(fb + FB_KEYS); mbar_wait(fb + FB_MT); }
        if (warp == TW) TSTAMP(17);
    }
    }
    const uint32_t lo = (mi & 1) * MU_HALF + (8 + col(r8)) * 16 + (mi >> 1) * 128;
#pragma unroll 1
    do {
        const int c = seq & 31;
        if (seq & 32) {
#pragma unroll 1
        for (int it = 0; !__all_sync(0xffffffffu, ((hi(1) ^ k_tag(epoch)) | (hi(3) ^ k_tag(epoch)) | (hi(5) ^ k_tag(epoch)) | ((uint32_t)v[5] & p.zero)) < 65536); it++) {
            fetch_k(src, v, 0, 0);
            if (it > (1 << 20)) give_up();
        }
        mbar_wait(fb + FB_MT + (seq & 16) / 2);
        sts128(kt + t * 16, 0, 0, 0, 0);
        if (warp == TW) TSTAMP(seq >> 8 ? 7 : 10);
        const uint32_t w[12] = {(uint32_t)v[0], hi(0), (uint32_t)v[1], (uint32_t)v[2], hi(2), (uint32_t)v[3], (uint32_t)v[4], hi(4), 0, 0, 0, 0};
        k_tables<false>(fresh(kt), fresh(lane), w);
        }
        __syncwarp();
        if (seq & 128) ffn_work(p, sb, warp, fresh(lane), f, epoch);
        if (!(seq & 32)) return 0;
        const uint32_t ab = sb - 49152 * (c >> 4), kb = fresh(kt) + (16 + g - 2 * t) * 4, ub = fresh(ab + SM_UT + (c & 15) * MU_STRIDE) + lo;
        const uint32_t yd = ab + SM_Y + (c & 15) * 1056 + (c & 8) * 8 + lane * 16;
        uint32_t kp = kb, u1 = ub;
        if (warp == TW && !(seq >> 8)) TSTAMP(13);
        seq >>= 8;
        src += ((int)(seq & 31) - c) * 96;
#pragma unroll
        for (int i = 0; i < 6; i++) v[i] = 0;
        key = 0;
        float acc[6][4];
#pragma unroll
        for (int i = 0; i < 6; i++) { acc[i][0] = acc[i][1] = acc[i][2] = acc[i][3] = 0.f; }
        uint32_t a[4][4], b[2][2][4];
        auto lda = [&](int j, int o) { const uint32_t x = kp + 64 * o + 512 * j; a[j][2] = o ? a[j][1] ^ p.zero : lds32((kp ^ p.zero) + 512 * j - 32); a[j][0] = lds32(x); a[j][1] = lds32(x + 32); a[j][3] = a[j][0] ^ p.zero; };
        auto ldb = [&](int s, int o) { ldsm4(b[s][0], u1 - 16 * o); ldsm4(b[s][1], u1 + 256 - 16 * o); };
        ldb(0, 0);
#pragma unroll
        for (int j = 0; j < 4; j++) lda(j, 0);
#pragma unroll
        for (int s = 0; s < 8; s++) {
            if (s == 4) {
                const uint32_t e = seq | (__float_as_uint(acc[0][0]) & p.zero);
                fetch_k(src, v, e & 32, 32);
                asm volatile("{ .reg .pred p; setp.eq.u32 p, %2, 0; @p ld.relaxed.gpu.global.u32 %0, [%1]; }" : "+r"(key) : "l"(&p.s->sel[((ch0 + c) >> 5) * 64 + r8]), "r"(e));
            }
            if (s < 7) ldb(~s & 1, s + 1);
#pragma unroll
            for (int i = 0; i < 4; i++) {
                const int j = (i >> 1) + 2 * (i & 1);
#pragma unroll
                for (int mu = 3 - j; mu >= 0; mu--) mma_bf(acc[j + mu + (j & 2)], a[j][0], a[j][1], a[j][2], a[j][3], b[s & 1][mu >> 1][2 * (mu & 1)], b[s & 1][mu >> 1][2 * (mu & 1) + 1]);
                if (s < 7) lda(j, s + 1);
            }
        }
        if (warp == TW && !seq) TSTAMP(14);
        mbar_wait(fb + FB_MG);
#pragma unroll
        for (int e = 0; e < 4; e++) { acc[2][e] += acc[4][e]; acc[3][e] += acc[5][e]; }
        uint32_t ug[4][4];
#pragma unroll
        for (int i = 0; i < 2; i++) { ldsm4t(ug[i], ub + 256 * i); ldsm4t(ug[2 + i], fresh(sb + SM_G) + lo + 256 * i); }
#pragma unroll
        for (int i = 0; i < 2; i++) {
            const uint32_t (&u)[4] = ug[i], (&gg)[4] = ug[2 + i];
            sts128(yd + 512 * i, gmix(gg[0], acc[2 * i][0], acc[2 * i][1], u[0]), gmix(gg[1], acc[2 * i][2], acc[2 * i][3], u[1]),
                   gmix(gg[2], acc[2 * i + 1][0], acc[2 * i + 1][1], u[2]), gmix(gg[3], acc[2 * i + 1][2], acc[2 * i + 1][3], u[3]));
        }
        __syncwarp();
        if (warp == TW) TSTAMP(18 + (seq != 0));
    } while (seq);
    if (warp >= 12) TSTAMP(12 + warp);
    return key;
}
__device__ __forceinline__ void mini_out(const Params& p, const CUtensorMap* maps, uint32_t sb, int warp, int lane, int f, unsigned epoch, uint32_t key) {
    const int g = lane >> 2, t = lane & 3, mi = lane >> 3, r8 = lane & 7;
    const uint32_t fb = sb + SF_MISC;
    const bool ism = f >= NW;
    const int ch0 = mini_ch0(f);
    const int k = ism ? warp >> 3 : 0;
    uint32_t first = 1;
    if (lane == 0) asm volatile("atom.shared.exch.b32 %0, [%1], 1;" : "=r"(first) : "r"(fb + FS_BM + 64 + 4 * k) : "memory");
    if (!__all_sync(0xffffffffu, first)) {
        if (elect()) prefetch_map(maps + 4);
        const int row = key_row(wait_sel(p, (ch0 + 16 * k) >> 5, r8, key_tag(epoch), key));
        if (row < 512) asm volatile("red.shared.or.b32 [%0], %1;" :: "r"(fb + FS_BM + (row >> 5) * 4), "r"(1u << (row & 31)) : "memory");
    }
    const int m = warp & 7, dr = 128 * (g >> 2) + 16 * (t >> 1) + 64 * (g & 1) + 8 * ((g >> 1) & 1);
    const uint32_t y = SM_Y + ((r8 >> 1) & 1) * 8512 + (2 * mi + (r8 & 1)) * 1056 + (2 * m + (r8 >> 2)) * 16;
    const uint32_t so = (g & 2) * 256 + (g >> 2) * 128 + r8 * 16;
    bar_sync(BAR_M - k, ism ? 256 : NTHR);
#pragma unroll 1
    for (int h = ism ? 0 : warp >> 3;; h++) {
        const int r0 = 256 * h + 32 * (m & 1) + (m >> 1), row = r0 + dr;
        const uint32_t bm = lds32(fresh(fb) + FS_BM + (row >> 5) * 4) >> (row & 31), ab = fresh(sb - 49152 * k + 512 * h), stg = ab + SM_UT + 2048 * m + 512 * h;
        uint32_t x[2][4];
        ldsm4t(x[0], ab + y); ldsm4t(x[1], ab + y + 256);
        if (warp == 0 && x[0][0] != 0x12345) TSTAMP(28);
        if (__any_sync(0xffffffffu, bm & 0x11u)) {
#pragma unroll
            for (int i = 0; i < 2; i++) store_or_add(p.out + (size_t)(row + 4 * i) * DM + ch0 + 16 * k + 8 * (t & 1), x[i], bm & (1u << (4 * i)));
        } else {
#pragma unroll
            for (int i = 0; i < 2; i++) sts128(stg + so + 256 * i, x[i][0], x[i][1], x[i][2], x[i][3]);
            asm volatile("fence.proxy.async.shared::cta;" ::: "memory");
            __syncwarp();
            if (elect()) store_rows(maps + 4, stg, ch0 + 16 * k, r0);
        }
        if (h >= ism) break;
    }
    if (elect()) { asm volatile("cp.async.bulk.commit_group;" ::: "memory"); asm volatile("cp.async.bulk.wait_group.read 0;" ::: "memory"); }
    if (warp == 8) TSTAMP(11);
    if (warp == 0) { TSTAMP(15); TFLUSH(); }
}

constexpr int SMEM_BYTES = 232448;
static_assert(SF_MISC + 1152 <= 232192, "layout");

struct Maps { CUtensorMap m[6]; };

__global__ void __cluster_dims__(2, 1, 1) __launch_bounds__(NTHR, 1)
fused_kernel(const Params p, const __grid_constant__ Maps maps) {
    extern __shared__ __align__(1024) uint8_t smem_raw[];
    uint32_t q[8];
    {
        const int b = blockIdx.x - NCONV, x = threadIdx.x, rc = 5 * b + (b & ~3) + 4 + (x >> 6);
        const int cv = (unsigned)b < NW ? 0 : -1, ca = (b < 0 ? 8 * b + DM : 48 * b - 2300) + ((x >> 5) & 3), cb = 2 * rc - (rc & 3) + 4;
        const uint32_t ch = (ca & cv) | (cb & ~cv), o = NST * ch + 2 * ((x & 31) + ((x >> (cv & 2)) & 32));
        const bool c = x < (cv ? 256 : 320);
        q[6] = ldg16_if(c, p.logdt + ch);
        q[2] = ldg32_if(c, p.Bre + o); q[3] = ldg32_if(c, p.Bim + o); q[4] = ldg32_if(c, p.Cre + o); q[5] = ldg32_if(c, p.Cim + o); q[0] = ldg32_if(c, p.Are + o); q[1] = ldg32_if(c, p.Aim + o);
        q[7] = ldg16_if(c, p.Dskip + ch);
    }
    const unsigned epoch = ld_rlx32(&p.s->epoch[blockIdx.x * 16 + (threadIdx.x >> 5)]);
    const uint32_t sb = __shfl_sync(0xffffffffu, smem_u32(smem_raw), 0);
    const int warp = __shfl_sync(0xffffffffu, threadIdx.x >> 5, 0), bid = __shfl_sync(0xffffffffu, blockIdx.x, 0);
    const int lane = __shfl_sync(0xffffffffu, threadIdx.x & 31, threadIdx.x);
    const bool conv = bid < NCONV;
    const int f = bid - NCONV;
    uint32_t w[12];
    uint64_t v[6];
    const bool four = (unsigned)f >= NW;
    if (warp < (four ? 8 : 10)) {
        const int half = four ? warp >> 2 : warp & 1, pr = four ? warp & 3 : warp >> 1;
        const int rc = 5 * f + (f & ~3) + 4 + pr;
        const uint32_t stage = sb + (conv ? SC_KG : SF_KG) + warp * KG_STAGE;
        uint4* const kp = p.s->kp + (four ? (conv ? 8 * bid : 48 * f - 2300) + pr : 2 * rc - (rc & 3) + 4) * 96 + lane;
        kgen(q, sb, half, stage, stage + (four ? 4 : 1) * KG_STAGE, 1 + pr, lane, w, [&] {
            sts128z_if(conv && lane < 20, sb + SC_KT + warp * KT_BYTES + lane * 16 + (lane < 4 ? 0 : lane < 14 ? 2048 : 2288));
            stg128z_if(!conv, kp + 64 * half); stg128z_if(!half && !conv, kp + 32);
            stg128z_if((unsigned)f < NW && warp < 6, (uint4*)(p.s->h + ((lane >> 4) * 288 + 6 * f + warp) * 32) + (lane & 15));
            if (conv) asm volatile("barrier.cluster.arrive.relaxed.aligned;" ::: "memory"); else bar_sync(0, NTHR);
        });
        if (!half) publish_k(kp, w, epoch, v);
        else for (int i = 0; i < 6; i++) v[i] = 0;
        if (conv) { conv_main(p, sb, warp, lane, bid, epoch, w); return; }
        {
            if (!half && lane == 0) mbar_arrive(sb + SF_MISC + FB_KDONE);
            if (warp == 0) TSTAMP(22);
            if (warp == 2) TSTAMP(23);
        }
    } else if (conv) {
        conv_aux(p, maps.m, sb, warp - 8, lane, bid, epoch);
        return;
    } else {
        ffn_front(p, maps.m, sb, warp, lane, f, epoch);
        for (int i = 0; i < 6; i++) v[i] = 0;
    }
    converged();
    next_epoch(p, epoch);
    if (warp >= 12 && f < NX) return;
    mini_out(p, maps.m, sb, warp, lane, f, epoch, mini_conv(p, sb, warp, __shfl_sync(0xffffffffu, lane, lane), f, epoch, v));
}

typedef CUresult (*EncodeFn)(CUtensorMap*, CUtensorMapDataType, cuuint32_t, void*, const cuuint64_t*, const cuuint64_t*, const cuuint32_t*, const cuuint32_t*,
                             CUtensorMapInterleave, CUtensorMapSwizzle, CUtensorMapL2promotion, CUtensorMapFloatOOBfill);

void make_map(EncodeFn fn, CUtensorMap* m, const void* base, int rank, const cuuint64_t* dims, const cuuint64_t* strides, const cuuint32_t* box, CUtensorMapSwizzle sw) {
    const cuuint32_t es[5] = {1, 1, 1, 1, 1};
    fn(m, CU_TENSOR_MAP_DATA_TYPE_BFLOAT16, rank, (void*)base, dims, strides, box, es, CU_TENSOR_MAP_INTERLEAVE_NONE, sw,
       CU_TENSOR_MAP_L2_PROMOTION_NONE, CU_TENSOR_MAP_FLOAT_OOB_FILL_NONE);
}

}

extern "C" void kernel_launch(void* const* d_in, const int* in_sizes, int n_in, void* d_out, int out_size) {
    (void)in_sizes; (void)n_in; (void)out_size;
    static EncodeFn fn = nullptr;
    static void* scratch = nullptr;
    if (!fn) {
        void* ptr = nullptr; cudaDriverEntryPointQueryResult qr;
        cudaGetDriverEntryPoint("cuTensorMapEncodeTiled", &ptr, cudaEnableDefault, &qr);
        fn = (EncodeFn)ptr;
        cudaGetSymbolAddress(&scratch, g_scratch);
        cudaFuncSetAttribute(fused_kernel, cudaFuncAttributeMaxDynamicSharedMemorySize, SMEM_BYTES);
    }
    typedef const __nv_bfloat16* bp;
    Params p;
    p.u = (bp)d_in[0]; p.Are = (bp)d_in[1]; p.Aim = (bp)d_in[2]; p.Bre = (bp)d_in[3]; p.Bim = (bp)d_in[4]; p.Cre = (bp)d_in[5]; p.Cim = (bp)d_in[6];
    p.logdt = (bp)d_in[7]; p.Dskip = (bp)d_in[8]; p.wr = (bp)d_in[10]; p.gatew = (bp)d_in[14];
    p.out = (__nv_bfloat16*)d_out; p.s = (Scratch*)scratch; p.zero = 0;
    Maps maps;
    {
        const cuuint64_t dims[4] = {DM, 4, 16, 32}, strides[3] = {16 * DM * 2, DM * 2, 64 * DM * 2};
        const cuuint32_t box[4] = {16, 4, 16, 2};
        make_map(fn, &maps.m[0], d_in[0], 4, dims, strides, box, CU_TENSOR_MAP_SWIZZLE_32B);
        const cuuint32_t box2[4] = {16, 4, 16, 8};
        make_map(fn, &maps.m[5], d_in[0], 4, dims, strides, box2, CU_TENSOR_MAP_SWIZZLE_32B);
    }
    for (int i = 0; i < 2; i++) {
        const cuuint64_t dims[3] = {32, DM, FF / 32}, strides[2] = {FF * 2, 64};
        const cuuint32_t box[3] = {32, 64, 3};
        make_map(fn, &maps.m[1 + i], d_in[11 + i], 3, dims, strides, box, CU_TENSOR_MAP_SWIZZLE_64B);
    }
    {
        const cuuint64_t dims[2] = {DM, FF}, strides[1] = {DM * 2};
        const cuuint32_t box[2] = {32, 192};
        make_map(fn, &maps.m[3], d_in[13], 2, dims, strides, box, CU_TENSOR_MAP_SWIZZLE_64B);
    }
    {
        const cuuint64_t dims[5] = {DM, 2, 4, 4, L_SEQ}, strides[4] = {16 * DM * 2, 64 * DM * 2, 4 * DM * 2, DM * 2};
        const cuuint32_t box[5] = {16, 2, 4, 4, 1};
        make_map(fn, &maps.m[4], d_out, 5, dims, strides, box, CU_TENSOR_MAP_SWIZZLE_NONE);
    }
    fused_kernel<<<NCTA, NTHR, SMEM_BYTES>>>(p, maps);
}
```

```cpp
#include <cuda_runtime.h>
#include <cuda_bf16.h>
#include <cuda_fp16.h>
#include <cuda.h>
#include <stdint.h>
#include <type_traits>

#define RESUME 300
#define MDELAY 2000
#define MGAP 0
#define DUN 1
#define KPOLL 500
#define DPA 7
#define DPB 9
#define RDELAY 900
#define WDELAY 2000
#define WGAP 290
#define NPRE 7
#define DGAP 260
namespace {
constexpr int DUNR = DUN;

constexpr int DM = 576, NST = 128, FF = 4608, L_SEQ = 2048;
constexpr int NCONV = 72, NX = 36, NW = 48, NCTA = 132, NTHR = 512;

struct __align__(128) Scratch {
    unsigned epoch[NCTA * 16];
    uint4 keys[16 * 128];
    uint32_t sel[18 * 64];
    uint16_t gate[L_SEQ];
    uint2 h[2 * 288 * 32];
    uint4 kp[DM * 96];
};
__device__ Scratch g_scratch;
#define TFLUSH()
#define TSTAMP(i)
#define TW 12

struct Params {
    const __nv_bfloat16 *Are, *Aim, *Bre, *Bim, *Cre, *Cim, *logdt, *Dskip, *u, *wr, *gatew;
    __nv_bfloat16* out;
    Scratch* s;
    uint32_t zero;
};

__device__ __forceinline__ void give_up() { asm volatile("trap; exit;"); __builtin_unreachable(); }
__device__ __forceinline__ void converged() { __syncwarp(); asm volatile("{ .reg .b32 t; mov.b32 t, 0; movmatrix.sync.aligned.m8n8.trans.b16 t, t; }" ::: "memory"); }
__device__ __forceinline__ bool elect() { uint32_t r; asm volatile("{ .reg .pred p; elect.sync _|p, 0xffffffff; selp.u32 %0, 1, 0, p; }" : "=r"(r)); return r; }
__device__ __forceinline__ uint32_t smem_u32(const void* p) { return (uint32_t)__cvta_generic_to_shared(p); }
__device__ __forceinline__ uint32_t pack_bf16(float lo, float hi) { uint32_t r; asm("cvt.rn.bf16x2.f32 %0, %1, %2;" : "=r"(r) : "f"(hi), "f"(lo)); return r; }
__device__ __forceinline__ uint32_t pack_f16(float lo, float hi) { uint32_t r; asm("cvt.rn.f16x2.f32 %0, %1, %2;" : "=r"(r) : "f"(hi), "f"(lo)); return r; }
__device__ __forceinline__ float bf_lo(uint32_t w) { return __uint_as_float(w << 16); }
__device__ __forceinline__ float bf_hi(uint32_t w) { return __uint_as_float(w & 0xffff0000u); }
__device__ __forceinline__ float rbf(float x) { return bf_lo(pack_bf16(x, 0.f)); }
__device__ __forceinline__ uint32_t badd2(uint32_t a, uint32_t b) { uint32_t r; asm("add.rn.bf16x2 %0, %1, %2;" : "=r"(r) : "r"(a), "r"(b)); return r; }
__device__ __forceinline__ uint32_t bsub2(uint32_t a, uint32_t b) { uint32_t r; asm("sub.rn.bf16x2 %0, %1, %2;" : "=r"(r) : "r"(a), "r"(b)); return r; }
__device__ __forceinline__ uint32_t gmix(uint32_t ng, float ny0, float ny1, uint32_t u) {
    uint32_t r; asm("{ .reg .b32 t; fma.rn.bf16x2 t, %1, %3, %3; fma.rn.bf16x2 %0, %1, %2, t; }" : "=r"(r) : "r"(ng), "r"(pack_bf16(ny0, ny1)), "r"(u)); return r;
}
__device__ __forceinline__ void mma_bf(float (&c)[4], uint32_t a0, uint32_t a1, uint32_t a2, uint32_t a3, uint32_t b0, uint32_t b1) {
    asm("mma.sync.aligned.m16n8k16.row.col.f32.bf16.bf16.f32 {%0,%1,%2,%3}, {%4,%5,%6,%7}, {%8,%9}, {%0,%1,%2,%3};"
        : "+f"(c[0]), "+f"(c[1]), "+f"(c[2]), "+f"(c[3]) : "r"(a0), "r"(a1), "r"(a2), "r"(a3), "r"(b0), "r"(b1));
}
__device__ __forceinline__ void mma_bf8(float (&c)[4], uint32_t a0, uint32_t a1, uint32_t b0) {
    asm("mma.sync.aligned.m16n8k8.row.col.f32.bf16.bf16.f32 {%0,%1,%2,%3}, {%4,%5}, {%6}, {%0,%1,%2,%3};"
        : "+f"(c[0]), "+f"(c[1]), "+f"(c[2]), "+f"(c[3]) : "r"(a0), "r"(a1), "r"(b0));
}
__device__ __forceinline__ void mma_h(float (&c)[4], uint32_t a0, uint32_t a1, uint32_t a2, uint32_t a3, uint32_t b0, uint32_t b1) {
    asm("mma.sync.aligned.m16n8k16.row.col.f32.f16.f16.f32 {%0,%1,%2,%3}, {%4,%5,%6,%7}, {%8,%9}, {%0,%1,%2,%3};"
        : "+f"(c[0]), "+f"(c[1]), "+f"(c[2]), "+f"(c[3]) : "r"(a0), "r"(a1), "r"(a2), "r"(a3), "r"(b0), "r"(b1));
}
__device__ __forceinline__ uint32_t fresh(uint32_t a) { asm volatile("" : "+r"(a) :: "memory"); return a; }
__device__ __forceinline__ uint32_t lds32(uint32_t a) { uint32_t v; asm("ld.shared.u32 %0, [%1];" : "=r"(v) : "r"(a)); return v; }
__device__ __forceinline__ uint2 lds64(uint32_t a) { uint2 v; asm("ld.shared.v2.u32 {%0,%1}, [%2];" : "=r"(v.x), "=r"(v.y) : "r"(a)); return v; }
__device__ __forceinline__ uint4 lds128(uint32_t a) { uint4 v; asm("ld.shared.v4.u32 {%0,%1,%2,%3}, [%4];" : "=r"(v.x), "=r"(v.y), "=r"(v.z), "=r"(v.w) : "r"(a)); return v; }
__device__ __forceinline__ void ldsm4(uint32_t (&r)[4], uint32_t a) {
    asm("ldmatrix.sync.aligned.m8n8.x4.shared.b16 {%0,%1,%2,%3}, [%4];" : "=r"(r[0]), "=r"(r[1]), "=r"(r[2]), "=r"(r[3]) : "r"(a));
}
__device__ __forceinline__ void ldsm4t(uint32_t (&r)[4], uint32_t a) {
    asm("ldmatrix.sync.aligned.m8n8.x4.trans.shared.b16 {%0,%1,%2,%3}, [%4];" : "=r"(r[0]), "=r"(r[1]), "=r"(r[2]), "=r"(r[3]) : "r"(a));
}
__device__ __forceinline__ void sts16(uint32_t a, uint32_t v) { asm volatile("st.shared.u16 [%0], %1;" :: "r"(a), "h"((unsigned short)v) : "memory"); }
__device__ __forceinline__ void sts32(uint32_t a, uint32_t v) { asm volatile("st.shared.u32 [%0], %1;" :: "r"(a), "r"(v) : "memory"); }
__device__ __forceinline__ void sts64(uint32_t a, uint32_t x, uint32_t y) { asm volatile("st.shared.v2.u32 [%0], {%1,%2};" :: "r"(a), "r"(x), "r"(y) : "memory"); }
__device__ __forceinline__ void sts128(uint32_t a, uint32_t x, uint32_t y, uint32_t z, uint32_t w) {
    asm volatile("st.shared.v4.u32 [%0], {%1,%2,%3,%4};" :: "r"(a), "r"(x), "r"(y), "r"(z), "r"(w) : "memory");
}
__device__ __forceinline__ void st_async128(uint32_t a, uint32_t x, uint32_t y, uint32_t z, uint32_t w, uint32_t bar) {
    asm volatile("st.async.weak.shared::cluster.mbarrier::complete_tx::bytes.v4.b32 [%0], {%1,%2,%3,%4}, [%5];" :: "r"(a), "r"(x), "r"(y), "r"(z), "r"(w), "r"(bar) : "memory");
}
__device__ __forceinline__ void mbar_init(uint32_t b, uint32_t cnt) { asm volatile("mbarrier.init.shared::cta.b64 [%0], %1;" :: "r"(b), "r"(cnt) : "memory"); }
__device__ __forceinline__ void mbar_fence() { asm volatile("fence.mbarrier_init.release.cluster;" ::: "memory"); }
__device__ __forceinline__ void mbar_expect(uint32_t b, uint32_t bytes) { asm volatile("mbarrier.arrive.expect_tx.shared::cta.b64 _, [%0], %1;" :: "r"(b), "r"(bytes) : "memory"); }
__device__ __forceinline__ void mbar_arrive(uint32_t b) { asm volatile("mbarrier.arrive.shared::cta.b64 _, [%0];" :: "r"(b) : "memory"); }
__device__ __forceinline__ void mbar_wait(uint32_t b, uint32_t parity = 0) {
    asm volatile("{ .reg .pred p; .reg .u32 n; mov.u32 n, 0;\n"
                 "LW: mbarrier.try_wait.parity.shared::cta.b64 p, [%0], %1; @p bra LD; add.u32 n, n, 1; setp.lt.u32 p, n, 65536; @p bra LW; trap;\n"
                 "LD: }" :: "r"(b), "r"(parity) : "memory");
}
__device__ __forceinline__ void mbar_wait_cluster(uint32_t b) {
    asm volatile("{ .reg .pred p; .reg .u32 n; mov.u32 n, 0;\n"
                 "LW: mbarrier.try_wait.parity.acquire.cluster.shared::cta.b64 p, [%0], 0; @p bra LD; add.u32 n, n, 1; setp.lt.u32 p, n, 65536; @p bra LW; trap;\n"
                 "LD: }" :: "r"(b) : "memory");
}
__device__ __forceinline__ void tma2d(uint32_t dst, const CUtensorMap* m, int c0, int c1, uint32_t bar) {
    asm volatile("cp.async.bulk.tensor.2d.shared::cluster.global.mbarrier::complete_tx::bytes [%0], [%1, {%3, %4}], [%2];"
                 :: "r"(dst), "l"(m), "r"(bar), "r"(c0), "r"(c1) : "memory");
}
__device__ __forceinline__ void tma3d(uint32_t dst, const CUtensorMap* m, int c0, int c1, int c2, uint32_t bar) {
    asm volatile("cp.async.bulk.tensor.3d.shared::cluster.global.mbarrier::complete_tx::bytes [%0], [%1, {%3, %4, %5}], [%2];"
                 :: "r"(dst), "l"(m), "r"(bar), "r"(c0), "r"(c1), "r"(c2) : "memory");
}
__device__ __forceinline__ void tma4d(uint32_t dst, const CUtensorMap* m, int c0, int c1, int c2, int c3, uint32_t bar) {
    asm volatile("cp.async.bulk.tensor.4d.shared::cluster.global.mbarrier::complete_tx::bytes [%0], [%1, {%3, %4, %5, %6}], [%2];"
                 :: "r"(dst), "l"(m), "r"(bar), "r"(c0), "r"(c1), "r"(c2), "r"(c3) : "memory");
}
__device__ __forceinline__ void bulk_g2s(uint32_t dst, const void* src, uint32_t bytes, uint32_t bar) {
    asm volatile("cp.async.bulk.shared::cluster.global.mbarrier::complete_tx::bytes [%0], [%1], %2, [%3];"
                 :: "r"(dst), "l"(src), "r"(bytes), "r"(bar) : "memory");
}
__device__ __forceinline__ uint32_t mapa(uint32_t a, uint32_t rank) { uint32_t r; asm("mapa.shared::cluster.u32 %0, %1, %2;" : "=r"(r) : "r"(a), "r"(rank)); return r; }
__device__ __forceinline__ void prefetch_map(const CUtensorMap* m) { asm volatile("prefetch.tensormap [%0];" :: "l"(m) : "memory"); }
__device__ __forceinline__ void bar_sync(int id, int n) { asm volatile("bar.sync %0, %1;" :: "r"(id), "r"(n) : "memory"); }
__device__ __forceinline__ void bar_arrive(int id, int n) { asm volatile("bar.arrive %0, %1;" :: "r"(id), "r"(n) : "memory"); }
__device__ __forceinline__ uint32_t ldg16_if(bool c, const void* p) { uint32_t v; asm volatile("{ .reg .pred p; setp.ne.u32 p, %2, 0; @p ld.global.nc.u16 %0, [%1]; }" : "=r"(v) : "l"(p), "r"((uint32_t)c)); return v; }
__device__ __forceinline__ uint32_t ldg32_if(bool c, const void* p) { uint32_t v; asm volatile("{ .reg .pred p; setp.ne.u32 p, %2, 0; @p ld.global.nc.u32 %0, [%1]; }" : "=r"(v) : "l"(p), "r"((uint32_t)c)); return v; }
__device__ __forceinline__ uint32_t ld_rlx32(const void* p) { uint32_t v; asm volatile("ld.relaxed.gpu.global.u32 %0, [%1];" : "=r"(v) : "l"(p) : "memory"); return v; }
__device__ __forceinline__ uint4 ld_rlx128(const void* p) {
    uint4 v; asm volatile("ld.relaxed.gpu.global.v4.u32 {%0,%1,%2,%3}, [%4];" : "=r"(v.x), "=r"(v.y), "=r"(v.z), "=r"(v.w) : "l"(p) : "memory"); return v;
}
__device__ __forceinline__ void st_rlx32(void* p, uint32_t v) { asm volatile("st.relaxed.gpu.global.u32 [%0], %1;" :: "l"(p), "r"(v) : "memory"); }
__device__ __forceinline__ void stg128(void* p, uint32_t x, uint32_t y, uint32_t z, uint32_t w) {
    asm volatile("st.global.v4.u32 [%0], {%1,%2,%3,%4};" :: "l"(p), "r"(x), "r"(y), "r"(z), "r"(w) : "memory");
}
__device__ __forceinline__ void next_epoch(const Params& p, unsigned e) { if ((threadIdx.x & 31) == 0) p.s->epoch[blockIdx.x * 16 + (threadIdx.x >> 5)] = e + 1; }
__device__ __forceinline__ void sts128z_if(bool c, uint32_t a) { asm volatile("{ .reg .pred p; setp.ne.u32 p, %1, 0; @p st.shared.v4.u32 [%0], {%2,%2,%2,%2}; }" :: "r"(a), "r"((uint32_t)c), "r"(0) : "memory"); }
__device__ __forceinline__ void stg128z_if(bool c, void* a) { asm volatile("{ .reg .pred p; setp.ne.u32 p, %1, 0; @p st.global.v4.u32 [%0], {%2,%2,%2,%2}; }" :: "l"(a), "r"((uint32_t)c), "r"(0) : "memory"); }
__device__ __forceinline__ unsigned clock32() { unsigned c; asm volatile("mov.u32 %0, %clock;" : "=r"(c) :: "memory"); return c; }
__device__ __forceinline__ void until(unsigned t0, int c) { while ((int)(clock32() - t0) < c) { } }
__device__ __forceinline__ float sigmoidf_(float x) { return __fdividef(1.0f, 1.0f + __expf(-x)); }
__device__ __forceinline__ uint32_t key_tag(unsigned epoch) { return ((epoch & 15u) | 16u) << 11; }
__device__ __forceinline__ int key_row(uint32_t key) { return 2047 - (int)(key & 2047u); }
__device__ __forceinline__ uint32_t wait_sel(const Params& p, int s32, int r8, uint32_t tag, uint32_t k = 0) {
#pragma unroll 1
    for (int it = 0; !__all_sync(0xffffffffu, (k & 0xf800u) == tag); it++) {
        k = ld_rlx32(&p.s->sel[s32 * 64 + r8]);
        if (it > (1 << 20)) give_up();
    }
    return k;
}

struct cplx { float re, im; };
__device__ __forceinline__ cplx csq(cplx a) { cplx r; r.re = a.re * a.re - a.im * a.im; r.im = (a.re * a.im) * 2.f; return r; }
__device__ __forceinline__ cplx cexpk(float ar, float ai, float k) {
    float mag, s, c;
    asm("ex2.approx.ftz.f32 %0, %1;" : "=f"(mag) : "f"(ar * (k * 1.4426950408889634f)));
    const float r = ai * k;
    asm("sin.approx.ftz.f32 %0, %1;" : "=f"(s) : "f"(r));
    asm("cos.approx.ftz.f32 %0, %1;" : "=f"(c) : "f"(r));
    cplx o; o.re = mag * c; o.im = mag * s; return o;
}
struct h2c { uint32_t re, im; };
__device__ __forceinline__ h2c cmul_cd(h2c v, __half2 c, __half2 d) {
    const __half2 r = *(const __half2*)&v.re, i = *(const __half2*)&v.im;
    const __half2 x = __hfma2(__hneg2(i), d, __hmul2(r, c)), y = __hfma2(i, c, __hmul2(r, d));
    h2c o; o.re = *(const uint32_t*)&x; o.im = *(const uint32_t*)&y; return o;
}
__device__ __forceinline__ h2c cmul_s(h2c v, uint32_t s) { const __half2 h = *(const __half2*)&s; return cmul_cd(v, __low2half2(h), __high2half2(h)); }
__device__ __forceinline__ h2c cmul_sc(h2c v, uint32_t s) {
    const __half2 h = *(const __half2*)&s, c = __low2half2(h), d = __high2half2(h), r = *(const __half2*)&v.re, i = *(const __half2*)&v.im;
    const __half2 x = __hfma2(i, d, __hmul2(r, c)), y = __hfma2(__hneg2(r), d, __hmul2(i, c));
    h2c o; o.re = *(const uint32_t*)&x; o.im = *(const uint32_t*)&y; return o;
}
__device__ __forceinline__ h2c cmul_vc(h2c v, uint32_t s) {
    const __half2 h = *(const __half2*)&s, c = __low2half2(h), d = __high2half2(h), r = *(const __half2*)&v.re, i = *(const __half2*)&v.im;
    const __half2 x = __hfma2(i, d, __hmul2(r, c)), y = __hfma2(__hneg2(i), c, __hmul2(r, d));
    h2c o; o.re = *(const uint32_t*)&x; o.im = *(const uint32_t*)&y; return o;
}

constexpr int UT_HALF = 2560, UT_STRIDE = 4768, GT_HALF = 2240;
__device__ __forceinline__ uint32_t swz(uint32_t x) { return x ^ ((x >> 2) & 64); }
__device__ __forceinline__ int col(int n) { return (n >> 1) + 4 * (n & 1); }
constexpr int KT_T = 542, KT_C = 552, KT_D = 645, KT_BYTES = 720 * 4;
constexpr int VC_OFF = 80, VE_BASE = 1616;
constexpr int V_STRIDE = (1616 + 1024) * 4 + 80;
constexpr int KG_STAGE = 5248;
constexpr int Y_CS = 2080, Y_RS = 8 * Y_CS + 64;

constexpr int SC_RT = 0;
constexpr int SC_UT = 33408;
constexpr int SC_KG = SC_UT + 8 * UT_STRIDE;
constexpr int SC_KT = SC_KG + 8 * KG_STAGE;
constexpr int SC_GT = SC_KT + 8 * KT_BYTES;
constexpr int SC_V = SC_GT + 4448;
constexpr int SC_MISC = SC_V + 8 * V_STRIDE;
static_assert(V_STRIDE % 128 == 16 && 2 * Y_RS <= SC_UT && SC_UT % 128 == 0 && SC_KG % 128 == 0, "layout");
static_assert(SC_MISC % 16 == 0 && SC_MISC + 512 <= 232192, "layout");

__device__ __forceinline__ void window_task(uint32_t s0, uint32_t s1, uint32_t d0, uint32_t d1, int k) {
    float S[51], s = 0.f;
    uint32_t w[28];
#pragma unroll
    for (int i = 0; i < 7; i++) {
        const uint4 v = lds128((i < 3 ? s0 : s1 - 32) + ((i & 1) ? 0 : UT_HALF) + ((i + 1) >> 1) * 16);
        w[4 * i] = v.x; w[4 * i + 1] = v.y; w[4 * i + 2] = v.z; w[4 * i + 3] = v.w;
    }
    auto sums = [&](int lo, int hi) {
#pragma unroll
        for (int i = lo; i < hi; i++) { const float x = (i & 1) ? bf_hi(w[i >> 1]) : bf_lo(w[i >> 1]); s = i > 3 ? s + x : x; S[i] = s; }
    };
    auto put = [&](int off, int b, int o0, int o1, int o2) {
        auto v = [&](int i) { i += 16 * b; return pack_bf16(S[o0 + i] - S[o1 + i], S[o1 + i] - S[o2 + i]); };
#pragma unroll
        for (int i = 0; i < 8; i += 2) sts128((i & 4 ? d1 : d0) + 4 * off + 64 * b + 8 * (i & 2), v(i), v(i + 8), v(i + 1), v(i + 9));
    };
    S[2] = 0.f;
    sums(3, 26); put(VC_OFF - 16, 0, 10, 5, 2);
    if (k == 12) return;
    sums(26, 42); put(VC_OFF - 16, 1, 10, 5, 2);
    if (k < 8) { put(VE_BASE, 0, 19, 12, 3); sums(42, 51); put(VE_BASE, 1, 19, 12, 3); }
}

template <class F>
__device__ __forceinline__ void kgen(const uint32_t (&q)[8], uint32_t sb, int half, uint32_t stage, uint32_t pstage, int barid, int lane, uint32_t (&w)[12], F shadow) {
    const int t = lane & 3, mi = lane >> 3, r8 = lane & 7;
    {
        const uint32_t pAr = q[0], pAi = q[1], pBr = q[2], pBi = q[3], pCr = q[4], pCi = q[5], pDt = q[6], pD = q[7];
        const uint32_t wb = fresh(stage + lane * 16), za = fresh(stage + 5120 + ((lane >> 1) & 3) * 16 + mi * 4 + (lane & 1) * 2), zr = fresh(stage + 5120 + t * 16);
        const uint32_t oA = fresh(stage + (mi & 1) * 1024 + (mi >> 1) * 512 + r8 * 16), oB = fresh(stage + 2048 + mi * 512 + r8 * 16), oC = fresh(stage + 4096 + (mi & 1) * 512 + (mi >> 1) * 128 + r8 * 16);
        float acc[6][4];
#pragma unroll
        for (int a = 0; a < 6; a++) { acc[a][0] = acc[a][1] = acc[a][2] = acc[a][3] = 0.f; asm volatile("" : "+f"(acc[a][0]), "+f"(acc[a][1]), "+f"(acc[a][2]), "+f"(acc[a][3])); }
        shadow();
        sts32(zr, clock32());
        const float dt = rbf(__expf(bf_lo(pDt)));
        float ar = dt * bf_lo(pAr), ai = dt * bf_lo(pAi), ar1 = dt * bf_hi(pAr), ai1 = dt * bf_hi(pAi);
        float wr, wi, wr1, wi1;
        { const float br = dt * bf_lo(pBr), bi = dt * bf_lo(pBi), cr = bf_lo(pCr), ci = bf_lo(pCi); wr = cr * br - ci * bi; wi = cr * bi + ci * br; }
        { const float br = dt * bf_hi(pBr), bi = dt * bf_hi(pBi), cr = bf_hi(pCr), ci = bf_hi(pCi); wr1 = cr * br - ci * bi; wi1 = cr * bi + ci * br; }
        const uint32_t ex = max(__reduce_max_sync(0xffffffffu, __float_as_uint(fmaxf(fmaxf(fabsf(wr), fabsf(wi)), fmaxf(fabsf(wr1), fabsf(wi1))))) >> 23, 14u);
        const float scl = __uint_as_float((267u - ex) << 23);
        uint32_t W = pack_f16(wr * scl, wi * -scl);
        const uint32_t W1 = pack_f16(wr1 * scl, wi1 * -scl);
        if (threadIdx.x < 32) TSTAMP(20);

#pragma unroll 1
        for (int r = 0; r < 2; r++) {
            const cplx z1 = cexpk(ar, ai, 1.f), z64 = cexpk(ar, ai, 64.f);
            const cplx z2 = csq(z1), z4 = csq(z2), z8 = csq(z4), z16 = csq(z8), z32 = csq(z16);
            const cplx z128 = csq(z64), z256 = csq(z128), z512 = csq(z256);
            auto put = [&](int grp, h2c a, h2c b, h2c c, h2c d) { sts128(wb + grp * 1024, a.re, b.re, c.re, d.re); sts128(wb + grp * 1024 + 512, a.im, b.im, c.im, d.im); };
            {
                const uint32_t s4 = pack_f16(z4.re, z4.im), s256 = pack_f16(z256.re, z256.im), s512 = pack_f16(z512.re, z512.im);
                auto mix = [](h2c a, h2c b, uint32_t sel) { return h2c{__byte_perm(a.re, b.re, sel), __byte_perm(a.im, b.im, sel)}; };
                const h2c c10 = cmul_vc(h2c{pack_f16(z1.re, 1.f), pack_f16(z1.im, 0.f)}, W), c32 = cmul_sc(c10, pack_f16(z2.re, z2.im)), c54 = cmul_sc(c10, s4);
                put(2, c10, c32, c54, cmul_sc(c32, s4));
                const h2c d20 = cmul_sc(mix(c32, c10, 0x7632), s256), e04 = cmul_sc(mix(c10, c54, 0x7632), s512), f04 = cmul_sc(e04, s256);
                put(3, d20, cmul_sc(d20, s4), e04, f04);
                const h2c ef = mix(e04, f04, 0x5410), gh = cmul_sc(ef, s512), g8 = cmul_sc(gh, pack_f16(z8.re, z8.im));
                put(4, g8, cmul_sc(g8, s512), gh, ef);
            }
            {
                const uint32_t s32 = pack_f16(z32.re, z32.im), s64 = pack_f16(z64.re, z64.im), s128 = pack_f16(z128.re, z128.im);
                const h2c p0 = {pack_f16(1.f, z8.re), pack_f16(0.f, z8.im)}, p1 = cmul_s(p0, pack_f16(z16.re, z16.im)), p2 = cmul_s(p0, s32), p3 = cmul_s(p1, s32);
                put(0, p0, p1, p2, p3);
                put(1, cmul_s(p0, s64), cmul_s(p1, s64), cmul_s(p2, s64), cmul_s(p3, s64));
                sts16(za, s128); sts16(za + 64, s128 >> 16);
            }
            __syncwarp();
            {
                const uint32_t aA = fresh(oA), aB = fresh(oB), aC = fresh(oC), aZ = fresh(zr);
                const uint4 zc = lds128(aZ), zd = lds128(aZ + 64);
                const uint32_t zcs[4] = {zc.x, zc.y, zc.z, zc.w}, zds[4] = {zd.x, zd.y, zd.z, zd.w};
                uint32_t c[4];
#pragma unroll
                for (int k = 0; k < 4; k++) {
                    uint32_t a[4], b[4];
                    ldsm4t(a, aA + 128 * k); ldsm4t(b, aB + 128 * k);
                    if (!(k & 1)) ldsm4t(c, aC + 128 * k);
                    const h2c x = cmul_cd(h2c{a[0], a[2]}, *(const __half2*)&zcs[k], *(const __half2*)&zds[k]), y = cmul_cd(h2c{a[1], a[3]}, *(const __half2*)&zcs[k], *(const __half2*)&zds[k]);
                    mma_h(acc[0], a[0], a[1], a[2], a[3], b[0], b[1]);
                    mma_h(acc[1], a[0], a[1], a[2], a[3], b[2], b[3]);
                    mma_h(acc[2], a[0], a[1], a[2], a[3], c[2 * (k & 1)], c[2 * (k & 1) + 1]);
                    mma_h(acc[3], x.re, y.re, x.im, y.im, b[0], b[1]);
                    mma_h(acc[4], x.re, y.re, x.im, y.im, b[2], b[3]);
                    mma_h(acc[5], x.re, y.re, x.im, y.im, c[2 * (k & 1)], c[2 * (k & 1) + 1]);
                }
                asm volatile("" :: "f"(acc[0][0]), "f"(acc[1][0]), "f"(acc[2][0]), "f"(acc[3][0]), "f"(acc[4][0]), "f"(acc[5][0]) : "memory");
            }
            __syncwarp();
            ar = ar1; ai = ai1; W = W1;
        }
        if (threadIdx.x < 32) TSTAMP(21);
        const float i0 = __uint_as_float((ex + 243u) << 23);
        if (half) {
#pragma unroll
            for (int a = 0; a < 6; a++) sts128(wb + a * 512, __float_as_uint(acc[a][0]), __float_as_uint(acc[a][1]), __float_as_uint(acc[a][2]), __float_as_uint(acc[a][3]));
            sts32(stage + 3072, __float_as_uint(i0));
            bar_arrive(barid, 64);
        } else {
#pragma unroll
            for (int a = 0; a < 6; a++) { acc[a][0] *= i0; acc[a][1] *= i0; acc[a][2] *= i0; acc[a][3] *= i0; }
            if (lane == 0) acc[0][1] -= bf_lo(pD);
            sts32(zr, clock32());
            bar_sync(barid, 64);
            const uint32_t src = fresh(pstage);
            const float i1 = __uint_as_float(lds32(src + 3072));
#pragma unroll
            for (int a = 0; a < 6; a++) {
                const uint4 y = lds128(src + lane * 16 + a * 512);
                w[4 * (a % 3) + 2 * (a / 3)] = pack_bf16(fmaf(__uint_as_float(y.x), i1, acc[a][0]), fmaf(__uint_as_float(y.y), i1, acc[a][1]));
                w[4 * (a % 3) + 2 * (a / 3) + 1] = pack_bf16(fmaf(__uint_as_float(y.z), i1, acc[a][2]), fmaf(__uint_as_float(y.w), i1, acc[a][3]));
            }
            const uint32_t x0 = __shfl_up_sync(0xffffffffu, w[10], 2), x1 = __shfl_up_sync(0xffffffffu, w[11], 2);
            w[10] = w[8];
            if (t >= 2) { w[8] = x0; w[9] = x1; }
        }
    }
}

__device__ __forceinline__ int swap01(int i) { return (i & ~3) | ((i & 1) << 1) | ((i >> 1) & 1); }
__device__ __forceinline__ int ut_off(int i) { return i * UT_STRIDE + (i & 4) * 4; }
enum { BC_AUX = 0, BC_U = 5 };

__device__ __forceinline__ void fetch_gates(const Params& p, int i, int lane, unsigned epoch, uint32_t dst) {
    const uint32_t par = (epoch & 1) ? 0x80008000u : 0u;
    uint4 v;
#pragma unroll 1
    for (int it = 0;; it++) {
        v = ld_rlx128(p.s->gate + 256 * i + 8 * lane);
        v.x ^= par; v.y ^= par; v.z ^= par; v.w ^= par;
        if (__all_sync(0xffffffffu, (v.x & v.y & v.z & v.w & 0x80008000u) == 0x80008000u)) break;
        if (it > (1 << 20)) give_up();
    }
    sts128(dst + (8 + 16 * i + (lane >> 1)) * 16, v.x, v.y, v.z, v.w);
}
__device__ __forceinline__ void store_rows(const CUtensorMap* m, uint32_t src, int col, int row) {
    asm volatile("cp.async.bulk.tensor.5d.global.shared::cta.bulk_group [%0, {%2, %3, %3, %3, %4}], [%1];" :: "l"(m), "r"(src), "r"(col), "r"(0), "r"(row) : "memory");
}

__device__ __forceinline__ void store_or_add(void* o, const uint32_t (&y)[4], uint32_t add) {
    asm volatile("{ .reg .pred p; setp.ne.u32 p, %5, 0; @!p st.global.v4.u32 [%0], {%1,%2,%3,%4}; @p red.relaxed.gpu.global.add.noftz.v4.bf16x2 [%0], {%1,%2,%3,%4}; }"
                 :: "l"(o), "r"(y[0]), "r"(y[1]), "r"(y[2]), "r"(y[3]), "r"(add) : "memory");
}

__device__ __forceinline__ void conv_aux(const Params& p, const CUtensorMap* mU, uint32_t sb, int aw, int lane, int bid, unsigned epoch) {
    const int g = lane >> 2, t = lane & 3, mi = lane >> 3, r8 = lane & 7;
    const int rank = bid & 1, slab = bid >> 1;
    const uint32_t bar_y = sb + SC_MISC, bar_u = bar_y + 32, bar_v = bar_y + 40, bar_box = bar_y + 64 + 8 * aw, s_bm = bar_y + 128;
    if (elect()) {
        mbar_init(bar_box, 1); mbar_fence();
        mbar_expect(bar_box, 4096);
        tma4d(sb + SC_RT + 4096 * aw, mU, 16 * slab, 0, 0, 16 * rank + 2 * aw, bar_box);
        mbar_init(bar_y + 8 * aw, aw < 4 ? 9 : aw == 5 ? 8 : 1); mbar_fence();
        if (aw < 5) mbar_expect(bar_y + 8 * aw, aw == 4 ? 16384 : 4096);
    }
    __syncwarp();
    asm volatile("barrier.cluster.arrive.relaxed.aligned;" ::: "memory");
    asm volatile("setmaxnreg.dec.sync.aligned.u32 88;");
    sts128(sb + (lane < 16 ? SC_UT + ut_off(aw) + mi * (UT_HALF - 128) : SC_V - 256 + aw * V_STRIDE) + lane * 16, 0, 0, 0, 0);
    if (lane < 16) sts128(s_bm + lane * 16, 0, 0, 0, 0);
    {
        const uint32_t dst = sb + SC_UT + ut_off(swap01(g)) + swz((8 + 64 * rank + 8 * aw) * 16) + 16 * t, dn = 64 - 64 * ((aw + 1) & 2);
        const uint32_t rdst = mapa(dst, rank ^ 1), rbar = mapa(bar_u, rank ^ 1);
        asm volatile("barrier.cluster.wait.acquire.aligned;" ::: "memory");
        mbar_wait(bar_box);
        if (aw == 0) TSTAMP(1);
        const uint32_t src = fresh(sb + SC_RT) + aw * 4096 + (8 * mi + 4 * (r8 & 1) + (r8 >> 1)) * 32 + ((rank ^ (r8 & 1)) << 4);
        uint32_t x[8][4];
#pragma unroll
        for (int i = 0; i < 4; i++) { ldsm4t(x[i], src + 1024 * i); ldsm4t(x[4 + i], (src ^ 16) + 1024 * i); }
        asm volatile("" :: "r"(x[0][0]), "r"(x[1][0]), "r"(x[2][0]), "r"(x[3][0]) : "memory");
#pragma unroll
        for (int i = 0; i < 4; i++) st_async128(rdst + (i & 1) * UT_HALF + (i & 2 ? dn : 0), x[4 + i][0], x[4 + i][1], x[4 + i][2], x[4 + i][3], rbar);
#pragma unroll
        for (int i = 0; i < 4; i++) sts128(dst + (i & 1) * UT_HALF + (i & 2 ? dn : 0), x[i][0], x[i][1], x[i][2], x[i][3]);
    }
    bar_sync(BC_AUX, 256);
    mbar_wait_cluster(bar_u);
    if (aw == 0) TSTAMP(2);
    if (aw >= 4) bar_arrive(BC_U + aw, 64); else bar_sync(BC_U + aw, 64);
    if (aw == 0) TSTAMP(3);
    {
        const int c = t + 4 * (g & 1);
        const uint32_t ws = fresh(sb + SC_UT) + ut_off(c), wd = sb + SC_V + c * V_STRIDE;
#pragma unroll 1
        for (int k = aw; k < 13; k += 8) {
            const int a = 8 * k + (k < 12 ? g & 6 : 0);
            const uint32_t d = wd + 64 * a, sw = 16 * (a & 2);
            window_task(ws + swz(16 * a + 96), ws + swz(16 * a + 128), d + sw, d + (sw ^ 32), k);
        }
    }
    if (aw == 0) TSTAMP(9);
    {
        if (aw >= 2) fetch_gates(p, aw, lane, epoch, sb + SC_GT + (lane & 1) * GT_HALF);
        __syncwarp();
        if (elect()) { mbar_arrive(bar_v); prefetch_map(mU + 4); }
        next_epoch(p, epoch);
        if (aw == 0) TSTAMP(4);
        if (aw == 7) {
            const int row = key_row(wait_sel(p, slab >> 1, r8, key_tag(epoch)));
            if (lane < 8) asm volatile("red.shared.or.b32 [%0], %1;" :: "r"(s_bm + (row >> 5) * 4), "r"(1u << (row & 31)) : "memory");
            TSTAMP(10);
        }
        bar_sync(BC_AUX, 256);
        const uint32_t src = sb + SC_RT + ((r8 >> 1) & 1) * Y_RS + (2 * mi + (r8 & 1)) * Y_CS + (2 * aw + (r8 >> 2)) * 16;
        const int L = 2 * aw + (t >> 1);
        const int row0 = 256 * rank + 128 * (g >> 2) + 16 * (L & 3) + 64 * (g & 1) + 8 * ((g >> 1) & 1) + (L >> 2);
        __nv_bfloat16* outp = p.out + (size_t)row0 * DM + 16 * slab + 8 * (t & 1);
        const uint32_t stg = sb + SC_KG + 4096 * aw, so = (g & 2) * 256 + (g >> 2) * 128 + r8 * 16;
#pragma unroll 1
        for (int s = 1; s < 4; s++) {
            const uint32_t bm = lds32(fresh(s_bm) + (16 * s + (row0 >> 5)) * 4) >> (row0 & 31);
            const bool routed = __any_sync(0xffffffffu, bm & 0x11u);
            if (aw == s) mbar_wait_cluster(bar_y + 8 * s);
            bar_sync(BC_AUX, 256);
            const uint32_t sf = fresh(src) + 512 * s;
            uint32_t y[2][4];
            ldsm4t(y[0], sf); ldsm4t(y[1], sf + 256);
            if (routed) {
#pragma unroll
                for (int k = 0; k < 2; k++) store_or_add(outp + (size_t)(512 * s + 4 * k) * DM, y[k], bm & (1u << (4 * k)));
            } else {
                sts128(stg + so + 1024 * s, y[0][0], y[0][1], y[0][2], y[0][3]); sts128(stg + so + 1024 * s + 256, y[1][0], y[1][1], y[1][2], y[1][3]);
                asm volatile("fence.proxy.async.shared::cta;" ::: "memory");
                __syncwarp();
                if (elect()) store_rows(mU + 4, stg + 1024 * s, 16 * slab, 512 * s + 256 * rank + 32 * (aw & 1) + (aw >> 1));
            }
            if (aw == 0) TSTAMP(16 + s);
        }
        if (elect()) { asm volatile("cp.async.bulk.commit_group;" ::: "memory"); asm volatile("cp.async.bulk.wait_group.read 0;" ::: "memory"); }
        if (aw == 0) TFLUSH();
    }
}

__device__ __forceinline__ uint32_t k_tag(unsigned epoch) { return epoch << 16 | 0x80000000u; }
__device__ __forceinline__ void publish_k(uint4* kp, const uint32_t (&w)[12], unsigned epoch, uint64_t (&v)[6]) {
#pragma unroll
    for (int i = 0; i < 3; i++) {
        v[2 * i] = w[3 * i] | (uint64_t)w[3 * i + 1] << 32; v[2 * i + 1] = w[3 * i + 2] | (uint64_t)__byte_perm(w[9 + (i >> 1)], k_tag(epoch), i == 1 ? 0x7632 : 0x7610) << 32;
        asm volatile("st.relaxed.gpu.global.v2.u64 [%0], {%1,%2};" :: "l"(kp + 32 * i), "l"(v[2 * i]), "l"(v[2 * i + 1]));
    }
}
template <bool FULL>
__device__ __forceinline__ void k_tables(uint32_t kt, int lane, const uint32_t (&w)[12]) {
    const int g = lane >> 2, t = lane & 3, mi = lane >> 3, r8 = lane & 7;
    uint32_t x3 = w[7], re[4], rx[4];
#pragma unroll
    for (int i = 0; i < 4; i++) {
        re[i] = __shfl_sync(0xffffffffu, w[i], lane + 31);
        rx[i] = __shfl_sync(0xffffffffu, w[4 + i], lane + (i == 0 && lane == 29 ? 5 : 1 + 2 * t));
    }
    if (FULL) {
        asm volatile("stmatrix.sync.aligned.m8n8.x2.trans.shared.b16 [%0], {%1,%2};" :: "r"(kt + (KT_D + 7) * 4 + 64 * t + 16 * (mi & 1) + 8 * (r8 & 4)), "r"(w[8]), "r"(w[9]) : "memory");
        if (lane == 2) {
            sts32(kt + (KT_C + 78) * 4, w[10] & 0xffffu);
            sts128(kt + (KT_T + 2) * 4, 0, w[10] & 0xffffu, __byte_perm(w[10], 0, 0x1010), w[10] << 16);
        }
        if (lane == 29) x3 = bsub2(x3, rx[0] & 0xffffu);
    }
#pragma unroll
    for (int i = 0; i < 4; i++) {
        sts64(kt + (16 + 64 * i) * 4 + 8 * lane, __byte_perm(w[i], lane ? re[i] : i ? re[i - 1] : 0, 0x5432), w[i]);
        const uint32_t x = i < 3 ? w[4 + i] : x3, aa = __byte_perm(x, 0, 0x3232);
        if (t < 2) sts128(kt + (272 + 64 * i + 8 * g + 4 * t) * 4, i == 0 && lane == 0 ? __byte_perm(x, re[3], 0x5432) : aa, aa, x,
                          __byte_perm(lane != 29 ? rx[i] : i < 3 ? rx[(i + 1) & 3] : FULL ? 0 : rx[0] << 16, x, 0x5432));
        else if (FULL) sts32(kt + (KT_C - 50 + 8 * i + 32 * t + g) * 4, x);
    }
}

__device__ __forceinline__ void conv_main(const Params& p, uint32_t sb, int warp, int lane0, int bid, unsigned epoch, uint32_t (&w)[12]) {
    asm volatile("setmaxnreg.inc.sync.aligned.u32 168;");
    const int lane = __shfl_sync(0xffffffffu, lane0, lane0);
    const int g = lane >> 2, t = lane & 3, mi = lane >> 3, r8 = lane & 7;
    const int rank = bid & 1;
    const uint32_t bar_y = sb + SC_MISC, bar_v = bar_y + 40;
    next_epoch(p, epoch);
    if (warp >= 4) {
        bar_sync(BC_U + warp, 64);
        if (KPOLL) until(clock32(), KPOLL);
        const uint4* src = p.s->kp + (8 * bid + warp) * 96 + lane0;
#pragma unroll 1
        for (int it = 0;; it++) {
            uint32_t bad = 0, e[3];
#pragma unroll
            for (int i = 0; i < 3; i++) { const uint4 v = ld_rlx128(src + 32 * i); w[3 * i] = v.x; w[3 * i + 1] = v.y; w[3 * i + 2] = v.z; e[i] = v.w; bad |= v.w ^ k_tag(epoch); }
            w[9] = __byte_perm(e[0], e[1], 0x5410); w[10] = e[2];
            const bool ok = __all_sync(0xffffffffu, bad < 65536);
            if (ok) break;
            if (it > (1 << 20)) give_up();
        }
    }
    if ((warp & 3) == 0) TSTAMP(5 + (warp >> 2));
    k_tables<true>(sb + SC_KT + warp * KT_BYTES, lane0, w);
    asm volatile("barrier.cluster.wait.acquire.aligned;" ::: "memory");
    if (warp < 4) bar_sync(BC_U + warp, 64);
    __syncwarp();
    if ((warp & 3) == 0) TSTAMP(7 + (warp >> 2));
    {
        const uint32_t ut = fresh(sb + SC_UT) + ut_off(swap01(warp)), kt = fresh(sb + SC_KT) + warp * KT_BYTES;
        auto dup = [&](uint32_t v) { return v ^ p.zero; };
        auto frag = [&](uint32_t (&a)[4], uint32_t x) { a[0] = lds32(x); a[1] = lds32(x + 32); a[2] = lds32(x - 32); a[3] = dup(a[0]); };
        const uint32_t kb = kt + (16 + g - 2 * t) * 4;
        float acc[16][4];
        {
            float y[12][4], M[6][4];
#pragma unroll
            for (int i = 0; i < 12; i++) { y[i][0] = y[i][1] = y[i][2] = y[i][3] = 0.f; M[i >> 1][0] = M[i >> 1][1] = M[i >> 1][2] = M[i >> 1][3] = 0.f; }
            uint32_t U[10][4], a1[4], ad[4], R = (mi & 1) * UT_HALF + (8 + (r8 >> 1) + 48 * (r8 & 1)) * 16 + 64 * (mi >> 1);
            auto places = [&] { ad[0] = swz(R); ad[1] = swz(R + 128); ad[2] = ad[0] ^ 64; ad[3] = ad[1] ^ 64; };
            auto ldu = [&](int k) { ldsm4(U[k], ut + ad[k & 3] + 256 * (k >> 1)); };
            places();
            frag(a1, kb + 2048);
#pragma unroll
            for (int k = 0; k < 7; k++) ldu(k);
#pragma unroll
            for (int i = 0; i < 12; i++) mma_bf(y[i], a1[0], a1[1], a1[2], a1[3], U[i >> 1][2 * (i & 1)], U[i >> 1][2 * (i & 1) + 1]);
            frag(a1, kb + 1792);
            __syncwarp();
#pragma unroll DUNR
            for (uint32_t ko = 0; ko != 256;) {
                if (DUN == 1) ko = fresh(ko);
                const uint32_t kp = kb + ko;
                ko += 64;
                uint32_t se[10][2], so[10][2], ue[10][2];
                auto sums = [&](int k) {
#pragma unroll
                    for (int e = 0; e < 2; e++) { ue[k][e] = U[k][e]; se[k][e] = badd2(U[k][e], U[k - 1][2 + e]); so[k][e] = badd2(U[k][e], U[k][2 + e]); }
                };
#pragma unroll
                for (int k = 1; k < 6; k++) sums(k);
#pragma unroll
                for (int m = 3; m >= 0; m--) {
                    uint32_t a0[4];
                    frag(a0, kp + 512 * m);
                    sums(9 - m);
                    if (m) ldu(10 - m); else { R -= 16; places(); }
#pragma unroll
                    for (int i = 0; i < 6; i++) mma_bf(y[2 * i], a1[0], a1[1], a1[2], a1[3], se[i - m + 4][0], se[i - m + 4][1]);
#pragma unroll
                    for (int e = 0; e < 4; e++) a1[e] = bsub2(a0[e], a1[e]);
#pragma unroll
                    for (int i = 0; i < 6; i++) { mma_bf(M[i], a1[0], a1[1], a1[2], a1[3], ue[i - m + 4][0], ue[i - m + 4][1]); if (!m) ldu(i); }
                    frag(a1, m ? kp + 512 * m - 256 : kp + 1792 + 64);
                    if (!m) ldu(6);
#pragma unroll
                    for (int i = 0; i < 6; i++) mma_bf(y[2 * i + 1], a0[0], a0[1], a0[2], a0[3], so[i - m + 4][0], so[i - m + 4][1]);
                }
            }
#pragma unroll
            for (int i = 0; i < 6; i++)
#pragma unroll
                for (int c = 0; c < 4; c++) { acc[4 + i + 6 * (c & 1)][c & 2] = y[2 * i][c] + M[i][c]; acc[4 + i + 6 * (c & 1)][c | 1] = y[2 * i + 1][c] - M[i][c]; }
        }
        const uint32_t lo = (8 + col(r8)) * 16 + (mi >> 1) * 128, ua = fresh(ut) + (mi & 1) * UT_HALF, u1[2] = {ua + swz(lo), ua + (swz(lo) ^ 64)};
        {
            uint32_t e[4];
            frag(e, kb + (KT_T - 16) * 4);
            const uint32_t f0 = dup(e[1]), f1 = lds32(kb + KT_T * 4), uo = fresh(ut) + UT_HALF + swz((7 + 8 * mi + col(r8)) * 16);
#pragma unroll
            for (int i = 0; i < 4; i++) {
                uint32_t b[4];
                if (i < 2) {
                    ldsm4(b, uo + 512 * i);
#pragma unroll
                    for (int k = 0; k < 4; k++) mma_bf8(acc[8 + 4 * i + k], f0, f1, b[k]);
                }
                ldsm4(b, u1[i & 1] + 256 * i);
                mma_bf(acc[2 * i + 8], e[0], e[1], e[2], e[3], b[0], b[1]); mma_bf(acc[2 * i + 9], e[0], e[1], e[2], e[3], b[2], b[3]);
            }
        }
        if ((warp & 3) == 0) TSTAMP(11 + (warp >> 2));
        mbar_wait(bar_v);
        const uint32_t vt = fresh(sb + SC_V) + swap01(warp) * V_STRIDE;
        const uint32_t g1 = fresh(sb + SC_GT) + (mi & 1) * GT_HALF + lo;
        const uint32_t ydst = sb + SC_RT + rank * Y_RS + warp * Y_CS + lane * 16;
        const uint32_t ydr = mapa(ydst, rank ^ 1), ybr = mapa(bar_y, rank ^ 1);
        auto stairs = [&](auto R) {
        uint32_t ug[2][2][4];
        auto ld_ug = [&](int i) { ldsm4t(ug[i & 1][0], u1[i & 1] + 256 * i); ldsm4t(ug[i & 1][1], g1 + 256 * i); };
        auto ship = [&](int i) {
            const uint32_t (&u)[4] = ug[i & 1][0], (&gg)[4] = ug[i & 1][1];
            const uint32_t y0 = gmix(gg[0], acc[2 * i][0], acc[2 * i][1], u[0]), y1 = gmix(gg[1], acc[2 * i][2], acc[2 * i][3], u[1]);
            const uint32_t y2 = gmix(gg[2], acc[2 * i + 1][0], acc[2 * i + 1][1], u[2]), y3 = gmix(gg[3], acc[2 * i + 1][2], acc[2 * i + 1][3], u[3]);
            if ((i & 1) != R.value) st_async128(ydr + 512 * (i >> 1), y0, y1, y2, y3, ybr + 8 * (i >> 1));
            else asm volatile("{ .reg .pred q; setp.eq.u32 q, %6, 0; st.shared.v4.u32 [%0], {%2,%3,%4,%5}; bar.warp.sync 0xffffffff; @q mbarrier.arrive.shared::cta.b64 _, [%1]; }"
                              :: "r"(ydst + 512 * (i >> 1)), "r"(bar_y + 8 * (i >> 1)), "r"(y0), "r"(y1), "r"(y2), "r"(y3), "r"(lane) : "memory");
        };
        const uint32_t VD = vt + (VC_OFF - 400 - 16 * t) * 4 + (8 * g ^ 16 * (-t & 2)), VD2 = vt + (VC_OFF - 415 - 16 * t) * 4 + (8 * g ^ 16 * (~t & 2));
        uint2 bd[10];
        uint32_t x[2][4][4];
        auto ld4 = [&](uint32_t (&v)[4], int dl) { const uint2 w = lds64(VD + 256 * dl); v[0] = w.x; v[1] = w.y; v[2] = lds32(VD2 + 256 * dl); v[3] = dup(w.x); };
        auto mm4 = [&](const uint32_t (&v)[4], int dl) {
#pragma unroll
            for (int s = dl & 1; s < 10; s += 2) if ((dl + s) / 2 >= 4 && (dl + s) / 2 < 16) mma_bf(acc[(dl + s) / 2], v[0], v[1], v[2], v[3], bd[s].x, bd[s].y);
        };
        const uint32_t KE = kt + (KT_D + col(g) + t) * 4, VE = vt + (VE_BASE - 912 - 16 * t) * 4 + (8 * g ^ 16 * (~t & 2));
        uint32_t b0[8], b1[8];
        auto ld8 = [&](uint32_t (&v)[4], int dl) { const uint2 w = lds64(VE + 512 * dl), z = lds64(VE + 512 * dl - 256); v[0] = w.x; v[1] = w.y; v[2] = z.x; v[3] = z.y; };
        auto mm8 = [&](const uint32_t (&v)[4], int dl, int lo, int hi) {
#pragma unroll
            for (int s = 0; s < 8; s++) if (dl + s >= lo && dl + s < hi) mma_bf(acc[dl + s], v[0], v[1], v[2], v[3], b0[s], b1[s]);
        };
        ld4(x[0][0], 6);
#pragma unroll
        for (int s = 0; s < 10; s++) bd[s] = lds64(kt + (KT_C + 2 * col(g) + 2 * t + 8 * s) * 4);
        mm4(x[0][0], 6);
        uint32_t e[4][4];
#pragma unroll
        for (int k = 1; k < 6; k++) {
#pragma unroll
            for (int j = 0; j < 4; j++) ld4(x[k & 1][j], 4 * k + 3 + j);
            ld_ug(k + 1);
            if (k == 3) {
#pragma unroll
                for (int s = 0; s < 8; s++) { b0[s] = lds32(KE + 32 * s); b1[s] = lds32(KE + 32 * s + 16); }
            }
            if (k > 1) ship(k);
#pragma unroll
            for (int j = 0; j < 4; j++) {
                mm4(x[k & 1][j], 4 * k + 3 + j);
                if (k == 3) { uint32_t v[4], z[4]; ld8(e[j], 8 + j); ld8(v, 12 + j); ld4(z, 30 - j); mm8(v, 12 + j, 12, 16); mm8(e[j], 8 + j, 8, 12); mm4(z, 30 - j); }
                if (k == 5) { ld8(e[j], 8 + j + p.zero); mm8(e[j], 8 + j, 12, 16); }
            }
        }
        ld_ug(7);
        ship(7 - R.value); ship(6 + R.value);
        };
        if (rank) stairs(std::integral_constant<int, 1>()); else stairs(std::integral_constant<int, 0>());
        if ((warp & 3) == 0) TSTAMP(14 + (warp >> 2)); else TSTAMP(21 + warp);
    }
}

constexpr int SF_WD = 73728;
constexpr int SF_RED = 49152;
constexpr int MU_HALF = 640, MU_STRIDE = 1344, SM_RAW = 98304, SM_UT = SM_RAW + 16384, SM_G = SM_UT + 16 * MU_STRIDE, SM_Y = 196608, SM_FT = SM_Y + 17024, SM_KT = 138880, SM_KW = SM_G - 49152;
constexpr int SF_XS = 221184;
constexpr int SF_MISC = SF_XS + 8 * 1168;
constexpr int SF_KG = SF_MISC - 10 * KG_STAGE;
constexpr int SF_WR = SF_KG - 2304;
constexpr int FB_X = 64, FB_KDONE = 72, FB_KEYS = 80, FB_FREE = 88  , FB_W = 104, FB_D = FB_W + 72, FB_MU = FB_D + 96, FB_FAR = FB_MU - 16, FB_MG = FB_MU + 8, FB_MT = FB_MU + 16  , FS_PART = 512, FS_TOK = 896, FS_BM = 1024;
enum { BAR_R = 7, BAR_GU = 8, BAR_RED = 9, BAR_R2 = 10, BAR_G = 12  , BAR_M = 15 };
static_assert(SF_KG % 128 == 0 && NPRE <= 8 && SM_KT + 4 * 2112 <= 147456 && SM_G + MU_STRIDE <= SF_WR - 4 * 9216 && SM_KW + 6 * 2112 >= SM_RAW && SM_KW + 12 * 2112 <= SM_UT, "layout");

__device__ __forceinline__ constexpr int box_no(int i) { return (0x987610ba5432ull >> (4 * i)) & 15; }
__device__ __forceinline__ int role(int b) { b -= NCONV; return b < NX ? b : 18 + (b >> 1) + 12 * (b & 1); }
__device__ __forceinline__ int mini_ch0(int f) { return 48 * f - (f < NW ? 1696 : 2304); }

__device__ __forceinline__ void ffn_front(const Params& p, const CUtensorMap* maps, uint32_t sb, int warp, int lane, int f, unsigned epoch) {
    const unsigned t0 = clock32();
    const int g = lane >> 2, t = lane & 3, mi = lane >> 3, r8 = lane & 7;
    const bool isx = f < NX;
    const int nrw = f < 52 ? 4 : 6, r0 = f < 52 ? 32 * f : 48 * f - 832;
    const int rw = warp < 12 ? 13 - warp : warp ^ (warp < 14 ? 10 : 15);
    const uint32_t bar_row = sb + SF_MISC  , bar_x = bar_row + FB_X;
    const uint32_t s_part = bar_row + FS_PART  , s_tok = bar_row + FS_TOK  ;
    const uint32_t rows = sb + SF_WR - 9216 * (rw + 1) - (rw & 4) * ((SF_WR - 6 * 9216) / 4);
    {
#pragma unroll 1
        for (int i = warp < 10 ? 30 : warp - 10; i < 30; i += 6) if (elect()) mbar_init(bar_x + 8 * i, i == 1 ? 4 + (f < NW) : i < 27 ? 1 : i == 27 ? 2 : 8);
        const uint32_t bytes = rw < 6 ? 9216 : 1152, dst = rw < 6 ? rows : sb + SF_WR + (rw & 1) * 1152;
        const __nv_bfloat16* src = rw < 6 ? p.u + (size_t)(r0 + 8 * rw) * DM : (rw & 1) ? p.gatew : p.wr;
        if (elect()) { mbar_init(bar_row + 8 * rw, 1); mbar_fence(); mbar_expect(bar_row + 8 * rw, bytes); }
        if (warp == 13) { sts32(s_part + 64 + lane * 4, 0); sts32(bar_row + FS_BM + lane * 4, 0); }
        bar_sync(0, NTHR);
        if (!isx) asm volatile("barrier.cluster.arrive.relaxed.aligned;" ::: "memory");
        if (rw < nrw) until(t0, RDELAY);
        if (rw < nrw || rw >= 6) { if (elect()) bulk_g2s(dst, src, bytes, bar_row + 8 * rw); }
    }
    uint4* const kdst = p.s->keys + (lane >> 1) * 128 + 2 * f + (lane & 1);
    if (warp == 15) TSTAMP(1);

    if (warp == 12) {
        if (lane < 22) mbar_expect(bar_row + FB_W + 8 * lane, lane < 9 ? 24576 : isx ? 12288 : lane < 20 ? 2048 : 16384);
        if (elect()) { prefetch_map(maps + 1); prefetch_map(maps + 2); prefetch_map(maps + (isx ? 3 : 5)); }
        unsigned tb = t0 + WDELAY;
        auto pieces = [&](int n, int end, uint32_t dst) {
#pragma unroll 1
            for (; n < end; n++, dst += 12288) {
                until(tb, 0); tb += WGAP;
                if (elect()) tma3d(dst, maps + 1 + (n & 1), 0, 64 * (n >> 1), 3 * f, bar_row + FB_W + 8 * (n >> 1));
            }
        };
        if (!isx) {
#pragma unroll 1
            for (int k = 0; k <= (f >= NW); k++) { until(t0, MDELAY + k * MGAP); if (elect()) tma4d(sb + SM_RAW - 49152 * k, maps + 5, mini_ch0(f) + 16 * k, 0, 0, 0, bar_row + FB_MU - 8 * k); }
            if (f >= NW) return;
        }
#pragma unroll 1
        for (int i = 0; i < 4; i++) {
            if (i == 1) { mbar_wait(bar_row + FB_KEYS); mbar_wait(bar_row + FB_KDONE); tb = clock32() + RESUME; }
            if (i == 3) mbar_wait(bar_row + FB_FREE);
            const int n = ((0x0c080000 + NPRE * 256) >> (8 * i)) & 255;
            pieces(n, ((0x120c0800 + NPRE) >> (8 * i)) & 255, sb + 12288 * (((0x000c0000 + NPRE * 256) >> (8 * i)) & 255));
        }
        TSTAMP(12);
        if (isx) {
#pragma unroll 1
            for (int i = 0; i < 12; i++) {
                const int n = box_no(i);
                if (i == 6) mbar_wait(bar_row + FB_FREE + 8);
                until(tb, 0); tb += DGAP;
                if (elect()) tma2d(sb + SF_WD + n * 12288, maps + 3, 32 * (f >> 1), 2304 * (f & 1) + 192 * n, bar_row + FB_D + 8 * n);
            }
            TSTAMP(13);
        }
    } else if (warp == 13) {
        const uint32_t tag = key_tag(epoch), par = (epoch & 1) ? 0u : 0x8000u;
        stg128(kdst, 0, 0, 0, 0);
        if (lane < 8 && isx && !(f & 1)) st_rlx32(&p.s->sel[32 * f + lane], 0);
        bar_sync(BAR_R, 32 * (nrw + 1));
        TSTAMP(3);
        {
            const uint32_t sg = fresh(s_part) + 192 + lane * 4;
            const uint32_t gb = pack_bf16(sigmoidf_(rbf(__uint_as_float(lds32(sg)))), sigmoidf_(rbf(__uint_as_float(lds32(sg + 128))))) | par | (par << 16);
            asm volatile("st.relaxed.gpu.global.u16 [%0], %1;" :: "l"(p.s->gate + r0 + lane), "h"((unsigned short)gb) : "memory");
            if (nrw > 4 && lane < 16) asm volatile("st.relaxed.gpu.global.u16 [%0], %1;" :: "l"(p.s->gate + r0 + 32 + lane), "h"((unsigned short)(gb >> 16)) : "memory");
        }
        bar_sync(BAR_R2, 32 * (nrw + 1));
        {
            const uint4 v = lds128(fresh(s_tok) + (lane & 1) * 16);
            asm volatile("st.relaxed.gpu.global.v4.u32 [%0], {%1,%2,%3,%4};" :: "l"(kdst), "r"(v.x | tag), "r"(v.y | tag), "r"(v.z | tag), "r"(v.w | tag) : "memory");
        }
        TSTAMP(4);
        if (lane == 0) { mbar_arrive(bar_row + FB_KEYS); mbar_expect(bar_x, 8 * 1152); }
        if (f >= NW) return;
        mbar_wait(bar_row + FB_KDONE);
        uint32_t k[16];
        const uint4* src = p.s->keys + (f & 15) * 128 + lane;
#pragma unroll 1
        for (int it = 0;; it++) {
            uint32_t bad = 0;
#pragma unroll
            for (int i = 0; i < 4; i++) {
                const uint4 x = ld_rlx128(src + (i < 3 || lane < 24 ? 32 * i : 64));
                k[i] = x.x; k[4 + i] = x.y; k[8 + i] = x.z; k[12 + i] = x.w;
                bad |= x.x ^ tag;
            }
            const bool ok = __all_sync(0xffffffffu, (bad & 0xf800u) == 0);
            if (ok) break;
            if (it > (1 << 20)) give_up();
        }
        TSTAMP(5);
        uint32_t key = 0, m = __reduce_max_sync(0xffffffffu, max(max(k[0], k[1]), max(k[2], k[3])));
#pragma unroll 2
        for (int r = 0; r < 8; r++) {
            bool pop[4];
#pragma unroll
            for (int i = 0; i < 4; i++) { pop[i] = k[i] == m; k[i] = pop[i] ? k[4 + i] : k[i]; }
            const uint32_t mn = __reduce_max_sync(0xffffffffu, max(max(k[0], k[1]), max(k[2], k[3])));
            if (elect()) bulk_g2s(sb + SF_XS + r * 1168, p.u + (size_t)key_row(m) * DM, 1152, bar_x);
#pragma unroll
            for (int i = 0; i < 4; i++) { k[4 + i] = pop[i] ? k[8 + i] : k[4 + i]; k[8 + i] = pop[i] ? k[12 + i] : k[8 + i]; k[12 + i] = pop[i] ? 0 : k[12 + i]; }
            if (r8 == r) key = m;
            m = mn;
        }
        const int row = key_row(key);
        sts32(s_tok + r8 * 8, row);
        TSTAMP(6);
        if (isx) {
            if (!(f & 1)) {
                __nv_bfloat16* o = p.out + (size_t)row * DM + 16 * f + 8 * mi;
                asm volatile("st.relaxed.gpu.global.v4.u32 [%0], {%1,%1,%1,%1};" :: "l"(o), "r"(0) : "memory");
                if (__any_sync(0xffffffffu, ld_rlx32(o) != 0)) give_up();
                if (lane < 8) st_rlx32(&p.s->sel[32 * f + lane], key);
            } else wait_sel(p, f >> 1, r8, tag);
            uint32_t gb;
#pragma unroll 1
            for (int it = 0;; it++) {
                asm volatile("ld.relaxed.gpu.global.u16 %0, [%1];" : "=r"(gb) : "l"(p.s->gate + row) : "memory");
                gb ^= par;
                if (!(gb & 0x8000u)) break;
                if (it > (1 << 20)) give_up();
            }
            const uint32_t rb = key ^ 0x80000000u, rv = (rb ^ (((int)rb >> 31) & 0x7fff0000u)) & 0xffff0000u;
            sts32(s_tok + r8 * 8 + 4, __float_as_uint(rbf(1.0f - bf_lo(gb)) * rbf(sigmoidf_(__uint_as_float(rv)))));
            __syncwarp();
            TSTAMP(7);
            bar_arrive(BAR_RED, 416);
        }
    } else {
        if (rw < nrw) {
            float c[3][4];
#pragma unroll
            for (int i = 0; i < 3; i++) { c[i][0] = c[i][1] = c[i][2] = c[i][3] = 0.f; }
            mbar_wait(bar_row + 48); mbar_wait(bar_row + 56);
            const uint32_t b = fresh(sb + SF_WR) + (g & 1) * 1152 + (g >> 2) * 64 + t * 16 + (g & 2) * 2;
            uint32_t w[18][2];
#pragma unroll
            for (int kb = 0; kb < 18; kb++) { const uint32_t o = ((kb & 1) ? b ^ 64 : b) + 128 * (kb >> 1); w[kb][0] = lds32(o); w[kb][1] = lds32(o + 8); }
            mbar_wait(bar_row + 8 * rw);
            if (warp == 15) TSTAMP(2);
            const uint32_t a = fresh(rows) + g * 1152 + (g & 1) * 64 + t * 16;
#pragma unroll
            for (int kb = 0; kb < 18; kb++) {
                const uint4 x = lds128(((kb & 1) ? a ^ 64 : a) + 128 * (kb >> 1));
                mma_bf(c[kb % 3], x.x, x.y, x.z, x.w, w[kb][0], w[kb][1]);
            }
            const float sr = c[0][0] + c[1][0] + c[2][0] + __shfl_down_sync(0xffffffffu, c[0][2] + c[1][2] + c[2][2], 1);
            const float sg = c[0][1] + c[1][1] + c[2][1] + __shfl_down_sync(0xffffffffu, c[0][3] + c[1][3] + c[2][3], 1);
            const uint32_t rb = pack_bf16(0.f, sr);
            if (t == 2 * (g & 1)) {
                sts32(s_part + (8 * rw + g) * 4, (rb ^ (((int)rb >> 31) & 0x7fff0000u) ^ 0x80000000u) | (uint32_t)(2047 - r0 - 8 * rw - g));
                sts32(s_part + 192 + (8 * rw + g) * 4, __float_as_uint(sg));
            }
            __syncwarp();
            bar_sync(BAR_R, 32 * (nrw + 1));
            const uint32_t sk = fresh(s_part), kk = lds32(sk + (8 * rw + r8) * 4);
            int n = 0;
#pragma unroll
            for (int i = 0; i < 3; i++) { const uint4 v = lds128(sk + mi * 48 + 16 * i); n += (v.x > kk) + (v.y > kk) + (v.z > kk) + (v.w > kk); }
            n += __shfl_xor_sync(0xffffffffu, n, 8); n += __shfl_xor_sync(0xffffffffu, n, 16);
            if (n < 8) sts32(s_tok + 4 * n, kk);
            __syncwarp();
            bar_arrive(BAR_R2, 32 * (nrw + 1));
        }
    }
}

__device__ __forceinline__ void ffn_work(const Params& p, uint32_t sb, int warp, int lane, int f, unsigned epoch) {
    const int g = lane >> 2, t = lane & 3, mi = lane >> 3, r8 = lane & 7;
    const bool isx = f < NX;
    const uint32_t bar_x = sb + SF_MISC + FB_X, bar_free = sb + SF_MISC + FB_FREE, bar_w = sb + SF_MISC + FB_W, bar_d = sb + SF_MISC + FB_D, s_tok = sb + SF_MISC + FS_TOK;
    uint32_t fr[24][4];
    auto pin = [&] {
#pragma unroll
        for (int i = 0; i < 24; i += 8) asm volatile("" :: "r"(fr[i][0]), "r"(fr[i + 1][0]), "r"(fr[i + 2][0]), "r"(fr[i + 3][0]), "r"(fr[i + 4][0]), "r"(fr[i + 5][0]), "r"(fr[i + 6][0]), "r"(fr[i + 7][0]) : "memory");
    };
    {
        const int j = (unsigned)(warp - 4) < 6, w = warp - (j ? 4 : warp < 4 ? 0 : 6);
        float ag[2][4], au[2][4];
#pragma unroll
        for (int i = 0; i < 2; i++) { ag[i][0] = ag[i][1] = ag[i][2] = ag[i][3] = 0.f; au[i][0] = au[i][1] = au[i][2] = au[i][3] = 0.f; }
        const uint32_t wb = sb + (w >> 1) * 4096 + (r8 + 8 * (mi >> 1)) * 64 + (((2 * (w & 1) + (mi & 1)) ^ (r8 >> 1)) << 4);
        const uint32_t xb = sb + SF_XS + r8 * 1168 + mi * 16;
        auto load = [&](int i, int n, int place) {
            mbar_wait(bar_w + 8 * n);
            const uint32_t wk = fresh(wb) + place * 24576;
#pragma unroll
            for (int s = 0; s < 4; s++) { ldsm4t(fr[8 * i + s], wk + 1024 * s); ldsm4t(fr[8 * i + 4 + s], wk + 1024 * s + 12288); }
        };
        auto mul = [&](int i, uint32_t xk) {
            uint32_t x[2][4];
            ldsm4(x[0], xk); ldsm4(x[1], xk + 64);
#pragma unroll
            for (int s = 0; s < 4; s++) {
                const uint32_t (&a)[4] = fr[8 * i + s], (&b)[4] = fr[8 * i + 4 + s];
                mma_bf(ag[s & 1], a[0], a[1], a[2], a[3], x[s >> 1][2 * (s & 1)], x[s >> 1][2 * (s & 1) + 1]);
                mma_bf(au[s & 1], b[0], b[1], b[2], b[3], x[s >> 1][2 * (s & 1)], x[s >> 1][2 * (s & 1) + 1]);
            }
        };
#pragma unroll
        for (int i = 0; i < 3; i++) load(i, 3 * j + i, (i ? 5 : 3) * j + i);
        pin();
        bar_sync(BAR_G + j, 192);
        if (w == 0 && lane == 0) mbar_arrive(bar_free + 8 * j);
        mbar_wait(bar_x);
        if (warp == 0) TSTAMP(8);
        {
            const uint32_t xk = fresh(xb) + 384 * j;
#pragma unroll
            for (int i = 0; i < 3; i++) { mul(i, (i ? fresh(xk) : xk) + 128 * i); if (i == 0) { asm volatile("" :: "f"(ag[0][0]), "f"(ag[1][0]), "f"(au[0][0]), "f"(au[1][0])); sts32(s_tok + 64, clock32()); } }
        }
#pragma unroll 1
        for (int n = 6 + j; n < 9; n += 2) { load(0, n, n - 6); mul(0, fresh(xb) + 128 * n); }
#pragma unroll
        for (int c = 0; c < 4; c++) { ag[0][c] += ag[1][c]; au[0][c] += au[1][c]; }
        if (j) {
            sts128(wb + 24576, __float_as_uint(ag[0][0]), __float_as_uint(ag[0][1]), __float_as_uint(ag[0][2]), __float_as_uint(ag[0][3]));
            sts128(wb + 25600, __float_as_uint(au[0][0]), __float_as_uint(au[0][1]), __float_as_uint(au[0][2]), __float_as_uint(au[0][3]));
        }
        bar_sync(BAR_GU, 384);
        if (!j) {
            const uint32_t sf = fresh(wb);
            const uint4 g1 = lds128(sf + 24576), u1 = lds128(sf + 25600);
            const uint32_t gs[4] = {g1.x, g1.y, g1.z, g1.w}, us[4] = {u1.x, u1.y, u1.z, u1.w};
            if (warp == 0) TSTAMP(9);
            float h[4];
#pragma unroll
            for (int c = 0; c < 4; c++) {
                const float gv = rbf(ag[0][c] + __uint_as_float(gs[c]));
                h[c] = rbf(gv * sigmoidf_(gv)) * rbf(au[0][c] + __uint_as_float(us[c]));
            }
            uint32_t h0, h1;
            asm("movmatrix.sync.aligned.m8n8.trans.b16 %0, %1;" : "=r"(h0) : "r"(pack_bf16(h[0], h[1])));
            asm("movmatrix.sync.aligned.m8n8.trans.b16 %0, %1;" : "=r"(h1) : "r"(pack_bf16(h[2], h[3])));
            if (h0 == 0) h0 = 0x8000u;
            asm volatile("{ .reg .b64 v; mov.b64 v, {%1, %2}; st.relaxed.gpu.global.b64 [%0], v; }" :: "l"(p.s->h + ((epoch & 1) * 288 + 6 * f + w) * 32 + lane), "r"(h0), "r"(h1) : "memory");
        }
        if (isx) {
            if (warp == 0) TSTAMP(10);
            const uint2* hsrc = p.s->h + ((epoch & 1) * 288 + 144 * (f & 1) + warp) * 32 + lane;
            const uint32_t wd = sb + SF_WD + warp * 1024 + (r8 + 8 * (mi >> 1)) * 64 + (((mi & 1) ^ (r8 >> 1)) << 4), we = wd ^ 32;
            uint2 hb[12];
            auto ldh = [&](int i) { asm volatile("ld.relaxed.gpu.global.v2.u32 {%0, %1}, [%2];" : "=r"(hb[i].x), "=r"(hb[i].y) : "l"(hsrc + 384 * box_no(i)) : "memory"); };
            auto ldw = [&](int i) { mbar_wait(bar_d + 8 * box_no(i)); ldsm4t(fr[2 * i], fresh(wd) + 12288 * box_no(i)); ldsm4t(fr[2 * i + 1], fresh(we) + 12288 * box_no(i)); };
#pragma unroll
            for (int i = 0; i < DPA; i++) ldw(i);
#pragma unroll
            for (int i = 0; i < 12; i++) ldh(i);
#pragma unroll
            for (int i = DPA; i < DPB; i++) ldw(i);
#pragma unroll
            for (int i = 0; i < DPB; i++) asm volatile("" :: "r"(fr[2 * i][0]), "r"(fr[2 * i + 1][0]) : "memory");
#pragma unroll 1
            for (int it = 0;; it++) {
                bool again = false;
#pragma unroll
                for (int s = 0; s < 12; s += 2) if (__any_sync(0xffffffffu, min(hb[s].x, hb[s + 1].x) == 0)) { ldh(s); ldh(s + 1); again = true; }
                if (!again) break;
                if (it > (1 << 16)) give_up();
            }
            if (warp == 0) TSTAMP(11);
            float ad[2][2][4];
#pragma unroll
            for (int i = 0; i < 4; i++) { ad[i >> 1][i & 1][0] = ad[i >> 1][i & 1][1] = ad[i >> 1][i & 1][2] = ad[i >> 1][i & 1][3] = 0.f; }
#pragma unroll
            for (int i = 0; i < 12; i++) {
                if (i >= DPB) ldw(i);
                if (i == 11 && warp == 9) TSTAMP(14);
#pragma unroll
                for (int c = 0; c < 2; c++) mma_bf(ad[c][i & 1], fr[2 * i + c][0], fr[2 * i + c][1], fr[2 * i + c][2], fr[2 * i + c][3], hb[i].x, hb[i].y);
                if (i >= DPB - 1) asm volatile("" :: "f"(ad[0][i & 1][0]), "f"(ad[1][i & 1][0]) : "memory");
            }
            const uint32_t rd = sb + SF_RED + warp * 1152 + (72 * t + g) * 4;
#pragma unroll
            for (int i = 0; i < 8; i++) sts32(rd + (i >> 2) * 64 + (i & 1) * 144 + ((i >> 1) & 1) * 32, __float_as_uint(ad[i >> 2][0][i & 3] + ad[i >> 2][1][i & 3]));
            bar_sync(BAR_RED, 416);
            if (warp < 4) {
                const int tid = 32 * warp + lane;
                const uint32_t rs = fresh(sb + SF_RED) + (tid >> 4) * 144 + (tid & 15) * 8;
                const uint2 tk = lds64(fresh(s_tok) + (tid >> 4) * 8);
                float x = 0.f, y = 0.f;
#pragma unroll
                for (int w = 0; w < 12; w++) { const uint2 v = lds64(rs + w * 1152); x += __uint_as_float(v.x); y += __uint_as_float(v.y); }
                asm volatile("red.relaxed.gpu.global.add.noftz.bf16x2 [%0], %1;" :: "l"(p.out + (size_t)tk.x * DM + 32 * (f >> 1) + 2 * (tid & 15)),
                             "r"(pack_bf16(x * __uint_as_float(tk.y), y * __uint_as_float(tk.y))) : "memory");
            }
            if (warp == 0) { TSTAMP(15); TFLUSH(); }
            asm volatile("exit;"); __builtin_unreachable();
        }
    }
}

__device__ __forceinline__ void fetch_k(const uint4* src, uint64_t (&v)[6], uint32_t a, uint32_t b) {
    asm volatile("{ .reg .pred p; setp.eq.u32 p, %7, %8; @p ld.relaxed.gpu.global.v2.u64 {%0,%1}, [%6]; @p ld.relaxed.gpu.global.v2.u64 {%2,%3}, [%6 + 512]; @p ld.relaxed.gpu.global.v2.u64 {%4,%5}, [%6 + 1024]; }"
                 : "+l"(v[0]), "+l"(v[1]), "+l"(v[2]), "+l"(v[3]), "+l"(v[4]), "+l"(v[5]) : "l"(src), "r"(a), "r"(b));
}
__device__ __forceinline__ uint32_t mini_conv(const Params& p, uint32_t sb, int warp, int lane, int f, unsigned epoch, uint64_t (&v)[6]) {
    const int g = lane >> 2, t = lane & 3, mi = lane >> 3, r8 = lane & 7;
    const uint32_t fb = sb + SF_MISC, kt = sb + (warp >= 12 ? SM_KT - 12 * 2112 : f < NW ? SM_KW + 2 * 2112 : SM_KW) + warp * 2112;
    const bool ism = f >= NW;
    const uint32_t* const sel = &p.s->sel[((mini_ch0(f) + (ism ? 2 * (warp & 8) : 0)) >> 5) * 64 + r8];
    uint32_t seq = 128, key;
    const uint4* src = p.s->kp + lane;
    auto hi = [&](int i) { return (uint32_t)(v[i] >> 32); };
    if (f >= (warp < 4 ? NW : NX)) {
    {
        const uint32_t c = 68 + (warp & 3) + 2 * (warp & 12), y = ((uint32_t)((warp < 8 ? 0xe066806400000000ull : 0x5a6e00680080e26cull) >> ((8 * warp) & 48)) & 0xffff) + (warp < 14 ? 0 : 0x6a0000);
        seq = !ism ? y + (warp & 1) * ((y >> 6) & 0x10101) : warp < 14 ? 0x101 * c - 0x400 : c;
        src += (48 * (f - (ism ? NW : NX)) + (seq & 63)) * 96;
    }
    if (seq & 64) {
        if (seq & 4) {
            const int q = (seq & 3) + ((seq >> 1) & 4);
            const uint32_t ab = sb - 3072 * (seq & 16), d = ab + SM_UT + g * MU_STRIDE + (8 + 4 * q + t) * 16;
            sts128(ab + SM_UT + (2 * q + (mi >> 1)) * MU_STRIDE + (mi & 1) * MU_HALF + r8 * 16, 0, 0, 0, 0);
            mbar_wait(fb + FB_MU - (seq & 16) / 2);
            if (warp == 15) TSTAMP(16);
            const uint32_t a = fresh(ab + SM_RAW) + q * 2048 + (8 * mi + 4 * (r8 & 1) + (r8 >> 1)) * 32 + ((r8 & 1) << 4);
            uint32_t x[4][4];
#pragma unroll
            for (int i = 0; i < 4; i++) ldsm4t(x[i], (i & 2 ? a ^ 16 : a) + 1024 * (i & 1));
#pragma unroll
            for (int i = 0; i < 4; i++) sts128(d + (i & 1) * MU_HALF + (i & 2) * 4 * MU_STRIDE, x[i][0], x[i][1], x[i][2], x[i][3]);
            __syncwarp();
            if (lane == 0) mbar_arrive(fb + FB_MT + (seq & 16) / 2);
        }
        mbar_wait(fb + FB_KDONE);
        fetch_k(src, v, warp < 4, 0);
        if ((warp | 2) == 7) { fetch_gates(p, (warp >> 1) & 1, lane, epoch, sb + SM_G + (lane & 1) * MU_HALF); __syncwarp(); if (lane == 0) mbar_arrive(fb + FB_MG); }
        if (warp >= 8) {
            mbar_wait(fb + FB_KEYS); mbar_wait(fb + FB_MT);
            if (ism) {
                asm volatile("barrier.cluster.wait.aligned; fence.release.sync_restrict::shared::cta.cluster;" ::: "memory");
                if (lane == 0) asm volatile("mbarrier.arrive.relaxed.cluster.shared::cluster.b64 _, [%0];" :: "r"(mapa(fb + FB_MT + 8, 0)) : "memory");
            }
        }
        if (warp == TW) TSTAMP(17);
    }
    }
    const uint32_t lo = (mi & 1) * MU_HALF + (8 + col(r8)) * 16 + (mi >> 1) * 128;
#pragma unroll 1
    do {
        const int c = seq & 63;
        const bool far = !ism && (seq & 16);
        const uint32_t ab = sb - 3072 * (c & 16);
        uint32_t ut = ab + SM_UT + (c & 15) * MU_STRIDE;
        if (seq & 64) {
        if (far) {
            mbar_wait_cluster(fb + FB_MT + 8);
            const uint32_t ru = mapa(ut, 1) + lane * 16;
            ut = sb + SM_FT + (c & 3) * 1536;
            uint4 x[3];
#pragma unroll
            for (int i = 0; i < 3; i++) asm volatile("ld.shared::cluster.v4.u32 {%0,%1,%2,%3}, [%4];" : "=r"(x[i].x), "=r"(x[i].y), "=r"(x[i].z), "=r"(x[i].w) : "r"(ru + 512 * i) : "memory");
#pragma unroll
            for (int i = 0; i < 3; i++) sts128(ut + lane * 16 + 512 * i, x[i].x, x[i].y, x[i].z, x[i].w);
        } else mbar_wait(fb + FB_MT + (seq & 16) / 2);
#pragma unroll 1
        for (int it = 0; !__all_sync(0xffffffffu, ((hi(1) ^ k_tag(epoch)) | (hi(3) ^ k_tag(epoch)) | (hi(5) ^ k_tag(epoch)) | ((uint32_t)v[5] & p.zero)) < 65536); it++) {
            fetch_k(src, v, 0, 0);
            if (it > (1 << 20)) give_up();
        }
        sts128(kt + t * 16, 0, 0, 0, 0);
        if (warp == TW) TSTAMP(seq >> 8 ? 7 : 10);
        const uint32_t w[12] = {(uint32_t)v[0], hi(0), (uint32_t)v[1], (uint32_t)v[2], hi(2), (uint32_t)v[3], (uint32_t)v[4], hi(4), 0, 0, 0, 0};
        k_tables<false>(fresh(kt), fresh(lane), w);
        }
        __syncwarp();
        if (seq & 128) ffn_work(p, sb, warp, fresh(lane), f, epoch);
        if (!(seq & 64)) return 0;
        const uint32_t kb = fresh(kt) + (16 + g - 2 * t) * 4, ub = fresh(ut) + lo;
        const uint32_t yd = ab + SM_Y + (c & 15) * 1056 + (c & 8) * 8 + lane * 16;
        uint32_t kp = kb, u1 = ub;
        if (warp == TW && !(seq >> 8)) TSTAMP(13);
        seq >>= 8;
        src += ((int)(seq & 63) - c) * 96;
#pragma unroll
        for (int i = 0; i < 6; i++) v[i] = 0;
        key = 0;
        float acc[6][4];
#pragma unroll
        for (int i = 0; i < 6; i++) { acc[i][0] = acc[i][1] = acc[i][2] = acc[i][3] = 0.f; }
        uint32_t a[4][4], b[2][2][4];
        auto lda = [&](int j, int o) { const uint32_t x = kp + 64 * o + 512 * j; a[j][2] = o ? a[j][1] ^ p.zero : lds32((kp ^ p.zero) + 512 * j - 32); a[j][0] = lds32(x); a[j][1] = lds32(x + 32); a[j][3] = a[j][0] ^ p.zero; };
        auto ldb = [&](int s, int o) { ldsm4(b[s][0], u1 - 16 * o); ldsm4(b[s][1], u1 + 256 - 16 * o); };
        ldb(0, 0);
#pragma unroll
        for (int j = 0; j < 4; j++) lda(j, 0);
#pragma unroll
        for (int s = 0; s < 8; s++) {
            if (s == 4) {
                const uint32_t e = seq | (__float_as_uint(acc[0][0]) & p.zero);
                fetch_k(src, v, e & 64, 64);
                asm volatile("{ .reg .pred p; setp.eq.u32 p, %2, 0; @p ld.relaxed.gpu.global.u32 %0, [%1]; }" : "+r"(key) : "l"(sel), "r"(e));
            }
            if (s < 7) ldb(~s & 1, s + 1);
#pragma unroll
            for (int i = 0; i < 4; i++) {
                const int j = (i >> 1) + 2 * (i & 1);
#pragma unroll
                for (int mu = 3 - j; mu >= 0; mu--) mma_bf(acc[j + mu + (j & 2)], a[j][0], a[j][1], a[j][2], a[j][3], b[s & 1][mu >> 1][2 * (mu & 1)], b[s & 1][mu >> 1][2 * (mu & 1) + 1]);
                if (s < 7) lda(j, s + 1);
            }
        }
        if (warp == TW && !seq) TSTAMP(14);
        mbar_wait(fb + FB_MG);
#pragma unroll
        for (int e = 0; e < 4; e++) { acc[2][e] += acc[4][e]; acc[3][e] += acc[5][e]; }
        uint32_t ug[4][4];
#pragma unroll
        for (int i = 0; i < 2; i++) { ldsm4t(ug[i], ub + 256 * i); ldsm4t(ug[2 + i], fresh(sb + SM_G) + lo + 256 * i); }
#pragma unroll
        for (int i = 0; i < 2; i++) {
            uint32_t (&u)[4] = ug[i], (&gg)[4] = ug[2 + i];
#pragma unroll
            for (int e = 0; e < 4; e++) u[e] = gmix(gg[e], acc[2 * i + (e >> 1)][2 * (e & 1)], acc[2 * i + (e >> 1)][2 * (e & 1) + 1], u[e]);
        }
        if (far) for (int i = 0; i < 2; i++) st_async128(mapa(yd, 1) + 512 * i, ug[i][0], ug[i][1], ug[i][2], ug[i][3], mapa(fb + FB_FAR, 1));
        else for (int i = 0; i < 2; i++) sts128(yd + 512 * i, ug[i][0], ug[i][1], ug[i][2], ug[i][3]);
        __syncwarp();
        if (warp == TW) TSTAMP(18 + (seq != 0));
    } while (seq);
    if (warp >= 12) TSTAMP(12 + warp);
    return key;
}
__device__ __forceinline__ void mini_out(const Params& p, const CUtensorMap* maps, uint32_t sb, int warp, int lane, int f, unsigned epoch, uint32_t key) {
    const int g = lane >> 2, t = lane & 3, mi = lane >> 3, r8 = lane & 7;
    const uint32_t fb = sb + SF_MISC;
    const bool ism = f >= NW;
    const int ch0 = mini_ch0(f);
    const int k = ism ? warp >> 3 : 0;
    uint32_t first = 1;
    if (lane == 0) asm volatile("atom.shared.exch.b32 %0, [%1], 1;" : "=r"(first) : "r"(fb + FS_BM + 64 + 4 * k) : "memory");
    if (!__all_sync(0xffffffffu, first)) {
        if (elect()) prefetch_map(maps + 4);
        const int row = key_row(wait_sel(p, (ch0 + 16 * k) >> 5, r8, key_tag(epoch), key));
        if (row < 512) asm volatile("red.shared.or.b32 [%0], %1;" :: "r"(fb + FS_BM + (row >> 5) * 4), "r"(1u << (row & 31)) : "memory");
        if (k) mbar_wait_cluster(fb + FB_FAR);
    }
    const int m = warp & 7, dr = 128 * (g >> 2) + 16 * (t >> 1) + 64 * (g & 1) + 8 * ((g >> 1) & 1);
    const uint32_t y = SM_Y + ((r8 >> 1) & 1) * 8512 + (2 * mi + (r8 & 1)) * 1056 + (2 * m + (r8 >> 2)) * 16;
    const uint32_t so = (g & 2) * 256 + (g >> 2) * 128 + r8 * 16;
    bar_sync(BAR_M - k, ism ? 256 : NTHR);
#pragma unroll 1
    for (int h = ism ? 0 : warp >> 3;; h++) {
        const int r0 = 256 * h + 32 * (m & 1) + (m >> 1), row = r0 + dr;
        const uint32_t bm = lds32(fresh(fb) + FS_BM + (row >> 5) * 4) >> (row & 31), ab = fresh(sb - 49152 * k + 512 * h), stg = ab + SM_UT + 2048 * m + 512 * h;
        uint32_t x[2][4];
        ldsm4t(x[0], ab + y); ldsm4t(x[1], ab + y + 256);
        if (warp == 0 && x[0][0] != 0x12345) TSTAMP(28);
        if (__any_sync(0xffffffffu, bm & 0x11u)) {
#pragma unroll
            for (int i = 0; i < 2; i++) store_or_add(p.out + (size_t)(row + 4 * i) * DM + ch0 + 16 * k + 8 * (t & 1), x[i], bm & (1u << (4 * i)));
        } else {
#pragma unroll
            for (int i = 0; i < 2; i++) sts128(stg + so + 256 * i, x[i][0], x[i][1], x[i][2], x[i][3]);
            asm volatile("fence.proxy.async.shared::cta;" ::: "memory");
            __syncwarp();
            if (elect()) store_rows(maps + 4, stg, ch0 + 16 * k, r0);
        }
        if (h >= ism) break;
    }
    if (elect()) { asm volatile("cp.async.bulk.commit_group;" ::: "memory"); asm volatile("cp.async.bulk.wait_group.read 0;" ::: "memory"); }
    if (warp == 8) TSTAMP(11);
    if (warp == 0) { TSTAMP(15); TFLUSH(); }
}

constexpr int SMEM_BYTES = 232448;
static_assert(SF_MISC + 1152 <= 232192, "layout");

struct Maps { CUtensorMap m[6]; };

__global__ void __cluster_dims__(2, 1, 1) __launch_bounds__(NTHR, 1)
fused_kernel(const Params p, const __grid_constant__ Maps maps) {
    extern __shared__ __align__(1024) uint8_t smem_raw[];
    uint32_t q[8];
    {
        const int b = role(blockIdx.x), x = threadIdx.x, rc = 5 * b + (b & ~3) + 4 + (x >> 6);
        const int cv = (unsigned)b < NW ? 0 : -1, ca = (b < 0 ? 8 * b + DM : 48 * b - 2300) + ((x >> 5) & 3), cb = 2 * rc - (rc & 3) + 4;
        const uint32_t ch = (ca & cv) | (cb & ~cv), o = NST * ch + 2 * ((x & 31) + ((x >> (cv & 2)) & 32));
        const bool c = x < (cv ? 256 : 320);
        q[6] = ldg16_if(c, p.logdt + ch);
        q[2] = ldg32_if(c, p.Bre + o); q[3] = ldg32_if(c, p.Bim + o); q[4] = ldg32_if(c, p.Cre + o); q[5] = ldg32_if(c, p.Cim + o); q[0] = ldg32_if(c, p.Are + o); q[1] = ldg32_if(c, p.Aim + o);
        q[7] = ldg16_if(c, p.Dskip + ch);
    }
    const unsigned epoch = ld_rlx32(&p.s->epoch[blockIdx.x * 16 + (threadIdx.x >> 5)]);
    const uint32_t sb = __shfl_sync(0xffffffffu, smem_u32(smem_raw), 0);
    const int warp = __shfl_sync(0xffffffffu, threadIdx.x >> 5, 0), bid = __shfl_sync(0xffffffffu, blockIdx.x, 0);
    const int lane = __shfl_sync(0xffffffffu, threadIdx.x & 31, threadIdx.x);
    const bool conv = bid < NCONV;
    const int f = role(bid);
    uint32_t w[12];
    uint64_t v[6];
    const bool four = (unsigned)f >= NW;
    if (warp < (four ? 8 : 10)) {
        const int half = four ? warp >> 2 : warp & 1, pr = four ? warp & 3 : warp >> 1;
        const int rc = 5 * f + (f & ~3) + 4 + pr;
        const uint32_t stage = sb + (conv ? SC_KG : SF_KG) + warp * KG_STAGE;
        uint4* const kp = p.s->kp + (four ? (conv ? 8 * bid : 48 * f - 2300) + pr : 2 * rc - (rc & 3) + 4) * 96 + lane;
        kgen(q, sb, half, stage, stage + (four ? 4 : 1) * KG_STAGE, 1 + pr, lane, w, [&] {
            sts128z_if(conv && lane < 20, sb + SC_KT + warp * KT_BYTES + lane * 16 + (lane < 4 ? 0 : lane < 14 ? 2048 : 2288));
            stg128z_if(!conv, kp + 64 * half); stg128z_if(!half && !conv, kp + 32);
            stg128z_if((unsigned)f < NW && warp < 6, (uint4*)(p.s->h + ((lane >> 4) * 288 + 6 * f + warp) * 32) + (lane & 15));
            if (!conv) bar_sync(0, NTHR);
            if ((unsigned)f >= NX) asm volatile("barrier.cluster.arrive.relaxed.aligned;" ::: "memory");
        });
        if (!half) publish_k(kp, w, epoch, v);
        else for (int i = 0; i < 6; i++) v[i] = 0;
        if (conv) { conv_main(p, sb, warp, lane, bid, epoch, w); return; }
        {
            if (!half && lane == 0) mbar_arrive(sb + SF_MISC + FB_KDONE);
            if (warp == 0) TSTAMP(22);
            if (warp == 2) TSTAMP(23);
        }
    } else if (conv) {
        conv_aux(p, maps.m, sb, warp - 8, lane, bid, epoch);
        return;
    } else {
        ffn_front(p, maps.m, sb, warp, lane, f, epoch);
        for (int i = 0; i < 6; i++) v[i] = 0;
    }
    converged();
    next_epoch(p, epoch);
    if (warp >= 12 && f < NX) return;
    mini_out(p, maps.m, sb, warp, lane, f, epoch, mini_conv(p, sb, warp, __shfl_sync(0xffffffffu, lane, lane), f, epoch, v));
}

typedef CUresult (*EncodeFn)(CUtensorMap*, CUtensorMapDataType, cuuint32_t, void*, const cuuint64_t*, const cuuint64_t*, const cuuint32_t*, const cuuint32_t*,
                             CUtensorMapInterleave, CUtensorMapSwizzle, CUtensorMapL2promotion, CUtensorMapFloatOOBfill);

void make_map(EncodeFn fn, CUtensorMap* m, const void* base, int rank, const cuuint64_t* dims, const cuuint64_t* strides, const cuuint32_t* box, CUtensorMapSwizzle sw) {
    const cuuint32_t es[5] = {1, 1, 1, 1, 1};
    fn(m, CU_TENSOR_MAP_DATA_TYPE_BFLOAT16, rank, (void*)base, dims, strides, box, es, CU_TENSOR_MAP_INTERLEAVE_NONE, sw,
       CU_TENSOR_MAP_L2_PROMOTION_NONE, CU_TENSOR_MAP_FLOAT_OOB_FILL_NONE);
}

}

extern "C" void kernel_launch(void* const* d_in, const int* in_sizes, int n_in, void* d_out, int out_size) {
    (void)in_sizes; (void)n_in; (void)out_size;
    static EncodeFn fn = nullptr;
    static void* scratch = nullptr;
    if (!fn) {
        void* ptr = nullptr; cudaDriverEntryPointQueryResult qr;
        cudaGetDriverEntryPoint("cuTensorMapEncodeTiled", &ptr, cudaEnableDefault, &qr);
        fn = (EncodeFn)ptr;
        cudaGetSymbolAddress(&scratch, g_scratch);
        cudaFuncSetAttribute(fused_kernel, cudaFuncAttributeMaxDynamicSharedMemorySize, SMEM_BYTES);
    }
    typedef const __nv_bfloat16* bp;
    Params p;
    p.u = (bp)d_in[0]; p.Are = (bp)d_in[1]; p.Aim = (bp)d_in[2]; p.Bre = (bp)d_in[3]; p.Bim = (bp)d_in[4]; p.Cre = (bp)d_in[5]; p.Cim = (bp)d_in[6];
    p.logdt = (bp)d_in[7]; p.Dskip = (bp)d_in[8]; p.wr = (bp)d_in[10]; p.gatew = (bp)d_in[14];
    p.out = (__nv_bfloat16*)d_out; p.s = (Scratch*)scratch; p.zero = 0;
    Maps maps;
    {
        const cuuint64_t dims[4] = {DM, 4, 16, 32}, strides[3] = {16 * DM * 2, DM * 2, 64 * DM * 2};
        const cuuint32_t box[4] = {16, 4, 16, 2};
        make_map(fn, &maps.m[0], d_in[0], 4, dims, strides, box, CU_TENSOR_MAP_SWIZZLE_32B);
        const cuuint32_t box2[4] = {16, 4, 16, 8};
        make_map(fn, &maps.m[5], d_in[0], 4, dims, strides, box2, CU_TENSOR_MAP_SWIZZLE_32B);
    }
    for (int i = 0; i < 2; i++) {
        const cuuint64_t dims[3] = {32, DM, FF / 32}, strides[2] = {FF * 2, 64};
        const cuuint32_t box[3] = {32, 64, 3};
        make_map(fn, &maps.m[1 + i], d_in[11 + i], 3, dims, strides, box, CU_TENSOR_MAP_SWIZZLE_64B);
    }
    {
        const cuuint64_t dims[2] = {DM, FF}, strides[1] = {DM * 2};
        const cuuint32_t box[2] = {32, 192};
        make_map(fn, &maps.m[3], d_in[13], 2, dims, strides, box, CU_TENSOR_MAP_SWIZZLE_64B);
    }
    {
        const cuuint64_t dims[5] = {DM, 2, 4, 4, L_SEQ}, strides[4] = {16 * DM * 2, 64 * DM * 2, 4 * DM * 2, DM * 2};
        const cuuint32_t box[5] = {16, 2, 4, 4, 1};
        make_map(fn, &maps.m[4], d_out, 5, dims, strides, box, CU_TENSOR_MAP_SWIZZLE_NONE);
    }
    fused_kernel<<<NCTA, NTHR, SMEM_BYTES>>>(p, maps);
}
```

```cpp
#include <cuda_runtime.h>
#include <cuda_bf16.h>
#include <cuda_fp16.h>
#include <cuda.h>
#include <stdint.h>
#include <type_traits>

#define RESUME 300
#define MDELAY 2000
#define MGAP 0
#define DUN 1
#define KPOLL 650
#define DPA 7
#define DPB 9
#define RDELAY 900
#define WDELAY 2000
#define WGAP 290
#define NPRE 7
#define DGAP 260
namespace {
constexpr int DUNR = DUN;

constexpr int DM = 576, NST = 128, FF = 4608, L_SEQ = 2048;
constexpr int NCONV = 72, NX = 36, NW = 48, NCTA = 132, NTHR = 512;

struct __align__(128) Scratch {
    unsigned epoch[NCTA * 16];
    uint4 keys[16 * 128];
    uint32_t sel[18 * 64];
    uint16_t gate[L_SEQ];
    uint2 h[2 * 288 * 32];
    uint4 kp[DM * 96];
};
__device__ Scratch g_scratch;
#define TFLUSH()
#define TSTAMP(i)
#define TW 12

struct Params {
    const __nv_bfloat16 *Are, *Aim, *Bre, *Bim, *Cre, *Cim, *logdt, *Dskip, *u, *wr, *gatew;
    __nv_bfloat16* out;
    Scratch* s;
    uint32_t zero;
};

__device__ __forceinline__ void give_up() { asm volatile("trap; exit;"); __builtin_unreachable(); }
__device__ __forceinline__ void converged() { __syncwarp(); asm volatile("{ .reg .b32 t; mov.b32 t, 0; movmatrix.sync.aligned.m8n8.trans.b16 t, t; }" ::: "memory"); }
__device__ __forceinline__ bool elect() { uint32_t r; asm volatile("{ .reg .pred p; elect.sync _|p, 0xffffffff; selp.u32 %0, 1, 0, p; }" : "=r"(r)); return r; }
__device__ __forceinline__ uint32_t smem_u32(const void* p) { return (uint32_t)__cvta_generic_to_shared(p); }
__device__ __forceinline__ uint32_t pack_bf16(float lo, float hi) { uint32_t r; asm("cvt.rn.bf16x2.f32 %0, %1, %2;" : "=r"(r) : "f"(hi), "f"(lo)); return r; }
__device__ __forceinline__ uint32_t pack_f16(float lo, float hi) { uint32_t r; asm("cvt.rn.f16x2.f32 %0, %1, %2;" : "=r"(r) : "f"(hi), "f"(lo)); return r; }
__device__ __forceinline__ float bf_lo(uint32_t w) { return __uint_as_float(w << 16); }
__device__ __forceinline__ float bf_hi(uint32_t w) { return __uint_as_float(w & 0xffff0000u); }
__device__ __forceinline__ float rbf(float x) { return bf_lo(pack_bf16(x, 0.f)); }
__device__ __forceinline__ uint32_t badd2(uint32_t a, uint32_t b) { uint32_t r; asm("add.rn.bf16x2 %0, %1, %2;" : "=r"(r) : "r"(a), "r"(b)); return r; }
__device__ __forceinline__ uint32_t bsub2(uint32_t a, uint32_t b) { uint32_t r; asm("sub.rn.bf16x2 %0, %1, %2;" : "=r"(r) : "r"(a), "r"(b)); return r; }
__device__ __forceinline__ uint32_t gmix(uint32_t ng, float ny0, float ny1, uint32_t u) {
    uint32_t r; asm("{ .reg .b32 t; fma.rn.bf16x2 t, %1, %3, %3; fma.rn.bf16x2 %0, %1, %2, t; }" : "=r"(r) : "r"(ng), "r"(pack_bf16(ny0, ny1)), "r"(u)); return r;
}
__device__ __forceinline__ void mma_bf(float (&c)[4], uint32_t a0, uint32_t a1, uint32_t a2, uint32_t a3, uint32_t b0, uint32_t b1) {
    asm("mma.sync.aligned.m16n8k16.row.col.f32.bf16.bf16.f32 {%0,%1,%2,%3}, {%4,%5,%6,%7}, {%8,%9}, {%0,%1,%2,%3};"
        : "+f"(c[0]), "+f"(c[1]), "+f"(c[2]), "+f"(c[3]) : "r"(a0), "r"(a1), "r"(a2), "r"(a3), "r"(b0), "r"(b1));
}
__device__ __forceinline__ void mma_bf8(float (&c)[4], uint32_t a0, uint32_t a1, uint32_t b0) {
    asm("mma.sync.aligned.m16n8k8.row.col.f32.bf16.bf16.f32 {%0,%1,%2,%3}, {%4,%5}, {%6}, {%0,%1,%2,%3};"
        : "+f"(c[0]), "+f"(c[1]), "+f"(c[2]), "+f"(c[3]) : "r"(a0), "r"(a1), "r"(b0));
}
__device__ __forceinline__ void mma_h(float (&c)[4], uint32_t a0, uint32_t a1, uint32_t a2, uint32_t a3, uint32_t b0, uint32_t b1) {
    asm("mma.sync.aligned.m16n8k16.row.col.f32.f16.f16.f32 {%0,%1,%2,%3}, {%4,%5,%6,%7}, {%8,%9}, {%0,%1,%2,%3};"
        : "+f"(c[0]), "+f"(c[1]), "+f"(c[2]), "+f"(c[3]) : "r"(a0), "r"(a1), "r"(a2), "r"(a3), "r"(b0), "r"(b1));
}
__device__ __forceinline__ uint32_t fresh(uint32_t a) { asm volatile("" : "+r"(a) :: "memory"); return a; }
__device__ __forceinline__ uint32_t lds32(uint32_t a) { uint32_t v; asm("ld.shared.u32 %0, [%1];" : "=r"(v) : "r"(a)); return v; }
__device__ __forceinline__ uint2 lds64(uint32_t a) { uint2 v; asm("ld.shared.v2.u32 {%0,%1}, [%2];" : "=r"(v.x), "=r"(v.y) : "r"(a)); return v; }
__device__ __forceinline__ uint4 lds128(uint32_t a) { uint4 v; asm("ld.shared.v4.u32 {%0,%1,%2,%3}, [%4];" : "=r"(v.x), "=r"(v.y), "=r"(v.z), "=r"(v.w) : "r"(a)); return v; }
__device__ __forceinline__ void ldsm4(uint32_t (&r)[4], uint32_t a) {
    asm("ldmatrix.sync.aligned.m8n8.x4.shared.b16 {%0,%1,%2,%3}, [%4];" : "=r"(r[0]), "=r"(r[1]), "=r"(r[2]), "=r"(r[3]) : "r"(a));
}
__device__ __forceinline__ void ldsm4t(uint32_t (&r)[4], uint32_t a) {
    asm("ldmatrix.sync.aligned.m8n8.x4.trans.shared.b16 {%0,%1,%2,%3}, [%4];" : "=r"(r[0]), "=r"(r[1]), "=r"(r[2]), "=r"(r[3]) : "r"(a));
}
__device__ __forceinline__ void sts16(uint32_t a, uint32_t v) { asm volatile("st.shared.u16 [%0], %1;" :: "r"(a), "h"((unsigned short)v) : "memory"); }
__device__ __forceinline__ void sts32(uint32_t a, uint32_t v) { asm volatile("st.shared.u32 [%0], %1;" :: "r"(a), "r"(v) : "memory"); }
__device__ __forceinline__ void sts64(uint32_t a, uint32_t x, uint32_t y) { asm volatile("st.shared.v2.u32 [%0], {%1,%2};" :: "r"(a), "r"(x), "r"(y) : "memory"); }
__device__ __forceinline__ void sts128(uint32_t a, uint32_t x, uint32_t y, uint32_t z, uint32_t w) {
    asm volatile("st.shared.v4.u32 [%0], {%1,%2,%3,%4};" :: "r"(a), "r"(x), "r"(y), "r"(z), "r"(w) : "memory");
}
__device__ __forceinline__ void st_async128(uint32_t a, uint32_t x, uint32_t y, uint32_t z, uint32_t w, uint32_t bar) {
    asm volatile("st.async.weak.shared::cluster.mbarrier::complete_tx::bytes.v4.b32 [%0], {%1,%2,%3,%4}, [%5];" :: "r"(a), "r"(x), "r"(y), "r"(z), "r"(w), "r"(bar) : "memory");
}
__device__ __forceinline__ void mbar_init(uint32_t b, uint32_t cnt) { asm volatile("mbarrier.init.shared::cta.b64 [%0], %1;" :: "r"(b), "r"(cnt) : "memory"); }
__device__ __forceinline__ void mbar_fence() { asm volatile("fence.mbarrier_init.release.cluster;" ::: "memory"); }
__device__ __forceinline__ void mbar_expect(uint32_t b, uint32_t bytes) { asm volatile("mbarrier.arrive.expect_tx.shared::cta.b64 _, [%0], %1;" :: "r"(b), "r"(bytes) : "memory"); }
__device__ __forceinline__ void mbar_arrive(uint32_t b) { asm volatile("mbarrier.arrive.shared::cta.b64 _, [%0];" :: "r"(b) : "memory"); }
__device__ __forceinline__ void mbar_wait(uint32_t b, uint32_t parity = 0) {
    asm volatile("{ .reg .pred p; .reg .u32 n; mov.u32 n, 0;\n"
                 "LW: mbarrier.try_wait.parity.shared::cta.b64 p, [%0], %1; @p bra LD; add.u32 n, n, 1; setp.lt.u32 p, n, 65536; @p bra LW; trap;\n"
                 "LD: }" :: "r"(b), "r"(parity) : "memory");
}
__device__ __forceinline__ void mbar_wait_cluster(uint32_t b) {
    asm volatile("{ .reg .pred p; .reg .u32 n; mov.u32 n, 0;\n"
                 "LW: mbarrier.try_wait.parity.acquire.cluster.shared::cta.b64 p, [%0], 0; @p bra LD; add.u32 n, n, 1; setp.lt.u32 p, n, 65536; @p bra LW; trap;\n"
                 "LD: }" :: "r"(b) : "memory");
}
__device__ __forceinline__ void tma2d(uint32_t dst, const CUtensorMap* m, int c0, int c1, uint32_t bar) {
    asm volatile("cp.async.bulk.tensor.2d.shared::cluster.global.mbarrier::complete_tx::bytes [%0], [%1, {%3, %4}], [%2];"
                 :: "r"(dst), "l"(m), "r"(bar), "r"(c0), "r"(c1) : "memory");
}
__device__ __forceinline__ void tma3d(uint32_t dst, const CUtensorMap* m, int c0, int c1, int c2, uint32_t bar) {
    asm volatile("cp.async.bulk.tensor.3d.shared::cluster.global.mbarrier::complete_tx::bytes [%0], [%1, {%3, %4, %5}], [%2];"
                 :: "r"(dst), "l"(m), "r"(bar), "r"(c0), "r"(c1), "r"(c2) : "memory");
}
__device__ __forceinline__ void tma4d(uint32_t dst, const CUtensorMap* m, int c0, int c1, int c2, int c3, uint32_t bar) {
    asm volatile("cp.async.bulk.tensor.4d.shared::cluster.global.mbarrier::complete_tx::bytes [%0], [%1, {%3, %4, %5, %6}], [%2];"
                 :: "r"(dst), "l"(m), "r"(bar), "r"(c0), "r"(c1), "r"(c2), "r"(c3) : "memory");
}
__device__ __forceinline__ void bulk_g2s(uint32_t dst, const void* src, uint32_t bytes, uint32_t bar) {
    asm volatile("cp.async.bulk.shared::cluster.global.mbarrier::complete_tx::bytes [%0], [%1], %2, [%3];"
                 :: "r"(dst), "l"(src), "r"(bytes), "r"(bar) : "memory");
}
__device__ __forceinline__ uint32_t mapa(uint32_t a, uint32_t rank) { uint32_t r; asm("mapa.shared::cluster.u32 %0, %1, %2;" : "=r"(r) : "r"(a), "r"(rank)); return r; }
__device__ __forceinline__ void prefetch_map(const CUtensorMap* m) { asm volatile("prefetch.tensormap [%0];" :: "l"(m) : "memory"); }
__device__ __forceinline__ void bar_sync(int id, int n) { asm volatile("bar.sync %0, %1;" :: "r"(id), "r"(n) : "memory"); }
__device__ __forceinline__ void bar_arrive(int id, int n) { asm volatile("bar.arrive %0, %1;" :: "r"(id), "r"(n) : "memory"); }
__device__ __forceinline__ uint32_t ldg16_if(bool c, const void* p) { uint32_t v; asm volatile("{ .reg .pred p; setp.ne.u32 p, %2, 0; @p ld.global.nc.u16 %0, [%1]; }" : "=r"(v) : "l"(p), "r"((uint32_t)c)); return v; }
__device__ __forceinline__ uint32_t ldg32_if(bool c, const void* p) { uint32_t v; asm volatile("{ .reg .pred p; setp.ne.u32 p, %2, 0; @p ld.global.nc.u32 %0, [%1]; }" : "=r"(v) : "l"(p), "r"((uint32_t)c)); return v; }
__device__ __forceinline__ uint32_t ld_rlx32(const void* p) { uint32_t v; asm volatile("ld.relaxed.gpu.global.u32 %0, [%1];" : "=r"(v) : "l"(p) : "memory"); return v; }
__device__ __forceinline__ uint4 ld_rlx128(const void* p) {
    uint4 v; asm volatile("ld.relaxed.gpu.global.v4.u32 {%0,%1,%2,%3}, [%4];" : "=r"(v.x), "=r"(v.y), "=r"(v.z), "=r"(v.w) : "l"(p) : "memory"); return v;
}
__device__ __forceinline__ void st_rlx32(void* p, uint32_t v) { asm volatile("st.relaxed.gpu.global.u32 [%0], %1;" :: "l"(p), "r"(v) : "memory"); }
__device__ __forceinline__ void stg128(void* p, uint32_t x, uint32_t y, uint32_t z, uint32_t w) {
    asm volatile("st.global.v4.u32 [%0], {%1,%2,%3,%4};" :: "l"(p), "r"(x), "r"(y), "r"(z), "r"(w) : "memory");
}
__device__ __forceinline__ void next_epoch(const Params& p, unsigned e) { if ((threadIdx.x & 31) == 0) p.s->epoch[blockIdx.x * 16 + (threadIdx.x >> 5)] = e + 1; }
__device__ __forceinline__ void sts128z_if(bool c, uint32_t a) { asm volatile("{ .reg .pred p; setp.ne.u32 p, %1, 0; @p st.shared.v4.u32 [%0], {%2,%2,%2,%2}; }" :: "r"(a), "r"((uint32_t)c), "r"(0) : "memory"); }
__device__ __forceinline__ void stg128z_if(bool c, void* a) { asm volatile("{ .reg .pred p; setp.ne.u32 p, %1, 0; @p st.global.v4.u32 [%0], {%2,%2,%2,%2}; }" :: "l"(a), "r"((uint32_t)c), "r"(0) : "memory"); }
__device__ __forceinline__ unsigned clock32() { unsigned c; asm volatile("mov.u32 %0, %clock;" : "=r"(c) :: "memory"); return c; }
__device__ __forceinline__ void until(unsigned t0, int c) { while ((int)(clock32() - t0) < c) { } }
__device__ __forceinline__ float sigmoidf_(float x) { return __fdividef(1.0f, 1.0f + __expf(-x)); }
__device__ __forceinline__ uint32_t key_tag(unsigned epoch) { return ((epoch & 15u) | 16u) << 11; }
__device__ __forceinline__ int key_row(uint32_t key) { return 2047 - (int)(key & 2047u); }
__device__ __forceinline__ uint32_t wait_sel(const Params& p, int s32, int r8, uint32_t tag, uint32_t k = 0) {
#pragma unroll 1
    for (int it = 0; !__all_sync(0xffffffffu, (k & 0xf800u) == tag); it++) {
        k = ld_rlx32(&p.s->sel[s32 * 64 + r8]);
        if (it > (1 << 20)) give_up();
    }
    return k;
}

struct cplx { float re, im; };
__device__ __forceinline__ cplx csq(cplx a) { cplx r; r.re = a.re * a.re - a.im * a.im; r.im = (a.re * a.im) * 2.f; return r; }
__device__ __forceinline__ cplx cexpk(float ar, float ai, float k) {
    float mag, s, c;
    asm("ex2.approx.ftz.f32 %0, %1;" : "=f"(mag) : "f"(ar * (k * 1.4426950408889634f)));
    const float r = ai * k;
    asm("sin.approx.ftz.f32 %0, %1;" : "=f"(s) : "f"(r));
    asm("cos.approx.ftz.f32 %0, %1;" : "=f"(c) : "f"(r));
    cplx o; o.re = mag * c; o.im = mag * s; return o;
}
struct h2c { uint32_t re, im; };
__device__ __forceinline__ h2c cmul_cd(h2c v, __half2 c, __half2 d) {
    const __half2 r = *(const __half2*)&v.re, i = *(const __half2*)&v.im;
    const __half2 x = __hfma2(__hneg2(i), d, __hmul2(r, c)), y = __hfma2(i, c, __hmul2(r, d));
    h2c o; o.re = *(const uint32_t*)&x; o.im = *(const uint32_t*)&y; return o;
}
__device__ __forceinline__ h2c cmul_s(h2c v, uint32_t s) { const __half2 h = *(const __half2*)&s; return cmul_cd(v, __low2half2(h), __high2half2(h)); }
__device__ __forceinline__ h2c cmul_sc(h2c v, uint32_t s) {
    const __half2 h = *(const __half2*)&s, c = __low2half2(h), d = __high2half2(h), r = *(const __half2*)&v.re, i = *(const __half2*)&v.im;
    const __half2 x = __hfma2(i, d, __hmul2(r, c)), y = __hfma2(__hneg2(r), d, __hmul2(i, c));
    h2c o; o.re = *(const uint32_t*)&x; o.im = *(const uint32_t*)&y; return o;
}
__device__ __forceinline__ h2c cmul_vc(h2c v, uint32_t s) {
    const __half2 h = *(const __half2*)&s, c = __low2half2(h), d = __high2half2(h), r = *(const __half2*)&v.re, i = *(const __half2*)&v.im;
    const __half2 x = __hfma2(i, d, __hmul2(r, c)), y = __hfma2(__hneg2(i), c, __hmul2(r, d));
    h2c o; o.re = *(const uint32_t*)&x; o.im = *(const uint32_t*)&y; return o;
}

constexpr int UT_HALF = 2560, UT_STRIDE = 4736, GT_HALF = 2240;
__device__ __forceinline__ uint32_t swz(uint32_t x, int c) { return x ^ (((x >> 2) & 64) ^ (64 * (c & 1) + 8 * (c & 6))); }
__device__ __forceinline__ int col(int n) { return (n >> 1) + 4 * (n & 1); }
constexpr int KT_T = 542, KT_C = 552, KT_D = 645, KT_BYTES = 720 * 4;
constexpr int VC_OFF = 80, VE_BASE = 1616;
constexpr int V_STRIDE = (1616 + 1024) * 4 + 80;
constexpr int KG_STAGE = 5248;
constexpr int Y_CS = 2080, Y_RS = 8 * Y_CS + 64;

constexpr int SC_RT = 0;
constexpr int SC_UT = 33408;
constexpr int SC_KG = SC_UT + 8 * UT_STRIDE;
constexpr int SC_KT = SC_KG + 8 * KG_STAGE;
constexpr int SC_GT = SC_KT + 8 * KT_BYTES;
constexpr int SC_V = SC_GT + 4448;
constexpr int SC_MISC = SC_V + 8 * V_STRIDE;
static_assert(V_STRIDE % 128 == 16 && 2 * Y_RS <= SC_UT && SC_UT % 128 == 0 && SC_KG % 128 == 0, "layout");
static_assert(SC_MISC % 16 == 0 && SC_MISC + 512 <= 232192, "layout");

__device__ __forceinline__ void window_task(uint32_t s0, uint32_t s1, uint32_t d0, uint32_t d1, int k) {
    float S[51], s = 0.f;
    uint32_t w[28];
#pragma unroll
    for (int i = 0; i < 7; i++) {
        const uint4 v = lds128(((i < 3 ? s0 : s1) ^ 8 * ((i + 1) & 2)) + ((i & 1) ? 0 : UT_HALF));
        w[4 * i] = v.x; w[4 * i + 1] = v.y; w[4 * i + 2] = v.z; w[4 * i + 3] = v.w;
    }
    auto sums = [&](int lo, int hi) {
#pragma unroll
        for (int i = lo; i < hi; i++) { const float x = (i & 1) ? bf_hi(w[i >> 1]) : bf_lo(w[i >> 1]); s = i > 3 ? s + x : x; S[i] = s; }
    };
    auto put = [&](int off, int b, int o0, int o1, int o2) {
        auto v = [&](int i) { i += 16 * b; return pack_bf16(S[o0 + i] - S[o1 + i], S[o1 + i] - S[o2 + i]); };
#pragma unroll
        for (int i = 0; i < 8; i += 2) sts128((i & 4 ? d1 : d0) + 4 * off + 64 * b + 8 * (i & 2), v(i), v(i + 8), v(i + 1), v(i + 9));
    };
    S[2] = 0.f;
    sums(3, 26); put(VC_OFF - 16, 0, 10, 5, 2);
    if (k == 12) return;
    sums(26, 42); put(VC_OFF - 16, 1, 10, 5, 2);
    if (k < 8) { put(VE_BASE, 0, 19, 12, 3); sums(42, 51); put(VE_BASE, 1, 19, 12, 3); }
}

template <class F>
__device__ __forceinline__ void kgen(const uint32_t (&q)[8], uint32_t sb, int half, uint32_t stage, uint32_t pstage, int barid, int lane, uint32_t (&w)[12], F shadow) {
    const int t = lane & 3, mi = lane >> 3, r8 = lane & 7;
    {
        const uint32_t pAr = q[0], pAi = q[1], pBr = q[2], pBi = q[3], pCr = q[4], pCi = q[5], pDt = q[6], pD = q[7];
        const uint32_t wb = fresh(stage + lane * 16), za = fresh(stage + 5120 + ((lane >> 1) & 3) * 16 + mi * 4 + (lane & 1) * 2), zr = fresh(stage + 5120 + t * 16);
        const uint32_t oA = fresh(stage + (mi & 1) * 1024 + (mi >> 1) * 512 + r8 * 16), oB = fresh(stage + 2048 + mi * 512 + r8 * 16), oC = fresh(stage + 4096 + (mi & 1) * 512 + (mi >> 1) * 128 + r8 * 16);
        float acc[6][4];
#pragma unroll
        for (int a = 0; a < 6; a++) { acc[a][0] = acc[a][1] = acc[a][2] = acc[a][3] = 0.f; asm volatile("" : "+f"(acc[a][0]), "+f"(acc[a][1]), "+f"(acc[a][2]), "+f"(acc[a][3])); }
        shadow();
        sts32(zr, clock32());
        const float dt = rbf(__expf(bf_lo(pDt)));
        float ar = dt * bf_lo(pAr), ai = dt * bf_lo(pAi), ar1 = dt * bf_hi(pAr), ai1 = dt * bf_hi(pAi);
        float wr, wi, wr1, wi1;
        { const float br = dt * bf_lo(pBr), bi = dt * bf_lo(pBi), cr = bf_lo(pCr), ci = bf_lo(pCi); wr = cr * br - ci * bi; wi = cr * bi + ci * br; }
        { const float br = dt * bf_hi(pBr), bi = dt * bf_hi(pBi), cr = bf_hi(pCr), ci = bf_hi(pCi); wr1 = cr * br - ci * bi; wi1 = cr * bi + ci * br; }
        const uint32_t ex = max(__reduce_max_sync(0xffffffffu, __float_as_uint(fmaxf(fmaxf(fabsf(wr), fabsf(wi)), fmaxf(fabsf(wr1), fabsf(wi1))))) >> 23, 14u);
        const float scl = __uint_as_float((267u - ex) << 23);
        uint32_t W = pack_f16(wr * scl, wi * -scl);
        const uint32_t W1 = pack_f16(wr1 * scl, wi1 * -scl);
        if (threadIdx.x < 32) TSTAMP(20);

#pragma unroll 1
        for (int r = 0; r < 2; r++) {
            const cplx z1 = cexpk(ar, ai, 1.f), z64 = cexpk(ar, ai, 64.f);
            const cplx z2 = csq(z1), z4 = csq(z2), z8 = csq(z4), z16 = csq(z8), z32 = csq(z16);
            const cplx z128 = csq(z64), z256 = csq(z128), z512 = csq(z256);
            auto put = [&](int grp, h2c a, h2c b, h2c c, h2c d) { sts128(wb + grp * 1024, a.re, b.re, c.re, d.re); sts128(wb + grp * 1024 + 512, a.im, b.im, c.im, d.im); };
            {
                const uint32_t s4 = pack_f16(z4.re, z4.im), s256 = pack_f16(z256.re, z256.im), s512 = pack_f16(z512.re, z512.im);
                auto mix = [](h2c a, h2c b, uint32_t sel) { return h2c{__byte_perm(a.re, b.re, sel), __byte_perm(a.im, b.im, sel)}; };
                const h2c c10 = cmul_vc(h2c{pack_f16(z1.re, 1.f), pack_f16(z1.im, 0.f)}, W), c32 = cmul_sc(c10, pack_f16(z2.re, z2.im)), c54 = cmul_sc(c10, s4);
                put(2, c10, c32, c54, cmul_sc(c32, s4));
                const h2c d20 = cmul_sc(mix(c32, c10, 0x7632), s256), e04 = cmul_sc(mix(c10, c54, 0x7632), s512), f04 = cmul_sc(e04, s256);
                put(3, d20, cmul_sc(d20, s4), e04, f04);
                const h2c ef = mix(e04, f04, 0x5410), gh = cmul_sc(ef, s512), g8 = cmul_sc(gh, pack_f16(z8.re, z8.im));
                put(4, g8, cmul_sc(g8, s512), gh, ef);
            }
            {
                const uint32_t s32 = pack_f16(z32.re, z32.im), s64 = pack_f16(z64.re, z64.im), s128 = pack_f16(z128.re, z128.im);
                const h2c p0 = {pack_f16(1.f, z8.re), pack_f16(0.f, z8.im)}, p1 = cmul_s(p0, pack_f16(z16.re, z16.im)), p2 = cmul_s(p0, s32), p3 = cmul_s(p1, s32);
                put(0, p0, p1, p2, p3);
                put(1, cmul_s(p0, s64), cmul_s(p1, s64), cmul_s(p2, s64), cmul_s(p3, s64));
                sts16(za, s128); sts16(za + 64, s128 >> 16);
            }
            __syncwarp();
            {
                const uint32_t aA = fresh(oA), aB = fresh(oB), aC = fresh(oC), aZ = fresh(zr);
                const uint4 zc = lds128(aZ), zd = lds128(aZ + 64);
                const uint32_t zcs[4] = {zc.x, zc.y, zc.z, zc.w}, zds[4] = {zd.x, zd.y, zd.z, zd.w};
                uint32_t c[4];
#pragma unroll
                for (int k = 0; k < 4; k++) {
                    uint32_t a[4], b[4];
                    ldsm4t(a, aA + 128 * k); ldsm4t(b, aB + 128 * k);
                    if (!(k & 1)) ldsm4t(c, aC + 128 * k);
                    const h2c x = cmul_cd(h2c{a[0], a[2]}, *(const __half2*)&zcs[k], *(const __half2*)&zds[k]), y = cmul_cd(h2c{a[1], a[3]}, *(const __half2*)&zcs[k], *(const __half2*)&zds[k]);
                    mma_h(acc[0], a[0], a[1], a[2], a[3], b[0], b[1]);
                    mma_h(acc[1], a[0], a[1], a[2], a[3], b[2], b[3]);
                    mma_h(acc[2], a[0], a[1], a[2], a[3], c[2 * (k & 1)], c[2 * (k & 1) + 1]);
                    mma_h(acc[3], x.re, y.re, x.im, y.im, b[0], b[1]);
                    mma_h(acc[4], x.re, y.re, x.im, y.im, b[2], b[3]);
                    mma_h(acc[5], x.re, y.re, x.im, y.im, c[2 * (k & 1)], c[2 * (k & 1) + 1]);
                }
                asm volatile("" :: "f"(acc[0][0]), "f"(acc[1][0]), "f"(acc[2][0]), "f"(acc[3][0]), "f"(acc[4][0]), "f"(acc[5][0]) : "memory");
            }
            __syncwarp();
            ar = ar1; ai = ai1; W = W1;
        }
        if (threadIdx.x < 32) TSTAMP(21);
        const float i0 = __uint_as_float((ex + 243u) << 23);
        if (half) {
#pragma unroll
            for (int a = 0; a < 6; a++) sts128(wb + a * 512, __float_as_uint(acc[a][0]), __float_as_uint(acc[a][1]), __float_as_uint(acc[a][2]), __float_as_uint(acc[a][3]));
            sts32(stage + 3072, __float_as_uint(i0));
            bar_arrive(barid, 64);
        } else {
#pragma unroll
            for (int a = 0; a < 6; a++) { acc[a][0] *= i0; acc[a][1] *= i0; acc[a][2] *= i0; acc[a][3] *= i0; }
            if (lane == 0) acc[0][1] -= bf_lo(pD);
            sts32(zr, clock32());
            bar_sync(barid, 64);
            const uint32_t src = fresh(pstage);
            const float i1 = __uint_as_float(lds32(src + 3072));
#pragma unroll
            for (int a = 0; a < 6; a++) {
                const uint4 y = lds128(src + lane * 16 + a * 512);
                w[4 * (a % 3) + 2 * (a / 3)] = pack_bf16(fmaf(__uint_as_float(y.x), i1, acc[a][0]), fmaf(__uint_as_float(y.y), i1, acc[a][1]));
                w[4 * (a % 3) + 2 * (a / 3) + 1] = pack_bf16(fmaf(__uint_as_float(y.z), i1, acc[a][2]), fmaf(__uint_as_float(y.w), i1, acc[a][3]));
            }
            const uint32_t x0 = __shfl_up_sync(0xffffffffu, w[10], 2), x1 = __shfl_up_sync(0xffffffffu, w[11], 2);
            w[10] = w[8];
            if (t >= 2) { w[8] = x0; w[9] = x1; }
        }
    }
}

enum { BC_AUX = 0, BC_U = 5 };

__device__ __forceinline__ void fetch_gates(const Params& p, int i, int lane, unsigned epoch, uint32_t dst) {
    const uint32_t par = (epoch & 1) ? 0x80008000u : 0u;
    uint4 v;
#pragma unroll 1
    for (int it = 0;; it++) {
        v = ld_rlx128(p.s->gate + 256 * i + 8 * lane);
        v.x ^= par; v.y ^= par; v.z ^= par; v.w ^= par;
        if (__all_sync(0xffffffffu, (v.x & v.y & v.z & v.w & 0x80008000u) == 0x80008000u)) break;
        if (it > (1 << 20)) give_up();
    }
    sts128(dst + (8 + 16 * i + (lane >> 1)) * 16, v.x, v.y, v.z, v.w);
}
__device__ __forceinline__ void store_rows(const CUtensorMap* m, uint32_t src, int col, int row) {
    asm volatile("cp.async.bulk.tensor.5d.global.shared::cta.bulk_group [%0, {%2, %3, %3, %3, %4}], [%1];" :: "l"(m), "r"(src), "r"(col), "r"(0), "r"(row) : "memory");
}

__device__ __forceinline__ void store_or_add(void* o, const uint32_t (&y)[4], uint32_t add) {
    asm volatile("{ .reg .pred p; setp.ne.u32 p, %5, 0; @!p st.global.v4.u32 [%0], {%1,%2,%3,%4}; @p red.relaxed.gpu.global.add.noftz.v4.bf16x2 [%0], {%1,%2,%3,%4}; }"
                 :: "l"(o), "r"(y[0]), "r"(y[1]), "r"(y[2]), "r"(y[3]), "r"(add) : "memory");
}

__device__ __forceinline__ void conv_aux(const Params& p, const CUtensorMap* mU, uint32_t sb, int aw, int lane, int bid, unsigned epoch) {
    const int g = lane >> 2, t = lane & 3, mi = lane >> 3, r8 = lane & 7;
    const int rank = bid & 1, slab = bid >> 1;
    const uint32_t bar_y = sb + SC_MISC, bar_u = bar_y + 32, bar_v = bar_y + 40, bar_box = bar_y + 64 + 8 * aw, s_bm = bar_y + 128;
    if (elect()) {
        mbar_init(bar_box, 1); mbar_fence();
        mbar_expect(bar_box, 4096);
        tma4d(sb + SC_RT + 4096 * aw, mU, 16 * slab, 0, 0, 16 * rank + 2 * aw, bar_box);
        mbar_init(bar_y + 8 * aw, aw < 4 ? 9 : aw == 5 ? 8 : 1); mbar_fence();
        if (aw < 5) mbar_expect(bar_y + 8 * aw, aw == 4 ? 16384 : 4096);
    }
    __syncwarp();
    asm volatile("barrier.cluster.arrive.relaxed.aligned;" ::: "memory");
    asm volatile("setmaxnreg.dec.sync.aligned.u32 88;");
    sts128(sb + (lane < 16 ? SC_UT + aw * UT_STRIDE + mi * (UT_HALF - 128) : SC_V - 256 + aw * V_STRIDE) + lane * 16, 0, 0, 0, 0);
    if (lane < 16) sts128(s_bm + lane * 16, 0, 0, 0, 0);
    {
        const uint32_t dst = sb + SC_UT + g * UT_STRIDE + swz((8 + 64 * rank + 8 * aw + t) * 16, g);
        const uint32_t rdst = mapa(dst, rank ^ 1), rbar = mapa(bar_u, rank ^ 1);
        asm volatile("barrier.cluster.wait.acquire.aligned;" ::: "memory");
        mbar_wait(bar_box);
        if (aw == 0) TSTAMP(1);
        const uint32_t src = fresh(sb + SC_RT) + aw * 4096 + (8 * mi + 4 * (r8 & 1) + (r8 >> 1)) * 32 + ((rank ^ (r8 & 1)) << 4);
        uint32_t x[8][4];
#pragma unroll
        for (int i = 0; i < 4; i++) { ldsm4t(x[i], src + 1024 * i); ldsm4t(x[4 + i], (src ^ 16) + 1024 * i); }
        asm volatile("" :: "r"(x[0][0]), "r"(x[1][0]), "r"(x[2][0]), "r"(x[3][0]) : "memory");
#pragma unroll
        for (int i = 0; i < 4; i++) st_async128((rdst ^ 32 * (i & 2)) + (i & 1) * UT_HALF, x[4 + i][0], x[4 + i][1], x[4 + i][2], x[4 + i][3], rbar);
#pragma unroll
        for (int i = 0; i < 4; i++) sts128((dst ^ 32 * (i & 2)) + (i & 1) * UT_HALF, x[i][0], x[i][1], x[i][2], x[i][3]);
    }
    bar_sync(BC_AUX, 256);
    mbar_wait_cluster(bar_u);
    if (aw == 0) TSTAMP(2);
    if (aw >= 4) bar_arrive(BC_U + aw, 64); else bar_sync(BC_U + aw, 64);
    if (aw == 0) TSTAMP(3);
    {
        const uint32_t ws = fresh(sb + SC_UT) + r8 * UT_STRIDE, wd = sb + SC_V + r8 * V_STRIDE;
#pragma unroll 1
        for (int k = aw; k < 13; k += 8) {
            const int a = 8 * k + (k < 12 ? g & 6 : 0);
            const uint32_t d = wd + 64 * a, sw = 16 * (a & 2);
            window_task(ws + swz(16 * a + 96, r8), ws + swz(16 * a + 128, r8), d + sw, d + (sw ^ 32), k);
        }
    }
    if (aw == 0) TSTAMP(9);
    {
        if (aw >= 2) fetch_gates(p, aw, lane, epoch, sb + SC_GT + (lane & 1) * GT_HALF);
        __syncwarp();
        if (elect()) { mbar_arrive(bar_v); prefetch_map(mU + 4); }
        next_epoch(p, epoch);
        if (aw == 0) TSTAMP(4);
        if (aw == 7) {
            const int row = key_row(wait_sel(p, slab >> 1, r8, key_tag(epoch)));
            if (lane < 8) asm volatile("red.shared.or.b32 [%0], %1;" :: "r"(s_bm + (row >> 5) * 4), "r"(1u << (row & 31)) : "memory");
            TSTAMP(10);
        }
        bar_sync(BC_AUX, 256);
        const uint32_t src = sb + SC_RT + ((r8 >> 1) & 1) * Y_RS + (2 * mi + (r8 & 1)) * Y_CS + (2 * aw + (r8 >> 2)) * 16;
        const int L = 2 * aw + (t >> 1);
        const int row0 = 256 * rank + 128 * (g >> 2) + 16 * (L & 3) + 64 * (g & 1) + 8 * ((g >> 1) & 1) + (L >> 2);
        __nv_bfloat16* outp = p.out + (size_t)row0 * DM + 16 * slab + 8 * (t & 1);
        const uint32_t stg = sb + SC_KG + 4096 * aw, so = (g & 2) * 256 + (g >> 2) * 128 + r8 * 16;
#pragma unroll 1
        for (int s = 1; s < 4; s++) {
            const uint32_t bm = lds32(fresh(s_bm) + (16 * s + (row0 >> 5)) * 4) >> (row0 & 31);
            const bool routed = __any_sync(0xffffffffu, bm & 0x11u);
            if (aw == s) mbar_wait_cluster(bar_y + 8 * s);
            bar_sync(BC_AUX, 256);
            const uint32_t sf = fresh(src) + 512 * s;
            uint32_t y[2][4];
            ldsm4t(y[0], sf); ldsm4t(y[1], sf + 256);
            if (routed) {
#pragma unroll
                for (int k = 0; k < 2; k++) store_or_add(outp + (size_t)(512 * s + 4 * k) * DM, y[k], bm & (1u << (4 * k)));
            } else {
                sts128(stg + so + 1024 * s, y[0][0], y[0][1], y[0][2], y[0][3]); sts128(stg + so + 1024 * s + 256, y[1][0], y[1][1], y[1][2], y[1][3]);
                asm volatile("fence.proxy.async.shared::cta;" ::: "memory");
                __syncwarp();
                if (elect()) store_rows(mU + 4, stg + 1024 * s, 16 * slab, 512 * s + 256 * rank + 32 * (aw & 1) + (aw >> 1));
            }
            if (aw == 0) TSTAMP(16 + s);
        }
        if (elect()) { asm volatile("cp.async.bulk.commit_group;" ::: "memory"); asm volatile("cp.async.bulk.wait_group.read 0;" ::: "memory"); }
        if (aw == 0) TFLUSH();
    }
}

__device__ __forceinline__ uint32_t k_tag(unsigned epoch) { return epoch << 16 | 0x80000000u; }
__device__ __forceinline__ void publish_k(uint4* kp, const uint32_t (&w)[12], unsigned epoch, uint64_t (&v)[6]) {
#pragma unroll
    for (int i = 0; i < 3; i++) {
        v[2 * i] = w[3 * i] | (uint64_t)w[3 * i + 1] << 32; v[2 * i + 1] = w[3 * i + 2] | (uint64_t)__byte_perm(w[9 + (i >> 1)], k_tag(epoch), i == 1 ? 0x7632 : 0x7610) << 32;
        asm volatile("st.relaxed.gpu.global.v2.u64 [%0], {%1,%2};" :: "l"(kp + 32 * i), "l"(v[2 * i]), "l"(v[2 * i + 1]));
    }
}
template <bool FULL>
__device__ __forceinline__ void k_tables(uint32_t kt, int lane, const uint32_t (&w)[12]) {
    const int g = lane >> 2, t = lane & 3, mi = lane >> 3, r8 = lane & 7;
    uint32_t x3 = w[7], re[4], rx[4];
#pragma unroll
    for (int i = 0; i < 4; i++) {
        re[i] = __shfl_sync(0xffffffffu, w[i], lane + 31);
        rx[i] = __shfl_sync(0xffffffffu, w[4 + i], lane + (i == 0 && lane == 29 ? 5 : 1 + 2 * t));
    }
    if (FULL) {
        asm volatile("stmatrix.sync.aligned.m8n8.x2.trans.shared.b16 [%0], {%1,%2};" :: "r"(kt + (KT_D + 7) * 4 + 64 * t + 16 * (mi & 1) + 8 * (r8 & 4)), "r"(w[8]), "r"(w[9]) : "memory");
        if (lane == 2) {
            sts32(kt + (KT_C + 78) * 4, w[10] & 0xffffu);
            sts128(kt + (KT_T + 2) * 4, 0, w[10] & 0xffffu, __byte_perm(w[10], 0, 0x1010), w[10] << 16);
        }
        if (lane == 29) x3 = bsub2(x3, rx[0] & 0xffffu);
    }
#pragma unroll
    for (int i = 0; i < 4; i++) {
        sts64(kt + (16 + 64 * i) * 4 + 8 * lane, __byte_perm(w[i], lane ? re[i] : i ? re[i - 1] : 0, 0x5432), w[i]);
        const uint32_t x = i < 3 ? w[4 + i] : x3, aa = __byte_perm(x, 0, 0x3232);
        if (t < 2) sts128(kt + (272 + 64 * i + 8 * g + 4 * t) * 4, i == 0 && lane == 0 ? __byte_perm(x, re[3], 0x5432) : aa, aa, x,
                          __byte_perm(lane != 29 ? rx[i] : i < 3 ? rx[(i + 1) & 3] : FULL ? 0 : rx[0] << 16, x, 0x5432));
        else if (FULL) sts32(kt + (KT_C - 50 + 8 * i + 32 * t + g) * 4, x);
    }
}

__device__ __forceinline__ void conv_main(const Params& p, uint32_t sb, int warp, int lane0, int bid, unsigned epoch, uint32_t (&w)[12]) {
    asm volatile("setmaxnreg.inc.sync.aligned.u32 168;");
    const int lane = __shfl_sync(0xffffffffu, lane0, lane0);
    const int g = lane >> 2, t = lane & 3, mi = lane >> 3, r8 = lane & 7;
    const int rank = bid & 1;
    const uint32_t bar_y = sb + SC_MISC, bar_v = bar_y + 40;
    next_epoch(p, epoch);
    if (warp >= 4) {
        bar_sync(BC_U + warp, 64);
        if (KPOLL) until(clock32(), KPOLL);
        const uint4* src = p.s->kp + (8 * bid + warp) * 96 + lane0;
#pragma unroll 1
        for (int it = 0;; it++) {
            uint32_t bad = 0, e[3];
#pragma unroll
            for (int i = 0; i < 3; i++) { const uint4 v = ld_rlx128(src + 32 * i); w[3 * i] = v.x; w[3 * i + 1] = v.y; w[3 * i + 2] = v.z; e[i] = v.w; bad |= v.w ^ k_tag(epoch); }
            w[9] = __byte_perm(e[0], e[1], 0x5410); w[10] = e[2];
            const bool ok = __all_sync(0xffffffffu, bad < 65536);
            if (ok) break;
            if (it > (1 << 20)) give_up();
        }
    }
    if ((warp & 3) == 0) TSTAMP(5 + (warp >> 2));
    k_tables<true>(sb + SC_KT + warp * KT_BYTES, lane0, w);
    asm volatile("barrier.cluster.wait.acquire.aligned;" ::: "memory");
    if (warp < 4) bar_sync(BC_U + warp, 64);
    __syncwarp();
    if ((warp & 3) == 0) TSTAMP(7 + (warp >> 2));
    {
        const uint32_t ut = fresh(sb + SC_UT) + warp * UT_STRIDE, kt = fresh(sb + SC_KT) + warp * KT_BYTES;
        auto dup = [&](uint32_t v) { return v ^ p.zero; };
        auto frag = [&](uint32_t (&a)[4], uint32_t x) { a[0] = lds32(x); a[1] = lds32(x + 32); a[2] = lds32(x - 32); a[3] = dup(a[0]); };
        const uint32_t kb = kt + (16 + g - 2 * t) * 4;
        float acc[16][4];
        {
            float y[12][4], M[6][4];
#pragma unroll
            for (int i = 0; i < 12; i++) { y[i][0] = y[i][1] = y[i][2] = y[i][3] = 0.f; M[i >> 1][0] = M[i >> 1][1] = M[i >> 1][2] = M[i >> 1][3] = 0.f; }
            uint32_t U[10][4], a1[4], ad[4], R = (mi & 1) * UT_HALF + (8 + (r8 >> 1) + 48 * (r8 & 1)) * 16 + 64 * (mi >> 1);
            auto places = [&] { ad[0] = swz(R, warp); ad[1] = swz(R + 128, warp); ad[2] = ad[0] ^ 64; ad[3] = ad[1] ^ 64; };
            auto ldu = [&](int k) { ldsm4(U[k], ut + ad[k & 3] + 256 * (k >> 1)); };
            places();
            frag(a1, kb + 2048);
#pragma unroll
            for (int k = 0; k < 7; k++) ldu(k);
#pragma unroll
            for (int i = 0; i < 12; i++) mma_bf(y[i], a1[0], a1[1], a1[2], a1[3], U[i >> 1][2 * (i & 1)], U[i >> 1][2 * (i & 1) + 1]);
            frag(a1, kb + 1792);
            __syncwarp();
#pragma unroll DUNR
            for (uint32_t ko = 0; ko != 256;) {
                if (DUN == 1) ko = fresh(ko);
                const uint32_t kp = kb + ko;
                ko += 64;
                uint32_t se[10][2], so[10][2], ue[10][2];
                auto sums = [&](int k) {
#pragma unroll
                    for (int e = 0; e < 2; e++) { ue[k][e] = U[k][e]; se[k][e] = badd2(U[k][e], U[k - 1][2 + e]); so[k][e] = badd2(U[k][e], U[k][2 + e]); }
                };
#pragma unroll
                for (int k = 1; k < 6; k++) sums(k);
#pragma unroll
                for (int m = 3; m >= 0; m--) {
                    uint32_t a0[4];
                    frag(a0, kp + 512 * m);
                    sums(9 - m);
                    if (m) ldu(10 - m); else { R -= 16; places(); }
#pragma unroll
                    for (int i = 0; i < 6; i++) mma_bf(y[2 * i], a1[0], a1[1], a1[2], a1[3], se[i - m + 4][0], se[i - m + 4][1]);
#pragma unroll
                    for (int e = 0; e < 4; e++) a1[e] = bsub2(a0[e], a1[e]);
#pragma unroll
                    for (int i = 0; i < 6; i++) { mma_bf(M[i], a1[0], a1[1], a1[2], a1[3], ue[i - m + 4][0], ue[i - m + 4][1]); if (!m) ldu(i); }
                    frag(a1, m ? kp + 512 * m - 256 : kp + 1792 + 64);
                    if (!m) ldu(6);
#pragma unroll
                    for (int i = 0; i < 6; i++) mma_bf(y[2 * i + 1], a0[0], a0[1], a0[2], a0[3], so[i - m + 4][0], so[i - m + 4][1]);
                }
            }
#pragma unroll
            for (int i = 0; i < 6; i++)
#pragma unroll
                for (int c = 0; c < 4; c++) { acc[4 + i + 6 * (c & 1)][c & 2] = y[2 * i][c] + M[i][c]; acc[4 + i + 6 * (c & 1)][c | 1] = y[2 * i + 1][c] - M[i][c]; }
        }
        const uint32_t lo = (8 + col(r8)) * 16 + (mi >> 1) * 128, ua = fresh(ut) + (mi & 1) * UT_HALF, u1[2] = {ua + swz(lo, warp), ua + (swz(lo, warp) ^ 64)};
        {
            uint32_t e[4];
            frag(e, kb + (KT_T - 16) * 4);
            const uint32_t f0 = dup(e[1]), f1 = lds32(kb + KT_T * 4), uo = fresh(ut) + UT_HALF + swz((7 + 8 * mi + col(r8)) * 16, warp);
#pragma unroll
            for (int i = 0; i < 4; i++) {
                uint32_t b[4];
                if (i < 2) {
                    ldsm4(b, uo + 512 * i);
#pragma unroll
                    for (int k = 0; k < 4; k++) mma_bf8(acc[8 + 4 * i + k], f0, f1, b[k]);
                }
                ldsm4(b, u1[i & 1] + 256 * i);
                mma_bf(acc[2 * i + 8], e[0], e[1], e[2], e[3], b[0], b[1]); mma_bf(acc[2 * i + 9], e[0], e[1], e[2], e[3], b[2], b[3]);
            }
        }
        if ((warp & 3) == 0) TSTAMP(11 + (warp >> 2));
        mbar_wait(bar_v);
        const uint32_t vt = fresh(sb + SC_V) + warp * V_STRIDE;
        const uint32_t g1 = fresh(sb + SC_GT) + (mi & 1) * GT_HALF + lo;
        const uint32_t ydst = sb + SC_RT + rank * Y_RS + warp * Y_CS + lane * 16;
        const uint32_t ydr = mapa(ydst, rank ^ 1), ybr = mapa(bar_y, rank ^ 1);
        auto stairs = [&](auto R) {
        uint32_t ug[2][2][4];
        auto ld_ug = [&](int i) { ldsm4t(ug[i & 1][0], u1[i & 1] + 256 * i); ldsm4t(ug[i & 1][1], g1 + 256 * i); };
        auto ship = [&](int i) {
            const uint32_t (&u)[4] = ug[i & 1][0], (&gg)[4] = ug[i & 1][1];
            const uint32_t y0 = gmix(gg[0], acc[2 * i][0], acc[2 * i][1], u[0]), y1 = gmix(gg[1], acc[2 * i][2], acc[2 * i][3], u[1]);
            const uint32_t y2 = gmix(gg[2], acc[2 * i + 1][0], acc[2 * i + 1][1], u[2]), y3 = gmix(gg[3], acc[2 * i + 1][2], acc[2 * i + 1][3], u[3]);
            if ((i & 1) != R.value) st_async128(ydr + 512 * (i >> 1), y0, y1, y2, y3, ybr + 8 * (i >> 1));
            else asm volatile("{ .reg .pred q; setp.eq.u32 q, %6, 0; st.shared.v4.u32 [%0], {%2,%3,%4,%5}; bar.warp.sync 0xffffffff; @q mbarrier.arrive.shared::cta.b64 _, [%1]; }"
                              :: "r"(ydst + 512 * (i >> 1)), "r"(bar_y + 8 * (i >> 1)), "r"(y0), "r"(y1), "r"(y2), "r"(y3), "r"(lane) : "memory");
        };
        const uint32_t VD = vt + (VC_OFF - 400 - 16 * t) * 4 + (8 * g ^ 16 * (-t & 2)), VD2 = vt + (VC_OFF - 415 - 16 * t) * 4 + (8 * g ^ 16 * (~t & 2));
        uint2 bd[10];
        uint32_t x[2][4][4];
        auto ld4 = [&](uint32_t (&v)[4], int dl) { const uint2 w = lds64(VD + 256 * dl); v[0] = w.x; v[1] = w.y; v[2] = lds32(VD2 + 256 * dl); v[3] = dup(w.x); };
        auto mm4 = [&](const uint32_t (&v)[4], int dl) {
#pragma unroll
            for (int s = dl & 1; s < 10; s += 2) if ((dl + s) / 2 >= 4 && (dl + s) / 2 < 16) mma_bf(acc[(dl + s) / 2], v[0], v[1], v[2], v[3], bd[s].x, bd[s].y);
        };
        const uint32_t KE = kt + (KT_D + col(g) + t) * 4, VE = vt + (VE_BASE - 912 - 16 * t) * 4 + (8 * g ^ 16 * (~t & 2));
        uint32_t b0[8], b1[8];
        auto ld8 = [&](uint32_t (&v)[4], int dl) { const uint2 w = lds64(VE + 512 * dl), z = lds64(VE + 512 * dl - 256); v[0] = w.x; v[1] = w.y; v[2] = z.x; v[3] = z.y; };
        auto mm8 = [&](const uint32_t (&v)[4], int dl, int lo, int hi) {
#pragma unroll
            for (int s = 0; s < 8; s++) if (dl + s >= lo && dl + s < hi) mma_bf(acc[dl + s], v[0], v[1], v[2], v[3], b0[s], b1[s]);
        };
        ld4(x[0][0], 6);
#pragma unroll
        for (int s = 0; s < 10; s++) bd[s] = lds64(kt + (KT_C + 2 * col(g) + 2 * t + 8 * s) * 4);
        mm4(x[0][0], 6);
        uint32_t e[4][4];
#pragma unroll
        for (int k = 1; k < 6; k++) {
#pragma unroll
            for (int j = 0; j < 4; j++) ld4(x[k & 1][j], 4 * k + 3 + j);
            ld_ug(k + 1);
            if (k == 3) {
#pragma unroll
                for (int s = 0; s < 8; s++) { b0[s] = lds32(KE + 32 * s); b1[s] = lds32(KE + 32 * s + 16); }
            }
            if (k > 1) ship(k);
#pragma unroll
            for (int j = 0; j < 4; j++) {
                mm4(x[k & 1][j], 4 * k + 3 + j);
                if (k == 3) { uint32_t v[4], z[4]; ld8(e[j], 8 + j); ld8(v, 12 + j); ld4(z, 30 - j); mm8(v, 12 + j, 12, 16); mm8(e[j], 8 + j, 8, 12); mm4(z, 30 - j); }
                if (k == 5) { ld8(e[j], 8 + j + p.zero); mm8(e[j], 8 + j, 12, 16); }
            }
        }
        ld_ug(7);
        ship(7 - R.value); ship(6 + R.value);
        };
        if (rank) stairs(std::integral_constant<int, 1>()); else stairs(std::integral_constant<int, 0>());
        if ((warp & 3) == 0) TSTAMP(14 + (warp >> 2)); else TSTAMP(21 + warp);
    }
}

constexpr int SF_WD = 73728;
constexpr int SF_RED = 49152;
constexpr int MU_HALF = 640, MU_STRIDE = 1344, SM_RAW = 98304, SM_UT = SM_RAW + 16384, SM_G = SM_UT + 16 * MU_STRIDE, SM_Y = 196608, SM_FT = SM_Y + 17024, SM_KT = 138880, SM_KW = SM_G - 49152;
constexpr int SF_XS = 221184;
constexpr int SF_MISC = SF_XS + 8 * 1168;
constexpr int SF_KG = SF_MISC - 10 * KG_STAGE;
constexpr int SF_WR = SF_KG - 2304;
constexpr int FB_X = 64, FB_KDONE = 72, FB_KEYS = 80, FB_FREE = 88  , FB_W = 104, FB_D = FB_W + 72, FB_MU = FB_D + 96, FB_FAR = FB_MU - 16, FB_MG = FB_MU + 8, FB_MT = FB_MU + 16  , FS_PART = 512, FS_TOK = 896, FS_BM = 1024;
enum { BAR_R = 7, BAR_GU = 8, BAR_RED = 9, BAR_R2 = 10, BAR_G = 12  , BAR_M = 15 };
static_assert(SF_KG % 128 == 0 && NPRE <= 8 && SM_KT + 4 * 2112 <= 147456 && SM_G + MU_STRIDE <= SF_WR - 4 * 9216 && SM_KW + 6 * 2112 >= SM_RAW && SM_KW + 12 * 2112 <= SM_UT, "layout");

__device__ __forceinline__ constexpr int box_no(int i) { return (0x987610ba5432ull >> (4 * i)) & 15; }
__device__ __forceinline__ int role(int b) { b -= NCONV; return b < NX ? b : 18 + (b >> 1) + 12 * (b & 1); }
__device__ __forceinline__ int mini_ch0(int f) { return 48 * f - (f < NW ? 1696 : 2304); }

__device__ __forceinline__ void ffn_front(const Params& p, const CUtensorMap* maps, uint32_t sb, int warp, int lane, int f, unsigned epoch) {
    const unsigned t0 = clock32();
    const int g = lane >> 2, t = lane & 3, mi = lane >> 3, r8 = lane & 7;
    const bool isx = f < NX;
    const int nrw = f < 52 ? 4 : 6, r0 = f < 52 ? 32 * f : 48 * f - 832;
    const int rw = warp < 12 ? 13 - warp : warp ^ (warp < 14 ? 10 : 15);
    const uint32_t bar_row = sb + SF_MISC  , bar_x = bar_row + FB_X;
    const uint32_t s_part = bar_row + FS_PART  , s_tok = bar_row + FS_TOK  ;
    const uint32_t rows = sb + SF_WR - 9216 * (rw + 1) - (rw & 4) * ((SF_WR - 6 * 9216) / 4);
    {
#pragma unroll 1
        for (int i = warp < 10 ? 30 : warp - 10; i < 30; i += 6) if (elect()) mbar_init(bar_x + 8 * i, i == 1 ? 4 + (f < NW) : i < 27 ? 1 : i == 27 ? 2 : 8);
        const uint32_t bytes = rw < 6 ? 9216 : 1152, dst = rw < 6 ? rows : sb + SF_WR + (rw & 1) * 1152;
        const __nv_bfloat16* src = rw < 6 ? p.u + (size_t)(r0 + 8 * rw) * DM : (rw & 1) ? p.gatew : p.wr;
        if (elect()) { mbar_init(bar_row + 8 * rw, 1); mbar_fence(); mbar_expect(bar_row + 8 * rw, bytes); }
        if (warp == 13) { sts32(s_part + 64 + lane * 4, 0); sts32(bar_row + FS_BM + lane * 4, 0); }
        bar_sync(0, NTHR);
        if (!isx) asm volatile("barrier.cluster.arrive.relaxed.aligned;" ::: "memory");
        if (rw < nrw) until(t0, RDELAY);
        if (rw < nrw || rw >= 6) { if (elect()) bulk_g2s(dst, src, bytes, bar_row + 8 * rw); }
    }
    uint4* const kdst = p.s->keys + (lane >> 1) * 128 + 2 * f + (lane & 1);
    if (warp == 15) TSTAMP(1);

    if (warp == 12) {
        if (lane < 22) mbar_expect(bar_row + FB_W + 8 * lane, lane < 9 ? 24576 : isx ? 12288 : lane < 20 ? 2048 : 16384);
        if (elect()) { prefetch_map(maps + 1); prefetch_map(maps + 2); prefetch_map(maps + (isx ? 3 : 5)); }
        unsigned tb = t0 + WDELAY;
        auto pieces = [&](int n, int end, uint32_t dst) {
#pragma unroll 1
            for (; n < end; n++, dst += 12288) {
                until(tb, 0); tb += WGAP;
                if (elect()) tma3d(dst, maps + 1 + (n & 1), 0, 64 * (n >> 1), 3 * f, bar_row + FB_W + 8 * (n >> 1));
            }
        };
        if (!isx) {
#pragma unroll 1
            for (int k = 0; k <= (f >= NW); k++) { until(t0, MDELAY + k * MGAP); if (elect()) tma4d(sb + SM_RAW - 49152 * k, maps + 5, mini_ch0(f) + 16 * k, 0, 0, 0, bar_row + FB_MU - 8 * k); }
            if (f >= NW) return;
        }
#pragma unroll 1
        for (int i = 0; i < 4; i++) {
            if (i == 1) { mbar_wait(bar_row + FB_KEYS); mbar_wait(bar_row + FB_KDONE); tb = clock32() + RESUME; }
            if (i == 3) mbar_wait(bar_row + FB_FREE);
            const int n = ((0x0c080000 + NPRE * 256) >> (8 * i)) & 255;
            pieces(n, ((0x120c0800 + NPRE) >> (8 * i)) & 255, sb + 12288 * (((0x000c0000 + NPRE * 256) >> (8 * i)) & 255));
        }
        TSTAMP(12);
        if (isx) {
#pragma unroll 1
            for (int i = 0; i < 12; i++) {
                const int n = box_no(i);
                if (i == 6) mbar_wait(bar_row + FB_FREE + 8);
                until(tb, 0); tb += DGAP;
                if (elect()) tma2d(sb + SF_WD + n * 12288, maps + 3, 32 * (f >> 1), 2304 * (f & 1) + 192 * n, bar_row + FB_D + 8 * n);
            }
            TSTAMP(13);
        }
    } else if (warp == 13) {
        const uint32_t tag = key_tag(epoch), par = (epoch & 1) ? 0u : 0x8000u;
        stg128(kdst, 0, 0, 0, 0);
        if (lane < 8 && isx && !(f & 1)) st_rlx32(&p.s->sel[32 * f + lane], 0);
        bar_sync(BAR_R, 32 * (nrw + 1));
        TSTAMP(3);
        {
            const uint32_t sg = fresh(s_part) + 192 + lane * 4;
            const uint32_t gb = pack_bf16(sigmoidf_(rbf(__uint_as_float(lds32(sg)))), sigmoidf_(rbf(__uint_as_float(lds32(sg + 128))))) | par | (par << 16);
            asm volatile("st.relaxed.gpu.global.u16 [%0], %1;" :: "l"(p.s->gate + r0 + lane), "h"((unsigned short)gb) : "memory");
            if (nrw > 4 && lane < 16) asm volatile("st.relaxed.gpu.global.u16 [%0], %1;" :: "l"(p.s->gate + r0 + 32 + lane), "h"((unsigned short)(gb >> 16)) : "memory");
        }
        bar_sync(BAR_R2, 32 * (nrw + 1));
        {
            const uint4 v = lds128(fresh(s_tok) + (lane & 1) * 16);
            asm volatile("st.relaxed.gpu.global.v4.u32 [%0], {%1,%2,%3,%4};" :: "l"(kdst), "r"(v.x | tag), "r"(v.y | tag), "r"(v.z | tag), "r"(v.w | tag) : "memory");
        }
        TSTAMP(4);
        if (lane == 0) { mbar_arrive(bar_row + FB_KEYS); mbar_expect(bar_x, 8 * 1152); }
        if (f >= NW) return;
        mbar_wait(bar_row + FB_KDONE);
        uint32_t k[16];
        const uint4* src = p.s->keys + (f & 15) * 128 + lane;
#pragma unroll 1
        for (int it = 0;; it++) {
            uint32_t bad = 0;
#pragma unroll
            for (int i = 0; i < 4; i++) {
                const uint4 x = ld_rlx128(src + (i < 3 || lane < 24 ? 32 * i : 64));
                k[i] = x.x; k[4 + i] = x.y; k[8 + i] = x.z; k[12 + i] = x.w;
                bad |= x.x ^ tag;
            }
            const bool ok = __all_sync(0xffffffffu, (bad & 0xf800u) == 0);
            if (ok) break;
            if (it > (1 << 20)) give_up();
        }
        TSTAMP(5);
        uint32_t key = 0, m = __reduce_max_sync(0xffffffffu, max(max(k[0], k[1]), max(k[2], k[3])));
#pragma unroll 2
        for (int r = 0; r < 8; r++) {
            bool pop[4];
#pragma unroll
            for (int i = 0; i < 4; i++) { pop[i] = k[i] == m; k[i] = pop[i] ? k[4 + i] : k[i]; }
            const uint32_t mn = __reduce_max_sync(0xffffffffu, max(max(k[0], k[1]), max(k[2], k[3])));
            if (elect()) bulk_g2s(sb + SF_XS + r * 1168, p.u + (size_t)key_row(m) * DM, 1152, bar_x);
#pragma unroll
            for (int i = 0; i < 4; i++) { k[4 + i] = pop[i] ? k[8 + i] : k[4 + i]; k[8 + i] = pop[i] ? k[12 + i] : k[8 + i]; k[12 + i] = pop[i] ? 0 : k[12 + i]; }
            if (r8 == r) key = m;
            m = mn;
        }
        const int row = key_row(key);
        sts32(s_tok + r8 * 8, row);
        TSTAMP(6);
        if (isx) {
            if (!(f & 1)) {
                __nv_bfloat16* o = p.out + (size_t)row * DM + 16 * f + 8 * mi;
                asm volatile("st.relaxed.gpu.global.v4.u32 [%0], {%1,%1,%1,%1};" :: "l"(o), "r"(0) : "memory");
                if (__any_sync(0xffffffffu, ld_rlx32(o) != 0)) give_up();
                if (lane < 8) st_rlx32(&p.s->sel[32 * f + lane], key);
            } else wait_sel(p, f >> 1, r8, tag);
            uint32_t gb;
#pragma unroll 1
            for (int it = 0;; it++) {
                asm volatile("ld.relaxed.gpu.global.u16 %0, [%1];" : "=r"(gb) : "l"(p.s->gate + row) : "memory");
                gb ^= par;
                if (!(gb & 0x8000u)) break;
                if (it > (1 << 20)) give_up();
            }
            const uint32_t rb = key ^ 0x80000000u, rv = (rb ^ (((int)rb >> 31) & 0x7fff0000u)) & 0xffff0000u;
            sts32(s_tok + r8 * 8 + 4, __float_as_uint(rbf(1.0f - bf_lo(gb)) * rbf(sigmoidf_(__uint_as_float(rv)))));
            __syncwarp();
            TSTAMP(7);
            bar_arrive(BAR_RED, 416);
        }
    } else {
        if (rw < nrw) {
            float c[3][4];
#pragma unroll
            for (int i = 0; i < 3; i++) { c[i][0] = c[i][1] = c[i][2] = c[i][3] = 0.f; }
            mbar_wait(bar_row + 48); mbar_wait(bar_row + 56);
            const uint32_t b = fresh(sb + SF_WR) + (g & 1) * 1152 + (g >> 2) * 64 + t * 16 + (g & 2) * 2;
            uint32_t w[18][2];
#pragma unroll
            for (int kb = 0; kb < 18; kb++) { const uint32_t o = ((kb & 1) ? b ^ 64 : b) + 128 * (kb >> 1); w[kb][0] = lds32(o); w[kb][1] = lds32(o + 8); }
            mbar_wait(bar_row + 8 * rw);
            if (warp == 15) TSTAMP(2);
            const uint32_t a = fresh(rows) + g * 1152 + (g & 1) * 64 + t * 16;
#pragma unroll
            for (int kb = 0; kb < 18; kb++) {
                const uint4 x = lds128(((kb & 1) ? a ^ 64 : a) + 128 * (kb >> 1));
                mma_bf(c[kb % 3], x.x, x.y, x.z, x.w, w[kb][0], w[kb][1]);
            }
            const float sr = c[0][0] + c[1][0] + c[2][0] + __shfl_down_sync(0xffffffffu, c[0][2] + c[1][2] + c[2][2], 1);
            const float sg = c[0][1] + c[1][1] + c[2][1] + __shfl_down_sync(0xffffffffu, c[0][3] + c[1][3] + c[2][3], 1);
            const uint32_t rb = pack_bf16(0.f, sr);
            if (t == 2 * (g & 1)) {
                sts32(s_part + (8 * rw + g) * 4, (rb ^ (((int)rb >> 31) & 0x7fff0000u) ^ 0x80000000u) | (uint32_t)(2047 - r0 - 8 * rw - g));
                sts32(s_part + 192 + (8 * rw + g) * 4, __float_as_uint(sg));
            }
            __syncwarp();
            bar_sync(BAR_R, 32 * (nrw + 1));
            const uint32_t sk = fresh(s_part), kk = lds32(sk + (8 * rw + r8) * 4);
            int n = 0;
#pragma unroll
            for (int i = 0; i < 3; i++) { const uint4 v = lds128(sk + mi * 48 + 16 * i); n += (v.x > kk) + (v.y > kk) + (v.z > kk) + (v.w > kk); }
            n += __shfl_xor_sync(0xffffffffu, n, 8); n += __shfl_xor_sync(0xffffffffu, n, 16);
            if (n < 8) sts32(s_tok + 4 * n, kk);
            __syncwarp();
            bar_arrive(BAR_R2, 32 * (nrw + 1));
        }
    }
}

__device__ __forceinline__ void ffn_work(const Params& p, uint32_t sb, int warp, int lane, int f, unsigned epoch) {
    const int g = lane >> 2, t = lane & 3, mi = lane >> 3, r8 = lane & 7;
    const bool isx = f < NX;
    const uint32_t bar_x = sb + SF_MISC + FB_X, bar_free = sb + SF_MISC + FB_FREE, bar_w = sb + SF_MISC + FB_W, bar_d = sb + SF_MISC + FB_D, s_tok = sb + SF_MISC + FS_TOK;
    uint32_t fr[24][4];
    auto pin = [&] {
#pragma unroll
        for (int i = 0; i < 24; i += 8) asm volatile("" :: "r"(fr[i][0]), "r"(fr[i + 1][0]), "r"(fr[i + 2][0]), "r"(fr[i + 3][0]), "r"(fr[i + 4][0]), "r"(fr[i + 5][0]), "r"(fr[i + 6][0]), "r"(fr[i + 7][0]) : "memory");
    };
    {
        const int j = (unsigned)(warp - 4) < 6, w = warp - (j ? 4 : warp < 4 ? 0 : 6);
        float ag[2][4], au[2][4];
#pragma unroll
        for (int i = 0; i < 2; i++) { ag[i][0] = ag[i][1] = ag[i][2] = ag[i][3] = 0.f; au[i][0] = au[i][1] = au[i][2] = au[i][3] = 0.f; }
        const uint32_t wb = sb + (w >> 1) * 4096 + (r8 + 8 * (mi >> 1)) * 64 + (((2 * (w & 1) + (mi & 1)) ^ (r8 >> 1)) << 4);
        const uint32_t xb = sb + SF_XS + r8 * 1168 + mi * 16;
        auto load = [&](int i, int n, int place) {
            mbar_wait(bar_w + 8 * n);
            const uint32_t wk = fresh(wb) + place * 24576;
#pragma unroll
            for (int s = 0; s < 4; s++) { ldsm4t(fr[8 * i + s], wk + 1024 * s); ldsm4t(fr[8 * i + 4 + s], wk + 1024 * s + 12288); }
        };
        auto mul = [&](int i, uint32_t xk) {
            uint32_t x[2][4];
            ldsm4(x[0], xk); ldsm4(x[1], xk + 64);
#pragma unroll
            for (int s = 0; s < 4; s++) {
                const uint32_t (&a)[4] = fr[8 * i + s], (&b)[4] = fr[8 * i + 4 + s];
                mma_bf(ag[s & 1], a[0], a[1], a[2], a[3], x[s >> 1][2 * (s & 1)], x[s >> 1][2 * (s & 1) + 1]);
                mma_bf(au[s & 1], b[0], b[1], b[2], b[3], x[s >> 1][2 * (s & 1)], x[s >> 1][2 * (s & 1) + 1]);
            }
        };
#pragma unroll
        for (int i = 0; i < 3; i++) load(i, 3 * j + i, (i ? 5 : 3) * j + i);
        pin();
        bar_sync(BAR_G + j, 192);
        if (w == 0 && lane == 0) mbar_arrive(bar_free + 8 * j);
        mbar_wait(bar_x);
        if (warp == 0) TSTAMP(8);
        {
            const uint32_t xk = fresh(xb) + 384 * j;
#pragma unroll
            for (int i = 0; i < 3; i++) { mul(i, (i ? fresh(xk) : xk) + 128 * i); if (i == 0) { asm volatile("" :: "f"(ag[0][0]), "f"(ag[1][0]), "f"(au[0][0]), "f"(au[1][0])); sts32(s_tok + 64, clock32()); } }
        }
#pragma unroll 1
        for (int n = 6 + j; n < 9; n += 2) { load(0, n, n - 6); mul(0, fresh(xb) + 128 * n); }
#pragma unroll
        for (int c = 0; c < 4; c++) { ag[0][c] += ag[1][c]; au[0][c] += au[1][c]; }
        if (j) {
            sts128(wb + 24576, __float_as_uint(ag[0][0]), __float_as_uint(ag[0][1]), __float_as_uint(ag[0][2]), __float_as_uint(ag[0][3]));
            sts128(wb + 25600, __float_as_uint(au[0][0]), __float_as_uint(au[0][1]), __float_as_uint(au[0][2]), __float_as_uint(au[0][3]));
        }
        bar_sync(BAR_GU, 384);
        if (!j) {
            const uint32_t sf = fresh(wb);
            const uint4 g1 = lds128(sf + 24576), u1 = lds128(sf + 25600);
            const uint32_t gs[4] = {g1.x, g1.y, g1.z, g1.w}, us[4] = {u1.x, u1.y, u1.z, u1.w};
            if (warp == 0) TSTAMP(9);
            float h[4];
#pragma unroll
            for (int c = 0; c < 4; c++) {
                const float gv = rbf(ag[0][c] + __uint_as_float(gs[c]));
                h[c] = rbf(gv * sigmoidf_(gv)) * rbf(au[0][c] + __uint_as_float(us[c]));
            }
            uint32_t h0, h1;
            asm("movmatrix.sync.aligned.m8n8.trans.b16 %0, %1;" : "=r"(h0) : "r"(pack_bf16(h[0], h[1])));
            asm("movmatrix.sync.aligned.m8n8.trans.b16 %0, %1;" : "=r"(h1) : "r"(pack_bf16(h[2], h[3])));
            if (h0 == 0) h0 = 0x8000u;
            asm volatile("{ .reg .b64 v; mov.b64 v, {%1, %2}; st.relaxed.gpu.global.b64 [%0], v; }" :: "l"(p.s->h + ((epoch & 1) * 288 + 6 * f + w) * 32 + lane), "r"(h0), "r"(h1) : "memory");
        }
        if (isx) {
            if (warp == 0) TSTAMP(10);
            const uint2* hsrc = p.s->h + ((epoch & 1) * 288 + 144 * (f & 1) + warp) * 32 + lane;
            const uint32_t wd = sb + SF_WD + warp * 1024 + (r8 + 8 * (mi >> 1)) * 64 + (((mi & 1) ^ (r8 >> 1)) << 4), we = wd ^ 32;
            uint2 hb[12];
            auto ldh = [&](int i) { asm volatile("ld.relaxed.gpu.global.v2.u32 {%0, %1}, [%2];" : "=r"(hb[i].x), "=r"(hb[i].y) : "l"(hsrc + 384 * box_no(i)) : "memory"); };
            auto ldw = [&](int i) { mbar_wait(bar_d + 8 * box_no(i)); ldsm4t(fr[2 * i], fresh(wd) + 12288 * box_no(i)); ldsm4t(fr[2 * i + 1], fresh(we) + 12288 * box_no(i)); };
#pragma unroll
            for (int i = 0; i < DPA; i++) ldw(i);
#pragma unroll
            for (int i = 0; i < 12; i++) ldh(i);
#pragma unroll
            for (int i = DPA; i < DPB; i++) ldw(i);
#pragma unroll
            for (int i = 0; i < DPB; i++) asm volatile("" :: "r"(fr[2 * i][0]), "r"(fr[2 * i + 1][0]) : "memory");
#pragma unroll 1
            for (int it = 0;; it++) {
                bool again = false;
#pragma unroll
                for (int s = 0; s < 12; s += 2) if (__any_sync(0xffffffffu, min(hb[s].x, hb[s + 1].x) == 0)) { ldh(s); ldh(s + 1); again = true; }
                if (!again) break;
                if (it > (1 << 16)) give_up();
            }
            if (warp == 0) TSTAMP(11);
            float ad[2][2][4];
#pragma unroll
            for (int i = 0; i < 4; i++) { ad[i >> 1][i & 1][0] = ad[i >> 1][i & 1][1] = ad[i >> 1][i & 1][2] = ad[i >> 1][i & 1][3] = 0.f; }
#pragma unroll
            for (int i = 0; i < 12; i++) {
                if (i >= DPB) ldw(i);
                if (i == 11 && warp == 9) TSTAMP(14);
#pragma unroll
                for (int c = 0; c < 2; c++) mma_bf(ad[c][i & 1], fr[2 * i + c][0], fr[2 * i + c][1], fr[2 * i + c][2], fr[2 * i + c][3], hb[i].x, hb[i].y);
                if (i >= DPB - 1) asm volatile("" :: "f"(ad[0][i & 1][0]), "f"(ad[1][i & 1][0]) : "memory");
            }
            const uint32_t rd = sb + SF_RED + warp * 1152 + (72 * t + g) * 4;
#pragma unroll
            for (int i = 0; i < 8; i++) sts32(rd + (i >> 2) * 64 + (i & 1) * 144 + ((i >> 1) & 1) * 32, __float_as_uint(ad[i >> 2][0][i & 3] + ad[i >> 2][1][i & 3]));
            bar_sync(BAR_RED, 416);
            if (warp < 4) {
                const int tid = 32 * warp + lane;
                const uint32_t rs = fresh(sb + SF_RED) + (tid >> 4) * 144 + (tid & 15) * 8;
                const uint2 tk = lds64(fresh(s_tok) + (tid >> 4) * 8);
                float x = 0.f, y = 0.f;
#pragma unroll
                for (int w = 0; w < 12; w++) { const uint2 v = lds64(rs + w * 1152); x += __uint_as_float(v.x); y += __uint_as_float(v.y); }
                asm volatile("red.relaxed.gpu.global.add.noftz.bf16x2 [%0], %1;" :: "l"(p.out + (size_t)tk.x * DM + 32 * (f >> 1) + 2 * (tid & 15)),
                             "r"(pack_bf16(x * __uint_as_float(tk.y), y * __uint_as_float(tk.y))) : "memory");
            }
            if (warp == 0) { TSTAMP(15); TFLUSH(); }
            asm volatile("exit;"); __builtin_unreachable();
        }
    }
}

__device__ __forceinline__ void fetch_k(const uint4* src, uint64_t (&v)[6], uint32_t a, uint32_t b) {
    asm volatile("{ .reg .pred p; setp.eq.u32 p, %7, %8; @p ld.relaxed.gpu.global.v2.u64 {%0,%1}, [%6]; @p ld.relaxed.gpu.global.v2.u64 {%2,%3}, [%6 + 512]; @p ld.relaxed.gpu.global.v2.u64 {%4,%5}, [%6 + 1024]; }"
                 : "+l"(v[0]), "+l"(v[1]), "+l"(v[2]), "+l"(v[3]), "+l"(v[4]), "+l"(v[5]) : "l"(src), "r"(a), "r"(b));
}
__device__ __forceinline__ uint32_t mini_conv(const Params& p, uint32_t sb, int warp, int lane, int f, unsigned epoch, uint64_t (&v)[6]) {
    const int g = lane >> 2, t = lane & 3, mi = lane >> 3, r8 = lane & 7;
    const uint32_t fb = sb + SF_MISC, kt = sb + (warp >= 12 ? SM_KT - 12 * 2112 : f < NW ? SM_KW + 2 * 2112 : SM_KW) + warp * 2112;
    const bool ism = f >= NW;
    const uint32_t* const sel = &p.s->sel[((mini_ch0(f) + (ism ? 2 * (warp & 8) : 0)) >> 5) * 64 + r8];
    uint32_t seq = 128, key;
    const uint4* src = p.s->kp + lane;
    auto hi = [&](int i) { return (uint32_t)(v[i] >> 32); };
    if (f >= (warp < 4 ? NW : NX)) {
    {
        const uint32_t c = 68 + (warp & 3) + 2 * (warp & 12), y = ((uint32_t)((warp < 8 ? 0xe066806400000000ull : 0x5a6e00680080e26cull) >> ((8 * warp) & 48)) & 0xffff) + (warp < 14 ? 0 : 0x6a0000);
        seq = !ism ? y + (warp & 1) * ((y >> 6) & 0x10101) : warp < 14 ? 0x101 * c - 0x400 : c;
        src += (48 * (f - (ism ? NW : NX)) + (seq & 63)) * 96;
    }
    if (seq & 64) {
        if (seq & 4) {
            const int q = (seq & 3) + ((seq >> 1) & 4);
            const uint32_t ab = sb - 3072 * (seq & 16), d = ab + SM_UT + g * MU_STRIDE + (8 + 4 * q + t) * 16;
            sts128(ab + SM_UT + (2 * q + (mi >> 1)) * MU_STRIDE + (mi & 1) * MU_HALF + r8 * 16, 0, 0, 0, 0);
            mbar_wait(fb + FB_MU - (seq & 16) / 2);
            if (warp == 15) TSTAMP(16);
            const uint32_t a = fresh(ab + SM_RAW) + q * 2048 + (8 * mi + 4 * (r8 & 1) + (r8 >> 1)) * 32 + ((r8 & 1) << 4);
            uint32_t x[4][4];
#pragma unroll
            for (int i = 0; i < 4; i++) ldsm4t(x[i], (i & 2 ? a ^ 16 : a) + 1024 * (i & 1));
#pragma unroll
            for (int i = 0; i < 4; i++) sts128(d + (i & 1) * MU_HALF + (i & 2) * 4 * MU_STRIDE, x[i][0], x[i][1], x[i][2], x[i][3]);
            __syncwarp();
            if (lane == 0) mbar_arrive(fb + FB_MT + (seq & 16) / 2);
        }
        mbar_wait(fb + FB_KDONE);
        fetch_k(src, v, warp < 4, 0);
        if ((warp | 2) == 7) { fetch_gates(p, (warp >> 1) & 1, lane, epoch, sb + SM_G + (lane & 1) * MU_HALF); __syncwarp(); if (lane == 0) mbar_arrive(fb + FB_MG); }
        if (warp >= 8) {
            mbar_wait(fb + FB_KEYS); mbar_wait(fb + FB_MT);
            if (ism) {
                asm volatile("barrier.cluster.wait.aligned; fence.release.sync_restrict::shared::cta.cluster;" ::: "memory");
                if (lane == 0) asm volatile("mbarrier.arrive.relaxed.cluster.shared::cluster.b64 _, [%0];" :: "r"(mapa(fb + FB_MT + 8, 0)) : "memory");
            }
        }
        if (warp == TW) TSTAMP(17);
    }
    }
    const uint32_t lo = (mi & 1) * MU_HALF + (8 + col(r8)) * 16 + (mi >> 1) * 128;
#pragma unroll 1
    do {
        const int c = seq & 63;
        const bool far = !ism && (seq & 16);
        const uint32_t ab = sb - 3072 * (c & 16);
        uint32_t ut = ab + SM_UT + (c & 15) * MU_STRIDE;
        if (seq & 64) {
        if (far) {
            mbar_wait_cluster(fb + FB_MT + 8);
            const uint32_t ru = mapa(ut, 1) + lane * 16;
            ut = sb + SM_FT + (c & 3) * 1536;
            uint4 x[3];
#pragma unroll
            for (int i = 0; i < 3; i++) asm volatile("ld.shared::cluster.v4.u32 {%0,%1,%2,%3}, [%4];" : "=r"(x[i].x), "=r"(x[i].y), "=r"(x[i].z), "=r"(x[i].w) : "r"(ru + 512 * i) : "memory");
#pragma unroll
            for (int i = 0; i < 3; i++) sts128(ut + lane * 16 + 512 * i, x[i].x, x[i].y, x[i].z, x[i].w);
        } else mbar_wait(fb + FB_MT + (seq & 16) / 2);
#pragma unroll 1
        for (int it = 0; !__all_sync(0xffffffffu, ((hi(1) ^ k_tag(epoch)) | (hi(3) ^ k_tag(epoch)) | (hi(5) ^ k_tag(epoch)) | ((uint32_t)v[5] & p.zero)) < 65536); it++) {
            fetch_k(src, v, 0, 0);
            if (it > (1 << 20)) give_up();
        }
        sts128(kt + t * 16, 0, 0, 0, 0);
        if (warp == TW) TSTAMP(seq >> 8 ? 7 : 10);
        const uint32_t w[12] = {(uint32_t)v[0], hi(0), (uint32_t)v[1], (uint32_t)v[2], hi(2), (uint32_t)v[3], (uint32_t)v[4], hi(4), 0, 0, 0, 0};
        k_tables<false>(fresh(kt), fresh(lane), w);
        }
        __syncwarp();
        if (seq & 128) ffn_work(p, sb, warp, fresh(lane), f, epoch);
        if (!(seq & 64)) return 0;
        const uint32_t kb = fresh(kt) + (16 + g - 2 * t) * 4, ub = fresh(ut) + lo;
        const uint32_t yd = ab + SM_Y + (c & 15) * 1056 + (c & 8) * 8 + lane * 16;
        uint32_t kp = kb, u1 = ub;
        if (warp == TW && !(seq >> 8)) TSTAMP(13);
        seq >>= 8;
        src += ((int)(seq & 63) - c) * 96;
#pragma unroll
        for (int i = 0; i < 6; i++) v[i] = 0;
        key = 0;
        float acc[6][4];
#pragma unroll
        for (int i = 0; i < 6; i++) { acc[i][0] = acc[i][1] = acc[i][2] = acc[i][3] = 0.f; }
        uint32_t a[4][4], b[2][2][4];
        auto lda = [&](int j, int o) { const uint32_t x = kp + 64 * o + 512 * j; a[j][2] = o ? a[j][1] ^ p.zero : lds32((kp ^ p.zero) + 512 * j - 32); a[j][0] = lds32(x); a[j][1] = lds32(x + 32); a[j][3] = a[j][0] ^ p.zero; };
        auto ldb = [&](int s, int o) { ldsm4(b[s][0], u1 - 16 * o); ldsm4(b[s][1], u1 + 256 - 16 * o); };
        ldb(0, 0);
#pragma unroll
        for (int j = 0; j < 4; j++) lda(j, 0);
#pragma unroll
        for (int s = 0; s < 8; s++) {
            if (s == 4) {
                const uint32_t e = seq | (__float_as_uint(acc[0][0]) & p.zero);
                fetch_k(src, v, e & 64, 64);
                asm volatile("{ .reg .pred p; setp.eq.u32 p, %2, 0; @p ld.relaxed.gpu.global.u32 %0, [%1]; }" : "+r"(key) : "l"(sel), "r"(e));
            }
            if (s < 7) ldb(~s & 1, s + 1);
#pragma unroll
            for (int i = 0; i < 4; i++) {
                const int j = (i >> 1) + 2 * (i & 1);
#pragma unroll
                for (int mu = 3 - j; mu >= 0; mu--) mma_bf(acc[j + mu + (j & 2)], a[j][0], a[j][1], a[j][2], a[j][3], b[s & 1][mu >> 1][2 * (mu & 1)], b[s & 1][mu >> 1][2 * (mu & 1) + 1]);
                if (s < 7) lda(j, s + 1);
            }
        }
        if (warp == TW && !seq) TSTAMP(14);
        mbar_wait(fb + FB_MG);
#pragma unroll
        for (int e = 0; e < 4; e++) { acc[2][e] += acc[4][e]; acc[3][e] += acc[5][e]; }
        uint32_t ug[4][4];
#pragma unroll
        for (int i = 0; i < 2; i++) { ldsm4t(ug[i], ub + 256 * i); ldsm4t(ug[2 + i], fresh(sb + SM_G) + lo + 256 * i); }
#pragma unroll
        for (int i = 0; i < 2; i++) {
            uint32_t (&u)[4] = ug[i], (&gg)[4] = ug[2 + i];
#pragma unroll
            for (int e = 0; e < 4; e++) u[e] = gmix(gg[e], acc[2 * i + (e >> 1)][2 * (e & 1)], acc[2 * i + (e >> 1)][2 * (e & 1) + 1], u[e]);
        }
        if (far) for (int i = 0; i < 2; i++) st_async128(mapa(yd, 1) + 512 * i, ug[i][0], ug[i][1], ug[i][2], ug[i][3], mapa(fb + FB_FAR, 1));
        else for (int i = 0; i < 2; i++) sts128(yd + 512 * i, ug[i][0], ug[i][1], ug[i][2], ug[i][3]);
        __syncwarp();
        if (warp == TW) TSTAMP(18 + (seq != 0));
    } while (seq);
    if (warp >= 12) TSTAMP(12 + warp);
    return key;
}
__device__ __forceinline__ void mini_out(const Params& p, const CUtensorMap* maps, uint32_t sb, int warp, int lane, int f, unsigned epoch, uint32_t key) {
    const int g = lane >> 2, t = lane & 3, mi = lane >> 3, r8 = lane & 7;
    const uint32_t fb = sb + SF_MISC;
    const bool ism = f >= NW;
    const int ch0 = mini_ch0(f);
    const int k = ism ? warp >> 3 : 0;
    uint32_t first = 1;
    if (lane == 0) asm volatile("atom.shared.exch.b32 %0, [%1], 1;" : "=r"(first) : "r"(fb + FS_BM + 64 + 4 * k) : "memory");
    if (!__all_sync(0xffffffffu, first)) {
        if (elect()) prefetch_map(maps + 4);
        const int row = key_row(wait_sel(p, (ch0 + 16 * k) >> 5, r8, key_tag(epoch), key));
        if (row < 512) asm volatile("red.shared.or.b32 [%0], %1;" :: "r"(fb + FS_BM + (row >> 5) * 4), "r"(1u << (row & 31)) : "memory");
        if (k) mbar_wait_cluster(fb + FB_FAR);
    }
    const int m = warp & 7, dr = 128 * (g >> 2) + 16 * (t >> 1) + 64 * (g & 1) + 8 * ((g >> 1) & 1);
    const uint32_t y = SM_Y + ((r8 >> 1) & 1) * 8512 + (2 * mi + (r8 & 1)) * 1056 + (2 * m + (r8 >> 2)) * 16;
    const uint32_t so = (g & 2) * 256 + (g >> 2) * 128 + r8 * 16;
    bar_sync(BAR_M - k, ism ? 256 : NTHR);
#pragma unroll 1
    for (int h = ism ? 0 : warp >> 3;; h++) {
        const int r0 = 256 * h + 32 * (m & 1) + (m >> 1), row = r0 + dr;
        const uint32_t bm = lds32(fresh(fb) + FS_BM + (row >> 5) * 4) >> (row & 31), ab = fresh(sb - 49152 * k + 512 * h), stg = ab + SM_UT + 2048 * m + 512 * h;
        uint32_t x[2][4];
        ldsm4t(x[0], ab + y); ldsm4t(x[1], ab + y + 256);
        if (warp == 0 && x[0][0] != 0x12345) TSTAMP(28);
        if (__any_sync(0xffffffffu, bm & 0x11u)) {
#pragma unroll
            for (int i = 0; i < 2; i++) store_or_add(p.out + (size_t)(row + 4 * i) * DM + ch0 + 16 * k + 8 * (t & 1), x[i], bm & (1u << (4 * i)));
        } else {
#pragma unroll
            for (int i = 0; i < 2; i++) sts128(stg + so + 256 * i, x[i][0], x[i][1], x[i][2], x[i][3]);
            asm volatile("fence.proxy.async.shared::cta;" ::: "memory");
            __syncwarp();
            if (elect()) store_rows(maps + 4, stg, ch0 + 16 * k, r0);
        }
        if (h >= ism) break;
    }
    if (elect()) { asm volatile("cp.async.bulk.commit_group;" ::: "memory"); asm volatile("cp.async.bulk.wait_group.read 0;" ::: "memory"); }
    if (warp == 8) TSTAMP(11);
    if (warp == 0) { TSTAMP(15); TFLUSH(); }
}

constexpr int SMEM_BYTES = 232448;
static_assert(SF_MISC + 1152 <= 232192, "layout");

struct Maps { CUtensorMap m[6]; };

__global__ void __cluster_dims__(2, 1, 1) __launch_bounds__(NTHR, 1)
fused_kernel(const Params p, const __grid_constant__ Maps maps) {
    extern __shared__ __align__(1024) uint8_t smem_raw[];
    uint32_t q[8];
    {
        const int b = role(blockIdx.x), x = threadIdx.x, rc = 5 * b + (b & ~3) + 4 + (x >> 6);
        const int cv = (unsigned)b < NW ? 0 : -1, ca = (b < 0 ? 8 * b + DM : 48 * b - 2300) + ((x >> 5) & 3), cb = 2 * rc - (rc & 3) + 4;
        const uint32_t ch = (ca & cv) | (cb & ~cv), o = NST * ch + 2 * ((x & 31) + ((x >> (cv & 2)) & 32));
        const bool c = x < (cv ? 256 : 320);
        q[6] = ldg16_if(c, p.logdt + ch);
        q[2] = ldg32_if(c, p.Bre + o); q[3] = ldg32_if(c, p.Bim + o); q[4] = ldg32_if(c, p.Cre + o); q[5] = ldg32_if(c, p.Cim + o); q[0] = ldg32_if(c, p.Are + o); q[1] = ldg32_if(c, p.Aim + o);
        q[7] = ldg16_if(c, p.Dskip + ch);
    }
    const unsigned epoch = ld_rlx32(&p.s->epoch[blockIdx.x * 16 + (threadIdx.x >> 5)]);
    const uint32_t sb = __shfl_sync(0xffffffffu, smem_u32(smem_raw), 0);
    const int warp = __shfl_sync(0xffffffffu, threadIdx.x >> 5, 0), bid = __shfl_sync(0xffffffffu, blockIdx.x, 0);
    const int lane = __shfl_sync(0xffffffffu, threadIdx.x & 31, threadIdx.x);
    const bool conv = bid < NCONV;
    const int f = role(bid);
    uint32_t w[12];
    uint64_t v[6];
    const bool four = (unsigned)f >= NW;
    if (warp < (four ? 8 : 10)) {
        const int half = four ? warp >> 2 : warp & 1, pr = four ? warp & 3 : warp >> 1;
        const int rc = 5 * f + (f & ~3) + 4 + pr;
        const uint32_t stage = sb + (conv ? SC_KG : SF_KG) + warp * KG_STAGE;
        uint4* const kp = p.s->kp + (four ? (conv ? 8 * bid : 48 * f - 2300) + pr : 2 * rc - (rc & 3) + 4) * 96 + lane;
        kgen(q, sb, half, stage, stage + (four ? 4 : 1) * KG_STAGE, 1 + pr, lane, w, [&] {
            sts128z_if(conv && lane < 20, sb + SC_KT + warp * KT_BYTES + lane * 16 + (lane < 4 ? 0 : lane < 14 ? 2048 : 2288));
            stg128z_if(!conv, kp + 64 * half); stg128z_if(!half && !conv, kp + 32);
            stg128z_if((unsigned)f < NW && warp < 6, (uint4*)(p.s->h + ((lane >> 4) * 288 + 6 * f + warp) * 32) + (lane & 15));
            if (!conv) bar_sync(0, NTHR);
            if ((unsigned)f >= NX) asm volatile("barrier.cluster.arrive.relaxed.aligned;" ::: "memory");
        });
        if (!half) publish_k(kp, w, epoch, v);
        else for (int i = 0; i < 6; i++) v[i] = 0;
        if (conv) { conv_main(p, sb, warp, lane, bid, epoch, w); return; }
        {
            if (!half && lane == 0) mbar_arrive(sb + SF_MISC + FB_KDONE);
            if (warp == 0) TSTAMP(22);
            if (warp == 2) TSTAMP(23);
        }
    } else if (conv) {
        conv_aux(p, maps.m, sb, warp - 8, lane, bid, epoch);
        return;
    } else {
        ffn_front(p, maps.m, sb, warp, lane, f, epoch);
        for (int i = 0; i < 6; i++) v[i] = 0;
    }
    converged();
    next_epoch(p, epoch);
    if (warp >= 12 && f < NX) return;
    mini_out(p, maps.m, sb, warp, lane, f, epoch, mini_conv(p, sb, warp, __shfl_sync(0xffffffffu, lane, lane), f, epoch, v));
}

typedef CUresult (*EncodeFn)(CUtensorMap*, CUtensorMapDataType, cuuint32_t, void*, const cuuint64_t*, const cuuint64_t*, const cuuint32_t*, const cuuint32_t*,
                             CUtensorMapInterleave, CUtensorMapSwizzle, CUtensorMapL2promotion, CUtensorMapFloatOOBfill);

void make_map(EncodeFn fn, CUtensorMap* m, const void* base, int rank, const cuuint64_t* dims, const cuuint64_t* strides, const cuuint32_t* box, CUtensorMapSwizzle sw) {
    const cuuint32_t es[5] = {1, 1, 1, 1, 1};
    fn(m, CU_TENSOR_MAP_DATA_TYPE_BFLOAT16, rank, (void*)base, dims, strides, box, es, CU_TENSOR_MAP_INTERLEAVE_NONE, sw,
       CU_TENSOR_MAP_L2_PROMOTION_NONE, CU_TENSOR_MAP_FLOAT_OOB_FILL_NONE);
}

}

extern "C" void kernel_launch(void* const* d_in, const int* in_sizes, int n_in, void* d_out, int out_size) {
    (void)in_sizes; (void)n_in; (void)out_size;
    static EncodeFn fn = nullptr;
    static void* scratch = nullptr;
    if (!fn) {
        void* ptr = nullptr; cudaDriverEntryPointQueryResult qr;
        cudaGetDriverEntryPoint("cuTensorMapEncodeTiled", &ptr, cudaEnableDefault, &qr);
        fn = (EncodeFn)ptr;
        cudaGetSymbolAddress(&scratch, g_scratch);
        cudaFuncSetAttribute(fused_kernel, cudaFuncAttributeMaxDynamicSharedMemorySize, SMEM_BYTES);
    }
    typedef const __nv_bfloat16* bp;
    Params p;
    p.u = (bp)d_in[0]; p.Are = (bp)d_in[1]; p.Aim = (bp)d_in[2]; p.Bre = (bp)d_in[3]; p.Bim = (bp)d_in[4]; p.Cre = (bp)d_in[5]; p.Cim = (bp)d_in[6];
    p.logdt = (bp)d_in[7]; p.Dskip = (bp)d_in[8]; p.wr = (bp)d_in[10]; p.gatew = (bp)d_in[14];
    p.out = (__nv_bfloat16*)d_out; p.s = (Scratch*)scratch; p.zero = 0;
    Maps maps;
    {
        const cuuint64_t dims[4] = {DM, 4, 16, 32}, strides[3] = {16 * DM * 2, DM * 2, 64 * DM * 2};
        const cuuint32_t box[4] = {16, 4, 16, 2};
        make_map(fn, &maps.m[0], d_in[0], 4, dims, strides, box, CU_TENSOR_MAP_SWIZZLE_32B);
        const cuuint32_t box2[4] = {16, 4, 16, 8};
        make_map(fn, &maps.m[5], d_in[0], 4, dims, strides, box2, CU_TENSOR_MAP_SWIZZLE_32B);
    }
    for (int i = 0; i < 2; i++) {
        const cuuint64_t dims[3] = {32, DM, FF / 32}, strides[2] = {FF * 2, 64};
        const cuuint32_t box[3] = {32, 64, 3};
        make_map(fn, &maps.m[1 + i], d_in[11 + i], 3, dims, strides, box, CU_TENSOR_MAP_SWIZZLE_64B);
    }
    {
        const cuuint64_t dims[2] = {DM, FF}, strides[1] = {DM * 2};
        const cuuint32_t box[2] = {32, 192};
        make_map(fn, &maps.m[3], d_in[13], 2, dims, strides, box, CU_TENSOR_MAP_SWIZZLE_64B);
    }
    {
        const cuuint64_t dims[5] = {DM, 2, 4, 4, L_SEQ}, strides[4] = {16 * DM * 2, 64 * DM * 2, 4 * DM * 2, DM * 2};
        const cuuint32_t box[5] = {16, 2, 4, 4, 1};
        make_map(fn, &maps.m[4], d_out, 5, dims, strides, box, CU_TENSOR_MAP_SWIZZLE_NONE);
    }
    fused_kernel<<<NCTA, NTHR, SMEM_BYTES>>>(p, maps);
}
```

```cpp
#include <cuda_runtime.h>
#include <cuda_bf16.h>
#include <cuda_fp16.h>
#include <cuda.h>
#include <stdint.h>
#include <type_traits>

#define RESUME 300
#define MDELAY 2000
#define MGAP 0
#define DUN 1
#define KPOLL 650
#define DPA 7
#define DPB 9
#define RDELAY 900
#define WDELAY 2000
#define WGAP 290
#define NPRE 7
#define DGAP 260
namespace {
constexpr int DUNR = DUN;

constexpr int DM = 576, NST = 128, FF = 4608, L_SEQ = 2048;
constexpr int NCONV = 72, NX = 36, NW = 48, NCTA = 132, NTHR = 512;

struct __align__(128) Scratch {
    unsigned epoch[NCTA * 16];
    uint4 keys[16 * 128];
    uint32_t sel[18 * 64];
    uint16_t gate[L_SEQ];
    uint2 h[2 * 288 * 32];
    uint4 kp[DM * 96];
};
__device__ Scratch g_scratch;
#define TFLUSH()
#define TSTAMP(i)
#define TW 12

struct Params {
    const __nv_bfloat16 *Are, *Aim, *Bre, *Bim, *Cre, *Cim, *logdt, *Dskip, *u, *wr, *gatew;
    __nv_bfloat16* out;
    Scratch* s;
    uint32_t zero;
};

__device__ __forceinline__ void give_up() { asm volatile("trap; exit;"); __builtin_unreachable(); }
__device__ __forceinline__ void converged() { __syncwarp(); asm volatile("{ .reg .b32 t; mov.b32 t, 0; movmatrix.sync.aligned.m8n8.trans.b16 t, t; }" ::: "memory"); }
__device__ __forceinline__ bool elect() { uint32_t r; asm volatile("{ .reg .pred p; elect.sync _|p, 0xffffffff; selp.u32 %0, 1, 0, p; }" : "=r"(r)); return r; }
__device__ __forceinline__ uint32_t smem_u32(const void* p) { return (uint32_t)__cvta_generic_to_shared(p); }
__device__ __forceinline__ uint32_t pack_bf16(float lo, float hi) { uint32_t r; asm("cvt.rn.bf16x2.f32 %0, %1, %2;" : "=r"(r) : "f"(hi), "f"(lo)); return r; }
__device__ __forceinline__ uint32_t pack_f16(float lo, float hi) { uint32_t r; asm("cvt.rn.f16x2.f32 %0, %1, %2;" : "=r"(r) : "f"(hi), "f"(lo)); return r; }
__device__ __forceinline__ float bf_lo(uint32_t w) { return __uint_as_float(w << 16); }
__device__ __forceinline__ float bf_hi(uint32_t w) { return __uint_as_float(w & 0xffff0000u); }
__device__ __forceinline__ float rbf(float x) { return bf_lo(pack_bf16(x, 0.f)); }
__device__ __forceinline__ uint32_t badd2(uint32_t a, uint32_t b) { uint32_t r; asm("add.rn.bf16x2 %0, %1, %2;" : "=r"(r) : "r"(a), "r"(b)); return r; }
__device__ __forceinline__ uint32_t bsub2(uint32_t a, uint32_t b) { uint32_t r; asm("sub.rn.bf16x2 %0, %1, %2;" : "=r"(r) : "r"(a), "r"(b)); return r; }
__device__ __forceinline__ uint32_t gmix(uint32_t ng, float ny0, float ny1, uint32_t u) {
    uint32_t r; asm("{ .reg .b32 t; fma.rn.bf16x2 t, %1, %3, %3; fma.rn.bf16x2 %0, %1, %2, t; }" : "=r"(r) : "r"(ng), "r"(pack_bf16(ny0, ny1)), "r"(u)); return r;
}
__device__ __forceinline__ void mma_bf(float (&c)[4], uint32_t a0, uint32_t a1, uint32_t a2, uint32_t a3, uint32_t b0, uint32_t b1) {
    asm("mma.sync.aligned.m16n8k16.row.col.f32.bf16.bf16.f32 {%0,%1,%2,%3}, {%4,%5,%6,%7}, {%8,%9}, {%0,%1,%2,%3};"
        : "+f"(c[0]), "+f"(c[1]), "+f"(c[2]), "+f"(c[3]) : "r"(a0), "r"(a1), "r"(a2), "r"(a3), "r"(b0), "r"(b1));
}
__device__ __forceinline__ void mma_bf8(float (&c)[4], uint32_t a0, uint32_t a1, uint32_t b0) {
    asm("mma.sync.aligned.m16n8k8.row.col.f32.bf16.bf16.f32 {%0,%1,%2,%3}, {%4,%5}, {%6}, {%0,%1,%2,%3};"
        : "+f"(c[0]), "+f"(c[1]), "+f"(c[2]), "+f"(c[3]) : "r"(a0), "r"(a1), "r"(b0));
}
__device__ __forceinline__ void mma_h(float (&c)[4], uint32_t a0, uint32_t a1, uint32_t a2, uint32_t a3, uint32_t b0, uint32_t b1) {
    asm("mma.sync.aligned.m16n8k16.row.col.f32.f16.f16.f32 {%0,%1,%2,%3}, {%4,%5,%6,%7}, {%8,%9}, {%0,%1,%2,%3};"
        : "+f"(c[0]), "+f"(c[1]), "+f"(c[2]), "+f"(c[3]) : "r"(a0), "r"(a1), "r"(a2), "r"(a3), "r"(b0), "r"(b1));
}
__device__ __forceinline__ uint32_t fresh(uint32_t a) { asm volatile("" : "+r"(a) :: "memory"); return a; }
__device__ __forceinline__ uint32_t lds32(uint32_t a) { uint32_t v; asm("ld.shared.u32 %0, [%1];" : "=r"(v) : "r"(a)); return v; }
__device__ __forceinline__ uint2 lds64(uint32_t a) { uint2 v; asm("ld.shared.v2.u32 {%0,%1}, [%2];" : "=r"(v.x), "=r"(v.y) : "r"(a)); return v; }
__device__ __forceinline__ uint4 lds128(uint32_t a) { uint4 v; asm("ld.shared.v4.u32 {%0,%1,%2,%3}, [%4];" : "=r"(v.x), "=r"(v.y), "=r"(v.z), "=r"(v.w) : "r"(a)); return v; }
__device__ __forceinline__ void ldsm4(uint32_t (&r)[4], uint32_t a) {
    asm("ldmatrix.sync.aligned.m8n8.x4.shared.b16 {%0,%1,%2,%3}, [%4];" : "=r"(r[0]), "=r"(r[1]), "=r"(r[2]), "=r"(r[3]) : "r"(a));
}
__device__ __forceinline__ void ldsm4t(uint32_t (&r)[4], uint32_t a) {
    asm("ldmatrix.sync.aligned.m8n8.x4.trans.shared.b16 {%0,%1,%2,%3}, [%4];" : "=r"(r[0]), "=r"(r[1]), "=r"(r[2]), "=r"(r[3]) : "r"(a));
}
__device__ __forceinline__ void sts16(uint32_t a, uint32_t v) { asm volatile("st.shared.u16 [%0], %1;" :: "r"(a), "h"((unsigned short)v) : "memory"); }
__device__ __forceinline__ void sts32(uint32_t a, uint32_t v) { asm volatile("st.shared.u32 [%0], %1;" :: "r"(a), "r"(v) : "memory"); }
__device__ __forceinline__ void sts64(uint32_t a, uint32_t x, uint32_t y) { asm volatile("st.shared.v2.u32 [%0], {%1,%2};" :: "r"(a), "r"(x), "r"(y) : "memory"); }
__device__ __forceinline__ void sts128(uint32_t a, uint32_t x, uint32_t y, uint32_t z, uint32_t w) {
    asm volatile("st.shared.v4.u32 [%0], {%1,%2,%3,%4};" :: "r"(a), "r"(x), "r"(y), "r"(z), "r"(w) : "memory");
}
__device__ __forceinline__ void st_async128(uint32_t a, uint32_t x, uint32_t y, uint32_t z, uint32_t w, uint32_t bar) {
    asm volatile("st.async.weak.shared::cluster.mbarrier::complete_tx::bytes.v4.b32 [%0], {%1,%2,%3,%4}, [%5];" :: "r"(a), "r"(x), "r"(y), "r"(z), "r"(w), "r"(bar) : "memory");
}
__device__ __forceinline__ void mbar_init(uint32_t b, uint32_t cnt) { asm volatile("mbarrier.init.shared::cta.b64 [%0], %1;" :: "r"(b), "r"(cnt) : "memory"); }
__device__ __forceinline__ void mbar_fence() { asm volatile("fence.mbarrier_init.release.cluster;" ::: "memory"); }
__device__ __forceinline__ void mbar_expect(uint32_t b, uint32_t bytes) { asm volatile("mbarrier.arrive.expect_tx.shared::cta.b64 _, [%0], %1;" :: "r"(b), "r"(bytes) : "memory"); }
__device__ __forceinline__ void mbar_arrive(uint32_t b) { asm volatile("mbarrier.arrive.shared::cta.b64 _, [%0];" :: "r"(b) : "memory"); }
__device__ __forceinline__ void mbar_wait(uint32_t b, uint32_t parity = 0) {
    asm volatile("{ .reg .pred p; .reg .u32 n; mov.u32 n, 0;\n"
                 "LW: mbarrier.try_wait.parity.shared::cta.b64 p, [%0], %1; @p bra LD; add.u32 n, n, 1; setp.lt.u32 p, n, 65536; @p bra LW; trap;\n"
                 "LD: }" :: "r"(b), "r"(parity) : "memory");
}
__device__ __forceinline__ void mbar_wait_cluster(uint32_t b) {
    asm volatile("{ .reg .pred p; .reg .u32 n; mov.u32 n, 0;\n"
                 "LW: mbarrier.try_wait.parity.acquire.cluster.shared::cta.b64 p, [%0], 0; @p bra LD; add.u32 n, n, 1; setp.lt.u32 p, n, 65536; @p bra LW; trap;\n"
                 "LD: }" :: "r"(b) : "memory");
}
__device__ __forceinline__ void tma2d(uint32_t dst, const CUtensorMap* m, int c0, int c1, uint32_t bar) {
    asm volatile("cp.async.bulk.tensor.2d.shared::cluster.global.mbarrier::complete_tx::bytes [%0], [%1, {%3, %4}], [%2];"
                 :: "r"(dst), "l"(m), "r"(bar), "r"(c0), "r"(c1) : "memory");
}
__device__ __forceinline__ void tma3d(uint32_t dst, const CUtensorMap* m, int c0, int c1, int c2, uint32_t bar) {
    asm volatile("cp.async.bulk.tensor.3d.shared::cluster.global.mbarrier::complete_tx::bytes [%0], [%1, {%3, %4, %5}], [%2];"
                 :: "r"(dst), "l"(m), "r"(bar), "r"(c0), "r"(c1), "r"(c2) : "memory");
}
__device__ __forceinline__ void tma4d(uint32_t dst, const CUtensorMap* m, int c0, int c1, int c2, int c3, uint32_t bar) {
    asm volatile("cp.async.bulk.tensor.4d.shared::cluster.global.mbarrier::complete_tx::bytes [%0], [%1, {%3, %4, %5, %6}], [%2];"
                 :: "r"(dst), "l"(m), "r"(bar), "r"(c0), "r"(c1), "r"(c2), "r"(c3) : "memory");
}
__device__ __forceinline__ void bulk_g2s(uint32_t dst, const void* src, uint32_t bytes, uint32_t bar) {
    asm volatile("cp.async.bulk.shared::cluster.global.mbarrier::complete_tx::bytes [%0], [%1], %2, [%3];"
                 :: "r"(dst), "l"(src), "r"(bytes), "r"(bar) : "memory");
}
__device__ __forceinline__ uint32_t mapa(uint32_t a, uint32_t rank) { uint32_t r; asm("mapa.shared::cluster.u32 %0, %1, %2;" : "=r"(r) : "r"(a), "r"(rank)); return r; }
__device__ __forceinline__ void prefetch_map(const CUtensorMap* m) { asm volatile("prefetch.tensormap [%0];" :: "l"(m) : "memory"); }
__device__ __forceinline__ void bar_sync(int id, int n) { asm volatile("bar.sync %0, %1;" :: "r"(id), "r"(n) : "memory"); }
__device__ __forceinline__ void bar_arrive(int id, int n) { asm volatile("bar.arrive %0, %1;" :: "r"(id), "r"(n) : "memory"); }
__device__ __forceinline__ uint32_t ldg16_if(bool c, const void* p) { uint32_t v; asm volatile("{ .reg .pred p; setp.ne.u32 p, %2, 0; @p ld.global.nc.u16 %0, [%1]; }" : "=r"(v) : "l"(p), "r"((uint32_t)c)); return v; }
__device__ __forceinline__ uint32_t ldg32_if(bool c, const void* p) { uint32_t v; asm volatile("{ .reg .pred p; setp.ne.u32 p, %2, 0; @p ld.global.nc.u32 %0, [%1]; }" : "=r"(v) : "l"(p), "r"((uint32_t)c)); return v; }
__device__ __forceinline__ uint32_t ld_rlx32(const void* p) { uint32_t v; asm volatile("ld.relaxed.gpu.global.u32 %0, [%1];" : "=r"(v) : "l"(p) : "memory"); return v; }
__device__ __forceinline__ uint4 ld_rlx128(const void* p) {
    uint4 v; asm volatile("ld.relaxed.gpu.global.v4.u32 {%0,%1,%2,%3}, [%4];" : "=r"(v.x), "=r"(v.y), "=r"(v.z), "=r"(v.w) : "l"(p) : "memory"); return v;
}
__device__ __forceinline__ void st_rlx32(void* p, uint32_t v) { asm volatile("st.relaxed.gpu.global.u32 [%0], %1;" :: "l"(p), "r"(v) : "memory"); }
__device__ __forceinline__ void stg128(void* p, uint32_t x, uint32_t y, uint32_t z, uint32_t w) {
    asm volatile("st.global.v4.u32 [%0], {%1,%2,%3,%4};" :: "l"(p), "r"(x), "r"(y), "r"(z), "r"(w) : "memory");
}
__device__ __forceinline__ void next_epoch(const Params& p, unsigned e) { if ((threadIdx.x & 31) == 0) p.s->epoch[blockIdx.x * 16 + (threadIdx.x >> 5)] = e + 1; }
__device__ __forceinline__ void sts128z_if(bool c, uint32_t a) { asm volatile("{ .reg .pred p; setp.ne.u32 p, %1, 0; @p st.shared.v4.u32 [%0], {%2,%2,%2,%2}; }" :: "r"(a), "r"((uint32_t)c), "r"(0) : "memory"); }
__device__ __forceinline__ void stg128z_if(bool c, void* a) { asm volatile("{ .reg .pred p; setp.ne.u32 p, %1, 0; @p st.global.v4.u32 [%0], {%2,%2,%2,%2}; }" :: "l"(a), "r"((uint32_t)c), "r"(0) : "memory"); }
__device__ __forceinline__ unsigned clock32() { unsigned c; asm volatile("mov.u32 %0, %clock;" : "=r"(c) :: "memory"); return c; }
__device__ __forceinline__ void until(unsigned t0, int c) { while ((int)(clock32() - t0) < c) { } }
__device__ __forceinline__ float sigmoidf_(float x) { return __fdividef(1.0f, 1.0f + __expf(-x)); }
__device__ __forceinline__ uint32_t key_tag(unsigned epoch) { return ((epoch & 15u) | 16u) << 11; }
__device__ __forceinline__ int key_row(uint32_t key) { return 2047 - (int)(key & 2047u); }
__device__ __forceinline__ uint32_t wait_sel(const Params& p, int s32, int r8, uint32_t tag, uint32_t k = 0) {
#pragma unroll 1
    for (int it = 0; !__all_sync(0xffffffffu, (k & 0xf800u) == tag); it++) {
        k = ld_rlx32(&p.s->sel[s32 * 64 + r8]);
        if (it > (1 << 20)) give_up();
    }
    return k;
}

struct cplx { float re, im; };
__device__ __forceinline__ cplx csq(cplx a) { cplx r; r.re = a.re * a.re - a.im * a.im; r.im = (a.re * a.im) * 2.f; return r; }
__device__ __forceinline__ cplx cexpk(float ar, float ai, float k) {
    float mag, s, c;
    asm("ex2.approx.ftz.f32 %0, %1;" : "=f"(mag) : "f"(ar * (k * 1.4426950408889634f)));
    const float r = ai * k;
    asm("sin.approx.ftz.f32 %0, %1;" : "=f"(s) : "f"(r));
    asm("cos.approx.ftz.f32 %0, %1;" : "=f"(c) : "f"(r));
    cplx o; o.re = mag * c; o.im = mag * s; return o;
}
struct h2c { uint32_t re, im; };
__device__ __forceinline__ h2c cmul_cd(h2c v, __half2 c, __half2 d) {
    const __half2 r = *(const __half2*)&v.re, i = *(const __half2*)&v.im;
    const __half2 x = __hfma2(__hneg2(i), d, __hmul2(r, c)), y = __hfma2(i, c, __hmul2(r, d));
    h2c o; o.re = *(const uint32_t*)&x; o.im = *(const uint32_t*)&y; return o;
}
__device__ __forceinline__ h2c cmul_s(h2c v, uint32_t s) { const __half2 h = *(const __half2*)&s; return cmul_cd(v, __low2half2(h), __high2half2(h)); }
__device__ __forceinline__ h2c cmul_sc(h2c v, uint32_t s) {
    const __half2 h = *(const __half2*)&s, c = __low2half2(h), d = __high2half2(h), r = *(const __half2*)&v.re, i = *(const __half2*)&v.im;
    const __half2 x = __hfma2(i, d, __hmul2(r, c)), y = __hfma2(__hneg2(r), d, __hmul2(i, c));
    h2c o; o.re = *(const uint32_t*)&x; o.im = *(const uint32_t*)&y; return o;
}
__device__ __forceinline__ h2c cmul_vc(h2c v, uint32_t s) {
    const __half2 h = *(const __half2*)&s, c = __low2half2(h), d = __high2half2(h), r = *(const __half2*)&v.re, i = *(const __half2*)&v.im;
    const __half2 x = __hfma2(i, d, __hmul2(r, c)), y = __hfma2(__hneg2(i), c, __hmul2(r, d));
    h2c o; o.re = *(const uint32_t*)&x; o.im = *(const uint32_t*)&y; return o;
}

constexpr int UT_HALF = 2560, UT_STRIDE = 4736, GT_HALF = 2240;
__device__ __forceinline__ uint32_t swz(uint32_t x, int c) { return x ^ (((x >> 2) & 64) ^ (64 * (c & 1) + 8 * (c & 6))); }
__device__ __forceinline__ int col(int n) { return (n >> 1) + 4 * (n & 1); }
constexpr int KT_T = 542, KT_C = 552, KT_D = 645, KT_BYTES = 720 * 4;
constexpr int VC_OFF = 80, VE_BASE = 1616;
constexpr int V_STRIDE = (1616 + 1024) * 4 + 80;
constexpr int KG_STAGE = 5248;
constexpr int Y_CS = 2080, Y_RS = 8 * Y_CS + 64;

constexpr int SC_RT = 0;
constexpr int SC_UT = 33408;
constexpr int SC_KG = SC_UT + 8 * UT_STRIDE;
constexpr int SC_KT = SC_KG + 8 * KG_STAGE;
constexpr int SC_GT = SC_KT + 8 * KT_BYTES;
constexpr int SC_V = SC_GT + 4448;
constexpr int SC_MISC = SC_V + 8 * V_STRIDE;
static_assert(V_STRIDE % 128 == 16 && 2 * Y_RS <= SC_UT && SC_UT % 128 == 0 && SC_KG % 128 == 0, "layout");
static_assert(SC_MISC % 16 == 0 && SC_MISC + 512 <= 232192, "layout");

__device__ __forceinline__ void window_task(uint32_t s0, uint32_t s1, uint32_t d0, uint32_t d1, int k) {
    float S[51], s = 0.f;
    uint32_t w[28];
#pragma unroll
    for (int i = 0; i < 7; i++) {
        const uint4 v = lds128(((i < 3 ? s0 : s1) ^ 8 * ((i + 1) & 2)) + ((i & 1) ? 0 : UT_HALF));
        w[4 * i] = v.x; w[4 * i + 1] = v.y; w[4 * i + 2] = v.z; w[4 * i + 3] = v.w;
    }
    auto sums = [&](int lo, int hi) {
#pragma unroll
        for (int i = lo; i < hi; i++) { const float x = (i & 1) ? bf_hi(w[i >> 1]) : bf_lo(w[i >> 1]); s = i > 3 ? s + x : x; S[i] = s; }
    };
    auto put = [&](int off, int b, int o0, int o1, int o2) {
        auto v = [&](int i) { i += 16 * b; return pack_bf16(S[o0 + i] - S[o1 + i], S[o1 + i] - S[o2 + i]); };
#pragma unroll
        for (int i = 0; i < 8; i += 2) sts128((i & 4 ? d1 : d0) + 4 * off + 64 * b + 8 * (i & 2), v(i), v(i + 8), v(i + 1), v(i + 9));
    };
    S[2] = 0.f;
    sums(3, 26); put(VC_OFF - 16, 0, 10, 5, 2);
    if (k == 12) return;
    sums(26, 42); put(VC_OFF - 16, 1, 10, 5, 2);
    if (k < 8) { put(VE_BASE, 0, 19, 12, 3); sums(42, 51); put(VE_BASE, 1, 19, 12, 3); }
}

template <class F>
__device__ __forceinline__ void kgen(const uint32_t (&q)[8], uint32_t sb, int half, uint32_t stage, uint32_t pstage, int barid, int lane, uint32_t (&w)[12], F shadow) {
    const int t = lane & 3, mi = lane >> 3, r8 = lane & 7;
    {
        const uint32_t pAr = q[0], pAi = q[1], pBr = q[2], pBi = q[3], pCr = q[4], pCi = q[5], pDt = q[6], pD = q[7];
        const uint32_t wb = fresh(stage + lane * 16), za = fresh(stage + 5120 + ((lane >> 1) & 3) * 16 + mi * 4 + (lane & 1) * 2), zr = fresh(stage + 5120 + t * 16);
        const uint32_t oA = fresh(stage + (mi & 1) * 1024 + (mi >> 1) * 512 + r8 * 16), oB = fresh(stage + 2048 + mi * 512 + r8 * 16), oC = fresh(stage + 4096 + (mi & 1) * 512 + (mi >> 1) * 128 + r8 * 16);
        float acc[6][4];
#pragma unroll
        for (int a = 0; a < 6; a++) { acc[a][0] = acc[a][1] = acc[a][2] = acc[a][3] = 0.f; asm volatile("" : "+f"(acc[a][0]), "+f"(acc[a][1]), "+f"(acc[a][2]), "+f"(acc[a][3])); }
        shadow();
        sts32(zr, clock32());
        const float dt = rbf(__expf(bf_lo(pDt)));
        float ar = dt * bf_lo(pAr), ai = dt * bf_lo(pAi), ar1 = dt * bf_hi(pAr), ai1 = dt * bf_hi(pAi);
        float wr, wi, wr1, wi1;
        { const float br = dt * bf_lo(pBr), bi = dt * bf_lo(pBi), cr = bf_lo(pCr), ci = bf_lo(pCi); wr = cr * br - ci * bi; wi = cr * bi + ci * br; }
        { const float br = dt * bf_hi(pBr), bi = dt * bf_hi(pBi), cr = bf_hi(pCr), ci = bf_hi(pCi); wr1 = cr * br - ci * bi; wi1 = cr * bi + ci * br; }
        const uint32_t ex = max(__reduce_max_sync(0xffffffffu, __float_as_uint(fmaxf(fmaxf(fabsf(wr), fabsf(wi)), fmaxf(fabsf(wr1), fabsf(wi1))))) >> 23, 14u);
        const float scl = __uint_as_float((267u - ex) << 23);
        uint32_t W = pack_f16(wr * scl, wi * -scl);
        const uint32_t W1 = pack_f16(wr1 * scl, wi1 * -scl);
        if (threadIdx.x < 32) TSTAMP(20);

#pragma unroll 1
        for (int r = 0; r < 2; r++) {
            const cplx z1 = cexpk(ar, ai, 1.f), z64 = cexpk(ar, ai, 64.f);
            const cplx z2 = csq(z1), z4 = csq(z2), z8 = csq(z4), z16 = csq(z8), z32 = csq(z16);
            const cplx z128 = csq(z64), z256 = csq(z128), z512 = csq(z256);
            auto put = [&](int grp, h2c a, h2c b, h2c c, h2c d) { sts128(wb + grp * 1024, a.re, b.re, c.re, d.re); sts128(wb + grp * 1024 + 512, a.im, b.im, c.im, d.im); };
            {
                const uint32_t s4 = pack_f16(z4.re, z4.im), s256 = pack_f16(z256.re, z256.im), s512 = pack_f16(z512.re, z512.im);
                auto mix = [](h2c a, h2c b, uint32_t sel) { return h2c{__byte_perm(a.re, b.re, sel), __byte_perm(a.im, b.im, sel)}; };
                const h2c c10 = cmul_vc(h2c{pack_f16(z1.re, 1.f), pack_f16(z1.im, 0.f)}, W), c32 = cmul_sc(c10, pack_f16(z2.re, z2.im)), c54 = cmul_sc(c10, s4);
                put(2, c10, c32, c54, cmul_sc(c32, s4));
                const h2c d20 = cmul_sc(mix(c32, c10, 0x7632), s256), e04 = cmul_sc(mix(c10, c54, 0x7632), s512), f04 = cmul_sc(e04, s256);
                put(3, d20, cmul_sc(d20, s4), e04, f04);
                const h2c ef = mix(e04, f04, 0x5410), gh = cmul_sc(ef, s512), g8 = cmul_sc(gh, pack_f16(z8.re, z8.im));
                put(4, g8, cmul_sc(g8, s512), gh, ef);
            }
            {
                const uint32_t s32 = pack_f16(z32.re, z32.im), s64 = pack_f16(z64.re, z64.im), s128 = pack_f16(z128.re, z128.im);
                const h2c p0 = {pack_f16(1.f, z8.re), pack_f16(0.f, z8.im)}, p1 = cmul_s(p0, pack_f16(z16.re, z16.im)), p2 = cmul_s(p0, s32), p3 = cmul_s(p1, s32);
                put(0, p0, p1, p2, p3);
                put(1, cmul_s(p0, s64), cmul_s(p1, s64), cmul_s(p2, s64), cmul_s(p3, s64));
                sts16(za, s128); sts16(za + 64, s128 >> 16);
            }
            __syncwarp();
            {
                const uint32_t aA = fresh(oA), aB = fresh(oB), aC = fresh(oC), aZ = fresh(zr);
                const uint4 zc = lds128(aZ), zd = lds128(aZ + 64);
                const uint32_t zcs[4] = {zc.x, zc.y, zc.z, zc.w}, zds[4] = {zd.x, zd.y, zd.z, zd.w};
                uint32_t c[4];
#pragma unroll
                for (int k = 0; k < 4; k++) {
                    uint32_t a[4], b[4];
                    ldsm4t(a, aA + 128 * k); ldsm4t(b, aB + 128 * k);
                    if (!(k & 1)) ldsm4t(c, aC + 128 * k);
                    const h2c x = cmul_cd(h2c{a[0], a[2]}, *(const __half2*)&zcs[k], *(const __half2*)&zds[k]), y = cmul_cd(h2c{a[1], a[3]}, *(const __half2*)&zcs[k], *(const __half2*)&zds[k]);
                    mma_h(acc[0], a[0], a[1], a[2], a[3], b[0], b[1]);
                    mma_h(acc[1], a[0], a[1], a[2], a[3], b[2], b[3]);
                    mma_h(acc[2], a[0], a[1], a[2], a[3], c[2 * (k & 1)], c[2 * (k & 1) + 1]);
                    mma_h(acc[3], x.re, y.re, x.im, y.im, b[0], b[1]);
                    mma_h(acc[4], x.re, y.re, x.im, y.im, b[2], b[3]);
                    mma_h(acc[5], x.re, y.re, x.im, y.im, c[2 * (k & 1)], c[2 * (k & 1) + 1]);
                }
                asm volatile("" :: "f"(acc[0][0]), "f"(acc[1][0]), "f"(acc[2][0]), "f"(acc[3][0]), "f"(acc[4][0]), "f"(acc[5][0]) : "memory");
            }
            __syncwarp();
            ar = ar1; ai = ai1; W = W1;
        }
        if (threadIdx.x < 32) TSTAMP(21);
        const float i0 = __uint_as_float((ex + 243u) << 23);
        if (half) {
#pragma unroll
            for (int a = 0; a < 6; a++) sts128(wb + a * 512, __float_as_uint(acc[a][0]), __float_as_uint(acc[a][1]), __float_as_uint(acc[a][2]), __float_as_uint(acc[a][3]));
            sts32(stage + 3072, __float_as_uint(i0));
            bar_arrive(barid, 64);
        } else {
#pragma unroll
            for (int a = 0; a < 6; a++) { acc[a][0] *= i0; acc[a][1] *= i0; acc[a][2] *= i0; acc[a][3] *= i0; }
            if (lane == 0) acc[0][1] -= bf_lo(pD);
            sts32(zr, clock32());
            bar_sync(barid, 64);
            const uint32_t src = fresh(pstage);
            const float i1 = __uint_as_float(lds32(src + 3072));
#pragma unroll
            for (int a = 0; a < 6; a++) {
                const uint4 y = lds128(src + lane * 16 + a * 512);
                w[4 * (a % 3) + 2 * (a / 3)] = pack_bf16(fmaf(__uint_as_float(y.x), i1, acc[a][0]), fmaf(__uint_as_float(y.y), i1, acc[a][1]));
                w[4 * (a % 3) + 2 * (a / 3) + 1] = pack_bf16(fmaf(__uint_as_float(y.z), i1, acc[a][2]), fmaf(__uint_as_float(y.w), i1, acc[a][3]));
            }
            const uint32_t x0 = __shfl_up_sync(0xffffffffu, w[10], 2), x1 = __shfl_up_sync(0xffffffffu, w[11], 2);
            w[10] = w[8];
            if (t >= 2) { w[8] = x0; w[9] = x1; }
        }
    }
}

enum { BC_AUX = 0, BC_U = 5 };

__device__ __forceinline__ void fetch_gates(const Params& p, int i, int lane, unsigned epoch, uint32_t dst) {
    const uint32_t par = (epoch & 1) ? 0x80008000u : 0u;
    uint4 v;
#pragma unroll 1
    for (int it = 0;; it++) {
        v = ld_rlx128(p.s->gate + 256 * i + 8 * lane);
        v.x ^= par; v.y ^= par; v.z ^= par; v.w ^= par;
        if (__all_sync(0xffffffffu, (v.x & v.y & v.z & v.w & 0x80008000u) == 0x80008000u)) break;
        if (it > (1 << 20)) give_up();
    }
    sts128(dst, v.x, v.y, v.z, v.w);
}
__device__ __forceinline__ void store_rows(const CUtensorMap* m, uint32_t src, int col, int row) {
    asm volatile("cp.async.bulk.tensor.5d.global.shared::cta.bulk_group [%0, {%2, %3, %3, %3, %4}], [%1];" :: "l"(m), "r"(src), "r"(col), "r"(0), "r"(row) : "memory");
}

__device__ __forceinline__ void store_or_add(void* o, const uint32_t (&y)[4], uint32_t add) {
    asm volatile("{ .reg .pred p; setp.ne.u32 p, %5, 0; @!p st.global.v4.u32 [%0], {%1,%2,%3,%4}; @p red.relaxed.gpu.global.add.noftz.v4.bf16x2 [%0], {%1,%2,%3,%4}; }"
                 :: "l"(o), "r"(y[0]), "r"(y[1]), "r"(y[2]), "r"(y[3]), "r"(add) : "memory");
}

__device__ __forceinline__ void conv_aux(const Params& p, const CUtensorMap* mU, uint32_t sb, int aw, int lane, int bid, unsigned epoch) {
    const int g = lane >> 2, t = lane & 3, mi = lane >> 3, r8 = lane & 7;
    const int rank = bid & 1, slab = bid >> 1;
    const uint32_t bar_y = sb + SC_MISC, bar_u = bar_y + 32, bar_v = bar_y + 40, bar_box = bar_y + 64 + 8 * aw, s_bm = bar_y + 128;
    if (elect()) {
        mbar_init(bar_box, 1); mbar_fence();
        mbar_expect(bar_box, 4096);
        tma4d(sb + SC_RT + 4096 * aw, mU, 16 * slab, 0, 0, 16 * rank + 2 * aw, bar_box);
        mbar_init(bar_y + 8 * aw, aw < 4 ? 9 : aw == 5 ? 8 : 1); mbar_fence();
        if (aw < 5) mbar_expect(bar_y + 8 * aw, aw == 4 ? 16384 : 4096);
    }
    __syncwarp();
    asm volatile("barrier.cluster.arrive.relaxed.aligned;" ::: "memory");
    asm volatile("setmaxnreg.dec.sync.aligned.u32 88;");
    sts128(sb + (lane < 16 ? SC_UT + aw * UT_STRIDE + mi * (UT_HALF - 128) : SC_V - 256 + aw * V_STRIDE) + lane * 16, 0, 0, 0, 0);
    if (lane < 16) sts128(s_bm + lane * 16, 0, 0, 0, 0);
    {
        const uint32_t dst = sb + SC_UT + g * UT_STRIDE + swz((8 + 64 * rank + 8 * aw + t) * 16, g);
        const uint32_t rdst = mapa(dst, rank ^ 1), rbar = mapa(bar_u, rank ^ 1);
        asm volatile("barrier.cluster.wait.acquire.aligned;" ::: "memory");
        mbar_wait(bar_box);
        if (aw == 0) TSTAMP(1);
        const uint32_t src = fresh(sb + SC_RT) + aw * 4096 + (8 * mi + 4 * (r8 & 1) + (r8 >> 1)) * 32 + ((rank ^ (r8 & 1)) << 4);
        uint32_t x[8][4];
#pragma unroll
        for (int i = 0; i < 4; i++) { ldsm4t(x[i], src + 1024 * i); ldsm4t(x[4 + i], (src ^ 16) + 1024 * i); }
        asm volatile("" :: "r"(x[0][0]), "r"(x[1][0]), "r"(x[2][0]), "r"(x[3][0]) : "memory");
#pragma unroll
        for (int i = 0; i < 4; i++) st_async128((rdst ^ 32 * (i & 2)) + (i & 1) * UT_HALF, x[4 + i][0], x[4 + i][1], x[4 + i][2], x[4 + i][3], rbar);
#pragma unroll
        for (int i = 0; i < 4; i++) sts128((dst ^ 32 * (i & 2)) + (i & 1) * UT_HALF, x[i][0], x[i][1], x[i][2], x[i][3]);
    }
    bar_sync(BC_AUX, 256);
    mbar_wait_cluster(bar_u);
    if (aw == 0) TSTAMP(2);
    if (aw >= 4) bar_arrive(BC_U + aw, 64); else bar_sync(BC_U + aw, 64);
    if (aw == 0) TSTAMP(3);
    {
        const uint32_t ws = fresh(sb + SC_UT) + r8 * UT_STRIDE, wd = sb + SC_V + r8 * V_STRIDE;
#pragma unroll 1
        for (int k = aw; k < 13; k += 8) {
            const int a = 8 * k + (k < 12 ? g & 6 : 0);
            const uint32_t d = wd + 64 * a, sw = 16 * (a & 2);
            window_task(ws + swz(16 * a + 96, r8), ws + swz(16 * a + 128, r8), d + sw, d + (sw ^ 32), k);
        }
    }
    if (aw == 0) TSTAMP(9);
    {
        if (aw >= 2) fetch_gates(p, aw, lane, epoch, sb + SC_GT + (lane & 1) * GT_HALF + (8 + 16 * aw + (lane >> 1)) * 16);
        __syncwarp();
        if (elect()) { mbar_arrive(bar_v); prefetch_map(mU + 4); }
        next_epoch(p, epoch);
        if (aw == 0) TSTAMP(4);
        if (aw == 7) {
            const int row = key_row(wait_sel(p, slab >> 1, r8, key_tag(epoch)));
            if (lane < 8) asm volatile("red.shared.or.b32 [%0], %1;" :: "r"(s_bm + (row >> 5) * 4), "r"(1u << (row & 31)) : "memory");
            TSTAMP(10);
        }
        bar_sync(BC_AUX, 256);
        const uint32_t src = sb + SC_RT + ((r8 >> 1) & 1) * Y_RS + (2 * mi + (r8 & 1)) * Y_CS + (2 * aw + (r8 >> 2)) * 16;
        const int L = 2 * aw + (t >> 1);
        const int row0 = 256 * rank + 128 * (g >> 2) + 16 * (L & 3) + 64 * (g & 1) + 8 * ((g >> 1) & 1) + (L >> 2);
        __nv_bfloat16* outp = p.out + (size_t)row0 * DM + 16 * slab + 8 * (t & 1);
        const uint32_t stg = sb + SC_KG + 4096 * aw, so = (g & 2) * 256 + (g >> 2) * 128 + r8 * 16;
#pragma unroll 1
        for (int s = 1; s < 4; s++) {
            const uint32_t bm = lds32(fresh(s_bm) + (16 * s + (row0 >> 5)) * 4) >> (row0 & 31);
            const bool routed = __any_sync(0xffffffffu, bm & 0x11u);
            if (aw == s) mbar_wait_cluster(bar_y + 8 * s);
            bar_sync(BC_AUX, 256);
            const uint32_t sf = fresh(src) + 512 * s;
            uint32_t y[2][4];
            ldsm4t(y[0], sf); ldsm4t(y[1], sf + 256);
            if (routed) {
#pragma unroll
                for (int k = 0; k < 2; k++) store_or_add(outp + (size_t)(512 * s + 4 * k) * DM, y[k], bm & (1u << (4 * k)));
            } else {
                sts128(stg + so + 1024 * s, y[0][0], y[0][1], y[0][2], y[0][3]); sts128(stg + so + 1024 * s + 256, y[1][0], y[1][1], y[1][2], y[1][3]);
                asm volatile("fence.proxy.async.shared::cta;" ::: "memory");
                __syncwarp();
                if (elect()) store_rows(mU + 4, stg + 1024 * s, 16 * slab, 512 * s + 256 * rank + 32 * (aw & 1) + (aw >> 1));
            }
            if (aw == 0) TSTAMP(16 + s);
        }
        if (elect()) { asm volatile("cp.async.bulk.commit_group;" ::: "memory"); asm volatile("cp.async.bulk.wait_group.read 0;" ::: "memory"); }
        if (aw == 0) TFLUSH();
    }
}

__device__ __forceinline__ uint32_t k_tag(unsigned epoch) { return epoch << 16 | 0x80000000u; }
__device__ __forceinline__ void publish_k(uint4* kp, const uint32_t (&w)[12], unsigned epoch, uint64_t (&v)[6]) {
#pragma unroll
    for (int i = 0; i < 3; i++) {
        v[2 * i] = w[3 * i] | (uint64_t)w[3 * i + 1] << 32; v[2 * i + 1] = w[3 * i + 2] | (uint64_t)__byte_perm(w[9 + (i >> 1)], k_tag(epoch), i == 1 ? 0x7632 : 0x7610) << 32;
        asm volatile("st.relaxed.gpu.global.v2.u64 [%0], {%1,%2};" :: "l"(kp + 32 * i), "l"(v[2 * i]), "l"(v[2 * i + 1]));
    }
}
template <bool FULL>
__device__ __forceinline__ void k_tables(uint32_t kt, int lane, const uint32_t (&w)[12]) {
    const int g = lane >> 2, t = lane & 3, mi = lane >> 3, r8 = lane & 7;
    uint32_t x3 = w[7], re[4], rx[4];
#pragma unroll
    for (int i = 0; i < 4; i++) {
        re[i] = __shfl_sync(0xffffffffu, w[i], lane + 31);
        rx[i] = __shfl_sync(0xffffffffu, w[4 + i], lane + (i == 0 && lane == 29 ? 5 : 1 + 2 * t));
    }
    if (FULL) {
        asm volatile("stmatrix.sync.aligned.m8n8.x2.trans.shared.b16 [%0], {%1,%2};" :: "r"(kt + (KT_D + 7) * 4 + 64 * t + 16 * (mi & 1) + 8 * (r8 & 4)), "r"(w[8]), "r"(w[9]) : "memory");
        if (lane == 2) {
            sts32(kt + (KT_C + 78) * 4, w[10] & 0xffffu);
            sts128(kt + (KT_T + 2) * 4, 0, w[10] & 0xffffu, __byte_perm(w[10], 0, 0x1010), w[10] << 16);
        }
        if (lane == 29) x3 = bsub2(x3, rx[0] & 0xffffu);
    }
#pragma unroll
    for (int i = 0; i < 4; i++) {
        sts64(kt + (16 + 64 * i) * 4 + 8 * lane, __byte_perm(w[i], lane ? re[i] : i ? re[i - 1] : 0, 0x5432), w[i]);
        const uint32_t x = i < 3 ? w[4 + i] : x3, aa = __byte_perm(x, 0, 0x3232);
        if (t < 2) sts128(kt + (272 + 64 * i + 8 * g + 4 * t) * 4, i == 0 && lane == 0 ? __byte_perm(x, re[3], 0x5432) : aa, aa, x,
                          __byte_perm(lane != 29 ? rx[i] : i < 3 ? rx[(i + 1) & 3] : FULL ? 0 : rx[0] << 16, x, 0x5432));
        else if (FULL) sts32(kt + (KT_C - 50 + 8 * i + 32 * t + g) * 4, x);
    }
}

__device__ __forceinline__ void conv_main(const Params& p, uint32_t sb, int warp, int lane0, int bid, unsigned epoch, uint32_t (&w)[12]) {
    asm volatile("setmaxnreg.inc.sync.aligned.u32 168;");
    const int lane = __shfl_sync(0xffffffffu, lane0, lane0);
    const int g = lane >> 2, t = lane & 3, mi = lane >> 3, r8 = lane & 7;
    const int rank = bid & 1;
    const uint32_t bar_y = sb + SC_MISC, bar_v = bar_y + 40;
    next_epoch(p, epoch);
    if (warp >= 4) {
        bar_sync(BC_U + warp, 64);
        if (KPOLL) until(clock32(), KPOLL);
        const uint4* src = p.s->kp + (8 * bid + warp) * 96 + lane0;
#pragma unroll 1
        for (int it = 0;; it++) {
            uint32_t bad = 0, e[3];
#pragma unroll
            for (int i = 0; i < 3; i++) { const uint4 v = ld_rlx128(src + 32 * i); w[3 * i] = v.x; w[3 * i + 1] = v.y; w[3 * i + 2] = v.z; e[i] = v.w; bad |= v.w ^ k_tag(epoch); }
            w[9] = __byte_perm(e[0], e[1], 0x5410); w[10] = e[2];
            const bool ok = __all_sync(0xffffffffu, bad < 65536);
            if (ok) break;
            if (it > (1 << 20)) give_up();
        }
    }
    if ((warp & 3) == 0) TSTAMP(5 + (warp >> 2));
    k_tables<true>(sb + SC_KT + warp * KT_BYTES, lane0, w);
    asm volatile("barrier.cluster.wait.acquire.aligned;" ::: "memory");
    if (warp < 4) bar_sync(BC_U + warp, 64);
    __syncwarp();
    if ((warp & 3) == 0) TSTAMP(7 + (warp >> 2));
    {
        const uint32_t ut = fresh(sb + SC_UT) + warp * UT_STRIDE, kt = fresh(sb + SC_KT) + warp * KT_BYTES;
        auto dup = [&](uint32_t v) { return v ^ p.zero; };
        auto frag = [&](uint32_t (&a)[4], uint32_t x) { a[0] = lds32(x); a[1] = lds32(x + 32); a[2] = lds32(x - 32); a[3] = dup(a[0]); };
        const uint32_t kb = kt + (16 + g - 2 * t) * 4;
        float acc[16][4];
        {
            float y[12][4], M[6][4];
#pragma unroll
            for (int i = 0; i < 12; i++) { y[i][0] = y[i][1] = y[i][2] = y[i][3] = 0.f; M[i >> 1][0] = M[i >> 1][1] = M[i >> 1][2] = M[i >> 1][3] = 0.f; }
            uint32_t U[10][4], a1[4], ad[4], R = (mi & 1) * UT_HALF + (8 + (r8 >> 1) + 48 * (r8 & 1)) * 16 + 64 * (mi >> 1);
            auto places = [&] { ad[0] = swz(R, warp); ad[1] = swz(R + 128, warp); ad[2] = ad[0] ^ 64; ad[3] = ad[1] ^ 64; };
            auto ldu = [&](int k) { ldsm4(U[k], ut + ad[k & 3] + 256 * (k >> 1)); };
            places();
            frag(a1, kb + 2048);
#pragma unroll
            for (int k = 0; k < 7; k++) ldu(k);
#pragma unroll
            for (int i = 0; i < 12; i++) mma_bf(y[i], a1[0], a1[1], a1[2], a1[3], U[i >> 1][2 * (i & 1)], U[i >> 1][2 * (i & 1) + 1]);
            frag(a1, kb + 1792);
            __syncwarp();
#pragma unroll DUNR
            for (uint32_t ko = 0; ko != 256;) {
                if (DUN == 1) ko = fresh(ko);
                const uint32_t kp = kb + ko;
                ko += 64;
                uint32_t se[10][2], so[10][2], ue[10][2];
                auto sums = [&](int k) {
#pragma unroll
                    for (int e = 0; e < 2; e++) { ue[k][e] = U[k][e]; se[k][e] = badd2(U[k][e], U[k - 1][2 + e]); so[k][e] = badd2(U[k][e], U[k][2 + e]); }
                };
#pragma unroll
                for (int k = 1; k < 6; k++) sums(k);
#pragma unroll
                for (int m = 3; m >= 0; m--) {
                    uint32_t a0[4];
                    frag(a0, kp + 512 * m);
                    sums(9 - m);
                    if (m) ldu(10 - m); else { R -= 16; places(); }
#pragma unroll
                    for (int i = 0; i < 6; i++) mma_bf(y[2 * i], a1[0], a1[1], a1[2], a1[3], se[i - m + 4][0], se[i - m + 4][1]);
#pragma unroll
                    for (int e = 0; e < 4; e++) a1[e] = bsub2(a0[e], a1[e]);
#pragma unroll
                    for (int i = 0; i < 6; i++) { mma_bf(M[i], a1[0], a1[1], a1[2], a1[3], ue[i - m + 4][0], ue[i - m + 4][1]); if (!m) ldu(i); }
                    frag(a1, m ? kp + 512 * m - 256 : kp + 1792 + 64);
                    if (!m) ldu(6);
#pragma unroll
                    for (int i = 0; i < 6; i++) mma_bf(y[2 * i + 1], a0[0], a0[1], a0[2], a0[3], so[i - m + 4][0], so[i - m + 4][1]);
                }
            }
#pragma unroll
            for (int i = 0; i < 6; i++)
#pragma unroll
                for (int c = 0; c < 4; c++) { acc[4 + i + 6 * (c & 1)][c & 2] = y[2 * i][c] + M[i][c]; acc[4 + i + 6 * (c & 1)][c | 1] = y[2 * i + 1][c] - M[i][c]; }
        }
        const uint32_t lo = (8 + col(r8)) * 16 + (mi >> 1) * 128, ua = fresh(ut) + (mi & 1) * UT_HALF, u1[2] = {ua + swz(lo, warp), ua + (swz(lo, warp) ^ 64)};
        {
            uint32_t e[4];
            frag(e, kb + (KT_T - 16) * 4);
            const uint32_t f0 = dup(e[1]), f1 = lds32(kb + KT_T * 4), uo = fresh(ut) + UT_HALF + swz((7 + 8 * mi + col(r8)) * 16, warp);
#pragma unroll
            for (int i = 0; i < 4; i++) {
                uint32_t b[4];
                if (i < 2) {
                    ldsm4(b, uo + 512 * i);
#pragma unroll
                    for (int k = 0; k < 4; k++) mma_bf8(acc[8 + 4 * i + k], f0, f1, b[k]);
                }
                ldsm4(b, u1[i & 1] + 256 * i);
                mma_bf(acc[2 * i + 8], e[0], e[1], e[2], e[3], b[0], b[1]); mma_bf(acc[2 * i + 9], e[0], e[1], e[2], e[3], b[2], b[3]);
            }
        }
        if ((warp & 3) == 0) TSTAMP(11 + (warp >> 2));
        mbar_wait(bar_v);
        const uint32_t vt = fresh(sb + SC_V) + warp * V_STRIDE;
        const uint32_t g1 = fresh(sb + SC_GT) + (mi & 1) * GT_HALF + lo;
        const uint32_t ydst = sb + SC_RT + rank * Y_RS + warp * Y_CS + lane * 16;
        const uint32_t ydr = mapa(ydst, rank ^ 1), ybr = mapa(bar_y, rank ^ 1);
        auto stairs = [&](auto R) {
        uint32_t ug[2][2][4];
        auto ld_ug = [&](int i) { ldsm4t(ug[i & 1][0], u1[i & 1] + 256 * i); ldsm4t(ug[i & 1][1], g1 + 256 * i); };
        auto ship = [&](int i) {
            const uint32_t (&u)[4] = ug[i & 1][0], (&gg)[4] = ug[i & 1][1];
            const uint32_t y0 = gmix(gg[0], acc[2 * i][0], acc[2 * i][1], u[0]), y1 = gmix(gg[1], acc[2 * i][2], acc[2 * i][3], u[1]);
            const uint32_t y2 = gmix(gg[2], acc[2 * i + 1][0], acc[2 * i + 1][1], u[2]), y3 = gmix(gg[3], acc[2 * i + 1][2], acc[2 * i + 1][3], u[3]);
            if ((i & 1) != R.value) st_async128(ydr + 512 * (i >> 1), y0, y1, y2, y3, ybr + 8 * (i >> 1));
            else asm volatile("{ .reg .pred q; setp.eq.u32 q, %6, 0; st.shared.v4.u32 [%0], {%2,%3,%4,%5}; bar.warp.sync 0xffffffff; @q mbarrier.arrive.shared::cta.b64 _, [%1]; }"
                              :: "r"(ydst + 512 * (i >> 1)), "r"(bar_y + 8 * (i >> 1)), "r"(y0), "r"(y1), "r"(y2), "r"(y3), "r"(lane) : "memory");
        };
        const uint32_t VD = vt + (VC_OFF - 400 - 16 * t) * 4 + (8 * g ^ 16 * (-t & 2)), VD2 = vt + (VC_OFF - 415 - 16 * t) * 4 + (8 * g ^ 16 * (~t & 2));
        uint2 bd[10];
        uint32_t x[2][4][4];
        auto ld4 = [&](uint32_t (&v)[4], int dl) { const uint2 w = lds64(VD + 256 * dl); v[0] = w.x; v[1] = w.y; v[2] = lds32(VD2 + 256 * dl); v[3] = dup(w.x); };
        auto mm4 = [&](const uint32_t (&v)[4], int dl) {
#pragma unroll
            for (int s = dl & 1; s < 10; s += 2) if ((dl + s) / 2 >= 4 && (dl + s) / 2 < 16) mma_bf(acc[(dl + s) / 2], v[0], v[1], v[2], v[3], bd[s].x, bd[s].y);
        };
        const uint32_t KE = kt + (KT_D + col(g) + t) * 4, VE = vt + (VE_BASE - 912 - 16 * t) * 4 + (8 * g ^ 16 * (~t & 2));
        uint32_t b0[8], b1[8];
        auto ld8 = [&](uint32_t (&v)[4], int dl) { const uint2 w = lds64(VE + 512 * dl), z = lds64(VE + 512 * dl - 256); v[0] = w.x; v[1] = w.y; v[2] = z.x; v[3] = z.y; };
        auto mm8 = [&](const uint32_t (&v)[4], int dl, int lo, int hi) {
#pragma unroll
            for (int s = 0; s < 8; s++) if (dl + s >= lo && dl + s < hi) mma_bf(acc[dl + s], v[0], v[1], v[2], v[3], b0[s], b1[s]);
        };
        ld4(x[0][0], 6);
#pragma unroll
        for (int s = 0; s < 10; s++) bd[s] = lds64(kt + (KT_C + 2 * col(g) + 2 * t + 8 * s) * 4);
        mm4(x[0][0], 6);
        uint32_t e[4][4];
#pragma unroll
        for (int k = 1; k < 6; k++) {
#pragma unroll
            for (int j = 0; j < 4; j++) ld4(x[k & 1][j], 4 * k + 3 + j);
            ld_ug(k + 1);
            if (k == 3) {
#pragma unroll
                for (int s = 0; s < 8; s++) { b0[s] = lds32(KE + 32 * s); b1[s] = lds32(KE + 32 * s + 16); }
            }
            if (k > 1) ship(k);
#pragma unroll
            for (int j = 0; j < 4; j++) {
                mm4(x[k & 1][j], 4 * k + 3 + j);
                if (k == 3) { uint32_t v[4], z[4]; ld8(e[j], 8 + j); ld8(v, 12 + j); ld4(z, 30 - j); mm8(v, 12 + j, 12, 16); mm8(e[j], 8 + j, 8, 12); mm4(z, 30 - j); }
                if (k == 5) { ld8(e[j], 8 + j + p.zero); mm8(e[j], 8 + j, 12, 16); }
            }
        }
        ld_ug(7);
        ship(7 - R.value); ship(6 + R.value);
        };
        if (rank) stairs(std::integral_constant<int, 1>()); else stairs(std::integral_constant<int, 0>());
        if ((warp & 3) == 0) TSTAMP(14 + (warp >> 2)); else TSTAMP(21 + warp);
    }
}

constexpr int SF_WD = 73728;
constexpr int SF_RED = 49152;
constexpr int MU_STRIDE = 1168  , SM_RAW = 98304, SM_UT = SM_RAW + 16384, SM_G = SM_UT + 21504, SM_Y = 196608, SM_FT = SM_Y + 17024, SM_KT = 138880, SM_KW = SM_G - 49152;
constexpr int SF_XS = 221184;
constexpr int SF_MISC = SF_XS + 8 * 1168;
constexpr int SF_KG = SF_MISC - 10 * KG_STAGE;
constexpr int SF_WR = SF_KG - 2304;
constexpr int FB_X = 64, FB_KDONE = 72, FB_KEYS = 80, FB_FREE = 88  , FB_W = 104, FB_D = FB_W + 72, FB_MU = FB_D + 96, FB_FAR = FB_MU - 16, FB_MG = FB_MU + 8, FB_MT = FB_MU + 16  , FS_PART = 512, FS_TOK = 896, FS_BM = 1024;
enum { BAR_R = 7, BAR_GU = 8, BAR_RED = 9, BAR_R2 = 10, BAR_G = 12  , BAR_M = 15 };
static_assert(SF_KG % 128 == 0 && NPRE <= 8 && SM_KT + 4 * 2112 <= 147456 && SM_G + MU_STRIDE <= SF_WR - 4 * 9216 && SM_KW + 6 * 2112 >= SM_RAW && SM_KW + 12 * 2112 <= SM_UT, "layout");

__device__ __forceinline__ constexpr int box_no(int i) { return (0x987610ba5432ull >> (4 * i)) & 15; }
__device__ __forceinline__ int role(int b) { b -= NCONV; return b < NX ? b : 18 + (b >> 1) + 12 * (b & 1); }
__device__ __forceinline__ int mini_ch0(int f) { return 48 * f - (f < NW ? 1696 : 2304); }

__device__ __forceinline__ void ffn_front(const Params& p, const CUtensorMap* maps, uint32_t sb, int warp, int lane, int f, unsigned epoch) {
    const unsigned t0 = clock32();
    const int g = lane >> 2, t = lane & 3, mi = lane >> 3, r8 = lane & 7;
    const bool isx = f < NX;
    const int nrw = f < 52 ? 4 : 6, r0 = f < 52 ? 32 * f : 48 * f - 832;
    const int rw = warp < 12 ? 13 - warp : warp ^ (warp < 14 ? 10 : 15);
    const uint32_t bar_row = sb + SF_MISC  , bar_x = bar_row + FB_X;
    const uint32_t s_part = bar_row + FS_PART  , s_tok = bar_row + FS_TOK  ;
    const uint32_t rows = sb + SF_WR - 9216 * (rw + 1) - (rw & 4) * ((SF_WR - 6 * 9216) / 4);
    {
#pragma unroll 1
        for (int i = warp < 10 ? 30 : warp - 10; i < 30; i += 6) if (elect()) mbar_init(bar_x + 8 * i, i == 1 ? 4 + (f < NW) : i < 27 ? 1 : i == 27 ? 2 : 8);
        const uint32_t bytes = rw < 6 ? 9216 : 1152, dst = rw < 6 ? rows : sb + SF_WR + (rw & 1) * 1152;
        const __nv_bfloat16* src = rw < 6 ? p.u + (size_t)(r0 + 8 * rw) * DM : (rw & 1) ? p.gatew : p.wr;
        if (elect()) { mbar_init(bar_row + 8 * rw, 1); mbar_fence(); mbar_expect(bar_row + 8 * rw, bytes); }
        if (warp == 13) { sts32(s_part + 64 + lane * 4, 0); sts32(bar_row + FS_BM + lane * 4, 0); }
        bar_sync(0, NTHR);
        if (!isx) asm volatile("barrier.cluster.arrive.relaxed.aligned;" ::: "memory");
        if (rw < nrw) until(t0, RDELAY);
        if (rw < nrw || rw >= 6) { if (elect()) bulk_g2s(dst, src, bytes, bar_row + 8 * rw); }
    }
    uint4* const kdst = p.s->keys + (lane >> 1) * 128 + 2 * f + (lane & 1);
    if (warp == 15) TSTAMP(1);

    if (warp == 12) {
        if (lane < 22) mbar_expect(bar_row + FB_W + 8 * lane, lane < 9 ? 24576 : isx ? 12288 : lane < 20 ? 2048 : 16384);
        if (elect()) { prefetch_map(maps + 1); prefetch_map(maps + 2); prefetch_map(maps + (isx ? 3 : 5)); }
        unsigned tb = t0 + WDELAY;
        auto pieces = [&](int n, int end, uint32_t dst) {
#pragma unroll 1
            for (; n < end; n++, dst += 12288) {
                until(tb, 0); tb += WGAP;
                if (elect()) tma3d(dst, maps + 1 + (n & 1), 0, 64 * (n >> 1), 3 * f, bar_row + FB_W + 8 * (n >> 1));
            }
        };
        if (!isx) {
#pragma unroll 1
            for (int k = 0; k <= (f >= NW); k++) { until(t0, MDELAY + k * MGAP); if (elect()) tma4d(sb + SM_RAW - 49152 * k, maps + 5, mini_ch0(f) + 16 * k, 0, 0, 0, bar_row + FB_MU - 8 * k); }
            if (f >= NW) return;
        }
#pragma unroll 1
        for (int i = 0; i < 4; i++) {
            if (i == 1) { mbar_wait(bar_row + FB_KEYS); mbar_wait(bar_row + FB_KDONE); tb = clock32() + RESUME; }
            if (i == 3) mbar_wait(bar_row + FB_FREE);
            const int n = ((0x0c080000 + NPRE * 256) >> (8 * i)) & 255;
            pieces(n, ((0x120c0800 + NPRE) >> (8 * i)) & 255, sb + 12288 * (((0x000c0000 + NPRE * 256) >> (8 * i)) & 255));
        }
        TSTAMP(12);
        if (isx) {
#pragma unroll 1
            for (int i = 0; i < 12; i++) {
                const int n = box_no(i);
                if (i == 6) mbar_wait(bar_row + FB_FREE + 8);
                until(tb, 0); tb += DGAP;
                if (elect()) tma2d(sb + SF_WD + n * 12288, maps + 3, 32 * (f >> 1), 2304 * (f & 1) + 192 * n, bar_row + FB_D + 8 * n);
            }
            TSTAMP(13);
        }
    } else if (warp == 13) {
        const uint32_t tag = key_tag(epoch), par = (epoch & 1) ? 0u : 0x8000u;
        stg128(kdst, 0, 0, 0, 0);
        if (lane < 8 && isx && !(f & 1)) st_rlx32(&p.s->sel[32 * f + lane], 0);
        bar_sync(BAR_R, 32 * (nrw + 1));
        TSTAMP(3);
        {
            const uint32_t sg = fresh(s_part) + 192 + lane * 4;
            const uint32_t gb = pack_bf16(sigmoidf_(rbf(__uint_as_float(lds32(sg)))), sigmoidf_(rbf(__uint_as_float(lds32(sg + 128))))) | par | (par << 16);
            asm volatile("st.relaxed.gpu.global.u16 [%0], %1;" :: "l"(p.s->gate + r0 + lane), "h"((unsigned short)gb) : "memory");
            if (nrw > 4 && lane < 16) asm volatile("st.relaxed.gpu.global.u16 [%0], %1;" :: "l"(p.s->gate + r0 + 32 + lane), "h"((unsigned short)(gb >> 16)) : "memory");
        }
        bar_sync(BAR_R2, 32 * (nrw + 1));
        {
            const uint4 v = lds128(fresh(s_tok) + (lane & 1) * 16);
            asm volatile("st.relaxed.gpu.global.v4.u32 [%0], {%1,%2,%3,%4};" :: "l"(kdst), "r"(v.x | tag), "r"(v.y | tag), "r"(v.z | tag), "r"(v.w | tag) : "memory");
        }
        TSTAMP(4);
        if (lane == 0) { mbar_arrive(bar_row + FB_KEYS); mbar_expect(bar_x, 8 * 1152); }
        if (f >= NW) return;
        mbar_wait(bar_row + FB_KDONE);
        uint32_t k[16];
        const uint4* src = p.s->keys + (f & 15) * 128 + lane;
#pragma unroll 1
        for (int it = 0;; it++) {
            uint32_t bad = 0;
#pragma unroll
            for (int i = 0; i < 4; i++) {
                const uint4 x = ld_rlx128(src + (i < 3 || lane < 24 ? 32 * i : 64));
                k[i] = x.x; k[4 + i] = x.y; k[8 + i] = x.z; k[12 + i] = x.w;
                bad |= x.x ^ tag;
            }
            const bool ok = __all_sync(0xffffffffu, (bad & 0xf800u) == 0);
            if (ok) break;
            if (it > (1 << 20)) give_up();
        }
        TSTAMP(5);
        uint32_t key = 0, m = __reduce_max_sync(0xffffffffu, max(max(k[0], k[1]), max(k[2], k[3])));
#pragma unroll 2
        for (int r = 0; r < 8; r++) {
            bool pop[4];
#pragma unroll
            for (int i = 0; i < 4; i++) { pop[i] = k[i] == m; k[i] = pop[i] ? k[4 + i] : k[i]; }
            const uint32_t mn = __reduce_max_sync(0xffffffffu, max(max(k[0], k[1]), max(k[2], k[3])));
            if (elect()) bulk_g2s(sb + SF_XS + r * 1168, p.u + (size_t)key_row(m) * DM, 1152, bar_x);
#pragma unroll
            for (int i = 0; i < 4; i++) { k[4 + i] = pop[i] ? k[8 + i] : k[4 + i]; k[8 + i] = pop[i] ? k[12 + i] : k[8 + i]; k[12 + i] = pop[i] ? 0 : k[12 + i]; }
            if (r8 == r) key = m;
            m = mn;
        }
        const int row = key_row(key);
        sts32(s_tok + r8 * 8, row);
        TSTAMP(6);
        if (isx) {
            if (!(f & 1)) {
                __nv_bfloat16* o = p.out + (size_t)row * DM + 16 * f + 8 * mi;
                asm volatile("st.relaxed.gpu.global.v4.u32 [%0], {%1,%1,%1,%1};" :: "l"(o), "r"(0) : "memory");
                if (__any_sync(0xffffffffu, ld_rlx32(o) != 0)) give_up();
                if (lane < 8) st_rlx32(&p.s->sel[32 * f + lane], key);
            } else wait_sel(p, f >> 1, r8, tag);
            uint32_t gb;
#pragma unroll 1
            for (int it = 0;; it++) {
                asm volatile("ld.relaxed.gpu.global.u16 %0, [%1];" : "=r"(gb) : "l"(p.s->gate + row) : "memory");
                gb ^= par;
                if (!(gb & 0x8000u)) break;
                if (it > (1 << 20)) give_up();
            }
            const uint32_t rb = key ^ 0x80000000u, rv = (rb ^ (((int)rb >> 31) & 0x7fff0000u)) & 0xffff0000u;
            sts32(s_tok + r8 * 8 + 4, __float_as_uint(rbf(1.0f - bf_lo(gb)) * rbf(sigmoidf_(__uint_as_float(rv)))));
            __syncwarp();
            TSTAMP(7);
            bar_arrive(BAR_RED, 416);
        }
    } else {
        if (rw < nrw) {
            float c[3][4];
#pragma unroll
            for (int i = 0; i < 3; i++) { c[i][0] = c[i][1] = c[i][2] = c[i][3] = 0.f; }
            mbar_wait(bar_row + 48); mbar_wait(bar_row + 56);
            const uint32_t b = fresh(sb + SF_WR) + (g & 1) * 1152 + (g >> 2) * 64 + t * 16 + (g & 2) * 2;
            uint32_t w[18][2];
#pragma unroll
            for (int kb = 0; kb < 18; kb++) { const uint32_t o = ((kb & 1) ? b ^ 64 : b) + 128 * (kb >> 1); w[kb][0] = lds32(o); w[kb][1] = lds32(o + 8); }
            mbar_wait(bar_row + 8 * rw);
            if (warp == 15) TSTAMP(2);
            const uint32_t a = fresh(rows) + g * 1152 + (g & 1) * 64 + t * 16;
#pragma unroll
            for (int kb = 0; kb < 18; kb++) {
                const uint4 x = lds128(((kb & 1) ? a ^ 64 : a) + 128 * (kb >> 1));
                mma_bf(c[kb % 3], x.x, x.y, x.z, x.w, w[kb][0], w[kb][1]);
            }
            const float sr = c[0][0] + c[1][0] + c[2][0] + __shfl_down_sync(0xffffffffu, c[0][2] + c[1][2] + c[2][2], 1);
            const float sg = c[0][1] + c[1][1] + c[2][1] + __shfl_down_sync(0xffffffffu, c[0][3] + c[1][3] + c[2][3], 1);
            const uint32_t rb = pack_bf16(0.f, sr);
            if (t == 2 * (g & 1)) {
                sts32(s_part + (8 * rw + g) * 4, (rb ^ (((int)rb >> 31) & 0x7fff0000u) ^ 0x80000000u) | (uint32_t)(2047 - r0 - 8 * rw - g));
                sts32(s_part + 192 + (8 * rw + g) * 4, __float_as_uint(sg));
            }
            __syncwarp();
            bar_sync(BAR_R, 32 * (nrw + 1));
            const uint32_t sk = fresh(s_part), kk = lds32(sk + (8 * rw + r8) * 4);
            int n = 0;
#pragma unroll
            for (int i = 0; i < 3; i++) { const uint4 v = lds128(sk + mi * 48 + 16 * i); n += (v.x > kk) + (v.y > kk) + (v.z > kk) + (v.w > kk); }
            n += __shfl_xor_sync(0xffffffffu, n, 8); n += __shfl_xor_sync(0xffffffffu, n, 16);
            if (n < 8) sts32(s_tok + 4 * n, kk);
            __syncwarp();
            bar_arrive(BAR_R2, 32 * (nrw + 1));
        }
    }
}

__device__ __forceinline__ void ffn_work(const Params& p, uint32_t sb, int warp, int lane, int f, unsigned epoch) {
    const int g = lane >> 2, t = lane & 3, mi = lane >> 3, r8 = lane & 7;
    const bool isx = f < NX;
    const uint32_t bar_x = sb + SF_MISC + FB_X, bar_free = sb + SF_MISC + FB_FREE, bar_w = sb + SF_MISC + FB_W, bar_d = sb + SF_MISC + FB_D, s_tok = sb + SF_MISC + FS_TOK;
    uint32_t fr[24][4];
    auto pin = [&] {
#pragma unroll
        for (int i = 0; i < 24; i += 8) asm volatile("" :: "r"(fr[i][0]), "r"(fr[i + 1][0]), "r"(fr[i + 2][0]), "r"(fr[i + 3][0]), "r"(fr[i + 4][0]), "r"(fr[i + 5][0]), "r"(fr[i + 6][0]), "r"(fr[i + 7][0]) : "memory");
    };
    {
        const int j = (unsigned)(warp - 4) < 6, w = warp - (j ? 4 : warp < 4 ? 0 : 6);
        float ag[2][4], au[2][4];
#pragma unroll
        for (int i = 0; i < 2; i++) { ag[i][0] = ag[i][1] = ag[i][2] = ag[i][3] = 0.f; au[i][0] = au[i][1] = au[i][2] = au[i][3] = 0.f; }
        const uint32_t wb = sb + (w >> 1) * 4096 + (r8 + 8 * (mi >> 1)) * 64 + (((2 * (w & 1) + (mi & 1)) ^ (r8 >> 1)) << 4);
        const uint32_t xb = sb + SF_XS + r8 * 1168 + mi * 16;
        auto load = [&](int i, int n, int place) {
            mbar_wait(bar_w + 8 * n);
            const uint32_t wk = fresh(wb) + place * 24576;
#pragma unroll
            for (int s = 0; s < 4; s++) { ldsm4t(fr[8 * i + s], wk + 1024 * s); ldsm4t(fr[8 * i + 4 + s], wk + 1024 * s + 12288); }
        };
        auto mul = [&](int i, uint32_t xk) {
            uint32_t x[2][4];
            ldsm4(x[0], xk); ldsm4(x[1], xk + 64);
#pragma unroll
            for (int s = 0; s < 4; s++) {
                const uint32_t (&a)[4] = fr[8 * i + s], (&b)[4] = fr[8 * i + 4 + s];
                mma_bf(ag[s & 1], a[0], a[1], a[2], a[3], x[s >> 1][2 * (s & 1)], x[s >> 1][2 * (s & 1) + 1]);
                mma_bf(au[s & 1], b[0], b[1], b[2], b[3], x[s >> 1][2 * (s & 1)], x[s >> 1][2 * (s & 1) + 1]);
            }
        };
#pragma unroll
        for (int i = 0; i < 3; i++) load(i, 3 * j + i, (i ? 5 : 3) * j + i);
        pin();
        bar_sync(BAR_G + j, 192);
        if (w == 0 && lane == 0) mbar_arrive(bar_free + 8 * j);
        mbar_wait(bar_x);
        if (warp == 0) TSTAMP(8);
        {
            const uint32_t xk = fresh(xb) + 384 * j;
#pragma unroll
            for (int i = 0; i < 3; i++) { mul(i, (i ? fresh(xk) : xk) + 128 * i); if (i == 0) { asm volatile("" :: "f"(ag[0][0]), "f"(ag[1][0]), "f"(au[0][0]), "f"(au[1][0])); sts32(s_tok + 64, clock32()); } }
        }
#pragma unroll 1
        for (int n = 6 + j; n < 9; n += 2) { load(0, n, n - 6); mul(0, fresh(xb) + 128 * n); }
#pragma unroll
        for (int c = 0; c < 4; c++) { ag[0][c] += ag[1][c]; au[0][c] += au[1][c]; }
        if (j) {
            sts128(wb + 24576, __float_as_uint(ag[0][0]), __float_as_uint(ag[0][1]), __float_as_uint(ag[0][2]), __float_as_uint(ag[0][3]));
            sts128(wb + 25600, __float_as_uint(au[0][0]), __float_as_uint(au[0][1]), __float_as_uint(au[0][2]), __float_as_uint(au[0][3]));
        }
        bar_sync(BAR_GU, 384);
        if (!j) {
            const uint32_t sf = fresh(wb);
            const uint4 g1 = lds128(sf + 24576), u1 = lds128(sf + 25600);
            const uint32_t gs[4] = {g1.x, g1.y, g1.z, g1.w}, us[4] = {u1.x, u1.y, u1.z, u1.w};
            if (warp == 0) TSTAMP(9);
            float h[4];
#pragma unroll
            for (int c = 0; c < 4; c++) {
                const float gv = rbf(ag[0][c] + __uint_as_float(gs[c]));
                h[c] = rbf(gv * sigmoidf_(gv)) * rbf(au[0][c] + __uint_as_float(us[c]));
            }
            uint32_t h0, h1;
            asm("movmatrix.sync.aligned.m8n8.trans.b16 %0, %1;" : "=r"(h0) : "r"(pack_bf16(h[0], h[1])));
            asm("movmatrix.sync.aligned.m8n8.trans.b16 %0, %1;" : "=r"(h1) : "r"(pack_bf16(h[2], h[3])));
            if (h0 == 0) h0 = 0x8000u;
            asm volatile("{ .reg .b64 v; mov.b64 v, {%1, %2}; st.relaxed.gpu.global.b64 [%0], v; }" :: "l"(p.s->h + ((epoch & 1) * 288 + 6 * f + w) * 32 + lane), "r"(h0), "r"(h1) : "memory");
        }
        if (isx) {
            if (warp == 0) TSTAMP(10);
            const uint2* hsrc = p.s->h + ((epoch & 1) * 288 + 144 * (f & 1) + warp) * 32 + lane;
            const uint32_t wd = sb + SF_WD + warp * 1024 + (r8 + 8 * (mi >> 1)) * 64 + (((mi & 1) ^ (r8 >> 1)) << 4), we = wd ^ 32;
            uint2 hb[12];
            auto ldh = [&](int i) { asm volatile("ld.relaxed.gpu.global.v2.u32 {%0, %1}, [%2];" : "=r"(hb[i].x), "=r"(hb[i].y) : "l"(hsrc + 384 * box_no(i)) : "memory"); };
            auto ldw = [&](int i) { mbar_wait(bar_d + 8 * box_no(i)); ldsm4t(fr[2 * i], fresh(wd) + 12288 * box_no(i)); ldsm4t(fr[2 * i + 1], fresh(we) + 12288 * box_no(i)); };
#pragma unroll
            for (int i = 0; i < DPA; i++) ldw(i);
#pragma unroll
            for (int i = 0; i < 12; i++) ldh(i);
#pragma unroll
            for (int i = DPA; i < DPB; i++) ldw(i);
#pragma unroll
            for (int i = 0; i < DPB; i++) asm volatile("" :: "r"(fr[2 * i][0]), "r"(fr[2 * i + 1][0]) : "memory");
#pragma unroll 1
            for (int it = 0;; it++) {
                bool again = false;
#pragma unroll
                for (int s = 0; s < 12; s += 2) if (__any_sync(0xffffffffu, min(hb[s].x, hb[s + 1].x) == 0)) { ldh(s); ldh(s + 1); again = true; }
                if (!again) break;
                if (it > (1 << 16)) give_up();
            }
            if (warp == 0) TSTAMP(11);
            float ad[2][2][4];
#pragma unroll
            for (int i = 0; i < 4; i++) { ad[i >> 1][i & 1][0] = ad[i >> 1][i & 1][1] = ad[i >> 1][i & 1][2] = ad[i >> 1][i & 1][3] = 0.f; }
#pragma unroll
            for (int i = 0; i < 12; i++) {
                if (i >= DPB) ldw(i);
                if (i == 11 && warp == 9) TSTAMP(14);
#pragma unroll
                for (int c = 0; c < 2; c++) mma_bf(ad[c][i & 1], fr[2 * i + c][0], fr[2 * i + c][1], fr[2 * i + c][2], fr[2 * i + c][3], hb[i].x, hb[i].y);
                if (i >= DPB - 1) asm volatile("" :: "f"(ad[0][i & 1][0]), "f"(ad[1][i & 1][0]) : "memory");
            }
            const uint32_t rd = sb + SF_RED + warp * 1152 + (72 * t + g) * 4;
#pragma unroll
            for (int i = 0; i < 8; i++) sts32(rd + (i >> 2) * 64 + (i & 1) * 144 + ((i >> 1) & 1) * 32, __float_as_uint(ad[i >> 2][0][i & 3] + ad[i >> 2][1][i & 3]));
            bar_sync(BAR_RED, 416);
            if (warp < 4) {
                const int tid = 32 * warp + lane;
                const uint32_t rs = fresh(sb + SF_RED) + (tid >> 4) * 144 + (tid & 15) * 8;
                const uint2 tk = lds64(fresh(s_tok) + (tid >> 4) * 8);
                float x = 0.f, y = 0.f;
#pragma unroll
                for (int w = 0; w < 12; w++) { const uint2 v = lds64(rs + w * 1152); x += __uint_as_float(v.x); y += __uint_as_float(v.y); }
                asm volatile("red.relaxed.gpu.global.add.noftz.bf16x2 [%0], %1;" :: "l"(p.out + (size_t)tk.x * DM + 32 * (f >> 1) + 2 * (tid & 15)),
                             "r"(pack_bf16(x * __uint_as_float(tk.y), y * __uint_as_float(tk.y))) : "memory");
            }
            if (warp == 0) { TSTAMP(15); TFLUSH(); }
            asm volatile("exit;"); __builtin_unreachable();
        }
    }
}

__device__ __forceinline__ void fetch_k(const uint4* src, uint64_t (&v)[6], uint32_t a, uint32_t b) {
    asm volatile("{ .reg .pred p; setp.eq.u32 p, %7, %8; @p ld.relaxed.gpu.global.v2.u64 {%0,%1}, [%6]; @p ld.relaxed.gpu.global.v2.u64 {%2,%3}, [%6 + 512]; @p ld.relaxed.gpu.global.v2.u64 {%4,%5}, [%6 + 1024]; }"
                 : "+l"(v[0]), "+l"(v[1]), "+l"(v[2]), "+l"(v[3]), "+l"(v[4]), "+l"(v[5]) : "l"(src), "r"(a), "r"(b));
}
__device__ __forceinline__ uint32_t mini_conv(const Params& p, uint32_t sb, int warp, int lane, int f, unsigned epoch, uint64_t (&v)[6]) {
    const int g = lane >> 2, t = lane & 3, mi = lane >> 3, r8 = lane & 7;
    const uint32_t fb = sb + SF_MISC, kt = sb + (warp >= 12 ? SM_KT - 12 * 2112 : f < NW ? SM_KW + 2 * 2112 : SM_KW) + warp * 2112;
    const bool ism = f >= NW;
    const uint32_t* const sel = &p.s->sel[((mini_ch0(f) + (ism ? 2 * (warp & 8) : 0)) >> 5) * 64 + r8];
    uint32_t seq = 128, key;
    const uint4* src = p.s->kp + lane;
    auto hi = [&](int i) { return (uint32_t)(v[i] >> 32); };
    if (f >= (warp < 4 ? NW : NX)) {
    {
        const uint32_t c = 68 + (warp & 3) + 2 * (warp & 12), y = ((uint32_t)((warp < 8 ? 0xe066806400000000ull : 0x5a6e00680080e26cull) >> ((8 * warp) & 48)) & 0xffff) + (warp < 14 ? 0 : 0x6a0000);
        seq = !ism ? y + (warp & 1) * ((y >> 6) & 0x10101) : warp < 14 ? 0x101 * c - 0x400 : c;
        src += (48 * (f - (ism ? NW : NX)) + (seq & 63)) * 96;
    }
    if (seq & 64) {
        if (seq & 4) {
            const int q = (seq & 3) + ((seq >> 1) & 4);
            const uint32_t ab = sb - 3072 * (seq & 16), d = ab + SM_UT + g * MU_STRIDE + (4 + 4 * q + t) * 32;
            asm volatile("st.shared.v2.u32 [%0], {%1,%1};" :: "r"(ab + SM_UT + (2 * q + (mi >> 1)) * MU_STRIDE + (lane & 15) * 8), "r"(0) : "memory");
            mbar_wait(fb + FB_MU - (seq & 16) / 2);
            if (warp == 15) TSTAMP(16);
            const uint32_t a = fresh(ab + SM_RAW) + q * 2048 + (8 * mi + 4 * (r8 & 1) + (r8 >> 1)) * 32 + ((r8 & 1) << 4);
            uint32_t x[4][4];
#pragma unroll
            for (int i = 0; i < 4; i++) ldsm4t(x[i], (i & 2 ? a ^ 16 : a) + 1024 * (i & 1));
#pragma unroll
            for (int i = 0; i < 4; i++) sts128(d + (i & 1) * 16 + (i & 2) * 4 * MU_STRIDE, x[i][0], x[i][1], x[i][2], x[i][3]);
            __syncwarp();
            if (lane == 0) mbar_arrive(fb + FB_MT + (seq & 16) / 2);
        }
        mbar_wait(fb + FB_KDONE);
        fetch_k(src, v, warp < 4, 0);
        if ((warp | 2) == 7) { fetch_gates(p, (warp >> 1) & 1, lane, epoch, sb + SM_G + 256 * (warp & 2) + 16 * lane); __syncwarp(); if (lane == 0) mbar_arrive(fb + FB_MG); }
        if (warp >= 8) {
            mbar_wait(fb + FB_KEYS); mbar_wait(fb + FB_MT);
            if (ism) {
                asm volatile("barrier.cluster.wait.aligned; fence.release.sync_restrict::shared::cta.cluster;" ::: "memory");
                if (lane == 0) asm volatile("mbarrier.arrive.relaxed.cluster.shared::cluster.b64 _, [%0];" :: "r"(mapa(fb + FB_MT + 8, 0)) : "memory");
            }
        }
        if (warp == TW) TSTAMP(17);
    }
    }
    const uint32_t lo = (8 + r8 - (mi & 1)) * 16 + (mi >> 1) * 128;
#pragma unroll 1
    do {
        const int c = seq & 63;
        const bool far = !ism && (seq & 16);
        const uint32_t ab = sb - 3072 * (c & 16);
        uint32_t ut = ab + SM_UT + (c & 15) * MU_STRIDE;
        if (seq & 64) {
        if (far) {
            mbar_wait_cluster(fb + FB_MT + 8);
            const uint32_t ru = mapa(ut, 1) + lane * 16;
            ut = sb + SM_FT + (c & 3) * 1536;
            uint4 x[3];
#pragma unroll
            for (int i = 0; i < 3; i++) asm volatile("ld.shared::cluster.v4.u32 {%0,%1,%2,%3}, [%4];" : "=r"(x[i].x), "=r"(x[i].y), "=r"(x[i].z), "=r"(x[i].w) : "r"(ru + 512 * i) : "memory");
#pragma unroll
            for (int i = 0; i < 3; i++) sts128(ut + lane * 16 + 512 * i, x[i].x, x[i].y, x[i].z, x[i].w);
        } else mbar_wait(fb + FB_MT + (seq & 16) / 2);
#pragma unroll 1
        for (int it = 0; !__all_sync(0xffffffffu, ((hi(1) ^ k_tag(epoch)) | (hi(3) ^ k_tag(epoch)) | (hi(5) ^ k_tag(epoch)) | ((uint32_t)v[5] & p.zero)) < 65536); it++) {
            fetch_k(src, v, 0, 0);
            if (it > (1 << 20)) give_up();
        }
        sts128(kt + t * 16, 0, 0, 0, 0);
        if (warp == TW) TSTAMP(seq >> 8 ? 7 : 10);
        const uint32_t w[12] = {(uint32_t)v[0], hi(0), (uint32_t)v[1], (uint32_t)v[2], hi(2), (uint32_t)v[3], (uint32_t)v[4], hi(4), 0, 0, 0, 0};
        k_tables<false>(fresh(kt), fresh(lane), w);
        }
        __syncwarp();
        if (seq & 128) ffn_work(p, sb, warp, fresh(lane), f, epoch);
        if (!(seq & 64)) return 0;
        const uint32_t kb = fresh(kt) + (16 + g - 2 * t) * 4, ub = fresh(ut);
        const uint32_t yd = ab + SM_Y + (c & 15) * 1056 + (c & 8) * 8 + lane * 16;
        if (warp == TW && !(seq >> 8)) TSTAMP(13);
        seq >>= 8;
        src += ((int)(seq & 63) - c) * 96;
#pragma unroll
        for (int i = 0; i < 6; i++) v[i] = 0;
        key = 0;
        float acc[8][4];
#pragma unroll
        for (int i = 0; i < 8; i++) { acc[i][0] = acc[i][1] = acc[i][2] = acc[i][3] = 0.f; }
        uint32_t a[4][4], b[2][4][4];
        auto lda = [&](int j, int s) { const uint32_t x = kb + 64 * s + 512 * j; a[j][0] = lds32(x); a[j][1] = lds32(x + 256); a[j][2] = lds32(x + 32); a[j][3] = lds32(x + 288); };
        auto ldb = [&](int i, int s) { ldsm4(b[s & 1][i], ub + lo + 256 * i - 32 * s); };
#pragma unroll
        for (int j = 0; j < 4; j++) { ldb(j, 0); lda(j, 0); }
#pragma unroll
        for (int s = 0; s < 4; s++) {
            if (s == 2) {
                const uint32_t e = seq | (__float_as_uint(acc[0][0]) & p.zero);
                fetch_k(src, v, e & 64, 64);
                asm volatile("{ .reg .pred p; setp.eq.u32 p, %2, 0; @p ld.relaxed.gpu.global.u32 %0, [%1]; }" : "+r"(key) : "l"(sel), "r"(e));
            }
#pragma unroll
            for (int i = 0; i < 4; i++) {
                const int j = (i >> 1) + 2 * (i & 1);
                if (s < 3) ldb(i, s + 1);
#pragma unroll
                for (int mu = 0; mu < 8; mu++) if (mu + 2 * j < 8) mma_bf(acc[mu + 2 * j], a[j][0], a[j][1], a[j][2], a[j][3], b[s & 1][mu >> 1][2 * (mu & 1)], b[s & 1][mu >> 1][2 * (mu & 1) + 1]);
                if (s < 3) lda(j, s + 1);
            }
        }
        if (warp == TW && !seq) TSTAMP(14);
        mbar_wait(fb + FB_MG);
        uint32_t ug[4][4];
#pragma unroll
        for (int i = 0; i < 2; i++) { ldsm4t(ug[i], ub + 128 + lane * 16 + 512 * i); ldsm4t(ug[2 + i], fresh(sb + SM_G) + lane * 16 + 512 * i); }
#pragma unroll
        for (int x = 0; x < 8; x++) ug[x >> 2][x & 3] = gmix(ug[2 + (x >> 2)][x & 3], x ? acc[x][0] + acc[x - 1][2] : acc[0][0], x ? acc[x][1] + acc[x - 1][3] : acc[0][1], ug[x >> 2][x & 3]);
        if (far) for (int i = 0; i < 2; i++) st_async128(mapa(yd, 1) + 512 * i, ug[i][0], ug[i][1], ug[i][2], ug[i][3], mapa(fb + FB_FAR, 1));
        else for (int i = 0; i < 2; i++) sts128(yd + 512 * i, ug[i][0], ug[i][1], ug[i][2], ug[i][3]);
        __syncwarp();
        if (warp == TW) TSTAMP(18 + (seq != 0));
    } while (seq);
    if (warp >= 12) TSTAMP(12 + warp);
    return key;
}
__device__ __forceinline__ void mini_out(const Params& p, const CUtensorMap* maps, uint32_t sb, int warp, int lane, int f, unsigned epoch, uint32_t key) {
    const int g = lane >> 2, t = lane & 3, mi = lane >> 3, r8 = lane & 7;
    const uint32_t fb = sb + SF_MISC;
    const bool ism = f >= NW;
    const int ch0 = mini_ch0(f);
    const int k = ism ? warp >> 3 : 0;
    uint32_t first = 1;
    if (lane == 0) asm volatile("atom.shared.exch.b32 %0, [%1], 1;" : "=r"(first) : "r"(fb + FS_BM + 64 + 4 * k) : "memory");
    if (!__all_sync(0xffffffffu, first)) {
        if (elect()) prefetch_map(maps + 6);
        const int row = key_row(wait_sel(p, (ch0 + 16 * k) >> 5, r8, key_tag(epoch), key));
        if (row < 512) asm volatile("red.shared.or.b32 [%0], %1;" :: "r"(fb + FS_BM + (row >> 5) * 4), "r"(1u << (row & 31)) : "memory");
        if (k) mbar_wait_cluster(fb + FB_FAR);
    }
    const int m = warp & 7, dr = 64 * (g >> 1) + 16 * (t >> 1) + 8 * (g & 1);
    const uint32_t y = SM_Y + ((r8 >> 1) & 1) * 8512 + (2 * mi + (r8 & 1)) * 1056 + (2 * m + (r8 >> 2)) * 16;
    const uint32_t so = (g >> 1) * 128 + (t >> 1) * 64 + (g & 1) * 32 + (t & 1) * 16;
    bar_sync(BAR_M - k, ism ? 256 : NTHR);
#pragma unroll 1
    for (int h = ism ? 0 : warp >> 3;; h++) {
        const int r0 = 256 * h + 32 * (m & 1) + (m >> 1), row = r0 + dr;
        const uint32_t bm = lds32(fresh(fb) + FS_BM + (row >> 5) * 4) >> (row & 31), ab = fresh(sb - 49152 * k + 512 * h), stg = ab + SM_UT + 2048 * m + 512 * h;
        uint32_t x[2][4];
        ldsm4t(x[0], ab + y); ldsm4t(x[1], ab + y + 256);
        if (warp == 0 && x[0][0] != 0x12345) TSTAMP(28);
        if (__any_sync(0xffffffffu, bm & 0x11u)) {
#pragma unroll
            for (int i = 0; i < 2; i++) store_or_add(p.out + (size_t)(row + 4 * i) * DM + ch0 + 16 * k + 8 * (t & 1), x[i], bm & (1u << (4 * i)));
        } else {
#pragma unroll
            for (int i = 0; i < 2; i++) sts128(stg + so + 512 * i, x[i][0], x[i][1], x[i][2], x[i][3]);
            asm volatile("fence.proxy.async.shared::cta;" ::: "memory");
            __syncwarp();
            if (elect()) store_rows(maps + 6, stg, ch0 + 16 * k, r0);
        }
        if (h >= ism) break;
    }
    if (elect()) { asm volatile("cp.async.bulk.commit_group;" ::: "memory"); asm volatile("cp.async.bulk.wait_group.read 0;" ::: "memory"); }
    if (warp == 8) TSTAMP(11);
    if (warp == 0) { TSTAMP(15); TFLUSH(); }
}

constexpr int SMEM_BYTES = 232448;
static_assert(SF_MISC + 1152 <= 232192, "layout");

struct Maps { CUtensorMap m[7]; };

__global__ void __cluster_dims__(2, 1, 1) __launch_bounds__(NTHR, 1)
fused_kernel(const Params p, const __grid_constant__ Maps maps) {
    extern __shared__ __align__(1024) uint8_t smem_raw[];
    uint32_t q[8];
    {
        const int b = role(blockIdx.x), x = threadIdx.x, rc = 5 * b + (b & ~3) + 4 + (x >> 6);
        const int cv = (unsigned)b < NW ? 0 : -1, ca = (b < 0 ? 8 * b + DM : 48 * b - 2300) + ((x >> 5) & 3), cb = 2 * rc - (rc & 3) + 4;
        const uint32_t ch = (ca & cv) | (cb & ~cv), o = NST * ch + 2 * ((x & 31) + ((x >> (cv & 2)) & 32));
        const bool c = x < (cv ? 256 : 320);
        q[6] = ldg16_if(c, p.logdt + ch);
        q[2] = ldg32_if(c, p.Bre + o); q[3] = ldg32_if(c, p.Bim + o); q[4] = ldg32_if(c, p.Cre + o); q[5] = ldg32_if(c, p.Cim + o); q[0] = ldg32_if(c, p.Are + o); q[1] = ldg32_if(c, p.Aim + o);
        q[7] = ldg16_if(c, p.Dskip + ch);
    }
    const unsigned epoch = ld_rlx32(&p.s->epoch[blockIdx.x * 16 + (threadIdx.x >> 5)]);
    const uint32_t sb = __shfl_sync(0xffffffffu, smem_u32(smem_raw), 0);
    const int warp = __shfl_sync(0xffffffffu, threadIdx.x >> 5, 0), bid = __shfl_sync(0xffffffffu, blockIdx.x, 0);
    const int lane = __shfl_sync(0xffffffffu, threadIdx.x & 31, threadIdx.x);
    const bool conv = bid < NCONV;
    const int f = role(bid);
    uint32_t w[12];
    uint64_t v[6];
    const bool four = (unsigned)f >= NW;
    if (warp < (four ? 8 : 10)) {
        const int half = four ? warp >> 2 : warp & 1, pr = four ? warp & 3 : warp >> 1;
        const int rc = 5 * f + (f & ~3) + 4 + pr;
        const uint32_t stage = sb + (conv ? SC_KG : SF_KG) + warp * KG_STAGE;
        uint4* const kp = p.s->kp + (four ? (conv ? 8 * bid : 48 * f - 2300) + pr : 2 * rc - (rc & 3) + 4) * 96 + lane;
        kgen(q, sb, half, stage, stage + (four ? 4 : 1) * KG_STAGE, 1 + pr, lane, w, [&] {
            sts128z_if(conv && lane < 20, sb + SC_KT + warp * KT_BYTES + lane * 16 + (lane < 4 ? 0 : lane < 14 ? 2048 : 2288));
            stg128z_if(!conv, kp + 64 * half); stg128z_if(!half && !conv, kp + 32);
            stg128z_if((unsigned)f < NW && warp < 6, (uint4*)(p.s->h + ((lane >> 4) * 288 + 6 * f + warp) * 32) + (lane & 15));
            if (!conv) bar_sync(0, NTHR);
            if ((unsigned)f >= NX) asm volatile("barrier.cluster.arrive.relaxed.aligned;" ::: "memory");
        });
        if (!half) publish_k(kp, w, epoch, v);
        else for (int i = 0; i < 6; i++) v[i] = 0;
        if (conv) { conv_main(p, sb, warp, lane, bid, epoch, w); return; }
        {
            if (!half && lane == 0) mbar_arrive(sb + SF_MISC + FB_KDONE);
            if (warp == 0) TSTAMP(22);
            if (warp == 2) TSTAMP(23);
        }
    } else if (conv) {
        conv_aux(p, maps.m, sb, warp - 8, lane, bid, epoch);
        return;
    } else {
        ffn_front(p, maps.m, sb, warp, lane, f, epoch);
        for (int i = 0; i < 6; i++) v[i] = 0;
    }
    converged();
    next_epoch(p, epoch);
    if (warp >= 12 && f < NX) return;
    mini_out(p, maps.m, sb, warp, lane, f, epoch, mini_conv(p, sb, warp, __shfl_sync(0xffffffffu, lane, lane), f, epoch, v));
}

typedef CUresult (*EncodeFn)(CUtensorMap*, CUtensorMapDataType, cuuint32_t, void*, const cuuint64_t*, const cuuint64_t*, const cuuint32_t*, const cuuint32_t*,
                             CUtensorMapInterleave, CUtensorMapSwizzle, CUtensorMapL2promotion, CUtensorMapFloatOOBfill);

void make_map(EncodeFn fn, CUtensorMap* m, const void* base, int rank, const cuuint64_t* dims, const cuuint64_t* strides, const cuuint32_t* box, CUtensorMapSwizzle sw) {
    const cuuint32_t es[5] = {1, 1, 1, 1, 1};
    fn(m, CU_TENSOR_MAP_DATA_TYPE_BFLOAT16, rank, (void*)base, dims, strides, box, es, CU_TENSOR_MAP_INTERLEAVE_NONE, sw,
       CU_TENSOR_MAP_L2_PROMOTION_NONE, CU_TENSOR_MAP_FLOAT_OOB_FILL_NONE);
}

}

extern "C" void kernel_launch(void* const* d_in, const int* in_sizes, int n_in, void* d_out, int out_size) {
    (void)in_sizes; (void)n_in; (void)out_size;
    static EncodeFn fn = nullptr;
    static void* scratch = nullptr;
    if (!fn) {
        void* ptr = nullptr; cudaDriverEntryPointQueryResult qr;
        cudaGetDriverEntryPoint("cuTensorMapEncodeTiled", &ptr, cudaEnableDefault, &qr);
        fn = (EncodeFn)ptr;
        cudaGetSymbolAddress(&scratch, g_scratch);
        cudaFuncSetAttribute(fused_kernel, cudaFuncAttributeMaxDynamicSharedMemorySize, SMEM_BYTES);
    }
    typedef const __nv_bfloat16* bp;
    Params p;
    p.u = (bp)d_in[0]; p.Are = (bp)d_in[1]; p.Aim = (bp)d_in[2]; p.Bre = (bp)d_in[3]; p.Bim = (bp)d_in[4]; p.Cre = (bp)d_in[5]; p.Cim = (bp)d_in[6];
    p.logdt = (bp)d_in[7]; p.Dskip = (bp)d_in[8]; p.wr = (bp)d_in[10]; p.gatew = (bp)d_in[14];
    p.out = (__nv_bfloat16*)d_out; p.s = (Scratch*)scratch; p.zero = 0;
    Maps maps;
    {
        const cuuint64_t dims[4] = {DM, 4, 16, 32}, strides[3] = {16 * DM * 2, DM * 2, 64 * DM * 2};
        const cuuint32_t box[4] = {16, 4, 16, 2};
        make_map(fn, &maps.m[0], d_in[0], 4, dims, strides, box, CU_TENSOR_MAP_SWIZZLE_32B);
        const cuuint32_t box2[4] = {16, 4, 16, 8};
        make_map(fn, &maps.m[5], d_in[0], 4, dims, strides, box2, CU_TENSOR_MAP_SWIZZLE_32B);
    }
    for (int i = 0; i < 2; i++) {
        const cuuint64_t dims[3] = {32, DM, FF / 32}, strides[2] = {FF * 2, 64};
        const cuuint32_t box[3] = {32, 64, 3};
        make_map(fn, &maps.m[1 + i], d_in[11 + i], 3, dims, strides, box, CU_TENSOR_MAP_SWIZZLE_64B);
    }
    {
        const cuuint64_t dims[2] = {DM, FF}, strides[1] = {DM * 2};
        const cuuint32_t box[2] = {32, 192};
        make_map(fn, &maps.m[3], d_in[13], 2, dims, strides, box, CU_TENSOR_MAP_SWIZZLE_64B);
    }
    {
        const cuuint64_t dims[5] = {DM, 2, 4, 4, L_SEQ}, strides[4] = {16 * DM * 2, 64 * DM * 2, 4 * DM * 2, DM * 2};
        const cuuint32_t box[5] = {16, 2, 4, 4, 1};
        make_map(fn, &maps.m[4], d_out, 5, dims, strides, box, CU_TENSOR_MAP_SWIZZLE_NONE);
    }
    {
        const cuuint64_t dims[5] = {DM, 4, 4, 2, L_SEQ}, strides[4] = {8 * DM * 2, 64 * DM * 2, 4 * DM * 2, DM * 2};
        const cuuint32_t box[5] = {16, 4, 4, 2, 1};
        make_map(fn, &maps.m[6], d_out, 5, dims, strides, box, CU_TENSOR_MAP_SWIZZLE_NONE);
    }
    fused_kernel<<<NCTA, NTHR, SMEM_BYTES>>>(p, maps);
}
```

```cpp
#include <cuda_runtime.h>
#include <cuda_bf16.h>
#include <cuda_fp16.h>
#include <cuda.h>
#include <stdint.h>
#include <type_traits>

#define RESUME 300
#define MDELAY 2000
#define MGAP 0
#define KPOLL 650
#define DPA 7
#define DPB 9
#define RDELAY 900
#define WDELAY 2000
#define WGAP 290
#define NPRE 7
#define DGAP 260
namespace {

constexpr int DM = 576, NST = 128, FF = 4608, L_SEQ = 2048;
constexpr int NCONV = 72, NX = 36, NW = 48, NCTA = 132, NTHR = 512;

struct __align__(128) Scratch {
    unsigned epoch[NCTA * 16];
    uint4 keys[16 * 128];
    uint32_t sel[18 * 64];
    uint16_t gate[L_SEQ];
    uint2 h[2 * 288 * 32];
    uint4 kp[DM * 96];
};
__device__ Scratch g_scratch;
#define TFLUSH()
#define TSTAMP(i)
#define TW 12

struct Params {
    const __nv_bfloat16 *Are, *Aim, *Bre, *Bim, *Cre, *Cim, *logdt, *Dskip, *u, *wr, *gatew;
    __nv_bfloat16* out;
    Scratch* s;
    uint32_t zero;
};

__device__ __forceinline__ void give_up() { asm volatile("trap; exit;"); __builtin_unreachable(); }
__device__ __forceinline__ void converged() { __syncwarp(); asm volatile("{ .reg .b32 t; mov.b32 t, 0; movmatrix.sync.aligned.m8n8.trans.b16 t, t; }" ::: "memory"); }
__device__ __forceinline__ bool elect() { uint32_t r; asm volatile("{ .reg .pred p; elect.sync _|p, 0xffffffff; selp.u32 %0, 1, 0, p; }" : "=r"(r)); return r; }
__device__ __forceinline__ uint32_t smem_u32(const void* p) { return (uint32_t)__cvta_generic_to_shared(p); }
__device__ __forceinline__ uint32_t pack_bf16(float lo, float hi) { uint32_t r; asm("cvt.rn.bf16x2.f32 %0, %1, %2;" : "=r"(r) : "f"(hi), "f"(lo)); return r; }
__device__ __forceinline__ uint32_t pack_f16(float lo, float hi) { uint32_t r; asm("cvt.rn.f16x2.f32 %0, %1, %2;" : "=r"(r) : "f"(hi), "f"(lo)); return r; }
__device__ __forceinline__ float bf_lo(uint32_t w) { return __uint_as_float(w << 16); }
__device__ __forceinline__ float bf_hi(uint32_t w) { return __uint_as_float(w & 0xffff0000u); }
__device__ __forceinline__ float rbf(float x) { return bf_lo(pack_bf16(x, 0.f)); }
__device__ __forceinline__ uint32_t badd2(uint32_t a, uint32_t b) { uint32_t r; asm("add.rn.bf16x2 %0, %1, %2;" : "=r"(r) : "r"(a), "r"(b)); return r; }
__device__ __forceinline__ uint32_t bsub2(uint32_t a, uint32_t b) { uint32_t r; asm("sub.rn.bf16x2 %0, %1, %2;" : "=r"(r) : "r"(a), "r"(b)); return r; }
__device__ __forceinline__ uint32_t gmix(uint32_t ng, float ny0, float ny1, uint32_t u) {
    uint32_t r; asm("{ .reg .b32 t; fma.rn.bf16x2 t, %1, %3, %3; fma.rn.bf16x2 %0, %1, %2, t; }" : "=r"(r) : "r"(ng), "r"(pack_bf16(ny0, ny1)), "r"(u)); return r;
}
__device__ __forceinline__ void mma_bf(float (&c)[4], uint32_t a0, uint32_t a1, uint32_t a2, uint32_t a3, uint32_t b0, uint32_t b1) {
    asm("mma.sync.aligned.m16n8k16.row.col.f32.bf16.bf16.f32 {%0,%1,%2,%3}, {%4,%5,%6,%7}, {%8,%9}, {%0,%1,%2,%3};"
        : "+f"(c[0]), "+f"(c[1]), "+f"(c[2]), "+f"(c[3]) : "r"(a0), "r"(a1), "r"(a2), "r"(a3), "r"(b0), "r"(b1));
}
__device__ __forceinline__ void mma_bf8(float (&c)[4], uint32_t a0, uint32_t a1, uint32_t b0) {
    asm("mma.sync.aligned.m16n8k8.row.col.f32.bf16.bf16.f32 {%0,%1,%2,%3}, {%4,%5}, {%6}, {%0,%1,%2,%3};"
        : "+f"(c[0]), "+f"(c[1]), "+f"(c[2]), "+f"(c[3]) : "r"(a0), "r"(a1), "r"(b0));
}
__device__ __forceinline__ void mma_h(float (&c)[4], uint32_t a0, uint32_t a1, uint32_t a2, uint32_t a3, uint32_t b0, uint32_t b1) {
    asm("mma.sync.aligned.m16n8k16.row.col.f32.f16.f16.f32 {%0,%1,%2,%3}, {%4,%5,%6,%7}, {%8,%9}, {%0,%1,%2,%3};"
        : "+f"(c[0]), "+f"(c[1]), "+f"(c[2]), "+f"(c[3]) : "r"(a0), "r"(a1), "r"(a2), "r"(a3), "r"(b0), "r"(b1));
}
__device__ __forceinline__ uint32_t fresh(uint32_t a) { asm volatile("" : "+r"(a) :: "memory"); return a; }
__device__ __forceinline__ uint32_t lds32(uint32_t a) { uint32_t v; asm("ld.shared.u32 %0, [%1];" : "=r"(v) : "r"(a)); return v; }
__device__ __forceinline__ uint2 lds64(uint32_t a) { uint2 v; asm("ld.shared.v2.u32 {%0,%1}, [%2];" : "=r"(v.x), "=r"(v.y) : "r"(a)); return v; }
__device__ __forceinline__ uint4 lds128(uint32_t a) { uint4 v; asm("ld.shared.v4.u32 {%0,%1,%2,%3}, [%4];" : "=r"(v.x), "=r"(v.y), "=r"(v.z), "=r"(v.w) : "r"(a)); return v; }
__device__ __forceinline__ void ldsm4(uint32_t (&r)[4], uint32_t a) {
    asm("ldmatrix.sync.aligned.m8n8.x4.shared.b16 {%0,%1,%2,%3}, [%4];" : "=r"(r[0]), "=r"(r[1]), "=r"(r[2]), "=r"(r[3]) : "r"(a));
}
__device__ __forceinline__ void ldsm4t(uint32_t (&r)[4], uint32_t a) {
    asm("ldmatrix.sync.aligned.m8n8.x4.trans.shared.b16 {%0,%1,%2,%3}, [%4];" : "=r"(r[0]), "=r"(r[1]), "=r"(r[2]), "=r"(r[3]) : "r"(a));
}
__device__ __forceinline__ void sts16(uint32_t a, uint32_t v) { asm volatile("st.shared.u16 [%0], %1;" :: "r"(a), "h"((unsigned short)v) : "memory"); }
__device__ __forceinline__ void sts32(uint32_t a, uint32_t v) { asm volatile("st.shared.u32 [%0], %1;" :: "r"(a), "r"(v) : "memory"); }
__device__ __forceinline__ void sts64(uint32_t a, uint32_t x, uint32_t y) { asm volatile("st.shared.v2.u32 [%0], {%1,%2};" :: "r"(a), "r"(x), "r"(y) : "memory"); }
__device__ __forceinline__ void sts128(uint32_t a, uint32_t x, uint32_t y, uint32_t z, uint32_t w) {
    asm volatile("st.shared.v4.u32 [%0], {%1,%2,%3,%4};" :: "r"(a), "r"(x), "r"(y), "r"(z), "r"(w) : "memory");
}
__device__ __forceinline__ void st_async128(uint32_t a, uint32_t x, uint32_t y, uint32_t z, uint32_t w, uint32_t bar) {
    asm volatile("st.async.weak.shared::cluster.mbarrier::complete_tx::bytes.v4.b32 [%0], {%1,%2,%3,%4}, [%5];" :: "r"(a), "r"(x), "r"(y), "r"(z), "r"(w), "r"(bar) : "memory");
}
__device__ __forceinline__ void mbar_init(uint32_t b, uint32_t cnt) { asm volatile("mbarrier.init.shared::cta.b64 [%0], %1;" :: "r"(b), "r"(cnt) : "memory"); }
__device__ __forceinline__ void mbar_fence() { asm volatile("fence.mbarrier_init.release.cluster;" ::: "memory"); }
__device__ __forceinline__ void mbar_expect(uint32_t b, uint32_t bytes) { asm volatile("mbarrier.arrive.expect_tx.shared::cta.b64 _, [%0], %1;" :: "r"(b), "r"(bytes) : "memory"); }
__device__ __forceinline__ void mbar_arrive(uint32_t b) { asm volatile("mbarrier.arrive.shared::cta.b64 _, [%0];" :: "r"(b) : "memory"); }
__device__ __forceinline__ void mbar_wait(uint32_t b, uint32_t parity = 0) {
    asm volatile("{ .reg .pred p; .reg .u32 n; mov.u32 n, 0;\n"
                 "LW: mbarrier.try_wait.parity.shared::cta.b64 p, [%0], %1; @p bra LD; add.u32 n, n, 1; setp.lt.u32 p, n, 65536; @p bra LW; trap;\n"
                 "LD: }" :: "r"(b), "r"(parity) : "memory");
}
__device__ __forceinline__ void mbar_wait_cluster(uint32_t b) {
    asm volatile("{ .reg .pred p; .reg .u32 n; mov.u32 n, 0;\n"
                 "LW: mbarrier.try_wait.parity.acquire.cluster.shared::cta.b64 p, [%0], 0; @p bra LD; add.u32 n, n, 1; setp.lt.u32 p, n, 65536; @p bra LW; trap;\n"
                 "LD: }" :: "r"(b) : "memory");
}
__device__ __forceinline__ void tma2d(uint32_t dst, const CUtensorMap* m, int c0, int c1, uint32_t bar) {
    asm volatile("cp.async.bulk.tensor.2d.shared::cluster.global.mbarrier::complete_tx::bytes [%0], [%1, {%3, %4}], [%2];"
                 :: "r"(dst), "l"(m), "r"(bar), "r"(c0), "r"(c1) : "memory");
}
__device__ __forceinline__ void tma3d(uint32_t dst, const CUtensorMap* m, int c0, int c1, int c2, uint32_t bar) {
    asm volatile("cp.async.bulk.tensor.3d.shared::cluster.global.mbarrier::complete_tx::bytes [%0], [%1, {%3, %4, %5}], [%2];"
                 :: "r"(dst), "l"(m), "r"(bar), "r"(c0), "r"(c1), "r"(c2) : "memory");
}
__device__ __forceinline__ void tma4d(uint32_t dst, const CUtensorMap* m, int c0, int c1, int c2, int c3, uint32_t bar) {
    asm volatile("cp.async.bulk.tensor.4d.shared::cluster.global.mbarrier::complete_tx::bytes [%0], [%1, {%3, %4, %5, %6}], [%2];"
                 :: "r"(dst), "l"(m), "r"(bar), "r"(c0), "r"(c1), "r"(c2), "r"(c3) : "memory");
}
__device__ __forceinline__ void bulk_g2s(uint32_t dst, const void* src, uint32_t bytes, uint32_t bar) {
    asm volatile("cp.async.bulk.shared::cluster.global.mbarrier::complete_tx::bytes [%0], [%1], %2, [%3];"
                 :: "r"(dst), "l"(src), "r"(bytes), "r"(bar) : "memory");
}
__device__ __forceinline__ uint32_t mapa(uint32_t a, uint32_t rank) { uint32_t r; asm("mapa.shared::cluster.u32 %0, %1, %2;" : "=r"(r) : "r"(a), "r"(rank)); return r; }
__device__ __forceinline__ void prefetch_map(const CUtensorMap* m) { asm volatile("prefetch.tensormap [%0];" :: "l"(m) : "memory"); }
__device__ __forceinline__ void bar_sync(int id, int n) { asm volatile("bar.sync %0, %1;" :: "r"(id), "r"(n) : "memory"); }
__device__ __forceinline__ void bar_arrive(int id, int n) { asm volatile("bar.arrive %0, %1;" :: "r"(id), "r"(n) : "memory"); }
__device__ __forceinline__ uint32_t ldg16_if(bool c, const void* p) { uint32_t v; asm volatile("{ .reg .pred p; setp.ne.u32 p, %2, 0; @p ld.global.nc.u16 %0, [%1]; }" : "=r"(v) : "l"(p), "r"((uint32_t)c)); return v; }
__device__ __forceinline__ uint32_t ldg32_if(bool c, const void* p) { uint32_t v; asm volatile("{ .reg .pred p; setp.ne.u32 p, %2, 0; @p ld.global.nc.u32 %0, [%1]; }" : "=r"(v) : "l"(p), "r"((uint32_t)c)); return v; }
__device__ __forceinline__ uint32_t ld_rlx32(const void* p) { uint32_t v; asm volatile("ld.relaxed.gpu.global.u32 %0, [%1];" : "=r"(v) : "l"(p) : "memory"); return v; }
__device__ __forceinline__ uint4 ld_rlx128(const void* p) {
    uint4 v; asm volatile("ld.relaxed.gpu.global.v4.u32 {%0,%1,%2,%3}, [%4];" : "=r"(v.x), "=r"(v.y), "=r"(v.z), "=r"(v.w) : "l"(p) : "memory"); return v;
}
__device__ __forceinline__ void st_rlx32(void* p, uint32_t v) { asm volatile("st.relaxed.gpu.global.u32 [%0], %1;" :: "l"(p), "r"(v) : "memory"); }
__device__ __forceinline__ void stg128(void* p, uint32_t x, uint32_t y, uint32_t z, uint32_t w) {
    asm volatile("st.global.v4.u32 [%0], {%1,%2,%3,%4};" :: "l"(p), "r"(x), "r"(y), "r"(z), "r"(w) : "memory");
}
__device__ __forceinline__ void next_epoch(const Params& p, unsigned e) { if ((threadIdx.x & 31) == 0) p.s->epoch[blockIdx.x * 16 + (threadIdx.x >> 5)] = e + 1; }
__device__ __forceinline__ void sts128z_if(bool c, uint32_t a) { asm volatile("{ .reg .pred p; setp.ne.u32 p, %1, 0; @p st.shared.v4.u32 [%0], {%2,%2,%2,%2}; }" :: "r"(a), "r"((uint32_t)c), "r"(0) : "memory"); }
__device__ __forceinline__ void stg128z_if(bool c, void* a) { asm volatile("{ .reg .pred p; setp.ne.u32 p, %1, 0; @p st.global.v4.u32 [%0], {%2,%2,%2,%2}; }" :: "l"(a), "r"((uint32_t)c), "r"(0) : "memory"); }
__device__ __forceinline__ unsigned clock32() { unsigned c; asm volatile("mov.u32 %0, %clock;" : "=r"(c) :: "memory"); return c; }
__device__ __forceinline__ void until(unsigned t0, int c) { while ((int)(clock32() - t0) < c) { } }
__device__ __forceinline__ float sigmoidf_(float x) { return __fdividef(1.0f, 1.0f + __expf(-x)); }
__device__ __forceinline__ uint32_t key_tag(unsigned epoch) { return ((epoch & 15u) | 16u) << 11; }
__device__ __forceinline__ int key_row(uint32_t key) { return 2047 - (int)(key & 2047u); }
__device__ __forceinline__ uint32_t wait_sel(const Params& p, int s32, int r8, uint32_t tag, uint32_t k = 0) {
#pragma unroll 1
    for (int it = 0; !__all_sync(0xffffffffu, (k & 0xf800u) == tag); it++) {
        k = ld_rlx32(&p.s->sel[s32 * 64 + r8]);
        if (it > (1 << 20)) give_up();
    }
    return k;
}

struct cplx { float re, im; };
__device__ __forceinline__ cplx csq(cplx a) { cplx r; r.re = a.re * a.re - a.im * a.im; r.im = (a.re * a.im) * 2.f; return r; }
__device__ __forceinline__ cplx cexpk(float ar, float ai, float k) {
    float mag, s, c;
    asm("ex2.approx.ftz.f32 %0, %1;" : "=f"(mag) : "f"(ar * (k * 1.4426950408889634f)));
    const float r = ai * k;
    asm("sin.approx.ftz.f32 %0, %1;" : "=f"(s) : "f"(r));
    asm("cos.approx.ftz.f32 %0, %1;" : "=f"(c) : "f"(r));
    cplx o; o.re = mag * c; o.im = mag * s; return o;
}
struct h2c { uint32_t re, im; };
__device__ __forceinline__ h2c cmul_cd(h2c v, __half2 c, __half2 d) {
    const __half2 r = *(const __half2*)&v.re, i = *(const __half2*)&v.im;
    const __half2 x = __hfma2(__hneg2(i), d, __hmul2(r, c)), y = __hfma2(i, c, __hmul2(r, d));
    h2c o; o.re = *(const uint32_t*)&x; o.im = *(const uint32_t*)&y; return o;
}
__device__ __forceinline__ h2c cmul_s(h2c v, uint32_t s) { const __half2 h = *(const __half2*)&s; return cmul_cd(v, __low2half2(h), __high2half2(h)); }
__device__ __forceinline__ h2c cmul_sc(h2c v, uint32_t s) {
    const __half2 h = *(const __half2*)&s, c = __low2half2(h), d = __high2half2(h), r = *(const __half2*)&v.re, i = *(const __half2*)&v.im;
    const __half2 x = __hfma2(i, d, __hmul2(r, c)), y = __hfma2(__hneg2(r), d, __hmul2(i, c));
    h2c o; o.re = *(const uint32_t*)&x; o.im = *(const uint32_t*)&y; return o;
}
__device__ __forceinline__ h2c cmul_vc(h2c v, uint32_t s) {
    const __half2 h = *(const __half2*)&s, c = __low2half2(h), d = __high2half2(h), r = *(const __half2*)&v.re, i = *(const __half2*)&v.im;
    const __half2 x = __hfma2(i, d, __hmul2(r, c)), y = __hfma2(__hneg2(i), c, __hmul2(r, d));
    h2c o; o.re = *(const uint32_t*)&x; o.im = *(const uint32_t*)&y; return o;
}

constexpr int UT_HALF = 2560, UT_STRIDE = 4736, GT_HALF = 2240;
__device__ __forceinline__ uint32_t swz(uint32_t x, int c) { return x ^ (((x >> 2) & 64) ^ (64 * (c & 1) + 8 * (c & 6))); }
__device__ __forceinline__ int col(int n) { return (n >> 1) + 4 * (n & 1); }
constexpr int KT_T = 542, KT_C = 552, KT_D = 645, KT_BYTES = 720 * 4;
constexpr int VC_OFF = 80, VE_BASE = 1616;
constexpr int V_STRIDE = (1616 + 1024) * 4 + 80;
constexpr int KG_STAGE = 5248;
constexpr int Y_CS = 2080, Y_RS = 8 * Y_CS + 64;

constexpr int SC_RT = 0;
constexpr int SC_UT = 33408;
constexpr int SC_KG = SC_UT + 8 * UT_STRIDE;
constexpr int SC_KT = SC_KG + 8 * KG_STAGE;
constexpr int SC_GT = SC_KT + 8 * KT_BYTES;
constexpr int SC_V = SC_GT + 4448;
constexpr int SC_MISC = SC_V + 8 * V_STRIDE;
static_assert(V_STRIDE % 128 == 16 && 2 * Y_RS <= SC_UT && SC_UT % 128 == 0 && SC_KG % 128 == 0, "layout");
static_assert(SC_MISC % 16 == 0 && SC_MISC + 512 <= 232192, "layout");

__device__ __forceinline__ void window_task(uint32_t s0, uint32_t s1, uint32_t d0, uint32_t d1, int k) {
    float S[51], s = 0.f;
    uint32_t w[28];
#pragma unroll
    for (int i = 0; i < 7; i++) {
        const uint4 v = lds128(((i < 3 ? s0 : s1) ^ 8 * ((i + 1) & 2)) + ((i & 1) ? 0 : UT_HALF));
        w[4 * i] = v.x; w[4 * i + 1] = v.y; w[4 * i + 2] = v.z; w[4 * i + 3] = v.w;
    }
    auto sums = [&](int lo, int hi) {
#pragma unroll
        for (int i = lo; i < hi; i++) { const float x = (i & 1) ? bf_hi(w[i >> 1]) : bf_lo(w[i >> 1]); s = i > 3 ? s + x : x; S[i] = s; }
    };
    auto put = [&](int off, int b, int o0, int o1, int o2) {
        auto v = [&](int i) { i += 16 * b; return pack_bf16(S[o0 + i] - S[o1 + i], S[o1 + i] - S[o2 + i]); };
#pragma unroll
        for (int i = 0; i < 8; i += 2) sts128((i & 4 ? d1 : d0) + 4 * off + 64 * b + 8 * (i & 2), v(i), v(i + 8), v(i + 1), v(i + 9));
    };
    S[2] = 0.f;
    sums(3, 26); put(VC_OFF - 16, 0, 10, 5, 2);
    if (k == 12) return;
    sums(26, 42); put(VC_OFF - 16, 1, 10, 5, 2);
    if (k < 8) { put(VE_BASE, 0, 19, 12, 3); sums(42, 51); put(VE_BASE, 1, 19, 12, 3); }
}

template <class F>
__device__ __forceinline__ void kgen(const uint32_t (&q)[8], uint32_t sb, int half, uint32_t stage, uint32_t pstage, int barid, int lane, uint32_t (&w)[12], F shadow) {
    const int t = lane & 3, mi = lane >> 3, r8 = lane & 7;
    {
        const uint32_t pAr = q[0], pAi = q[1], pBr = q[2], pBi = q[3], pCr = q[4], pCi = q[5], pDt = q[6], pD = q[7];
        const uint32_t wb = fresh(stage + lane * 16), za = fresh(stage + 5120 + ((lane >> 1) & 3) * 16 + mi * 4 + (lane & 1) * 2), zr = fresh(stage + 5120 + t * 16);
        const uint32_t oA = fresh(stage + (mi & 1) * 1024 + (mi >> 1) * 512 + r8 * 16), oB = fresh(stage + 2048 + mi * 512 + r8 * 16), oC = fresh(stage + 4096 + (mi & 1) * 512 + (mi >> 1) * 128 + r8 * 16);
        float acc[6][4];
#pragma unroll
        for (int a = 0; a < 6; a++) { acc[a][0] = acc[a][1] = acc[a][2] = acc[a][3] = 0.f; asm volatile("" : "+f"(acc[a][0]), "+f"(acc[a][1]), "+f"(acc[a][2]), "+f"(acc[a][3])); }
        shadow();
        sts32(zr, clock32());
        const float dt = rbf(__expf(bf_lo(pDt)));
        float ar = dt * bf_lo(pAr), ai = dt * bf_lo(pAi), ar1 = dt * bf_hi(pAr), ai1 = dt * bf_hi(pAi);
        float wr, wi, wr1, wi1;
        { const float br = dt * bf_lo(pBr), bi = dt * bf_lo(pBi), cr = bf_lo(pCr), ci = bf_lo(pCi); wr = cr * br - ci * bi; wi = cr * bi + ci * br; }
        { const float br = dt * bf_hi(pBr), bi = dt * bf_hi(pBi), cr = bf_hi(pCr), ci = bf_hi(pCi); wr1 = cr * br - ci * bi; wi1 = cr * bi + ci * br; }
        const uint32_t ex = max(__reduce_max_sync(0xffffffffu, __float_as_uint(fmaxf(fmaxf(fabsf(wr), fabsf(wi)), fmaxf(fabsf(wr1), fabsf(wi1))))) >> 23, 14u);
        const float scl = __uint_as_float((267u - ex) << 23);
        uint32_t W = pack_f16(wr * scl, wi * -scl);
        const uint32_t W1 = pack_f16(wr1 * scl, wi1 * -scl);
        if (threadIdx.x < 32) TSTAMP(20);

#pragma unroll 1
        for (int r = 0; r < 2; r++) {
            const cplx z1 = cexpk(ar, ai, 1.f), z64 = cexpk(ar, ai, 64.f);
            const cplx z2 = csq(z1), z4 = csq(z2), z8 = csq(z4), z16 = csq(z8), z32 = csq(z16);
            const cplx z128 = csq(z64), z256 = csq(z128), z512 = csq(z256);
            auto put = [&](int grp, h2c a, h2c b, h2c c, h2c d) { sts128(wb + grp * 1024, a.re, b.re, c.re, d.re); sts128(wb + grp * 1024 + 512, a.im, b.im, c.im, d.im); };
            {
                const uint32_t s4 = pack_f16(z4.re, z4.im), s256 = pack_f16(z256.re, z256.im), s512 = pack_f16(z512.re, z512.im);
                auto mix = [](h2c a, h2c b, uint32_t sel) { return h2c{__byte_perm(a.re, b.re, sel), __byte_perm(a.im, b.im, sel)}; };
                const h2c c10 = cmul_vc(h2c{pack_f16(z1.re, 1.f), pack_f16(z1.im, 0.f)}, W), c32 = cmul_sc(c10, pack_f16(z2.re, z2.im)), c54 = cmul_sc(c10, s4);
                put(2, c10, c32, c54, cmul_sc(c32, s4));
                const h2c d20 = cmul_sc(mix(c32, c10, 0x7632), s256), e04 = cmul_sc(mix(c10, c54, 0x7632), s512), f04 = cmul_sc(e04, s256);
                put(3, d20, cmul_sc(d20, s4), e04, f04);
                const h2c ef = mix(e04, f04, 0x5410), gh = cmul_sc(ef, s512), g8 = cmul_sc(gh, pack_f16(z8.re, z8.im));
                put(4, g8, cmul_sc(g8, s512), gh, ef);
            }
            {
                const uint32_t s32 = pack_f16(z32.re, z32.im), s64 = pack_f16(z64.re, z64.im), s128 = pack_f16(z128.re, z128.im);
                const h2c p0 = {pack_f16(1.f, z8.re), pack_f16(0.f, z8.im)}, p1 = cmul_s(p0, pack_f16(z16.re, z16.im)), p2 = cmul_s(p0, s32), p3 = cmul_s(p1, s32);
                put(0, p0, p1, p2, p3);
                put(1, cmul_s(p0, s64), cmul_s(p1, s64), cmul_s(p2, s64), cmul_s(p3, s64));
                sts16(za, s128); sts16(za + 64, s128 >> 16);
            }
            __syncwarp();
            {
                const uint32_t aA = fresh(oA), aB = fresh(oB), aC = fresh(oC), aZ = fresh(zr);
                const uint4 zc = lds128(aZ), zd = lds128(aZ + 64);
                const uint32_t zcs[4] = {zc.x, zc.y, zc.z, zc.w}, zds[4] = {zd.x, zd.y, zd.z, zd.w};
                uint32_t c[4];
#pragma unroll
                for (int k = 0; k < 4; k++) {
                    uint32_t a[4], b[4];
                    ldsm4t(a, aA + 128 * k); ldsm4t(b, aB + 128 * k);
                    if (!(k & 1)) ldsm4t(c, aC + 128 * k);
                    const h2c x = cmul_cd(h2c{a[0], a[2]}, *(const __half2*)&zcs[k], *(const __half2*)&zds[k]), y = cmul_cd(h2c{a[1], a[3]}, *(const __half2*)&zcs[k], *(const __half2*)&zds[k]);
                    mma_h(acc[0], a[0], a[1], a[2], a[3], b[0], b[1]);
                    mma_h(acc[1], a[0], a[1], a[2], a[3], b[2], b[3]);
                    mma_h(acc[2], a[0], a[1], a[2], a[3], c[2 * (k & 1)], c[2 * (k & 1) + 1]);
                    mma_h(acc[3], x.re, y.re, x.im, y.im, b[0], b[1]);
                    mma_h(acc[4], x.re, y.re, x.im, y.im, b[2], b[3]);
                    mma_h(acc[5], x.re, y.re, x.im, y.im, c[2 * (k & 1)], c[2 * (k & 1) + 1]);
                }
                asm volatile("" :: "f"(acc[0][0]), "f"(acc[1][0]), "f"(acc[2][0]), "f"(acc[3][0]), "f"(acc[4][0]), "f"(acc[5][0]) : "memory");
            }
            __syncwarp();
            ar = ar1; ai = ai1; W = W1;
        }
        if (threadIdx.x < 32) TSTAMP(21);
        const float i0 = __uint_as_float((ex + 243u) << 23);
        if (half) {
#pragma unroll
            for (int a = 0; a < 6; a++) { acc[a][0] *= i0; acc[a][1] *= i0; acc[a][2] *= i0; acc[a][3] *= i0; }
            if (lane == 0) acc[0][1] -= bf_lo(pD);
#pragma unroll
            for (int a = 0; a < 6; a++) sts128(wb + a * 512, __float_as_uint(acc[a][0]), __float_as_uint(acc[a][1]), __float_as_uint(acc[a][2]), __float_as_uint(acc[a][3]));
            bar_arrive(barid, 64);
        } else {
            if (blockIdx.x < NCONV) bar_arrive(barid + 8, 64);
            bar_sync(barid, 64);
            const uint32_t src = fresh(pstage);
#pragma unroll
            for (int a = 0; a < 6; a++) {
                const uint4 y = lds128(src + lane * 16 + a * 512);
                auto sum = [&](uint32_t x, float c) { return fmaf(c, i0, __uint_as_float(x)); };
                w[4 * (a % 3) + 2 * (a / 3)] = pack_bf16(sum(y.x, acc[a][0]), sum(y.y, acc[a][1]));
                w[4 * (a % 3) + 2 * (a / 3) + 1] = pack_bf16(sum(y.z, acc[a][2]), sum(y.w, acc[a][3]));
            }
            const uint32_t x0 = __shfl_up_sync(0xffffffffu, w[10], 2), x1 = __shfl_up_sync(0xffffffffu, w[11], 2);
            w[10] = w[8];
            if (t >= 2) { w[8] = x0; w[9] = x1; }
        }
    }
}

enum { BC_AUX = 0, BC_U = 5 };

__device__ __forceinline__ void fetch_gates(const Params& p, int i, int lane, unsigned epoch, uint32_t dst) {
    const uint32_t par = (epoch & 1) ? 0x80008000u : 0u;
    uint4 v;
#pragma unroll 1
    for (int it = 0;; it++) {
        v = ld_rlx128(p.s->gate + 256 * i + 8 * lane);
        v.x ^= par; v.y ^= par; v.z ^= par; v.w ^= par;
        if (__all_sync(0xffffffffu, (v.x & v.y & v.z & v.w & 0x80008000u) == 0x80008000u)) break;
        if (it > (1 << 20)) give_up();
    }
    sts128(dst, v.x, v.y, v.z, v.w);
}
__device__ __forceinline__ void store_rows(const CUtensorMap* m, uint32_t src, int col, int row) {
    asm volatile("cp.async.bulk.tensor.5d.global.shared::cta.bulk_group [%0, {%2, %3, %3, %3, %4}], [%1];" :: "l"(m), "r"(src), "r"(col), "r"(0), "r"(row) : "memory");
}

__device__ __forceinline__ void store_or_add(void* o, const uint32_t (&y)[4], uint32_t add) {
    asm volatile("{ .reg .pred p; setp.ne.u32 p, %5, 0; @!p st.global.v4.u32 [%0], {%1,%2,%3,%4}; @p red.relaxed.gpu.global.add.noftz.v4.bf16x2 [%0], {%1,%2,%3,%4}; }"
                 :: "l"(o), "r"(y[0]), "r"(y[1]), "r"(y[2]), "r"(y[3]), "r"(add) : "memory");
}

__device__ __forceinline__ void conv_aux(const Params& p, const CUtensorMap* mU, uint32_t sb, int aw, int lane, int bid, unsigned epoch) {
    const int g = lane >> 2, t = lane & 3, mi = lane >> 3, r8 = lane & 7;
    const int rank = bid & 1, slab = bid >> 1;
    const uint32_t bar_y = sb + SC_MISC, bar_u = bar_y + 32, bar_v = bar_y + 40, bar_box = bar_y + 64 + 8 * aw, s_bm = bar_y + 128;
    if (elect()) {
        mbar_init(bar_box, 1); mbar_fence();
        mbar_expect(bar_box, 4096);
        tma4d(sb + SC_RT + 4096 * aw, mU, 16 * slab, 0, 0, 16 * rank + 2 * aw, bar_box);
        mbar_init(bar_y + 8 * aw, aw < 4 ? 9 : aw == 5 ? 8 : 1); mbar_fence();
        if (aw < 5) mbar_expect(bar_y + 8 * aw, aw == 4 ? 16384 : 4096);
    }
    __syncwarp();
    asm volatile("barrier.cluster.arrive.relaxed.aligned;" ::: "memory");
    asm volatile("setmaxnreg.dec.sync.aligned.u32 88;");
    sts128(sb + (lane < 16 ? SC_UT + aw * UT_STRIDE + mi * (UT_HALF - 128) : SC_V - 256 + aw * V_STRIDE) + lane * 16, 0, 0, 0, 0);
    if (lane < 16) sts128(s_bm + lane * 16, 0, 0, 0, 0);
    {
        const uint32_t dst = sb + SC_UT + g * UT_STRIDE + swz((8 + 64 * rank + 8 * aw + t) * 16, g);
        const uint32_t rdst = mapa(dst, rank ^ 1), rbar = mapa(bar_u, rank ^ 1);
        asm volatile("barrier.cluster.wait.acquire.aligned;" ::: "memory");
        mbar_wait(bar_box);
        if (aw == 0) TSTAMP(1);
        const uint32_t src = fresh(sb + SC_RT) + aw * 4096 + (8 * mi + 4 * (r8 & 1) + (r8 >> 1)) * 32 + ((rank ^ (r8 & 1)) << 4);
        uint32_t x[8][4];
#pragma unroll
        for (int i = 0; i < 4; i++) { ldsm4t(x[i], src + 1024 * i); ldsm4t(x[4 + i], (src ^ 16) + 1024 * i); }
        asm volatile("" :: "r"(x[0][0]), "r"(x[1][0]), "r"(x[2][0]), "r"(x[3][0]) : "memory");
#pragma unroll
        for (int i = 0; i < 4; i++) st_async128((rdst ^ 32 * (i & 2)) + (i & 1) * UT_HALF, x[4 + i][0], x[4 + i][1], x[4 + i][2], x[4 + i][3], rbar);
#pragma unroll
        for (int i = 0; i < 4; i++) sts128((dst ^ 32 * (i & 2)) + (i & 1) * UT_HALF, x[i][0], x[i][1], x[i][2], x[i][3]);
    }
    bar_sync(BC_AUX, 256);
    mbar_wait_cluster(bar_u);
    if (aw == 0) TSTAMP(2);
    if (aw == 6 && elect()) mbar_arrive(bar_y + 48);
    bar_sync(BC_U + aw, 64);
    if (aw == 0) TSTAMP(3);
    {
        const uint32_t ws = fresh(sb + SC_UT) + r8 * UT_STRIDE, wd = sb + SC_V + r8 * V_STRIDE;
#pragma unroll 1
        for (int k = aw; k < 13; k += 8) {
            const int a = 8 * k + (k < 12 ? g & 6 : 0);
            const uint32_t d = wd + 64 * a, sw = 16 * (a & 2);
            window_task(ws + swz(16 * a + 96, r8), ws + swz(16 * a + 128, r8), d + sw, d + (sw ^ 32), k);
        }
    }
    if (aw == 0) TSTAMP(9);
    {
        if (aw >= 2) fetch_gates(p, aw, lane, epoch, sb + SC_GT + (lane & 1) * GT_HALF + (8 + 16 * aw + (lane >> 1)) * 16);
        __syncwarp();
        if (elect()) { mbar_arrive(bar_v); prefetch_map(mU + 4); }
        next_epoch(p, epoch);
        if (aw == 0) TSTAMP(4);
        if (aw == 7) {
            const int row = key_row(wait_sel(p, slab >> 1, r8, key_tag(epoch)));
            if (lane < 8) asm volatile("red.shared.or.b32 [%0], %1;" :: "r"(s_bm + (row >> 5) * 4), "r"(1u << (row & 31)) : "memory");
            TSTAMP(10);
        }
        bar_sync(BC_AUX, 256);
        const uint32_t src = sb + SC_RT + ((r8 >> 1) & 1) * Y_RS + (2 * mi + (r8 & 1)) * Y_CS + (2 * aw + (r8 >> 2)) * 16;
        const int L = 2 * aw + (t >> 1);
        const int row0 = 256 * rank + 128 * (g >> 2) + 16 * (L & 3) + 64 * (g & 1) + 8 * ((g >> 1) & 1) + (L >> 2);
        __nv_bfloat16* outp = p.out + (size_t)row0 * DM + 16 * slab + 8 * (t & 1);
        const uint32_t stg = sb + SC_KG + 4096 * aw, so = (g & 2) * 256 + (g >> 2) * 128 + r8 * 16;
#pragma unroll 1
        for (int s = 1; s < 4; s++) {
            const uint32_t bm = lds32(fresh(s_bm) + (16 * s + (row0 >> 5)) * 4) >> (row0 & 31);
            const bool routed = __any_sync(0xffffffffu, bm & 0x11u);
            if (aw == s) mbar_wait_cluster(bar_y + 8 * s);
            bar_sync(BC_AUX, 256);
            const uint32_t sf = fresh(src) + 512 * s;
            uint32_t y[2][4];
            ldsm4t(y[0], sf); ldsm4t(y[1], sf + 256);
            if (routed) {
#pragma unroll
                for (int k = 0; k < 2; k++) store_or_add(outp + (size_t)(512 * s + 4 * k) * DM, y[k], bm & (1u << (4 * k)));
            } else {
                sts128(stg + so + 1024 * s, y[0][0], y[0][1], y[0][2], y[0][3]); sts128(stg + so + 1024 * s + 256, y[1][0], y[1][1], y[1][2], y[1][3]);
                asm volatile("fence.proxy.async.shared::cta;" ::: "memory");
                __syncwarp();
                if (elect()) store_rows(mU + 4, stg + 1024 * s, 16 * slab, 512 * s + 256 * rank + 32 * (aw & 1) + (aw >> 1));
            }
            if (aw == 0) TSTAMP(16 + s);
        }
        if (elect()) { asm volatile("cp.async.bulk.commit_group;" ::: "memory"); asm volatile("cp.async.bulk.wait_group.read 0;" ::: "memory"); }
        if (aw == 0) TFLUSH();
    }
}

__device__ __forceinline__ uint32_t k_tag(unsigned epoch) { return epoch << 16 | 0x80000000u; }
__device__ __forceinline__ void publish_k(uint4* kp, const uint32_t (&w)[12], unsigned epoch, uint64_t (&v)[6]) {
#pragma unroll
    for (int i = 0; i < 3; i++) {
        v[2 * i] = w[3 * i] | (uint64_t)w[3 * i + 1] << 32; v[2 * i + 1] = w[3 * i + 2] | (uint64_t)__byte_perm(w[9 + (i >> 1)], k_tag(epoch), i == 1 ? 0x7632 : 0x7610) << 32;
        asm volatile("st.relaxed.gpu.global.v2.u64 [%0], {%1,%2};" :: "l"(kp + 32 * i), "l"(v[2 * i]), "l"(v[2 * i + 1]));
    }
}
template <bool FULL>
__device__ __forceinline__ void k_tables(uint32_t kt, int lane, const uint32_t (&w)[12]) {
    const int g = lane >> 2, t = lane & 3, mi = lane >> 3, r8 = lane & 7;
    uint32_t x3 = w[7], re[4], rx[4];
#pragma unroll
    for (int i = 0; i < 4; i++) {
        re[i] = __shfl_sync(0xffffffffu, w[i], lane + 31);
        rx[i] = __shfl_sync(0xffffffffu, w[4 + i], lane + (i == 0 && lane == 29 ? 5 : 1 + 2 * t));
    }
    if (FULL) {
        asm volatile("stmatrix.sync.aligned.m8n8.x2.trans.shared.b16 [%0], {%1,%2};" :: "r"(kt + (KT_D + 7) * 4 + 64 * t + 16 * (mi & 1) + 8 * (r8 & 4)), "r"(w[8]), "r"(w[9]) : "memory");
        if (lane == 2) {
            sts32(kt + (KT_C + 78) * 4, w[10] & 0xffffu);
            sts128(kt + (KT_T + 2) * 4, 0, w[10] & 0xffffu, __byte_perm(w[10], 0, 0x1010), w[10] << 16);
        }
        if (lane == 29) x3 = bsub2(x3, rx[0] & 0xffffu);
    }
#pragma unroll
    for (int i = 0; i < 4; i++) {
        sts64(kt + (16 + 64 * i) * 4 + 8 * lane, __byte_perm(w[i], lane ? re[i] : i ? re[i - 1] : 0, 0x5432), w[i]);
        const uint32_t x = i < 3 ? w[4 + i] : x3, aa = __byte_perm(x, 0, 0x3232);
        if (t < 2) sts128(kt + (272 + 64 * i + 8 * g + 4 * t) * 4, i == 0 && lane == 0 ? __byte_perm(x, re[3], 0x5432) : aa, aa, x,
                          __byte_perm(lane != 29 ? rx[i] : i < 3 ? rx[(i + 1) & 3] : FULL ? 0 : rx[0] << 16, x, 0x5432));
        else if (FULL) sts32(kt + (KT_C - 50 + 8 * i + 32 * t + g) * 4, x);
    }
}

__device__ __forceinline__ void conv_main(const Params& p, uint32_t sb, int warp, int lane0, int bid, unsigned epoch, uint32_t (&w)[12]) {
    asm volatile("setmaxnreg.inc.sync.aligned.u32 168;");
    const int lane = __shfl_sync(0xffffffffu, lane0, lane0);
    const int g = lane >> 2, t = lane & 3, mi = lane >> 3, r8 = lane & 7;
    const int rank = bid & 1;
    const uint32_t bar_y = sb + SC_MISC, bar_v = bar_y + 40;
    next_epoch(p, epoch);
    asm volatile("barrier.cluster.wait.acquire.aligned;" ::: "memory");
    if (warp < 4) {
        bar_arrive(BC_U + warp, 64);
    } else {
        mbar_wait(bar_y + 48);
        if (KPOLL) until(clock32(), KPOLL);
        const uint4* src = p.s->kp + (8 * bid + warp) * 96 + lane0;
#pragma unroll 1
        for (int it = 0;; it++) {
            uint32_t bad = 0, e[3];
#pragma unroll
            for (int i = 0; i < 3; i++) { const uint4 v = ld_rlx128(src + 32 * i); w[3 * i] = v.x; w[3 * i + 1] = v.y; w[3 * i + 2] = v.z; e[i] = v.w; bad |= v.w ^ k_tag(epoch); }
            w[9] = __byte_perm(e[0], e[1], 0x5410); w[10] = e[2];
            const bool ok = __all_sync(0xffffffffu, bad < 65536);
            if (ok) break;
            if (it > (1 << 20)) give_up();
        }
    }
    if ((warp & 3) == 0) TSTAMP(5 + (warp >> 2));
    k_tables<true>(sb + SC_KT + warp * KT_BYTES, lane0, w);
    mbar_wait(bar_y + 48);
    __syncwarp();
    if ((warp & 3) == 0) TSTAMP(7 + (warp >> 2));
    {
        const uint32_t ut = fresh(sb + SC_UT) + warp * UT_STRIDE, kt = fresh(sb + SC_KT) + warp * KT_BYTES;
        auto dup = [&](uint32_t v) { return v ^ p.zero; };
        auto frag = [&](uint32_t (&a)[4], uint32_t x) { a[0] = lds32(x); a[1] = lds32(x + 32); a[2] = lds32(x - 32); a[3] = dup(a[0]); };
        const uint32_t kb = kt + (16 + g - 2 * t) * 4;
        float acc[16][4];
        {
            float y[12][4], M[6][4];
#pragma unroll
            for (int i = 0; i < 12; i++) { y[i][0] = y[i][1] = y[i][2] = y[i][3] = 0.f; M[i >> 1][0] = M[i >> 1][1] = M[i >> 1][2] = M[i >> 1][3] = 0.f; }
            uint32_t U[10][4], a1[4], ad[4], R = (mi & 1) * UT_HALF + (8 + (r8 >> 1) + 48 * (r8 & 1)) * 16 + 64 * (mi >> 1);
            auto places = [&] { ad[0] = swz(R, warp); ad[1] = swz(R + 128, warp); ad[2] = ad[0] ^ 64; ad[3] = ad[1] ^ 64; };
            auto ldu = [&](int k) { ldsm4(U[k], ut + ad[k & 3] + 256 * (k >> 1)); };
            places();
            frag(a1, kb + 2048);
#pragma unroll
            for (int k = 0; k < 7; k++) ldu(k);
#pragma unroll
            for (int i = 0; i < 12; i++) mma_bf(y[i], a1[0], a1[1], a1[2], a1[3], U[i >> 1][2 * (i & 1)], U[i >> 1][2 * (i & 1) + 1]);
            frag(a1, kb + 1792);
            __syncwarp();
#pragma unroll 1
            for (uint32_t ko = 0; ko != 256;) {
                ko = fresh(ko);
                const uint32_t kp = kb + ko;
                ko += 64;
                uint32_t se[10][2], so[10][2], ue[10][2];
                auto sums = [&](int k) {
#pragma unroll
                    for (int e = 0; e < 2; e++) { ue[k][e] = U[k][e]; se[k][e] = badd2(U[k][e], U[k - 1][2 + e]); so[k][e] = badd2(U[k][e], U[k][2 + e]); }
                };
#pragma unroll
                for (int k = 1; k < 6; k++) sums(k);
#pragma unroll
                for (int m = 3; m >= 0; m--) {
                    uint32_t a0[4];
                    frag(a0, kp + 512 * m);
                    sums(9 - m);
                    if (m) ldu(10 - m); else { R -= 16; places(); }
#pragma unroll
                    for (int i = 0; i < 6; i++) mma_bf(y[2 * i], a1[0], a1[1], a1[2], a1[3], se[i - m + 4][0], se[i - m + 4][1]);
#pragma unroll
                    for (int e = 0; e < 4; e++) a1[e] = bsub2(a0[e], a1[e]);
#pragma unroll
                    for (int i = 0; i < 6; i++) { mma_bf(M[i], a1[0], a1[1], a1[2], a1[3], ue[i - m + 4][0], ue[i - m + 4][1]); if (!m) ldu(i); }
                    frag(a1, m ? kp + 512 * m - 256 : kp + 1792 + 64);
                    if (!m) ldu(6);
#pragma unroll
                    for (int i = 0; i < 6; i++) mma_bf(y[2 * i + 1], a0[0], a0[1], a0[2], a0[3], so[i - m + 4][0], so[i - m + 4][1]);
                }
            }
#pragma unroll
            for (int i = 0; i < 6; i++)
#pragma unroll
                for (int c = 0; c < 4; c++) { acc[4 + i + 6 * (c & 1)][c & 2] = y[2 * i][c] + M[i][c]; acc[4 + i + 6 * (c & 1)][c | 1] = y[2 * i + 1][c] - M[i][c]; }
        }
        const uint32_t lo = (8 + col(r8)) * 16 + (mi >> 1) * 128, ua = fresh(ut) + (mi & 1) * UT_HALF, u1[2] = {ua + swz(lo, warp), ua + (swz(lo, warp) ^ 64)};
        {
            uint32_t e[4];
            frag(e, kb + (KT_T - 16) * 4);
            const uint32_t f0 = dup(e[1]), f1 = lds32(kb + KT_T * 4), uo = fresh(ut) + UT_HALF + swz((7 + 8 * mi + col(r8)) * 16, warp);
#pragma unroll
            for (int i = 0; i < 4; i++) {
                uint32_t b[4];
                if (i < 2) {
                    ldsm4(b, uo + 512 * i);
#pragma unroll
                    for (int k = 0; k < 4; k++) mma_bf8(acc[8 + 4 * i + k], f0, f1, b[k]);
                }
                ldsm4(b, u1[i & 1] + 256 * i);
                mma_bf(acc[2 * i + 8], e[0], e[1], e[2], e[3], b[0], b[1]); mma_bf(acc[2 * i + 9], e[0], e[1], e[2], e[3], b[2], b[3]);
            }
        }
        if ((warp & 3) == 0) TSTAMP(11 + (warp >> 2));
        mbar_wait(bar_v);
        const uint32_t vt = fresh(sb + SC_V) + warp * V_STRIDE;
        const uint32_t g1 = fresh(sb + SC_GT) + (mi & 1) * GT_HALF + lo;
        const uint32_t ydst = sb + SC_RT + rank * Y_RS + warp * Y_CS + lane * 16;
        const uint32_t ydr = mapa(ydst, rank ^ 1), ybr = mapa(bar_y, rank ^ 1);
        auto stairs = [&](auto R) {
        uint32_t ug[2][2][4];
        auto ld_ug = [&](int i) { ldsm4t(ug[i & 1][0], u1[i & 1] + 256 * i); ldsm4t(ug[i & 1][1], g1 + 256 * i); };
        auto ship = [&](int i) {
            const uint32_t (&u)[4] = ug[i & 1][0], (&gg)[4] = ug[i & 1][1];
            const uint32_t y0 = gmix(gg[0], acc[2 * i][0], acc[2 * i][1], u[0]), y1 = gmix(gg[1], acc[2 * i][2], acc[2 * i][3], u[1]);
            const uint32_t y2 = gmix(gg[2], acc[2 * i + 1][0], acc[2 * i + 1][1], u[2]), y3 = gmix(gg[3], acc[2 * i + 1][2], acc[2 * i + 1][3], u[3]);
            if ((i & 1) != R.value) st_async128(ydr + 512 * (i >> 1), y0, y1, y2, y3, ybr + 8 * (i >> 1));
            else asm volatile("{ .reg .pred q; setp.eq.u32 q, %6, 0; st.shared.v4.u32 [%0], {%2,%3,%4,%5}; bar.warp.sync 0xffffffff; @q mbarrier.arrive.shared::cta.b64 _, [%1]; }"
                              :: "r"(ydst + 512 * (i >> 1)), "r"(bar_y + 8 * (i >> 1)), "r"(y0), "r"(y1), "r"(y2), "r"(y3), "r"(lane) : "memory");
        };
        const uint32_t VD = vt + (VC_OFF - 400 - 16 * t) * 4 + (8 * g ^ 16 * (-t & 2)), VD2 = vt + (VC_OFF - 415 - 16 * t) * 4 + (8 * g ^ 16 * (~t & 2));
        uint2 bd[10];
        uint32_t x[2][4][4];
        auto ld4 = [&](uint32_t (&v)[4], int dl) { const uint2 w = lds64(VD + 256 * dl); v[0] = w.x; v[1] = w.y; v[2] = lds32(VD2 + 256 * dl); v[3] = dup(w.x); };
        auto mm4 = [&](const uint32_t (&v)[4], int dl) {
#pragma unroll
            for (int s = dl & 1; s < 10; s += 2) if ((dl + s) / 2 >= 4 && (dl + s) / 2 < 16) mma_bf(acc[(dl + s) / 2], v[0], v[1], v[2], v[3], bd[s].x, bd[s].y);
        };
        const uint32_t KE = kt + (KT_D + col(g) + t) * 4, VE = vt + (VE_BASE - 912 - 16 * t) * 4 + (8 * g ^ 16 * (~t & 2));
        uint32_t b0[8], b1[8];
        auto ld8 = [&](uint32_t (&v)[4], int dl) { const uint2 w = lds64(VE + 512 * dl), z = lds64(VE + 512 * dl - 256); v[0] = w.x; v[1] = w.y; v[2] = z.x; v[3] = z.y; };
        auto mm8 = [&](const uint32_t (&v)[4], int dl, int lo, int hi) {
#pragma unroll
            for (int s = 0; s < 8; s++) if (dl + s >= lo && dl + s < hi) mma_bf(acc[dl + s], v[0], v[1], v[2], v[3], b0[s], b1[s]);
        };
        ld4(x[0][0], 6);
#pragma unroll
        for (int s = 0; s < 10; s++) bd[s] = lds64(kt + (KT_C + 2 * col(g) + 2 * t + 8 * s) * 4);
        mm4(x[0][0], 6);
        uint32_t e[4][4];
#pragma unroll
        for (int k = 1; k < 6; k++) {
#pragma unroll
            for (int j = 0; j < 4; j++) ld4(x[k & 1][j], 4 * k + 3 + j);
            ld_ug(k + 1);
            if (k == 3) {
#pragma unroll
                for (int s = 0; s < 8; s++) { b0[s] = lds32(KE + 32 * s); b1[s] = lds32(KE + 32 * s + 16); }
            }
            if (k > 1) ship(k);
#pragma unroll
            for (int j = 0; j < 4; j++) {
                mm4(x[k & 1][j], 4 * k + 3 + j);
                if (k == 3) { uint32_t v[4], z[4]; ld8(e[j], 8 + j); ld8(v, 12 + j); ld4(z, 30 - j); mm8(v, 12 + j, 12, 16); mm8(e[j], 8 + j, 8, 12); mm4(z, 30 - j); }
                if (k == 5) { ld8(e[j], 8 + j + p.zero); mm8(e[j], 8 + j, 12, 16); }
            }
        }
        ld_ug(7);
        ship(7 - R.value); ship(6 + R.value);
        };
        if (rank) stairs(std::integral_constant<int, 1>()); else stairs(std::integral_constant<int, 0>());
        if ((warp & 3) == 0) TSTAMP(14 + (warp >> 2)); else TSTAMP(21 + warp);
    }
}

constexpr int SF_WD = 73728;
constexpr int SF_RED = 49152;
constexpr int MU_STRIDE = 1168  , SM_RAW = 98304, SM_UT = SM_RAW + 16384, SM_G = SM_UT + 21504, SM_Y = 196608, SM_FT = SM_Y + 17024, SM_KT = 138880, SM_KW = SM_G - 49152;
constexpr int SF_XS = 221184;
constexpr int SF_MISC = SF_XS + 8 * 1168;
constexpr int SF_KG = SF_MISC - 10 * KG_STAGE;
constexpr int SF_WR = SF_KG - 2304;
constexpr int FB_X = 64, FB_KDONE = 72, FB_KEYS = 80, FB_FREE = 88  , FB_W = 104, FB_D = FB_W + 72, FB_MU = FB_D + 96, FB_FAR = FB_MU - 16, FB_MG = FB_MU + 8, FB_MT = FB_MU + 16  , FS_PART = 512, FS_TOK = 896, FS_BM = 1024;
enum { BAR_R = 7, BAR_GU = 8, BAR_RED = 9, BAR_R2 = 10, BAR_G = 12  , BAR_M = 15 };
static_assert(SF_KG % 128 == 0 && NPRE <= 8 && SM_KT + 4 * 2112 <= 147456 && SM_G + MU_STRIDE <= SF_WR - 4 * 9216 && SM_KW + 6 * 2112 >= SM_RAW && SM_KW + 12 * 2112 <= SM_UT, "layout");

__device__ __forceinline__ constexpr int box_no(int i) { return (0x987610ba5432ull >> (4 * i)) & 15; }
__device__ __forceinline__ int role(int b) { b -= NCONV; return b < NX ? b : 18 + (b >> 1) + 12 * (b & 1); }
__device__ __forceinline__ int mini_ch0(int f) { return 48 * f - (f < NW ? 1696 : 2304); }

__device__ __forceinline__ void ffn_front(const Params& p, const CUtensorMap* maps, uint32_t sb, int warp, int lane, int f, unsigned epoch) {
    const unsigned t0 = clock32();
    const int g = lane >> 2, t = lane & 3, mi = lane >> 3, r8 = lane & 7;
    const bool isx = f < NX;
    const int nrw = f < 52 ? 4 : 6, r0 = f < 52 ? 32 * f : 48 * f - 832;
    const int rw = warp < 12 ? 13 - warp : warp ^ (warp < 14 ? 10 : 15);
    const uint32_t bar_row = sb + SF_MISC  , bar_x = bar_row + FB_X;
    const uint32_t s_part = bar_row + FS_PART  , s_tok = bar_row + FS_TOK  ;
    const uint32_t rows = sb + SF_WR - 9216 * (rw + 1) - (rw & 4) * ((SF_WR - 6 * 9216) / 4);
    {
#pragma unroll 1
        for (int i = warp < 10 ? 30 : warp - 10; i < 30; i += 6) if (elect()) mbar_init(bar_x + 8 * i, i == 1 ? 4 + (f < NW) : i < 27 ? 1 : i == 27 ? 2 : 8);
        const uint32_t bytes = rw < 6 ? 9216 : 1152, dst = rw < 6 ? rows : sb + SF_WR + (rw & 1) * 1152;
        const __nv_bfloat16* src = rw < 6 ? p.u + (size_t)(r0 + 8 * rw) * DM : (rw & 1) ? p.gatew : p.wr;
        if (elect()) { mbar_init(bar_row + 8 * rw, 1); mbar_fence(); mbar_expect(bar_row + 8 * rw, bytes); }
        if (warp == 13) { sts32(s_part + 64 + lane * 4, 0); sts32(bar_row + FS_BM + lane * 4, 0); }
        bar_sync(0, NTHR);
        if (!isx) asm volatile("barrier.cluster.arrive.relaxed.aligned;" ::: "memory");
        if (rw < nrw) until(t0, RDELAY);
        if (rw < nrw || rw >= 6) { if (elect()) bulk_g2s(dst, src, bytes, bar_row + 8 * rw); }
    }
    uint4* const kdst = p.s->keys + (lane >> 1) * 128 + 2 * f + (lane & 1);
    if (warp == 15) TSTAMP(1);

    if (warp == 12) {
        if (lane < 22) mbar_expect(bar_row + FB_W + 8 * lane, lane < 9 ? 24576 : isx ? 12288 : lane < 20 ? 2048 : 16384);
        if (elect()) { prefetch_map(maps + 1); prefetch_map(maps + 2); prefetch_map(maps + (isx ? 3 : 5)); }
        unsigned tb = t0 + WDELAY;
        auto pieces = [&](int n, int end, uint32_t dst) {
#pragma unroll 1
            for (; n < end; n++, dst += 12288) {
                until(tb, 0); tb += WGAP;
                if (elect()) tma3d(dst, maps + 1 + (n & 1), 0, 64 * (n >> 1), 3 * f, bar_row + FB_W + 8 * (n >> 1));
            }
        };
        if (!isx) {
#pragma unroll 1
            for (int k = 0; k <= (f >= NW); k++) { until(t0, MDELAY + k * MGAP); if (elect()) tma4d(sb + SM_RAW - 49152 * k, maps + 5, mini_ch0(f) + 16 * k, 0, 0, 0, bar_row + FB_MU - 8 * k); }
            if (f >= NW) return;
        }
#pragma unroll 1
        for (int i = 0; i < 4; i++) {
            if (i == 1) { mbar_wait(bar_row + FB_KEYS); mbar_wait(bar_row + FB_KDONE); tb = clock32() + RESUME; }
            if (i == 3) mbar_wait(bar_row + FB_FREE);
            const int n = ((0x0c080000 + NPRE * 256) >> (8 * i)) & 255;
            pieces(n, ((0x120c0800 + NPRE) >> (8 * i)) & 255, sb + 12288 * (((0x000c0000 + NPRE * 256) >> (8 * i)) & 255));
        }
        TSTAMP(12);
        if (isx) {
#pragma unroll 1
            for (int i = 0; i < 12; i++) {
                const int n = box_no(i);
                if (i == 6) mbar_wait(bar_row + FB_FREE + 8);
                until(tb, 0); tb += DGAP;
                if (elect()) tma2d(sb + SF_WD + n * 12288, maps + 3, 32 * (f >> 1), 2304 * (f & 1) + 192 * n, bar_row + FB_D + 8 * n);
            }
            TSTAMP(13);
        }
    } else if (warp == 13) {
        const uint32_t tag = key_tag(epoch), par = (epoch & 1) ? 0u : 0x8000u;
        stg128(kdst, 0, 0, 0, 0);
        if (lane < 8 && isx && !(f & 1)) st_rlx32(&p.s->sel[32 * f + lane], 0);
        bar_sync(BAR_R, 32 * (nrw + 1));
        TSTAMP(3);
        {
            const uint32_t sg = fresh(s_part) + 192 + lane * 4;
            const uint32_t gb = pack_bf16(sigmoidf_(rbf(__uint_as_float(lds32(sg)))), sigmoidf_(rbf(__uint_as_float(lds32(sg + 128))))) | par | (par << 16);
            asm volatile("st.relaxed.gpu.global.u16 [%0], %1;" :: "l"(p.s->gate + r0 + lane), "h"((unsigned short)gb) : "memory");
            if (nrw > 4 && lane < 16) asm volatile("st.relaxed.gpu.global.u16 [%0], %1;" :: "l"(p.s->gate + r0 + 32 + lane), "h"((unsigned short)(gb >> 16)) : "memory");
        }
        bar_sync(BAR_R2, 32 * (nrw + 1));
        {
            const uint4 v = lds128(fresh(s_tok) + (lane & 1) * 16);
            asm volatile("st.relaxed.gpu.global.v4.u32 [%0], {%1,%2,%3,%4};" :: "l"(kdst), "r"(v.x | tag), "r"(v.y | tag), "r"(v.z | tag), "r"(v.w | tag) : "memory");
        }
        TSTAMP(4);
        if (lane == 0) { mbar_arrive(bar_row + FB_KEYS); mbar_expect(bar_x, 8 * 1152); }
        if (f >= NW) return;
        mbar_wait(bar_row + FB_KDONE);
        uint32_t k[16];
        const uint4* src = p.s->keys + (f & 15) * 128 + lane;
#pragma unroll 1
        for (int it = 0;; it++) {
            uint32_t bad = 0;
#pragma unroll
            for (int i = 0; i < 4; i++) {
                const uint4 x = ld_rlx128(src + (i < 3 || lane < 24 ? 32 * i : 64));
                k[i] = x.x; k[4 + i] = x.y; k[8 + i] = x.z; k[12 + i] = x.w;
                bad |= x.x ^ tag;
            }
            const bool ok = __all_sync(0xffffffffu, (bad & 0xf800u) == 0);
            if (ok) break;
            if (it > (1 << 20)) give_up();
        }
        TSTAMP(5);
        uint32_t key = 0, m = __reduce_max_sync(0xffffffffu, max(max(k[0], k[1]), max(k[2], k[3])));
#pragma unroll 2
        for (int r = 0; r < 8; r++) {
            bool pop[4];
#pragma unroll
            for (int i = 0; i < 4; i++) { pop[i] = k[i] == m; k[i] = pop[i] ? k[4 + i] : k[i]; }
            const uint32_t mn = __reduce_max_sync(0xffffffffu, max(max(k[0], k[1]), max(k[2], k[3])));
            if (elect()) bulk_g2s(sb + SF_XS + r * 1168, p.u + (size_t)key_row(m) * DM, 1152, bar_x);
#pragma unroll
            for (int i = 0; i < 4; i++) { k[4 + i] = pop[i] ? k[8 + i] : k[4 + i]; k[8 + i] = pop[i] ? k[12 + i] : k[8 + i]; k[12 + i] = pop[i] ? 0 : k[12 + i]; }
            if (r8 == r) key = m;
            m = mn;
        }
        const int row = key_row(key);
        sts32(s_tok + r8 * 8, row);
        TSTAMP(6);
        if (isx) {
            if (!(f & 1)) {
                __nv_bfloat16* o = p.out + (size_t)row * DM + 16 * f + 8 * mi;
                asm volatile("st.relaxed.gpu.global.v4.u32 [%0], {%1,%1,%1,%1};" :: "l"(o), "r"(0) : "memory");
                if (__any_sync(0xffffffffu, ld_rlx32(o) != 0)) give_up();
                if (lane < 8) st_rlx32(&p.s->sel[32 * f + lane], key);
            } else wait_sel(p, f >> 1, r8, tag);
            uint32_t gb;
#pragma unroll 1
            for (int it = 0;; it++) {
                asm volatile("ld.relaxed.gpu.global.u16 %0, [%1];" : "=r"(gb) : "l"(p.s->gate + row) : "memory");
                gb ^= par;
                if (!(gb & 0x8000u)) break;
                if (it > (1 << 20)) give_up();
            }
            const uint32_t rb = key ^ 0x80000000u, rv = (rb ^ (((int)rb >> 31) & 0x7fff0000u)) & 0xffff0000u;
            sts32(s_tok + r8 * 8 + 4, __float_as_uint(rbf(1.0f - bf_lo(gb)) * rbf(sigmoidf_(__uint_as_float(rv)))));
            __syncwarp();
            TSTAMP(7);
            bar_arrive(BAR_RED, 416);
        }
    } else {
        if (rw < nrw) {
            float c[3][4];
#pragma unroll
            for (int i = 0; i < 3; i++) { c[i][0] = c[i][1] = c[i][2] = c[i][3] = 0.f; }
            mbar_wait(bar_row + 48); mbar_wait(bar_row + 56);
            const uint32_t b = fresh(sb + SF_WR) + (g & 1) * 1152 + (g >> 2) * 64 + t * 16 + (g & 2) * 2;
            uint32_t w[18][2];
#pragma unroll
            for (int kb = 0; kb < 18; kb++) { const uint32_t o = ((kb & 1) ? b ^ 64 : b) + 128 * (kb >> 1); w[kb][0] = lds32(o); w[kb][1] = lds32(o + 8); }
            mbar_wait(bar_row + 8 * rw);
            if (warp == 15) TSTAMP(2);
            const uint32_t a = fresh(rows) + g * 1152 + (g & 1) * 64 + t * 16;
#pragma unroll
            for (int kb = 0; kb < 18; kb++) {
                const uint4 x = lds128(((kb & 1) ? a ^ 64 : a) + 128 * (kb >> 1));
                mma_bf(c[kb % 3], x.x, x.y, x.z, x.w, w[kb][0], w[kb][1]);
            }
            const float sr = c[0][0] + c[1][0] + c[2][0] + __shfl_down_sync(0xffffffffu, c[0][2] + c[1][2] + c[2][2], 1);
            const float sg = c[0][1] + c[1][1] + c[2][1] + __shfl_down_sync(0xffffffffu, c[0][3] + c[1][3] + c[2][3], 1);
            const uint32_t rb = pack_bf16(0.f, sr);
            if (t == 2 * (g & 1)) {
                sts32(s_part + (8 * rw + g) * 4, (rb ^ (((int)rb >> 31) & 0x7fff0000u) ^ 0x80000000u) | (uint32_t)(2047 - r0 - 8 * rw - g));
                sts32(s_part + 192 + (8 * rw + g) * 4, __float_as_uint(sg));
            }
            __syncwarp();
            bar_sync(BAR_R, 32 * (nrw + 1));
            const uint32_t sk = fresh(s_part), kk = lds32(sk + (8 * rw + r8) * 4);
            int n = 0;
#pragma unroll
            for (int i = 0; i < 3; i++) { const uint4 v = lds128(sk + mi * 48 + 16 * i); n += (v.x > kk) + (v.y > kk) + (v.z > kk) + (v.w > kk); }
            n += __shfl_xor_sync(0xffffffffu, n, 8); n += __shfl_xor_sync(0xffffffffu, n, 16);
            if (n < 8) sts32(s_tok + 4 * n, kk);
            __syncwarp();
            bar_arrive(BAR_R2, 32 * (nrw + 1));
        }
    }
}

__device__ __forceinline__ void ffn_work(const Params& p, uint32_t sb, int warp, int lane, int f, unsigned epoch) {
    const int g = lane >> 2, t = lane & 3, mi = lane >> 3, r8 = lane & 7;
    const bool isx = f < NX;
    const uint32_t bar_x = sb + SF_MISC + FB_X, bar_free = sb + SF_MISC + FB_FREE, bar_w = sb + SF_MISC + FB_W, bar_d = sb + SF_MISC + FB_D, s_tok = sb + SF_MISC + FS_TOK;
    uint32_t fr[24][4];
    auto pin = [&] {
#pragma unroll
        for (int i = 0; i < 24; i += 8) asm volatile("" :: "r"(fr[i][0]), "r"(fr[i + 1][0]), "r"(fr[i + 2][0]), "r"(fr[i + 3][0]), "r"(fr[i + 4][0]), "r"(fr[i + 5][0]), "r"(fr[i + 6][0]), "r"(fr[i + 7][0]) : "memory");
    };
    {
        const int j = (unsigned)(warp - 4) < 6, w = warp - (j ? 4 : warp < 4 ? 0 : 6);
        float ag[2][4], au[2][4];
#pragma unroll
        for (int i = 0; i < 2; i++) { ag[i][0] = ag[i][1] = ag[i][2] = ag[i][3] = 0.f; au[i][0] = au[i][1] = au[i][2] = au[i][3] = 0.f; }
        const uint32_t wb = sb + (w >> 1) * 4096 + (r8 + 8 * (mi >> 1)) * 64 + (((2 * (w & 1) + (mi & 1)) ^ (r8 >> 1)) << 4);
        const uint32_t xb = sb + SF_XS + r8 * 1168 + mi * 16;
        auto load = [&](int i, int n, int place) {
            mbar_wait(bar_w + 8 * n);
            const uint32_t wk = fresh(wb) + place * 24576;
#pragma unroll
            for (int s = 0; s < 4; s++) { ldsm4t(fr[8 * i + s], wk + 1024 * s); ldsm4t(fr[8 * i + 4 + s], wk + 1024 * s + 12288); }
        };
        auto mul = [&](int i, uint32_t xk) {
            uint32_t x[2][4];
            ldsm4(x[0], xk); ldsm4(x[1], xk + 64);
#pragma unroll
            for (int s = 0; s < 4; s++) {
                const uint32_t (&a)[4] = fr[8 * i + s], (&b)[4] = fr[8 * i + 4 + s];
                mma_bf(ag[s & 1], a[0], a[1], a[2], a[3], x[s >> 1][2 * (s & 1)], x[s >> 1][2 * (s & 1) + 1]);
                mma_bf(au[s & 1], b[0], b[1], b[2], b[3], x[s >> 1][2 * (s & 1)], x[s >> 1][2 * (s & 1) + 1]);
            }
        };
#pragma unroll
        for (int i = 0; i < 3; i++) load(i, 3 * j + i, (i ? 5 : 3) * j + i);
        pin();
        bar_sync(BAR_G + j, 192);
        if (w == 0 && lane == 0) mbar_arrive(bar_free + 8 * j);
        mbar_wait(bar_x);
        if (warp == 0) TSTAMP(8);
        {
            const uint32_t xk = fresh(xb) + 384 * j;
#pragma unroll
            for (int i = 0; i < 3; i++) { mul(i, (i ? fresh(xk) : xk) + 128 * i); if (i == 0) { asm volatile("" :: "f"(ag[0][0]), "f"(ag[1][0]), "f"(au[0][0]), "f"(au[1][0])); sts32(s_tok + 64, clock32()); } }
        }
#pragma unroll 1
        for (int n = 6 + j; n < 9; n += 2) { load(0, n, n - 6); mul(0, fresh(xb) + 128 * n); }
#pragma unroll
        for (int c = 0; c < 4; c++) { ag[0][c] += ag[1][c]; au[0][c] += au[1][c]; }
        if (j) {
            sts128(wb + 24576, __float_as_uint(ag[0][0]), __float_as_uint(ag[0][1]), __float_as_uint(ag[0][2]), __float_as_uint(ag[0][3]));
            sts128(wb + 25600, __float_as_uint(au[0][0]), __float_as_uint(au[0][1]), __float_as_uint(au[0][2]), __float_as_uint(au[0][3]));
        }
        bar_sync(BAR_GU, 384);
        if (!j) {
            const uint32_t sf = fresh(wb);
            const uint4 g1 = lds128(sf + 24576), u1 = lds128(sf + 25600);
            const uint32_t gs[4] = {g1.x, g1.y, g1.z, g1.w}, us[4] = {u1.x, u1.y, u1.z, u1.w};
            if (warp == 0) TSTAMP(9);
            float h[4];
#pragma unroll
            for (int c = 0; c < 4; c++) {
                const float gv = rbf(ag[0][c] + __uint_as_float(gs[c]));
                h[c] = rbf(gv * sigmoidf_(gv)) * rbf(au[0][c] + __uint_as_float(us[c]));
            }
            uint32_t h0, h1;
            asm("movmatrix.sync.aligned.m8n8.trans.b16 %0, %1;" : "=r"(h0) : "r"(pack_bf16(h[0], h[1])));
            asm("movmatrix.sync.aligned.m8n8.trans.b16 %0, %1;" : "=r"(h1) : "r"(pack_bf16(h[2], h[3])));
            if (h0 == 0) h0 = 0x8000u;
            asm volatile("{ .reg .b64 v; mov.b64 v, {%1, %2}; st.relaxed.gpu.global.b64 [%0], v; }" :: "l"(p.s->h + ((epoch & 1) * 288 + 6 * f + w) * 32 + lane), "r"(h0), "r"(h1) : "memory");
        }
        if (isx) {
            if (warp == 0) TSTAMP(10);
            const uint2* hsrc = p.s->h + ((epoch & 1) * 288 + 144 * (f & 1) + warp) * 32 + lane;
            const uint32_t wd = sb + SF_WD + warp * 1024 + (r8 + 8 * (mi >> 1)) * 64 + (((mi & 1) ^ (r8 >> 1)) << 4), we = wd ^ 32;
            uint2 hb[12];
            auto ldh = [&](int i) { asm volatile("ld.relaxed.gpu.global.v2.u32 {%0, %1}, [%2];" : "=r"(hb[i].x), "=r"(hb[i].y) : "l"(hsrc + 384 * box_no(i)) : "memory"); };
            auto ldw = [&](int i) { mbar_wait(bar_d + 8 * box_no(i)); ldsm4t(fr[2 * i], fresh(wd) + 12288 * box_no(i)); ldsm4t(fr[2 * i + 1], fresh(we) + 12288 * box_no(i)); };
#pragma unroll
            for (int i = 0; i < DPA; i++) ldw(i);
#pragma unroll
            for (int i = 0; i < 12; i++) ldh(i);
#pragma unroll
            for (int i = DPA; i < DPB; i++) ldw(i);
#pragma unroll
            for (int i = 0; i < DPB; i++) asm volatile("" :: "r"(fr[2 * i][0]), "r"(fr[2 * i + 1][0]) : "memory");
#pragma unroll 1
            for (int it = 0;; it++) {
                bool again = false;
#pragma unroll
                for (int s = 0; s < 12; s += 2) if (__any_sync(0xffffffffu, min(hb[s].x, hb[s + 1].x) == 0)) { ldh(s); ldh(s + 1); again = true; }
                if (!again) break;
                if (it > (1 << 16)) give_up();
            }
            if (warp == 0) TSTAMP(11);
            float ad[2][2][4];
#pragma unroll
            for (int i = 0; i < 4; i++) { ad[i >> 1][i & 1][0] = ad[i >> 1][i & 1][1] = ad[i >> 1][i & 1][2] = ad[i >> 1][i & 1][3] = 0.f; }
#pragma unroll
            for (int i = 0; i < 12; i++) {
                if (i >= DPB) ldw(i);
                if (i == 11 && warp == 9) TSTAMP(14);
#pragma unroll
                for (int c = 0; c < 2; c++) mma_bf(ad[c][i & 1], fr[2 * i + c][0], fr[2 * i + c][1], fr[2 * i + c][2], fr[2 * i + c][3], hb[i].x, hb[i].y);
                if (i >= DPB - 1) asm volatile("" :: "f"(ad[0][i & 1][0]), "f"(ad[1][i & 1][0]) : "memory");
            }
            const uint32_t rd = sb + SF_RED + warp * 1152 + (72 * t + g) * 4;
#pragma unroll
            for (int i = 0; i < 8; i++) sts32(rd + (i >> 2) * 64 + (i & 1) * 144 + ((i >> 1) & 1) * 32, __float_as_uint(ad[i >> 2][0][i & 3] + ad[i >> 2][1][i & 3]));
            bar_sync(BAR_RED, 416);
            if (warp < 4) {
                const int tid = 32 * warp + lane;
                const uint32_t rs = fresh(sb + SF_RED) + (tid >> 4) * 144 + (tid & 15) * 8;
                const uint2 tk = lds64(fresh(s_tok) + (tid >> 4) * 8);
                float x = 0.f, y = 0.f;
#pragma unroll
                for (int w = 0; w < 12; w++) { const uint2 v = lds64(rs + w * 1152); x += __uint_as_float(v.x); y += __uint_as_float(v.y); }
                asm volatile("red.relaxed.gpu.global.add.noftz.bf16x2 [%0], %1;" :: "l"(p.out + (size_t)tk.x * DM + 32 * (f >> 1) + 2 * (tid & 15)),
                             "r"(pack_bf16(x * __uint_as_float(tk.y), y * __uint_as_float(tk.y))) : "memory");
            }
            if (warp == 0) { TSTAMP(15); TFLUSH(); }
            asm volatile("exit;"); __builtin_unreachable();
        }
    }
}

__device__ __forceinline__ void fetch_k(const uint4* src, uint64_t (&v)[6], uint32_t a, uint32_t b) {
    asm volatile("{ .reg .pred p; setp.eq.u32 p, %7, %8; @p ld.relaxed.gpu.global.v2.u64 {%0,%1}, [%6]; @p ld.relaxed.gpu.global.v2.u64 {%2,%3}, [%6 + 512]; @p ld.relaxed.gpu.global.v2.u64 {%4,%5}, [%6 + 1024]; }"
                 : "+l"(v[0]), "+l"(v[1]), "+l"(v[2]), "+l"(v[3]), "+l"(v[4]), "+l"(v[5]) : "l"(src), "r"(a), "r"(b));
}
__device__ __forceinline__ uint32_t mini_conv(const Params& p, uint32_t sb, int warp, int lane, int f, unsigned epoch, uint64_t (&v)[6]) {
    const int g = lane >> 2, t = lane & 3, mi = lane >> 3, r8 = lane & 7;
    const uint32_t fb = sb + SF_MISC, kt = sb + (warp >= 12 ? SM_KT - 12 * 2112 : f < NW ? SM_KW + 2 * 2112 : SM_KW) + warp * 2112;
    const bool ism = f >= NW;
    const uint32_t* const sel = &p.s->sel[((mini_ch0(f) + (ism ? 2 * (warp & 8) : 0)) >> 5) * 64 + r8];
    uint32_t seq = 128, key;
    const uint4* src = p.s->kp + lane;
    auto hi = [&](int i) { return (uint32_t)(v[i] >> 32); };
    if (f >= (warp < 4 ? NW : NX)) {
    {
        const uint32_t c = 68 + (warp & 3) + 2 * (warp & 12), y = ((uint32_t)((warp < 8 ? 0xe066806400000000ull : 0x5a6e00680080e26cull) >> ((8 * warp) & 48)) & 0xffff) + (warp < 14 ? 0 : 0x6a0000);
        seq = !ism ? y + (warp & 1) * ((y >> 6) & 0x10101) : warp < 14 ? 0x101 * c - 0x400 : c;
        src += (48 * (f - (ism ? NW : NX)) + (seq & 63)) * 96;
    }
    if (seq & 64) {
        if (seq & 4) {
            const int q = (seq & 3) + ((seq >> 1) & 4);
            const uint32_t ab = sb - 3072 * (seq & 16), d = ab + SM_UT + g * MU_STRIDE + (4 + 4 * q + t) * 32;
            asm volatile("st.shared.v2.u32 [%0], {%1,%1};" :: "r"(ab + SM_UT + (2 * q + (mi >> 1)) * MU_STRIDE + (lane & 15) * 8), "r"(0) : "memory");
            mbar_wait(fb + FB_MU - (seq & 16) / 2);
            if (warp == 15) TSTAMP(16);
            const uint32_t a = fresh(ab + SM_RAW) + q * 2048 + (8 * mi + 4 * (r8 & 1) + (r8 >> 1)) * 32 + ((r8 & 1) << 4);
            uint32_t x[4][4];
#pragma unroll
            for (int i = 0; i < 4; i++) ldsm4t(x[i], (i & 2 ? a ^ 16 : a) + 1024 * (i & 1));
#pragma unroll
            for (int i = 0; i < 4; i++) sts128(d + (i & 1) * 16 + (i & 2) * 4 * MU_STRIDE, x[i][0], x[i][1], x[i][2], x[i][3]);
            __syncwarp();
            if (lane == 0) mbar_arrive(fb + FB_MT + (seq & 16) / 2);
        }
        mbar_wait(fb + FB_KDONE);
        fetch_k(src, v, warp < 4, 0);
        if ((warp | 2) == 7) { fetch_gates(p, (warp >> 1) & 1, lane, epoch, sb + SM_G + 256 * (warp & 2) + 16 * lane); __syncwarp(); if (lane == 0) mbar_arrive(fb + FB_MG); }
        if (warp >= 8) {
            mbar_wait(fb + FB_KEYS); mbar_wait(fb + FB_MT);
            if (ism) {
                asm volatile("barrier.cluster.wait.aligned; fence.release.sync_restrict::shared::cta.cluster;" ::: "memory");
                if (lane == 0) asm volatile("mbarrier.arrive.relaxed.cluster.shared::cluster.b64 _, [%0];" :: "r"(mapa(fb + FB_MT + 8, 0)) : "memory");
            }
        }
        if (warp == TW) TSTAMP(17);
    }
    }
    const uint32_t lo = (8 + r8 - (mi & 1)) * 16 + (mi >> 1) * 128;
#pragma unroll 1
    do {
        const int c = seq & 63;
        const bool far = !ism && (seq & 16);
        const uint32_t ab = sb - 3072 * (c & 16);
        uint32_t ut = ab + SM_UT + (c & 15) * MU_STRIDE;
        if (seq & 64) {
        if (far) {
            mbar_wait_cluster(fb + FB_MT + 8);
            const uint32_t ru = mapa(ut, 1) + lane * 16;
            ut = sb + SM_FT + (c & 3) * 1536;
            uint4 x[3];
#pragma unroll
            for (int i = 0; i < 3; i++) asm volatile("ld.shared::cluster.v4.u32 {%0,%1,%2,%3}, [%4];" : "=r"(x[i].x), "=r"(x[i].y), "=r"(x[i].z), "=r"(x[i].w) : "r"(ru + 512 * i) : "memory");
#pragma unroll
            for (int i = 0; i < 3; i++) sts128(ut + lane * 16 + 512 * i, x[i].x, x[i].y, x[i].z, x[i].w);
        } else mbar_wait(fb + FB_MT + (seq & 16) / 2);
#pragma unroll 1
        for (int it = 0; !__all_sync(0xffffffffu, ((hi(1) ^ k_tag(epoch)) | (hi(3) ^ k_tag(epoch)) | (hi(5) ^ k_tag(epoch)) | ((uint32_t)v[5] & p.zero)) < 65536); it++) {
            fetch_k(src, v, 0, 0);
            if (it > (1 << 20)) give_up();
        }
        sts128(kt + t * 16, 0, 0, 0, 0);
        if (warp == TW) TSTAMP(seq >> 8 ? 7 : 10);
        const uint32_t w[12] = {(uint32_t)v[0], hi(0), (uint32_t)v[1], (uint32_t)v[2], hi(2), (uint32_t)v[3], (uint32_t)v[4], hi(4), 0, 0, 0, 0};
        k_tables<false>(fresh(kt), fresh(lane), w);
        }
        __syncwarp();
        if (seq & 128) ffn_work(p, sb, warp, fresh(lane), f, epoch);
        if (!(seq & 64)) return 0;
        const uint32_t kb = fresh(kt) + (16 + g - 2 * t) * 4, ub = fresh(ut);
        const uint32_t yd = ab + SM_Y + (c & 15) * 1056 + (c & 8) * 8 + lane * 16;
        if (warp == TW && !(seq >> 8)) TSTAMP(13);
        seq >>= 8;
        src += ((int)(seq & 63) - c) * 96;
#pragma unroll
        for (int i = 0; i < 6; i++) v[i] = 0;
        key = 0;
        float acc[8][4];
#pragma unroll
        for (int i = 0; i < 8; i++) { acc[i][0] = acc[i][1] = acc[i][2] = acc[i][3] = 0.f; }
        uint32_t a[4][4], b[2][4][4];
        auto lda = [&](int j, int s) { const uint32_t x = kb + 64 * s + 512 * j; a[j][0] = lds32(x); a[j][1] = lds32(x + 256); a[j][2] = lds32(x + 32); a[j][3] = lds32(x + 288); };
        auto ldb = [&](int i, int s) { ldsm4(b[s & 1][i], ub + lo + 256 * i - 32 * s); };
#pragma unroll
        for (int j = 0; j < 4; j++) { ldb(j, 0); lda(j, 0); }
#pragma unroll
        for (int s = 0; s < 4; s++) {
            if (s == 2) {
                const uint32_t e = seq | (__float_as_uint(acc[0][0]) & p.zero);
                fetch_k(src, v, e & 64, 64);
                asm volatile("{ .reg .pred p; setp.eq.u32 p, %2, 0; @p ld.relaxed.gpu.global.u32 %0, [%1]; }" : "+r"(key) : "l"(sel), "r"(e));
            }
#pragma unroll
            for (int i = 0; i < 4; i++) {
                const int j = (i >> 1) + 2 * (i & 1);
                if (s < 3) ldb(i, s + 1);
#pragma unroll
                for (int mu = 0; mu < 8; mu++) if (mu + 2 * j < 8) mma_bf(acc[mu + 2 * j], a[j][0], a[j][1], a[j][2], a[j][3], b[s & 1][mu >> 1][2 * (mu & 1)], b[s & 1][mu >> 1][2 * (mu & 1) + 1]);
                if (s < 3) lda(j, s + 1);
            }
        }
        if (warp == TW && !seq) TSTAMP(14);
        mbar_wait(fb + FB_MG);
        uint32_t ug[4][4];
#pragma unroll
        for (int i = 0; i < 2; i++) { ldsm4t(ug[i], ub + 128 + lane * 16 + 512 * i); ldsm4t(ug[2 + i], fresh(sb + SM_G) + lane * 16 + 512 * i); }
#pragma unroll
        for (int x = 0; x < 8; x++) ug[x >> 2][x & 3] = gmix(ug[2 + (x >> 2)][x & 3], x ? acc[x][0] + acc[x - 1][2] : acc[0][0], x ? acc[x][1] + acc[x - 1][3] : acc[0][1], ug[x >> 2][x & 3]);
        if (far) for (int i = 0; i < 2; i++) st_async128(mapa(yd, 1) + 512 * i, ug[i][0], ug[i][1], ug[i][2], ug[i][3], mapa(fb + FB_FAR, 1));
        else for (int i = 0; i < 2; i++) sts128(yd + 512 * i, ug[i][0], ug[i][1], ug[i][2], ug[i][3]);
        __syncwarp();
        if (warp == TW) TSTAMP(18 + (seq != 0));
    } while (seq);
    if (warp >= 12) TSTAMP(12 + warp);
    return key;
}
__device__ __forceinline__ void mini_out(const Params& p, const CUtensorMap* maps, uint32_t sb, int warp, int lane, int f, unsigned epoch, uint32_t key) {
    const int g = lane >> 2, t = lane & 3, mi = lane >> 3, r8 = lane & 7;
    const uint32_t fb = sb + SF_MISC;
    const bool ism = f >= NW;
    const int ch0 = mini_ch0(f);
    const int k = ism ? warp >> 3 : 0;
    uint32_t first = 1;
    if (lane == 0) asm volatile("atom.shared.exch.b32 %0, [%1], 1;" : "=r"(first) : "r"(fb + FS_BM + 64 + 4 * k) : "memory");
    if (!__all_sync(0xffffffffu, first)) {
        if (elect()) prefetch_map(maps + 6);
        const int row = key_row(wait_sel(p, (ch0 + 16 * k) >> 5, r8, key_tag(epoch), key));
        if (row < 512) asm volatile("red.shared.or.b32 [%0], %1;" :: "r"(fb + FS_BM + (row >> 5) * 4), "r"(1u << (row & 31)) : "memory");
        if (k) mbar_wait_cluster(fb + FB_FAR);
    }
    const int m = warp & 7, dr = 64 * (g >> 1) + 16 * (t >> 1) + 8 * (g & 1);
    const uint32_t y = SM_Y + ((r8 >> 1) & 1) * 8512 + (2 * mi + (r8 & 1)) * 1056 + (2 * m + (r8 >> 2)) * 16;
    const uint32_t so = (g >> 1) * 128 + (t >> 1) * 64 + (g & 1) * 32 + (t & 1) * 16;
    bar_sync(BAR_M - k, ism ? 256 : NTHR);
#pragma unroll 1
    for (int h = ism ? 0 : warp >> 3;; h++) {
        const int r0 = 256 * h + 32 * (m & 1) + (m >> 1), row = r0 + dr;
        const uint32_t bm = lds32(fresh(fb) + FS_BM + (row >> 5) * 4) >> (row & 31), ab = fresh(sb - 49152 * k + 512 * h), stg = ab + SM_UT + 2048 * m + 512 * h;
        uint32_t x[2][4];
        ldsm4t(x[0], ab + y); ldsm4t(x[1], ab + y + 256);
        if (warp == 0 && x[0][0] != 0x12345) TSTAMP(28);
        if (__any_sync(0xffffffffu, bm & 0x11u)) {
#pragma unroll
            for (int i = 0; i < 2; i++) store_or_add(p.out + (size_t)(row + 4 * i) * DM + ch0 + 16 * k + 8 * (t & 1), x[i], bm & (1u << (4 * i)));
        } else {
#pragma unroll
            for (int i = 0; i < 2; i++) sts128(stg + so + 512 * i, x[i][0], x[i][1], x[i][2], x[i][3]);
            asm volatile("fence.proxy.async.shared::cta;" ::: "memory");
            __syncwarp();
            if (elect()) store_rows(maps + 6, stg, ch0 + 16 * k, r0);
        }
        if (h >= ism) break;
    }
    if (elect()) { asm volatile("cp.async.bulk.commit_group;" ::: "memory"); asm volatile("cp.async.bulk.wait_group.read 0;" ::: "memory"); }
    if (warp == 8) TSTAMP(11);
    if (warp == 0) { TSTAMP(15); TFLUSH(); }
}

constexpr int SMEM_BYTES = 232448;
static_assert(SF_MISC + 1152 <= 232192, "layout");

struct Maps { CUtensorMap m[7]; };

__global__ void __cluster_dims__(2, 1, 1) __launch_bounds__(NTHR, 1)
fused_kernel(const Params p, const __grid_constant__ Maps maps) {
    extern __shared__ __align__(1024) uint8_t smem_raw[];
    uint32_t q[8];
    {
        const int b = role(blockIdx.x), x = threadIdx.x, rc = 5 * b + (b & ~3) + 4 + (x >> 6);
        const int cv = (unsigned)b < NW ? 0 : -1, ca = (b < 0 ? 8 * b + DM : 48 * b - 2300) + ((x >> 5) & 3), cb = 2 * rc - (rc & 3) + 4;
        const uint32_t ch = (ca & cv) | (cb & ~cv), o = NST * ch + 2 * ((x & 31) + ((x >> (cv & 2)) & 32));
        const bool c = x < (cv ? 256 : 320);
        q[6] = ldg16_if(c, p.logdt + ch);
        q[2] = ldg32_if(c, p.Bre + o); q[3] = ldg32_if(c, p.Bim + o); q[4] = ldg32_if(c, p.Cre + o); q[5] = ldg32_if(c, p.Cim + o); q[0] = ldg32_if(c, p.Are + o); q[1] = ldg32_if(c, p.Aim + o);
        q[7] = ldg16_if(c, p.Dskip + ch);
    }
    const unsigned epoch = ld_rlx32(&p.s->epoch[blockIdx.x * 16 + (threadIdx.x >> 5)]);
    const uint32_t sb = __shfl_sync(0xffffffffu, smem_u32(smem_raw), 0);
    const int warp = __shfl_sync(0xffffffffu, threadIdx.x >> 5, 0), bid = __shfl_sync(0xffffffffu, blockIdx.x, 0);
    const int lane = __shfl_sync(0xffffffffu, threadIdx.x & 31, threadIdx.x);
    const bool conv = bid < NCONV;
    const int f = role(bid);
    uint32_t w[12];
    uint64_t v[6];
    const bool four = (unsigned)f >= NW;
    if (warp < (four ? 8 : 10)) {
        const int half = four ? warp >> 2 : warp & 1, pr = four ? warp & 3 : warp >> 1;
        const int rc = 5 * f + (f & ~3) + 4 + pr;
        const uint32_t stage = sb + (conv ? SC_KG : SF_KG) + warp * KG_STAGE;
        uint4* const kp = p.s->kp + (four ? (conv ? 8 * bid : 48 * f - 2300) + pr : 2 * rc - (rc & 3) + 4) * 96 + lane;
        kgen(q, sb, half, stage, stage + (four ? 4 : 1) * KG_STAGE, 1 + pr, lane, w, [&] {
            sts128z_if(conv && lane < 20, sb + SC_KT + warp * KT_BYTES + lane * 16 + (lane < 4 ? 0 : lane < 14 ? 2048 : 2288));
            stg128z_if(!conv, kp + 64 * half); stg128z_if(!half && !conv, kp + 32);
            stg128z_if((unsigned)f < NW && warp < 6, (uint4*)(p.s->h + ((lane >> 4) * 288 + 6 * f + warp) * 32) + (lane & 15));
            if (!conv) bar_sync(0, NTHR);
            if ((unsigned)f >= NX) asm volatile("barrier.cluster.arrive.relaxed.aligned;" ::: "memory");
        });
        if (!half) publish_k(kp, w, epoch, v);
        else for (int i = 0; i < 6; i++) v[i] = 0;
        if (conv) { conv_main(p, sb, warp, lane, bid, epoch, w); return; }
        {
            if (!half && lane == 0) mbar_arrive(sb + SF_MISC + FB_KDONE);
            if (warp == 0) TSTAMP(22);
            if (warp == 2) TSTAMP(23);
        }
    } else if (conv) {
        conv_aux(p, maps.m, sb, warp - 8, lane, bid, epoch);
        return;
    } else {
        ffn_front(p, maps.m, sb, warp, lane, f, epoch);
        for (int i = 0; i < 6; i++) v[i] = 0;
    }
    converged();
    next_epoch(p, epoch);
    if (warp >= 12 && f < NX) return;
    mini_out(p, maps.m, sb, warp, lane, f, epoch, mini_conv(p, sb, warp, __shfl_sync(0xffffffffu, lane, lane), f, epoch, v));
}

typedef CUresult (*EncodeFn)(CUtensorMap*, CUtensorMapDataType, cuuint32_t, void*, const cuuint64_t*, const cuuint64_t*, const cuuint32_t*, const cuuint32_t*,
                             CUtensorMapInterleave, CUtensorMapSwizzle, CUtensorMapL2promotion, CUtensorMapFloatOOBfill);

void make_map(EncodeFn fn, CUtensorMap* m, const void* base, int rank, const cuuint64_t* dims, const cuuint64_t* strides, const cuuint32_t* box, CUtensorMapSwizzle sw) {
    const cuuint32_t es[5] = {1, 1, 1, 1, 1};
    fn(m, CU_TENSOR_MAP_DATA_TYPE_BFLOAT16, rank, (void*)base, dims, strides, box, es, CU_TENSOR_MAP_INTERLEAVE_NONE, sw,
       CU_TENSOR_MAP_L2_PROMOTION_NONE, CU_TENSOR_MAP_FLOAT_OOB_FILL_NONE);
}

}

extern "C" void kernel_launch(void* const* d_in, const int* in_sizes, int n_in, void* d_out, int out_size) {
    (void)in_sizes; (void)n_in; (void)out_size;
    static EncodeFn fn = nullptr;
    static void* scratch = nullptr;
    if (!fn) {
        void* ptr = nullptr; cudaDriverEntryPointQueryResult qr;
        cudaGetDriverEntryPoint("cuTensorMapEncodeTiled", &ptr, cudaEnableDefault, &qr);
        fn = (EncodeFn)ptr;
        cudaGetSymbolAddress(&scratch, g_scratch);
        cudaFuncSetAttribute(fused_kernel, cudaFuncAttributeMaxDynamicSharedMemorySize, SMEM_BYTES);
    }
    typedef const __nv_bfloat16* bp;
    Params p;
    p.u = (bp)d_in[0]; p.Are = (bp)d_in[1]; p.Aim = (bp)d_in[2]; p.Bre = (bp)d_in[3]; p.Bim = (bp)d_in[4]; p.Cre = (bp)d_in[5]; p.Cim = (bp)d_in[6];
    p.logdt = (bp)d_in[7]; p.Dskip = (bp)d_in[8]; p.wr = (bp)d_in[10]; p.gatew = (bp)d_in[14];
    p.out = (__nv_bfloat16*)d_out; p.s = (Scratch*)scratch; p.zero = 0;
    Maps maps;
    {
        const cuuint64_t dims[4] = {DM, 4, 16, 32}, strides[3] = {16 * DM * 2, DM * 2, 64 * DM * 2};
        const cuuint32_t box[4] = {16, 4, 16, 2};
        make_map(fn, &maps.m[0], d_in[0], 4, dims, strides, box, CU_TENSOR_MAP_SWIZZLE_32B);
        const cuuint32_t box2[4] = {16, 4, 16, 8};
        make_map(fn, &maps.m[5], d_in[0], 4, dims, strides, box2, CU_TENSOR_MAP_SWIZZLE_32B);
    }
    for (int i = 0; i < 2; i++) {
        const cuuint64_t dims[3] = {32, DM, FF / 32}, strides[2] = {FF * 2, 64};
        const cuuint32_t box[3] = {32, 64, 3};
        make_map(fn, &maps.m[1 + i], d_in[11 + i], 3, dims, strides, box, CU_TENSOR_MAP_SWIZZLE_64B);
    }
    {
        const cuuint64_t dims[2] = {DM, FF}, strides[1] = {DM * 2};
        const cuuint32_t box[2] = {32, 192};
        make_map(fn, &maps.m[3], d_in[13], 2, dims, strides, box, CU_TENSOR_MAP_SWIZZLE_64B);
    }
    {
        const cuuint64_t dims[5] = {DM, 2, 4, 4, L_SEQ}, strides[4] = {16 * DM * 2, 64 * DM * 2, 4 * DM * 2, DM * 2};
        const cuuint32_t box[5] = {16, 2, 4, 4, 1};
        make_map(fn, &maps.m[4], d_out, 5, dims, strides, box, CU_TENSOR_MAP_SWIZZLE_NONE);
    }
    {
        const cuuint64_t dims[5] = {DM, 4, 4, 2, L_SEQ}, strides[4] = {8 * DM * 2, 64 * DM * 2, 4 * DM * 2, DM * 2};
        const cuuint32_t box[5] = {16, 4, 4, 2, 1};
        make_map(fn, &maps.m[6], d_out, 5, dims, strides, box, CU_TENSOR_MAP_SWIZZLE_NONE);
    }
    fused_kernel<<<NCTA, NTHR, SMEM_BYTES>>>(p, maps);
}
```

```cpp
#include <cuda_runtime.h>
#include <cuda_bf16.h>
#include <cuda_fp16.h>
#include <cuda.h>
#include <stdint.h>

#define RESUME 300
#define MDELAY 2000
#define MGAP 0
#define KPOLL 650
#define DPA 7
#define DPB 9
#define LASTK 1
#define SCH 1
#define RDELAY 900
#define WDELAY 1700
#define WGAP 290
#define NPRE 8
#define DGAP 290
namespace {

constexpr int DM = 576, NST = 128, FF = 4608, L_SEQ = 2048;
constexpr int NCONV = 72, NX = 36, NW = 48, NCTA = 132, NTHR = 512;

struct __align__(128) Scratch {
    unsigned epoch[NCTA * 16];
    uint4 keys[16 * 128];
    uint32_t sel[18 * 64];
    uint16_t gate[L_SEQ];
    uint2 h[2 * 288 * 32];
    uint4 kp[DM * 96];
};
__device__ Scratch g_scratch;
#define TFLUSH()
#define TSTAMP(i)
#define TW 12

struct Params {
    const __nv_bfloat16 *Are, *Aim, *Bre, *Bim, *Cre, *Cim, *logdt, *Dskip, *u, *wr, *gatew;
    __nv_bfloat16* out;
    Scratch* s;
    uint32_t zero;
};

__device__ __forceinline__ void give_up() { asm volatile("trap; exit;"); __builtin_unreachable(); }
__device__ __forceinline__ void converged() { __syncwarp(); asm volatile("{ .reg .b32 t; mov.b32 t, 0; movmatrix.sync.aligned.m8n8.trans.b16 t, t; }" ::: "memory"); }
__device__ __forceinline__ bool elect() { uint32_t r; asm volatile("{ .reg .pred p; elect.sync _|p, 0xffffffff; selp.u32 %0, 1, 0, p; }" : "=r"(r)); return r; }
__device__ __forceinline__ uint32_t smem_u32(const void* p) { return (uint32_t)__cvta_generic_to_shared(p); }
__device__ __forceinline__ uint32_t pack_bf16(float lo, float hi) { uint32_t r; asm("cvt.rn.bf16x2.f32 %0, %1, %2;" : "=r"(r) : "f"(hi), "f"(lo)); return r; }
__device__ __forceinline__ uint32_t pack_f16(float lo, float hi) { uint32_t r; asm("cvt.rn.f16x2.f32 %0, %1, %2;" : "=r"(r) : "f"(hi), "f"(lo)); return r; }
__device__ __forceinline__ float bf_lo(uint32_t w) { return __uint_as_float(w << 16); }
__device__ __forceinline__ float bf_hi(uint32_t w) { return __uint_as_float(w & 0xffff0000u); }
__device__ __forceinline__ float rbf(float x) { return bf_lo(pack_bf16(x, 0.f)); }
__device__ __forceinline__ uint32_t badd2(uint32_t a, uint32_t b) { uint32_t r; asm("add.rn.bf16x2 %0, %1, %2;" : "=r"(r) : "r"(a), "r"(b)); return r; }
__device__ __forceinline__ uint32_t bsub2(uint32_t a, uint32_t b) { uint32_t r; asm("sub.rn.bf16x2 %0, %1, %2;" : "=r"(r) : "r"(a), "r"(b)); return r; }
__device__ __forceinline__ uint32_t gmix(uint32_t ng, float ny0, float ny1, uint32_t u) {
    uint32_t r; asm("{ .reg .b32 t; fma.rn.bf16x2 t, %1, %3, %3; fma.rn.bf16x2 %0, %1, %2, t; }" : "=r"(r) : "r"(ng), "r"(pack_bf16(ny0, ny1)), "r"(u)); return r;
}
__device__ __forceinline__ void mma_bf(float (&c)[4], uint32_t a0, uint32_t a1, uint32_t a2, uint32_t a3, uint32_t b0, uint32_t b1) {
    asm("mma.sync.aligned.m16n8k16.row.col.f32.bf16.bf16.f32 {%0,%1,%2,%3}, {%4,%5,%6,%7}, {%8,%9}, {%0,%1,%2,%3};"
        : "+f"(c[0]), "+f"(c[1]), "+f"(c[2]), "+f"(c[3]) : "r"(a0), "r"(a1), "r"(a2), "r"(a3), "r"(b0), "r"(b1));
}
__device__ __forceinline__ void mma_bf8(float (&c)[4], uint32_t a0, uint32_t a1, uint32_t b0) {
    asm("mma.sync.aligned.m16n8k8.row.col.f32.bf16.bf16.f32 {%0,%1,%2,%3}, {%4,%5}, {%6}, {%0,%1,%2,%3};"
        : "+f"(c[0]), "+f"(c[1]), "+f"(c[2]), "+f"(c[3]) : "r"(a0), "r"(a1), "r"(b0));
}
__device__ __forceinline__ void mma_h(float (&c)[4], uint32_t a0, uint32_t a1, uint32_t a2, uint32_t a3, uint32_t b0, uint32_t b1) {
    asm("mma.sync.aligned.m16n8k16.row.col.f32.f16.f16.f32 {%0,%1,%2,%3}, {%4,%5,%6,%7}, {%8,%9}, {%0,%1,%2,%3};"
        : "+f"(c[0]), "+f"(c[1]), "+f"(c[2]), "+f"(c[3]) : "r"(a0), "r"(a1), "r"(a2), "r"(a3), "r"(b0), "r"(b1));
}
__device__ __forceinline__ uint32_t fresh(uint32_t a) { asm volatile("" : "+r"(a) :: "memory"); return a; }
__device__ __forceinline__ uint32_t lds32(uint32_t a) { uint32_t v; asm("ld.shared.u32 %0, [%1];" : "=r"(v) : "r"(a)); return v; }
__device__ __forceinline__ uint2 lds64(uint32_t a) { uint2 v; asm("ld.shared.v2.u32 {%0,%1}, [%2];" : "=r"(v.x), "=r"(v.y) : "r"(a)); return v; }
__device__ __forceinline__ uint4 lds128(uint32_t a) { uint4 v; asm("ld.shared.v4.u32 {%0,%1,%2,%3}, [%4];" : "=r"(v.x), "=r"(v.y), "=r"(v.z), "=r"(v.w) : "r"(a)); return v; }
__device__ __forceinline__ void ldsm4(uint32_t (&r)[4], uint32_t a) {
    asm("ldmatrix.sync.aligned.m8n8.x4.shared.b16 {%0,%1,%2,%3}, [%4];" : "=r"(r[0]), "=r"(r[1]), "=r"(r[2]), "=r"(r[3]) : "r"(a));
}
__device__ __forceinline__ void ldsm4t(uint32_t (&r)[4], uint32_t a) {
    asm("ldmatrix.sync.aligned.m8n8.x4.trans.shared.b16 {%0,%1,%2,%3}, [%4];" : "=r"(r[0]), "=r"(r[1]), "=r"(r[2]), "=r"(r[3]) : "r"(a));
}
__device__ __forceinline__ void sts16(uint32_t a, uint32_t v) { asm volatile("st.shared.u16 [%0], %1;" :: "r"(a), "h"((unsigned short)v) : "memory"); }
__device__ __forceinline__ void sts32(uint32_t a, uint32_t v) { asm volatile("st.shared.u32 [%0], %1;" :: "r"(a), "r"(v) : "memory"); }
__device__ __forceinline__ void sts64(uint32_t a, uint32_t x, uint32_t y) { asm volatile("st.shared.v2.u32 [%0], {%1,%2};" :: "r"(a), "r"(x), "r"(y) : "memory"); }
__device__ __forceinline__ void sts128(uint32_t a, uint32_t x, uint32_t y, uint32_t z, uint32_t w) {
    asm volatile("st.shared.v4.u32 [%0], {%1,%2,%3,%4};" :: "r"(a), "r"(x), "r"(y), "r"(z), "r"(w) : "memory");
}
__device__ __forceinline__ void st_async128(uint32_t a, uint32_t x, uint32_t y, uint32_t z, uint32_t w, uint32_t bar) {
    asm volatile("st.async.weak.shared::cluster.mbarrier::complete_tx::bytes.v4.b32 [%0], {%1,%2,%3,%4}, [%5];" :: "r"(a), "r"(x), "r"(y), "r"(z), "r"(w), "r"(bar) : "memory");
}
__device__ __forceinline__ void mbar_init(uint32_t b, uint32_t cnt) { asm volatile("mbarrier.init.shared::cta.b64 [%0], %1;" :: "r"(b), "r"(cnt) : "memory"); }
__device__ __forceinline__ void mbar_fence() { asm volatile("fence.mbarrier_init.release.cluster;" ::: "memory"); }
__device__ __forceinline__ void mbar_expect(uint32_t b, uint32_t bytes) { asm volatile("mbarrier.arrive.expect_tx.shared::cta.b64 _, [%0], %1;" :: "r"(b), "r"(bytes) : "memory"); }
__device__ __forceinline__ void mbar_arrive(uint32_t b) { asm volatile("mbarrier.arrive.shared::cta.b64 _, [%0];" :: "r"(b) : "memory"); }
__device__ __forceinline__ void mbar_wait(uint32_t b, uint32_t parity = 0) {
    asm volatile("{ .reg .pred p; .reg .u32 n; mov.u32 n, 0;\n"
                 "LW: mbarrier.try_wait.parity.shared::cta.b64 p, [%0], %1; @p bra LD; add.u32 n, n, 1; setp.lt.u32 p, n, 65536; @p bra LW; trap;\n"
                 "LD: }" :: "r"(b), "r"(parity) : "memory");
}
__device__ __forceinline__ void mbar_wait_cluster(uint32_t b) {
    asm volatile("{ .reg .pred p; .reg .u32 n; mov.u32 n, 0;\n"
                 "LW: mbarrier.try_wait.parity.acquire.cluster.shared::cta.b64 p, [%0], 0; @p bra LD; add.u32 n, n, 1; setp.lt.u32 p, n, 65536; @p bra LW; trap;\n"
                 "LD: }" :: "r"(b) : "memory");
}
__device__ __forceinline__ void tma2d(uint32_t dst, const CUtensorMap* m, int c0, int c1, uint32_t bar) {
    asm volatile("cp.async.bulk.tensor.2d.shared::cluster.global.mbarrier::complete_tx::bytes [%0], [%1, {%3, %4}], [%2];"
                 :: "r"(dst), "l"(m), "r"(bar), "r"(c0), "r"(c1) : "memory");
}
__device__ __forceinline__ void tma3d(uint32_t dst, const CUtensorMap* m, int c0, int c1, int c2, uint32_t bar) {
    asm volatile("cp.async.bulk.tensor.3d.shared::cluster.global.mbarrier::complete_tx::bytes [%0], [%1, {%3, %4, %5}], [%2];"
                 :: "r"(dst), "l"(m), "r"(bar), "r"(c0), "r"(c1), "r"(c2) : "memory");
}
__device__ __forceinline__ void tma4d(uint32_t dst, const CUtensorMap* m, int c0, int c1, int c2, int c3, uint32_t bar) {
    asm volatile("cp.async.bulk.tensor.4d.shared::cluster.global.mbarrier::complete_tx::bytes [%0], [%1, {%3, %4, %5, %6}], [%2];"
                 :: "r"(dst), "l"(m), "r"(bar), "r"(c0), "r"(c1), "r"(c2), "r"(c3) : "memory");
}
__device__ __forceinline__ void bulk_g2s(uint32_t dst, const void* src, uint32_t bytes, uint32_t bar) {
    asm volatile("cp.async.bulk.shared::cluster.global.mbarrier::complete_tx::bytes [%0], [%1], %2, [%3];"
                 :: "r"(dst), "l"(src), "r"(bytes), "r"(bar) : "memory");
}
__device__ __forceinline__ uint32_t mapa(uint32_t a, uint32_t rank) { uint32_t r; asm("mapa.shared::cluster.u32 %0, %1, %2;" : "=r"(r) : "r"(a), "r"(rank)); return r; }
__device__ __forceinline__ void prefetch_map(const CUtensorMap* m) { asm volatile("prefetch.tensormap [%0];" :: "l"(m) : "memory"); }
__device__ __forceinline__ void bar_sync(int id, int n) { asm volatile("bar.sync %0, %1;" :: "r"(id), "r"(n) : "memory"); }
__device__ __forceinline__ void bar_arrive(int id, int n) { asm volatile("bar.arrive %0, %1;" :: "r"(id), "r"(n) : "memory"); }
__device__ __forceinline__ uint32_t ldg16_if(bool c, const void* p) { uint32_t v; asm volatile("{ .reg .pred p; setp.ne.u32 p, %2, 0; @p ld.global.nc.u16 %0, [%1]; }" : "=r"(v) : "l"(p), "r"((uint32_t)c)); return v; }
__device__ __forceinline__ uint32_t ldg32_if(bool c, const void* p) { uint32_t v; asm volatile("{ .reg .pred p; setp.ne.u32 p, %2, 0; @p ld.global.nc.u32 %0, [%1]; }" : "=r"(v) : "l"(p), "r"((uint32_t)c)); return v; }
__device__ __forceinline__ uint32_t ld_rlx32(const void* p) { uint32_t v; asm volatile("ld.relaxed.gpu.global.u32 %0, [%1];" : "=r"(v) : "l"(p) : "memory"); return v; }
__device__ __forceinline__ uint4 ld_rlx128(const void* p) {
    uint4 v; asm volatile("ld.relaxed.gpu.global.v4.u32 {%0,%1,%2,%3}, [%4];" : "=r"(v.x), "=r"(v.y), "=r"(v.z), "=r"(v.w) : "l"(p) : "memory"); return v;
}
__device__ __forceinline__ void st_rlx32(void* p, uint32_t v) { asm volatile("st.relaxed.gpu.global.u32 [%0], %1;" :: "l"(p), "r"(v) : "memory"); }
__device__ __forceinline__ void stg128(void* p, uint32_t x, uint32_t y, uint32_t z, uint32_t w) {
    asm volatile("st.global.v4.u32 [%0], {%1,%2,%3,%4};" :: "l"(p), "r"(x), "r"(y), "r"(z), "r"(w) : "memory");
}
__device__ __forceinline__ void next_epoch(const Params& p, unsigned e) { if ((threadIdx.x & 31) == 0) p.s->epoch[blockIdx.x * 16 + (threadIdx.x >> 5)] = e + 1; }
__device__ __forceinline__ void sts128z_if(bool c, uint32_t a) { asm volatile("{ .reg .pred p; setp.ne.u32 p, %1, 0; @p st.shared.v4.u32 [%0], {%2,%2,%2,%2}; }" :: "r"(a), "r"((uint32_t)c), "r"(0) : "memory"); }
__device__ __forceinline__ void stg128z_if(bool c, void* a) { asm volatile("{ .reg .pred p; setp.ne.u32 p, %1, 0; @p st.global.v4.u32 [%0], {%2,%2,%2,%2}; }" :: "l"(a), "r"((uint32_t)c), "r"(0) : "memory"); }
__device__ __forceinline__ unsigned clock32() { unsigned c; asm volatile("mov.u32 %0, %clock;" : "=r"(c) :: "memory"); return c; }
__device__ __forceinline__ void until(unsigned t0, int c) { while ((int)(clock32() - t0) < c) { } }
__device__ __forceinline__ float sigmoidf_(float x) { return __fdividef(1.0f, 1.0f + __expf(-x)); }
__device__ __forceinline__ uint32_t key_tag(unsigned epoch) { return ((epoch & 15u) | 16u) << 11; }
__device__ __forceinline__ int key_row(uint32_t key) { return 2047 - (int)(key & 2047u); }
__device__ __forceinline__ uint32_t wait_sel(const Params& p, int s32, int r8, uint32_t tag, uint32_t k = 0) {
#pragma unroll 1
    for (int it = 0; !__all_sync(0xffffffffu, (k & 0xf800u) == tag); it++) {
        k = ld_rlx32(&p.s->sel[s32 * 64 + r8]);
        if (it > (1 << 20)) give_up();
    }
    return k;
}

struct cplx { float re, im; };
__device__ __forceinline__ cplx csq(cplx a) { cplx r; r.re = a.re * a.re - a.im * a.im; r.im = (a.re * a.im) * 2.f; return r; }
__device__ __forceinline__ cplx cexpk(float ar, float ai, float k) {
    float mag, s, c;
    asm("ex2.approx.ftz.f32 %0, %1;" : "=f"(mag) : "f"(ar * (k * 1.4426950408889634f)));
    const float r = ai * k;
    asm("sin.approx.ftz.f32 %0, %1;" : "=f"(s) : "f"(r));
    asm("cos.approx.ftz.f32 %0, %1;" : "=f"(c) : "f"(r));
    cplx o; o.re = mag * c; o.im = mag * s; return o;
}
struct h2c { uint32_t re, im; };
__device__ __forceinline__ h2c cmul_cd(h2c v, __half2 c, __half2 d) {
    const __half2 r = *(const __half2*)&v.re, i = *(const __half2*)&v.im;
    const __half2 x = __hfma2(__hneg2(i), d, __hmul2(r, c)), y = __hfma2(i, c, __hmul2(r, d));
    h2c o; o.re = *(const uint32_t*)&x; o.im = *(const uint32_t*)&y; return o;
}
__device__ __forceinline__ h2c cmul_s(h2c v, uint32_t s) { const __half2 h = *(const __half2*)&s; return cmul_cd(v, __low2half2(h), __high2half2(h)); }
__device__ __forceinline__ h2c cmul_sc(h2c v, uint32_t s) {
    const __half2 h = *(const __half2*)&s, c = __low2half2(h), d = __high2half2(h), r = *(const __half2*)&v.re, i = *(const __half2*)&v.im;
    const __half2 x = __hfma2(i, d, __hmul2(r, c)), y = __hfma2(__hneg2(r), d, __hmul2(i, c));
    h2c o; o.re = *(const uint32_t*)&x; o.im = *(const uint32_t*)&y; return o;
}
__device__ __forceinline__ h2c cmul_vc(h2c v, uint32_t s) {
    const __half2 h = *(const __half2*)&s, c = __low2half2(h), d = __high2half2(h), r = *(const __half2*)&v.re, i = *(const __half2*)&v.im;
    const __half2 x = __hfma2(i, d, __hmul2(r, c)), y = __hfma2(__hneg2(i), c, __hmul2(r, d));
    h2c o; o.re = *(const uint32_t*)&x; o.im = *(const uint32_t*)&y; return o;
}

constexpr int UT_HALF = 2560, UT_STRIDE = 4736, GT_HALF = 2240;
__device__ __forceinline__ uint32_t swz(uint32_t x, int c) { return x ^ (((x >> 2) & 64) ^ (64 * (c & 1) + 8 * (c & 6))); }
__device__ __forceinline__ int col(int n) { return (n >> 1) + 4 * (n & 1); }
constexpr int KT_T = 542, KT_C = 552, KT_D = 645, KT_BYTES = 720 * 4;
constexpr int VC_OFF = 80, VE_BASE = 1616;
constexpr int V_STRIDE = (1616 + 1024) * 4 + 80;
constexpr int KG_STAGE = 5248;
constexpr int Y_CS = 2080, Y_RS = 8 * Y_CS + 64;

constexpr int SC_RT = 0;
constexpr int SC_UT = 33408;
constexpr int SC_KG = SC_UT + 8 * UT_STRIDE;
constexpr int SC_KT = SC_KG + 8 * KG_STAGE;
constexpr int SC_GT = SC_KT + 8 * KT_BYTES;
constexpr int SC_V = SC_GT + 4448;
constexpr int SC_MISC = SC_V + 8 * V_STRIDE;
static_assert(V_STRIDE % 128 == 16 && 2 * Y_RS <= SC_UT && SC_UT % 128 == 0 && SC_KG % 128 == 0, "layout");
static_assert(SC_MISC % 16 == 0 && SC_MISC + 512 <= 232192, "layout");

__device__ __forceinline__ void window_task(uint32_t s0, uint32_t s1, uint32_t d0, uint32_t d1, int k) {
    float S[51], s = 0.f;
    uint32_t w[28];
#pragma unroll
    for (int i = 0; i < 7; i++) {
        const uint4 v = lds128(((i < 3 ? s0 : s1) ^ 8 * ((i + 1) & 2)) + ((i & 1) ? 0 : UT_HALF));
        w[4 * i] = v.x; w[4 * i + 1] = v.y; w[4 * i + 2] = v.z; w[4 * i + 3] = v.w;
    }
    auto sums = [&](int lo, int hi) {
#pragma unroll
        for (int i = lo; i < hi; i++) { const float x = (i & 1) ? bf_hi(w[i >> 1]) : bf_lo(w[i >> 1]); s = i > 3 ? s + x : x; S[i] = s; }
    };
    auto put = [&](int off, int b, int o0, int o1, int o2) {
        auto v = [&](int i) { i += 16 * b; return pack_bf16(S[o0 + i] - S[o1 + i], S[o1 + i] - S[o2 + i]); };
#pragma unroll
        for (int i = 0; i < 8; i += 2) sts128((i & 4 ? d1 : d0) + 4 * off + 64 * b + 8 * (i & 2), v(i), v(i + 8), v(i + 1), v(i + 9));
    };
    S[2] = 0.f;
    sums(3, 26); put(VC_OFF - 16, 0, 10, 5, 2);
    if (k == 12) return;
    sums(26, 42); put(VC_OFF - 16, 1, 10, 5, 2);
    if (k < 8) { put(VE_BASE, 0, 19, 12, 3); sums(42, 51); put(VE_BASE, 1, 19, 12, 3); }
}

template <class F>
__device__ __forceinline__ void kgen(const uint32_t (&q)[8], uint32_t sb, int half, uint32_t stage, uint32_t pstage, int barid, int lane, uint32_t (&w)[12], F shadow) {
    const int t = lane & 3, mi = lane >> 3, r8 = lane & 7;
    {
        const uint32_t pAr = q[0], pAi = q[1], pBr = q[2], pBi = q[3], pCr = q[4], pCi = q[5], pDt = q[6], pD = q[7];
        const uint32_t wb = fresh(stage + lane * 16), za = fresh(stage + 5120 + ((lane >> 1) & 3) * 16 + mi * 4 + (lane & 1) * 2), zr = fresh(stage + 5120 + t * 16);
        const uint32_t oA = fresh(stage + (mi & 1) * 1024 + (mi >> 1) * 512 + r8 * 16), oB = fresh(stage + 2048 + mi * 512 + r8 * 16), oC = fresh(stage + 4096 + (mi & 1) * 512 + (mi >> 1) * 128 + r8 * 16);
        float acc[6][4];
#pragma unroll
        for (int a = 0; a < 6; a++) { acc[a][0] = acc[a][1] = acc[a][2] = acc[a][3] = 0.f; asm volatile("" : "+f"(acc[a][0]), "+f"(acc[a][1]), "+f"(acc[a][2]), "+f"(acc[a][3])); }
        shadow();
        sts32(zr, clock32());
        const float dt = rbf(__expf(bf_lo(pDt)));
        float ar = dt * bf_lo(pAr), ai = dt * bf_lo(pAi), ar1 = dt * bf_hi(pAr), ai1 = dt * bf_hi(pAi);
        float wr, wi, wr1, wi1;
        { const float br = dt * bf_lo(pBr), bi = dt * bf_lo(pBi), cr = bf_lo(pCr), ci = bf_lo(pCi); wr = cr * br - ci * bi; wi = cr * bi + ci * br; }
        { const float br = dt * bf_hi(pBr), bi = dt * bf_hi(pBi), cr = bf_hi(pCr), ci = bf_hi(pCi); wr1 = cr * br - ci * bi; wi1 = cr * bi + ci * br; }
        const uint32_t ex = max(__reduce_max_sync(0xffffffffu, __float_as_uint(fmaxf(fmaxf(fabsf(wr), fabsf(wi)), fmaxf(fabsf(wr1), fabsf(wi1))))) >> 23, 14u);
        const float scl = __uint_as_float((267u - ex) << 23);
        uint32_t W = pack_f16(wr * scl, wi * -scl);
        const uint32_t W1 = pack_f16(wr1 * scl, wi1 * -scl);
        if (threadIdx.x < 32) TSTAMP(20);

#pragma unroll 1
        for (int r = 0; r < 2; r++) {
            const cplx z1 = cexpk(ar, ai, 1.f), z64 = cexpk(ar, ai, 64.f);
            const cplx z2 = csq(z1), z4 = csq(z2), z8 = csq(z4), z16 = csq(z8), z32 = csq(z16);
            const cplx z128 = csq(z64), z256 = csq(z128), z512 = csq(z256);
            auto put = [&](int grp, h2c a, h2c b, h2c c, h2c d) { sts128(wb + grp * 1024, a.re, b.re, c.re, d.re); sts128(wb + grp * 1024 + 512, a.im, b.im, c.im, d.im); };
            {
                const uint32_t s4 = pack_f16(z4.re, z4.im), s256 = pack_f16(z256.re, z256.im), s512 = pack_f16(z512.re, z512.im);
                auto mix = [](h2c a, h2c b, uint32_t sel) { return h2c{__byte_perm(a.re, b.re, sel), __byte_perm(a.im, b.im, sel)}; };
                const h2c c10 = cmul_vc(h2c{pack_f16(z1.re, 1.f), pack_f16(z1.im, 0.f)}, W), c32 = cmul_sc(c10, pack_f16(z2.re, z2.im)), c54 = cmul_sc(c10, s4);
                put(2, c10, c32, c54, cmul_sc(c32, s4));
                const h2c d20 = cmul_sc(mix(c32, c10, 0x7632), s256), e04 = cmul_sc(mix(c10, c54, 0x7632), s512), f04 = cmul_sc(e04, s256);
                put(3, d20, cmul_sc(d20, s4), e04, f04);
                const h2c ef = mix(e04, f04, 0x5410), gh = cmul_sc(ef, s512), g8 = cmul_sc(gh, pack_f16(z8.re, z8.im));
                put(4, g8, cmul_sc(g8, s512), gh, ef);
            }
            {
                const uint32_t s32 = pack_f16(z32.re, z32.im), s64 = pack_f16(z64.re, z64.im), s128 = pack_f16(z128.re, z128.im);
                const h2c p0 = {pack_f16(1.f, z8.re), pack_f16(0.f, z8.im)}, p1 = cmul_s(p0, pack_f16(z16.re, z16.im)), p2 = cmul_s(p0, s32), p3 = cmul_s(p1, s32);
                put(0, p0, p1, p2, p3);
                put(1, cmul_s(p0, s64), cmul_s(p1, s64), cmul_s(p2, s64), cmul_s(p3, s64));
                sts16(za, s128); sts16(za + 64, s128 >> 16);
            }
            __syncwarp();
            {
                const uint32_t aA = fresh(oA), aB = fresh(oB), aC = fresh(oC), aZ = fresh(zr);
                const uint4 zc = lds128(aZ), zd = lds128(aZ + 64);
                const uint32_t zcs[4] = {zc.x, zc.y, zc.z, zc.w}, zds[4] = {zd.x, zd.y, zd.z, zd.w};
                uint32_t c[4];
#pragma unroll
                for (int k = 0; k < 4; k++) {
                    uint32_t a[4], b[4];
                    ldsm4t(a, aA + 128 * k); ldsm4t(b, aB + 128 * k);
                    if (!(k & 1)) ldsm4t(c, aC + 128 * k);
                    const h2c x = cmul_cd(h2c{a[0], a[2]}, *(const __half2*)&zcs[k], *(const __half2*)&zds[k]), y = cmul_cd(h2c{a[1], a[3]}, *(const __half2*)&zcs[k], *(const __half2*)&zds[k]);
                    mma_h(acc[0], a[0], a[1], a[2], a[3], b[0], b[1]);
                    mma_h(acc[1], a[0], a[1], a[2], a[3], b[2], b[3]);
                    mma_h(acc[2], a[0], a[1], a[2], a[3], c[2 * (k & 1)], c[2 * (k & 1) + 1]);
                    mma_h(acc[3], x.re, y.re, x.im, y.im, b[0], b[1]);
                    mma_h(acc[4], x.re, y.re, x.im, y.im, b[2], b[3]);
                    mma_h(acc[5], x.re, y.re, x.im, y.im, c[2 * (k & 1)], c[2 * (k & 1) + 1]);
                }
                asm volatile("" :: "f"(acc[0][0]), "f"(acc[1][0]), "f"(acc[2][0]), "f"(acc[3][0]), "f"(acc[4][0]), "f"(acc[5][0]) : "memory");
            }
            __syncwarp();
            ar = ar1; ai = ai1; W = W1;
        }
        if (threadIdx.x < 32) TSTAMP(21);
        const float i0 = __uint_as_float((ex + 243u) << 23);
        if (half) {
#pragma unroll
            for (int a = 0; a < 6; a++) { acc[a][0] *= i0; acc[a][1] *= i0; acc[a][2] *= i0; acc[a][3] *= i0; }
            if (lane == 0) acc[0][1] -= bf_lo(pD);
#pragma unroll
            for (int a = 0; a < 6; a++) sts128(wb + a * 512, __float_as_uint(acc[a][0]), __float_as_uint(acc[a][1]), __float_as_uint(acc[a][2]), __float_as_uint(acc[a][3]));
            bar_arrive(barid, 64);
        } else {
            if (blockIdx.x < NCONV) bar_arrive(barid + 8, 64);
            bar_sync(barid, 64);
            const uint32_t src = fresh(pstage);
#pragma unroll
            for (int a = 0; a < 6; a++) {
                const uint4 y = lds128(src + lane * 16 + a * 512);
                auto sum = [&](uint32_t x, float c) { return fmaf(c, i0, __uint_as_float(x)); };
                w[4 * (a % 3) + 2 * (a / 3)] = pack_bf16(sum(y.x, acc[a][0]), sum(y.y, acc[a][1]));
                w[4 * (a % 3) + 2 * (a / 3) + 1] = pack_bf16(sum(y.z, acc[a][2]), sum(y.w, acc[a][3]));
            }
            const uint32_t x0 = __shfl_up_sync(0xffffffffu, w[10], 2), x1 = __shfl_up_sync(0xffffffffu, w[11], 2);
            w[10] = w[8];
            if (t >= 2) { w[8] = x0; w[9] = x1; }
        }
    }
}

enum { BC_AUX = 0, BC_U = 5  , BC_Y = 13   };

__device__ __forceinline__ void fetch_gates(const Params& p, int i, int lane, unsigned epoch, uint32_t dst) {
    const uint32_t par = (epoch & 1) ? 0x80008000u : 0u;
    uint4 v;
#pragma unroll 1
    for (int it = 0;; it++) {
        v = ld_rlx128(p.s->gate + 256 * i + 8 * lane);
        v.x ^= par; v.y ^= par; v.z ^= par; v.w ^= par;
        if (__all_sync(0xffffffffu, (v.x & v.y & v.z & v.w & 0x80008000u) == 0x80008000u)) break;
        if (it > (1 << 20)) give_up();
    }
    sts128(dst, v.x, v.y, v.z, v.w);
}
__device__ __forceinline__ void store_rows(const CUtensorMap* m, uint32_t src, int col, int row) {
    asm volatile("cp.async.bulk.tensor.5d.global.shared::cta.bulk_group [%0, {%2, %3, %3, %3, %4}], [%1];" :: "l"(m), "r"(src), "r"(col), "r"(0), "r"(row) : "memory");
}

__device__ __forceinline__ void store_or_add(void* o, const uint32_t (&y)[4], uint32_t add) {
    asm volatile("{ .reg .pred p; setp.ne.u32 p, %5, 0; @!p st.global.v4.u32 [%0], {%1,%2,%3,%4}; @p red.relaxed.gpu.global.add.noftz.v4.bf16x2 [%0], {%1,%2,%3,%4}; }"
                 :: "l"(o), "r"(y[0]), "r"(y[1]), "r"(y[2]), "r"(y[3]), "r"(add) : "memory");
}

__device__ __forceinline__ void conv_aux(const Params& p, const CUtensorMap* mU, uint32_t sb, int aw, int lane, int bid, unsigned epoch) {
    const int g = lane >> 2, t = lane & 3, mi = lane >> 3, r8 = lane & 7;
    const int rank = bid & 1, slab = bid >> 1;
    const uint32_t bar_y = sb + SC_MISC, bar_u = bar_y  , bar_v = bar_y + 8, bar_box = bar_y + 64 + 8 * aw, s_bm = bar_y + 128;
    if (elect()) {
        mbar_init(bar_box, 1); mbar_fence();
        mbar_expect(bar_box, 4096);
        tma4d(sb + SC_RT + 4096 * aw, mU, 16 * slab, 0, 0, 16 * rank + 2 * aw, bar_box);
        mbar_init(bar_y + 8 * aw, aw == 1 ? 8 : 1);
        if (aw == 1) mbar_init(bar_y + 384, 1);
        mbar_fence();
        if (aw != 1) mbar_expect(bar_y + 8 * aw, aw ? 4096 : 16384);
    }
    __syncwarp();
    asm volatile("barrier.cluster.arrive.relaxed.aligned;" ::: "memory");
    asm volatile("setmaxnreg.dec.sync.aligned.u32 88;");
    sts128(sb + (lane < 16 ? SC_UT + aw * UT_STRIDE + mi * (UT_HALF - 128) : SC_V - 256 + aw * V_STRIDE) + lane * 16, 0, 0, 0, 0);
    if (lane < 16) sts128(s_bm + lane * 16, 0, 0, 0, 0);
    {
        const uint32_t dst = sb + SC_UT + g * UT_STRIDE + swz((8 + 64 * rank + 8 * aw + t) * 16, g);
        const uint32_t rdst = mapa(dst, rank ^ 1), rbar = mapa(bar_u, rank ^ 1);
        asm volatile("barrier.cluster.wait.acquire.aligned;" ::: "memory");
        mbar_wait(bar_box);
        if (aw == 0) TSTAMP(1);
        const uint32_t src = fresh(sb + SC_RT) + aw * 4096 + (8 * mi + 4 * (r8 & 1) + (r8 >> 1)) * 32 + ((rank ^ (r8 & 1)) << 4);
        uint32_t x[8][4];
#pragma unroll
        for (int i = 0; i < 4; i++) { ldsm4t(x[i], src + 1024 * i); ldsm4t(x[4 + i], (src ^ 16) + 1024 * i); }
        asm volatile("" :: "r"(x[0][0]), "r"(x[1][0]), "r"(x[2][0]), "r"(x[3][0]) : "memory");
#pragma unroll
        for (int i = 0; i < 4; i++) st_async128((rdst ^ 32 * (i & 2)) + (i & 1) * UT_HALF, x[4 + i][0], x[4 + i][1], x[4 + i][2], x[4 + i][3], rbar);
#pragma unroll
        for (int i = 0; i < 4; i++) sts128((dst ^ 32 * (i & 2)) + (i & 1) * UT_HALF, x[i][0], x[i][1], x[i][2], x[i][3]);
    }
    bar_sync(BC_AUX, 256);
    mbar_wait_cluster(bar_u);
    if (aw == 0) TSTAMP(2);
    if (aw == 6 && elect()) mbar_arrive(bar_y + 384);
    bar_sync(BC_U + aw, 64);
    if (aw == 0) TSTAMP(3);
    {
        const uint32_t ws = fresh(sb + SC_UT) + r8 * UT_STRIDE, wd = sb + SC_V + r8 * V_STRIDE;
#pragma unroll 1
        for (int k = aw; k < 13; k += 8) {
            const int a = 8 * k + (k < 12 ? g & 6 : 0);
            const uint32_t d = wd + 64 * a, sw = 16 * (a & 2);
            window_task(ws + swz(16 * a + 96, r8), ws + swz(16 * a + 128, r8), d + sw, d + (sw ^ 32), k);
        }
    }
    if (aw == 0) TSTAMP(9);
    {
        if (aw >= 2) fetch_gates(p, aw, lane, epoch, sb + SC_GT + (lane & 1) * GT_HALF + (8 + 16 * aw + (lane >> 1)) * 16);
        __syncwarp();
        if (elect()) { mbar_arrive(bar_v); prefetch_map(mU + 4); }
        next_epoch(p, epoch);
        if (aw == 0) TSTAMP(4);
        if (aw == 7) {
            const int row = key_row(wait_sel(p, slab >> 1, r8, key_tag(epoch)));
            if (lane < 8) asm volatile("red.shared.or.b32 [%0], %1;" :: "r"(s_bm + (row >> 5) * 4), "r"(1u << (row & 31)) : "memory");
            TSTAMP(10);
        }
        bar_sync(BC_AUX, 256);
        const uint32_t src = sb + SC_RT + ((r8 >> 1) & 1) * Y_RS + (2 * mi + (r8 & 1)) * Y_CS + (2 * aw + (r8 >> 2)) * 16;
        const int rb = 64 * (aw & 4) + 32 * (aw & 1) + ((aw >> 1) & 1) + 2 * rank, row0 = rb + 128 * (g >> 2) + 16 * (t >> 1) + 64 * (g & 1) + 8 * ((g >> 1) & 1);
        __nv_bfloat16* outp = p.out + (size_t)row0 * DM + 16 * slab + 8 * (t & 1);
        const uint32_t stg = sb + SC_KG + 4096 * aw, so = (g & 2) * 256 + (g >> 2) * 128 + r8 * 16;
#pragma unroll 1
        for (int s = 1; s < 4; s++) {
            const uint32_t bm = lds32(fresh(s_bm) + (16 * s + (row0 >> 5)) * 4) >> (row0 & 31);
            const bool routed = __any_sync(0xffffffffu, bm & 0x11u);
            if ((aw & 3) == s) mbar_wait_cluster(bar_y + 16 * s + 2 * (aw & 4));
            bar_sync(BC_Y + (aw >> 2), 128);
            const uint32_t sf = fresh(src) + 512 * s;
            uint32_t y[2][4];
            ldsm4t(y[0], sf); ldsm4t(y[1], sf + 256);
            if (routed) {
#pragma unroll
                for (int k = 0; k < 2; k++) store_or_add(outp + (size_t)(512 * s + 4 * k) * DM, y[k], bm & (1u << (4 * k)));
            } else {
                sts128(stg + so + 1024 * s, y[0][0], y[0][1], y[0][2], y[0][3]); sts128(stg + so + 1024 * s + 256, y[1][0], y[1][1], y[1][2], y[1][3]);
                asm volatile("fence.proxy.async.shared::cta;" ::: "memory");
                __syncwarp();
                if (elect()) store_rows(mU + 4, stg + 1024 * s, 16 * slab, 512 * s + rb);
            }
            if (aw == 4) TSTAMP(16 + s);
            if (aw == 0) TSTAMP(16);
        }
        if (elect()) { asm volatile("cp.async.bulk.commit_group;" ::: "memory"); asm volatile("cp.async.bulk.wait_group.read 0;" ::: "memory"); }
        if (aw == 4) TFLUSH();
    }
}

__device__ __forceinline__ uint32_t k_tag(unsigned epoch) { return epoch << 16 | 0x80000000u; }
__device__ __forceinline__ void publish_k(uint4* kp, const uint32_t (&w)[12], unsigned epoch, uint64_t (&v)[6]) {
#pragma unroll
    for (int i = 0; i < 3; i++) {
        v[2 * i] = w[3 * i] | (uint64_t)w[3 * i + 1] << 32; v[2 * i + 1] = w[3 * i + 2] | (uint64_t)__byte_perm(w[9 + (i >> 1)], k_tag(epoch), i == 1 ? 0x7632 : 0x7610) << 32;
        asm volatile("st.relaxed.gpu.global.v2.u64 [%0], {%1,%2};" :: "l"(kp + 32 * i), "l"(v[2 * i]), "l"(v[2 * i + 1]));
    }
}
template <bool FULL>
__device__ __forceinline__ void k_tables(uint32_t kt, int lane, const uint32_t (&w)[12]) {
    const int g = lane >> 2, t = lane & 3, mi = lane >> 3, r8 = lane & 7;
    uint32_t x3 = w[7], re[4], rx[4];
#pragma unroll
    for (int i = 0; i < 4; i++) {
        re[i] = __shfl_sync(0xffffffffu, w[i], lane + 31);
        rx[i] = __shfl_sync(0xffffffffu, w[4 + i], lane + (i == 0 && lane == 29 ? 5 : 1 + 2 * t));
    }
    if (FULL) {
        asm volatile("stmatrix.sync.aligned.m8n8.x2.trans.shared.b16 [%0], {%1,%2};" :: "r"(kt + (KT_D + 7) * 4 + 64 * t + 16 * (mi & 1) + 8 * (r8 & 4)), "r"(w[8]), "r"(w[9]) : "memory");
        if (lane == 2) {
            sts32(kt + (KT_C + 78) * 4, w[10] & 0xffffu);
            sts128(kt + (KT_T + 2) * 4, 0, w[10] & 0xffffu, __byte_perm(w[10], 0, 0x1010), w[10] << 16);
        }
        if (lane == 29) x3 = bsub2(x3, rx[0] & 0xffffu);
    }
#pragma unroll
    for (int i = 0; i < 4; i++) {
        sts64(kt + (16 + 64 * i) * 4 + 8 * lane, __byte_perm(w[i], lane ? re[i] : i ? re[i - 1] : 0, 0x5432), w[i]);
        const uint32_t x = i < 3 ? w[4 + i] : x3, aa = __byte_perm(x, 0, 0x3232);
        if (t < 2) sts128(kt + (272 + 64 * i + 8 * g + 4 * t) * 4, i == 0 && lane == 0 ? __byte_perm(x, re[3], 0x5432) : aa, aa, x,
                          __byte_perm(lane != 29 ? rx[i] : i < 3 ? rx[(i + 1) & 3] : FULL ? 0 : rx[0] << 16, x, 0x5432));
        else if (FULL) sts32(kt + (KT_C - 50 + 8 * i + 32 * t + g) * 4, x);
    }
}

__device__ __forceinline__ void conv_main(const Params& p, uint32_t sb, int warp, int lane0, int bid, unsigned epoch, uint32_t (&w)[12]) {
    asm volatile("setmaxnreg.inc.sync.aligned.u32 168;");
    const int lane = __shfl_sync(0xffffffffu, lane0, lane0);
    const int g = lane >> 2, t = lane & 3, mi = lane >> 3, r8 = lane & 7;
    const int rank = bid & 1;
    const uint32_t bar_y = sb + SC_MISC, bar_v = bar_y + 8;
    next_epoch(p, epoch);
    asm volatile("barrier.cluster.wait.acquire.aligned;" ::: "memory");
    if (warp < 4) {
        bar_arrive(BC_U + warp, 64);
    } else {
        mbar_wait(bar_y + 384);
        if (KPOLL) until(clock32(), KPOLL);
        const uint4* src = p.s->kp + (8 * bid + warp) * 96 + lane0;
#pragma unroll 1
        for (int it = 0;; it++) {
            uint32_t bad = 0, e[3];
#pragma unroll
            for (int i = 0; i < 3; i++) { const uint4 v = ld_rlx128(src + 32 * i); w[3 * i] = v.x; w[3 * i + 1] = v.y; w[3 * i + 2] = v.z; e[i] = v.w; bad |= v.w ^ k_tag(epoch); }
            w[9] = __byte_perm(e[0], e[1], 0x5410); w[10] = e[2];
            const bool ok = __all_sync(0xffffffffu, bad < 65536);
            if (ok) break;
            if (it > (1 << 20)) give_up();
        }
    }
    if ((warp & 3) == 0) TSTAMP(5 + (warp >> 2));
    k_tables<true>(sb + SC_KT + warp * KT_BYTES, lane0, w);
    mbar_wait(bar_y + 384);
    __syncwarp();
    if ((warp & 3) == 0) TSTAMP(7 + (warp >> 2));
    {
        const uint32_t ut = fresh(sb + SC_UT) + warp * UT_STRIDE, kt = fresh(sb + SC_KT) + warp * KT_BYTES;
        auto dup = [&](uint32_t v) { return v ^ p.zero; };
        auto frag = [&](uint32_t (&a)[4], uint32_t x) { a[0] = lds32(x); a[1] = lds32(x + 32); a[2] = lds32(x - 32); a[3] = dup(a[0]); };
        const uint32_t kb = kt + (16 + g - 2 * t) * 4;
        float acc[16][4];
        {
            float y[12][4], M[6][4];
#pragma unroll
            for (int i = 0; i < 12; i++) { y[i][0] = y[i][1] = y[i][2] = y[i][3] = 0.f; M[i >> 1][0] = M[i >> 1][1] = M[i >> 1][2] = M[i >> 1][3] = 0.f; }
            uint32_t U[10][4], a1[4], ad[4], R = (mi & 1) * UT_HALF + (8 + (r8 >> 1) + 48 * (r8 & 1)) * 16 + 64 * (mi >> 1);
            auto places = [&] { ad[0] = swz(R, warp); ad[1] = swz(R + 128, warp); ad[2] = ad[0] ^ 64; ad[3] = ad[1] ^ 64; };
            auto ldu = [&](int k) { ldsm4(U[k], ut + ad[k & 3] + 256 * (k >> 1)); };
            places();
            frag(a1, kb + 2048);
#pragma unroll
            for (int k = 0; k < 7; k++) ldu(k);
#pragma unroll
            for (int i = 0; i < 12; i++) mma_bf(y[i], a1[0], a1[1], a1[2], a1[3], U[i >> 1][2 * (i & 1)], U[i >> 1][2 * (i & 1) + 1]);
            frag(a1, kb + 1792);
            __syncwarp();
#pragma unroll 1
            for (uint32_t ko = 0; ko != 256;) {
                ko = fresh(ko);
                const uint32_t kp = kb + ko;
                ko += 64;
                uint32_t se[10][2], so[10][2], ue[10][2];
                auto sums = [&](int k) {
#pragma unroll
                    for (int e = 0; e < 2; e++) { ue[k][e] = U[k][e]; se[k][e] = badd2(U[k][e], U[k - 1][2 + e]); so[k][e] = badd2(U[k][e], U[k][2 + e]); }
                };
#pragma unroll
                for (int k = 1; k < 6; k++) sums(k);
#pragma unroll
                for (int m = 3; m >= 0; m--) {
                    uint32_t a0[4];
                    frag(a0, kp + 512 * m);
                    sums(9 - m);
                    if (m) ldu(10 - m); else { R -= 16; places(); }
#pragma unroll
                    for (int i = 0; i < 6; i++) mma_bf(y[2 * i], a1[0], a1[1], a1[2], a1[3], se[i - m + 4][0], se[i - m + 4][1]);
#pragma unroll
                    for (int e = 0; e < 4; e++) a1[e] = bsub2(a0[e], a1[e]);
#pragma unroll
                    for (int i = 0; i < 6; i++) { mma_bf(M[i], a1[0], a1[1], a1[2], a1[3], ue[i - m + 4][0], ue[i - m + 4][1]); if (!m) ldu(i); }
                    frag(a1, m ? kp + 512 * m - 256 : kp + 1792 + 64);
                    if (!m) ldu(6);
#pragma unroll
                    for (int i = 0; i < 6; i++) mma_bf(y[2 * i + 1], a0[0], a0[1], a0[2], a0[3], so[i - m + 4][0], so[i - m + 4][1]);
                }
            }
#pragma unroll
            for (int i = 0; i < 6; i++)
#pragma unroll
                for (int c = 0; c < 4; c++) { acc[4 + i + 6 * (c & 1)][c & 2] = y[2 * i][c] + M[i][c]; acc[4 + i + 6 * (c & 1)][c | 1] = y[2 * i + 1][c] - M[i][c]; }
        }
        const uint32_t lo = (8 + col(r8)) * 16 + (mi >> 1) * 128, ua = fresh(ut) + (mi & 1) * UT_HALF, u1[2] = {ua + swz(lo, warp), ua + (swz(lo, warp) ^ 64)};
        {
            uint32_t e[4];
            frag(e, kb + (KT_T - 16) * 4);
            const uint32_t f0 = dup(e[1]), f1 = lds32(kb + KT_T * 4), uo = fresh(ut) + UT_HALF + swz((7 + 8 * mi + col(r8)) * 16, warp);
#pragma unroll
            for (int i = 0; i < 4; i++) {
                uint32_t b[4];
                if (i < 2) {
                    ldsm4(b, uo + 512 * i);
#pragma unroll
                    for (int k = 0; k < 4; k++) mma_bf8(acc[8 + 4 * i + k], f0, f1, b[k]);
                }
                ldsm4(b, u1[i & 1] + 256 * i);
                mma_bf(acc[2 * i + 8], e[0], e[1], e[2], e[3], b[0], b[1]); mma_bf(acc[2 * i + 9], e[0], e[1], e[2], e[3], b[2], b[3]);
            }
        }
        if ((warp & 3) == 0) TSTAMP(11 + (warp >> 2));
        mbar_wait(bar_v);
        const uint32_t vt = fresh(sb + SC_V) + warp * V_STRIDE;
        const uint32_t g1 = fresh(sb + SC_GT) + (mi & 1) * GT_HALF + lo;
        const uint32_t ydst = mapa(sb + SC_RT + rank * Y_RS + warp * Y_CS + (lane & 23) * 16, mi & 1), ybr = mapa(bar_y, mi & 1);
        uint32_t ug[2][2][4];
        auto ld_ug = [&](int i) { ldsm4t(ug[i & 1][0], u1[i & 1] + 256 * i); ldsm4t(ug[i & 1][1], g1 + 256 * i); };
        auto ship = [&](int i) {
            const uint32_t (&u)[4] = ug[i & 1][0], (&gg)[4] = ug[i & 1][1];
            const uint32_t y0 = gmix(gg[0], acc[2 * i][0], acc[2 * i][1], u[0]), y1 = gmix(gg[1], acc[2 * i][2], acc[2 * i][3], u[1]);
            const uint32_t y2 = gmix(gg[2], acc[2 * i + 1][0], acc[2 * i + 1][1], u[2]), y3 = gmix(gg[3], acc[2 * i + 1][2], acc[2 * i + 1][3], u[3]);
            st_async128(ydst + 512 * (i >> 1) + 128 * (i & 1), y0, y1, y2, y3, ybr + 8 * i);
        };
        const uint32_t VD = vt + (VC_OFF - 400 - 16 * t) * 4 + (8 * g ^ 16 * (-t & 2)), VD2 = vt + (VC_OFF - 415 - 16 * t) * 4 + (8 * g ^ 16 * (~t & 2));
        uint2 bd[10];
        uint32_t x[2][4][4];
        auto ld4 = [&](uint32_t (&v)[4], int dl) { const uint2 w = lds64(VD + 256 * dl); v[0] = w.x; v[1] = w.y; v[2] = lds32(VD2 + 256 * dl); v[3] = dup(w.x); };
        auto mm4 = [&](const uint32_t (&v)[4], int dl) {
#pragma unroll
            for (int s = dl & 1; s < 10; s += 2) if ((dl + s) / 2 >= 4 && (dl + s) / 2 < 16) mma_bf(acc[(dl + s) / 2], v[0], v[1], v[2], v[3], bd[s].x, bd[s].y);
        };
        const uint32_t KE = kt + (KT_D + col(g) + t) * 4, VE = vt + (VE_BASE - 912 - 16 * t) * 4 + (8 * g ^ 16 * (~t & 2));
        uint32_t b0[8], b1[8];
        auto ld8 = [&](uint32_t (&v)[4], int dl) { const uint2 w = lds64(VE + 512 * dl), z = lds64(VE + 512 * dl - 256); v[0] = w.x; v[1] = w.y; v[2] = z.x; v[3] = z.y; };
        auto mm8 = [&](const uint32_t (&v)[4], int dl, int lo, int hi) {
#pragma unroll
            for (int s = 0; s < 8; s++) if (dl + s >= lo && dl + s < hi) mma_bf(acc[dl + s], v[0], v[1], v[2], v[3], b0[s], b1[s]);
        };
        ld4(x[0][0], 6);
#pragma unroll
        for (int s = 0; s < 10; s++) bd[s] = lds64(kt + (KT_C + 2 * col(g) + 2 * t + 8 * s) * 4);
        mm4(x[0][0], 6);
        uint32_t e[8][4];
#pragma unroll
        for (int k = 1; k < 6; k++) {
#pragma unroll
            for (int j = 0; j < 4; j++) ld4(x[k & 1][j], 4 * k + 3 + j);
            ld_ug(k + 1);
            if (k == (SCH < 2 ? 3 : 2)) {
#pragma unroll
                for (int s = 0; s < 8; s++) { b0[s] = lds32(KE + 32 * s); b1[s] = lds32(KE + 32 * s + 16); }
            }
            if (k > 1) ship(k);
#pragma unroll
            for (int j = 0; j < 4; j++) {
                mm4(x[k & 1][j], 4 * k + 3 + j);
                if (k == 3) { ld8(e[j], 8 + j); mm8(e[j], 8 + j, 8, 14); }
                if (k == 5 && j < 2) { ld8(e[4 + j], 12 + j); mm8(e[4 + j], 12 + j, 12, 14); }
            }
        }
        ld_ug(7);
        {
            float (&q0)[4] = acc[0], (&q1)[4] = acc[1];
#pragma unroll
            for (int c = 0; c < 4; c++) q0[c] = q1[c] = 0.f;
#pragma unroll
            for (int j = 0; j < 5; j++) {
                if (j == LASTK - 1) ship(6);
                mma_bf(q0, e[j][0], e[j][1], e[j][2], e[j][3], b0[6 - j], b1[6 - j]); mma_bf(q1, e[j][0], e[j][1], e[j][2], e[j][3], b0[7 - j], b1[7 - j]);
            }
            ld8(e[6], 14); ld8(e[7], 15);
#pragma unroll
            for (int j = 0; j < 4; j++) ld4(x[0][j], 27 + j);
            mm8(e[6], 14, 14, 16); mm4(x[0][0], 27); mm4(x[0][1], 28); mm8(e[5], 13, 14, 16); mm8(e[7], 15, 14, 16);
            mma_bf(q1, x[0][2][0], x[0][2][1], x[0][2][2], x[0][2][3], bd[1].x, bd[1].y); mm4(x[0][3], 30);
#pragma unroll
            for (int c = 0; c < 4; c++) { acc[14][c] += q0[c]; acc[15][c] += q1[c]; }
            ship(7);
        }
        if ((warp & 3) == 0) TSTAMP(14 + (warp >> 2)); else TSTAMP(21 + warp);
    }
}

constexpr int SF_WD = 73728;
constexpr int SF_RED = 49152;
constexpr int MU_STRIDE = 1168  , SM_RAW = 98304, SM_UT = SM_RAW + 16384, SM_G = SM_UT + 21504, SM_Y = 196608, SM_FT = SM_Y + 17024, SM_KT = 138880, SM_KW = SM_G - 49152;
constexpr int SF_XS = 221184;
constexpr int SF_MISC = SF_XS + 8 * 1168;
constexpr int SF_KG = SF_MISC - 10 * KG_STAGE;
constexpr int SF_WR = SF_KG - 2304;
constexpr int FB_X = 64, FB_KDONE = 72, FB_KEYS = 80, FB_FREE = 88  , FB_W = 104, FB_D = FB_W + 72, FB_MU = FB_D + 96, FB_FAR = FB_MU - 16, FB_MG = FB_MU + 8, FB_MT = FB_MU + 16  , FS_PART = 512, FS_TOK = 896, FS_BM = 1024;
enum { BAR_R = 7, BAR_GU = 8, BAR_RED = 9, BAR_R2 = 10, BAR_G = 12  , BAR_M = 15 };
static_assert(SF_KG % 128 == 0 && NPRE <= 8 && SM_KT + 4 * 2112 <= 147456 && SM_G + MU_STRIDE <= SF_WR - 4 * 9216 && SM_KW + 6 * 2112 >= SM_RAW && SM_KW + 12 * 2112 <= SM_UT, "layout");

__device__ __forceinline__ constexpr int box_no(int i) { return (0x987610ba5432ull >> (4 * i)) & 15; }
__device__ __forceinline__ int role(int b) { b -= NCONV; return b < NX ? b : 18 + (b >> 1) + 12 * (b & 1); }
__device__ __forceinline__ int mini_ch0(int f) { return 48 * f - (f < NW ? 1696 : 2304); }

__device__ __forceinline__ void ffn_front(const Params& p, const CUtensorMap* maps, uint32_t sb, int warp, int lane, int f, unsigned epoch) {
    const unsigned t0 = clock32();
    const int g = lane >> 2, t = lane & 3, mi = lane >> 3, r8 = lane & 7;
    const bool isx = f < NX;
    const int nrw = f < 52 ? 4 : 6, r0 = f < 52 ? 32 * f : 48 * f - 832;
    const int rw = warp < 12 ? 13 - warp : warp ^ (warp < 14 ? 10 : 15);
    const uint32_t bar_row = sb + SF_MISC  , bar_x = bar_row + FB_X;
    const uint32_t s_part = bar_row + FS_PART  , s_tok = bar_row + FS_TOK  ;
    const uint32_t rows = sb + SF_WR - 9216 * (rw + 1) - (rw & 4) * ((SF_WR - 6 * 9216) / 4);
    {
#pragma unroll 1
        for (int i = warp < 10 ? 30 : warp - 10; i < 30; i += 6) if (elect()) mbar_init(bar_x + 8 * i, i == 1 ? 4 + (f < NW) : i < 27 ? 1 : i == 27 ? 2 : 8);
        const uint32_t bytes = rw < 6 ? 9216 : 1152, dst = rw < 6 ? rows : sb + SF_WR + (rw & 1) * 1152;
        const __nv_bfloat16* src = rw < 6 ? p.u + (size_t)(r0 + 8 * rw) * DM : (rw & 1) ? p.gatew : p.wr;
        if (elect()) { mbar_init(bar_row + 8 * rw, 1); mbar_fence(); mbar_expect(bar_row + 8 * rw, bytes); }
        if (warp == 13) { sts32(s_part + 64 + lane * 4, 0); sts32(bar_row + FS_BM + lane * 4, 0); }
        bar_sync(0, NTHR);
        if (!isx) asm volatile("barrier.cluster.arrive.relaxed.aligned;" ::: "memory");
        if (rw < nrw) until(t0, RDELAY);
        if (rw < nrw || rw >= 6) { if (elect()) bulk_g2s(dst, src, bytes, bar_row + 8 * rw); }
    }
    uint4* const kdst = p.s->keys + (lane >> 1) * 128 + 2 * f + (lane & 1);
    if (warp == 15) TSTAMP(1);

    if (warp == 12) {
        if (lane < 22) mbar_expect(bar_row + FB_W + 8 * lane, lane < 9 ? 24576 : isx ? 12288 : lane < 20 ? 2048 : 16384);
        if (elect()) { prefetch_map(maps + 1); prefetch_map(maps + 2); prefetch_map(maps + (isx ? 3 : 5)); }
        unsigned tb = t0 + WDELAY;
        auto pieces = [&](int n, int end, uint32_t dst) {
#pragma unroll 1
            for (; n < end; n++, dst += 12288) {
                until(tb, 0); tb += WGAP;
                if (elect()) tma3d(dst, maps + 1 + (n & 1), 0, 64 * (n >> 1), 3 * f, bar_row + FB_W + 8 * (n >> 1));
            }
        };
        if (!isx) {
#pragma unroll 1
            for (int k = 0; k <= (f >= NW); k++) { until(t0, MDELAY + k * MGAP); if (elect()) tma4d(sb + SM_RAW - 49152 * k, maps + 5, mini_ch0(f) + 16 * k, 0, 0, 0, bar_row + FB_MU - 8 * k); }
            if (f >= NW) return;
        }
#pragma unroll 1
        for (int i = 0; i < 4; i++) {
            if (i == 1) { mbar_wait(bar_row + FB_KEYS); mbar_wait(bar_row + FB_KDONE); tb = clock32() + RESUME; }
            if (i == 3) mbar_wait(bar_row + FB_FREE);
            const int n = ((0x0c080000 + NPRE * 256) >> (8 * i)) & 255;
            pieces(n, ((0x120c0800 + NPRE) >> (8 * i)) & 255, sb + 12288 * (((0x000c0000 + NPRE * 256) >> (8 * i)) & 255));
        }
        TSTAMP(12);
        if (isx) {
#pragma unroll 1
            for (int i = 0; i < 12; i++) {
                const int n = box_no(i);
                if (i == 6) mbar_wait(bar_row + FB_FREE + 8);
                until(tb, 0); tb += DGAP;
                if (elect()) tma2d(sb + SF_WD + n * 12288, maps + 3, 32 * (f >> 1), 2304 * (f & 1) + 192 * n, bar_row + FB_D + 8 * n);
            }
            TSTAMP(13);
        }
    } else if (warp == 13) {
        const uint32_t tag = key_tag(epoch), par = (epoch & 1) ? 0u : 0x8000u;
        stg128(kdst, 0, 0, 0, 0);
        if (lane < 8 && isx && !(f & 1)) st_rlx32(&p.s->sel[32 * f + lane], 0);
        bar_sync(BAR_R, 32 * (nrw + 1));
        TSTAMP(3);
        {
            const uint32_t sg = fresh(s_part) + 192 + lane * 4;
            const uint32_t gb = pack_bf16(sigmoidf_(rbf(__uint_as_float(lds32(sg)))), sigmoidf_(rbf(__uint_as_float(lds32(sg + 128))))) | par | (par << 16);
            asm volatile("st.relaxed.gpu.global.u16 [%0], %1;" :: "l"(p.s->gate + r0 + lane), "h"((unsigned short)gb) : "memory");
            if (nrw > 4 && lane < 16) asm volatile("st.relaxed.gpu.global.u16 [%0], %1;" :: "l"(p.s->gate + r0 + 32 + lane), "h"((unsigned short)(gb >> 16)) : "memory");
        }
        bar_sync(BAR_R2, 32 * (nrw + 1));
        {
            const uint4 v = lds128(fresh(s_tok) + (lane & 1) * 16);
            asm volatile("st.relaxed.gpu.global.v4.u32 [%0], {%1,%2,%3,%4};" :: "l"(kdst), "r"(v.x | tag), "r"(v.y | tag), "r"(v.z | tag), "r"(v.w | tag) : "memory");
        }
        TSTAMP(4);
        if (lane == 0) { mbar_arrive(bar_row + FB_KEYS); mbar_expect(bar_x, 8 * 1152); }
        if (f >= NW) return;
        mbar_wait(bar_row + FB_KDONE);
        uint32_t k[16];
        const uint4* src = p.s->keys + (f & 15) * 128 + lane;
#pragma unroll 1
        for (int it = 0;; it++) {
            uint32_t bad = 0;
#pragma unroll
            for (int i = 0; i < 4; i++) {
                const uint4 x = ld_rlx128(src + (i < 3 || lane < 24 ? 32 * i : 64));
                k[i] = x.x; k[4 + i] = x.y; k[8 + i] = x.z; k[12 + i] = x.w;
                bad |= x.x ^ tag;
            }
            const bool ok = __all_sync(0xffffffffu, (bad & 0xf800u) == 0);
            if (ok) break;
            if (it > (1 << 20)) give_up();
        }
        TSTAMP(5);
        uint32_t key = 0, m = __reduce_max_sync(0xffffffffu, max(max(k[0], k[1]), max(k[2], k[3])));
#pragma unroll 2
        for (int r = 0; r < 8; r++) {
            bool pop[4];
#pragma unroll
            for (int i = 0; i < 4; i++) { pop[i] = k[i] == m; k[i] = pop[i] ? k[4 + i] : k[i]; }
            const uint32_t mn = __reduce_max_sync(0xffffffffu, max(max(k[0], k[1]), max(k[2], k[3])));
            if (elect()) bulk_g2s(sb + SF_XS + r * 1168, p.u + (size_t)key_row(m) * DM, 1152, bar_x);
#pragma unroll
            for (int i = 0; i < 4; i++) { k[4 + i] = pop[i] ? k[8 + i] : k[4 + i]; k[8 + i] = pop[i] ? k[12 + i] : k[8 + i]; k[12 + i] = pop[i] ? 0 : k[12 + i]; }
            if (r8 == r) key = m;
            m = mn;
        }
        const int row = key_row(key);
        sts32(s_tok + r8 * 8, row);
        TSTAMP(6);
        if (isx) {
            if (!(f & 1)) {
                __nv_bfloat16* o = p.out + (size_t)row * DM + 16 * f + 8 * mi;
                asm volatile("st.relaxed.gpu.global.v4.u32 [%0], {%1,%1,%1,%1};" :: "l"(o), "r"(0) : "memory");
                if (__any_sync(0xffffffffu, ld_rlx32(o) != 0)) give_up();
                if (lane < 8) st_rlx32(&p.s->sel[32 * f + lane], key);
            } else wait_sel(p, f >> 1, r8, tag);
            uint32_t gb;
#pragma unroll 1
            for (int it = 0;; it++) {
                asm volatile("ld.relaxed.gpu.global.u16 %0, [%1];" : "=r"(gb) : "l"(p.s->gate + row) : "memory");
                gb ^= par;
                if (!(gb & 0x8000u)) break;
                if (it > (1 << 20)) give_up();
            }
            const uint32_t rb = key ^ 0x80000000u, rv = (rb ^ (((int)rb >> 31) & 0x7fff0000u)) & 0xffff0000u;
            sts32(s_tok + r8 * 8 + 4, __float_as_uint(rbf(1.0f - bf_lo(gb)) * rbf(sigmoidf_(__uint_as_float(rv)))));
            __syncwarp();
            TSTAMP(7);
            bar_arrive(BAR_RED, 416);
        }
    } else {
        if (rw < nrw) {
            float c[3][4];
#pragma unroll
            for (int i = 0; i < 3; i++) { c[i][0] = c[i][1] = c[i][2] = c[i][3] = 0.f; }
            mbar_wait(bar_row + 48); mbar_wait(bar_row + 56);
            const uint32_t b = fresh(sb + SF_WR) + (g & 1) * 1152 + (g >> 2) * 64 + t * 16 + (g & 2) * 2;
            uint32_t w[18][2];
#pragma unroll
            for (int kb = 0; kb < 18; kb++) { const uint32_t o = ((kb & 1) ? b ^ 64 : b) + 128 * (kb >> 1); w[kb][0] = lds32(o); w[kb][1] = lds32(o + 8); }
            mbar_wait(bar_row + 8 * rw);
            if (warp == 15) TSTAMP(2);
            const uint32_t a = fresh(rows) + g * 1152 + (g & 1) * 64 + t * 16;
#pragma unroll
            for (int kb = 0; kb < 18; kb++) {
                const uint4 x = lds128(((kb & 1) ? a ^ 64 : a) + 128 * (kb >> 1));
                mma_bf(c[kb % 3], x.x, x.y, x.z, x.w, w[kb][0], w[kb][1]);
            }
            const float sr = c[0][0] + c[1][0] + c[2][0] + __shfl_down_sync(0xffffffffu, c[0][2] + c[1][2] + c[2][2], 1);
            const float sg = c[0][1] + c[1][1] + c[2][1] + __shfl_down_sync(0xffffffffu, c[0][3] + c[1][3] + c[2][3], 1);
            const uint32_t rb = pack_bf16(0.f, sr);
            if (t == 2 * (g & 1)) {
                sts32(s_part + (8 * rw + g) * 4, (rb ^ (((int)rb >> 31) & 0x7fff0000u) ^ 0x80000000u) | (uint32_t)(2047 - r0 - 8 * rw - g));
                sts32(s_part + 192 + (8 * rw + g) * 4, __float_as_uint(sg));
            }
            __syncwarp();
            bar_sync(BAR_R, 32 * (nrw + 1));
            const uint32_t sk = fresh(s_part), kk = lds32(sk + (8 * rw + r8) * 4);
            int n = 0;
#pragma unroll
            for (int i = 0; i < 3; i++) { const uint4 v = lds128(sk + mi * 48 + 16 * i); n += (v.x > kk) + (v.y > kk) + (v.z > kk) + (v.w > kk); }
            n += __shfl_xor_sync(0xffffffffu, n, 8); n += __shfl_xor_sync(0xffffffffu, n, 16);
            if (n < 8) sts32(s_tok + 4 * n, kk);
            __syncwarp();
            bar_arrive(BAR_R2, 32 * (nrw + 1));
        }
    }
}

__device__ __forceinline__ void ffn_work(const Params& p, uint32_t sb, int warp, int lane, int f, unsigned epoch) {
    const int g = lane >> 2, t = lane & 3, mi = lane >> 3, r8 = lane & 7;
    const bool isx = f < NX;
    const uint32_t bar_x = sb + SF_MISC + FB_X, bar_free = sb + SF_MISC + FB_FREE, bar_w = sb + SF_MISC + FB_W, bar_d = sb + SF_MISC + FB_D, s_tok = sb + SF_MISC + FS_TOK;
    uint32_t fr[24][4];
    auto pin = [&] {
#pragma unroll
        for (int i = 0; i < 24; i += 8) asm volatile("" :: "r"(fr[i][0]), "r"(fr[i + 1][0]), "r"(fr[i + 2][0]), "r"(fr[i + 3][0]), "r"(fr[i + 4][0]), "r"(fr[i + 5][0]), "r"(fr[i + 6][0]), "r"(fr[i + 7][0]) : "memory");
    };
    {
        const int j = (unsigned)(warp - 4) < 6, w = warp - (j ? 4 : warp < 4 ? 0 : 6);
        float ag[2][4], au[2][4];
#pragma unroll
        for (int i = 0; i < 2; i++) { ag[i][0] = ag[i][1] = ag[i][2] = ag[i][3] = 0.f; au[i][0] = au[i][1] = au[i][2] = au[i][3] = 0.f; }
        const uint32_t wb = sb + (w >> 1) * 4096 + (r8 + 8 * (mi >> 1)) * 64 + (((2 * (w & 1) + (mi & 1)) ^ (r8 >> 1)) << 4);
        const uint32_t xb = sb + SF_XS + r8 * 1168 + mi * 16;
        auto load = [&](int i, int n, int place) {
            mbar_wait(bar_w + 8 * n);
            const uint32_t wk = fresh(wb) + place * 24576;
#pragma unroll
            for (int s = 0; s < 4; s++) { ldsm4t(fr[8 * i + s], wk + 1024 * s); ldsm4t(fr[8 * i + 4 + s], wk + 1024 * s + 12288); }
        };
        auto mul = [&](int i, uint32_t xk) {
            uint32_t x[2][4];
            ldsm4(x[0], xk); ldsm4(x[1], xk + 64);
#pragma unroll
            for (int s = 0; s < 4; s++) {
                const uint32_t (&a)[4] = fr[8 * i + s], (&b)[4] = fr[8 * i + 4 + s];
                mma_bf(ag[s & 1], a[0], a[1], a[2], a[3], x[s >> 1][2 * (s & 1)], x[s >> 1][2 * (s & 1) + 1]);
                mma_bf(au[s & 1], b[0], b[1], b[2], b[3], x[s >> 1][2 * (s & 1)], x[s >> 1][2 * (s & 1) + 1]);
            }
        };
#pragma unroll
        for (int i = 0; i < 3; i++) load(i, 3 * j + i, (i ? 5 : 3) * j + i);
        pin();
        bar_sync(BAR_G + j, 192);
        if (w == 0 && lane == 0) mbar_arrive(bar_free + 8 * j);
        mbar_wait(bar_x);
        if (warp == 0) TSTAMP(8);
        {
            const uint32_t xk = fresh(xb) + 384 * j;
#pragma unroll
            for (int i = 0; i < 3; i++) { mul(i, (i ? fresh(xk) : xk) + 128 * i); if (i == 0) { asm volatile("" :: "f"(ag[0][0]), "f"(ag[1][0]), "f"(au[0][0]), "f"(au[1][0])); sts32(s_tok + 64, clock32()); } }
        }
#pragma unroll 1
        for (int n = 6 + j; n < 9; n += 2) { load(0, n, n - 6); mul(0, fresh(xb) + 128 * n); }
#pragma unroll
        for (int c = 0; c < 4; c++) { ag[0][c] += ag[1][c]; au[0][c] += au[1][c]; }
        if (j) {
            sts128(wb + 24576, __float_as_uint(ag[0][0]), __float_as_uint(ag[0][1]), __float_as_uint(ag[0][2]), __float_as_uint(ag[0][3]));
            sts128(wb + 25600, __float_as_uint(au[0][0]), __float_as_uint(au[0][1]), __float_as_uint(au[0][2]), __float_as_uint(au[0][3]));
        }
        bar_sync(BAR_GU, 384);
        if (!j) {
            const uint32_t sf = fresh(wb);
            const uint4 g1 = lds128(sf + 24576), u1 = lds128(sf + 25600);
            const uint32_t gs[4] = {g1.x, g1.y, g1.z, g1.w}, us[4] = {u1.x, u1.y, u1.z, u1.w};
            if (warp == 0) TSTAMP(9);
            float h[4];
#pragma unroll
            for (int c = 0; c < 4; c++) {
                const float gv = rbf(ag[0][c] + __uint_as_float(gs[c]));
                h[c] = rbf(gv * sigmoidf_(gv)) * rbf(au[0][c] + __uint_as_float(us[c]));
            }
            uint32_t h0, h1;
            asm("movmatrix.sync.aligned.m8n8.trans.b16 %0, %1;" : "=r"(h0) : "r"(pack_bf16(h[0], h[1])));
            asm("movmatrix.sync.aligned.m8n8.trans.b16 %0, %1;" : "=r"(h1) : "r"(pack_bf16(h[2], h[3])));
            if (h0 == 0) h0 = 0x8000u;
            asm volatile("{ .reg .b64 v; mov.b64 v, {%1, %2}; st.relaxed.gpu.global.b64 [%0], v; }" :: "l"(p.s->h + ((epoch & 1) * 288 + 6 * f + w) * 32 + lane), "r"(h0), "r"(h1) : "memory");
        }
        if (isx) {
            if (warp == 0) TSTAMP(10);
            const uint2* hsrc = p.s->h + ((epoch & 1) * 288 + 144 * (f & 1) + warp) * 32 + lane;
            const uint32_t wd = sb + SF_WD + warp * 1024 + (r8 + 8 * (mi >> 1)) * 64 + (((mi & 1) ^ (r8 >> 1)) << 4), we = wd ^ 32;
            uint2 hb[12];
            auto ldh = [&](int i) { asm volatile("ld.relaxed.gpu.global.v2.u32 {%0, %1}, [%2];" : "=r"(hb[i].x), "=r"(hb[i].y) : "l"(hsrc + 384 * box_no(i)) : "memory"); };
            auto ldw = [&](int i) { mbar_wait(bar_d + 8 * box_no(i)); ldsm4t(fr[2 * i], fresh(wd) + 12288 * box_no(i)); ldsm4t(fr[2 * i + 1], fresh(we) + 12288 * box_no(i)); };
#pragma unroll
            for (int i = 0; i < DPA; i++) ldw(i);
#pragma unroll
            for (int i = 0; i < 12; i++) ldh(i);
#pragma unroll
            for (int i = DPA; i < DPB; i++) ldw(i);
#pragma unroll
            for (int i = 0; i < DPB; i++) asm volatile("" :: "r"(fr[2 * i][0]), "r"(fr[2 * i + 1][0]) : "memory");
#pragma unroll 1
            for (int it = 0;; it++) {
                bool again = false;
#pragma unroll
                for (int s = 0; s < 12; s += 2) if (__any_sync(0xffffffffu, min(hb[s].x, hb[s + 1].x) == 0)) { ldh(s); ldh(s + 1); again = true; }
                if (!again) break;
                if (it > (1 << 16)) give_up();
            }
            if (warp == 0) TSTAMP(11);
            float ad[2][2][4];
#pragma unroll
            for (int i = 0; i < 4; i++) { ad[i >> 1][i & 1][0] = ad[i >> 1][i & 1][1] = ad[i >> 1][i & 1][2] = ad[i >> 1][i & 1][3] = 0.f; }
#pragma unroll
            for (int i = 0; i < 12; i++) {
                if (i >= DPB) ldw(i);
                if (i == 11 && warp == 9) TSTAMP(14);
#pragma unroll
                for (int c = 0; c < 2; c++) mma_bf(ad[c][i & 1], fr[2 * i + c][0], fr[2 * i + c][1], fr[2 * i + c][2], fr[2 * i + c][3], hb[i].x, hb[i].y);
                if (i >= DPB - 1) asm volatile("" :: "f"(ad[0][i & 1][0]), "f"(ad[1][i & 1][0]) : "memory");
            }
            const uint32_t rd = sb + SF_RED + warp * 1152 + (72 * t + g) * 4;
#pragma unroll
            for (int i = 0; i < 8; i++) sts32(rd + (i >> 2) * 64 + (i & 1) * 144 + ((i >> 1) & 1) * 32, __float_as_uint(ad[i >> 2][0][i & 3] + ad[i >> 2][1][i & 3]));
            bar_sync(BAR_RED, 416);
            if (warp < 4) {
                const int tid = 32 * warp + lane;
                const uint32_t rs = fresh(sb + SF_RED) + (tid >> 4) * 144 + (tid & 15) * 8;
                const uint2 tk = lds64(fresh(s_tok) + (tid >> 4) * 8);
                float x = 0.f, y = 0.f;
#pragma unroll
                for (int w = 0; w < 12; w++) { const uint2 v = lds64(rs + w * 1152); x += __uint_as_float(v.x); y += __uint_as_float(v.y); }
                asm volatile("red.relaxed.gpu.global.add.noftz.bf16x2 [%0], %1;" :: "l"(p.out + (size_t)tk.x * DM + 32 * (f >> 1) + 2 * (tid & 15)),
                             "r"(pack_bf16(x * __uint_as_float(tk.y), y * __uint_as_float(tk.y))) : "memory");
            }
            if (warp == 0) { TSTAMP(15); TFLUSH(); }
            asm volatile("exit;"); __builtin_unreachable();
        }
    }
}

__device__ __forceinline__ void fetch_k(const uint4* src, uint64_t (&v)[6], uint32_t a, uint32_t b) {
    asm volatile("{ .reg .pred p; setp.eq.u32 p, %7, %8; @p ld.relaxed.gpu.global.v2.u64 {%0,%1}, [%6]; @p ld.relaxed.gpu.global.v2.u64 {%2,%3}, [%6 + 512]; @p ld.relaxed.gpu.global.v2.u64 {%4,%5}, [%6 + 1024]; }"
                 : "+l"(v[0]), "+l"(v[1]), "+l"(v[2]), "+l"(v[3]), "+l"(v[4]), "+l"(v[5]) : "l"(src), "r"(a), "r"(b));
}
__device__ __forceinline__ uint32_t mini_conv(const Params& p, uint32_t sb, int warp, int lane, int f, unsigned epoch, uint64_t (&v)[6]) {
    const int g = lane >> 2, t = lane & 3, mi = lane >> 3, r8 = lane & 7;
    const uint32_t fb = sb + SF_MISC, kt = sb + (warp >= 12 ? SM_KT - 12 * 2112 : f < NW ? SM_KW + 2 * 2112 : SM_KW) + warp * 2112;
    const bool ism = f >= NW;
    const uint32_t* const sel = &p.s->sel[((mini_ch0(f) + (ism ? 2 * (warp & 8) : 0)) >> 5) * 64 + r8];
    uint32_t seq = 128, key;
    const uint4* src = p.s->kp + lane;
    auto hi = [&](int i) { return (uint32_t)(v[i] >> 32); };
    if (f >= (warp < 4 ? NW : NX)) {
    {
        const uint32_t c = 68 + (warp & 3) + 2 * (warp & 12), y = ((uint32_t)((warp < 8 ? 0xe066806400000000ull : 0x5a6e00680080e26cull) >> ((8 * warp) & 48)) & 0xffff) + (warp < 14 ? 0 : 0x6a0000);
        seq = !ism ? y + (warp & 1) * ((y >> 6) & 0x10101) : warp < 14 ? 0x101 * c - 0x400 : c;
        src += (48 * (f - (ism ? NW : NX)) + (seq & 63)) * 96;
    }
    if (seq & 64) {
        if (seq & 4) {
            const int q = (seq & 3) + ((seq >> 1) & 4);
            const uint32_t ab = sb - 3072 * (seq & 16), d = ab + SM_UT + g * MU_STRIDE + (4 + 4 * q + t) * 32;
            asm volatile("st.shared.v2.u32 [%0], {%1,%1};" :: "r"(ab + SM_UT + (2 * q + (mi >> 1)) * MU_STRIDE + (lane & 15) * 8), "r"(0) : "memory");
            mbar_wait(fb + FB_MU - (seq & 16) / 2);
            if (warp == 15) TSTAMP(16);
            const uint32_t a = fresh(ab + SM_RAW) + q * 2048 + (8 * mi + 4 * (r8 & 1) + (r8 >> 1)) * 32 + ((r8 & 1) << 4);
            uint32_t x[4][4];
#pragma unroll
            for (int i = 0; i < 4; i++) ldsm4t(x[i], (i & 2 ? a ^ 16 : a) + 1024 * (i & 1));
#pragma unroll
            for (int i = 0; i < 4; i++) sts128(d + (i & 1) * 16 + (i & 2) * 4 * MU_STRIDE, x[i][0], x[i][1], x[i][2], x[i][3]);
            __syncwarp();
            if (lane == 0) mbar_arrive(fb + FB_MT + (seq & 16) / 2);
        }
        mbar_wait(fb + FB_KDONE);
        fetch_k(src, v, warp < 4, 0);
        if ((warp | 2) == 7) { fetch_gates(p, (warp >> 1) & 1, lane, epoch, sb + SM_G + 256 * (warp & 2) + 16 * lane); __syncwarp(); if (lane == 0) mbar_arrive(fb + FB_MG); }
        if (warp >= 8) {
            mbar_wait(fb + FB_KEYS); mbar_wait(fb + FB_MT);
            if (ism) {
                asm volatile("barrier.cluster.wait.aligned; fence.release.sync_restrict::shared::cta.cluster;" ::: "memory");
                if (lane == 0) asm volatile("mbarrier.arrive.relaxed.cluster.shared::cluster.b64 _, [%0];" :: "r"(mapa(fb + FB_MT + 8, 0)) : "memory");
            }
        }
        if (warp == TW) TSTAMP(17);
    }
    }
    const uint32_t lo = (8 + r8 - (mi & 1)) * 16 + (mi >> 1) * 128;
#pragma unroll 1
    do {
        const int c = seq & 63;
        const bool far = !ism && (seq & 16);
        const uint32_t ab = sb - 3072 * (c & 16);
        uint32_t ut = ab + SM_UT + (c & 15) * MU_STRIDE;
        if (seq & 64) {
        if (far) {
            mbar_wait_cluster(fb + FB_MT + 8);
            const uint32_t ru = mapa(ut, 1) + lane * 16;
            ut = sb + SM_FT + (c & 3) * 1536;
            uint4 x[3];
#pragma unroll
            for (int i = 0; i < 3; i++) asm volatile("ld.shared::cluster.v4.u32 {%0,%1,%2,%3}, [%4];" : "=r"(x[i].x), "=r"(x[i].y), "=r"(x[i].z), "=r"(x[i].w) : "r"(ru + 512 * i) : "memory");
#pragma unroll
            for (int i = 0; i < 3; i++) sts128(ut + lane * 16 + 512 * i, x[i].x, x[i].y, x[i].z, x[i].w);
        } else mbar_wait(fb + FB_MT + (seq & 16) / 2);
#pragma unroll 1
        for (int it = 0; !__all_sync(0xffffffffu, ((hi(1) ^ k_tag(epoch)) | (hi(3) ^ k_tag(epoch)) | (hi(5) ^ k_tag(epoch)) | ((uint32_t)v[5] & p.zero)) < 65536); it++) {
            fetch_k(src, v, 0, 0);
            if (it > (1 << 20)) give_up();
        }
        sts128(kt + t * 16, 0, 0, 0, 0);
        if (warp == TW) TSTAMP(seq >> 8 ? 7 : 10);
        const uint32_t w[12] = {(uint32_t)v[0], hi(0), (uint32_t)v[1], (uint32_t)v[2], hi(2), (uint32_t)v[3], (uint32_t)v[4], hi(4), 0, 0, 0, 0};
        k_tables<false>(fresh(kt), fresh(lane), w);
        }
        __syncwarp();
        if (seq & 128) ffn_work(p, sb, warp, fresh(lane), f, epoch);
        if (!(seq & 64)) return 0;
        const uint32_t kb = fresh(kt) + (16 + g - 2 * t) * 4, ub = fresh(ut);
        const uint32_t yd = ab + SM_Y + (c & 15) * 1056 + (c & 8) * 8 + lane * 16;
        if (warp == TW && !(seq >> 8)) TSTAMP(13);
        seq >>= 8;
        src += ((int)(seq & 63) - c) * 96;
#pragma unroll
        for (int i = 0; i < 6; i++) v[i] = 0;
        key = 0;
        float acc[8][4];
#pragma unroll
        for (int i = 0; i < 8; i++) { acc[i][0] = acc[i][1] = acc[i][2] = acc[i][3] = 0.f; }
        uint32_t a[4][4], b[2][4][4];
        auto lda = [&](int j, int s) { const uint32_t x = kb + 64 * s + 512 * j; a[j][0] = lds32(x); a[j][1] = lds32(x + 256); a[j][2] = lds32(x + 32); a[j][3] = lds32(x + 288); };
        auto ldb = [&](int i, int s) { ldsm4(b[s & 1][i], ub + lo + 256 * i - 32 * s); };
#pragma unroll
        for (int j = 0; j < 4; j++) { ldb(j, 0); lda(j, 0); }
#pragma unroll
        for (int s = 0; s < 4; s++) {
            if (s == 2) {
                const uint32_t e = seq | (__float_as_uint(acc[0][0]) & p.zero);
                fetch_k(src, v, e & 64, 64);
                asm volatile("{ .reg .pred p; setp.eq.u32 p, %2, 0; @p ld.relaxed.gpu.global.u32 %0, [%1]; }" : "+r"(key) : "l"(sel), "r"(e));
            }
#pragma unroll
            for (int i = 0; i < 4; i++) {
                const int j = (i >> 1) + 2 * (i & 1);
                if (s < 3) ldb(i, s + 1);
#pragma unroll
                for (int mu = 0; mu < 8; mu++) if (mu + 2 * j < 8) mma_bf(acc[mu + 2 * j], a[j][0], a[j][1], a[j][2], a[j][3], b[s & 1][mu >> 1][2 * (mu & 1)], b[s & 1][mu >> 1][2 * (mu & 1) + 1]);
                if (s < 3) lda(j, s + 1);
            }
        }
        if (warp == TW && !seq) TSTAMP(14);
        mbar_wait(fb + FB_MG);
        uint32_t ug[4][4];
#pragma unroll
        for (int i = 0; i < 2; i++) { ldsm4t(ug[i], ub + 128 + lane * 16 + 512 * i); ldsm4t(ug[2 + i], fresh(sb + SM_G) + lane * 16 + 512 * i); }
#pragma unroll
        for (int x = 0; x < 8; x++) ug[x >> 2][x & 3] = gmix(ug[2 + (x >> 2)][x & 3], x ? acc[x][0] + acc[x - 1][2] : acc[0][0], x ? acc[x][1] + acc[x - 1][3] : acc[0][1], ug[x >> 2][x & 3]);
        if (far) for (int i = 0; i < 2; i++) st_async128(mapa(yd, 1) + 512 * i, ug[i][0], ug[i][1], ug[i][2], ug[i][3], mapa(fb + FB_FAR, 1));
        else for (int i = 0; i < 2; i++) sts128(yd + 512 * i, ug[i][0], ug[i][1], ug[i][2], ug[i][3]);
        __syncwarp();
        if (warp == TW) TSTAMP(18 + (seq != 0));
    } while (seq);
    if (warp >= 12) TSTAMP(12 + warp);
    return key;
}
__device__ __forceinline__ void mini_out(const Params& p, const CUtensorMap* maps, uint32_t sb, int warp, int lane, int f, unsigned epoch, uint32_t key) {
    const int g = lane >> 2, t = lane & 3, mi = lane >> 3, r8 = lane & 7;
    const uint32_t fb = sb + SF_MISC;
    const bool ism = f >= NW;
    const int ch0 = mini_ch0(f);
    const int k = ism ? warp >> 3 : 0;
    uint32_t first = 1;
    if (lane == 0) asm volatile("atom.shared.exch.b32 %0, [%1], 1;" : "=r"(first) : "r"(fb + FS_BM + 64 + 4 * k) : "memory");
    if (!__all_sync(0xffffffffu, first)) {
        if (elect()) prefetch_map(maps + 6);
        const int row = key_row(wait_sel(p, (ch0 + 16 * k) >> 5, r8, key_tag(epoch), key));
        if (row < 512) asm volatile("red.shared.or.b32 [%0], %1;" :: "r"(fb + FS_BM + (row >> 5) * 4), "r"(1u << (row & 31)) : "memory");
        if (k) mbar_wait_cluster(fb + FB_FAR);
    }
    const int m = warp & 7, dr = 64 * (g >> 1) + 16 * (t >> 1) + 8 * (g & 1);
    const uint32_t y = SM_Y + ((r8 >> 1) & 1) * 8512 + (2 * mi + (r8 & 1)) * 1056 + (2 * m + (r8 >> 2)) * 16;
    const uint32_t so = (g >> 1) * 128 + (t >> 1) * 64 + (g & 1) * 32 + (t & 1) * 16;
    bar_sync(BAR_M - k, ism ? 256 : NTHR);
#pragma unroll 1
    for (int h = ism ? 0 : warp >> 3;; h++) {
        const int r0 = 256 * h + 32 * (m & 1) + (m >> 1), row = r0 + dr;
        const uint32_t bm = lds32(fresh(fb) + FS_BM + (row >> 5) * 4) >> (row & 31), ab = fresh(sb - 49152 * k + 512 * h), stg = ab + SM_UT + 2048 * m + 512 * h;
        uint32_t x[2][4];
        ldsm4t(x[0], ab + y); ldsm4t(x[1], ab + y + 256);
        if (warp == 0 && x[0][0] != 0x12345) TSTAMP(28);
        if (__any_sync(0xffffffffu, bm & 0x11u)) {
#pragma unroll
            for (int i = 0; i < 2; i++) store_or_add(p.out + (size_t)(row + 4 * i) * DM + ch0 + 16 * k + 8 * (t & 1), x[i], bm & (1u << (4 * i)));
        } else {
#pragma unroll
            for (int i = 0; i < 2; i++) sts128(stg + so + 512 * i, x[i][0], x[i][1], x[i][2], x[i][3]);
            asm volatile("fence.proxy.async.shared::cta;" ::: "memory");
            __syncwarp();
            if (elect()) store_rows(maps + 6, stg, ch0 + 16 * k, r0);
        }
        if (h >= ism) break;
    }
    if (elect()) { asm volatile("cp.async.bulk.commit_group;" ::: "memory"); asm volatile("cp.async.bulk.wait_group.read 0;" ::: "memory"); }
    if (warp == 8) TSTAMP(11);
    if (warp == 0) { TSTAMP(15); TFLUSH(); }
}

constexpr int SMEM_BYTES = 232448;
static_assert(SF_MISC + 1152 <= 232192, "layout");

struct Maps { CUtensorMap m[7]; };

__global__ void __cluster_dims__(2, 1, 1) __launch_bounds__(NTHR, 1)
fused_kernel(const Params p, const __grid_constant__ Maps maps) {
    extern __shared__ __align__(1024) uint8_t smem_raw[];
    uint32_t q[8];
    {
        const int b = role(blockIdx.x), x = threadIdx.x, rc = 5 * b + (b & ~3) + 4 + (x >> 6);
        const int cv = (unsigned)b < NW ? 0 : -1, ca = (b < 0 ? 8 * b + DM : 48 * b - 2300) + ((x >> 5) & 3), cb = 2 * rc - (rc & 3) + 4;
        const uint32_t ch = (ca & cv) | (cb & ~cv), o = NST * ch + 2 * ((x & 31) + ((x >> (cv & 2)) & 32));
        const bool c = x < (cv ? 256 : 320);
        q[6] = ldg16_if(c, p.logdt + ch);
        q[2] = ldg32_if(c, p.Bre + o); q[3] = ldg32_if(c, p.Bim + o); q[4] = ldg32_if(c, p.Cre + o); q[5] = ldg32_if(c, p.Cim + o); q[0] = ldg32_if(c, p.Are + o); q[1] = ldg32_if(c, p.Aim + o);
        q[7] = ldg16_if(c, p.Dskip + ch);
    }
    const unsigned epoch = ld_rlx32(&p.s->epoch[blockIdx.x * 16 + (threadIdx.x >> 5)]);
    const uint32_t sb = __shfl_sync(0xffffffffu, smem_u32(smem_raw), 0);
    const int warp = __shfl_sync(0xffffffffu, threadIdx.x >> 5, 0), bid = __shfl_sync(0xffffffffu, blockIdx.x, 0);
    const int lane = __shfl_sync(0xffffffffu, threadIdx.x & 31, threadIdx.x);
    const bool conv = bid < NCONV;
    const int f = role(bid);
    uint32_t w[12];
    uint64_t v[6];
    const bool four = (unsigned)f >= NW;
    if (warp < (four ? 8 : 10)) {
        const int half = four ? warp >> 2 : warp & 1, pr = four ? warp & 3 : warp >> 1;
        const int rc = 5 * f + (f & ~3) + 4 + pr;
        const uint32_t stage = sb + (conv ? SC_KG : SF_KG) + warp * KG_STAGE;
        uint4* const kp = p.s->kp + (four ? (conv ? 8 * bid : 48 * f - 2300) + pr : 2 * rc - (rc & 3) + 4) * 96 + lane;
        kgen(q, sb, half, stage, stage + (four ? 4 : 1) * KG_STAGE, 1 + pr, lane, w, [&] {
            sts128z_if(conv && lane < 20, sb + SC_KT + warp * KT_BYTES + lane * 16 + (lane < 4 ? 0 : lane < 14 ? 2048 : 2288));
            stg128z_if(!conv, kp + 64 * half); stg128z_if(!half && !conv, kp + 32);
            stg128z_if((unsigned)f < NW && warp < 6, (uint4*)(p.s->h + ((lane >> 4) * 288 + 6 * f + warp) * 32) + (lane & 15));
            if (!conv) bar_sync(0, NTHR);
            if ((unsigned)f >= NX) asm volatile("barrier.cluster.arrive.relaxed.aligned;" ::: "memory");
        });
        if (!half) publish_k(kp, w, epoch, v);
        else for (int i = 0; i < 6; i++) v[i] = 0;
        if (conv) { conv_main(p, sb, warp, lane, bid, epoch, w); return; }
        {
            if (!half && lane == 0) mbar_arrive(sb + SF_MISC + FB_KDONE);
            if (warp == 0) TSTAMP(22);
            if (warp == 2) TSTAMP(23);
        }
    } else if (conv) {
        conv_aux(p, maps.m, sb, warp - 8, lane, bid, epoch);
        return;
    } else {
        ffn_front(p, maps.m, sb, warp, lane, f, epoch);
        for (int i = 0; i < 6; i++) v[i] = 0;
    }
    converged();
    next_epoch(p, epoch);
    if (warp >= 12 && f < NX) return;
    mini_out(p, maps.m, sb, warp, lane, f, epoch, mini_conv(p, sb, warp, __shfl_sync(0xffffffffu, lane, lane), f, epoch, v));
}

typedef CUresult (*EncodeFn)(CUtensorMap*, CUtensorMapDataType, cuuint32_t, void*, const cuuint64_t*, const cuuint64_t*, const cuuint32_t*, const cuuint32_t*,
                             CUtensorMapInterleave, CUtensorMapSwizzle, CUtensorMapL2promotion, CUtensorMapFloatOOBfill);

void make_map(EncodeFn fn, CUtensorMap* m, const void* base, int rank, const cuuint64_t* dims, const cuuint64_t* strides, const cuuint32_t* box, CUtensorMapSwizzle sw) {
    const cuuint32_t es[5] = {1, 1, 1, 1, 1};
    fn(m, CU_TENSOR_MAP_DATA_TYPE_BFLOAT16, rank, (void*)base, dims, strides, box, es, CU_TENSOR_MAP_INTERLEAVE_NONE, sw,
       CU_TENSOR_MAP_L2_PROMOTION_NONE, CU_TENSOR_MAP_FLOAT_OOB_FILL_NONE);
}

}

extern "C" void kernel_launch(void* const* d_in, const int* in_sizes, int n_in, void* d_out, int out_size) {
    (void)in_sizes; (void)n_in; (void)out_size;
    static EncodeFn fn = nullptr;
    static void* scratch = nullptr;
    if (!fn) {
        void* ptr = nullptr; cudaDriverEntryPointQueryResult qr;
        cudaGetDriverEntryPoint("cuTensorMapEncodeTiled", &ptr, cudaEnableDefault, &qr);
        fn = (EncodeFn)ptr;
        cudaGetSymbolAddress(&scratch, g_scratch);
        cudaFuncSetAttribute(fused_kernel, cudaFuncAttributeMaxDynamicSharedMemorySize, SMEM_BYTES);
    }
    typedef const __nv_bfloat16* bp;
    Params p;
    p.u = (bp)d_in[0]; p.Are = (bp)d_in[1]; p.Aim = (bp)d_in[2]; p.Bre = (bp)d_in[3]; p.Bim = (bp)d_in[4]; p.Cre = (bp)d_in[5]; p.Cim = (bp)d_in[6];
    p.logdt = (bp)d_in[7]; p.Dskip = (bp)d_in[8]; p.wr = (bp)d_in[10]; p.gatew = (bp)d_in[14];
    p.out = (__nv_bfloat16*)d_out; p.s = (Scratch*)scratch; p.zero = 0;
    Maps maps;
    {
        const cuuint64_t dims[4] = {DM, 4, 16, 32}, strides[3] = {16 * DM * 2, DM * 2, 64 * DM * 2};
        const cuuint32_t box[4] = {16, 4, 16, 2};
        make_map(fn, &maps.m[0], d_in[0], 4, dims, strides, box, CU_TENSOR_MAP_SWIZZLE_32B);
        const cuuint32_t box2[4] = {16, 4, 16, 8};
        make_map(fn, &maps.m[5], d_in[0], 4, dims, strides, box2, CU_TENSOR_MAP_SWIZZLE_32B);
    }
    for (int i = 0; i < 2; i++) {
        const cuuint64_t dims[3] = {32, DM, FF / 32}, strides[2] = {FF * 2, 64};
        const cuuint32_t box[3] = {32, 64, 3};
        make_map(fn, &maps.m[1 + i], d_in[11 + i], 3, dims, strides, box, CU_TENSOR_MAP_SWIZZLE_64B);
    }
    {
        const cuuint64_t dims[2] = {DM, FF}, strides[1] = {DM * 2};
        const cuuint32_t box[2] = {32, 192};
        make_map(fn, &maps.m[3], d_in[13], 2, dims, strides, box, CU_TENSOR_MAP_SWIZZLE_64B);
    }
    {
        const cuuint64_t dims[5] = {DM, 2, 4, 4, L_SEQ}, strides[4] = {16 * DM * 2, 64 * DM * 2, 4 * DM * 2, DM * 2};
        const cuuint32_t box[5] = {16, 2, 4, 4, 1};
        make_map(fn, &maps.m[4], d_out, 5, dims, strides, box, CU_TENSOR_MAP_SWIZZLE_NONE);
    }
    {
        const cuuint64_t dims[5] = {DM, 4, 4, 2, L_SEQ}, strides[4] = {8 * DM * 2, 64 * DM * 2, 4 * DM * 2, DM * 2};
        const cuuint32_t box[5] = {16, 4, 4, 2, 1};
        make_map(fn, &maps.m[6], d_out, 5, dims, strides, box, CU_TENSOR_MAP_SWIZZLE_NONE);
    }
    fused_kernel<<<NCTA, NTHR, SMEM_BYTES>>>(p, maps);
}
```

```cpp
#include <cuda_runtime.h>
#include <cuda_bf16.h>
#include <cuda_fp16.h>
#include <cuda.h>
#include <stdint.h>

#define RESUME 300
#define MDELAY 2000
#define MGAP 0
#define KPOLL 650
#define DPA 7
#define DPB 9
#define RDELAY 900
#define WDELAY 1700
#define WGAP 290
#define NPRE 8
#define DGAP 290
namespace {

constexpr int DM = 576, NST = 128, FF = 4608, L_SEQ = 2048;
constexpr int NCONV = 72, NX = 36, NW = 48, NCTA = 132, NTHR = 512;

struct __align__(128) Scratch {
    unsigned epoch[NCTA * 16];
    uint4 keys[16 * 128];
    uint32_t sel[18 * 64];
    uint16_t gate[L_SEQ];
    uint2 h[2 * 288 * 32];
    uint4 kp[DM * 96];
};
__device__ Scratch g_scratch;
#define TFLUSH()
#define TSTAMP(i)
#define TW 12

struct Params {
    const __nv_bfloat16 *Are, *Aim, *Bre, *Bim, *Cre, *Cim, *logdt, *Dskip, *u, *wr, *gatew;
    __nv_bfloat16* out;
    Scratch* s;
    uint32_t zero;
};

__device__ __forceinline__ void give_up() { asm volatile("trap; exit;"); __builtin_unreachable(); }
__device__ __forceinline__ void converged() { __syncwarp(); asm volatile("{ .reg .b32 t; mov.b32 t, 0; movmatrix.sync.aligned.m8n8.trans.b16 t, t; }" ::: "memory"); }
__device__ __forceinline__ bool elect() { uint32_t r; asm volatile("{ .reg .pred p; elect.sync _|p, 0xffffffff; selp.u32 %0, 1, 0, p; }" : "=r"(r)); return r; }
__device__ __forceinline__ uint32_t smem_u32(const void* p) { return (uint32_t)__cvta_generic_to_shared(p); }
__device__ __forceinline__ uint32_t pack_bf16(float lo, float hi) { uint32_t r; asm("cvt.rn.bf16x2.f32 %0, %1, %2;" : "=r"(r) : "f"(hi), "f"(lo)); return r; }
__device__ __forceinline__ uint32_t pack_f16(float lo, float hi) { uint32_t r; asm("cvt.rn.f16x2.f32 %0, %1, %2;" : "=r"(r) : "f"(hi), "f"(lo)); return r; }
__device__ __forceinline__ float bf_lo(uint32_t w) { return __uint_as_float(w << 16); }
__device__ __forceinline__ float bf_hi(uint32_t w) { return __uint_as_float(w & 0xffff0000u); }
__device__ __forceinline__ float rbf(float x) { return bf_lo(pack_bf16(x, 0.f)); }
__device__ __forceinline__ uint32_t badd2(uint32_t a, uint32_t b) { uint32_t r; asm("add.rn.bf16x2 %0, %1, %2;" : "=r"(r) : "r"(a), "r"(b)); return r; }
__device__ __forceinline__ uint32_t bsub2(uint32_t a, uint32_t b) { uint32_t r; asm("sub.rn.bf16x2 %0, %1, %2;" : "=r"(r) : "r"(a), "r"(b)); return r; }
__device__ __forceinline__ uint32_t gmix(uint32_t ng, float ny0, float ny1, uint32_t u) {
    uint32_t r; asm("{ .reg .b32 t; fma.rn.bf16x2 t, %1, %3, %3; fma.rn.bf16x2 %0, %1, %2, t; }" : "=r"(r) : "r"(ng), "r"(pack_bf16(ny0, ny1)), "r"(u)); return r;
}
__device__ __forceinline__ void mma_bf(float (&c)[4], uint32_t a0, uint32_t a1, uint32_t a2, uint32_t a3, uint32_t b0, uint32_t b1) {
    asm("mma.sync.aligned.m16n8k16.row.col.f32.bf16.bf16.f32 {%0,%1,%2,%3}, {%4,%5,%6,%7}, {%8,%9}, {%0,%1,%2,%3};"
        : "+f"(c[0]), "+f"(c[1]), "+f"(c[2]), "+f"(c[3]) : "r"(a0), "r"(a1), "r"(a2), "r"(a3), "r"(b0), "r"(b1));
}
__device__ __forceinline__ void mma_bf8(float (&c)[4], uint32_t a0, uint32_t a1, uint32_t b0) {
    asm("mma.sync.aligned.m16n8k8.row.col.f32.bf16.bf16.f32 {%0,%1,%2,%3}, {%4,%5}, {%6}, {%0,%1,%2,%3};"
        : "+f"(c[0]), "+f"(c[1]), "+f"(c[2]), "+f"(c[3]) : "r"(a0), "r"(a1), "r"(b0));
}
__device__ __forceinline__ void mma_h(float (&c)[4], uint32_t a0, uint32_t a1, uint32_t a2, uint32_t a3, uint32_t b0, uint32_t b1) {
    asm("mma.sync.aligned.m16n8k16.row.col.f32.f16.f16.f32 {%0,%1,%2,%3}, {%4,%5,%6,%7}, {%8,%9}, {%0,%1,%2,%3};"
        : "+f"(c[0]), "+f"(c[1]), "+f"(c[2]), "+f"(c[3]) : "r"(a0), "r"(a1), "r"(a2), "r"(a3), "r"(b0), "r"(b1));
}
__device__ __forceinline__ uint32_t fresh(uint32_t a) { asm volatile("" : "+r"(a) :: "memory"); return a; }
__device__ __forceinline__ uint32_t lds32(uint32_t a) { uint32_t v; asm("ld.shared.u32 %0, [%1];" : "=r"(v) : "r"(a)); return v; }
__device__ __forceinline__ uint2 lds64(uint32_t a) { uint2 v; asm("ld.shared.v2.u32 {%0,%1}, [%2];" : "=r"(v.x), "=r"(v.y) : "r"(a)); return v; }
__device__ __forceinline__ uint4 lds128(uint32_t a) { uint4 v; asm("ld.shared.v4.u32 {%0,%1,%2,%3}, [%4];" : "=r"(v.x), "=r"(v.y), "=r"(v.z), "=r"(v.w) : "r"(a)); return v; }
__device__ __forceinline__ void ldsm4(uint32_t (&r)[4], uint32_t a) {
    asm("ldmatrix.sync.aligned.m8n8.x4.shared.b16 {%0,%1,%2,%3}, [%4];" : "=r"(r[0]), "=r"(r[1]), "=r"(r[2]), "=r"(r[3]) : "r"(a));
}
__device__ __forceinline__ void ldsm4t(uint32_t (&r)[4], uint32_t a) {
    asm("ldmatrix.sync.aligned.m8n8.x4.trans.shared.b16 {%0,%1,%2,%3}, [%4];" : "=r"(r[0]), "=r"(r[1]), "=r"(r[2]), "=r"(r[3]) : "r"(a));
}
__device__ __forceinline__ void sts16(uint32_t a, uint32_t v) { asm volatile("st.shared.u16 [%0], %1;" :: "r"(a), "h"((unsigned short)v) : "memory"); }
__device__ __forceinline__ void sts32(uint32_t a, uint32_t v) { asm volatile("st.shared.u32 [%0], %1;" :: "r"(a), "r"(v) : "memory"); }
__device__ __forceinline__ void sts64(uint32_t a, uint32_t x, uint32_t y) { asm volatile("st.shared.v2.u32 [%0], {%1,%2};" :: "r"(a), "r"(x), "r"(y) : "memory"); }
__device__ __forceinline__ void sts128(uint32_t a, uint32_t x, uint32_t y, uint32_t z, uint32_t w) {
    asm volatile("st.shared.v4.u32 [%0], {%1,%2,%3,%4};" :: "r"(a), "r"(x), "r"(y), "r"(z), "r"(w) : "memory");
}
__device__ __forceinline__ void st_async128(uint32_t a, uint32_t x, uint32_t y, uint32_t z, uint32_t w, uint32_t bar) {
    asm volatile("st.async.weak.shared::cluster.mbarrier::complete_tx::bytes.v4.b32 [%0], {%1,%2,%3,%4}, [%5];" :: "r"(a), "r"(x), "r"(y), "r"(z), "r"(w), "r"(bar) : "memory");
}
__device__ __forceinline__ void mbar_init(uint32_t b, uint32_t cnt) { asm volatile("mbarrier.init.shared::cta.b64 [%0], %1;" :: "r"(b), "r"(cnt) : "memory"); }
__device__ __forceinline__ void mbar_fence() { asm volatile("fence.mbarrier_init.release.cluster;" ::: "memory"); }
__device__ __forceinline__ void mbar_expect(uint32_t b, uint32_t bytes) { asm volatile("mbarrier.arrive.expect_tx.shared::cta.b64 _, [%0], %1;" :: "r"(b), "r"(bytes) : "memory"); }
__device__ __forceinline__ void mbar_arrive(uint32_t b) { asm volatile("mbarrier.arrive.shared::cta.b64 _, [%0];" :: "r"(b) : "memory"); }
__device__ __forceinline__ void mbar_wait(uint32_t b, uint32_t parity = 0) {
    asm volatile("{ .reg .pred p; .reg .u32 n; mov.u32 n, 0;\n"
                 "LW: mbarrier.try_wait.parity.shared::cta.b64 p, [%0], %1; @p bra LD; add.u32 n, n, 1; setp.lt.u32 p, n, 65536; @p bra LW; trap;\n"
                 "LD: }" :: "r"(b), "r"(parity) : "memory");
}
__device__ __forceinline__ void mbar_wait_cluster(uint32_t b) {
    asm volatile("{ .reg .pred p; .reg .u32 n; mov.u32 n, 0;\n"
                 "LW: mbarrier.try_wait.parity.acquire.cluster.shared::cta.b64 p, [%0], 0; @p bra LD; add.u32 n, n, 1; setp.lt.u32 p, n, 65536; @p bra LW; trap;\n"
                 "LD: }" :: "r"(b) : "memory");
}
__device__ __forceinline__ void tma2d(uint32_t dst, const CUtensorMap* m, int c0, int c1, uint32_t bar) {
    asm volatile("cp.async.bulk.tensor.2d.shared::cluster.global.mbarrier::complete_tx::bytes [%0], [%1, {%3, %4}], [%2];"
                 :: "r"(dst), "l"(m), "r"(bar), "r"(c0), "r"(c1) : "memory");
}
__device__ __forceinline__ void tma3d(uint32_t dst, const CUtensorMap* m, int c0, int c1, int c2, uint32_t bar) {
    asm volatile("cp.async.bulk.tensor.3d.shared::cluster.global.mbarrier::complete_tx::bytes [%0], [%1, {%3, %4, %5}], [%2];"
                 :: "r"(dst), "l"(m), "r"(bar), "r"(c0), "r"(c1), "r"(c2) : "memory");
}
__device__ __forceinline__ void tma4d(uint32_t dst, const CUtensorMap* m, int c0, int c1, int c2, int c3, uint32_t bar) {
    asm volatile("cp.async.bulk.tensor.4d.shared::cluster.global.mbarrier::complete_tx::bytes [%0], [%1, {%3, %4, %5, %6}], [%2];"
                 :: "r"(dst), "l"(m), "r"(bar), "r"(c0), "r"(c1), "r"(c2), "r"(c3) : "memory");
}
__device__ __forceinline__ void bulk_g2s(uint32_t dst, const void* src, uint32_t bytes, uint32_t bar) {
    asm volatile("cp.async.bulk.shared::cluster.global.mbarrier::complete_tx::bytes [%0], [%1], %2, [%3];"
                 :: "r"(dst), "l"(src), "r"(bytes), "r"(bar) : "memory");
}
__device__ __forceinline__ uint32_t mapa(uint32_t a, uint32_t rank) { uint32_t r; asm("mapa.shared::cluster.u32 %0, %1, %2;" : "=r"(r) : "r"(a), "r"(rank)); return r; }
__device__ __forceinline__ void prefetch_map(const CUtensorMap* m) { asm volatile("prefetch.tensormap [%0];" :: "l"(m) : "memory"); }
__device__ __forceinline__ void bar_sync(int id, int n) { asm volatile("bar.sync %0, %1;" :: "r"(id), "r"(n) : "memory"); }
__device__ __forceinline__ void bar_arrive(int id, int n) { asm volatile("bar.arrive %0, %1;" :: "r"(id), "r"(n) : "memory"); }
__device__ __forceinline__ uint32_t ldg16_if(bool c, const void* p) { uint32_t v; asm volatile("{ .reg .pred p; setp.ne.u32 p, %2, 0; @p ld.global.nc.u16 %0, [%1]; }" : "=r"(v) : "l"(p), "r"((uint32_t)c)); return v; }
__device__ __forceinline__ uint32_t ldg32_if(bool c, const void* p) { uint32_t v; asm volatile("{ .reg .pred p; setp.ne.u32 p, %2, 0; @p ld.global.nc.u32 %0, [%1]; }" : "=r"(v) : "l"(p), "r"((uint32_t)c)); return v; }
__device__ __forceinline__ uint32_t ld_rlx32(const void* p) { uint32_t v; asm volatile("ld.relaxed.gpu.global.u32 %0, [%1];" : "=r"(v) : "l"(p) : "memory"); return v; }
__device__ __forceinline__ uint4 ld_rlx128(const void* p) {
    uint4 v; asm volatile("ld.relaxed.gpu.global.v4.u32 {%0,%1,%2,%3}, [%4];" : "=r"(v.x), "=r"(v.y), "=r"(v.z), "=r"(v.w) : "l"(p) : "memory"); return v;
}
__device__ __forceinline__ void st_rlx32(void* p, uint32_t v) { asm volatile("st.relaxed.gpu.global.u32 [%0], %1;" :: "l"(p), "r"(v) : "memory"); }
__device__ __forceinline__ void stg128(void* p, uint32_t x, uint32_t y, uint32_t z, uint32_t w) {
    asm volatile("st.global.v4.u32 [%0], {%1,%2,%3,%4};" :: "l"(p), "r"(x), "r"(y), "r"(z), "r"(w) : "memory");
}
__device__ __forceinline__ void next_epoch(const Params& p, unsigned e) { if ((threadIdx.x & 31) == 0) p.s->epoch[blockIdx.x * 16 + (threadIdx.x >> 5)] = e + 1; }
__device__ __forceinline__ void sts128z_if(bool c, uint32_t a) { asm volatile("{ .reg .pred p; setp.ne.u32 p, %1, 0; @p st.shared.v4.u32 [%0], {%2,%2,%2,%2}; }" :: "r"(a), "r"((uint32_t)c), "r"(0) : "memory"); }
__device__ __forceinline__ void stg128z_if(bool c, void* a) { asm volatile("{ .reg .pred p; setp.ne.u32 p, %1, 0; @p st.global.v4.u32 [%0], {%2,%2,%2,%2}; }" :: "l"(a), "r"((uint32_t)c), "r"(0) : "memory"); }
__device__ __forceinline__ unsigned clock32() { unsigned c; asm volatile("mov.u32 %0, %clock;" : "=r"(c) :: "memory"); return c; }
__device__ __forceinline__ void until(unsigned t0, int c) { while ((int)(clock32() - t0) < c) { } }
__device__ __forceinline__ float sigmoidf_(float x) { return __fdividef(1.0f, 1.0f + __expf(-x)); }
__device__ __forceinline__ uint32_t key_tag(unsigned epoch) { return ((epoch & 15u) | 16u) << 11; }
__device__ __forceinline__ int key_row(uint32_t key) { return 2047 - (int)(key & 2047u); }
__device__ __forceinline__ uint32_t wait_sel(const Params& p, int s32, int r8, uint32_t tag, uint32_t k = 0) {
#pragma unroll 1
    for (int it = 0; !__all_sync(0xffffffffu, (k & 0xf800u) == tag); it++) {
        k = ld_rlx32(&p.s->sel[s32 * 64 + r8]);
        if (it > (1 << 20)) give_up();
    }
    return k;
}

struct cplx { float re, im; };
__device__ __forceinline__ cplx csq(cplx a) { cplx r; r.re = a.re * a.re - a.im * a.im; r.im = (a.re * a.im) * 2.f; return r; }
__device__ __forceinline__ cplx cexpk(float ar, float ai, float k) {
    float mag, s, c;
    asm("ex2.approx.ftz.f32 %0, %1;" : "=f"(mag) : "f"(ar * (k * 1.4426950408889634f)));
    const float r = ai * k;
    asm("sin.approx.ftz.f32 %0, %1;" : "=f"(s) : "f"(r));
    asm("cos.approx.ftz.f32 %0, %1;" : "=f"(c) : "f"(r));
    cplx o; o.re = mag * c; o.im = mag * s; return o;
}
struct h2c { uint32_t re, im; };
__device__ __forceinline__ h2c cmul_cd(h2c v, __half2 c, __half2 d) {
    const __half2 r = *(const __half2*)&v.re, i = *(const __half2*)&v.im;
    const __half2 x = __hfma2(__hneg2(i), d, __hmul2(r, c)), y = __hfma2(i, c, __hmul2(r, d));
    h2c o; o.re = *(const uint32_t*)&x; o.im = *(const uint32_t*)&y; return o;
}
__device__ __forceinline__ h2c cmul_s(h2c v, uint32_t s) { const __half2 h = *(const __half2*)&s; return cmul_cd(v, __low2half2(h), __high2half2(h)); }
__device__ __forceinline__ h2c cmul_sc(h2c v, uint32_t s) {
    const __half2 h = *(const __half2*)&s, c = __low2half2(h), d = __high2half2(h), r = *(const __half2*)&v.re, i = *(const __half2*)&v.im;
    const __half2 x = __hfma2(i, d, __hmul2(r, c)), y = __hfma2(__hneg2(r), d, __hmul2(i, c));
    h2c o; o.re = *(const uint32_t*)&x; o.im = *(const uint32_t*)&y; return o;
}
__device__ __forceinline__ h2c cmul_vc(h2c v, uint32_t s) {
    const __half2 h = *(const __half2*)&s, c = __low2half2(h), d = __high2half2(h), r = *(const __half2*)&v.re, i = *(const __half2*)&v.im;
    const __half2 x = __hfma2(i, d, __hmul2(r, c)), y = __hfma2(__hneg2(i), c, __hmul2(r, d));
    h2c o; o.re = *(const uint32_t*)&x; o.im = *(const uint32_t*)&y; return o;
}

constexpr int UT_HALF = 2560, UT_STRIDE = 4736, GT_HALF = 2240;
__device__ __forceinline__ uint32_t swz(uint32_t x, int c) { return x ^ (((x >> 2) & 64) ^ (64 * (c & 1) + 8 * (c & 6))); }
__device__ __forceinline__ int col(int n) { return (n >> 1) + 4 * (n & 1); }
constexpr int KT_T = 542, KT_C = 552, KT_D = 645, KT_BYTES = 720 * 4;
constexpr int VC_OFF = 80, VE_BASE = 1616;
constexpr int V_STRIDE = (1616 + 1024) * 4 + 80;
constexpr int KG_STAGE = 5248;
constexpr int Y_CS = 2080, Y_RS = 8 * Y_CS + 64;

constexpr int SC_RT = 0;
constexpr int SC_UT = 33408;
constexpr int SC_KG = SC_UT + 8 * UT_STRIDE;
constexpr int SC_KT = SC_KG + 8 * KG_STAGE;
constexpr int SC_GT = SC_KT + 8 * KT_BYTES;
constexpr int SC_V = SC_GT + 4448;
constexpr int SC_MISC = SC_V + 8 * V_STRIDE;
static_assert(V_STRIDE % 128 == 16 && 2 * Y_RS <= SC_UT && SC_UT % 128 == 0 && SC_KG % 128 == 0, "layout");
static_assert(SC_MISC % 16 == 0 && SC_MISC + 512 <= 232192, "layout");

__device__ __forceinline__ void window_task(uint32_t s0, uint32_t s1, uint32_t d0, uint32_t d1, int k) {
    float S[51], s = 0.f;
    uint32_t w[28];
#pragma unroll
    for (int i = 0; i < 7; i++) {
        const uint4 v = lds128(((i < 3 ? s0 : s1) ^ 8 * ((i + 1) & 2)) + ((i & 1) ? 0 : UT_HALF));
        w[4 * i] = v.x; w[4 * i + 1] = v.y; w[4 * i + 2] = v.z; w[4 * i + 3] = v.w;
    }
    auto sums = [&](int lo, int hi) {
#pragma unroll
        for (int i = lo; i < hi; i++) { const float x = (i & 1) ? bf_hi(w[i >> 1]) : bf_lo(w[i >> 1]); s = i > 3 ? s + x : x; S[i] = s; }
    };
    auto put = [&](int off, int b, int o0, int o1, int o2) {
        auto v = [&](int i) { i += 16 * b; return pack_bf16(S[o0 + i] - S[o1 + i], S[o1 + i] - S[o2 + i]); };
#pragma unroll
        for (int i = 0; i < 8; i += 2) sts128((i & 4 ? d1 : d0) + 4 * off + 64 * b + 8 * (i & 2), v(i), v(i + 8), v(i + 1), v(i + 9));
    };
    S[2] = 0.f;
    sums(3, 26); put(VC_OFF - 16, 0, 10, 5, 2);
    if (k == 12) return;
    sums(26, 42); put(VC_OFF - 16, 1, 10, 5, 2);
    if (k < 8) { put(VE_BASE, 0, 19, 12, 3); sums(42, 51); put(VE_BASE, 1, 19, 12, 3); }
}

template <class F>
__device__ __forceinline__ void kgen(const uint32_t (&q)[8], uint32_t sb, int half, uint32_t stage, uint32_t pstage, int barid, int lane, uint32_t (&w)[12], F shadow) {
    const int t = lane & 3, mi = lane >> 3, r8 = lane & 7;
    {
        const uint32_t pAr = q[0], pAi = q[1], pBr = q[2], pBi = q[3], pCr = q[4], pCi = q[5], pDt = q[6], pD = q[7];
        const uint32_t wb = fresh(stage + lane * 16), za = fresh(stage + 5120 + ((lane >> 1) & 3) * 16 + mi * 4 + (lane & 1) * 2), zr = fresh(stage + 5120 + t * 16);
        const uint32_t oA = fresh(stage + (mi & 1) * 1024 + (mi >> 1) * 512 + r8 * 16), oB = fresh(stage + 2048 + mi * 512 + r8 * 16), oC = fresh(stage + 4096 + (mi & 1) * 512 + (mi >> 1) * 128 + r8 * 16);
        float acc[6][4];
#pragma unroll
        for (int a = 0; a < 6; a++) { acc[a][0] = acc[a][1] = acc[a][2] = acc[a][3] = 0.f; asm volatile("" : "+f"(acc[a][0]), "+f"(acc[a][1]), "+f"(acc[a][2]), "+f"(acc[a][3])); }
        shadow();
        sts32(zr, clock32());
        const float dt = rbf(__expf(bf_lo(pDt)));
        float ar = dt * bf_lo(pAr), ai = dt * bf_lo(pAi), ar1 = dt * bf_hi(pAr), ai1 = dt * bf_hi(pAi);
        float wr, wi, wr1, wi1;
        { const float br = dt * bf_lo(pBr), bi = dt * bf_lo(pBi), cr = bf_lo(pCr), ci = bf_lo(pCi); wr = cr * br - ci * bi; wi = cr * bi + ci * br; }
        { const float br = dt * bf_hi(pBr), bi = dt * bf_hi(pBi), cr = bf_hi(pCr), ci = bf_hi(pCi); wr1 = cr * br - ci * bi; wi1 = cr * bi + ci * br; }
        const uint32_t ex = max(__reduce_max_sync(0xffffffffu, __float_as_uint(fmaxf(fmaxf(fabsf(wr), fabsf(wi)), fmaxf(fabsf(wr1), fabsf(wi1))))) >> 23, 14u);
        const float scl = __uint_as_float((267u - ex) << 23);
        uint32_t W = pack_f16(wr * scl, wi * -scl);
        const uint32_t W1 = pack_f16(wr1 * scl, wi1 * -scl);
        if (threadIdx.x < 32) TSTAMP(20);

#pragma unroll 1
        for (int r = 0; r < 2; r++) {
            const cplx z1 = cexpk(ar, ai, 1.f), z64 = cexpk(ar, ai, 64.f);
            const cplx z2 = csq(z1), z4 = csq(z2), z8 = csq(z4), z16 = csq(z8), z32 = csq(z16);
            const cplx z128 = csq(z64), z256 = csq(z128), z512 = csq(z256);
            auto put = [&](int grp, h2c a, h2c b, h2c c, h2c d) { sts128(wb + grp * 1024, a.re, b.re, c.re, d.re); sts128(wb + grp * 1024 + 512, a.im, b.im, c.im, d.im); };
            {
                const uint32_t s4 = pack_f16(z4.re, z4.im), s256 = pack_f16(z256.re, z256.im), s512 = pack_f16(z512.re, z512.im);
                auto mix = [](h2c a, h2c b, uint32_t sel) { return h2c{__byte_perm(a.re, b.re, sel), __byte_perm(a.im, b.im, sel)}; };
                const h2c c10 = cmul_vc(h2c{pack_f16(z1.re, 1.f), pack_f16(z1.im, 0.f)}, W), c32 = cmul_sc(c10, pack_f16(z2.re, z2.im)), c54 = cmul_sc(c10, s4);
                put(2, c10, c32, c54, cmul_sc(c32, s4));
                const h2c d20 = cmul_sc(mix(c32, c10, 0x7632), s256), e04 = cmul_sc(mix(c10, c54, 0x7632), s512), f04 = cmul_sc(e04, s256);
                put(3, d20, cmul_sc(d20, s4), e04, f04);
                const h2c ef = mix(e04, f04, 0x5410), gh = cmul_sc(ef, s512), g8 = cmul_sc(gh, pack_f16(z8.re, z8.im));
                put(4, g8, cmul_sc(g8, s512), gh, ef);
            }
            {
                const uint32_t s32 = pack_f16(z32.re, z32.im), s64 = pack_f16(z64.re, z64.im), s128 = pack_f16(z128.re, z128.im);
                const h2c p0 = {pack_f16(1.f, z8.re), pack_f16(0.f, z8.im)}, p1 = cmul_s(p0, pack_f16(z16.re, z16.im)), p2 = cmul_s(p0, s32), p3 = cmul_s(p1, s32);
                put(0, p0, p1, p2, p3);
                put(1, cmul_s(p0, s64), cmul_s(p1, s64), cmul_s(p2, s64), cmul_s(p3, s64));
                sts16(za, s128); sts16(za + 64, s128 >> 16);
            }
            __syncwarp();
            {
                const uint32_t aA = fresh(oA), aB = fresh(oB), aC = fresh(oC), aZ = fresh(zr);
                const uint4 zc = lds128(aZ), zd = lds128(aZ + 64);
                const uint32_t zcs[4] = {zc.x, zc.y, zc.z, zc.w}, zds[4] = {zd.x, zd.y, zd.z, zd.w};
                uint32_t c[4];
#pragma unroll
                for (int k = 0; k < 4; k++) {
                    uint32_t a[4], b[4];
                    ldsm4t(a, aA + 128 * k); ldsm4t(b, aB + 128 * k);
                    if (!(k & 1)) ldsm4t(c, aC + 128 * k);
                    const h2c x = cmul_cd(h2c{a[0], a[2]}, *(const __half2*)&zcs[k], *(const __half2*)&zds[k]), y = cmul_cd(h2c{a[1], a[3]}, *(const __half2*)&zcs[k], *(const __half2*)&zds[k]);
                    mma_h(acc[0], a[0], a[1], a[2], a[3], b[0], b[1]);
                    mma_h(acc[1], a[0], a[1], a[2], a[3], b[2], b[3]);
                    mma_h(acc[2], a[0], a[1], a[2], a[3], c[2 * (k & 1)], c[2 * (k & 1) + 1]);
                    mma_h(acc[3], x.re, y.re, x.im, y.im, b[0], b[1]);
                    mma_h(acc[4], x.re, y.re, x.im, y.im, b[2], b[3]);
                    mma_h(acc[5], x.re, y.re, x.im, y.im, c[2 * (k & 1)], c[2 * (k & 1) + 1]);
                }
                asm volatile("" :: "f"(acc[0][0]), "f"(acc[1][0]), "f"(acc[2][0]), "f"(acc[3][0]), "f"(acc[4][0]), "f"(acc[5][0]) : "memory");
            }
            __syncwarp();
            ar = ar1; ai = ai1; W = W1;
        }
        if (threadIdx.x < 32) TSTAMP(21);
        const float i0 = __uint_as_float((ex + 243u) << 23);
        if (half) {
#pragma unroll
            for (int a = 0; a < 6; a++) { acc[a][0] *= i0; acc[a][1] *= i0; acc[a][2] *= i0; acc[a][3] *= i0; }
            if (lane == 0) acc[0][1] -= bf_lo(pD);
#pragma unroll
            for (int a = 0; a < 6; a++) sts128(wb + a * 512, __float_as_uint(acc[a][0]), __float_as_uint(acc[a][1]), __float_as_uint(acc[a][2]), __float_as_uint(acc[a][3]));
            bar_arrive(barid, 64);
        } else {
            if (blockIdx.x < NCONV) bar_arrive(barid + 8, 64);
            bar_sync(barid, 64);
            const uint32_t src = fresh(pstage);
#pragma unroll
            for (int a = 0; a < 6; a++) {
                const uint4 y = lds128(src + lane * 16 + a * 512);
                auto sum = [&](uint32_t x, float c) { return fmaf(c, i0, __uint_as_float(x)); };
                w[4 * (a % 3) + 2 * (a / 3)] = pack_bf16(sum(y.x, acc[a][0]), sum(y.y, acc[a][1]));
                w[4 * (a % 3) + 2 * (a / 3) + 1] = pack_bf16(sum(y.z, acc[a][2]), sum(y.w, acc[a][3]));
            }
            const uint32_t x0 = __shfl_up_sync(0xffffffffu, w[10], 2), x1 = __shfl_up_sync(0xffffffffu, w[11], 2);
            w[10] = w[8];
            if (t >= 2) { w[8] = x0; w[9] = x1; }
        }
    }
}

enum { BC_AUX = 0, BC_U = 5  , BC_Y = 13   };

__device__ __forceinline__ void fetch_gates(const Params& p, int i, int lane, unsigned epoch, uint32_t dst) {
    const uint32_t par = (epoch & 1) ? 0x80008000u : 0u;
    uint4 v;
#pragma unroll 1
    for (int it = 0;; it++) {
        v = ld_rlx128(p.s->gate + 256 * i + 8 * lane);
        v.x ^= par; v.y ^= par; v.z ^= par; v.w ^= par;
        if (__all_sync(0xffffffffu, (v.x & v.y & v.z & v.w & 0x80008000u) == 0x80008000u)) break;
        if (it > (1 << 20)) give_up();
    }
    sts128(dst, v.x, v.y, v.z, v.w);
}
__device__ __forceinline__ void store_rows(const CUtensorMap* m, uint32_t src, int col, int row) {
    asm volatile("cp.async.bulk.tensor.5d.global.shared::cta.bulk_group [%0, {%2, %3, %3, %3, %4}], [%1];" :: "l"(m), "r"(src), "r"(col), "r"(0), "r"(row) : "memory");
}

__device__ __forceinline__ void store_or_add(void* o, const uint32_t (&y)[4], uint32_t add) {
    asm volatile("{ .reg .pred p; setp.ne.u32 p, %5, 0; @!p st.global.v4.u32 [%0], {%1,%2,%3,%4}; @p red.relaxed.gpu.global.add.noftz.v4.bf16x2 [%0], {%1,%2,%3,%4}; }"
                 :: "l"(o), "r"(y[0]), "r"(y[1]), "r"(y[2]), "r"(y[3]), "r"(add) : "memory");
}

__device__ __forceinline__ void conv_aux(const Params& p, const CUtensorMap* mU, uint32_t sb, int aw, int lane, int bid, unsigned epoch) {
    const int g = lane >> 2, t = lane & 3, mi = lane >> 3, r8 = lane & 7;
    const int rank = bid & 1, slab = bid >> 1;
    const uint32_t bar_y = sb + SC_MISC, bar_u = bar_y  , bar_v = bar_y + 8, bar_box = bar_y + 64 + 8 * aw, s_bm = bar_y + 128;
    if (elect()) {
        mbar_init(bar_box, 1); mbar_fence();
        mbar_expect(bar_box, 4096);
        tma4d(sb + SC_RT + 4096 * aw, mU, 16 * slab, 0, 0, 16 * rank + 2 * aw, bar_box);
        mbar_init(bar_y + 8 * aw, aw == 1 ? 8 : 1);
        if (aw == 1) mbar_init(bar_y + 384, 1);
        mbar_fence();
        if (aw != 1) mbar_expect(bar_y + 8 * aw, aw ? 4096 : 16384);
    }
    __syncwarp();
    asm volatile("barrier.cluster.arrive.relaxed.aligned;" ::: "memory");
    asm volatile("setmaxnreg.dec.sync.aligned.u32 88;");
    sts128(sb + (lane < 16 ? SC_UT + aw * UT_STRIDE + mi * (UT_HALF - 128) : SC_V - 256 + aw * V_STRIDE) + lane * 16, 0, 0, 0, 0);
    if (lane < 16) sts128(s_bm + lane * 16, 0, 0, 0, 0);
    {
        const uint32_t dst = sb + SC_UT + g * UT_STRIDE + swz((8 + 64 * rank + 8 * aw + t) * 16, g);
        const uint32_t rdst = mapa(dst, rank ^ 1), rbar = mapa(bar_u, rank ^ 1);
        asm volatile("barrier.cluster.wait.acquire.aligned;" ::: "memory");
        mbar_wait(bar_box);
        if (aw == 0) TSTAMP(1);
        const uint32_t src = fresh(sb + SC_RT) + aw * 4096 + (8 * mi + 4 * (r8 & 1) + (r8 >> 1)) * 32 + ((rank ^ (r8 & 1)) << 4);
        uint32_t x[8][4];
#pragma unroll
        for (int i = 0; i < 4; i++) { ldsm4t(x[i], src + 1024 * i); ldsm4t(x[4 + i], (src ^ 16) + 1024 * i); }
        asm volatile("" :: "r"(x[0][0]), "r"(x[1][0]), "r"(x[2][0]), "r"(x[3][0]) : "memory");
#pragma unroll
        for (int i = 0; i < 4; i++) st_async128((rdst ^ 32 * (i & 2)) + (i & 1) * UT_HALF, x[4 + i][0], x[4 + i][1], x[4 + i][2], x[4 + i][3], rbar);
#pragma unroll
        for (int i = 0; i < 4; i++) sts128((dst ^ 32 * (i & 2)) + (i & 1) * UT_HALF, x[i][0], x[i][1], x[i][2], x[i][3]);
    }
    bar_sync(BC_AUX, 256);
    mbar_wait_cluster(bar_u);
    if (aw == 0) TSTAMP(2);
    if (aw == 6 && elect()) mbar_arrive(bar_y + 384);
    bar_sync(BC_U + aw, 64);
    if (aw == 0) TSTAMP(3);
    {
        const uint32_t ws = fresh(sb + SC_UT) + r8 * UT_STRIDE, wd = sb + SC_V + r8 * V_STRIDE;
#pragma unroll 1
        for (int k = aw; k < 13; k += 8) {
            const int a = 8 * k + (k < 12 ? g & 6 : 0);
            const uint32_t d = wd + 64 * a, sw = 16 * (a & 2);
            window_task(ws + swz(16 * a + 96, r8), ws + swz(16 * a + 128, r8), d + sw, d + (sw ^ 32), k);
        }
    }
    if (aw == 0) TSTAMP(9);
    {
        if (aw >= 2) fetch_gates(p, aw, lane, epoch, sb + SC_GT + (lane & 1) * GT_HALF + (8 + 16 * aw + (lane >> 1)) * 16);
        __syncwarp();
        if (elect()) { mbar_arrive(bar_v); prefetch_map(mU + 4); }
        next_epoch(p, epoch);
        if (aw == 0) TSTAMP(4);
        if (aw == 7) {
            const int row = key_row(wait_sel(p, slab >> 1, r8, key_tag(epoch)));
            if (lane < 8) asm volatile("red.shared.or.b32 [%0], %1;" :: "r"(s_bm + (row >> 5) * 4), "r"(1u << (row & 31)) : "memory");
            TSTAMP(10);
        }
        bar_sync(BC_AUX, 256);
        const uint32_t src = sb + SC_RT + ((r8 >> 1) & 1) * Y_RS + (2 * mi + (r8 & 1)) * Y_CS + (2 * aw + (r8 >> 2)) * 16;
        const int rb = 64 * (aw & 4) + 32 * (aw & 1) + ((aw >> 1) & 1) + 2 * rank, row0 = rb + 128 * (g >> 2) + 16 * (t >> 1) + 64 * (g & 1) + 8 * ((g >> 1) & 1);
        __nv_bfloat16* outp = p.out + (size_t)row0 * DM + 16 * slab + 8 * (t & 1);
        const uint32_t stg = sb + SC_KG + 4096 * aw, so = (g & 2) * 256 + (g >> 2) * 128 + r8 * 16;
#pragma unroll 1
        for (int s = 1; s < 4; s++) {
            const uint32_t bm = lds32(fresh(s_bm) + (16 * s + (row0 >> 5)) * 4) >> (row0 & 31);
            const bool routed = __any_sync(0xffffffffu, bm & 0x11u);
            if ((aw & 3) == s) mbar_wait_cluster(bar_y + 16 * s + 2 * (aw & 4));
            bar_sync(BC_Y + (aw >> 2), 128);
            const uint32_t sf = fresh(src) + 512 * s;
            uint32_t y[2][4];
            ldsm4t(y[0], sf); ldsm4t(y[1], sf + 256);
            if (routed) {
#pragma unroll
                for (int k = 0; k < 2; k++) store_or_add(outp + (size_t)(512 * s + 4 * k) * DM, y[k], bm & (1u << (4 * k)));
            } else {
                sts128(stg + so + 1024 * s, y[0][0], y[0][1], y[0][2], y[0][3]); sts128(stg + so + 1024 * s + 256, y[1][0], y[1][1], y[1][2], y[1][3]);
                asm volatile("fence.proxy.async.shared::cta;" ::: "memory");
                __syncwarp();
                if (elect()) store_rows(mU + 4, stg + 1024 * s, 16 * slab, 512 * s + rb);
            }
            if (aw == 4) TSTAMP(16 + s);
            if (aw == 0) TSTAMP(16);
        }
        if (elect()) { asm volatile("cp.async.bulk.commit_group;" ::: "memory"); asm volatile("cp.async.bulk.wait_group.read 0;" ::: "memory"); }
        if (aw == 4) TFLUSH();
    }
}

__device__ __forceinline__ uint32_t k_tag(unsigned epoch) { return epoch << 16 | 0x80000000u; }
__device__ __forceinline__ void publish_k(uint4* kp, const uint32_t (&w)[12], unsigned epoch, uint64_t (&v)[6]) {
#pragma unroll
    for (int i = 0; i < 3; i++) {
        v[2 * i] = w[3 * i] | (uint64_t)w[3 * i + 1] << 32; v[2 * i + 1] = w[3 * i + 2] | (uint64_t)__byte_perm(w[9 + (i >> 1)], k_tag(epoch), i == 1 ? 0x7632 : 0x7610) << 32;
        asm volatile("st.relaxed.gpu.global.v2.u64 [%0], {%1,%2};" :: "l"(kp + 32 * i), "l"(v[2 * i]), "l"(v[2 * i + 1]));
    }
}
template <bool FULL>
__device__ __forceinline__ void k_tables(uint32_t kt, int lane, const uint32_t (&w)[12]) {
    const int g = lane >> 2, t = lane & 3, mi = lane >> 3, r8 = lane & 7;
    uint32_t x3 = w[7], re[4], rx[4];
#pragma unroll
    for (int i = 0; i < 4; i++) {
        re[i] = __shfl_sync(0xffffffffu, w[i], lane + 31);
        rx[i] = __shfl_sync(0xffffffffu, w[4 + i], lane + (i == 0 && lane == 29 ? 5 : 1 + 2 * t));
    }
    if (FULL) {
        asm volatile("stmatrix.sync.aligned.m8n8.x2.trans.shared.b16 [%0], {%1,%2};" :: "r"(kt + (KT_D + 7) * 4 + 64 * t + 16 * (mi & 1) + 8 * (r8 & 4)), "r"(w[8]), "r"(w[9]) : "memory");
        if (lane == 2) {
            sts32(kt + (KT_C + 78) * 4, w[10] & 0xffffu);
            sts128(kt + (KT_T + 2) * 4, 0, w[10] & 0xffffu, __byte_perm(w[10], 0, 0x1010), w[10] << 16);
        }
        if (lane == 29) x3 = bsub2(x3, rx[0] & 0xffffu);
    }
#pragma unroll
    for (int i = 0; i < 4; i++) {
        sts64(kt + (16 + 64 * i) * 4 + 8 * lane, __byte_perm(w[i], lane ? re[i] : i ? re[i - 1] : 0, 0x5432), w[i]);
        const uint32_t x = i < 3 ? w[4 + i] : x3, aa = __byte_perm(x, 0, 0x3232);
        if (t < 2) sts128(kt + (272 + 64 * i + 8 * g + 4 * t) * 4, i == 0 && lane == 0 ? __byte_perm(x, re[3], 0x5432) : aa, aa, x,
                          __byte_perm(lane != 29 ? rx[i] : i < 3 ? rx[(i + 1) & 3] : FULL ? 0 : rx[0] << 16, x, 0x5432));
        else if (FULL) sts32(kt + (KT_C - 50 + 8 * i + 32 * t + g) * 4, x);
    }
}

__device__ __forceinline__ void conv_main(const Params& p, uint32_t sb, int warp, int lane0, int bid, unsigned epoch, uint32_t (&w)[12]) {
    asm volatile("setmaxnreg.inc.sync.aligned.u32 168;");
    const int lane = __shfl_sync(0xffffffffu, lane0, lane0);
    const int g = lane >> 2, t = lane & 3, mi = lane >> 3, r8 = lane & 7;
    const int rank = bid & 1;
    const uint32_t bar_y = sb + SC_MISC, bar_v = bar_y + 8;
    next_epoch(p, epoch);
    asm volatile("barrier.cluster.wait.acquire.aligned;" ::: "memory");
    if (warp < 4) {
        bar_arrive(BC_U + warp, 64);
    } else {
        mbar_wait(bar_y + 384);
        if (KPOLL) until(clock32(), KPOLL);
        const uint4* src = p.s->kp + (8 * bid + warp) * 96 + lane0;
#pragma unroll 1
        for (int it = 0;; it++) {
            uint32_t bad = 0, e[3];
#pragma unroll
            for (int i = 0; i < 3; i++) { const uint4 v = ld_rlx128(src + 32 * i); w[3 * i] = v.x; w[3 * i + 1] = v.y; w[3 * i + 2] = v.z; e[i] = v.w; bad |= v.w ^ k_tag(epoch); }
            w[9] = __byte_perm(e[0], e[1], 0x5410); w[10] = e[2];
            const bool ok = __all_sync(0xffffffffu, bad < 65536);
            if (ok) break;
            if (it > (1 << 20)) give_up();
        }
    }
    if ((warp & 3) == 0) TSTAMP(5 + (warp >> 2));
    k_tables<true>(sb + SC_KT + warp * KT_BYTES, lane0, w);
    mbar_wait(bar_y + 384);
    __syncwarp();
    if ((warp & 3) == 0) TSTAMP(7 + (warp >> 2));
    {
        const uint32_t ut = fresh(sb + SC_UT) + warp * UT_STRIDE, kt = fresh(sb + SC_KT) + warp * KT_BYTES;
        auto dup = [&](uint32_t v) { return v ^ p.zero; };
        auto frag = [&](uint32_t (&a)[4], uint32_t x) { a[0] = lds32(x); a[1] = lds32(x + 32); a[2] = lds32(x - 32); a[3] = dup(a[0]); };
        const uint32_t kb = kt + (16 + g - 2 * t) * 4;
        float acc[16][4];
        {
            float y[12][4], M[6][4];
#pragma unroll
            for (int i = 0; i < 12; i++) { y[i][0] = y[i][1] = y[i][2] = y[i][3] = 0.f; M[i >> 1][0] = M[i >> 1][1] = M[i >> 1][2] = M[i >> 1][3] = 0.f; }
            uint32_t U[10][4], a1[4], ad[4], R = (mi & 1) * UT_HALF + (8 + (r8 >> 1) + 48 * (r8 & 1)) * 16 + 64 * (mi >> 1);
            auto places = [&] { ad[0] = swz(R, warp); ad[1] = swz(R + 128, warp); ad[2] = ad[0] ^ 64; ad[3] = ad[1] ^ 64; };
            auto ldu = [&](int k) { ldsm4(U[k], ut + ad[k & 3] + 256 * (k >> 1)); };
            places();
            frag(a1, kb + 2048);
#pragma unroll
            for (int k = 0; k < 7; k++) ldu(k);
#pragma unroll
            for (int i = 0; i < 12; i++) mma_bf(y[i], a1[0], a1[1], a1[2], a1[3], U[i >> 1][2 * (i & 1)], U[i >> 1][2 * (i & 1) + 1]);
            frag(a1, kb + 1792);
            __syncwarp();
#pragma unroll 1
            for (uint32_t ko = 0; ko != 256;) {
                ko = fresh(ko);
                const uint32_t kp = kb + ko;
                ko += 64;
                uint32_t se[10][2], so[10][2], ue[10][2];
                auto sums = [&](int k) {
#pragma unroll
                    for (int e = 0; e < 2; e++) { ue[k][e] = U[k][e]; se[k][e] = badd2(U[k][e], U[k - 1][2 + e]); so[k][e] = badd2(U[k][e], U[k][2 + e]); }
                };
#pragma unroll
                for (int k = 1; k < 6; k++) sums(k);
#pragma unroll
                for (int m = 3; m >= 0; m--) {
                    uint32_t a0[4];
                    frag(a0, kp + 512 * m);
                    sums(9 - m);
                    if (m) ldu(10 - m); else { R -= 16; places(); }
#pragma unroll
                    for (int i = 0; i < 6; i++) mma_bf(y[2 * i], a1[0], a1[1], a1[2], a1[3], se[i - m + 4][0], se[i - m + 4][1]);
#pragma unroll
                    for (int e = 0; e < 4; e++) a1[e] = bsub2(a0[e], a1[e]);
#pragma unroll
                    for (int i = 0; i < 6; i++) { mma_bf(M[i], a1[0], a1[1], a1[2], a1[3], ue[i - m + 4][0], ue[i - m + 4][1]); if (!m) ldu(i); }
                    frag(a1, m ? kp + 512 * m - 256 : kp + 1792 + 64);
                    if (!m) ldu(6);
#pragma unroll
                    for (int i = 0; i < 6; i++) mma_bf(y[2 * i + 1], a0[0], a0[1], a0[2], a0[3], so[i - m + 4][0], so[i - m + 4][1]);
                }
            }
#pragma unroll
            for (int i = 0; i < 6; i++)
#pragma unroll
                for (int c = 0; c < 4; c++) { acc[4 + i + 6 * (c & 1)][c & 2] = y[2 * i][c] + M[i][c]; acc[4 + i + 6 * (c & 1)][c | 1] = y[2 * i + 1][c] - M[i][c]; }
        }
        const uint32_t lo = (8 + col(r8)) * 16 + (mi >> 1) * 128, ua = fresh(ut) + (mi & 1) * UT_HALF, u1[2] = {ua + swz(lo, warp), ua + (swz(lo, warp) ^ 64)};
        {
            uint32_t e[4];
            frag(e, kb + (KT_T - 16) * 4);
            const uint32_t f0 = dup(e[1]), f1 = lds32(kb + KT_T * 4), uo = fresh(ut) + UT_HALF + swz((7 + 8 * mi + col(r8)) * 16, warp);
#pragma unroll
            for (int i = 0; i < 4; i++) {
                uint32_t b[4];
                if (i < 2) {
                    ldsm4(b, uo + 512 * i);
#pragma unroll
                    for (int k = 0; k < 4; k++) mma_bf8(acc[8 + 4 * i + k], f0, f1, b[k]);
                }
                ldsm4(b, u1[i & 1] + 256 * i);
                mma_bf(acc[2 * i + 8], e[0], e[1], e[2], e[3], b[0], b[1]); mma_bf(acc[2 * i + 9], e[0], e[1], e[2], e[3], b[2], b[3]);
            }
        }
        if ((warp & 3) == 0) TSTAMP(11 + (warp >> 2));
        mbar_wait(bar_v);
        const uint32_t vt = fresh(sb + SC_V) + warp * V_STRIDE;
        const uint32_t g1 = fresh(sb + SC_GT) + (mi & 1) * GT_HALF + lo;
        const uint32_t ydst = mapa(sb + SC_RT + rank * Y_RS + warp * Y_CS + (lane & 23) * 16, mi & 1), ybr = mapa(bar_y, mi & 1);
        uint32_t ug[2][2][4];
        auto ld_ug = [&](int i) { ldsm4t(ug[i & 1][0], u1[i & 1] + 256 * i); ldsm4t(ug[i & 1][1], g1 + 256 * i); };
        auto ship = [&](int i) {
            const uint32_t (&u)[4] = ug[i & 1][0], (&gg)[4] = ug[i & 1][1];
            const uint32_t y0 = gmix(gg[0], acc[2 * i][0], acc[2 * i][1], u[0]), y1 = gmix(gg[1], acc[2 * i][2], acc[2 * i][3], u[1]);
            const uint32_t y2 = gmix(gg[2], acc[2 * i + 1][0], acc[2 * i + 1][1], u[2]), y3 = gmix(gg[3], acc[2 * i + 1][2], acc[2 * i + 1][3], u[3]);
            st_async128(ydst + 512 * (i >> 1) + 128 * (i & 1), y0, y1, y2, y3, ybr + 8 * i);
        };
        const uint32_t VD = vt + (VC_OFF - 400 - 16 * t) * 4 + (8 * g ^ 16 * (-t & 2)), VD2 = vt + (VC_OFF - 415 - 16 * t) * 4 + (8 * g ^ 16 * (~t & 2));
        uint2 bd[10];
        uint32_t x[2][4][4];
        auto ld4 = [&](uint32_t (&v)[4], int dl) { const uint2 w = lds64(VD + 256 * dl); v[0] = w.x; v[1] = w.y; v[2] = lds32(VD2 + 256 * dl); v[3] = dup(w.x); };
        auto mm4 = [&](const uint32_t (&v)[4], int dl) {
#pragma unroll
            for (int s = dl & 1; s < 10; s += 2) if ((dl + s) / 2 >= 4 && (dl + s) / 2 < 16) mma_bf(acc[(dl + s) / 2], v[0], v[1], v[2], v[3], bd[s].x, bd[s].y);
        };
        const uint32_t KE = kt + (KT_D + col(g) + t) * 4, VE = vt + (VE_BASE - 912 - 16 * t) * 4 + (8 * g ^ 16 * (~t & 2));
        uint32_t b0[8], b1[8];
        auto ld8 = [&](uint32_t (&v)[4], int dl) { const uint2 w = lds64(VE + 512 * dl), z = lds64(VE + 512 * dl - 256); v[0] = w.x; v[1] = w.y; v[2] = z.x; v[3] = z.y; };
        auto mm8 = [&](const uint32_t (&v)[4], int dl, int lo, int hi) {
#pragma unroll
            for (int s = 0; s < 8; s++) if (dl + s >= lo && dl + s < hi) mma_bf(acc[dl + s], v[0], v[1], v[2], v[3], b0[s], b1[s]);
        };
        ld4(x[0][0], 6);
#pragma unroll
        for (int s = 0; s < 10; s++) bd[s] = lds64(kt + (KT_C + 2 * col(g) + 2 * t + 8 * s) * 4);
        mm4(x[0][0], 6);
        uint32_t e[8][4];
#pragma unroll
        for (int k = 1; k < 6; k++) {
#pragma unroll
            for (int j = 0; j < 4; j++) ld4(x[k & 1][j], 4 * k + 3 + j);
            ld_ug(k + 1);
            if (k == 3) {
#pragma unroll
                for (int s = 0; s < 8; s++) { b0[s] = lds32(KE + 32 * s); b1[s] = lds32(KE + 32 * s + 16); }
            }
            if (k > 1) ship(k);
#pragma unroll
            for (int j = 0; j < 4; j++) {
                mm4(x[k & 1][j], 4 * k + 3 + j);
                if (k == 3) { ld8(e[j], 8 + j); mm8(e[j], 8 + j, 8, 14); }
                if (k == 5 && j < 2) { ld8(e[4 + j], 12 + j); mm8(e[4 + j], 12 + j, 12, 14); }
            }
        }
        ld_ug(7);
        {
            float (&q0)[4] = acc[0], (&q1)[4] = acc[1];
#pragma unroll
            for (int c = 0; c < 4; c++) q0[c] = q1[c] = 0.f;
            auto m8 = [&](float (&c)[4], int T, int j) { mma_bf(c, e[j][0], e[j][1], e[j][2], e[j][3], b0[T - 8 - j], b1[T - 8 - j]); };
            auto m4 = [&](float (&c)[4], int T, int j) { mma_bf(c, x[0][j][0], x[0][j][1], x[0][j][2], x[0][j][3], bd[2 * T - 27 - j].x, bd[2 * T - 27 - j].y); };
            ship(6);
            ld8(e[6], 14); ld8(e[7], 15);
#pragma unroll
            for (int j = 0; j < 4; j++) ld4(x[0][j], 27 + j);
            m8(q1, 15, 0); m8(q0, 14, 0); m8(q1, 15, 1);
            m8(acc[15], 15, 6); m4(q1, 15, 0); m8(acc[14], 14, 6); m4(q0, 14, 0);
            m8(acc[15], 15, 4); m8(q1, 15, 2); m4(acc[14], 14, 1); m8(q0, 14, 1);
            m4(acc[15], 15, 1); m4(q1, 15, 2); m8(acc[14], 14, 4); m8(q0, 14, 2);
            m8(acc[15], 15, 5); m8(q1, 15, 3); m8(acc[14], 14, 5); m8(q0, 14, 3);
            m4(acc[15], 15, 3); m8(q1, 15, 7);
#pragma unroll
            for (int c = 0; c < 4; c++) { acc[14][c] += q0[c]; acc[15][c] += q1[c]; }
            ship(7);
        }
        if ((warp & 3) == 0) TSTAMP(14 + (warp >> 2)); else TSTAMP(21 + warp);
    }
}

constexpr int SF_WD = 73728;
constexpr int SF_RED = 49152;
constexpr int MU_STRIDE = 1168  , SM_RAW = 98304, SM_UT = SM_RAW + 16384, SM_G = SM_UT + 21504, SM_Y = 196608, SM_FT = SM_Y + 17024, SM_KT = 138880, SM_KW = SM_G - 49152;
constexpr int SF_XS = 221184;
constexpr int SF_MISC = SF_XS + 8 * 1168;
constexpr int SF_KG = SF_MISC - 10 * KG_STAGE;
constexpr int SF_WR = SF_KG - 2304;
constexpr int FB_X = 64, FB_KDONE = 72, FB_KEYS = 80, FB_FREE = 88  , FB_W = 104, FB_D = FB_W + 72, FB_MU = FB_D + 96, FB_FAR = FB_MU - 16, FB_MG = FB_MU + 8, FB_MT = FB_MU + 16  , FS_PART = 512, FS_TOK = 896, FS_BM = 1024;
enum { BAR_R = 7, BAR_GU = 8, BAR_RED = 9, BAR_R2 = 10, BAR_G = 12  , BAR_M = 15 };
static_assert(SF_KG % 128 == 0 && NPRE <= 8 && SM_KT + 4 * 2112 <= 147456 && SM_G + MU_STRIDE <= SF_WR - 4 * 9216 && SM_KW + 6 * 2112 >= SM_RAW && SM_KW + 12 * 2112 <= SM_UT, "layout");

__device__ __forceinline__ constexpr int box_no(int i) { return (0x987610ba5432ull >> (4 * i)) & 15; }
__device__ __forceinline__ int role(int b) { b -= NCONV; return b < NX ? b : 18 + (b >> 1) + 12 * (b & 1); }
__device__ __forceinline__ int mini_ch0(int f) { return 48 * f - (f < NW ? 1696 : 2304); }

__device__ __forceinline__ void ffn_front(const Params& p, const CUtensorMap* maps, uint32_t sb, int warp, int lane, int f, unsigned epoch) {
    const unsigned t0 = clock32();
    const int g = lane >> 2, t = lane & 3, mi = lane >> 3, r8 = lane & 7;
    const bool isx = f < NX;
    const int nrw = f < 52 ? 4 : 6, r0 = f < 52 ? 32 * f : 48 * f - 832;
    const int rw = warp < 12 ? 13 - warp : warp ^ (warp < 14 ? 10 : 15);
    const uint32_t bar_row = sb + SF_MISC  , bar_x = bar_row + FB_X;
    const uint32_t s_part = bar_row + FS_PART  , s_tok = bar_row + FS_TOK  ;
    const uint32_t rows = sb + SF_WR - 9216 * (rw + 1) - (rw & 4) * ((SF_WR - 6 * 9216) / 4);
    {
#pragma unroll 1
        for (int i = warp < 10 ? 30 : warp - 10; i < 30; i += 6) if (elect()) mbar_init(bar_x + 8 * i, i == 1 ? 4 + (f < NW) : i < 27 ? 1 : i == 27 ? 2 : 8);
        const uint32_t bytes = rw < 6 ? 9216 : 1152, dst = rw < 6 ? rows : sb + SF_WR + (rw & 1) * 1152;
        const __nv_bfloat16* src = rw < 6 ? p.u + (size_t)(r0 + 8 * rw) * DM : (rw & 1) ? p.gatew : p.wr;
        if (elect()) { mbar_init(bar_row + 8 * rw, 1); mbar_fence(); mbar_expect(bar_row + 8 * rw, bytes); }
        if (warp == 13) { sts32(s_part + 64 + lane * 4, 0); sts32(bar_row + FS_BM + lane * 4, 0); }
        bar_sync(0, NTHR);
        if (!isx) asm volatile("barrier.cluster.arrive.relaxed.aligned;" ::: "memory");
        if (rw < nrw) until(t0, RDELAY);
        if (rw < nrw || rw >= 6) { if (elect()) bulk_g2s(dst, src, bytes, bar_row + 8 * rw); }
    }
    uint4* const kdst = p.s->keys + (lane >> 1) * 128 + 2 * f + (lane & 1);
    if (warp == 15) TSTAMP(1);

    if (warp == 12) {
        if (lane < 22) mbar_expect(bar_row + FB_W + 8 * lane, lane < 9 ? 24576 : isx ? 12288 : lane < 20 ? 2048 : 16384);
        if (elect()) { prefetch_map(maps + 1); prefetch_map(maps + 2); prefetch_map(maps + (isx ? 3 : 5)); }
        unsigned tb = t0 + WDELAY;
        auto pieces = [&](int n, int end, uint32_t dst) {
#pragma unroll 1
            for (; n < end; n++, dst += 12288) {
                until(tb, 0); tb += WGAP;
                if (elect()) tma3d(dst, maps + 1 + (n & 1), 0, 64 * (n >> 1), 3 * f, bar_row + FB_W + 8 * (n >> 1));
            }
        };
        if (!isx) {
#pragma unroll 1
            for (int k = 0; k <= (f >= NW); k++) { until(t0, MDELAY + k * MGAP); if (elect()) tma4d(sb + SM_RAW - 49152 * k, maps + 5, mini_ch0(f) + 16 * k, 0, 0, 0, bar_row + FB_MU - 8 * k); }
            if (f >= NW) return;
        }
#pragma unroll 1
        for (int i = 0; i < 4; i++) {
            if (i == 1) { mbar_wait(bar_row + FB_KEYS); mbar_wait(bar_row + FB_KDONE); tb = clock32() + RESUME; }
            if (i == 3) mbar_wait(bar_row + FB_FREE);
            const int n = ((0x0c080000 + NPRE * 256) >> (8 * i)) & 255;
            pieces(n, ((0x120c0800 + NPRE) >> (8 * i)) & 255, sb + 12288 * (((0x000c0000 + NPRE * 256) >> (8 * i)) & 255));
        }
        TSTAMP(12);
        if (isx) {
#pragma unroll 1
            for (int i = 0; i < 12; i++) {
                const int n = box_no(i);
                if (i == 6) mbar_wait(bar_row + FB_FREE + 8);
                until(tb, 0); tb += DGAP;
                if (elect()) tma2d(sb + SF_WD + n * 12288, maps + 3, 32 * (f >> 1), 2304 * (f & 1) + 192 * n, bar_row + FB_D + 8 * n);
            }
            TSTAMP(13);
        }
    } else if (warp == 13) {
        const uint32_t tag = key_tag(epoch), par = (epoch & 1) ? 0u : 0x8000u;
        stg128(kdst, 0, 0, 0, 0);
        if (lane < 8 && isx && !(f & 1)) st_rlx32(&p.s->sel[32 * f + lane], 0);
        bar_sync(BAR_R, 32 * (nrw + 1));
        TSTAMP(3);
        {
            const uint32_t sg = fresh(s_part) + 192 + lane * 4;
            const uint32_t gb = pack_bf16(sigmoidf_(rbf(__uint_as_float(lds32(sg)))), sigmoidf_(rbf(__uint_as_float(lds32(sg + 128))))) | par | (par << 16);
            asm volatile("st.relaxed.gpu.global.u16 [%0], %1;" :: "l"(p.s->gate + r0 + lane), "h"((unsigned short)gb) : "memory");
            if (nrw > 4 && lane < 16) asm volatile("st.relaxed.gpu.global.u16 [%0], %1;" :: "l"(p.s->gate + r0 + 32 + lane), "h"((unsigned short)(gb >> 16)) : "memory");
        }
        bar_sync(BAR_R2, 32 * (nrw + 1));
        {
            const uint4 v = lds128(fresh(s_tok) + (lane & 1) * 16);
            asm volatile("st.relaxed.gpu.global.v4.u32 [%0], {%1,%2,%3,%4};" :: "l"(kdst), "r"(v.x | tag), "r"(v.y | tag), "r"(v.z | tag), "r"(v.w | tag) : "memory");
        }
        TSTAMP(4);
        if (lane == 0) { mbar_arrive(bar_row + FB_KEYS); mbar_expect(bar_x, 8 * 1152); }
        if (f >= NW) return;
        mbar_wait(bar_row + FB_KDONE);
        uint32_t k[16];
        const uint4* src = p.s->keys + (f & 15) * 128 + lane;
#pragma unroll 1
        for (int it = 0;; it++) {
            uint32_t bad = 0;
#pragma unroll
            for (int i = 0; i < 4; i++) {
                const uint4 x = ld_rlx128(src + (i < 3 || lane < 24 ? 32 * i : 64));
                k[i] = x.x; k[4 + i] = x.y; k[8 + i] = x.z; k[12 + i] = x.w;
                bad |= x.x ^ tag;
            }
            const bool ok = __all_sync(0xffffffffu, (bad & 0xf800u) == 0);
            if (ok) break;
            if (it > (1 << 20)) give_up();
        }
        TSTAMP(5);
        uint32_t key = 0, m = __reduce_max_sync(0xffffffffu, max(max(k[0], k[1]), max(k[2], k[3])));
#pragma unroll 2
        for (int r = 0; r < 8; r++) {
            bool pop[4];
#pragma unroll
            for (int i = 0; i < 4; i++) { pop[i] = k[i] == m; k[i] = pop[i] ? k[4 + i] : k[i]; }
            const uint32_t mn = __reduce_max_sync(0xffffffffu, max(max(k[0], k[1]), max(k[2], k[3])));
            if (elect()) bulk_g2s(sb + SF_XS + r * 1168, p.u + (size_t)key_row(m) * DM, 1152, bar_x);
#pragma unroll
            for (int i = 0; i < 4; i++) { k[4 + i] = pop[i] ? k[8 + i] : k[4 + i]; k[8 + i] = pop[i] ? k[12 + i] : k[8 + i]; k[12 + i] = pop[i] ? 0 : k[12 + i]; }
            if (r8 == r) key = m;
            m = mn;
        }
        const int row = key_row(key);
        sts32(s_tok + r8 * 8, row);
        TSTAMP(6);
        if (isx) {
            if (!(f & 1)) {
                __nv_bfloat16* o = p.out + (size_t)row * DM + 16 * f + 8 * mi;
                asm volatile("st.relaxed.gpu.global.v4.u32 [%0], {%1,%1,%1,%1};" :: "l"(o), "r"(0) : "memory");
                if (__any_sync(0xffffffffu, ld_rlx32(o) != 0)) give_up();
                if (lane < 8) st_rlx32(&p.s->sel[32 * f + lane], key);
            } else wait_sel(p, f >> 1, r8, tag);
            uint32_t gb;
#pragma unroll 1
            for (int it = 0;; it++) {
                asm volatile("ld.relaxed.gpu.global.u16 %0, [%1];" : "=r"(gb) : "l"(p.s->gate + row) : "memory");
                gb ^= par;
                if (!(gb & 0x8000u)) break;
                if (it > (1 << 20)) give_up();
            }
            const uint32_t rb = key ^ 0x80000000u, rv = (rb ^ (((int)rb >> 31) & 0x7fff0000u)) & 0xffff0000u;
            sts32(s_tok + r8 * 8 + 4, __float_as_uint(rbf(1.0f - bf_lo(gb)) * rbf(sigmoidf_(__uint_as_float(rv)))));
            __syncwarp();
            TSTAMP(7);
            bar_arrive(BAR_RED, 416);
        }
    } else {
        if (rw < nrw) {
            float c[3][4];
#pragma unroll
            for (int i = 0; i < 3; i++) { c[i][0] = c[i][1] = c[i][2] = c[i][3] = 0.f; }
            mbar_wait(bar_row + 48); mbar_wait(bar_row + 56);
            const uint32_t b = fresh(sb + SF_WR) + (g & 1) * 1152 + (g >> 2) * 64 + t * 16 + (g & 2) * 2;
            uint32_t w[18][2];
#pragma unroll
            for (int kb = 0; kb < 18; kb++) { const uint32_t o = ((kb & 1) ? b ^ 64 : b) + 128 * (kb >> 1); w[kb][0] = lds32(o); w[kb][1] = lds32(o + 8); }
            mbar_wait(bar_row + 8 * rw);
            if (warp == 15) TSTAMP(2);
            const uint32_t a = fresh(rows) + g * 1152 + (g & 1) * 64 + t * 16;
#pragma unroll
            for (int kb = 0; kb < 18; kb++) {
                const uint4 x = lds128(((kb & 1) ? a ^ 64 : a) + 128 * (kb >> 1));
                mma_bf(c[kb % 3], x.x, x.y, x.z, x.w, w[kb][0], w[kb][1]);
            }
            const float sr = c[0][0] + c[1][0] + c[2][0] + __shfl_down_sync(0xffffffffu, c[0][2] + c[1][2] + c[2][2], 1);
            const float sg = c[0][1] + c[1][1] + c[2][1] + __shfl_down_sync(0xffffffffu, c[0][3] + c[1][3] + c[2][3], 1);
            const uint32_t rb = pack_bf16(0.f, sr);
            if (t == 2 * (g & 1)) {
                sts32(s_part + (8 * rw + g) * 4, (rb ^ (((int)rb >> 31) & 0x7fff0000u) ^ 0x80000000u) | (uint32_t)(2047 - r0 - 8 * rw - g));
                sts32(s_part + 192 + (8 * rw + g) * 4, __float_as_uint(sg));
            }
            __syncwarp();
            bar_sync(BAR_R, 32 * (nrw + 1));
            const uint32_t sk = fresh(s_part), kk = lds32(sk + (8 * rw + r8) * 4);
            int n = 0;
#pragma unroll
            for (int i = 0; i < 3; i++) { const uint4 v = lds128(sk + mi * 48 + 16 * i); n += (v.x > kk) + (v.y > kk) + (v.z > kk) + (v.w > kk); }
            n += __shfl_xor_sync(0xffffffffu, n, 8); n += __shfl_xor_sync(0xffffffffu, n, 16);
            if (n < 8) sts32(s_tok + 4 * n, kk);
            __syncwarp();
            bar_arrive(BAR_R2, 32 * (nrw + 1));
        }
    }
}

__device__ __forceinline__ void ffn_work(const Params& p, uint32_t sb, int warp, int lane, int f, unsigned epoch) {
    const int g = lane >> 2, t = lane & 3, mi = lane >> 3, r8 = lane & 7;
    const bool isx = f < NX;
    const uint32_t bar_x = sb + SF_MISC + FB_X, bar_free = sb + SF_MISC + FB_FREE, bar_w = sb + SF_MISC + FB_W, bar_d = sb + SF_MISC + FB_D, s_tok = sb + SF_MISC + FS_TOK;
    uint32_t fr[24][4];
    auto pin = [&] {
#pragma unroll
        for (int i = 0; i < 24; i += 8) asm volatile("" :: "r"(fr[i][0]), "r"(fr[i + 1][0]), "r"(fr[i + 2][0]), "r"(fr[i + 3][0]), "r"(fr[i + 4][0]), "r"(fr[i + 5][0]), "r"(fr[i + 6][0]), "r"(fr[i + 7][0]) : "memory");
    };
    {
        const int j = (unsigned)(warp - 4) < 6, w = warp - (j ? 4 : warp < 4 ? 0 : 6);
        float ag[2][4], au[2][4];
#pragma unroll
        for (int i = 0; i < 2; i++) { ag[i][0] = ag[i][1] = ag[i][2] = ag[i][3] = 0.f; au[i][0] = au[i][1] = au[i][2] = au[i][3] = 0.f; }
        const uint32_t wb = sb + (w >> 1) * 4096 + (r8 + 8 * (mi >> 1)) * 64 + (((2 * (w & 1) + (mi & 1)) ^ (r8 >> 1)) << 4);
        const uint32_t xb = sb + SF_XS + r8 * 1168 + mi * 16;
        auto load = [&](int i, int n, int place) {
            mbar_wait(bar_w + 8 * n);
            const uint32_t wk = fresh(wb) + place * 24576;
#pragma unroll
            for (int s = 0; s < 4; s++) { ldsm4t(fr[8 * i + s], wk + 1024 * s); ldsm4t(fr[8 * i + 4 + s], wk + 1024 * s + 12288); }
        };
        auto mul = [&](int i, uint32_t xk) {
            uint32_t x[2][4];
            ldsm4(x[0], xk); ldsm4(x[1], xk + 64);
#pragma unroll
            for (int s = 0; s < 4; s++) {
                const uint32_t (&a)[4] = fr[8 * i + s], (&b)[4] = fr[8 * i + 4 + s];
                mma_bf(ag[s & 1], a[0], a[1], a[2], a[3], x[s >> 1][2 * (s & 1)], x[s >> 1][2 * (s & 1) + 1]);
                mma_bf(au[s & 1], b[0], b[1], b[2], b[3], x[s >> 1][2 * (s & 1)], x[s >> 1][2 * (s & 1) + 1]);
            }
        };
#pragma unroll
        for (int i = 0; i < 3; i++) load(i, 3 * j + i, (i ? 5 : 3) * j + i);
        pin();
        bar_sync(BAR_G + j, 192);
        if (w == 0 && lane == 0) mbar_arrive(bar_free + 8 * j);
        mbar_wait(bar_x);
        if (warp == 0) TSTAMP(8);
        {
            const uint32_t xk = fresh(xb) + 384 * j;
#pragma unroll
            for (int i = 0; i < 3; i++) { mul(i, (i ? fresh(xk) : xk) + 128 * i); if (i == 0) { asm volatile("" :: "f"(ag[0][0]), "f"(ag[1][0]), "f"(au[0][0]), "f"(au[1][0])); sts32(s_tok + 64, clock32()); } }
        }
#pragma unroll 1
        for (int n = 6 + j; n < 9; n += 2) { load(0, n, n - 6); mul(0, fresh(xb) + 128 * n); }
#pragma unroll
        for (int c = 0; c < 4; c++) { ag[0][c] += ag[1][c]; au[0][c] += au[1][c]; }
        if (j) {
            sts128(wb + 24576, __float_as_uint(ag[0][0]), __float_as_uint(ag[0][1]), __float_as_uint(ag[0][2]), __float_as_uint(ag[0][3]));
            sts128(wb + 25600, __float_as_uint(au[0][0]), __float_as_uint(au[0][1]), __float_as_uint(au[0][2]), __float_as_uint(au[0][3]));
        }
        bar_sync(BAR_GU, 384);
        if (!j) {
            const uint32_t sf = fresh(wb);
            const uint4 g1 = lds128(sf + 24576), u1 = lds128(sf + 25600);
            const uint32_t gs[4] = {g1.x, g1.y, g1.z, g1.w}, us[4] = {u1.x, u1.y, u1.z, u1.w};
            if (warp == 0) TSTAMP(9);
            float h[4];
#pragma unroll
            for (int c = 0; c < 4; c++) {
                const float gv = rbf(ag[0][c] + __uint_as_float(gs[c]));
                h[c] = rbf(gv * sigmoidf_(gv)) * rbf(au[0][c] + __uint_as_float(us[c]));
            }
            uint32_t h0, h1;
            asm("movmatrix.sync.aligned.m8n8.trans.b16 %0, %1;" : "=r"(h0) : "r"(pack_bf16(h[0], h[1])));
            asm("movmatrix.sync.aligned.m8n8.trans.b16 %0, %1;" : "=r"(h1) : "r"(pack_bf16(h[2], h[3])));
            if (h0 == 0) h0 = 0x8000u;
            asm volatile("{ .reg .b64 v; mov.b64 v, {%1, %2}; st.relaxed.gpu.global.b64 [%0], v; }" :: "l"(p.s->h + ((epoch & 1) * 288 + 6 * f + w) * 32 + lane), "r"(h0), "r"(h1) : "memory");
        }
        if (isx) {
            if (warp == 0) TSTAMP(10);
            const uint2* hsrc = p.s->h + ((epoch & 1) * 288 + 144 * (f & 1) + warp) * 32 + lane;
            const uint32_t wd = sb + SF_WD + warp * 1024 + (r8 + 8 * (mi >> 1)) * 64 + (((mi & 1) ^ (r8 >> 1)) << 4), we = wd ^ 32;
            uint2 hb[12];
            auto ldh = [&](int i) { asm volatile("ld.relaxed.gpu.global.v2.u32 {%0, %1}, [%2];" : "=r"(hb[i].x), "=r"(hb[i].y) : "l"(hsrc + 384 * box_no(i)) : "memory"); };
            auto ldw = [&](int i) { mbar_wait(bar_d + 8 * box_no(i)); ldsm4t(fr[2 * i], fresh(wd) + 12288 * box_no(i)); ldsm4t(fr[2 * i + 1], fresh(we) + 12288 * box_no(i)); };
#pragma unroll
            for (int i = 0; i < DPA; i++) ldw(i);
#pragma unroll
            for (int i = 0; i < 12; i++) ldh(i);
#pragma unroll
            for (int i = DPA; i < DPB; i++) ldw(i);
#pragma unroll
            for (int i = 0; i < DPB; i++) asm volatile("" :: "r"(fr[2 * i][0]), "r"(fr[2 * i + 1][0]) : "memory");
#pragma unroll 1
            for (int it = 0;; it++) {
                bool again = false;
#pragma unroll
                for (int s = 0; s < 12; s += 2) if (__any_sync(0xffffffffu, min(hb[s].x, hb[s + 1].x) == 0)) { ldh(s); ldh(s + 1); again = true; }
                if (!again) break;
                if (it > (1 << 16)) give_up();
            }
            if (warp == 0) TSTAMP(11);
            float ad[2][2][4];
#pragma unroll
            for (int i = 0; i < 4; i++) { ad[i >> 1][i & 1][0] = ad[i >> 1][i & 1][1] = ad[i >> 1][i & 1][2] = ad[i >> 1][i & 1][3] = 0.f; }
#pragma unroll
            for (int i = 0; i < 12; i++) {
                if (i >= DPB) ldw(i);
                if (i == 11 && warp == 9) TSTAMP(14);
#pragma unroll
                for (int c = 0; c < 2; c++) mma_bf(ad[c][i & 1], fr[2 * i + c][0], fr[2 * i + c][1], fr[2 * i + c][2], fr[2 * i + c][3], hb[i].x, hb[i].y);
                if (i >= DPB - 1) asm volatile("" :: "f"(ad[0][i & 1][0]), "f"(ad[1][i & 1][0]) : "memory");
            }
            const uint32_t rd = sb + SF_RED + warp * 1152 + (72 * t + g) * 4;
#pragma unroll
            for (int i = 0; i < 8; i++) sts32(rd + (i >> 2) * 64 + (i & 1) * 144 + ((i >> 1) & 1) * 32, __float_as_uint(ad[i >> 2][0][i & 3] + ad[i >> 2][1][i & 3]));
            bar_sync(BAR_RED, 416);
            if (warp < 4) {
                const int tid = 32 * warp + lane;
                const uint32_t rs = fresh(sb + SF_RED) + (tid >> 4) * 144 + (tid & 15) * 8;
                const uint2 tk = lds64(fresh(s_tok) + (tid >> 4) * 8);
                float x = 0.f, y = 0.f;
#pragma unroll
                for (int w = 0; w < 12; w++) { const uint2 v = lds64(rs + w * 1152); x += __uint_as_float(v.x); y += __uint_as_float(v.y); }
                asm volatile("red.relaxed.gpu.global.add.noftz.bf16x2 [%0], %1;" :: "l"(p.out + (size_t)tk.x * DM + 32 * (f >> 1) + 2 * (tid & 15)),
                             "r"(pack_bf16(x * __uint_as_float(tk.y), y * __uint_as_float(tk.y))) : "memory");
            }
            if (warp == 0) { TSTAMP(15); TFLUSH(); }
            asm volatile("exit;"); __builtin_unreachable();
        }
    }
}

__device__ __forceinline__ void fetch_k(const uint4* src, uint64_t (&v)[6], uint32_t a, uint32_t b) {
    asm volatile("{ .reg .pred p; setp.eq.u32 p, %7, %8; @p ld.relaxed.gpu.global.v2.u64 {%0,%1}, [%6]; @p ld.relaxed.gpu.global.v2.u64 {%2,%3}, [%6 + 512]; @p ld.relaxed.gpu.global.v2.u64 {%4,%5}, [%6 + 1024]; }"
                 : "+l"(v[0]), "+l"(v[1]), "+l"(v[2]), "+l"(v[3]), "+l"(v[4]), "+l"(v[5]) : "l"(src), "r"(a), "r"(b));
}
__device__ __forceinline__ uint32_t mini_conv(const Params& p, uint32_t sb, int warp, int lane, int f, unsigned epoch, uint64_t (&v)[6]) {
    const int g = lane >> 2, t = lane & 3, mi = lane >> 3, r8 = lane & 7;
    const uint32_t fb = sb + SF_MISC, kt = sb + (warp >= 12 ? SM_KT - 12 * 2112 : f < NW ? SM_KW + 2 * 2112 : SM_KW) + warp * 2112;
    const bool ism = f >= NW;
    const uint32_t* const sel = &p.s->sel[((mini_ch0(f) + (ism ? 2 * (warp & 8) : 0)) >> 5) * 64 + r8];
    uint32_t seq = 128, key;
    const uint4* src = p.s->kp + lane;
    auto hi = [&](int i) { return (uint32_t)(v[i] >> 32); };
    if (f >= (warp < 4 ? NW : NX)) {
    {
        const uint32_t c = 68 + (warp & 3) + 2 * (warp & 12), y = ((uint32_t)((warp < 8 ? 0xe066806400000000ull : 0x5a6e00680080e26cull) >> ((8 * warp) & 48)) & 0xffff) + (warp < 14 ? 0 : 0x6a0000);
        seq = !ism ? y + (warp & 1) * ((y >> 6) & 0x10101) : warp < 14 ? 0x101 * c - 0x400 : c;
        src += (48 * (f - (ism ? NW : NX)) + (seq & 63)) * 96;
    }
    if (seq & 64) {
        if (seq & 4) {
            const int q = (seq & 3) + ((seq >> 1) & 4);
            const uint32_t ab = sb - 3072 * (seq & 16), d = ab + SM_UT + g * MU_STRIDE + (4 + 4 * q + t) * 32;
            asm volatile("st.shared.v2.u32 [%0], {%1,%1};" :: "r"(ab + SM_UT + (2 * q + (mi >> 1)) * MU_STRIDE + (lane & 15) * 8), "r"(0) : "memory");
            mbar_wait(fb + FB_MU - (seq & 16) / 2);
            if (warp == 15) TSTAMP(16);
            const uint32_t a = fresh(ab + SM_RAW) + q * 2048 + (8 * mi + 4 * (r8 & 1) + (r8 >> 1)) * 32 + ((r8 & 1) << 4);
            uint32_t x[4][4];
#pragma unroll
            for (int i = 0; i < 4; i++) ldsm4t(x[i], (i & 2 ? a ^ 16 : a) + 1024 * (i & 1));
#pragma unroll
            for (int i = 0; i < 4; i++) sts128(d + (i & 1) * 16 + (i & 2) * 4 * MU_STRIDE, x[i][0], x[i][1], x[i][2], x[i][3]);
            __syncwarp();
            if (lane == 0) mbar_arrive(fb + FB_MT + (seq & 16) / 2);
        }
        mbar_wait(fb + FB_KDONE);
        fetch_k(src, v, warp < 4, 0);
        if ((warp | 2) == 7) { fetch_gates(p, (warp >> 1) & 1, lane, epoch, sb + SM_G + 256 * (warp & 2) + 16 * lane); __syncwarp(); if (lane == 0) mbar_arrive(fb + FB_MG); }
        if (warp >= 8) {
            mbar_wait(fb + FB_KEYS); mbar_wait(fb + FB_MT);
            if (ism) {
                asm volatile("barrier.cluster.wait.aligned; fence.release.sync_restrict::shared::cta.cluster;" ::: "memory");
                if (lane == 0) asm volatile("mbarrier.arrive.relaxed.cluster.shared::cluster.b64 _, [%0];" :: "r"(mapa(fb + FB_MT + 8, 0)) : "memory");
            }
        }
        if (warp == TW) TSTAMP(17);
    }
    }
    const uint32_t lo = (8 + r8 - (mi & 1)) * 16 + (mi >> 1) * 128;
#pragma unroll 1
    do {
        const int c = seq & 63;
        const bool far = !ism && (seq & 16);
        const uint32_t ab = sb - 3072 * (c & 16);
        uint32_t ut = ab + SM_UT + (c & 15) * MU_STRIDE;
        if (seq & 64) {
        if (far) {
            mbar_wait_cluster(fb + FB_MT + 8);
            const uint32_t ru = mapa(ut, 1) + lane * 16;
            ut = sb + SM_FT + (c & 3) * 1536;
            uint4 x[3];
#pragma unroll
            for (int i = 0; i < 3; i++) asm volatile("ld.shared::cluster.v4.u32 {%0,%1,%2,%3}, [%4];" : "=r"(x[i].x), "=r"(x[i].y), "=r"(x[i].z), "=r"(x[i].w) : "r"(ru + 512 * i) : "memory");
#pragma unroll
            for (int i = 0; i < 3; i++) sts128(ut + lane * 16 + 512 * i, x[i].x, x[i].y, x[i].z, x[i].w);
        } else mbar_wait(fb + FB_MT + (seq & 16) / 2);
#pragma unroll 1
        for (int it = 0; !__all_sync(0xffffffffu, ((hi(1) ^ k_tag(epoch)) | (hi(3) ^ k_tag(epoch)) | (hi(5) ^ k_tag(epoch)) | ((uint32_t)v[5] & p.zero)) < 65536); it++) {
            fetch_k(src, v, 0, 0);
            if (it > (1 << 20)) give_up();
        }
        sts128(kt + t * 16, 0, 0, 0, 0);
        if (warp == TW) TSTAMP(seq >> 8 ? 7 : 10);
        const uint32_t w[12] = {(uint32_t)v[0], hi(0), (uint32_t)v[1], (uint32_t)v[2], hi(2), (uint32_t)v[3], (uint32_t)v[4], hi(4), 0, 0, 0, 0};
        k_tables<false>(fresh(kt), fresh(lane), w);
        }
        __syncwarp();
        if (seq & 128) ffn_work(p, sb, warp, fresh(lane), f, epoch);
        if (!(seq & 64)) return 0;
        const uint32_t kb = fresh(kt) + (16 + g - 2 * t) * 4, ub = fresh(ut);
        const uint32_t yd = ab + SM_Y + (c & 15) * 1056 + (c & 8) * 8 + lane * 16;
        if (warp == TW && !(seq >> 8)) TSTAMP(13);
        seq >>= 8;
        src += ((int)(seq & 63) - c) * 96;
#pragma unroll
        for (int i = 0; i < 6; i++) v[i] = 0;
        key = 0;
        float acc[8][4];
#pragma unroll
        for (int i = 0; i < 8; i++) { acc[i][0] = acc[i][1] = acc[i][2] = acc[i][3] = 0.f; }
        uint32_t a[4][4], b[2][4][4];
        auto lda = [&](int j, int s) { const uint32_t x = kb + 64 * s + 512 * j; a[j][0] = lds32(x); a[j][1] = lds32(x + 256); a[j][2] = lds32(x + 32); a[j][3] = lds32(x + 288); };
        auto ldb = [&](int i, int s) { ldsm4(b[s & 1][i], ub + lo + 256 * i - 32 * s); };
#pragma unroll
        for (int j = 0; j < 4; j++) { ldb(j, 0); lda(j, 0); }
#pragma unroll
        for (int s = 0; s < 4; s++) {
            if (s == 2) {
                const uint32_t e = seq | (__float_as_uint(acc[0][0]) & p.zero);
                fetch_k(src, v, e & 64, 64);
                asm volatile("{ .reg .pred p; setp.eq.u32 p, %2, 0; @p ld.relaxed.gpu.global.u32 %0, [%1]; }" : "+r"(key) : "l"(sel), "r"(e));
            }
#pragma unroll
            for (int i = 0; i < 4; i++) {
                const int j = (i >> 1) + 2 * (i & 1);
                if (s < 3) ldb(i, s + 1);
#pragma unroll
                for (int mu = 0; mu < 8; mu++) if (mu + 2 * j < 8) mma_bf(acc[mu + 2 * j], a[j][0], a[j][1], a[j][2], a[j][3], b[s & 1][mu >> 1][2 * (mu & 1)], b[s & 1][mu >> 1][2 * (mu & 1) + 1]);
                if (s < 3) lda(j, s + 1);
            }
        }
        if (warp == TW && !seq) TSTAMP(14);
        mbar_wait(fb + FB_MG);
        uint32_t ug[4][4];
#pragma unroll
        for (int i = 0; i < 2; i++) { ldsm4t(ug[i], ub + 128 + lane * 16 + 512 * i); ldsm4t(ug[2 + i], fresh(sb + SM_G) + lane * 16 + 512 * i); }
#pragma unroll
        for (int x = 0; x < 8; x++) ug[x >> 2][x & 3] = gmix(ug[2 + (x >> 2)][x & 3], x ? acc[x][0] + acc[x - 1][2] : acc[0][0], x ? acc[x][1] + acc[x - 1][3] : acc[0][1], ug[x >> 2][x & 3]);
        if (far) for (int i = 0; i < 2; i++) st_async128(mapa(yd, 1) + 512 * i, ug[i][0], ug[i][1], ug[i][2], ug[i][3], mapa(fb + FB_FAR, 1));
        else for (int i = 0; i < 2; i++) sts128(yd + 512 * i, ug[i][0], ug[i][1], ug[i][2], ug[i][3]);
        __syncwarp();
        if (warp == TW) TSTAMP(18 + (seq != 0));
    } while (seq);
    if (warp >= 12) TSTAMP(12 + warp);
    return key;
}
__device__ __forceinline__ void mini_out(const Params& p, const CUtensorMap* maps, uint32_t sb, int warp, int lane, int f, unsigned epoch, uint32_t key) {
    const int g = lane >> 2, t = lane & 3, mi = lane >> 3, r8 = lane & 7;
    const uint32_t fb = sb + SF_MISC;
    const bool ism = f >= NW;
    const int ch0 = mini_ch0(f);
    const int k = ism ? warp >> 3 : 0;
    uint32_t first = 1;
    if (lane == 0) asm volatile("atom.shared.exch.b32 %0, [%1], 1;" : "=r"(first) : "r"(fb + FS_BM + 64 + 4 * k) : "memory");
    if (!__all_sync(0xffffffffu, first)) {
        if (elect()) prefetch_map(maps + 6);
        const int row = key_row(wait_sel(p, (ch0 + 16 * k) >> 5, r8, key_tag(epoch), key));
        if (row < 512) asm volatile("red.shared.or.b32 [%0], %1;" :: "r"(fb + FS_BM + (row >> 5) * 4), "r"(1u << (row & 31)) : "memory");
        if (k) mbar_wait_cluster(fb + FB_FAR);
    }
    const int m = warp & 7, dr = 64 * (g >> 1) + 16 * (t >> 1) + 8 * (g & 1);
    const uint32_t y = SM_Y + ((r8 >> 1) & 1) * 8512 + (2 * mi + (r8 & 1)) * 1056 + (2 * m + (r8 >> 2)) * 16;
    const uint32_t so = (g >> 1) * 128 + (t >> 1) * 64 + (g & 1) * 32 + (t & 1) * 16;
    bar_sync(BAR_M - k, ism ? 256 : NTHR);
#pragma unroll 1
    for (int h = ism ? 0 : warp >> 3;; h++) {
        const int r0 = 256 * h + 32 * (m & 1) + (m >> 1), row = r0 + dr;
        const uint32_t bm = lds32(fresh(fb) + FS_BM + (row >> 5) * 4) >> (row & 31), ab = fresh(sb - 49152 * k + 512 * h), stg = ab + SM_UT + 2048 * m + 512 * h;
        uint32_t x[2][4];
        ldsm4t(x[0], ab + y); ldsm4t(x[1], ab + y + 256);
        if (warp == 0 && x[0][0] != 0x12345) TSTAMP(28);
        if (__any_sync(0xffffffffu, bm & 0x11u)) {
#pragma unroll
            for (int i = 0; i < 2; i++) store_or_add(p.out + (size_t)(row + 4 * i) * DM + ch0 + 16 * k + 8 * (t & 1), x[i], bm & (1u << (4 * i)));
        } else {
#pragma unroll
            for (int i = 0; i < 2; i++) sts128(stg + so + 512 * i, x[i][0], x[i][1], x[i][2], x[i][3]);
            asm volatile("fence.proxy.async.shared::cta;" ::: "memory");
            __syncwarp();
            if (elect()) store_rows(maps + 6, stg, ch0 + 16 * k, r0);
        }
        if (h >= ism) break;
    }
    if (elect()) { asm volatile("cp.async.bulk.commit_group;" ::: "memory"); asm volatile("cp.async.bulk.wait_group.read 0;" ::: "memory"); }
    if (warp == 8) TSTAMP(11);
    if (warp == 0) { TSTAMP(15); TFLUSH(); }
}

constexpr int SMEM_BYTES = 232448;
static_assert(SF_MISC + 1152 <= 232192, "layout");

struct Maps { CUtensorMap m[7]; };

__global__ void __cluster_dims__(2, 1, 1) __launch_bounds__(NTHR, 1)
fused_kernel(const Params p, const __grid_constant__ Maps maps) {
    extern __shared__ __align__(1024) uint8_t smem_raw[];
    uint32_t q[8];
    {
        const int b = role(blockIdx.x), x = threadIdx.x, rc = 5 * b + (b & ~3) + 4 + (x >> 6);
        const int cv = (unsigned)b < NW ? 0 : -1, ca = (b < 0 ? 8 * b + DM : 48 * b - 2300) + ((x >> 5) & 3), cb = 2 * rc - (rc & 3) + 4;
        const uint32_t ch = (ca & cv) | (cb & ~cv), o = NST * ch + 2 * ((x & 31) + ((x >> (cv & 2)) & 32));
        const bool c = x < (cv ? 256 : 320);
        q[6] = ldg16_if(c, p.logdt + ch);
        q[2] = ldg32_if(c, p.Bre + o); q[3] = ldg32_if(c, p.Bim + o); q[4] = ldg32_if(c, p.Cre + o); q[5] = ldg32_if(c, p.Cim + o); q[0] = ldg32_if(c, p.Are + o); q[1] = ldg32_if(c, p.Aim + o);
        q[7] = ldg16_if(c, p.Dskip + ch);
    }
    const unsigned epoch = ld_rlx32(&p.s->epoch[blockIdx.x * 16 + (threadIdx.x >> 5)]);
    const uint32_t sb = __shfl_sync(0xffffffffu, smem_u32(smem_raw), 0);
    const int warp = __shfl_sync(0xffffffffu, threadIdx.x >> 5, 0), bid = __shfl_sync(0xffffffffu, blockIdx.x, 0);
    const int lane = __shfl_sync(0xffffffffu, threadIdx.x & 31, threadIdx.x);
    const bool conv = bid < NCONV;
    const int f = role(bid);
    uint32_t w[12];
    uint64_t v[6];
    const bool four = (unsigned)f >= NW;
    if (warp < (four ? 8 : 10)) {
        const int half = four ? warp >> 2 : warp & 1, pr = four ? warp & 3 : warp >> 1;
        const int rc = 5 * f + (f & ~3) + 4 + pr;
        const uint32_t stage = sb + (conv ? SC_KG : SF_KG) + warp * KG_STAGE;
        uint4* const kp = p.s->kp + (four ? (conv ? 8 * bid : 48 * f - 2300) + pr : 2 * rc - (rc & 3) + 4) * 96 + lane;
        kgen(q, sb, half, stage, stage + (four ? 4 : 1) * KG_STAGE, 1 + pr, lane, w, [&] {
            sts128z_if(conv && lane < 20, sb + SC_KT + warp * KT_BYTES + lane * 16 + (lane < 4 ? 0 : lane < 14 ? 2048 : 2288));
            stg128z_if(!conv, kp + 64 * half); stg128z_if(!half && !conv, kp + 32);
            stg128z_if((unsigned)f < NW && warp < 6, (uint4*)(p.s->h + ((lane >> 4) * 288 + 6 * f + warp) * 32) + (lane & 15));
            if (!conv) bar_sync(0, NTHR);
            if ((unsigned)f >= NX) asm volatile("barrier.cluster.arrive.relaxed.aligned;" ::: "memory");
        });
        if (!half) publish_k(kp, w, epoch, v);
        else for (int i = 0; i < 6; i++) v[i] = 0;
        if (conv) { conv_main(p, sb, warp, lane, bid, epoch, w); return; }
        {
            if (!half && lane == 0) mbar_arrive(sb + SF_MISC + FB_KDONE);
            if (warp == 0) TSTAMP(22);
            if (warp == 2) TSTAMP(23);
        }
    } else if (conv) {
        conv_aux(p, maps.m, sb, warp - 8, lane, bid, epoch);
        return;
    } else {
        ffn_front(p, maps.m, sb, warp, lane, f, epoch);
        for (int i = 0; i < 6; i++) v[i] = 0;
    }
    converged();
    next_epoch(p, epoch);
    if (warp >= 12 && f < NX) return;
    mini_out(p, maps.m, sb, warp, lane, f, epoch, mini_conv(p, sb, warp, __shfl_sync(0xffffffffu, lane, lane), f, epoch, v));
}

typedef CUresult (*EncodeFn)(CUtensorMap*, CUtensorMapDataType, cuuint32_t, void*, const cuuint64_t*, const cuuint64_t*, const cuuint32_t*, const cuuint32_t*,
                             CUtensorMapInterleave, CUtensorMapSwizzle, CUtensorMapL2promotion, CUtensorMapFloatOOBfill);

void make_map(EncodeFn fn, CUtensorMap* m, const void* base, int rank, const cuuint64_t* dims, const cuuint64_t* strides, const cuuint32_t* box, CUtensorMapSwizzle sw) {
    const cuuint32_t es[5] = {1, 1, 1, 1, 1};
    fn(m, CU_TENSOR_MAP_DATA_TYPE_BFLOAT16, rank, (void*)base, dims, strides, box, es, CU_TENSOR_MAP_INTERLEAVE_NONE, sw,
       CU_TENSOR_MAP_L2_PROMOTION_NONE, CU_TENSOR_MAP_FLOAT_OOB_FILL_NONE);
}

}

extern "C" void kernel_launch(void* const* d_in, const int* in_sizes, int n_in, void* d_out, int out_size) {
    (void)in_sizes; (void)n_in; (void)out_size;
    static EncodeFn fn = nullptr;
    static void* scratch = nullptr;
    if (!fn) {
        void* ptr = nullptr; cudaDriverEntryPointQueryResult qr;
        cudaGetDriverEntryPoint("cuTensorMapEncodeTiled", &ptr, cudaEnableDefault, &qr);
        fn = (EncodeFn)ptr;
        cudaGetSymbolAddress(&scratch, g_scratch);
        cudaFuncSetAttribute(fused_kernel, cudaFuncAttributeMaxDynamicSharedMemorySize, SMEM_BYTES);
    }
    typedef const __nv_bfloat16* bp;
    Params p;
    p.u = (bp)d_in[0]; p.Are = (bp)d_in[1]; p.Aim = (bp)d_in[2]; p.Bre = (bp)d_in[3]; p.Bim = (bp)d_in[4]; p.Cre = (bp)d_in[5]; p.Cim = (bp)d_in[6];
    p.logdt = (bp)d_in[7]; p.Dskip = (bp)d_in[8]; p.wr = (bp)d_in[10]; p.gatew = (bp)d_in[14];
    p.out = (__nv_bfloat16*)d_out; p.s = (Scratch*)scratch; p.zero = 0;
    Maps maps;
    {
        const cuuint64_t dims[4] = {DM, 4, 16, 32}, strides[3] = {16 * DM * 2, DM * 2, 64 * DM * 2};
        const cuuint32_t box[4] = {16, 4, 16, 2};
        make_map(fn, &maps.m[0], d_in[0], 4, dims, strides, box, CU_TENSOR_MAP_SWIZZLE_32B);
        const cuuint32_t box2[4] = {16, 4, 16, 8};
        make_map(fn, &maps.m[5], d_in[0], 4, dims, strides, box2, CU_TENSOR_MAP_SWIZZLE_32B);
    }
    for (int i = 0; i < 2; i++) {
        const cuuint64_t dims[3] = {32, DM, FF / 32}, strides[2] = {FF * 2, 64};
        const cuuint32_t box[3] = {32, 64, 3};
        make_map(fn, &maps.m[1 + i], d_in[11 + i], 3, dims, strides, box, CU_TENSOR_MAP_SWIZZLE_64B);
    }
    {
        const cuuint64_t dims[2] = {DM, FF}, strides[1] = {DM * 2};
        const cuuint32_t box[2] = {32, 192};
        make_map(fn, &maps.m[3], d_in[13], 2, dims, strides, box, CU_TENSOR_MAP_SWIZZLE_64B);
    }
    {
        const cuuint64_t dims[5] = {DM, 2, 4, 4, L_SEQ}, strides[4] = {16 * DM * 2, 64 * DM * 2, 4 * DM * 2, DM * 2};
        const cuuint32_t box[5] = {16, 2, 4, 4, 1};
        make_map(fn, &maps.m[4], d_out, 5, dims, strides, box, CU_TENSOR_MAP_SWIZZLE_NONE);
    }
    {
        const cuuint64_t dims[5] = {DM, 4, 4, 2, L_SEQ}, strides[4] = {8 * DM * 2, 64 * DM * 2, 4 * DM * 2, DM * 2};
        const cuuint32_t box[5] = {16, 4, 4, 2, 1};
        make_map(fn, &maps.m[6], d_out, 5, dims, strides, box, CU_TENSOR_MAP_SWIZZLE_NONE);
    }
    fused_kernel<<<NCTA, NTHR, SMEM_BYTES>>>(p, maps);
}
```

```cpp
#include <cuda_runtime.h>
#include <cuda_bf16.h>
#include <cuda_fp16.h>
#include <cuda.h>
#include <stdint.h>

#define RESUME 300
#define MDELAY 2000
#define MGAP 0
#define KPOLL 650
#define DPA 7
#define DPB 9
#define RDELAY 900
#define WDELAY 1700
#define WGAP 290
#define NPRE 8
#define DGAP 290
namespace {

constexpr int DM = 576, NST = 128, FF = 4608, L_SEQ = 2048;
constexpr int NCONV = 72, NX = 36, NW = 48, NCTA = 132, NTHR = 512;

struct __align__(128) Scratch {
    unsigned epoch[NCTA * 16];
    uint4 keys[16 * 128];
    uint32_t sel[18 * 64];
    uint16_t gate[L_SEQ];
    uint2 h[2 * 288 * 32];
    uint4 kp[DM * 96];
};
__device__ Scratch g_scratch;
#define TFLUSH()
#define TSTAMP(i)
#define TW 12

struct Params {
    const __nv_bfloat16 *Are, *Aim, *Bre, *Bim, *Cre, *Cim, *logdt, *Dskip, *u, *wr, *gatew;
    __nv_bfloat16* out;
    Scratch* s;
    uint32_t zero;
};

__device__ __forceinline__ void give_up() { asm volatile("trap; exit;"); __builtin_unreachable(); }
__device__ __forceinline__ void converged() { __syncwarp(); asm volatile("{ .reg .b32 t; mov.b32 t, 0; movmatrix.sync.aligned.m8n8.trans.b16 t, t; }" ::: "memory"); }
__device__ __forceinline__ bool elect() { uint32_t r; asm volatile("{ .reg .pred p; elect.sync _|p, 0xffffffff; selp.u32 %0, 1, 0, p; }" : "=r"(r)); return r; }
__device__ __forceinline__ uint32_t smem_u32(const void* p) { return (uint32_t)__cvta_generic_to_shared(p); }
__device__ __forceinline__ uint32_t pack_bf16(float lo, float hi) { uint32_t r; asm("cvt.rn.bf16x2.f32 %0, %1, %2;" : "=r"(r) : "f"(hi), "f"(lo)); return r; }
__device__ __forceinline__ uint32_t pack_f16(float lo, float hi) { uint32_t r; asm("cvt.rn.f16x2.f32 %0, %1, %2;" : "=r"(r) : "f"(hi), "f"(lo)); return r; }
__device__ __forceinline__ float bf_lo(uint32_t w) { return __uint_as_float(w << 16); }
__device__ __forceinline__ float bf_hi(uint32_t w) { return __uint_as_float(w & 0xffff0000u); }
__device__ __forceinline__ float rbf(float x) { return bf_lo(pack_bf16(x, 0.f)); }
__device__ __forceinline__ uint32_t badd2(uint32_t a, uint32_t b) { uint32_t r; asm("add.rn.bf16x2 %0, %1, %2;" : "=r"(r) : "r"(a), "r"(b)); return r; }
__device__ __forceinline__ uint32_t bsub2(uint32_t a, uint32_t b) { uint32_t r; asm("sub.rn.bf16x2 %0, %1, %2;" : "=r"(r) : "r"(a), "r"(b)); return r; }
__device__ __forceinline__ uint32_t gmix(uint32_t ng, float ny0, float ny1, uint32_t u) {
    uint32_t r; asm("{ .reg .b32 t; fma.rn.bf16x2 t, %1, %3, %3; fma.rn.bf16x2 %0, %1, %2, t; }" : "=r"(r) : "r"(ng), "r"(pack_bf16(ny0, ny1)), "r"(u)); return r;
}
__device__ __forceinline__ void mma_bf(float (&c)[4], uint32_t a0, uint32_t a1, uint32_t a2, uint32_t a3, uint32_t b0, uint32_t b1) {
    asm("mma.sync.aligned.m16n8k16.row.col.f32.bf16.bf16.f32 {%0,%1,%2,%3}, {%4,%5,%6,%7}, {%8,%9}, {%0,%1,%2,%3};"
        : "+f"(c[0]), "+f"(c[1]), "+f"(c[2]), "+f"(c[3]) : "r"(a0), "r"(a1), "r"(a2), "r"(a3), "r"(b0), "r"(b1));
}
__device__ __forceinline__ void mma_bf8(float (&c)[4], uint32_t a0, uint32_t a1, uint32_t b0) {
    asm("mma.sync.aligned.m16n8k8.row.col.f32.bf16.bf16.f32 {%0,%1,%2,%3}, {%4,%5}, {%6}, {%0,%1,%2,%3};"
        : "+f"(c[0]), "+f"(c[1]), "+f"(c[2]), "+f"(c[3]) : "r"(a0), "r"(a1), "r"(b0));
}
__device__ __forceinline__ void mma_h(float (&c)[4], uint32_t a0, uint32_t a1, uint32_t a2, uint32_t a3, uint32_t b0, uint32_t b1) {
    asm("mma.sync.aligned.m16n8k16.row.col.f32.f16.f16.f32 {%0,%1,%2,%3}, {%4,%5,%6,%7}, {%8,%9}, {%0,%1,%2,%3};"
        : "+f"(c[0]), "+f"(c[1]), "+f"(c[2]), "+f"(c[3]) : "r"(a0), "r"(a1), "r"(a2), "r"(a3), "r"(b0), "r"(b1));
}
__device__ __forceinline__ uint32_t fresh(uint32_t a) { asm volatile("" : "+r"(a) :: "memory"); return a; }
__device__ __forceinline__ uint32_t lds32(uint32_t a) { uint32_t v; asm("ld.shared.u32 %0, [%1];" : "=r"(v) : "r"(a)); return v; }
__device__ __forceinline__ uint2 lds64(uint32_t a) { uint2 v; asm("ld.shared.v2.u32 {%0,%1}, [%2];" : "=r"(v.x), "=r"(v.y) : "r"(a)); return v; }
__device__ __forceinline__ uint4 lds128(uint32_t a) { uint4 v; asm("ld.shared.v4.u32 {%0,%1,%2,%3}, [%4];" : "=r"(v.x), "=r"(v.y), "=r"(v.z), "=r"(v.w) : "r"(a)); return v; }
__device__ __forceinline__ void ldsm4(uint32_t (&r)[4], uint32_t a) {
    asm("ldmatrix.sync.aligned.m8n8.x4.shared.b16 {%0,%1,%2,%3}, [%4];" : "=r"(r[0]), "=r"(r[1]), "=r"(r[2]), "=r"(r[3]) : "r"(a));
}
__device__ __forceinline__ void ldsm4t(uint32_t (&r)[4], uint32_t a) {
    asm("ldmatrix.sync.aligned.m8n8.x4.trans.shared.b16 {%0,%1,%2,%3}, [%4];" : "=r"(r[0]), "=r"(r[1]), "=r"(r[2]), "=r"(r[3]) : "r"(a));
}
__device__ __forceinline__ void sts16(uint32_t a, uint32_t v) { asm volatile("st.shared.u16 [%0], %1;" :: "r"(a), "h"((unsigned short)v) : "memory"); }
__device__ __forceinline__ void sts32(uint32_t a, uint32_t v) { asm volatile("st.shared.u32 [%0], %1;" :: "r"(a), "r"(v) : "memory"); }
__device__ __forceinline__ void sts64(uint32_t a, uint32_t x, uint32_t y) { asm volatile("st.shared.v2.u32 [%0], {%1,%2};" :: "r"(a), "r"(x), "r"(y) : "memory"); }
__device__ __forceinline__ void sts128(uint32_t a, uint32_t x, uint32_t y, uint32_t z, uint32_t w) {
    asm volatile("st.shared.v4.u32 [%0], {%1,%2,%3,%4};" :: "r"(a), "r"(x), "r"(y), "r"(z), "r"(w) : "memory");
}
__device__ __forceinline__ void st_async128(uint32_t a, uint32_t x, uint32_t y, uint32_t z, uint32_t w, uint32_t bar) {
    asm volatile("st.async.weak.shared::cluster.mbarrier::complete_tx::bytes.v4.b32 [%0], {%1,%2,%3,%4}, [%5];" :: "r"(a), "r"(x), "r"(y), "r"(z), "r"(w), "r"(bar) : "memory");
}
__device__ __forceinline__ void mbar_init(uint32_t b, uint32_t cnt) { asm volatile("mbarrier.init.shared::cta.b64 [%0], %1;" :: "r"(b), "r"(cnt) : "memory"); }
__device__ __forceinline__ void mbar_fence() { asm volatile("fence.mbarrier_init.release.cluster;" ::: "memory"); }
__device__ __forceinline__ void mbar_expect(uint32_t b, uint32_t bytes) { asm volatile("mbarrier.arrive.expect_tx.shared::cta.b64 _, [%0], %1;" :: "r"(b), "r"(bytes) : "memory"); }
__device__ __forceinline__ void mbar_arrive(uint32_t b) { asm volatile("mbarrier.arrive.shared::cta.b64 _, [%0];" :: "r"(b) : "memory"); }
__device__ __forceinline__ void mbar_wait(uint32_t b, uint32_t parity = 0) {
    asm volatile("{ .reg .pred p; .reg .u32 n; mov.u32 n, 0;\n"
                 "LW: mbarrier.try_wait.parity.shared::cta.b64 p, [%0], %1; @p bra LD; add.u32 n, n, 1; setp.lt.u32 p, n, 65536; @p bra LW; trap;\n"
                 "LD: }" :: "r"(b), "r"(parity) : "memory");
}
__device__ __forceinline__ void mbar_wait_cluster(uint32_t b) {
    asm volatile("{ .reg .pred p; .reg .u32 n; mov.u32 n, 0;\n"
                 "LW: mbarrier.try_wait.parity.acquire.cluster.shared::cta.b64 p, [%0], 0; @p bra LD; add.u32 n, n, 1; setp.lt.u32 p, n, 65536; @p bra LW; trap;\n"
                 "LD: }" :: "r"(b) : "memory");
}
__device__ __forceinline__ void tma2d(uint32_t dst, const CUtensorMap* m, int c0, int c1, uint32_t bar) {
    asm volatile("cp.async.bulk.tensor.2d.shared::cluster.global.mbarrier::complete_tx::bytes [%0], [%1, {%3, %4}], [%2];"
                 :: "r"(dst), "l"(m), "r"(bar), "r"(c0), "r"(c1) : "memory");
}
__device__ __forceinline__ void tma3d(uint32_t dst, const CUtensorMap* m, int c0, int c1, int c2, uint32_t bar) {
    asm volatile("cp.async.bulk.tensor.3d.shared::cluster.global.mbarrier::complete_tx::bytes [%0], [%1, {%3, %4, %5}], [%2];"
                 :: "r"(dst), "l"(m), "r"(bar), "r"(c0), "r"(c1), "r"(c2) : "memory");
}
__device__ __forceinline__ void tma4d(uint32_t dst, const CUtensorMap* m, int c0, int c1, int c2, int c3, uint32_t bar) {
    asm volatile("cp.async.bulk.tensor.4d.shared::cluster.global.mbarrier::complete_tx::bytes [%0], [%1, {%3, %4, %5, %6}], [%2];"
                 :: "r"(dst), "l"(m), "r"(bar), "r"(c0), "r"(c1), "r"(c2), "r"(c3) : "memory");
}
__device__ __forceinline__ void bulk_g2s(uint32_t dst, const void* src, uint32_t bytes, uint32_t bar) {
    asm volatile("cp.async.bulk.shared::cluster.global.mbarrier::complete_tx::bytes [%0], [%1], %2, [%3];"
                 :: "r"(dst), "l"(src), "r"(bytes), "r"(bar) : "memory");
}
__device__ __forceinline__ uint32_t mapa(uint32_t a, uint32_t rank) { uint32_t r; asm("mapa.shared::cluster.u32 %0, %1, %2;" : "=r"(r) : "r"(a), "r"(rank)); return r; }
__device__ __forceinline__ void prefetch_map(const CUtensorMap* m) { asm volatile("prefetch.tensormap [%0];" :: "l"(m) : "memory"); }
__device__ __forceinline__ void bar_sync(int id, int n) { asm volatile("bar.sync %0, %1;" :: "r"(id), "r"(n) : "memory"); }
__device__ __forceinline__ void bar_arrive(int id, int n) { asm volatile("bar.arrive %0, %1;" :: "r"(id), "r"(n) : "memory"); }
__device__ __forceinline__ uint32_t ldg16_if(bool c, const void* p) { uint32_t v; asm volatile("{ .reg .pred p; setp.ne.u32 p, %2, 0; @p ld.global.nc.u16 %0, [%1]; }" : "=r"(v) : "l"(p), "r"((uint32_t)c)); return v; }
__device__ __forceinline__ uint32_t ldg32_if(bool c, const void* p) { uint32_t v; asm volatile("{ .reg .pred p; setp.ne.u32 p, %2, 0; @p ld.global.nc.u32 %0, [%1]; }" : "=r"(v) : "l"(p), "r"((uint32_t)c)); return v; }
__device__ __forceinline__ uint32_t ld_rlx32(const void* p) { uint32_t v; asm volatile("ld.relaxed.gpu.global.u32 %0, [%1];" : "=r"(v) : "l"(p) : "memory"); return v; }
__device__ __forceinline__ uint4 ld_rlx128(const void* p) {
    uint4 v; asm volatile("ld.relaxed.gpu.global.v4.u32 {%0,%1,%2,%3}, [%4];" : "=r"(v.x), "=r"(v.y), "=r"(v.z), "=r"(v.w) : "l"(p) : "memory"); return v;
}
__device__ __forceinline__ void st_rlx32(void* p, uint32_t v) { asm volatile("st.relaxed.gpu.global.u32 [%0], %1;" :: "l"(p), "r"(v) : "memory"); }
__device__ __forceinline__ void stg128(void* p, uint32_t x, uint32_t y, uint32_t z, uint32_t w) {
    asm volatile("st.global.v4.u32 [%0], {%1,%2,%3,%4};" :: "l"(p), "r"(x), "r"(y), "r"(z), "r"(w) : "memory");
}
__device__ __forceinline__ void next_epoch(const Params& p, unsigned e) { if ((threadIdx.x & 31) == 0) p.s->epoch[blockIdx.x * 16 + (threadIdx.x >> 5)] = e + 1; }
__device__ __forceinline__ void sts128z_if(bool c, uint32_t a) { asm volatile("{ .reg .pred p; setp.ne.u32 p, %1, 0; @p st.shared.v4.u32 [%0], {%2,%2,%2,%2}; }" :: "r"(a), "r"((uint32_t)c), "r"(0) : "memory"); }
__device__ __forceinline__ void stg128z_if(bool c, void* a) { asm volatile("{ .reg .pred p; setp.ne.u32 p, %1, 0; @p st.global.v4.u32 [%0], {%2,%2,%2,%2}; }" :: "l"(a), "r"((uint32_t)c), "r"(0) : "memory"); }
__device__ __forceinline__ unsigned clock32() { unsigned c; asm volatile("mov.u32 %0, %clock;" : "=r"(c) :: "memory"); return c; }
__device__ __forceinline__ void until(unsigned t0, int c) { while ((int)(clock32() - t0) < c) { } }
__device__ __forceinline__ float sigmoidf_(float x) { return __fdividef(1.0f, 1.0f + __expf(-x)); }
__device__ __forceinline__ uint32_t key_tag(unsigned epoch) { return ((epoch & 15u) | 16u) << 11; }
__device__ __forceinline__ int key_row(uint32_t key) { return 2047 - (int)(key & 2047u); }
__device__ __forceinline__ uint32_t wait_sel(const Params& p, int s32, int r8, uint32_t tag, uint32_t k = 0) {
#pragma unroll 1
    for (int it = 0; !__all_sync(0xffffffffu, (k & 0xf800u) == tag); it++) {
        k = ld_rlx32(&p.s->sel[s32 * 64 + r8]);
        if (it > (1 << 20)) give_up();
    }
    return k;
}

struct cplx { float re, im; };
__device__ __forceinline__ cplx csq(cplx a) { cplx r; r.re = a.re * a.re - a.im * a.im; r.im = (a.re * a.im) * 2.f; return r; }
__device__ __forceinline__ cplx cexpk(float ar, float ai, float k) {
    float mag, s, c;
    asm("ex2.approx.ftz.f32 %0, %1;" : "=f"(mag) : "f"(ar * (k * 1.4426950408889634f)));
    const float r = ai * k;
    asm("sin.approx.ftz.f32 %0, %1;" : "=f"(s) : "f"(r));
    asm("cos.approx.ftz.f32 %0, %1;" : "=f"(c) : "f"(r));
    cplx o; o.re = mag * c; o.im = mag * s; return o;
}
struct h2c { uint32_t re, im; };
__device__ __forceinline__ h2c cmul_cd(h2c v, __half2 c, __half2 d) {
    const __half2 r = *(const __half2*)&v.re, i = *(const __half2*)&v.im;
    const __half2 x = __hfma2(__hneg2(i), d, __hmul2(r, c)), y = __hfma2(i, c, __hmul2(r, d));
    h2c o; o.re = *(const uint32_t*)&x; o.im = *(const uint32_t*)&y; return o;
}
__device__ __forceinline__ h2c cmul_s(h2c v, uint32_t s) { const __half2 h = *(const __half2*)&s; return cmul_cd(v, __low2half2(h), __high2half2(h)); }
__device__ __forceinline__ h2c cmul_sc(h2c v, uint32_t s) {
    const __half2 h = *(const __half2*)&s, c = __low2half2(h), d = __high2half2(h), r = *(const __half2*)&v.re, i = *(const __half2*)&v.im;
    const __half2 x = __hfma2(i, d, __hmul2(r, c)), y = __hfma2(__hneg2(r), d, __hmul2(i, c));
    h2c o; o.re = *(const uint32_t*)&x; o.im = *(const uint32_t*)&y; return o;
}
__device__ __forceinline__ h2c cmul_vc(h2c v, uint32_t s) {
    const __half2 h = *(const __half2*)&s, c = __low2half2(h), d = __high2half2(h), r = *(const __half2*)&v.re, i = *(const __half2*)&v.im;
    const __half2 x = __hfma2(i, d, __hmul2(r, c)), y = __hfma2(__hneg2(i), c, __hmul2(r, d));
    h2c o; o.re = *(const uint32_t*)&x; o.im = *(const uint32_t*)&y; return o;
}

constexpr int UT_HALF = 2560, UT_STRIDE = 4736, GT_HALF = 2240;
__device__ __forceinline__ uint32_t swz(uint32_t x, int c) { return x ^ (((x >> 2) & 64) ^ (64 * (c & 1) + 8 * (c & 6))); }
__device__ __forceinline__ int col(int n) { return (n >> 1) + 4 * (n & 1); }
constexpr int KT_T = 542, KT_C = 552, KT_D = 645, KT_BYTES = 720 * 4;
constexpr int VC_OFF = 80, VE_BASE = 1616;
constexpr int V_STRIDE = (1616 + 1024) * 4 + 80;
constexpr int KG_STAGE = 5248;
constexpr int Y_CS = 2080, Y_RS = 8 * Y_CS + 64;

constexpr int SC_RT = 0;
constexpr int SC_UT = 33408;
constexpr int SC_KG = SC_UT + 8 * UT_STRIDE;
constexpr int SC_KT = SC_KG + 8 * KG_STAGE;
constexpr int SC_GT = SC_KT + 8 * KT_BYTES;
constexpr int SC_V = SC_GT + 4448;
constexpr int SC_MISC = SC_V + 8 * V_STRIDE;
static_assert(V_STRIDE % 128 == 16 && 2 * Y_RS <= SC_UT && SC_UT % 128 == 0 && SC_KG % 128 == 0, "layout");
static_assert(SC_MISC % 16 == 0 && SC_MISC + 512 <= 232192, "layout");

__device__ __forceinline__ void window_task(uint32_t s0, uint32_t s1, uint32_t d0, uint32_t d1, int k) {
    float S[51], s = 0.f;
    uint32_t w[28];
#pragma unroll
    for (int i = 0; i < 7; i++) {
        const uint4 v = lds128(((i < 3 ? s0 : s1) ^ 8 * ((i + 1) & 2)) + ((i & 1) ? 0 : UT_HALF));
        w[4 * i] = v.x; w[4 * i + 1] = v.y; w[4 * i + 2] = v.z; w[4 * i + 3] = v.w;
    }
    auto sums = [&](int lo, int hi) {
#pragma unroll
        for (int i = lo; i < hi; i++) { const float x = (i & 1) ? bf_hi(w[i >> 1]) : bf_lo(w[i >> 1]); s = i > 3 ? s + x : x; S[i] = s; }
    };
    auto put = [&](int off, int b, int o0, int o1, int o2) {
        auto v = [&](int i) { i += 16 * b; return pack_bf16(S[o0 + i] - S[o1 + i], S[o1 + i] - S[o2 + i]); };
#pragma unroll
        for (int i = 0; i < 8; i += 2) sts128((i & 4 ? d1 : d0) + 4 * off + 64 * b + 8 * (i & 2), v(i), v(i + 8), v(i + 1), v(i + 9));
    };
    S[2] = 0.f;
    sums(3, 26); put(VC_OFF - 16, 0, 10, 5, 2);
    if (k == 12) return;
    sums(26, 42); put(VC_OFF - 16, 1, 10, 5, 2);
    if (k < 8) { put(VE_BASE, 0, 19, 12, 3); sums(42, 51); put(VE_BASE, 1, 19, 12, 3); }
}

template <class F>
__device__ __forceinline__ void kgen(const uint32_t (&q)[8], uint32_t sb, int half, uint32_t stage, uint32_t pstage, int barid, int lane, uint32_t (&w)[12], F shadow) {
    const int t = lane & 3, mi = lane >> 3, r8 = lane & 7;
    {
        const uint32_t pAr = q[0], pAi = q[1], pBr = q[2], pBi = q[3], pCr = q[4], pCi = q[5], pDt = q[6], pD = q[7];
        const uint32_t wb = fresh(stage + lane * 16), za = fresh(stage + 5120 + ((lane >> 1) & 3) * 16 + mi * 4 + (lane & 1) * 2), zr = fresh(stage + 5120 + t * 16);
        const uint32_t oA = fresh(stage + (mi & 1) * 1024 + (mi >> 1) * 512 + r8 * 16), oB = fresh(stage + 2048 + mi * 512 + r8 * 16), oC = fresh(stage + 4096 + (mi & 1) * 512 + (mi >> 1) * 128 + r8 * 16);
        float acc[6][4];
#pragma unroll
        for (int a = 0; a < 6; a++) { acc[a][0] = acc[a][1] = acc[a][2] = acc[a][3] = 0.f; asm volatile("" : "+f"(acc[a][0]), "+f"(acc[a][1]), "+f"(acc[a][2]), "+f"(acc[a][3])); }
        shadow();
        sts32(zr, clock32());
        const float dt = rbf(__expf(bf_lo(pDt)));
        float ar = dt * bf_lo(pAr), ai = dt * bf_lo(pAi), ar1 = dt * bf_hi(pAr), ai1 = dt * bf_hi(pAi);
        float wr, wi, wr1, wi1;
        { const float br = dt * bf_lo(pBr), bi = dt * bf_lo(pBi), cr = bf_lo(pCr), ci = bf_lo(pCi); wr = cr * br - ci * bi; wi = cr * bi + ci * br; }
        { const float br = dt * bf_hi(pBr), bi = dt * bf_hi(pBi), cr = bf_hi(pCr), ci = bf_hi(pCi); wr1 = cr * br - ci * bi; wi1 = cr * bi + ci * br; }
        const uint32_t ex = max(__reduce_max_sync(0xffffffffu, __float_as_uint(fmaxf(fmaxf(fabsf(wr), fabsf(wi)), fmaxf(fabsf(wr1), fabsf(wi1))))) >> 23, 14u);
        const float scl = __uint_as_float((267u - ex) << 23);
        uint32_t W = pack_f16(wr * scl, wi * -scl);
        const uint32_t W1 = pack_f16(wr1 * scl, wi1 * -scl);
        if (threadIdx.x < 32) TSTAMP(20);

#pragma unroll 1
        for (int r = 0; r < 2; r++) {
            const cplx z1 = cexpk(ar, ai, 1.f), z64 = cexpk(ar, ai, 64.f);
            const cplx z2 = csq(z1), z4 = csq(z2), z8 = csq(z4), z16 = csq(z8), z32 = csq(z16);
            const cplx z128 = csq(z64), z256 = csq(z128), z512 = csq(z256);
            auto put = [&](int grp, h2c a, h2c b, h2c c, h2c d) { sts128(wb + grp * 1024, a.re, b.re, c.re, d.re); sts128(wb + grp * 1024 + 512, a.im, b.im, c.im, d.im); };
            {
                const uint32_t s4 = pack_f16(z4.re, z4.im), s256 = pack_f16(z256.re, z256.im), s512 = pack_f16(z512.re, z512.im);
                auto mix = [](h2c a, h2c b, uint32_t sel) { return h2c{__byte_perm(a.re, b.re, sel), __byte_perm(a.im, b.im, sel)}; };
                const h2c c10 = cmul_vc(h2c{pack_f16(z1.re, 1.f), pack_f16(z1.im, 0.f)}, W), c32 = cmul_sc(c10, pack_f16(z2.re, z2.im)), c54 = cmul_sc(c10, s4);
                put(2, c10, c32, c54, cmul_sc(c32, s4));
                const h2c d20 = cmul_sc(mix(c32, c10, 0x7632), s256), e04 = cmul_sc(mix(c10, c54, 0x7632), s512), f04 = cmul_sc(e04, s256);
                put(3, d20, cmul_sc(d20, s4), e04, f04);
                const h2c ef = mix(e04, f04, 0x5410), gh = cmul_sc(ef, s512), g8 = cmul_sc(gh, pack_f16(z8.re, z8.im));
                put(4, g8, cmul_sc(g8, s512), gh, ef);
            }
            {
                const uint32_t s32 = pack_f16(z32.re, z32.im), s64 = pack_f16(z64.re, z64.im), s128 = pack_f16(z128.re, z128.im);
                const h2c p0 = {pack_f16(1.f, z8.re), pack_f16(0.f, z8.im)}, p1 = cmul_s(p0, pack_f16(z16.re, z16.im)), p2 = cmul_s(p0, s32), p3 = cmul_s(p1, s32);
                put(0, p0, p1, p2, p3);
                put(1, cmul_s(p0, s64), cmul_s(p1, s64), cmul_s(p2, s64), cmul_s(p3, s64));
                sts16(za, s128); sts16(za + 64, s128 >> 16);
            }
            __syncwarp();
            {
                const uint32_t aA = fresh(oA), aB = fresh(oB), aC = fresh(oC), aZ = fresh(zr);
                const uint4 zc = lds128(aZ), zd = lds128(aZ + 64);
                const uint32_t zcs[4] = {zc.x, zc.y, zc.z, zc.w}, zds[4] = {zd.x, zd.y, zd.z, zd.w};
                uint32_t c[4];
#pragma unroll
                for (int k = 0; k < 4; k++) {
                    uint32_t a[4], b[4];
                    ldsm4t(a, aA + 128 * k); ldsm4t(b, aB + 128 * k);
                    if (!(k & 1)) ldsm4t(c, aC + 128 * k);
                    const h2c x = cmul_cd(h2c{a[0], a[2]}, *(const __half2*)&zcs[k], *(const __half2*)&zds[k]), y = cmul_cd(h2c{a[1], a[3]}, *(const __half2*)&zcs[k], *(const __half2*)&zds[k]);
                    mma_h(acc[0], a[0], a[1], a[2], a[3], b[0], b[1]);
                    mma_h(acc[1], a[0], a[1], a[2], a[3], b[2], b[3]);
                    mma_h(acc[2], a[0], a[1], a[2], a[3], c[2 * (k & 1)], c[2 * (k & 1) + 1]);
                    mma_h(acc[3], x.re, y.re, x.im, y.im, b[0], b[1]);
                    mma_h(acc[4], x.re, y.re, x.im, y.im, b[2], b[3]);
                    mma_h(acc[5], x.re, y.re, x.im, y.im, c[2 * (k & 1)], c[2 * (k & 1) + 1]);
                }
                asm volatile("" :: "f"(acc[0][0]), "f"(acc[1][0]), "f"(acc[2][0]), "f"(acc[3][0]), "f"(acc[4][0]), "f"(acc[5][0]) : "memory");
            }
            __syncwarp();
            ar = ar1; ai = ai1; W = W1;
        }
        if (threadIdx.x < 32) TSTAMP(21);
        const float i0 = __uint_as_float((ex + 243u) << 23);
        if (half) {
#pragma unroll
            for (int a = 0; a < 6; a++) { acc[a][0] *= i0; acc[a][1] *= i0; acc[a][2] *= i0; acc[a][3] *= i0; }
            if (lane == 0) acc[0][1] -= bf_lo(pD);
#pragma unroll
            for (int a = 0; a < 6; a++) sts128(wb + a * 512, __float_as_uint(acc[a][0]), __float_as_uint(acc[a][1]), __float_as_uint(acc[a][2]), __float_as_uint(acc[a][3]));
            bar_arrive(barid, 64);
        } else {
            bar_sync(barid, 64);
            const uint32_t src = fresh(pstage);
#pragma unroll
            for (int a = 0; a < 6; a++) {
                const uint4 y = lds128(src + lane * 16 + a * 512);
                auto sum = [&](uint32_t x, float c) { return fmaf(c, i0, __uint_as_float(x)); };
                w[4 * (a % 3) + 2 * (a / 3)] = pack_bf16(sum(y.x, acc[a][0]), sum(y.y, acc[a][1]));
                w[4 * (a % 3) + 2 * (a / 3) + 1] = pack_bf16(sum(y.z, acc[a][2]), sum(y.w, acc[a][3]));
            }
            const uint32_t x0 = __shfl_up_sync(0xffffffffu, w[10], 2), x1 = __shfl_up_sync(0xffffffffu, w[11], 2);
            w[10] = w[8];
            if (t >= 2) { w[8] = x0; w[9] = x1; }
        }
    }
}

enum { BC_AUX = 0, BC_U = 5  , BC_Y = 13   };

__device__ __forceinline__ void fetch_gates(const Params& p, int i, int lane, unsigned epoch, uint32_t dst) {
    const uint32_t par = (epoch & 1) ? 0x80008000u : 0u;
    uint4 v;
#pragma unroll 1
    for (int it = 0;; it++) {
        v = ld_rlx128(p.s->gate + 256 * i + 8 * lane);
        v.x ^= par; v.y ^= par; v.z ^= par; v.w ^= par;
        if (__all_sync(0xffffffffu, (v.x & v.y & v.z & v.w & 0x80008000u) == 0x80008000u)) break;
        if (it > (1 << 20)) give_up();
    }
    sts128(dst, v.x, v.y, v.z, v.w);
}
__device__ __forceinline__ void store_rows(const CUtensorMap* m, uint32_t src, int col, int row) {
    asm volatile("cp.async.bulk.tensor.5d.global.shared::cta.bulk_group [%0, {%2, %3, %3, %3, %4}], [%1];" :: "l"(m), "r"(src), "r"(col), "r"(0), "r"(row) : "memory");
}

__device__ __forceinline__ void store_or_add(void* o, const uint32_t (&y)[4], uint32_t add) {
    asm volatile("{ .reg .pred p; setp.ne.u32 p, %5, 0; @!p st.global.v4.u32 [%0], {%1,%2,%3,%4}; @p red.relaxed.gpu.global.add.noftz.v4.bf16x2 [%0], {%1,%2,%3,%4}; }"
                 :: "l"(o), "r"(y[0]), "r"(y[1]), "r"(y[2]), "r"(y[3]), "r"(add) : "memory");
}

__device__ __forceinline__ void conv_aux(const Params& p, const CUtensorMap* mU, uint32_t sb, int aw, int lane, int bid, unsigned epoch) {
    const int g = lane >> 2, t = lane & 3, mi = lane >> 3, r8 = lane & 7;
    const int rank = bid & 1, slab = bid >> 1;
    const uint32_t bar_y = sb + SC_MISC, bar_u = bar_y  , bar_v = bar_y + 8, bar_box = bar_y + 64 + 8 * aw, s_bm = bar_y + 128;
    if (elect()) {
        mbar_init(bar_box, 1); mbar_fence();
        mbar_expect(bar_box, 4096);
        tma4d(sb + SC_RT + 4096 * aw, mU, 16 * slab, 0, 0, 16 * rank + 2 * aw, bar_box);
        mbar_init(bar_y + 8 * aw, aw == 1 ? 8 : 1);
        if (aw == 1) mbar_init(bar_y + 384, 1);
        mbar_fence();
        if (aw != 1) mbar_expect(bar_y + 8 * aw, aw ? 4096 : 16384);
    }
    __syncwarp();
    asm volatile("barrier.cluster.arrive.relaxed.aligned;" ::: "memory");
    asm volatile("setmaxnreg.dec.sync.aligned.u32 88;");
    sts128(sb + (lane < 16 ? SC_UT + aw * UT_STRIDE + mi * (UT_HALF - 128) : SC_V - 256 + aw * V_STRIDE) + lane * 16, 0, 0, 0, 0);
    if (lane < 16) sts128(s_bm + lane * 16, 0, 0, 0, 0);
    {
        const uint32_t dst = sb + SC_UT + g * UT_STRIDE + swz((8 + 64 * rank + 8 * aw + t) * 16, g);
        const uint32_t rdst = mapa(dst, rank ^ 1), rbar = mapa(bar_u, rank ^ 1);
        asm volatile("barrier.cluster.wait.acquire.aligned;" ::: "memory");
        mbar_wait(bar_box);
        if (aw == 0) TSTAMP(1);
        const uint32_t src = fresh(sb + SC_RT) + aw * 4096 + (8 * mi + 4 * (r8 & 1) + (r8 >> 1)) * 32 + ((rank ^ (r8 & 1)) << 4);
        uint32_t x[8][4];
#pragma unroll
        for (int i = 0; i < 4; i++) { ldsm4t(x[i], src + 1024 * i); ldsm4t(x[4 + i], (src ^ 16) + 1024 * i); }
        asm volatile("" :: "r"(x[0][0]), "r"(x[1][0]), "r"(x[2][0]), "r"(x[3][0]) : "memory");
#pragma unroll
        for (int i = 0; i < 4; i++) st_async128((rdst ^ 32 * (i & 2)) + (i & 1) * UT_HALF, x[4 + i][0], x[4 + i][1], x[4 + i][2], x[4 + i][3], rbar);
#pragma unroll
        for (int i = 0; i < 4; i++) sts128((dst ^ 32 * (i & 2)) + (i & 1) * UT_HALF, x[i][0], x[i][1], x[i][2], x[i][3]);
    }
    bar_sync(BC_AUX, 256);
    mbar_wait_cluster(bar_u);
    if (aw == 0) TSTAMP(2);
    if (aw == 6 && elect()) mbar_arrive(bar_y + 384);
    if (aw < 4) bar_sync(BC_U + aw, 64);
    if (aw == 0) TSTAMP(3);
    {
        const uint32_t ws = fresh(sb + SC_UT) + r8 * UT_STRIDE, wd = sb + SC_V + r8 * V_STRIDE;
#pragma unroll 1
        for (int k = aw; k < 13; k += 8) {
            const int a = 8 * k + (k < 12 ? g & 6 : 0);
            const uint32_t d = wd + 64 * a, sw = 16 * (a & 2);
            window_task(ws + swz(16 * a + 96, r8), ws + swz(16 * a + 128, r8), d + sw, d + (sw ^ 32), k);
            if ((k & 12) == 4) bar_arrive(BC_U + k - 4, 64);
        }
    }
    if (aw == 0) TSTAMP(9);
    {
        if (aw >= 2) fetch_gates(p, aw, lane, epoch, sb + SC_GT + (lane & 1) * GT_HALF + (8 + 16 * aw + (lane >> 1)) * 16);
        __syncwarp();
        if (elect()) { mbar_arrive(bar_v); prefetch_map(mU + 4); }
        next_epoch(p, epoch);
        if (aw == 0) TSTAMP(4);
        if (aw == 7) {
            const int row = key_row(wait_sel(p, slab >> 1, r8, key_tag(epoch)));
            if (lane < 8) asm volatile("red.shared.or.b32 [%0], %1;" :: "r"(s_bm + (row >> 5) * 4), "r"(1u << (row & 31)) : "memory");
            TSTAMP(10);
        }
        bar_sync(BC_AUX, 256);
        const uint32_t src = sb + SC_RT + ((r8 >> 1) & 1) * Y_RS + (2 * mi + (r8 & 1)) * Y_CS + (2 * aw + (r8 >> 2)) * 16;
        const int rb = 64 * (aw & 4) + 32 * (aw & 1) + ((aw >> 1) & 1) + 2 * rank, row0 = rb + 128 * (g >> 2) + 16 * (t >> 1) + 64 * (g & 1) + 8 * ((g >> 1) & 1);
        __nv_bfloat16* outp = p.out + (size_t)row0 * DM + 16 * slab + 8 * (t & 1);
        const uint32_t stg = sb + SC_KG + 4096 * aw, so = (g & 2) * 256 + (g >> 2) * 128 + r8 * 16;
#pragma unroll 1
        for (int s = 1; s < 4; s++) {
            const uint32_t bm = lds32(fresh(s_bm) + (16 * s + (row0 >> 5)) * 4) >> (row0 & 31);
            const bool routed = __any_sync(0xffffffffu, bm & 0x11u);
            if ((aw & 3) == s) mbar_wait_cluster(bar_y + 16 * s + 2 * (aw & 4));
            bar_sync(BC_Y + (aw >> 2), 128);
            const uint32_t sf = fresh(src) + 512 * s;
            uint32_t y[2][4];
            ldsm4t(y[0], sf); ldsm4t(y[1], sf + 256);
            if (routed) {
#pragma unroll
                for (int k = 0; k < 2; k++) store_or_add(outp + (size_t)(512 * s + 4 * k) * DM, y[k], bm & (1u << (4 * k)));
            } else {
                sts128(stg + so + 1024 * s, y[0][0], y[0][1], y[0][2], y[0][3]); sts128(stg + so + 1024 * s + 256, y[1][0], y[1][1], y[1][2], y[1][3]);
                asm volatile("fence.proxy.async.shared::cta;" ::: "memory");
                __syncwarp();
                if (elect()) store_rows(mU + 4, stg + 1024 * s, 16 * slab, 512 * s + rb);
            }
            if (aw == 4) TSTAMP(16 + s);
            if (aw == 0) TSTAMP(16);
        }
        if (elect()) { asm volatile("cp.async.bulk.commit_group;" ::: "memory"); asm volatile("cp.async.bulk.wait_group.read 0;" ::: "memory"); }
        if (aw == 4) TFLUSH();
    }
}

__device__ __forceinline__ uint32_t k_tag(unsigned epoch) { return epoch << 16 | 0x80000000u; }
__device__ __forceinline__ void publish_k(uint4* kp, const uint32_t (&w)[12], unsigned epoch, uint64_t (&v)[6]) {
#pragma unroll
    for (int i = 0; i < 3; i++) {
        v[2 * i] = w[3 * i] | (uint64_t)w[3 * i + 1] << 32; v[2 * i + 1] = w[3 * i + 2] | (uint64_t)__byte_perm(w[9 + (i >> 1)], k_tag(epoch), i == 1 ? 0x7632 : 0x7610) << 32;
        asm volatile("st.relaxed.gpu.global.v2.u64 [%0], {%1,%2};" :: "l"(kp + 32 * i), "l"(v[2 * i]), "l"(v[2 * i + 1]));
    }
}
template <bool FULL>
__device__ __forceinline__ void k_tables(uint32_t kt, int lane, const uint32_t (&w)[12]) {
    const int g = lane >> 2, t = lane & 3, mi = lane >> 3, r8 = lane & 7;
    uint32_t x3 = w[7], re[4], rx[4];
#pragma unroll
    for (int i = 0; i < 4; i++) {
        re[i] = __shfl_sync(0xffffffffu, w[i], lane + 31);
        rx[i] = __shfl_sync(0xffffffffu, w[4 + i], lane + (i == 0 && lane == 29 ? 5 : 1 + 2 * t));
    }
    if (FULL) {
        asm volatile("stmatrix.sync.aligned.m8n8.x2.trans.shared.b16 [%0], {%1,%2};" :: "r"(kt + (KT_D + 7) * 4 + 64 * t + 16 * (mi & 1) + 8 * (r8 & 4)), "r"(w[8]), "r"(w[9]) : "memory");
        if (lane == 2) {
            sts32(kt + (KT_C + 78) * 4, w[10] & 0xffffu);
            sts128(kt + (KT_T + 2) * 4, 0, w[10] & 0xffffu, __byte_perm(w[10], 0, 0x1010), w[10] << 16);
        }
        if (lane == 29) x3 = bsub2(x3, rx[0] & 0xffffu);
    }
#pragma unroll
    for (int i = 0; i < 4; i++) {
        sts64(kt + (16 + 64 * i) * 4 + 8 * lane, __byte_perm(w[i], lane ? re[i] : i ? re[i - 1] : 0, 0x5432), w[i]);
        const uint32_t x = i < 3 ? w[4 + i] : x3, aa = __byte_perm(x, 0, 0x3232);
        if (t < 2) sts128(kt + (272 + 64 * i + 8 * g + 4 * t) * 4, i == 0 && lane == 0 ? __byte_perm(x, re[3], 0x5432) : aa, aa, x,
                          __byte_perm(lane != 29 ? rx[i] : i < 3 ? rx[(i + 1) & 3] : FULL ? 0 : rx[0] << 16, x, 0x5432));
        else if (FULL) sts32(kt + (KT_C - 50 + 8 * i + 32 * t + g) * 4, x);
    }
}

__device__ __forceinline__ void conv_main(const Params& p, uint32_t sb, int warp, int lane0, int bid, unsigned epoch, uint32_t (&w)[12]) {
    asm volatile("setmaxnreg.inc.sync.aligned.u32 168;");
    const int lane = __shfl_sync(0xffffffffu, lane0, lane0);
    const int g = lane >> 2, t = lane & 3, mi = lane >> 3, r8 = lane & 7;
    const int rank = bid & 1;
    const uint32_t bar_y = sb + SC_MISC, bar_v = bar_y + 8;
    next_epoch(p, epoch);
    asm volatile("barrier.cluster.wait.acquire.aligned;" ::: "memory");
    if (warp >= 4) {
        mbar_wait(bar_y + 384);
        if (KPOLL) until(clock32(), KPOLL);
        const uint4* src = p.s->kp + (8 * bid + warp) * 96 + lane0;
#pragma unroll 1
        for (int it = 0;; it++) {
            uint32_t bad = 0, e[3];
#pragma unroll
            for (int i = 0; i < 3; i++) { const uint4 v = ld_rlx128(src + 32 * i); w[3 * i] = v.x; w[3 * i + 1] = v.y; w[3 * i + 2] = v.z; e[i] = v.w; bad |= v.w ^ k_tag(epoch); }
            w[9] = __byte_perm(e[0], e[1], 0x5410); w[10] = e[2];
            const bool ok = __all_sync(0xffffffffu, bad < 65536);
            if (ok) break;
            if (it > (1 << 20)) give_up();
        }
    }
    if ((warp & 3) == 0) TSTAMP(5 + (warp >> 2));
    k_tables<true>(sb + SC_KT + warp * KT_BYTES, lane0, w);
    mbar_wait(bar_y + 384);
    __syncwarp();
    if ((warp & 3) == 0) TSTAMP(7 + (warp >> 2));
    {
        const uint32_t ut = fresh(sb + SC_UT) + warp * UT_STRIDE, kt = fresh(sb + SC_KT) + warp * KT_BYTES;
        auto dup = [&](uint32_t v) { return v ^ p.zero; };
        auto frag = [&](uint32_t (&a)[4], uint32_t x) { a[0] = lds32(x); a[1] = lds32(x + 32); a[2] = lds32(x - 32); a[3] = dup(a[0]); };
        const uint32_t kb = kt + (16 + g - 2 * t) * 4;
        float acc[16][4];
        {
            float y[12][4], M[6][4];
#pragma unroll
            for (int i = 0; i < 12; i++) { y[i][0] = y[i][1] = y[i][2] = y[i][3] = 0.f; M[i >> 1][0] = M[i >> 1][1] = M[i >> 1][2] = M[i >> 1][3] = 0.f; }
            uint32_t U[10][4], a1[4], ad[4], R = (mi & 1) * UT_HALF + (8 + (r8 >> 1) + 48 * (r8 & 1)) * 16 + 64 * (mi >> 1);
            auto places = [&] { ad[0] = swz(R, warp); ad[1] = swz(R + 128, warp); ad[2] = ad[0] ^ 64; ad[3] = ad[1] ^ 64; };
            auto ldu = [&](int k) { ldsm4(U[k], ut + ad[k & 3] + 256 * (k >> 1)); };
            places();
            frag(a1, kb + 2048);
#pragma unroll
            for (int k = 0; k < 7; k++) ldu(k);
#pragma unroll
            for (int i = 0; i < 12; i++) mma_bf(y[i], a1[0], a1[1], a1[2], a1[3], U[i >> 1][2 * (i & 1)], U[i >> 1][2 * (i & 1) + 1]);
            frag(a1, kb + 1792);
            __syncwarp();
#pragma unroll 1
            for (uint32_t ko = 0; ko != 256;) {
                ko = fresh(ko);
                const uint32_t kp = kb + ko;
                ko += 64;
                uint32_t se[10][2], so[10][2], ue[10][2];
                auto sums = [&](int k) {
#pragma unroll
                    for (int e = 0; e < 2; e++) { ue[k][e] = U[k][e]; se[k][e] = badd2(U[k][e], U[k - 1][2 + e]); so[k][e] = badd2(U[k][e], U[k][2 + e]); }
                };
#pragma unroll
                for (int k = 1; k < 6; k++) sums(k);
#pragma unroll
                for (int m = 3; m >= 0; m--) {
                    uint32_t a0[4];
                    frag(a0, kp + 512 * m);
                    sums(9 - m);
                    if (m) ldu(10 - m); else { R -= 16; places(); }
#pragma unroll
                    for (int i = 0; i < 6; i++) mma_bf(y[2 * i], a1[0], a1[1], a1[2], a1[3], se[i - m + 4][0], se[i - m + 4][1]);
#pragma unroll
                    for (int e = 0; e < 4; e++) a1[e] = bsub2(a0[e], a1[e]);
#pragma unroll
                    for (int i = 0; i < 6; i++) { mma_bf(M[i], a1[0], a1[1], a1[2], a1[3], ue[i - m + 4][0], ue[i - m + 4][1]); if (!m) ldu(i); }
                    frag(a1, m ? kp + 512 * m - 256 : kp + 1792 + 64);
                    if (!m) ldu(6);
#pragma unroll
                    for (int i = 0; i < 6; i++) mma_bf(y[2 * i + 1], a0[0], a0[1], a0[2], a0[3], so[i - m + 4][0], so[i - m + 4][1]);
                }
            }
#pragma unroll
            for (int i = 0; i < 6; i++)
#pragma unroll
                for (int c = 0; c < 4; c++) { acc[4 + i + 6 * (c & 1)][c & 2] = y[2 * i][c] + M[i][c]; acc[4 + i + 6 * (c & 1)][c | 1] = y[2 * i + 1][c] - M[i][c]; }
        }
        const uint32_t lo = (8 + col(r8)) * 16 + (mi >> 1) * 128, ua = fresh(ut) + (mi & 1) * UT_HALF, u1[2] = {ua + swz(lo, warp), ua + (swz(lo, warp) ^ 64)};
        {
            uint32_t e[4];
            frag(e, kb + (KT_T - 16) * 4);
            const uint32_t f0 = dup(e[1]), f1 = lds32(kb + KT_T * 4), uo = fresh(ut) + UT_HALF + swz((7 + 8 * mi + col(r8)) * 16, warp);
#pragma unroll
            for (int i = 0; i < 4; i++) {
                uint32_t b[4];
                if (i < 2) {
                    ldsm4(b, uo + 512 * i);
#pragma unroll
                    for (int k = 0; k < 4; k++) mma_bf8(acc[8 + 4 * i + k], f0, f1, b[k]);
                }
                ldsm4(b, u1[i & 1] + 256 * i);
                mma_bf(acc[2 * i + 8], e[0], e[1], e[2], e[3], b[0], b[1]); mma_bf(acc[2 * i + 9], e[0], e[1], e[2], e[3], b[2], b[3]);
            }
        }
        if ((warp & 3) == 0) TSTAMP(11 + (warp >> 2));
        mbar_wait(bar_v);
        const uint32_t vt = fresh(sb + SC_V) + warp * V_STRIDE;
        const uint32_t g1 = fresh(sb + SC_GT) + (mi & 1) * GT_HALF + lo;
        const uint32_t ydst = mapa(sb + SC_RT + rank * Y_RS + warp * Y_CS + (lane & 23) * 16, mi & 1), ybr = mapa(bar_y, mi & 1);
        uint32_t ug[2][2][4];
        auto ld_ug = [&](int i) { ldsm4t(ug[i & 1][0], u1[i & 1] + 256 * i); ldsm4t(ug[i & 1][1], g1 + 256 * i); };
        auto ship = [&](int i) {
            const uint32_t (&u)[4] = ug[i & 1][0], (&gg)[4] = ug[i & 1][1];
            const uint32_t y0 = gmix(gg[0], acc[2 * i][0], acc[2 * i][1], u[0]), y1 = gmix(gg[1], acc[2 * i][2], acc[2 * i][3], u[1]);
            const uint32_t y2 = gmix(gg[2], acc[2 * i + 1][0], acc[2 * i + 1][1], u[2]), y3 = gmix(gg[3], acc[2 * i + 1][2], acc[2 * i + 1][3], u[3]);
            st_async128(ydst + 512 * (i >> 1) + 128 * (i & 1), y0, y1, y2, y3, ybr + 8 * i);
        };
        const uint32_t VD = vt + (VC_OFF - 400 - 16 * t) * 4 + (8 * g ^ 16 * (-t & 2)), VD2 = vt + (VC_OFF - 415 - 16 * t) * 4 + (8 * g ^ 16 * (~t & 2));
        uint2 bd[10];
        uint32_t x[2][4][4];
        auto ld4 = [&](uint32_t (&v)[4], int dl) { const uint2 w = lds64(VD + 256 * dl); v[0] = w.x; v[1] = w.y; v[2] = lds32(VD2 + 256 * dl); v[3] = dup(w.x); };
        auto mm4 = [&](const uint32_t (&v)[4], int dl) {
#pragma unroll
            for (int s = dl & 1; s < 10; s += 2) if ((dl + s) / 2 >= 4 && (dl + s) / 2 < 16) mma_bf(acc[(dl + s) / 2], v[0], v[1], v[2], v[3], bd[s].x, bd[s].y);
        };
        const uint32_t KE = kt + (KT_D + col(g) + t) * 4, VE = vt + (VE_BASE - 912 - 16 * t) * 4 + (8 * g ^ 16 * (~t & 2));
        uint32_t b0[8], b1[8];
        auto ld8 = [&](uint32_t (&v)[4], int dl) { const uint2 w = lds64(VE + 512 * dl), z = lds64(VE + 512 * dl - 256); v[0] = w.x; v[1] = w.y; v[2] = z.x; v[3] = z.y; };
        auto mm8 = [&](const uint32_t (&v)[4], int dl, int lo, int hi) {
#pragma unroll
            for (int s = 0; s < 8; s++) if (dl + s >= lo && dl + s < hi) mma_bf(acc[dl + s], v[0], v[1], v[2], v[3], b0[s], b1[s]);
        };
        ld4(x[0][0], 6);
#pragma unroll
        for (int s = 0; s < 10; s++) bd[s] = lds64(kt + (KT_C + 2 * col(g) + 2 * t + 8 * s) * 4);
        mm4(x[0][0], 6);
        uint32_t e[8][4];
#pragma unroll
        for (int k = 1; k < 6; k++) {
#pragma unroll
            for (int j = 0; j < 4; j++) ld4(x[k & 1][j], 4 * k + 3 + j);
            ld_ug(k + 1);
            if (k == 3) {
#pragma unroll
                for (int s = 0; s < 8; s++) { b0[s] = lds32(KE + 32 * s); b1[s] = lds32(KE + 32 * s + 16); }
            }
            if (k > 1) ship(k);
#pragma unroll
            for (int j = 0; j < 4; j++) {
                mm4(x[k & 1][j], 4 * k + 3 + j);
                if (k == 3) { ld8(e[j], 8 + j); mm8(e[j], 8 + j, 8, 14); }
                if (k == 5 && j < 2) { ld8(e[4 + j], 12 + j); mm8(e[4 + j], 12 + j, 12, 14); }
            }
        }
        ld_ug(7);
        {
            float (&q0)[4] = acc[0], (&q1)[4] = acc[1];
#pragma unroll
            for (int c = 0; c < 4; c++) q0[c] = q1[c] = 0.f;
            auto m8 = [&](float (&c)[4], int T, int j) { mma_bf(c, e[j][0], e[j][1], e[j][2], e[j][3], b0[T - 8 - j], b1[T - 8 - j]); };
            auto m4 = [&](float (&c)[4], int T, int j) { mma_bf(c, x[0][j][0], x[0][j][1], x[0][j][2], x[0][j][3], bd[2 * T - 27 - j].x, bd[2 * T - 27 - j].y); };
            ship(6);
            ld8(e[6], 14); ld8(e[7], 15);
#pragma unroll
            for (int j = 0; j < 4; j++) ld4(x[0][j], 27 + j);
            m8(q1, 15, 0); m8(q0, 14, 0); m8(q1, 15, 1);
            m8(acc[15], 15, 6); m4(q1, 15, 0); m8(acc[14], 14, 6); m4(q0, 14, 0);
            m8(acc[15], 15, 4); m8(q1, 15, 2); m4(acc[14], 14, 1); m8(q0, 14, 1);
            m4(acc[15], 15, 1); m4(q1, 15, 2); m8(acc[14], 14, 4); m8(q0, 14, 2);
            m8(acc[15], 15, 5); m8(q1, 15, 3); m8(acc[14], 14, 5); m8(q0, 14, 3);
            m4(acc[15], 15, 3); m8(q1, 15, 7);
#pragma unroll
            for (int c = 0; c < 4; c++) { acc[14][c] += q0[c]; acc[15][c] += q1[c]; }
            ship(7);
        }
        if ((warp & 3) == 0) TSTAMP(14 + (warp >> 2)); else TSTAMP(21 + warp);
    }
}

constexpr int SF_WD = 73728;
constexpr int SF_RED = 49152;
constexpr int MU_STRIDE = 1168  , SM_RAW = 98304, SM_UT = SM_RAW + 16384, SM_G = SM_UT + 21504, SM_Y = 196608, SM_FT = SM_Y + 17024, SM_KT = 138880, SM_KW = SM_G - 49152;
constexpr int SF_XS = 221184;
constexpr int SF_MISC = SF_XS + 8 * 1168;
constexpr int SF_KG = SF_MISC - 10 * KG_STAGE;
constexpr int SF_WR = SF_KG - 2304;
constexpr int FB_X = 64, FB_KDONE = 72, FB_KEYS = 80, FB_FREE = 88  , FB_W = 104, FB_D = FB_W + 72, FB_MU = FB_D + 96, FB_FAR = FB_MU - 16, FB_MG = FB_MU + 8, FB_MT = FB_MU + 16  , FS_PART = 512, FS_TOK = 896, FS_BM = 1024;
enum { BAR_R = 7, BAR_GU = 8, BAR_RED = 9, BAR_R2 = 10, BAR_G = 12  , BAR_M = 15 };
static_assert(SF_KG % 128 == 0 && NPRE <= 8 && SM_KT + 4 * 2112 <= 147456 && SM_G + MU_STRIDE <= SF_WR - 4 * 9216 && SM_KW + 6 * 2112 >= SM_RAW && SM_KW + 12 * 2112 <= SM_UT, "layout");

__device__ __forceinline__ constexpr int box_no(int i) { return (0x987610ba5432ull >> (4 * i)) & 15; }
__device__ __forceinline__ int role(int b) { b -= NCONV; return b < NX ? b : 18 + (b >> 1) + 12 * (b & 1); }
__device__ __forceinline__ int mini_ch0(int f) { return 48 * f - (f < NW ? 1696 : 2304); }

__device__ __forceinline__ void ffn_front(const Params& p, const CUtensorMap* maps, uint32_t sb, int warp, int lane, int f, unsigned epoch) {
    const unsigned t0 = clock32();
    const int g = lane >> 2, t = lane & 3, mi = lane >> 3, r8 = lane & 7;
    const bool isx = f < NX;
    const int nrw = f < 52 ? 4 : 6, r0 = f < 52 ? 32 * f : 48 * f - 832;
    const int rw = warp < 12 ? 13 - warp : warp ^ (warp < 14 ? 10 : 15);
    const uint32_t bar_row = sb + SF_MISC  , bar_x = bar_row + FB_X;
    const uint32_t s_part = bar_row + FS_PART  , s_tok = bar_row + FS_TOK  ;
    const uint32_t rows = sb + SF_WR - 9216 * (rw + 1) - (rw & 4) * ((SF_WR - 6 * 9216) / 4);
    {
#pragma unroll 1
        for (int i = warp < 10 ? 30 : warp - 10; i < 30; i += 6) if (elect()) mbar_init(bar_x + 8 * i, i == 1 ? 4 + (f < NW) : i < 27 ? 1 : i == 27 ? 2 : 8);
        const uint32_t bytes = rw < 6 ? 9216 : 1152, dst = rw < 6 ? rows : sb + SF_WR + (rw & 1) * 1152;
        const __nv_bfloat16* src = rw < 6 ? p.u + (size_t)(r0 + 8 * rw) * DM : (rw & 1) ? p.gatew : p.wr;
        if (elect()) { mbar_init(bar_row + 8 * rw, 1); mbar_fence(); mbar_expect(bar_row + 8 * rw, bytes); }
        if (warp == 13) { sts32(s_part + 64 + lane * 4, 0); sts32(bar_row + FS_BM + lane * 4, 0); }
        bar_sync(0, NTHR);
        if (!isx) asm volatile("barrier.cluster.arrive.relaxed.aligned;" ::: "memory");
        if (rw < nrw) until(t0, RDELAY);
        if (rw < nrw || rw >= 6) { if (elect()) bulk_g2s(dst, src, bytes, bar_row + 8 * rw); }
    }
    uint4* const kdst = p.s->keys + (lane >> 1) * 128 + 2 * f + (lane & 1);
    if (warp == 15) TSTAMP(1);

    if (warp == 12) {
        if (lane < 22) mbar_expect(bar_row + FB_W + 8 * lane, lane < 9 ? 24576 : isx ? 12288 : lane < 20 ? 2048 : 16384);
        if (elect()) { prefetch_map(maps + 1); prefetch_map(maps + 2); prefetch_map(maps + (isx ? 3 : 5)); }
        unsigned tb = t0 + WDELAY;
        auto pieces = [&](int n, int end, uint32_t dst) {
#pragma unroll 1
            for (; n < end; n++, dst += 12288) {
                until(tb, 0); tb += WGAP;
                if (elect()) tma3d(dst, maps + 1 + (n & 1), 0, 64 * (n >> 1), 3 * f, bar_row + FB_W + 8 * (n >> 1));
            }
        };
        if (!isx) {
#pragma unroll 1
            for (int k = 0; k <= (f >= NW); k++) { until(t0, MDELAY + k * MGAP); if (elect()) tma4d(sb + SM_RAW - 49152 * k, maps + 5, mini_ch0(f) + 16 * k, 0, 0, 0, bar_row + FB_MU - 8 * k); }
            if (f >= NW) return;
        }
#pragma unroll 1
        for (int i = 0; i < 4; i++) {
            if (i == 1) { mbar_wait(bar_row + FB_KEYS); mbar_wait(bar_row + FB_KDONE); tb = clock32() + RESUME; }
            if (i == 3) mbar_wait(bar_row + FB_FREE);
            const int n = ((0x0c080000 + NPRE * 256) >> (8 * i)) & 255;
            pieces(n, ((0x120c0800 + NPRE) >> (8 * i)) & 255, sb + 12288 * (((0x000c0000 + NPRE * 256) >> (8 * i)) & 255));
        }
        TSTAMP(12);
        if (isx) {
#pragma unroll 1
            for (int i = 0; i < 12; i++) {
                const int n = box_no(i);
                if (i == 6) mbar_wait(bar_row + FB_FREE + 8);
                until(tb, 0); tb += DGAP;
                if (elect()) tma2d(sb + SF_WD + n * 12288, maps + 3, 32 * (f >> 1), 2304 * (f & 1) + 192 * n, bar_row + FB_D + 8 * n);
            }
            TSTAMP(13);
        }
    } else if (warp == 13) {
        const uint32_t tag = key_tag(epoch), par = (epoch & 1) ? 0u : 0x8000u;
        stg128(kdst, 0, 0, 0, 0);
        if (lane < 8 && isx && !(f & 1)) st_rlx32(&p.s->sel[32 * f + lane], 0);
        bar_sync(BAR_R, 32 * (nrw + 1));
        TSTAMP(3);
        {
            const uint32_t sg = fresh(s_part) + 192 + lane * 4;
            const uint32_t gb = pack_bf16(sigmoidf_(rbf(__uint_as_float(lds32(sg)))), sigmoidf_(rbf(__uint_as_float(lds32(sg + 128))))) | par | (par << 16);
            asm volatile("st.relaxed.gpu.global.u16 [%0], %1;" :: "l"(p.s->gate + r0 + lane), "h"((unsigned short)gb) : "memory");
            if (nrw > 4 && lane < 16) asm volatile("st.relaxed.gpu.global.u16 [%0], %1;" :: "l"(p.s->gate + r0 + 32 + lane), "h"((unsigned short)(gb >> 16)) : "memory");
        }
        bar_sync(BAR_R2, 32 * (nrw + 1));
        {
            const uint4 v = lds128(fresh(s_tok) + (lane & 1) * 16);
            asm volatile("st.relaxed.gpu.global.v4.u32 [%0], {%1,%2,%3,%4};" :: "l"(kdst), "r"(v.x | tag), "r"(v.y | tag), "r"(v.z | tag), "r"(v.w | tag) : "memory");
        }
        TSTAMP(4);
        if (lane == 0) { mbar_arrive(bar_row + FB_KEYS); mbar_expect(bar_x, 8 * 1152); }
        if (f >= NW) return;
        mbar_wait(bar_row + FB_KDONE);
        uint32_t k[16];
        const uint4* src = p.s->keys + (f & 15) * 128 + lane;
#pragma unroll 1
        for (int it = 0;; it++) {
            uint32_t bad = 0;
#pragma unroll
            for (int i = 0; i < 4; i++) {
                const uint4 x = ld_rlx128(src + (i < 3 || lane < 24 ? 32 * i : 64));
                k[i] = x.x; k[4 + i] = x.y; k[8 + i] = x.z; k[12 + i] = x.w;
                bad |= x.x ^ tag;
            }
            const bool ok = __all_sync(0xffffffffu, (bad & 0xf800u) == 0);
            if (ok) break;
            if (it > (1 << 20)) give_up();
        }
        TSTAMP(5);
        uint32_t key = 0, m = __reduce_max_sync(0xffffffffu, max(max(k[0], k[1]), max(k[2], k[3])));
#pragma unroll 2
        for (int r = 0; r < 8; r++) {
            bool pop[4];
#pragma unroll
            for (int i = 0; i < 4; i++) { pop[i] = k[i] == m; k[i] = pop[i] ? k[4 + i] : k[i]; }
            const uint32_t mn = __reduce_max_sync(0xffffffffu, max(max(k[0], k[1]), max(k[2], k[3])));
            if (elect()) bulk_g2s(sb + SF_XS + r * 1168, p.u + (size_t)key_row(m) * DM, 1152, bar_x);
#pragma unroll
            for (int i = 0; i < 4; i++) { k[4 + i] = pop[i] ? k[8 + i] : k[4 + i]; k[8 + i] = pop[i] ? k[12 + i] : k[8 + i]; k[12 + i] = pop[i] ? 0 : k[12 + i]; }
            if (r8 == r) key = m;
            m = mn;
        }
        const int row = key_row(key);
        sts32(s_tok + r8 * 8, row);
        TSTAMP(6);
        if (isx) {
            if (!(f & 1)) {
                __nv_bfloat16* o = p.out + (size_t)row * DM + 16 * f + 8 * mi;
                asm volatile("st.relaxed.gpu.global.v4.u32 [%0], {%1,%1,%1,%1};" :: "l"(o), "r"(0) : "memory");
                if (__any_sync(0xffffffffu, ld_rlx32(o) != 0)) give_up();
                if (lane < 8) st_rlx32(&p.s->sel[32 * f + lane], key);
            } else wait_sel(p, f >> 1, r8, tag);
            uint32_t gb;
#pragma unroll 1
            for (int it = 0;; it++) {
                asm volatile("ld.relaxed.gpu.global.u16 %0, [%1];" : "=r"(gb) : "l"(p.s->gate + row) : "memory");
                gb ^= par;
                if (!(gb & 0x8000u)) break;
                if (it > (1 << 20)) give_up();
            }
            const uint32_t rb = key ^ 0x80000000u, rv = (rb ^ (((int)rb >> 31) & 0x7fff0000u)) & 0xffff0000u;
            sts32(s_tok + r8 * 8 + 4, __float_as_uint(rbf(1.0f - bf_lo(gb)) * rbf(sigmoidf_(__uint_as_float(rv)))));
            __syncwarp();
            TSTAMP(7);
            bar_arrive(BAR_RED, 416);
        }
    } else {
        if (rw < nrw) {
            float c[3][4];
#pragma unroll
            for (int i = 0; i < 3; i++) { c[i][0] = c[i][1] = c[i][2] = c[i][3] = 0.f; }
            mbar_wait(bar_row + 48); mbar_wait(bar_row + 56);
            const uint32_t b = fresh(sb + SF_WR) + (g & 1) * 1152 + (g >> 2) * 64 + t * 16 + (g & 2) * 2;
            uint32_t w[18][2];
#pragma unroll
            for (int kb = 0; kb < 18; kb++) { const uint32_t o = ((kb & 1) ? b ^ 64 : b) + 128 * (kb >> 1); w[kb][0] = lds32(o); w[kb][1] = lds32(o + 8); }
            mbar_wait(bar_row + 8 * rw);
            if (warp == 15) TSTAMP(2);
            const uint32_t a = fresh(rows) + g * 1152 + (g & 1) * 64 + t * 16;
#pragma unroll
            for (int kb = 0; kb < 18; kb++) {
                const uint4 x = lds128(((kb & 1) ? a ^ 64 : a) + 128 * (kb >> 1));
                mma_bf(c[kb % 3], x.x, x.y, x.z, x.w, w[kb][0], w[kb][1]);
            }
            const float sr = c[0][0] + c[1][0] + c[2][0] + __shfl_down_sync(0xffffffffu, c[0][2] + c[1][2] + c[2][2], 1);
            const float sg = c[0][1] + c[1][1] + c[2][1] + __shfl_down_sync(0xffffffffu, c[0][3] + c[1][3] + c[2][3], 1);
            const uint32_t rb = pack_bf16(0.f, sr);
            if (t == 2 * (g & 1)) {
                sts32(s_part + (8 * rw + g) * 4, (rb ^ (((int)rb >> 31) & 0x7fff0000u) ^ 0x80000000u) | (uint32_t)(2047 - r0 - 8 * rw - g));
                sts32(s_part + 192 + (8 * rw + g) * 4, __float_as_uint(sg));
            }
            __syncwarp();
            bar_sync(BAR_R, 32 * (nrw + 1));
            const uint32_t sk = fresh(s_part), kk = lds32(sk + (8 * rw + r8) * 4);
            int n = 0;
#pragma unroll
            for (int i = 0; i < 3; i++) { const uint4 v = lds128(sk + mi * 48 + 16 * i); n += (v.x > kk) + (v.y > kk) + (v.z > kk) + (v.w > kk); }
            n += __shfl_xor_sync(0xffffffffu, n, 8); n += __shfl_xor_sync(0xffffffffu, n, 16);
            if (n < 8) sts32(s_tok + 4 * n, kk);
            __syncwarp();
            bar_arrive(BAR_R2, 32 * (nrw + 1));
        }
    }
}

__device__ __forceinline__ void ffn_work(const Params& p, uint32_t sb, int warp, int lane, int f, unsigned epoch) {
    const int g = lane >> 2, t = lane & 3, mi = lane >> 3, r8 = lane & 7;
    const bool isx = f < NX;
    const uint32_t bar_x = sb + SF_MISC + FB_X, bar_free = sb + SF_MISC + FB_FREE, bar_w = sb + SF_MISC + FB_W, bar_d = sb + SF_MISC + FB_D, s_tok = sb + SF_MISC + FS_TOK;
    uint32_t fr[24][4];
    auto pin = [&] {
#pragma unroll
        for (int i = 0; i < 24; i += 8) asm volatile("" :: "r"(fr[i][0]), "r"(fr[i + 1][0]), "r"(fr[i + 2][0]), "r"(fr[i + 3][0]), "r"(fr[i + 4][0]), "r"(fr[i + 5][0]), "r"(fr[i + 6][0]), "r"(fr[i + 7][0]) : "memory");
    };
    {
        const int j = (unsigned)(warp - 4) < 6, w = warp - (j ? 4 : warp < 4 ? 0 : 6);
        float ag[2][4], au[2][4];
#pragma unroll
        for (int i = 0; i < 2; i++) { ag[i][0] = ag[i][1] = ag[i][2] = ag[i][3] = 0.f; au[i][0] = au[i][1] = au[i][2] = au[i][3] = 0.f; }
        const uint32_t wb = sb + (w >> 1) * 4096 + (r8 + 8 * (mi >> 1)) * 64 + (((2 * (w & 1) + (mi & 1)) ^ (r8 >> 1)) << 4);
        const uint32_t xb = sb + SF_XS + r8 * 1168 + mi * 16;
        auto load = [&](int i, int n, int place) {
            mbar_wait(bar_w + 8 * n);
            const uint32_t wk = fresh(wb) + place * 24576;
#pragma unroll
            for (int s = 0; s < 4; s++) { ldsm4t(fr[8 * i + s], wk + 1024 * s); ldsm4t(fr[8 * i + 4 + s], wk + 1024 * s + 12288); }
        };
        auto mul = [&](int i, uint32_t xk) {
            uint32_t x[2][4];
            ldsm4(x[0], xk); ldsm4(x[1], xk + 64);
#pragma unroll
            for (int s = 0; s < 4; s++) {
                const uint32_t (&a)[4] = fr[8 * i + s], (&b)[4] = fr[8 * i + 4 + s];
                mma_bf(ag[s & 1], a[0], a[1], a[2], a[3], x[s >> 1][2 * (s & 1)], x[s >> 1][2 * (s & 1) + 1]);
                mma_bf(au[s & 1], b[0], b[1], b[2], b[3], x[s >> 1][2 * (s & 1)], x[s >> 1][2 * (s & 1) + 1]);
            }
        };
#pragma unroll
        for (int i = 0; i < 3; i++) load(i, 3 * j + i, (i ? 5 : 3) * j + i);
        pin();
        bar_sync(BAR_G + j, 192);
        if (w == 0 && lane == 0) mbar_arrive(bar_free + 8 * j);
        mbar_wait(bar_x);
        if (warp == 0) TSTAMP(8);
        {
            const uint32_t xk = fresh(xb) + 384 * j;
#pragma unroll
            for (int i = 0; i < 3; i++) { mul(i, (i ? fresh(xk) : xk) + 128 * i); if (i == 0) { asm volatile("" :: "f"(ag[0][0]), "f"(ag[1][0]), "f"(au[0][0]), "f"(au[1][0])); sts32(s_tok + 64, clock32()); } }
        }
#pragma unroll 1
        for (int n = 6 + j; n < 9; n += 2) { load(0, n, n - 6); mul(0, fresh(xb) + 128 * n); }
#pragma unroll
        for (int c = 0; c < 4; c++) { ag[0][c] += ag[1][c]; au[0][c] += au[1][c]; }
        if (j) {
            sts128(wb + 24576, __float_as_uint(ag[0][0]), __float_as_uint(ag[0][1]), __float_as_uint(ag[0][2]), __float_as_uint(ag[0][3]));
            sts128(wb + 25600, __float_as_uint(au[0][0]), __float_as_uint(au[0][1]), __float_as_uint(au[0][2]), __float_as_uint(au[0][3]));
        }
        bar_sync(BAR_GU, 384);
        if (!j) {
            const uint32_t sf = fresh(wb);
            const uint4 g1 = lds128(sf + 24576), u1 = lds128(sf + 25600);
            const uint32_t gs[4] = {g1.x, g1.y, g1.z, g1.w}, us[4] = {u1.x, u1.y, u1.z, u1.w};
            if (warp == 0) TSTAMP(9);
            float h[4];
#pragma unroll
            for (int c = 0; c < 4; c++) {
                const float gv = rbf(ag[0][c] + __uint_as_float(gs[c]));
                h[c] = rbf(gv * sigmoidf_(gv)) * rbf(au[0][c] + __uint_as_float(us[c]));
            }
            uint32_t h0, h1;
            asm("movmatrix.sync.aligned.m8n8.trans.b16 %0, %1;" : "=r"(h0) : "r"(pack_bf16(h[0], h[1])));
            asm("movmatrix.sync.aligned.m8n8.trans.b16 %0, %1;" : "=r"(h1) : "r"(pack_bf16(h[2], h[3])));
            if (h0 == 0) h0 = 0x8000u;
            asm volatile("{ .reg .b64 v; mov.b64 v, {%1, %2}; st.relaxed.gpu.global.b64 [%0], v; }" :: "l"(p.s->h + ((epoch & 1) * 288 + 6 * f + w) * 32 + lane), "r"(h0), "r"(h1) : "memory");
        }
        if (isx) {
            if (warp == 0) TSTAMP(10);
            const uint2* hsrc = p.s->h + ((epoch & 1) * 288 + 144 * (f & 1) + warp) * 32 + lane;
            const uint32_t wd = sb + SF_WD + warp * 1024 + (r8 + 8 * (mi >> 1)) * 64 + (((mi & 1) ^ (r8 >> 1)) << 4), we = wd ^ 32;
            uint2 hb[12];
            auto ldh = [&](int i) { asm volatile("ld.relaxed.gpu.global.v2.u32 {%0, %1}, [%2];" : "=r"(hb[i].x), "=r"(hb[i].y) : "l"(hsrc + 384 * box_no(i)) : "memory"); };
            auto ldw = [&](int i) { mbar_wait(bar_d + 8 * box_no(i)); ldsm4t(fr[2 * i], fresh(wd) + 12288 * box_no(i)); ldsm4t(fr[2 * i + 1], fresh(we) + 12288 * box_no(i)); };
#pragma unroll
            for (int i = 0; i < DPA; i++) ldw(i);
#pragma unroll
            for (int i = 0; i < 12; i++) ldh(i);
#pragma unroll
            for (int i = DPA; i < DPB; i++) ldw(i);
#pragma unroll
            for (int i = 0; i < DPB; i++) asm volatile("" :: "r"(fr[2 * i][0]), "r"(fr[2 * i + 1][0]) : "memory");
#pragma unroll 1
            for (int it = 0;; it++) {
                bool again = false;
#pragma unroll
                for (int s = 0; s < 12; s += 2) if (__any_sync(0xffffffffu, min(hb[s].x, hb[s + 1].x) == 0)) { ldh(s); ldh(s + 1); again = true; }
                if (!again) break;
                if (it > (1 << 16)) give_up();
            }
            if (warp == 0) TSTAMP(11);
            float ad[2][2][4];
#pragma unroll
            for (int i = 0; i < 4; i++) { ad[i >> 1][i & 1][0] = ad[i >> 1][i & 1][1] = ad[i >> 1][i & 1][2] = ad[i >> 1][i & 1][3] = 0.f; }
#pragma unroll
            for (int i = 0; i < 12; i++) {
                if (i >= DPB) ldw(i);
                if (i == 11 && warp == 9) TSTAMP(14);
#pragma unroll
                for (int c = 0; c < 2; c++) mma_bf(ad[c][i & 1], fr[2 * i + c][0], fr[2 * i + c][1], fr[2 * i + c][2], fr[2 * i + c][3], hb[i].x, hb[i].y);
                if (i >= DPB - 1) asm volatile("" :: "f"(ad[0][i & 1][0]), "f"(ad[1][i & 1][0]) : "memory");
            }
            const uint32_t rd = sb + SF_RED + warp * 1152 + (72 * t + g) * 4;
#pragma unroll
            for (int i = 0; i < 8; i++) sts32(rd + (i >> 2) * 64 + (i & 1) * 144 + ((i >> 1) & 1) * 32, __float_as_uint(ad[i >> 2][0][i & 3] + ad[i >> 2][1][i & 3]));
            bar_sync(BAR_RED, 416);
            if (warp < 4) {
                const int tid = 32 * warp + lane;
                const uint32_t rs = fresh(sb + SF_RED) + (tid >> 4) * 144 + (tid & 15) * 8;
                const uint2 tk = lds64(fresh(s_tok) + (tid >> 4) * 8);
                float x = 0.f, y = 0.f;
#pragma unroll
                for (int w = 0; w < 12; w++) { const uint2 v = lds64(rs + w * 1152); x += __uint_as_float(v.x); y += __uint_as_float(v.y); }
                asm volatile("red.relaxed.gpu.global.add.noftz.bf16x2 [%0], %1;" :: "l"(p.out + (size_t)tk.x * DM + 32 * (f >> 1) + 2 * (tid & 15)),
                             "r"(pack_bf16(x * __uint_as_float(tk.y), y * __uint_as_float(tk.y))) : "memory");
            }
            if (warp == 0) { TSTAMP(15); TFLUSH(); }
            asm volatile("exit;"); __builtin_unreachable();
        }
    }
}

__device__ __forceinline__ void fetch_k(const uint4* src, uint64_t (&v)[6], uint32_t a, uint32_t b) {
    asm volatile("{ .reg .pred p; setp.eq.u32 p, %7, %8; @p ld.relaxed.gpu.global.v2.u64 {%0,%1}, [%6]; @p ld.relaxed.gpu.global.v2.u64 {%2,%3}, [%6 + 512]; @p ld.relaxed.gpu.global.v2.u64 {%4,%5}, [%6 + 1024]; }"
                 : "+l"(v[0]), "+l"(v[1]), "+l"(v[2]), "+l"(v[3]), "+l"(v[4]), "+l"(v[5]) : "l"(src), "r"(a), "r"(b));
}
__device__ __forceinline__ uint32_t mini_conv(const Params& p, uint32_t sb, int warp, int lane, int f, unsigned epoch, uint64_t (&v)[6]) {
    const int g = lane >> 2, t = lane & 3, mi = lane >> 3, r8 = lane & 7;
    const uint32_t fb = sb + SF_MISC, kt = sb + (warp >= 12 ? SM_KT - 12 * 2112 : f < NW ? SM_KW + 2 * 2112 : SM_KW) + warp * 2112;
    const bool ism = f >= NW;
    const uint32_t* const sel = &p.s->sel[((mini_ch0(f) + (ism ? 2 * (warp & 8) : 0)) >> 5) * 64 + r8];
    uint32_t seq = 128, key;
    const uint4* src = p.s->kp + lane;
    auto hi = [&](int i) { return (uint32_t)(v[i] >> 32); };
    if (f >= (warp < 4 ? NW : NX)) {
    {
        const uint32_t c = 68 + (warp & 3) + 2 * (warp & 12), y = ((uint32_t)((warp < 8 ? 0xe066806400000000ull : 0x5a6e00680080e26cull) >> ((8 * warp) & 48)) & 0xffff) + (warp < 14 ? 0 : 0x6a0000);
        seq = !ism ? y + (warp & 1) * ((y >> 6) & 0x10101) : warp < 14 ? 0x101 * c - 0x400 : c;
        src += (48 * (f - (ism ? NW : NX)) + (seq & 63)) * 96;
    }
    if (seq & 64) {
        if (seq & 4) {
            const int q = (seq & 3) + ((seq >> 1) & 4);
            const uint32_t ab = sb - 3072 * (seq & 16), d = ab + SM_UT + g * MU_STRIDE + (4 + 4 * q + t) * 32;
            asm volatile("st.shared.v2.u32 [%0], {%1,%1};" :: "r"(ab + SM_UT + (2 * q + (mi >> 1)) * MU_STRIDE + (lane & 15) * 8), "r"(0) : "memory");
            mbar_wait(fb + FB_MU - (seq & 16) / 2);
            if (warp == 15) TSTAMP(16);
            const uint32_t a = fresh(ab + SM_RAW) + q * 2048 + (8 * mi + 4 * (r8 & 1) + (r8 >> 1)) * 32 + ((r8 & 1) << 4);
            uint32_t x[4][4];
#pragma unroll
            for (int i = 0; i < 4; i++) ldsm4t(x[i], (i & 2 ? a ^ 16 : a) + 1024 * (i & 1));
#pragma unroll
            for (int i = 0; i < 4; i++) sts128(d + (i & 1) * 16 + (i & 2) * 4 * MU_STRIDE, x[i][0], x[i][1], x[i][2], x[i][3]);
            __syncwarp();
            if (lane == 0) mbar_arrive(fb + FB_MT + (seq & 16) / 2);
        }
        mbar_wait(fb + FB_KDONE);
        fetch_k(src, v, warp < 4, 0);
        if ((warp | 2) == 7) { fetch_gates(p, (warp >> 1) & 1, lane, epoch, sb + SM_G + 256 * (warp & 2) + 16 * lane); __syncwarp(); if (lane == 0) mbar_arrive(fb + FB_MG); }
        if (warp >= 8) {
            mbar_wait(fb + FB_KEYS); mbar_wait(fb + FB_MT);
            if (ism) {
                asm volatile("barrier.cluster.wait.aligned; fence.release.sync_restrict::shared::cta.cluster;" ::: "memory");
                if (lane == 0) asm volatile("mbarrier.arrive.relaxed.cluster.shared::cluster.b64 _, [%0];" :: "r"(mapa(fb + FB_MT + 8, 0)) : "memory");
            }
        }
        if (warp == TW) TSTAMP(17);
    }
    }
    const uint32_t lo = (8 + r8 - (mi & 1)) * 16 + (mi >> 1) * 128;
#pragma unroll 1
    do {
        const int c = seq & 63;
        const bool far = !ism && (seq & 16);
        const uint32_t ab = sb - 3072 * (c & 16);
        uint32_t ut = ab + SM_UT + (c & 15) * MU_STRIDE;
        if (seq & 64) {
        if (far) {
            mbar_wait_cluster(fb + FB_MT + 8);
            const uint32_t ru = mapa(ut, 1) + lane * 16;
            ut = sb + SM_FT + (c & 3) * 1536;
            uint4 x[3];
#pragma unroll
            for (int i = 0; i < 3; i++) asm volatile("ld.shared::cluster.v4.u32 {%0,%1,%2,%3}, [%4];" : "=r"(x[i].x), "=r"(x[i].y), "=r"(x[i].z), "=r"(x[i].w) : "r"(ru + 512 * i) : "memory");
#pragma unroll
            for (int i = 0; i < 3; i++) sts128(ut + lane * 16 + 512 * i, x[i].x, x[i].y, x[i].z, x[i].w);
        } else mbar_wait(fb + FB_MT + (seq & 16) / 2);
#pragma unroll 1
        for (int it = 0; !__all_sync(0xffffffffu, ((hi(1) ^ k_tag(epoch)) | (hi(3) ^ k_tag(epoch)) | (hi(5) ^ k_tag(epoch)) | ((uint32_t)v[5] & p.zero)) < 65536); it++) {
            fetch_k(src, v, 0, 0);
            if (it > (1 << 20)) give_up();
        }
        sts128(kt + t * 16, 0, 0, 0, 0);
        if (warp == TW) TSTAMP(seq >> 8 ? 7 : 10);
        const uint32_t w[12] = {(uint32_t)v[0], hi(0), (uint32_t)v[1], (uint32_t)v[2], hi(2), (uint32_t)v[3], (uint32_t)v[4], hi(4), 0, 0, 0, 0};
        k_tables<false>(fresh(kt), fresh(lane), w);
        }
        __syncwarp();
        if (seq & 128) ffn_work(p, sb, warp, fresh(lane), f, epoch);
        if (!(seq & 64)) return 0;
        const uint32_t kb = fresh(kt) + (16 + g - 2 * t) * 4, ub = fresh(ut);
        const uint32_t yd = ab + SM_Y + (c & 15) * 1056 + (c & 8) * 8 + lane * 16;
        if (warp == TW && !(seq >> 8)) TSTAMP(13);
        seq >>= 8;
        src += ((int)(seq & 63) - c) * 96;
#pragma unroll
        for (int i = 0; i < 6; i++) v[i] = 0;
        key = 0;
        float acc[8][4];
#pragma unroll
        for (int i = 0; i < 8; i++) { acc[i][0] = acc[i][1] = acc[i][2] = acc[i][3] = 0.f; }
        uint32_t a[4][4], b[2][4][4];
        auto lda = [&](int j, int s) { const uint32_t x = kb + 64 * s + 512 * j; a[j][0] = lds32(x); a[j][1] = lds32(x + 256); a[j][2] = lds32(x + 32); a[j][3] = lds32(x + 288); };
        auto ldb = [&](int i, int s) { ldsm4(b[s & 1][i], ub + lo + 256 * i - 32 * s); };
#pragma unroll
        for (int j = 0; j < 4; j++) { ldb(j, 0); lda(j, 0); }
#pragma unroll
        for (int s = 0; s < 4; s++) {
            if (s == 2) {
                const uint32_t e = seq | (__float_as_uint(acc[0][0]) & p.zero);
                fetch_k(src, v, e & 64, 64);
                asm volatile("{ .reg .pred p; setp.eq.u32 p, %2, 0; @p ld.relaxed.gpu.global.u32 %0, [%1]; }" : "+r"(key) : "l"(sel), "r"(e));
            }
#pragma unroll
            for (int i = 0; i < 4; i++) {
                const int j = (i >> 1) + 2 * (i & 1);
                if (s < 3) ldb(i, s + 1);
#pragma unroll
                for (int mu = 0; mu < 8; mu++) if (mu + 2 * j < 8) mma_bf(acc[mu + 2 * j], a[j][0], a[j][1], a[j][2], a[j][3], b[s & 1][mu >> 1][2 * (mu & 1)], b[s & 1][mu >> 1][2 * (mu & 1) + 1]);
                if (s < 3) lda(j, s + 1);
            }
        }
        if (warp == TW && !seq) TSTAMP(14);
        mbar_wait(fb + FB_MG);
        uint32_t ug[4][4];
#pragma unroll
        for (int i = 0; i < 2; i++) { ldsm4t(ug[i], ub + 128 + lane * 16 + 512 * i); ldsm4t(ug[2 + i], fresh(sb + SM_G) + lane * 16 + 512 * i); }
#pragma unroll
        for (int x = 0; x < 8; x++) ug[x >> 2][x & 3] = gmix(ug[2 + (x >> 2)][x & 3], x ? acc[x][0] + acc[x - 1][2] : acc[0][0], x ? acc[x][1] + acc[x - 1][3] : acc[0][1], ug[x >> 2][x & 3]);
        if (far) for (int i = 0; i < 2; i++) st_async128(mapa(yd, 1) + 512 * i, ug[i][0], ug[i][1], ug[i][2], ug[i][3], mapa(fb + FB_FAR, 1));
        else for (int i = 0; i < 2; i++) sts128(yd + 512 * i, ug[i][0], ug[i][1], ug[i][2], ug[i][3]);
        __syncwarp();
        if (warp == TW) TSTAMP(18 + (seq != 0));
    } while (seq);
    if (warp >= 12) TSTAMP(12 + warp);
    return key;
}
__device__ __forceinline__ void mini_out(const Params& p, const CUtensorMap* maps, uint32_t sb, int warp, int lane, int f, unsigned epoch, uint32_t key) {
    const int g = lane >> 2, t = lane & 3, mi = lane >> 3, r8 = lane & 7;
    const uint32_t fb = sb + SF_MISC;
    const bool ism = f >= NW;
    const int ch0 = mini_ch0(f);
    const int k = ism ? warp >> 3 : 0;
    uint32_t first = 1;
    if (lane == 0) asm volatile("atom.shared.exch.b32 %0, [%1], 1;" : "=r"(first) : "r"(fb + FS_BM + 64 + 4 * k) : "memory");
    if (!__all_sync(0xffffffffu, first)) {
        if (elect()) prefetch_map(maps + 6);
        const int row = key_row(wait_sel(p, (ch0 + 16 * k) >> 5, r8, key_tag(epoch), key));
        if (row < 512) asm volatile("red.shared.or.b32 [%0], %1;" :: "r"(fb + FS_BM + (row >> 5) * 4), "r"(1u << (row & 31)) : "memory");
        if (k) mbar_wait_cluster(fb + FB_FAR);
    }
    const int m = warp & 7, dr = 64 * (g >> 1) + 16 * (t >> 1) + 8 * (g & 1);
    const uint32_t y = SM_Y + ((r8 >> 1) & 1) * 8512 + (2 * mi + (r8 & 1)) * 1056 + (2 * m + (r8 >> 2)) * 16;
    const uint32_t so = (g >> 1) * 128 + (t >> 1) * 64 + (g & 1) * 32 + (t & 1) * 16;
    bar_sync(BAR_M - k, ism ? 256 : NTHR);
#pragma unroll 1
    for (int h = ism ? 0 : warp >> 3;; h++) {
        const int r0 = 256 * h + 32 * (m & 1) + (m >> 1), row = r0 + dr;
        const uint32_t bm = lds32(fresh(fb) + FS_BM + (row >> 5) * 4) >> (row & 31), ab = fresh(sb - 49152 * k + 512 * h), stg = ab + SM_UT + 2048 * m + 512 * h;
        uint32_t x[2][4];
        ldsm4t(x[0], ab + y); ldsm4t(x[1], ab + y + 256);
        if (warp == 0 && x[0][0] != 0x12345) TSTAMP(28);
        if (__any_sync(0xffffffffu, bm & 0x11u)) {
#pragma unroll
            for (int i = 0; i < 2; i++) store_or_add(p.out + (size_t)(row + 4 * i) * DM + ch0 + 16 * k + 8 * (t & 1), x[i], bm & (1u << (4 * i)));
        } else {
#pragma unroll
            for (int i = 0; i < 2; i++) sts128(stg + so + 512 * i, x[i][0], x[i][1], x[i][2], x[i][3]);
            asm volatile("fence.proxy.async.shared::cta;" ::: "memory");
            __syncwarp();
            if (elect()) store_rows(maps + 6, stg, ch0 + 16 * k, r0);
        }
        if (h >= ism) break;
    }
    if (elect()) { asm volatile("cp.async.bulk.commit_group;" ::: "memory"); asm volatile("cp.async.bulk.wait_group.read 0;" ::: "memory"); }
    if (warp == 8) TSTAMP(11);
    if (warp == 0) { TSTAMP(15); TFLUSH(); }
}

constexpr int SMEM_BYTES = 232448;
static_assert(SF_MISC + 1152 <= 232192, "layout");

struct Maps { CUtensorMap m[7]; };

__global__ void __cluster_dims__(2, 1, 1) __launch_bounds__(NTHR, 1)
fused_kernel(const Params p, const __grid_constant__ Maps maps) {
    extern __shared__ __align__(1024) uint8_t smem_raw[];
    uint32_t q[8];
    {
        const int b = role(blockIdx.x), x = threadIdx.x, rc = 5 * b + (b & ~3) + 4 + (x >> 6);
        const int cv = (unsigned)b < NW ? 0 : -1, ca = (b < 0 ? 8 * b + DM : 48 * b - 2300) + ((x >> 5) & 3), cb = 2 * rc - (rc & 3) + 4;
        const uint32_t ch = (ca & cv) | (cb & ~cv), o = NST * ch + 2 * ((x & 31) + ((x >> (cv & 2)) & 32));
        const bool c = x < (cv ? 256 : 320);
        q[6] = ldg16_if(c, p.logdt + ch);
        q[2] = ldg32_if(c, p.Bre + o); q[3] = ldg32_if(c, p.Bim + o); q[4] = ldg32_if(c, p.Cre + o); q[5] = ldg32_if(c, p.Cim + o); q[0] = ldg32_if(c, p.Are + o); q[1] = ldg32_if(c, p.Aim + o);
        q[7] = ldg16_if(c, p.Dskip + ch);
    }
    const unsigned epoch = ld_rlx32(&p.s->epoch[blockIdx.x * 16 + (threadIdx.x >> 5)]);
    const uint32_t sb = __shfl_sync(0xffffffffu, smem_u32(smem_raw), 0);
    const int warp = __shfl_sync(0xffffffffu, threadIdx.x >> 5, 0), bid = __shfl_sync(0xffffffffu, blockIdx.x, 0);
    const int lane = __shfl_sync(0xffffffffu, threadIdx.x & 31, threadIdx.x);
    const bool conv = bid < NCONV;
    const int f = role(bid);
    uint32_t w[12];
    uint64_t v[6];
    const bool four = (unsigned)f >= NW;
    if (warp < (four ? 8 : 10)) {
        const int half = four ? warp >> 2 : warp & 1, pr = four ? warp & 3 : warp >> 1;
        const int rc = 5 * f + (f & ~3) + 4 + pr;
        const uint32_t stage = sb + (conv ? SC_KG : SF_KG) + warp * KG_STAGE;
        uint4* const kp = p.s->kp + (four ? (conv ? 8 * bid : 48 * f - 2300) + pr : 2 * rc - (rc & 3) + 4) * 96 + lane;
        kgen(q, sb, half, stage, stage + (four ? 4 : 1) * KG_STAGE, 1 + pr, lane, w, [&] {
            sts128z_if(conv && lane < 20, sb + SC_KT + warp * KT_BYTES + lane * 16 + (lane < 4 ? 0 : lane < 14 ? 2048 : 2288));
            stg128z_if(!conv, kp + 64 * half); stg128z_if(!half && !conv, kp + 32);
            stg128z_if((unsigned)f < NW && warp < 6, (uint4*)(p.s->h + ((lane >> 4) * 288 + 6 * f + warp) * 32) + (lane & 15));
            if (!conv) bar_sync(0, NTHR);
            if ((unsigned)f >= NX) asm volatile("barrier.cluster.arrive.relaxed.aligned;" ::: "memory");
        });
        if (!half) publish_k(kp, w, epoch, v);
        else for (int i = 0; i < 6; i++) v[i] = 0;
        if (conv) { conv_main(p, sb, warp, lane, bid, epoch, w); return; }
        {
            if (!half && lane == 0) mbar_arrive(sb + SF_MISC + FB_KDONE);
            if (warp == 0) TSTAMP(22);
            if (warp == 2) TSTAMP(23);
        }
    } else if (conv) {
        conv_aux(p, maps.m, sb, warp - 8, lane, bid, epoch);
        return;
    } else {
        ffn_front(p, maps.m, sb, warp, lane, f, epoch);
        for (int i = 0; i < 6; i++) v[i] = 0;
    }
    converged();
    next_epoch(p, epoch);
    if (warp >= 12 && f < NX) return;
    mini_out(p, maps.m, sb, warp, lane, f, epoch, mini_conv(p, sb, warp, __shfl_sync(0xffffffffu, lane, lane), f, epoch, v));
}

typedef CUresult (*EncodeFn)(CUtensorMap*, CUtensorMapDataType, cuuint32_t, void*, const cuuint64_t*, const cuuint64_t*, const cuuint32_t*, const cuuint32_t*,
                             CUtensorMapInterleave, CUtensorMapSwizzle, CUtensorMapL2promotion, CUtensorMapFloatOOBfill);

void make_map(EncodeFn fn, CUtensorMap* m, const void* base, int rank, const cuuint64_t* dims, const cuuint64_t* strides, const cuuint32_t* box, CUtensorMapSwizzle sw) {
    const cuuint32_t es[5] = {1, 1, 1, 1, 1};
    fn(m, CU_TENSOR_MAP_DATA_TYPE_BFLOAT16, rank, (void*)base, dims, strides, box, es, CU_TENSOR_MAP_INTERLEAVE_NONE, sw,
       CU_TENSOR_MAP_L2_PROMOTION_NONE, CU_TENSOR_MAP_FLOAT_OOB_FILL_NONE);
}

}

extern "C" void kernel_launch(void* const* d_in, const int* in_sizes, int n_in, void* d_out, int out_size) {
    (void)in_sizes; (void)n_in; (void)out_size;
    static EncodeFn fn = nullptr;
    static void* scratch = nullptr;
    if (!fn) {
        void* ptr = nullptr; cudaDriverEntryPointQueryResult qr;
        cudaGetDriverEntryPoint("cuTensorMapEncodeTiled", &ptr, cudaEnableDefault, &qr);
        fn = (EncodeFn)ptr;
        cudaGetSymbolAddress(&scratch, g_scratch);
        cudaFuncSetAttribute(fused_kernel, cudaFuncAttributeMaxDynamicSharedMemorySize, SMEM_BYTES);
    }
    typedef const __nv_bfloat16* bp;
    Params p;
    p.u = (bp)d_in[0]; p.Are = (bp)d_in[1]; p.Aim = (bp)d_in[2]; p.Bre = (bp)d_in[3]; p.Bim = (bp)d_in[4]; p.Cre = (bp)d_in[5]; p.Cim = (bp)d_in[6];
    p.logdt = (bp)d_in[7]; p.Dskip = (bp)d_in[8]; p.wr = (bp)d_in[10]; p.gatew = (bp)d_in[14];
    p.out = (__nv_bfloat16*)d_out; p.s = (Scratch*)scratch; p.zero = 0;
    Maps maps;
    {
        const cuuint64_t dims[4] = {DM, 4, 16, 32}, strides[3] = {16 * DM * 2, DM * 2, 64 * DM * 2};
        const cuuint32_t box[4] = {16, 4, 16, 2};
        make_map(fn, &maps.m[0], d_in[0], 4, dims, strides, box, CU_TENSOR_MAP_SWIZZLE_32B);
        const cuuint32_t box2[4] = {16, 4, 16, 8};
        make_map(fn, &maps.m[5], d_in[0], 4, dims, strides, box2, CU_TENSOR_MAP_SWIZZLE_32B);
    }
    for (int i = 0; i < 2; i++) {
        const cuuint64_t dims[3] = {32, DM, FF / 32}, strides[2] = {FF * 2, 64};
        const cuuint32_t box[3] = {32, 64, 3};
        make_map(fn, &maps.m[1 + i], d_in[11 + i], 3, dims, strides, box, CU_TENSOR_MAP_SWIZZLE_64B);
    }
    {
        const cuuint64_t dims[2] = {DM, FF}, strides[1] = {DM * 2};
        const cuuint32_t box[2] = {32, 192};
        make_map(fn, &maps.m[3], d_in[13], 2, dims, strides, box, CU_TENSOR_MAP_SWIZZLE_64B);
    }
    {
        const cuuint64_t dims[5] = {DM, 2, 4, 4, L_SEQ}, strides[4] = {16 * DM * 2, 64 * DM * 2, 4 * DM * 2, DM * 2};
        const cuuint32_t box[5] = {16, 2, 4, 4, 1};
        make_map(fn, &maps.m[4], d_out, 5, dims, strides, box, CU_TENSOR_MAP_SWIZZLE_NONE);
    }
    {
        const cuuint64_t dims[5] = {DM, 4, 4, 2, L_SEQ}, strides[4] = {8 * DM * 2, 64 * DM * 2, 4 * DM * 2, DM * 2};
        const cuuint32_t box[5] = {16, 4, 4, 2, 1};
        make_map(fn, &maps.m[6], d_out, 5, dims, strides, box, CU_TENSOR_MAP_SWIZZLE_NONE);
    }
    fused_kernel<<<NCTA, NTHR, SMEM_BYTES>>>(p, maps);
}
```

```cpp
#include <cuda_runtime.h>
#include <cuda_bf16.h>
#include <cuda_fp16.h>
#include <cuda.h>
#include <stdint.h>

#define RESUME 300
#define MDELAY 2000
#define MGAP 0
#define KPOLL 650
#define DPA 7
#define DPB 9
#define M2 0
#define RDELAY 900
#define WDELAY 1700
#define WGAP 290
#define NPRE 8
#define DGAP 290
namespace {

constexpr int DM = 576, NST = 128, FF = 4608, L_SEQ = 2048;
constexpr int NCONV = 72, NX = 36, NW = 48, NCTA = 132, NTHR = 512;

struct __align__(128) Scratch {
    unsigned epoch[NCTA * 16];
    uint4 keys[16 * 128];
    uint32_t sel[18 * 64];
    uint16_t gate[L_SEQ];
    uint2 h[2 * 288 * 32];
    uint4 kp[DM * 96];
};
__device__ Scratch g_scratch;
#define TFLUSH()
#define TSTAMP(i)
#define TW 12

struct Params {
    const __nv_bfloat16 *Are, *Aim, *Bre, *Bim, *Cre, *Cim, *logdt, *Dskip, *u, *wr, *gatew;
    __nv_bfloat16* out;
    Scratch* s;
    uint32_t zero;
};

__device__ __forceinline__ void give_up() { asm volatile("trap; exit;"); __builtin_unreachable(); }
__device__ __forceinline__ void converged() { __syncwarp(); asm volatile("{ .reg .b32 t; mov.b32 t, 0; movmatrix.sync.aligned.m8n8.trans.b16 t, t; }" ::: "memory"); }
__device__ __forceinline__ bool elect() { uint32_t r; asm volatile("{ .reg .pred p; elect.sync _|p, 0xffffffff; selp.u32 %0, 1, 0, p; }" : "=r"(r)); return r; }
__device__ __forceinline__ uint32_t smem_u32(const void* p) { return (uint32_t)__cvta_generic_to_shared(p); }
__device__ __forceinline__ uint32_t pack_bf16(float lo, float hi) { uint32_t r; asm("cvt.rn.bf16x2.f32 %0, %1, %2;" : "=r"(r) : "f"(hi), "f"(lo)); return r; }
__device__ __forceinline__ uint32_t pack_f16(float lo, float hi) { uint32_t r; asm("cvt.rn.f16x2.f32 %0, %1, %2;" : "=r"(r) : "f"(hi), "f"(lo)); return r; }
__device__ __forceinline__ float bf_lo(uint32_t w) { return __uint_as_float(w << 16); }
__device__ __forceinline__ float bf_hi(uint32_t w) { return __uint_as_float(w & 0xffff0000u); }
__device__ __forceinline__ float rbf(float x) { return bf_lo(pack_bf16(x, 0.f)); }
__device__ __forceinline__ uint32_t badd2(uint32_t a, uint32_t b) { uint32_t r; asm("add.rn.bf16x2 %0, %1, %2;" : "=r"(r) : "r"(a), "r"(b)); return r; }
__device__ __forceinline__ uint32_t bsub2(uint32_t a, uint32_t b) { uint32_t r; asm("sub.rn.bf16x2 %0, %1, %2;" : "=r"(r) : "r"(a), "r"(b)); return r; }
__device__ __forceinline__ uint32_t gmix(uint32_t ng, float ny0, float ny1, uint32_t u) {
    uint32_t r; asm("{ .reg .b32 t; fma.rn.bf16x2 t, %1, %3, %3; fma.rn.bf16x2 %0, %1, %2, t; }" : "=r"(r) : "r"(ng), "r"(pack_bf16(ny0, ny1)), "r"(u)); return r;
}
__device__ __forceinline__ void mma_bf(float (&c)[4], uint32_t a0, uint32_t a1, uint32_t a2, uint32_t a3, uint32_t b0, uint32_t b1) {
    asm("mma.sync.aligned.m16n8k16.row.col.f32.bf16.bf16.f32 {%0,%1,%2,%3}, {%4,%5,%6,%7}, {%8,%9}, {%0,%1,%2,%3};"
        : "+f"(c[0]), "+f"(c[1]), "+f"(c[2]), "+f"(c[3]) : "r"(a0), "r"(a1), "r"(a2), "r"(a3), "r"(b0), "r"(b1));
}
__device__ __forceinline__ void mma_bf8(float (&c)[4], uint32_t a0, uint32_t a1, uint32_t b0) {
    asm("mma.sync.aligned.m16n8k8.row.col.f32.bf16.bf16.f32 {%0,%1,%2,%3}, {%4,%5}, {%6}, {%0,%1,%2,%3};"
        : "+f"(c[0]), "+f"(c[1]), "+f"(c[2]), "+f"(c[3]) : "r"(a0), "r"(a1), "r"(b0));
}
__device__ __forceinline__ void mma_h(float (&c)[4], uint32_t a0, uint32_t a1, uint32_t a2, uint32_t a3, uint32_t b0, uint32_t b1) {
    asm("mma.sync.aligned.m16n8k16.row.col.f32.f16.f16.f32 {%0,%1,%2,%3}, {%4,%5,%6,%7}, {%8,%9}, {%0,%1,%2,%3};"
        : "+f"(c[0]), "+f"(c[1]), "+f"(c[2]), "+f"(c[3]) : "r"(a0), "r"(a1), "r"(a2), "r"(a3), "r"(b0), "r"(b1));
}
__device__ __forceinline__ uint32_t fresh(uint32_t a) { asm volatile("" : "+r"(a) :: "memory"); return a; }
__device__ __forceinline__ uint32_t lds32(uint32_t a) { uint32_t v; asm("ld.shared.u32 %0, [%1];" : "=r"(v) : "r"(a)); return v; }
__device__ __forceinline__ uint2 lds64(uint32_t a) { uint2 v; asm("ld.shared.v2.u32 {%0,%1}, [%2];" : "=r"(v.x), "=r"(v.y) : "r"(a)); return v; }
__device__ __forceinline__ uint4 lds128(uint32_t a) { uint4 v; asm("ld.shared.v4.u32 {%0,%1,%2,%3}, [%4];" : "=r"(v.x), "=r"(v.y), "=r"(v.z), "=r"(v.w) : "r"(a)); return v; }
__device__ __forceinline__ void ldsm4(uint32_t (&r)[4], uint32_t a) {
    asm("ldmatrix.sync.aligned.m8n8.x4.shared.b16 {%0,%1,%2,%3}, [%4];" : "=r"(r[0]), "=r"(r[1]), "=r"(r[2]), "=r"(r[3]) : "r"(a));
}
__device__ __forceinline__ void ldsm4t(uint32_t (&r)[4], uint32_t a) {
    asm("ldmatrix.sync.aligned.m8n8.x4.trans.shared.b16 {%0,%1,%2,%3}, [%4];" : "=r"(r[0]), "=r"(r[1]), "=r"(r[2]), "=r"(r[3]) : "r"(a));
}
__device__ __forceinline__ void sts16(uint32_t a, uint32_t v) { asm volatile("st.shared.u16 [%0], %1;" :: "r"(a), "h"((unsigned short)v) : "memory"); }
__device__ __forceinline__ void sts32(uint32_t a, uint32_t v) { asm volatile("st.shared.u32 [%0], %1;" :: "r"(a), "r"(v) : "memory"); }
__device__ __forceinline__ void sts64(uint32_t a, uint32_t x, uint32_t y) { asm volatile("st.shared.v2.u32 [%0], {%1,%2};" :: "r"(a), "r"(x), "r"(y) : "memory"); }
__device__ __forceinline__ void sts128(uint32_t a, uint32_t x, uint32_t y, uint32_t z, uint32_t w) {
    asm volatile("st.shared.v4.u32 [%0], {%1,%2,%3,%4};" :: "r"(a), "r"(x), "r"(y), "r"(z), "r"(w) : "memory");
}
__device__ __forceinline__ void st_async128(uint32_t a, uint32_t x, uint32_t y, uint32_t z, uint32_t w, uint32_t bar) {
    asm volatile("st.async.weak.shared::cluster.mbarrier::complete_tx::bytes.v4.b32 [%0], {%1,%2,%3,%4}, [%5];" :: "r"(a), "r"(x), "r"(y), "r"(z), "r"(w), "r"(bar) : "memory");
}
__device__ __forceinline__ void mbar_init(uint32_t b, uint32_t cnt) { asm volatile("mbarrier.init.shared::cta.b64 [%0], %1;" :: "r"(b), "r"(cnt) : "memory"); }
__device__ __forceinline__ void mbar_fence() { asm volatile("fence.mbarrier_init.release.cluster;" ::: "memory"); }
__device__ __forceinline__ void mbar_expect(uint32_t b, uint32_t bytes) { asm volatile("mbarrier.arrive.expect_tx.shared::cta.b64 _, [%0], %1;" :: "r"(b), "r"(bytes) : "memory"); }
__device__ __forceinline__ void mbar_arrive(uint32_t b) { asm volatile("mbarrier.arrive.shared::cta.b64 _, [%0];" :: "r"(b) : "memory"); }
__device__ __forceinline__ void mbar_wait(uint32_t b, uint32_t parity = 0) {
    asm volatile("{ .reg .pred p; .reg .u32 n; mov.u32 n, 0;\n"
                 "LW: mbarrier.try_wait.parity.shared::cta.b64 p, [%0], %1; @p bra LD; add.u32 n, n, 1; setp.lt.u32 p, n, 65536; @p bra LW; trap;\n"
                 "LD: }" :: "r"(b), "r"(parity) : "memory");
}
__device__ __forceinline__ void mbar_wait_cluster(uint32_t b) {
    asm volatile("{ .reg .pred p; .reg .u32 n; mov.u32 n, 0;\n"
                 "LW: mbarrier.try_wait.parity.acquire.cluster.shared::cta.b64 p, [%0], 0; @p bra LD; add.u32 n, n, 1; setp.lt.u32 p, n, 65536; @p bra LW; trap;\n"
                 "LD: }" :: "r"(b) : "memory");
}
__device__ __forceinline__ void tma2d(uint32_t dst, const CUtensorMap* m, int c0, int c1, uint32_t bar) {
    asm volatile("cp.async.bulk.tensor.2d.shared::cluster.global.mbarrier::complete_tx::bytes [%0], [%1, {%3, %4}], [%2];"
                 :: "r"(dst), "l"(m), "r"(bar), "r"(c0), "r"(c1) : "memory");
}
__device__ __forceinline__ void tma3d(uint32_t dst, const CUtensorMap* m, int c0, int c1, int c2, uint32_t bar) {
    asm volatile("cp.async.bulk.tensor.3d.shared::cluster.global.mbarrier::complete_tx::bytes [%0], [%1, {%3, %4, %5}], [%2];"
                 :: "r"(dst), "l"(m), "r"(bar), "r"(c0), "r"(c1), "r"(c2) : "memory");
}
__device__ __forceinline__ void tma4d(uint32_t dst, const CUtensorMap* m, int c0, int c1, int c2, int c3, uint32_t bar) {
    asm volatile("cp.async.bulk.tensor.4d.shared::cluster.global.mbarrier::complete_tx::bytes [%0], [%1, {%3, %4, %5, %6}], [%2];"
                 :: "r"(dst), "l"(m), "r"(bar), "r"(c0), "r"(c1), "r"(c2), "r"(c3) : "memory");
}
__device__ __forceinline__ void bulk_g2s(uint32_t dst, const void* src, uint32_t bytes, uint32_t bar) {
    asm volatile("cp.async.bulk.shared::cluster.global.mbarrier::complete_tx::bytes [%0], [%1], %2, [%3];"
                 :: "r"(dst), "l"(src), "r"(bytes), "r"(bar) : "memory");
}
__device__ __forceinline__ uint32_t mapa(uint32_t a, uint32_t rank) { uint32_t r; asm("mapa.shared::cluster.u32 %0, %1, %2;" : "=r"(r) : "r"(a), "r"(rank)); return r; }
__device__ __forceinline__ void prefetch_map(const CUtensorMap* m) { asm volatile("prefetch.tensormap [%0];" :: "l"(m) : "memory"); }
__device__ __forceinline__ void bar_sync(int id, int n) { asm volatile("bar.sync %0, %1;" :: "r"(id), "r"(n) : "memory"); }
__device__ __forceinline__ void bar_arrive(int id, int n) { asm volatile("bar.arrive %0, %1;" :: "r"(id), "r"(n) : "memory"); }
__device__ __forceinline__ uint32_t ldg16_if(bool c, const void* p) { uint32_t v; asm volatile("{ .reg .pred p; setp.ne.u32 p, %2, 0; @p ld.global.nc.u16 %0, [%1]; }" : "=r"(v) : "l"(p), "r"((uint32_t)c)); return v; }
__device__ __forceinline__ uint32_t ldg32_if(bool c, const void* p) { uint32_t v; asm volatile("{ .reg .pred p; setp.ne.u32 p, %2, 0; @p ld.global.nc.u32 %0, [%1]; }" : "=r"(v) : "l"(p), "r"((uint32_t)c)); return v; }
__device__ __forceinline__ uint32_t ld_rlx32(const void* p) { uint32_t v; asm volatile("ld.relaxed.gpu.global.u32 %0, [%1];" : "=r"(v) : "l"(p) : "memory"); return v; }
__device__ __forceinline__ uint4 ld_rlx128(const void* p) {
    uint4 v; asm volatile("ld.relaxed.gpu.global.v4.u32 {%0,%1,%2,%3}, [%4];" : "=r"(v.x), "=r"(v.y), "=r"(v.z), "=r"(v.w) : "l"(p) : "memory"); return v;
}
__device__ __forceinline__ void st_rlx32(void* p, uint32_t v) { asm volatile("st.relaxed.gpu.global.u32 [%0], %1;" :: "l"(p), "r"(v) : "memory"); }
__device__ __forceinline__ void stg128(void* p, uint32_t x, uint32_t y, uint32_t z, uint32_t w) {
    asm volatile("st.global.v4.u32 [%0], {%1,%2,%3,%4};" :: "l"(p), "r"(x), "r"(y), "r"(z), "r"(w) : "memory");
}
__device__ __forceinline__ void next_epoch(const Params& p, unsigned e) { if ((threadIdx.x & 31) == 0) p.s->epoch[blockIdx.x * 16 + (threadIdx.x >> 5)] = e + 1; }
__device__ __forceinline__ void sts128z_if(bool c, uint32_t a) { asm volatile("{ .reg .pred p; setp.ne.u32 p, %1, 0; @p st.shared.v4.u32 [%0], {%2,%2,%2,%2}; }" :: "r"(a), "r"((uint32_t)c), "r"(0) : "memory"); }
__device__ __forceinline__ void stg128z_if(bool c, void* a) { asm volatile("{ .reg .pred p; setp.ne.u32 p, %1, 0; @p st.global.v4.u32 [%0], {%2,%2,%2,%2}; }" :: "l"(a), "r"((uint32_t)c), "r"(0) : "memory"); }
__device__ __forceinline__ unsigned clock32() { unsigned c; asm volatile("mov.u32 %0, %clock;" : "=r"(c) :: "memory"); return c; }
__device__ __forceinline__ void until(unsigned t0, int c) { while ((int)(clock32() - t0) < c) { } }
__device__ __forceinline__ float sigmoidf_(float x) { return __fdividef(1.0f, 1.0f + __expf(-x)); }
__device__ __forceinline__ uint32_t key_tag(unsigned epoch) { return ((epoch & 15u) | 16u) << 11; }
__device__ __forceinline__ int key_row(uint32_t key) { return 2047 - (int)(key & 2047u); }
__device__ __forceinline__ uint32_t wait_sel(const Params& p, int s32, int r8, uint32_t tag, uint32_t k = 0) {
#pragma unroll 1
    for (int it = 0; !__all_sync(0xffffffffu, (k & 0xf800u) == tag); it++) {
        k = ld_rlx32(&p.s->sel[s32 * 64 + r8]);
        if (it > (1 << 20)) give_up();
    }
    return k;
}

struct cplx { float re, im; };
__device__ __forceinline__ cplx csq(cplx a) { cplx r; r.re = a.re * a.re - a.im * a.im;
    if (!M2) r.im = (a.re * a.im) * 2.f; else
    asm("{ .reg .f32 t; mul.f32 t, %1, %2; mul.f32 %0, t, 0f40000000; }" : "=f"(r.im) : "f"(a.re), "f"(a.im));
    return r;
}
__device__ __forceinline__ cplx cexpk(float ar, float ai, float k) {
    float mag, s, c;
    asm("ex2.approx.ftz.f32 %0, %1;" : "=f"(mag) : "f"(ar * (k * 1.4426950408889634f)));
    const float r = ai * k;
    asm("sin.approx.ftz.f32 %0, %1;" : "=f"(s) : "f"(r));
    asm("cos.approx.ftz.f32 %0, %1;" : "=f"(c) : "f"(r));
    cplx o; o.re = mag * c; o.im = mag * s; return o;
}
struct h2c { uint32_t re, im; };
__device__ __forceinline__ h2c cmul_cd(h2c v, __half2 c, __half2 d) {
    const __half2 r = *(const __half2*)&v.re, i = *(const __half2*)&v.im;
    const __half2 x = __hfma2(__hneg2(i), d, __hmul2(r, c)), y = __hfma2(i, c, __hmul2(r, d));
    h2c o; o.re = *(const uint32_t*)&x; o.im = *(const uint32_t*)&y; return o;
}
__device__ __forceinline__ h2c cmul_s(h2c v, uint32_t s) { const __half2 h = *(const __half2*)&s; return cmul_cd(v, __low2half2(h), __high2half2(h)); }
__device__ __forceinline__ h2c cmul_sc(h2c v, uint32_t s) {
    const __half2 h = *(const __half2*)&s, c = __low2half2(h), d = __high2half2(h), r = *(const __half2*)&v.re, i = *(const __half2*)&v.im;
    const __half2 x = __hfma2(i, d, __hmul2(r, c)), y = __hfma2(__hneg2(r), d, __hmul2(i, c));
    h2c o; o.re = *(const uint32_t*)&x; o.im = *(const uint32_t*)&y; return o;
}
__device__ __forceinline__ h2c cmul_vc(h2c v, uint32_t s) {
    const __half2 h = *(const __half2*)&s, c = __low2half2(h), d = __high2half2(h), r = *(const __half2*)&v.re, i = *(const __half2*)&v.im;
    const __half2 x = __hfma2(i, d, __hmul2(r, c)), y = __hfma2(__hneg2(i), c, __hmul2(r, d));
    h2c o; o.re = *(const uint32_t*)&x; o.im = *(const uint32_t*)&y; return o;
}

constexpr int UT_HALF = 2560, UT_STRIDE = 4736, GT_HALF = 2240;
__device__ __forceinline__ uint32_t swz(uint32_t x, int c) { return x ^ (((x >> 2) & 64) ^ (64 * (c & 1) + 8 * (c & 6))); }
__device__ __forceinline__ int col(int n) { return (n >> 1) + 4 * (n & 1); }
constexpr int KT_T = 542, KT_C = 552, KT_D = 645, KT_BYTES = 720 * 4;
constexpr int VC_OFF = 80, VE_BASE = 1616;
constexpr int V_STRIDE = (1616 + 1024) * 4 + 80;
constexpr int KG_STAGE = 5248;
constexpr int Y_CS = 2080, Y_RS = 8 * Y_CS + 64;

constexpr int SC_RT = 0;
constexpr int SC_UT = 33408;
constexpr int SC_KG = SC_UT + 8 * UT_STRIDE;
constexpr int SC_KT = SC_KG + 8 * KG_STAGE;
constexpr int SC_GT = SC_KT + 8 * KT_BYTES;
constexpr int SC_V = SC_GT + 4448;
constexpr int SC_MISC = SC_V + 8 * V_STRIDE;
static_assert(V_STRIDE % 128 == 16 && 2 * Y_RS <= SC_UT && SC_UT % 128 == 0 && SC_KG % 128 == 0, "layout");
static_assert(SC_MISC % 16 == 0 && SC_MISC + 512 <= 232192, "layout");

__device__ __forceinline__ void window_task(uint32_t s0, uint32_t s1, uint32_t d0, uint32_t d1, int k) {
    float S[51], s = 0.f;
    uint32_t w[28];
#pragma unroll
    for (int i = 0; i < 7; i++) {
        const uint4 v = lds128(((i < 3 ? s0 : s1) ^ 8 * ((i + 1) & 2)) + ((i & 1) ? 0 : UT_HALF));
        w[4 * i] = v.x; w[4 * i + 1] = v.y; w[4 * i + 2] = v.z; w[4 * i + 3] = v.w;
    }
    auto sums = [&](int lo, int hi) {
#pragma unroll
        for (int i = lo; i < hi; i++) { const float x = (i & 1) ? bf_hi(w[i >> 1]) : bf_lo(w[i >> 1]); s = i > 3 ? s + x : x; S[i] = s; }
    };
    auto put = [&](int off, int b, int o0, int o1, int o2) {
        auto v = [&](int i) { i += 16 * b; return pack_bf16(S[o0 + i] - S[o1 + i], S[o1 + i] - S[o2 + i]); };
#pragma unroll
        for (int i = 0; i < 8; i += 2) sts128((i & 4 ? d1 : d0) + 4 * off + 64 * b + 8 * (i & 2), v(i), v(i + 8), v(i + 1), v(i + 9));
    };
    S[2] = 0.f;
    sums(3, 26); put(VC_OFF - 16, 0, 10, 5, 2);
    if (k == 12) return;
    sums(26, 42); put(VC_OFF - 16, 1, 10, 5, 2);
    if (k < 8) { put(VE_BASE, 0, 19, 12, 3); sums(42, 51); put(VE_BASE, 1, 19, 12, 3); }
}

template <class F>
__device__ __forceinline__ void kgen(const uint32_t (&q)[8], uint32_t sb, int half, uint32_t stage, uint32_t pstage, int barid, int lane, uint32_t (&w)[12], F shadow) {
    const int t = lane & 3, mi = lane >> 3, r8 = lane & 7;
    {
        const uint32_t pAr = q[0], pAi = q[1], pBr = q[2], pBi = q[3], pCr = q[4], pCi = q[5], pDt = q[6], pD = q[7];
        const uint32_t wb = fresh(stage + lane * 16), za = fresh(stage + 5120 + ((lane >> 1) & 3) * 16 + mi * 4 + (lane & 1) * 2), zr = fresh(stage + 5120 + t * 16);
        const uint32_t oB = fresh(stage + 2048 + mi * 512 + r8 * 16), oC = fresh(stage + 4096 + (mi & 1) * 512 + (mi >> 1) * 128 + r8 * 16);
        float acc[6][4];
#pragma unroll
        for (int a = 0; a < 6; a++) { acc[a][0] = acc[a][1] = acc[a][2] = acc[a][3] = 0.f; asm volatile("" : "+f"(acc[a][0]), "+f"(acc[a][1]), "+f"(acc[a][2]), "+f"(acc[a][3])); }
        shadow();
        sts32(zr, clock32());
        const float dt = rbf(__expf(bf_lo(pDt)));
        float ar = dt * bf_lo(pAr), ai = dt * bf_lo(pAi), ar1 = dt * bf_hi(pAr), ai1 = dt * bf_hi(pAi);
        float wr, wi, wr1, wi1;
        { const float br = dt * bf_lo(pBr), bi = dt * bf_lo(pBi), cr = bf_lo(pCr), ci = bf_lo(pCi); wr = cr * br - ci * bi; wi = cr * bi + ci * br; }
        { const float br = dt * bf_hi(pBr), bi = dt * bf_hi(pBi), cr = bf_hi(pCr), ci = bf_hi(pCi); wr1 = cr * br - ci * bi; wi1 = cr * bi + ci * br; }
        const uint32_t ex = max(__reduce_max_sync(0xffffffffu, __float_as_uint(fmaxf(fmaxf(fabsf(wr), fabsf(wi)), fmaxf(fabsf(wr1), fabsf(wi1))))) >> 23, 14u);
        const float scl = __uint_as_float((267u - ex) << 23);
        uint32_t W = pack_f16(wr * scl, wi * -scl);
        const uint32_t W1 = pack_f16(wr1 * scl, wi1 * -scl);
        if (threadIdx.x < 32) TSTAMP(20);

#pragma unroll 1
        for (int r = 0; r < 2; r++) {
            const cplx z1 = cexpk(ar, ai, 1.f), z64 = cexpk(ar, ai, 64.f);
            const cplx z2 = csq(z1), z4 = csq(z2), z8 = csq(z4), z16 = csq(z8), z32 = csq(z16);
            const cplx z128 = csq(z64), z256 = csq(z128), z512 = csq(z256);
            auto put = [&](int grp, h2c a, h2c b, h2c c, h2c d) { sts128(wb + grp * 1024, a.re, b.re, c.re, d.re); sts128(wb + grp * 1024 + 512, a.im, b.im, c.im, d.im); };
            {
                const uint32_t s4 = pack_f16(z4.re, z4.im), s256 = pack_f16(z256.re, z256.im), s512 = pack_f16(z512.re, z512.im);
                auto mix = [](h2c a, h2c b, uint32_t sel) { return h2c{__byte_perm(a.re, b.re, sel), __byte_perm(a.im, b.im, sel)}; };
                const h2c c10 = cmul_vc(h2c{pack_f16(z1.re, 1.f), pack_f16(z1.im, 0.f)}, W), c32 = cmul_sc(c10, pack_f16(z2.re, z2.im)), c54 = cmul_sc(c10, s4);
                put(2, c10, c32, c54, cmul_sc(c32, s4));
                const h2c d20 = cmul_sc(mix(c32, c10, 0x7632), s256), e04 = cmul_sc(mix(c10, c54, 0x7632), s512), f04 = cmul_sc(e04, s256);
                put(3, d20, cmul_sc(d20, s4), e04, f04);
                const h2c ef = mix(e04, f04, 0x5410), gh = cmul_sc(ef, s512), g8 = cmul_sc(gh, pack_f16(z8.re, z8.im));
                put(4, g8, cmul_sc(g8, s512), gh, ef);
            }
            {
                const uint32_t s32 = pack_f16(z32.re, z32.im), s64 = pack_f16(z64.re, z64.im), s128 = pack_f16(z128.re, z128.im);
                const h2c p0 = {pack_f16(1.f, z8.re), pack_f16(0.f, z8.im)}, p1 = cmul_s(p0, pack_f16(z16.re, z16.im)), p2 = cmul_s(p0, s32), p3 = cmul_s(p1, s32);
                put(0, p0, p1, p2, p3);
                sts16(za - 4096, s64); sts16(za - 4032, s64 >> 16);
                sts16(za, s128); sts16(za + 64, s128 >> 16);
            }
            __syncwarp();
            {
                const uint32_t aB = fresh(oB), aC = fresh(oC), aZ = fresh(zr);
                const uint4 zc = lds128(aZ), zd = lds128(aZ + 64);
                const uint32_t zcs[4] = {zc.x, zc.y, zc.z, zc.w}, zds[4] = {zd.x, zd.y, zd.z, zd.w};
                const uint4 yc = lds128(aZ - 4096), yd = lds128(aZ - 4032);
                const uint32_t ycs[4] = {yc.x, yc.y, yc.z, yc.w}, yds[4] = {yd.x, yd.y, yd.z, yd.w};
                uint32_t c[4];
#pragma unroll
                for (int k = 0; k < 4; k++) {
                    uint32_t a[4], b[4];
                    for (int e = 0; e < 2; e++) asm("ldmatrix.sync.aligned.m8n8.x1.trans.shared.b16 {%0}, [%1];" : "=r"(a[2 * e]) : "r"(aB - 2048 + 128 * k + 512 * e));
                    const h2c a1 = cmul_cd(h2c{a[0], a[2]}, *(const __half2*)&ycs[k], *(const __half2*)&yds[k]);
                    a[1] = a1.re; a[3] = a1.im;
                    ldsm4t(b, aB + 128 * k);
                    if (!(k & 1)) ldsm4t(c, aC + 128 * k);
                    const h2c x = cmul_cd(h2c{a[0], a[2]}, *(const __half2*)&zcs[k], *(const __half2*)&zds[k]), y = cmul_cd(h2c{a[1], a[3]}, *(const __half2*)&zcs[k], *(const __half2*)&zds[k]);
                    mma_h(acc[0], a[0], a[1], a[2], a[3], b[0], b[1]);
                    mma_h(acc[1], a[0], a[1], a[2], a[3], b[2], b[3]);
                    mma_h(acc[2], a[0], a[1], a[2], a[3], c[2 * (k & 1)], c[2 * (k & 1) + 1]);
                    mma_h(acc[3], x.re, y.re, x.im, y.im, b[0], b[1]);
                    mma_h(acc[4], x.re, y.re, x.im, y.im, b[2], b[3]);
                    mma_h(acc[5], x.re, y.re, x.im, y.im, c[2 * (k & 1)], c[2 * (k & 1) + 1]);
                }
                asm volatile("" :: "f"(acc[0][0]), "f"(acc[1][0]), "f"(acc[2][0]), "f"(acc[3][0]), "f"(acc[4][0]), "f"(acc[5][0]) : "memory");
            }
            __syncwarp();
            ar = ar1; ai = ai1; W = W1;
        }
        if (threadIdx.x < 32) TSTAMP(21);
        const float i0 = __uint_as_float((ex + 243u) << 23);
        if (half) {
#pragma unroll
            for (int a = 0; a < 6; a++) { acc[a][0] *= i0; acc[a][1] *= i0; acc[a][2] *= i0; acc[a][3] *= i0; }
            if (lane == 0) acc[0][1] -= bf_lo(pD);
#pragma unroll
            for (int a = 0; a < 6; a++) sts128(wb + a * 512, __float_as_uint(acc[a][0]), __float_as_uint(acc[a][1]), __float_as_uint(acc[a][2]), __float_as_uint(acc[a][3]));
            bar_arrive(barid, 64);
        } else {
            bar_sync(barid, 64);
            const uint32_t src = fresh(pstage);
#pragma unroll
            for (int a = 0; a < 6; a++) {
                const uint4 y = lds128(src + lane * 16 + a * 512);
                auto sum = [&](uint32_t x, float c) { return fmaf(c, i0, __uint_as_float(x)); };
                w[4 * (a % 3) + 2 * (a / 3)] = pack_bf16(sum(y.x, acc[a][0]), sum(y.y, acc[a][1]));
                w[4 * (a % 3) + 2 * (a / 3) + 1] = pack_bf16(sum(y.z, acc[a][2]), sum(y.w, acc[a][3]));
            }
            const uint32_t x0 = __shfl_up_sync(0xffffffffu, w[10], 2), x1 = __shfl_up_sync(0xffffffffu, w[11], 2);
            w[10] = w[8];
            if (t >= 2) { w[8] = x0; w[9] = x1; }
        }
    }
}

enum { BC_AUX = 0, BC_U = 5  , BC_Y = 13   };

__device__ __forceinline__ void fetch_gates(const Params& p, int i, int lane, unsigned epoch, uint32_t dst) {
    const uint32_t par = (epoch & 1) ? 0x80008000u : 0u;
    uint4 v;
#pragma unroll 1
    for (int it = 0;; it++) {
        v = ld_rlx128(p.s->gate + 256 * i + 8 * lane);
        v.x ^= par; v.y ^= par; v.z ^= par; v.w ^= par;
        if (__all_sync(0xffffffffu, (v.x & v.y & v.z & v.w & 0x80008000u) == 0x80008000u)) break;
        if (it > (1 << 20)) give_up();
    }
    sts128(dst, v.x, v.y, v.z, v.w);
}
__device__ __forceinline__ void store_rows(const CUtensorMap* m, uint32_t src, int col, int row) {
    asm volatile("cp.async.bulk.tensor.5d.global.shared::cta.bulk_group [%0, {%2, %3, %3, %3, %4}], [%1];" :: "l"(m), "r"(src), "r"(col), "r"(0), "r"(row) : "memory");
}

__device__ __forceinline__ void store_or_add(void* o, const uint32_t (&y)[4], uint32_t add) {
    asm volatile("{ .reg .pred p; setp.ne.u32 p, %5, 0; @!p st.global.v4.u32 [%0], {%1,%2,%3,%4}; @p red.relaxed.gpu.global.add.noftz.v4.bf16x2 [%0], {%1,%2,%3,%4}; }"
                 :: "l"(o), "r"(y[0]), "r"(y[1]), "r"(y[2]), "r"(y[3]), "r"(add) : "memory");
}

__device__ __forceinline__ void conv_aux(const Params& p, const CUtensorMap* mU, uint32_t sb, int aw, int lane, int bid, unsigned epoch) {
    const int g = lane >> 2, t = lane & 3, mi = lane >> 3, r8 = lane & 7;
    const int rank = bid & 1, slab = bid >> 1;
    const uint32_t bar_y = sb + SC_MISC, bar_u = bar_y  , bar_v = bar_y + 8, bar_box = bar_y + 64 + 8 * aw, s_bm = bar_y + 128;
    if (elect()) {
        mbar_init(bar_box, 1); mbar_fence();
        mbar_expect(bar_box, 4096);
        tma4d(sb + SC_RT + 4096 * aw, mU, 16 * slab, 0, 0, 16 * rank + 2 * aw, bar_box);
        mbar_init(bar_y + 8 * aw, aw == 1 ? 8 : 1);
        if (aw == 1) mbar_init(bar_y + 384, 1);
        mbar_fence();
        if (aw != 1) mbar_expect(bar_y + 8 * aw, aw ? 4096 : 16384);
    }
    __syncwarp();
    asm volatile("barrier.cluster.arrive.relaxed.aligned;" ::: "memory");
    asm volatile("setmaxnreg.dec.sync.aligned.u32 88;");
    sts128(sb + (lane < 16 ? SC_UT + aw * UT_STRIDE + mi * (UT_HALF - 128) : SC_V - 256 + aw * V_STRIDE) + lane * 16, 0, 0, 0, 0);
    if (lane < 16) sts128(s_bm + lane * 16, 0, 0, 0, 0);
    {
        const uint32_t dst = sb + SC_UT + g * UT_STRIDE + swz((8 + 64 * rank + 8 * aw + t) * 16, g);
        const uint32_t rdst = mapa(dst, rank ^ 1), rbar = mapa(bar_u, rank ^ 1);
        asm volatile("barrier.cluster.wait.acquire.aligned;" ::: "memory");
        mbar_wait(bar_box);
        if (aw == 0) TSTAMP(1);
        const uint32_t src = fresh(sb + SC_RT) + aw * 4096 + (8 * mi + 4 * (r8 & 1) + (r8 >> 1)) * 32 + ((rank ^ (r8 & 1)) << 4);
        uint32_t x[8][4];
#pragma unroll
        for (int i = 0; i < 4; i++) { ldsm4t(x[i], src + 1024 * i); ldsm4t(x[4 + i], (src ^ 16) + 1024 * i); }
        asm volatile("" :: "r"(x[0][0]), "r"(x[1][0]), "r"(x[2][0]), "r"(x[3][0]) : "memory");
#pragma unroll
        for (int i = 0; i < 4; i++) st_async128((rdst ^ 32 * (i & 2)) + (i & 1) * UT_HALF, x[4 + i][0], x[4 + i][1], x[4 + i][2], x[4 + i][3], rbar);
#pragma unroll
        for (int i = 0; i < 4; i++) sts128((dst ^ 32 * (i & 2)) + (i & 1) * UT_HALF, x[i][0], x[i][1], x[i][2], x[i][3]);
    }
    bar_sync(BC_AUX, 256);
    mbar_wait_cluster(bar_u);
    if (aw == 0) TSTAMP(2);
    if (aw == 6 && elect()) mbar_arrive(bar_y + 384);
    if (aw < 4) bar_sync(BC_U + aw, 64);
    if (aw == 0) TSTAMP(3);
    {
        const uint32_t ws = fresh(sb + SC_UT) + r8 * UT_STRIDE, wd = sb + SC_V + r8 * V_STRIDE;
#pragma unroll 1
        for (int k = aw; k < 13; k += 8) {
            const int a = 8 * k + (k < 12 ? g & 6 : 0);
            const uint32_t d = wd + 64 * a, sw = 16 * (a & 2);
            window_task(ws + swz(16 * a + 96, r8), ws + swz(16 * a + 128, r8), d + sw, d + (sw ^ 32), k);
            if ((k & 12) == 4) bar_arrive(BC_U + k - 4, 64);
        }
    }
    if (aw == 0) TSTAMP(9);
    {
        if (aw >= 2) fetch_gates(p, aw, lane, epoch, sb + SC_GT + (lane & 1) * GT_HALF + (8 + 16 * aw + (lane >> 1)) * 16);
        __syncwarp();
        if (elect()) { mbar_arrive(bar_v); prefetch_map(mU + 4); p.s->epoch[fresh(bid) * 16 + aw + 8] = epoch + 1; }
        if (aw == 0) TSTAMP(4);
        if (aw == 7) {
            const int row = key_row(wait_sel(p, slab >> 1, r8, key_tag(epoch)));
            if (lane < 8) asm volatile("red.shared.or.b32 [%0], %1;" :: "r"(s_bm + (row >> 5) * 4), "r"(1u << (row & 31)) : "memory");
            TSTAMP(10);
        }
        bar_sync(BC_AUX, 256);
        const uint32_t src = sb + SC_RT + ((r8 >> 1) & 1) * Y_RS + (2 * mi + (r8 & 1)) * Y_CS + (2 * aw + (r8 >> 2)) * 16;
        const int rb = 64 * (aw & 4) + 32 * (aw & 1) + ((aw >> 1) & 1) + 2 * rank, row0 = rb + 128 * (g >> 2) + 16 * (t >> 1) + 64 * (g & 1) + 8 * ((g >> 1) & 1);
        __nv_bfloat16* outp = p.out + (size_t)row0 * DM + 16 * slab + 8 * (t & 1);
        const uint32_t stg = sb + SC_KG + 4096 * aw, so = (g & 2) * 256 + (g >> 2) * 128 + r8 * 16;
#pragma unroll 1
        for (int s = 1; s < 4; s++) {
            const uint32_t bm = lds32(fresh(s_bm) + (16 * s + (row0 >> 5)) * 4) >> (row0 & 31);
            const bool routed = __any_sync(0xffffffffu, bm & 0x11u);
            if ((aw & 3) == s) mbar_wait_cluster(bar_y + 16 * s + 2 * (aw & 4));
            bar_sync(BC_Y + (aw >> 2), 128);
            const uint32_t sf = fresh(src) + 512 * s;
            uint32_t y[2][4];
            ldsm4t(y[0], sf); ldsm4t(y[1], sf + 256);
            if (routed) {
#pragma unroll
                for (int k = 0; k < 2; k++) store_or_add(outp + (size_t)(512 * s + 4 * k) * DM, y[k], bm & (1u << (4 * k)));
            } else {
                sts128(stg + so + 1024 * s, y[0][0], y[0][1], y[0][2], y[0][3]); sts128(stg + so + 1024 * s + 256, y[1][0], y[1][1], y[1][2], y[1][3]);
                asm volatile("fence.proxy.async.shared::cta;" ::: "memory");
                __syncwarp();
                if (elect()) store_rows(mU + 4, stg + 1024 * s, 16 * slab, 512 * s + rb);
            }
            if (aw == 4) TSTAMP(16 + s);
            if (aw == 0) TSTAMP(16);
        }
        if (elect()) { asm volatile("cp.async.bulk.commit_group;" ::: "memory"); asm volatile("cp.async.bulk.wait_group.read 0;" ::: "memory"); }
        if (aw == 4) TFLUSH();
    }
}

__device__ __forceinline__ uint32_t k_tag(unsigned epoch) { return epoch << 16 | 0x80000000u; }
__device__ __forceinline__ void publish_k(uint4* kp, const uint32_t (&w)[12], unsigned epoch, uint64_t (&v)[6]) {
#pragma unroll
    for (int i = 0; i < 3; i++) {
        v[2 * i] = w[3 * i] | (uint64_t)w[3 * i + 1] << 32; v[2 * i + 1] = w[3 * i + 2] | (uint64_t)__byte_perm(w[9 + (i >> 1)], k_tag(epoch), i == 1 ? 0x7632 : 0x7610) << 32;
        asm volatile("st.relaxed.gpu.global.v2.u64 [%0], {%1,%2};" :: "l"(kp + 32 * i), "l"(v[2 * i]), "l"(v[2 * i + 1]));
    }
}
template <bool FULL>
__device__ __forceinline__ void k_tables(uint32_t kt, int lane, const uint32_t (&w)[12]) {
    const int g = lane >> 2, t = lane & 3, mi = lane >> 3, r8 = lane & 7;
    uint32_t x3 = w[7], re[4], rx[4];
#pragma unroll
    for (int i = 0; i < 4; i++) {
        re[i] = __shfl_sync(0xffffffffu, w[i], lane + 31);
        rx[i] = __shfl_sync(0xffffffffu, w[4 + i], lane + (i == 0 && lane == 29 ? 5 : 1 + 2 * t));
    }
    if (FULL) {
        asm volatile("stmatrix.sync.aligned.m8n8.x2.trans.shared.b16 [%0], {%1,%2};" :: "r"(kt + (KT_D + 7) * 4 + 64 * t + 16 * (mi & 1) + 8 * (r8 & 4)), "r"(w[8]), "r"(w[9]) : "memory");
        if (lane == 2) {
            sts32(kt + (KT_C + 78) * 4, w[10] & 0xffffu);
            sts128(kt + (KT_T + 2) * 4, 0, w[10] & 0xffffu, __byte_perm(w[10], 0, 0x1010), w[10] << 16);
        }
        if (lane == 29) x3 = bsub2(x3, rx[0] & 0xffffu);
    }
#pragma unroll
    for (int i = 0; i < 4; i++) {
        sts64(kt + (16 + 64 * i) * 4 + 8 * lane, __byte_perm(w[i], lane ? re[i] : i ? re[i - 1] : 0, 0x5432), w[i]);
        const uint32_t x = i < 3 ? w[4 + i] : x3, aa = __byte_perm(x, 0, 0x3232);
        if (t < 2) sts128(kt + (272 + 64 * i + 8 * g + 4 * t) * 4, i == 0 && lane == 0 ? __byte_perm(x, re[3], 0x5432) : aa, aa, x,
                          __byte_perm(lane != 29 ? rx[i] : i < 3 ? rx[(i + 1) & 3] : FULL ? 0 : rx[0] << 16, x, 0x5432));
        else if (FULL) sts32(kt + (KT_C - 50 + 8 * i + 32 * t + g) * 4, x);
    }
}

__device__ __forceinline__ void conv_main(const Params& p, uint32_t sb, int warp, int lane0, int bid, unsigned epoch, uint32_t (&w)[12]) {
    asm volatile("setmaxnreg.inc.sync.aligned.u32 168;");
    const int lane = __shfl_sync(0xffffffffu, lane0, lane0);
    const int g = lane >> 2, t = lane & 3, mi = lane >> 3, r8 = lane & 7;
    const int rank = bid & 1;
    const uint32_t bar_y = sb + SC_MISC, bar_v = bar_y + 8;
    next_epoch(p, epoch);
    asm volatile("barrier.cluster.wait.acquire.aligned;" ::: "memory");
    if (warp >= 4) {
        mbar_wait(bar_y + 384);
        if (KPOLL) until(clock32(), KPOLL);
        const uint4* src = p.s->kp + (8 * bid + warp) * 96 + lane0;
#pragma unroll 1
        for (int it = 0;; it++) {
            uint32_t bad = 0, e[3];
#pragma unroll
            for (int i = 0; i < 3; i++) { const uint4 v = ld_rlx128(src + 32 * i); w[3 * i] = v.x; w[3 * i + 1] = v.y; w[3 * i + 2] = v.z; e[i] = v.w; bad |= v.w ^ k_tag(epoch); }
            w[9] = __byte_perm(e[0], e[1], 0x5410); w[10] = e[2];
            const bool ok = __all_sync(0xffffffffu, bad < 65536);
            if (ok) break;
            if (it > (1 << 20)) give_up();
        }
    }
    if ((warp & 3) == 0) TSTAMP(5 + (warp >> 2));
    k_tables<true>(sb + SC_KT + warp * KT_BYTES, lane0, w);
    mbar_wait(bar_y + 384);
    __syncwarp();
    if ((warp & 3) == 0) TSTAMP(7 + (warp >> 2));
    {
        const uint32_t ut = fresh(sb + SC_UT) + warp * UT_STRIDE, kt = fresh(sb + SC_KT) + warp * KT_BYTES;
        auto dup = [&](uint32_t v) { return v ^ p.zero; };
        auto frag = [&](uint32_t (&a)[4], uint32_t x) { a[0] = lds32(x); a[1] = lds32(x + 32); a[2] = lds32(x - 32); a[3] = dup(a[0]); };
        const uint32_t kb = kt + (16 + g - 2 * t) * 4;
        float acc[16][4];
        {
            float y[12][4], M[6][4];
#pragma unroll
            for (int i = 0; i < 12; i++) { y[i][0] = y[i][1] = y[i][2] = y[i][3] = 0.f; M[i >> 1][0] = M[i >> 1][1] = M[i >> 1][2] = M[i >> 1][3] = 0.f; }
            uint32_t U[10][4], a1[4], ad[4], R = (mi & 1) * UT_HALF + (8 + (r8 >> 1) + 48 * (r8 & 1)) * 16 + 64 * (mi >> 1);
            auto places = [&] { ad[0] = swz(R, warp); ad[1] = swz(R + 128, warp); ad[2] = ad[0] ^ 64; ad[3] = ad[1] ^ 64; };
            auto ldu = [&](int k) { ldsm4(U[k], ut + ad[k & 3] + 256 * (k >> 1)); };
            places();
            frag(a1, kb + 2048);
#pragma unroll
            for (int k = 0; k < 7; k++) ldu(k);
#pragma unroll
            for (int i = 0; i < 12; i++) mma_bf(y[i], a1[0], a1[1], a1[2], a1[3], U[i >> 1][2 * (i & 1)], U[i >> 1][2 * (i & 1) + 1]);
            frag(a1, kb + 1792);
            __syncwarp();
#pragma unroll 1
            for (uint32_t ko = 0; ko != 256;) {
                ko = fresh(ko);
                const uint32_t kp = kb + ko;
                ko += 64;
                uint32_t se[10][2], so[10][2], ue[10][2];
                auto sums = [&](int k) {
#pragma unroll
                    for (int e = 0; e < 2; e++) { ue[k][e] = U[k][e]; se[k][e] = badd2(U[k][e], U[k - 1][2 + e]); so[k][e] = badd2(U[k][e], U[k][2 + e]); }
                };
#pragma unroll
                for (int k = 1; k < 6; k++) sums(k);
#pragma unroll
                for (int m = 3; m >= 0; m--) {
                    uint32_t a0[4];
                    frag(a0, kp + 512 * m);
                    sums(9 - m);
                    if (m) ldu(10 - m); else { R -= 16; places(); }
#pragma unroll
                    for (int i = 0; i < 6; i++) mma_bf(y[2 * i], a1[0], a1[1], a1[2], a1[3], se[i - m + 4][0], se[i - m + 4][1]);
#pragma unroll
                    for (int e = 0; e < 4; e++) a1[e] = bsub2(a0[e], a1[e]);
#pragma unroll
                    for (int i = 0; i < 6; i++) { mma_bf(M[i], a1[0], a1[1], a1[2], a1[3], ue[i - m + 4][0], ue[i - m + 4][1]); if (!m) ldu(i); }
                    frag(a1, m ? kp + 512 * m - 256 : kp + 1792 + 64);
                    if (!m) ldu(6);
#pragma unroll
                    for (int i = 0; i < 6; i++) mma_bf(y[2 * i + 1], a0[0], a0[1], a0[2], a0[3], so[i - m + 4][0], so[i - m + 4][1]);
                }
            }
#pragma unroll
            for (int i = 0; i < 6; i++)
#pragma unroll
                for (int c = 0; c < 4; c++) { acc[4 + i + 6 * (c & 1)][c & 2] = y[2 * i][c] + M[i][c]; acc[4 + i + 6 * (c & 1)][c | 1] = y[2 * i + 1][c] - M[i][c]; }
        }
        const uint32_t lo = (8 + col(r8)) * 16 + (mi >> 1) * 128, ua = fresh(ut) + (mi & 1) * UT_HALF, u1[2] = {ua + swz(lo, warp), ua + (swz(lo, warp) ^ 64)};
        {
            uint32_t e[4];
            frag(e, kb + (KT_T - 16) * 4);
            const uint32_t f0 = dup(e[1]), f1 = lds32(kb + KT_T * 4), uo = fresh(ut) + UT_HALF + swz((7 + 8 * mi + col(r8)) * 16, warp);
#pragma unroll
            for (int i = 0; i < 4; i++) {
                uint32_t b[4];
                if (i < 2) {
                    ldsm4(b, uo + 512 * i);
#pragma unroll
                    for (int k = 0; k < 4; k++) mma_bf8(acc[8 + 4 * i + k], f0, f1, b[k]);
                }
                ldsm4(b, u1[i & 1] + 256 * i);
                mma_bf(acc[2 * i + 8], e[0], e[1], e[2], e[3], b[0], b[1]); mma_bf(acc[2 * i + 9], e[0], e[1], e[2], e[3], b[2], b[3]);
            }
        }
        if ((warp & 3) == 0) TSTAMP(11 + (warp >> 2));
        mbar_wait(bar_v);
        const uint32_t vt = fresh(sb + SC_V) + warp * V_STRIDE;
        const uint32_t g1 = fresh(sb + SC_GT) + (mi & 1) * GT_HALF + lo;
        const uint32_t ydst = mapa(sb + SC_RT + rank * Y_RS + warp * Y_CS + (lane & 23) * 16, mi & 1), ybr = mapa(bar_y, mi & 1);
        uint32_t ug[2][2][4];
        auto ld_ug = [&](int i) { ldsm4t(ug[i & 1][0], u1[i & 1] + 256 * i); ldsm4t(ug[i & 1][1], g1 + 256 * i); };
        auto ship = [&](int i) {
            const uint32_t (&u)[4] = ug[i & 1][0], (&gg)[4] = ug[i & 1][1];
            const uint32_t y0 = gmix(gg[0], acc[2 * i][0], acc[2 * i][1], u[0]), y1 = gmix(gg[1], acc[2 * i][2], acc[2 * i][3], u[1]);
            const uint32_t y2 = gmix(gg[2], acc[2 * i + 1][0], acc[2 * i + 1][1], u[2]), y3 = gmix(gg[3], acc[2 * i + 1][2], acc[2 * i + 1][3], u[3]);
            st_async128(ydst + 512 * (i >> 1) + 128 * (i & 1), y0, y1, y2, y3, ybr + 8 * i);
        };
        const uint32_t VD = vt + (VC_OFF - 400 - 16 * t) * 4 + (8 * g ^ 16 * (-t & 2)), VD2 = vt + (VC_OFF - 415 - 16 * t) * 4 + (8 * g ^ 16 * (~t & 2));
        uint2 bd[10];
        uint32_t x[2][4][4];
        auto ld4 = [&](uint32_t (&v)[4], int dl) { const uint2 w = lds64(VD + 256 * dl); v[0] = w.x; v[1] = w.y; v[2] = lds32(VD2 + 256 * dl); v[3] = dup(w.x); };
        auto mm4 = [&](const uint32_t (&v)[4], int dl) {
#pragma unroll
            for (int s = dl & 1; s < 10; s += 2) if ((dl + s) / 2 >= 4 && (dl + s) / 2 < 16) mma_bf(acc[(dl + s) / 2], v[0], v[1], v[2], v[3], bd[s].x, bd[s].y);
        };
        const uint32_t KE = kt + (KT_D + col(g) + t) * 4, VE = vt + (VE_BASE - 912 - 16 * t) * 4 + (8 * g ^ 16 * (~t & 2));
        uint32_t b0[8], b1[8];
        auto ld8 = [&](uint32_t (&v)[4], int dl) { const uint2 w = lds64(VE + 512 * dl), z = lds64(VE + 512 * dl - 256); v[0] = w.x; v[1] = w.y; v[2] = z.x; v[3] = z.y; };
        auto mm8 = [&](const uint32_t (&v)[4], int dl, int lo, int hi) {
#pragma unroll
            for (int s = 0; s < 8; s++) if (dl + s >= lo && dl + s < hi) mma_bf(acc[dl + s], v[0], v[1], v[2], v[3], b0[s], b1[s]);
        };
        ld4(x[0][0], 6);
#pragma unroll
        for (int s = 0; s < 10; s++) bd[s] = lds64(kt + (KT_C + 2 * col(g) + 2 * t + 8 * s) * 4);
        mm4(x[0][0], 6);
        uint32_t e[8][4];
#pragma unroll
        for (int k = 1; k < 6; k++) {
#pragma unroll
            for (int j = 0; j < 4; j++) ld4(x[k & 1][j], 4 * k + 3 + j);
            ld_ug(k + 1);
            if (k == 3) {
#pragma unroll
                for (int s = 0; s < 8; s++) { b0[s] = lds32(KE + 32 * s); b1[s] = lds32(KE + 32 * s + 16); }
            }
            if (k > 1) ship(k);
#pragma unroll
            for (int j = 0; j < 4; j++) {
                mm4(x[k & 1][j], 4 * k + 3 + j);
                if (k == 3) { ld8(e[j], 8 + j); mm8(e[j], 8 + j, 8, 14); }
                if (k == 5 && j < 2) { ld8(e[4 + j], 12 + j); mm8(e[4 + j], 12 + j, 12, 14); }
            }
        }
        ld_ug(7);
        {
            float (&q0)[4] = acc[0], (&q1)[4] = acc[1];
#pragma unroll
            for (int c = 0; c < 4; c++) q0[c] = q1[c] = 0.f;
            auto m8 = [&](float (&c)[4], int T, int j) { mma_bf(c, e[j][0], e[j][1], e[j][2], e[j][3], b0[T - 8 - j], b1[T - 8 - j]); };
            auto m4 = [&](float (&c)[4], int T, int j) { mma_bf(c, x[0][j][0], x[0][j][1], x[0][j][2], x[0][j][3], bd[2 * T - 27 - j].x, bd[2 * T - 27 - j].y); };
            ship(6);
            ld8(e[6], 14); ld8(e[7], 15);
#pragma unroll
            for (int j = 0; j < 4; j++) ld4(x[0][j], 27 + j);
            m8(q1, 15, 0); m8(q0, 14, 0); m8(q1, 15, 1);
            m8(acc[15], 15, 6); m4(q1, 15, 0); m8(acc[14], 14, 6); m4(q0, 14, 0);
            m8(acc[15], 15, 4); m8(q1, 15, 2); m4(acc[14], 14, 1); m8(q0, 14, 1);
            m4(acc[15], 15, 1); m4(q1, 15, 2); m8(acc[14], 14, 4); m8(q0, 14, 2);
            m8(acc[15], 15, 5); m8(q1, 15, 3); m8(acc[14], 14, 5); m8(q0, 14, 3);
            m4(acc[15], 15, 3); m8(q1, 15, 7);
#pragma unroll
            for (int c = 0; c < 4; c++) { acc[14][c] += q0[c]; acc[15][c] += q1[c]; }
            ship(7);
        }
        if ((warp & 3) == 0) TSTAMP(14 + (warp >> 2)); else TSTAMP(21 + warp);
    }
}

constexpr int SF_WD = 73728;
constexpr int SF_RED = 49152;
constexpr int MU_STRIDE = 1168  , SM_RAW = 98304, SM_UT = SM_RAW + 16384, SM_G = SM_UT + 21504, SM_Y = 196608, SM_FT = SM_Y + 17024, SM_KT = 138880, SM_KW = SM_G - 49152;
constexpr int SF_XS = 221184;
constexpr int SF_MISC = SF_XS + 8 * 1168;
constexpr int SF_KG = SF_MISC - 10 * KG_STAGE;
constexpr int SF_WR = SF_KG - 2304;
constexpr int FB_X = 64, FB_KDONE = 72, FB_KEYS = 80, FB_FREE = 88  , FB_W = 104, FB_D = FB_W + 72, FB_MU = FB_D + 96, FB_FAR = FB_MU - 16, FB_MG = FB_MU + 8, FB_MT = FB_MU + 16  , FS_PART = 512, FS_TOK = 896, FS_BM = 1024;
enum { BAR_R = 7, BAR_GU = 8, BAR_RED = 9, BAR_R2 = 10, BAR_G = 12  , BAR_M = 15 };
static_assert(SF_KG % 128 == 0 && NPRE <= 8 && SM_KT + 4 * 2112 <= 147456 && SM_G + MU_STRIDE <= SF_WR - 4 * 9216 && SM_KW + 6 * 2112 >= SM_RAW && SM_KW + 12 * 2112 <= SM_UT, "layout");

__device__ __forceinline__ constexpr int box_no(int i) { return (0x987610ba5432ull >> (4 * i)) & 15; }
__device__ __forceinline__ int role(int b) { b -= NCONV; return b < NX ? b : 18 + (b >> 1) + 12 * (b & 1); }
__device__ __forceinline__ int mini_ch0(int f) { return 48 * f - (f < NW ? 1696 : 2304); }

__device__ __forceinline__ void ffn_front(const Params& p, const CUtensorMap* maps, uint32_t sb, int warp, int lane, int f, unsigned epoch) {
    const unsigned t0 = clock32();
    const int g = lane >> 2, t = lane & 3, mi = lane >> 3, r8 = lane & 7;
    const bool isx = f < NX;
    const int nrw = f < 52 ? 4 : 6, r0 = f < 52 ? 32 * f : 48 * f - 832;
    const int rw = warp < 12 ? 13 - warp : warp ^ (warp < 14 ? 10 : 15);
    const uint32_t bar_row = sb + SF_MISC  , bar_x = bar_row + FB_X;
    const uint32_t s_part = bar_row + FS_PART  , s_tok = bar_row + FS_TOK  ;
    const uint32_t rows = sb + SF_WR - 9216 * (rw + 1) - (rw & 4) * ((SF_WR - 6 * 9216) / 4);
    {
#pragma unroll 1
        for (int i = warp < 10 ? 30 : warp - 10; i < 30; i += 6) if (elect()) mbar_init(bar_x + 8 * i, i == 1 ? 4 + (f < NW) : i < 27 ? 1 : i == 27 ? 2 : 8);
        const uint32_t bytes = rw < 6 ? 9216 : 1152, dst = rw < 6 ? rows : sb + SF_WR + (rw & 1) * 1152;
        const __nv_bfloat16* src = rw < 6 ? p.u + (size_t)(r0 + 8 * rw) * DM : (rw & 1) ? p.gatew : p.wr;
        if (elect()) { mbar_init(bar_row + 8 * rw, 1); mbar_fence(); mbar_expect(bar_row + 8 * rw, bytes); }
        if (warp == 13) { sts32(s_part + 64 + lane * 4, 0); sts32(bar_row + FS_BM + lane * 4, 0); }
        bar_sync(0, NTHR);
        if (!isx) asm volatile("barrier.cluster.arrive.relaxed.aligned;" ::: "memory");
        if (rw < nrw) until(t0, RDELAY);
        if (rw < nrw || rw >= 6) { if (elect()) bulk_g2s(dst, src, bytes, bar_row + 8 * rw); }
    }
    uint4* const kdst = p.s->keys + (lane >> 1) * 128 + 2 * f + (lane & 1);
    if (warp == 15) TSTAMP(1);

    if (warp == 12) {
        if (lane < 22) mbar_expect(bar_row + FB_W + 8 * lane, lane < 9 ? 24576 : isx ? 12288 : lane < 20 ? 2048 : 16384);
        if (elect()) { prefetch_map(maps + 1); prefetch_map(maps + 2); prefetch_map(maps + (isx ? 3 : 5)); }
        unsigned tb = t0 + WDELAY;
        auto pieces = [&](int n, int end, uint32_t dst) {
#pragma unroll 1
            for (; n < end; n++, dst += 12288) {
                until(tb, 0); tb += WGAP;
                if (elect()) tma3d(dst, maps + 1 + (n & 1), 0, 64 * (n >> 1), 3 * f, bar_row + FB_W + 8 * (n >> 1));
            }
        };
        if (!isx) {
#pragma unroll 1
            for (int k = 0; k <= (f >= NW); k++) { until(t0, MDELAY + k * MGAP); if (elect()) tma4d(sb + SM_RAW - 49152 * k, maps + 5, mini_ch0(f) + 16 * k, 0, 0, 0, bar_row + FB_MU - 8 * k); }
            if (f >= NW) return;
        }
#pragma unroll 1
        for (int i = 0; i < 4; i++) {
            if (i == 1) { mbar_wait(bar_row + FB_KEYS); mbar_wait(bar_row + FB_KDONE); tb = clock32() + RESUME; }
            if (i == 3) mbar_wait(bar_row + FB_FREE);
            const int n = ((0x0c080000 + NPRE * 256) >> (8 * i)) & 255;
            pieces(n, ((0x120c0800 + NPRE) >> (8 * i)) & 255, sb + 12288 * (((0x000c0000 + NPRE * 256) >> (8 * i)) & 255));
        }
        TSTAMP(12);
        if (isx) {
#pragma unroll 1
            for (int i = 0; i < 12; i++) {
                const int n = box_no(i);
                if (i == 6) mbar_wait(bar_row + FB_FREE + 8);
                until(tb, 0); tb += DGAP;
                if (elect()) tma2d(sb + SF_WD + n * 12288, maps + 3, 32 * (f >> 1), 2304 * (f & 1) + 192 * n, bar_row + FB_D + 8 * n);
            }
            TSTAMP(13);
        }
    } else if (warp == 13) {
        const uint32_t tag = key_tag(epoch), par = (epoch & 1) ? 0u : 0x8000u;
        stg128(kdst, 0, 0, 0, 0);
        if (lane < 8 && isx && !(f & 1)) st_rlx32(&p.s->sel[32 * f + lane], 0);
        bar_sync(BAR_R, 32 * (nrw + 1));
        TSTAMP(3);
        {
            const uint32_t sg = fresh(s_part) + 192 + lane * 4;
            const uint32_t gb = pack_bf16(sigmoidf_(rbf(__uint_as_float(lds32(sg)))), sigmoidf_(rbf(__uint_as_float(lds32(sg + 128))))) | par | (par << 16);
            asm volatile("st.relaxed.gpu.global.u16 [%0], %1;" :: "l"(p.s->gate + r0 + lane), "h"((unsigned short)gb) : "memory");
            if (nrw > 4 && lane < 16) asm volatile("st.relaxed.gpu.global.u16 [%0], %1;" :: "l"(p.s->gate + r0 + 32 + lane), "h"((unsigned short)(gb >> 16)) : "memory");
        }
        bar_sync(BAR_R2, 32 * (nrw + 1));
        {
            const uint4 v = lds128(fresh(s_tok) + (lane & 1) * 16);
            asm volatile("st.relaxed.gpu.global.v4.u32 [%0], {%1,%2,%3,%4};" :: "l"(kdst), "r"(v.x | tag), "r"(v.y | tag), "r"(v.z | tag), "r"(v.w | tag) : "memory");
        }
        TSTAMP(4);
        if (lane == 0) { mbar_arrive(bar_row + FB_KEYS); mbar_expect(bar_x, 8 * 1152); }
        if (f >= NW) return;
        mbar_wait(bar_row + FB_KDONE);
        uint32_t k[16];
        const uint4* src = p.s->keys + (f & 15) * 128 + lane;
#pragma unroll 1
        for (int it = 0;; it++) {
            uint32_t bad = 0;
#pragma unroll
            for (int i = 0; i < 4; i++) {
                const uint4 x = ld_rlx128(src + (i < 3 || lane < 24 ? 32 * i : 64));
                k[i] = x.x; k[4 + i] = x.y; k[8 + i] = x.z; k[12 + i] = x.w;
                bad |= x.x ^ tag;
            }
            const bool ok = __all_sync(0xffffffffu, (bad & 0xf800u) == 0);
            if (ok) break;
            if (it > (1 << 20)) give_up();
        }
        TSTAMP(5);
        uint32_t key = 0, m = __reduce_max_sync(0xffffffffu, max(max(k[0], k[1]), max(k[2], k[3])));
#pragma unroll 2
        for (int r = 0; r < 8; r++) {
            bool pop[4];
#pragma unroll
            for (int i = 0; i < 4; i++) { pop[i] = k[i] == m; k[i] = pop[i] ? k[4 + i] : k[i]; }
            const uint32_t mn = __reduce_max_sync(0xffffffffu, max(max(k[0], k[1]), max(k[2], k[3])));
            if (elect()) bulk_g2s(sb + SF_XS + r * 1168, p.u + (size_t)key_row(m) * DM, 1152, bar_x);
#pragma unroll
            for (int i = 0; i < 4; i++) { k[4 + i] = pop[i] ? k[8 + i] : k[4 + i]; k[8 + i] = pop[i] ? k[12 + i] : k[8 + i]; k[12 + i] = pop[i] ? 0 : k[12 + i]; }
            if (r8 == r) key = m;
            m = mn;
        }
        const int row = key_row(key);
        sts32(s_tok + r8 * 8, row);
        TSTAMP(6);
        if (isx) {
            if (!(f & 1)) {
                __nv_bfloat16* o = p.out + (size_t)row * DM + 16 * f + 8 * mi;
                asm volatile("st.relaxed.gpu.global.v4.u32 [%0], {%1,%1,%1,%1};" :: "l"(o), "r"(0) : "memory");
                if (__any_sync(0xffffffffu, ld_rlx32(o) != 0)) give_up();
                if (lane < 8) st_rlx32(&p.s->sel[32 * f + lane], key);
            } else wait_sel(p, f >> 1, r8, tag);
            uint32_t gb;
#pragma unroll 1
            for (int it = 0;; it++) {
                asm volatile("ld.relaxed.gpu.global.u16 %0, [%1];" : "=r"(gb) : "l"(p.s->gate + row) : "memory");
                gb ^= par;
                if (!(gb & 0x8000u)) break;
                if (it > (1 << 20)) give_up();
            }
            const uint32_t rb = key ^ 0x80000000u, rv = (rb ^ (((int)rb >> 31) & 0x7fff0000u)) & 0xffff0000u;
            sts32(s_tok + r8 * 8 + 4, __float_as_uint(rbf(1.0f - bf_lo(gb)) * rbf(sigmoidf_(__uint_as_float(rv)))));
            __syncwarp();
            TSTAMP(7);
            bar_arrive(BAR_RED, 416);
        }
    } else {
        if (rw < nrw) {
            float c[3][4];
#pragma unroll
            for (int i = 0; i < 3; i++) { c[i][0] = c[i][1] = c[i][2] = c[i][3] = 0.f; }
            mbar_wait(bar_row + 48); mbar_wait(bar_row + 56);
            const uint32_t b = fresh(sb + SF_WR) + (g & 1) * 1152 + (g >> 2) * 64 + t * 16 + (g & 2) * 2;
            uint32_t w[18][2];
#pragma unroll
            for (int kb = 0; kb < 18; kb++) { const uint32_t o = ((kb & 1) ? b ^ 64 : b) + 128 * (kb >> 1); w[kb][0] = lds32(o); w[kb][1] = lds32(o + 8); }
            mbar_wait(bar_row + 8 * rw);
            if (warp == 15) TSTAMP(2);
            const uint32_t a = fresh(rows) + g * 1152 + (g & 1) * 64 + t * 16;
#pragma unroll
            for (int kb = 0; kb < 18; kb++) {
                const uint4 x = lds128(((kb & 1) ? a ^ 64 : a) + 128 * (kb >> 1));
                mma_bf(c[kb % 3], x.x, x.y, x.z, x.w, w[kb][0], w[kb][1]);
            }
            const float sr = c[0][0] + c[1][0] + c[2][0] + __shfl_down_sync(0xffffffffu, c[0][2] + c[1][2] + c[2][2], 1);
            const float sg = c[0][1] + c[1][1] + c[2][1] + __shfl_down_sync(0xffffffffu, c[0][3] + c[1][3] + c[2][3], 1);
            const uint32_t rb = pack_bf16(0.f, sr);
            if (t == 2 * (g & 1)) {
                sts32(s_part + (8 * rw + g) * 4, (rb ^ (((int)rb >> 31) & 0x7fff0000u) ^ 0x80000000u) | (uint32_t)(2047 - r0 - 8 * rw - g));
                sts32(s_part + 192 + (8 * rw + g) * 4, __float_as_uint(sg));
            }
            __syncwarp();
            bar_sync(BAR_R, 32 * (nrw + 1));
            const uint32_t sk = fresh(s_part), kk = lds32(sk + (8 * rw + r8) * 4);
            int n = 0;
#pragma unroll
            for (int i = 0; i < 3; i++) { const uint4 v = lds128(sk + mi * 48 + 16 * i); n += (v.x > kk) + (v.y > kk) + (v.z > kk) + (v.w > kk); }
            n += __shfl_xor_sync(0xffffffffu, n, 8); n += __shfl_xor_sync(0xffffffffu, n, 16);
            if (n < 8) sts32(s_tok + 4 * n, kk);
            __syncwarp();
            bar_arrive(BAR_R2, 32 * (nrw + 1));
        }
    }
}

__device__ __forceinline__ void ffn_work(const Params& p, uint32_t sb, int warp, int lane, int f, unsigned epoch) {
    const int g = lane >> 2, t = lane & 3, mi = lane >> 3, r8 = lane & 7;
    const bool isx = f < NX;
    const uint32_t bar_x = sb + SF_MISC + FB_X, bar_free = sb + SF_MISC + FB_FREE, bar_w = sb + SF_MISC + FB_W, bar_d = sb + SF_MISC + FB_D, s_tok = sb + SF_MISC + FS_TOK;
    uint32_t fr[24][4];
    auto pin = [&] {
#pragma unroll
        for (int i = 0; i < 24; i += 8) asm volatile("" :: "r"(fr[i][0]), "r"(fr[i + 1][0]), "r"(fr[i + 2][0]), "r"(fr[i + 3][0]), "r"(fr[i + 4][0]), "r"(fr[i + 5][0]), "r"(fr[i + 6][0]), "r"(fr[i + 7][0]) : "memory");
    };
    {
        const int j = (unsigned)(warp - 4) < 6, w = warp - (j ? 4 : warp < 4 ? 0 : 6);
        float ag[2][4], au[2][4];
#pragma unroll
        for (int i = 0; i < 2; i++) { ag[i][0] = ag[i][1] = ag[i][2] = ag[i][3] = 0.f; au[i][0] = au[i][1] = au[i][2] = au[i][3] = 0.f; }
        const uint32_t wb = sb + (w >> 1) * 4096 + (r8 + 8 * (mi >> 1)) * 64 + (((2 * (w & 1) + (mi & 1)) ^ (r8 >> 1)) << 4);
        const uint32_t xb = sb + SF_XS + r8 * 1168 + mi * 16;
        auto load = [&](int i, int n, int place) {
            mbar_wait(bar_w + 8 * n);
            const uint32_t wk = fresh(wb) + place * 24576;
#pragma unroll
            for (int s = 0; s < 4; s++) { ldsm4t(fr[8 * i + s], wk + 1024 * s); ldsm4t(fr[8 * i + 4 + s], wk + 1024 * s + 12288); }
        };
        auto mul = [&](int i, uint32_t xk) {
            uint32_t x[2][4];
            ldsm4(x[0], xk); ldsm4(x[1], xk + 64);
#pragma unroll
            for (int s = 0; s < 4; s++) {
                const uint32_t (&a)[4] = fr[8 * i + s], (&b)[4] = fr[8 * i + 4 + s];
                mma_bf(ag[s & 1], a[0], a[1], a[2], a[3], x[s >> 1][2 * (s & 1)], x[s >> 1][2 * (s & 1) + 1]);
                mma_bf(au[s & 1], b[0], b[1], b[2], b[3], x[s >> 1][2 * (s & 1)], x[s >> 1][2 * (s & 1) + 1]);
            }
        };
#pragma unroll
        for (int i = 0; i < 3; i++) load(i, 3 * j + i, (i ? 5 : 3) * j + i);
        pin();
        bar_sync(BAR_G + j, 192);
        if (w == 0 && lane == 0) mbar_arrive(bar_free + 8 * j);
        mbar_wait(bar_x);
        if (warp == 0) TSTAMP(8);
        {
            const uint32_t xk = fresh(xb) + 384 * j;
#pragma unroll
            for (int i = 0; i < 3; i++) { mul(i, (i ? fresh(xk) : xk) + 128 * i); if (i == 0) { asm volatile("" :: "f"(ag[0][0]), "f"(ag[1][0]), "f"(au[0][0]), "f"(au[1][0])); sts32(s_tok + 64, clock32()); } }
        }
#pragma unroll 1
        for (int n = 6 + j; n < 9; n += 2) { load(0, n, n - 6); mul(0, fresh(xb) + 128 * n); }
#pragma unroll
        for (int c = 0; c < 4; c++) { ag[0][c] += ag[1][c]; au[0][c] += au[1][c]; }
        if (j) {
            sts128(wb + 24576, __float_as_uint(ag[0][0]), __float_as_uint(ag[0][1]), __float_as_uint(ag[0][2]), __float_as_uint(ag[0][3]));
            sts128(wb + 25600, __float_as_uint(au[0][0]), __float_as_uint(au[0][1]), __float_as_uint(au[0][2]), __float_as_uint(au[0][3]));
        }
        bar_sync(BAR_GU, 384);
        if (!j) {
            const uint32_t sf = fresh(wb);
            const uint4 g1 = lds128(sf + 24576), u1 = lds128(sf + 25600);
            const uint32_t gs[4] = {g1.x, g1.y, g1.z, g1.w}, us[4] = {u1.x, u1.y, u1.z, u1.w};
            if (warp == 0) TSTAMP(9);
            float h[4];
#pragma unroll
            for (int c = 0; c < 4; c++) {
                const float gv = rbf(ag[0][c] + __uint_as_float(gs[c]));
                h[c] = rbf(gv * sigmoidf_(gv)) * rbf(au[0][c] + __uint_as_float(us[c]));
            }
            uint32_t h0, h1;
            asm("movmatrix.sync.aligned.m8n8.trans.b16 %0, %1;" : "=r"(h0) : "r"(pack_bf16(h[0], h[1])));
            asm("movmatrix.sync.aligned.m8n8.trans.b16 %0, %1;" : "=r"(h1) : "r"(pack_bf16(h[2], h[3])));
            if (h0 == 0) h0 = 0x8000u;
            asm volatile("{ .reg .b64 v; mov.b64 v, {%1, %2}; st.relaxed.gpu.global.b64 [%0], v; }" :: "l"(p.s->h + ((epoch & 1) * 288 + 6 * f + w) * 32 + lane), "r"(h0), "r"(h1) : "memory");
        }
        if (isx) {
            if (warp == 0) TSTAMP(10);
            const uint2* hsrc = p.s->h + ((epoch & 1) * 288 + 144 * (f & 1) + warp) * 32 + lane;
            const uint32_t wd = sb + SF_WD + warp * 1024 + (r8 + 8 * (mi >> 1)) * 64 + (((mi & 1) ^ (r8 >> 1)) << 4), we = wd ^ 32;
            uint2 hb[12];
            auto ldh = [&](int i) { asm volatile("ld.relaxed.gpu.global.v2.u32 {%0, %1}, [%2];" : "=r"(hb[i].x), "=r"(hb[i].y) : "l"(hsrc + 384 * box_no(i)) : "memory"); };
            auto ldw = [&](int i) { mbar_wait(bar_d + 8 * box_no(i)); ldsm4t(fr[2 * i], fresh(wd) + 12288 * box_no(i)); ldsm4t(fr[2 * i + 1], fresh(we) + 12288 * box_no(i)); };
#pragma unroll
            for (int i = 0; i < DPA; i++) ldw(i);
#pragma unroll
            for (int i = 0; i < 12; i++) ldh(i);
#pragma unroll
            for (int i = DPA; i < DPB; i++) ldw(i);
#pragma unroll
            for (int i = 0; i < DPB; i++) asm volatile("" :: "r"(fr[2 * i][0]), "r"(fr[2 * i + 1][0]) : "memory");
#pragma unroll 1
            for (int it = 0;; it++) {
                bool again = false;
#pragma unroll
                for (int s = 0; s < 12; s += 2) if (__any_sync(0xffffffffu, min(hb[s].x, hb[s + 1].x) == 0)) { ldh(s); ldh(s + 1); again = true; }
                if (!again) break;
                if (it > (1 << 16)) give_up();
            }
            if (warp == 0) TSTAMP(11);
            float ad[2][2][4];
#pragma unroll
            for (int i = 0; i < 4; i++) { ad[i >> 1][i & 1][0] = ad[i >> 1][i & 1][1] = ad[i >> 1][i & 1][2] = ad[i >> 1][i & 1][3] = 0.f; }
#pragma unroll
            for (int i = 0; i < 12; i++) {
                if (i >= DPB) ldw(i);
                if (i == 11 && warp == 9) TSTAMP(14);
#pragma unroll
                for (int c = 0; c < 2; c++) mma_bf(ad[c][i & 1], fr[2 * i + c][0], fr[2 * i + c][1], fr[2 * i + c][2], fr[2 * i + c][3], hb[i].x, hb[i].y);
                if (i >= DPB - 1) asm volatile("" :: "f"(ad[0][i & 1][0]), "f"(ad[1][i & 1][0]) : "memory");
            }
            const uint32_t rd = sb + SF_RED + warp * 1152 + (72 * t + g) * 4;
#pragma unroll
            for (int i = 0; i < 8; i++) sts32(rd + (i >> 2) * 64 + (i & 1) * 144 + ((i >> 1) & 1) * 32, __float_as_uint(ad[i >> 2][0][i & 3] + ad[i >> 2][1][i & 3]));
            bar_sync(BAR_RED, 416);
            if (warp < 4) {
                const int tid = 32 * warp + lane;
                const uint32_t rs = fresh(sb + SF_RED) + (tid >> 4) * 144 + (tid & 15) * 8;
                const uint2 tk = lds64(fresh(s_tok) + (tid >> 4) * 8);
                float x = 0.f, y = 0.f;
#pragma unroll
                for (int w = 0; w < 12; w++) { const uint2 v = lds64(rs + w * 1152); x += __uint_as_float(v.x); y += __uint_as_float(v.y); }
                asm volatile("red.relaxed.gpu.global.add.noftz.bf16x2 [%0], %1;" :: "l"(p.out + (size_t)tk.x * DM + 32 * (f >> 1) + 2 * (tid & 15)),
                             "r"(pack_bf16(x * __uint_as_float(tk.y), y * __uint_as_float(tk.y))) : "memory");
            }
            if (warp == 0) { TSTAMP(15); TFLUSH(); }
            asm volatile("exit;"); __builtin_unreachable();
        }
    }
}

__device__ __forceinline__ void fetch_k(const uint4* src, uint64_t (&v)[6], uint32_t a, uint32_t b) {
    asm volatile("{ .reg .pred p; setp.eq.u32 p, %7, %8; @p ld.relaxed.gpu.global.v2.u64 {%0,%1}, [%6]; @p ld.relaxed.gpu.global.v2.u64 {%2,%3}, [%6 + 512]; @p ld.relaxed.gpu.global.v2.u64 {%4,%5}, [%6 + 1024]; }"
                 : "+l"(v[0]), "+l"(v[1]), "+l"(v[2]), "+l"(v[3]), "+l"(v[4]), "+l"(v[5]) : "l"(src), "r"(a), "r"(b));
}
__device__ __forceinline__ uint32_t mini_conv(const Params& p, uint32_t sb, int warp, int lane, int f, unsigned epoch, uint64_t (&v)[6]) {
    const int g = lane >> 2, t = lane & 3, mi = lane >> 3, r8 = lane & 7;
    const uint32_t fb = sb + SF_MISC, kt = sb + (warp >= 12 ? SM_KT - 12 * 2112 : f < NW ? SM_KW + 2 * 2112 : SM_KW) + warp * 2112;
    const bool ism = f >= NW;
    const uint32_t* const sel = &p.s->sel[((mini_ch0(f) + (ism ? 2 * (warp & 8) : 0)) >> 5) * 64 + r8];
    uint32_t seq = 128, key;
    const uint4* src = p.s->kp + lane;
    auto hi = [&](int i) { return (uint32_t)(v[i] >> 32); };
    if (f >= (warp < 4 ? NW : NX)) {
    {
        const uint32_t c = 68 + (warp & 3) + 2 * (warp & 12), y = ((uint32_t)((warp < 8 ? 0xe066806400000000ull : 0x5a6e00680080e26cull) >> ((8 * warp) & 48)) & 0xffff) + (warp < 14 ? 0 : 0x6a0000);
        seq = !ism ? y + (warp & 1) * ((y >> 6) & 0x10101) : warp < 14 ? 0x101 * c - 0x400 : c;
        src += (48 * (f - (ism ? NW : NX)) + (seq & 63)) * 96;
    }
    if (seq & 64) {
        if (seq & 4) {
            const int q = (seq & 3) + ((seq >> 1) & 4);
            const uint32_t ab = sb - 3072 * (seq & 16), d = ab + SM_UT + g * MU_STRIDE + (4 + 4 * q + t) * 32;
            asm volatile("st.shared.v2.u32 [%0], {%1,%1};" :: "r"(ab + SM_UT + (2 * q + (mi >> 1)) * MU_STRIDE + (lane & 15) * 8), "r"(0) : "memory");
            mbar_wait(fb + FB_MU - (seq & 16) / 2);
            if (warp == 15) TSTAMP(16);
            const uint32_t a = fresh(ab + SM_RAW) + q * 2048 + (8 * mi + 4 * (r8 & 1) + (r8 >> 1)) * 32 + ((r8 & 1) << 4);
            uint32_t x[4][4];
#pragma unroll
            for (int i = 0; i < 4; i++) ldsm4t(x[i], (i & 2 ? a ^ 16 : a) + 1024 * (i & 1));
#pragma unroll
            for (int i = 0; i < 4; i++) sts128(d + (i & 1) * 16 + (i & 2) * 4 * MU_STRIDE, x[i][0], x[i][1], x[i][2], x[i][3]);
            __syncwarp();
            if (lane == 0) mbar_arrive(fb + FB_MT + (seq & 16) / 2);
        }
        mbar_wait(fb + FB_KDONE);
        fetch_k(src, v, warp < 4, 0);
        if ((warp | 2) == 7) { fetch_gates(p, (warp >> 1) & 1, lane, epoch, sb + SM_G + 256 * (warp & 2) + 16 * lane); __syncwarp(); if (lane == 0) mbar_arrive(fb + FB_MG); }
        if (warp >= 8) {
            mbar_wait(fb + FB_KEYS); mbar_wait(fb + FB_MT);
            if (ism) {
                asm volatile("barrier.cluster.wait.aligned; fence.release.sync_restrict::shared::cta.cluster;" ::: "memory");
                if (lane == 0) asm volatile("mbarrier.arrive.relaxed.cluster.shared::cluster.b64 _, [%0];" :: "r"(mapa(fb + FB_MT + 8, 0)) : "memory");
            }
        }
        if (warp == TW) TSTAMP(17);
    }
    }
    const uint32_t lo = (8 + r8 - (mi & 1)) * 16 + (mi >> 1) * 128;
#pragma unroll 1
    do {
        const int c = seq & 63;
        const bool far = !ism && (seq & 16);
        const uint32_t ab = sb - 3072 * (c & 16);
        uint32_t ut = ab + SM_UT + (c & 15) * MU_STRIDE;
        if (seq & 64) {
        if (far) {
            mbar_wait_cluster(fb + FB_MT + 8);
            const uint32_t ru = mapa(ut, 1) + lane * 16;
            ut = sb + SM_FT + (c & 3) * 1536;
            uint4 x[3];
#pragma unroll
            for (int i = 0; i < 3; i++) asm volatile("ld.shared::cluster.v4.u32 {%0,%1,%2,%3}, [%4];" : "=r"(x[i].x), "=r"(x[i].y), "=r"(x[i].z), "=r"(x[i].w) : "r"(ru + 512 * i) : "memory");
#pragma unroll
            for (int i = 0; i < 3; i++) sts128(ut + lane * 16 + 512 * i, x[i].x, x[i].y, x[i].z, x[i].w);
        } else mbar_wait(fb + FB_MT + (seq & 16) / 2);
#pragma unroll 1
        for (int it = 0; !__all_sync(0xffffffffu, ((hi(1) ^ k_tag(epoch)) | (hi(3) ^ k_tag(epoch)) | (hi(5) ^ k_tag(epoch)) | ((uint32_t)v[5] & p.zero)) < 65536); it++) {
            fetch_k(src, v, 0, 0);
            if (it > (1 << 20)) give_up();
        }
        sts128(kt + t * 16, 0, 0, 0, 0);
        if (warp == TW) TSTAMP(seq >> 8 ? 7 : 10);
        const uint32_t w[12] = {(uint32_t)v[0], hi(0), (uint32_t)v[1], (uint32_t)v[2], hi(2), (uint32_t)v[3], (uint32_t)v[4], hi(4), 0, 0, 0, 0};
        k_tables<false>(fresh(kt), fresh(lane), w);
        }
        __syncwarp();
        if (seq & 128) ffn_work(p, sb, warp, fresh(lane), f, epoch);
        if (!(seq & 64)) return 0;
        const uint32_t kb = fresh(kt) + (16 + g - 2 * t) * 4, ub = fresh(ut);
        const uint32_t yd = ab + SM_Y + (c & 15) * 1056 + (c & 8) * 8 + lane * 16;
        if (warp == TW && !(seq >> 8)) TSTAMP(13);
        seq >>= 8;
        src += ((int)(seq & 63) - c) * 96;
#pragma unroll
        for (int i = 0; i < 6; i++) v[i] = 0;
        key = 0;
        float acc[8][4];
#pragma unroll
        for (int i = 0; i < 8; i++) { acc[i][0] = acc[i][1] = acc[i][2] = acc[i][3] = 0.f; }
        uint32_t a[4][4], b[2][4][4];
        auto lda = [&](int j, int s) { const uint32_t x = kb + 64 * s + 512 * j; a[j][0] = lds32(x); a[j][1] = lds32(x + 256); a[j][2] = lds32(x + 32); a[j][3] = lds32(x + 288); };
        auto ldb = [&](int i, int s) { ldsm4(b[s & 1][i], ub + lo + 256 * i - 32 * s); };
#pragma unroll
        for (int j = 0; j < 4; j++) { ldb(j, 0); lda(j, 0); }
#pragma unroll
        for (int s = 0; s < 4; s++) {
            if (s == 2) {
                const uint32_t e = seq | (__float_as_uint(acc[0][0]) & p.zero);
                fetch_k(src, v, e & 64, 64);
                asm volatile("{ .reg .pred p; setp.eq.u32 p, %2, 0; @p ld.relaxed.gpu.global.u32 %0, [%1]; }" : "+r"(key) : "l"(sel), "r"(e));
            }
#pragma unroll
            for (int i = 0; i < 4; i++) {
                const int j = (i >> 1) + 2 * (i & 1);
                if (s < 3) ldb(i, s + 1);
#pragma unroll
                for (int mu = 0; mu < 8; mu++) if (mu + 2 * j < 8) mma_bf(acc[mu + 2 * j], a[j][0], a[j][1], a[j][2], a[j][3], b[s & 1][mu >> 1][2 * (mu & 1)], b[s & 1][mu >> 1][2 * (mu & 1) + 1]);
                if (s < 3) lda(j, s + 1);
            }
        }
        if (warp == TW && !seq) TSTAMP(14);
        mbar_wait(fb + FB_MG);
        uint32_t ug[4][4];
#pragma unroll
        for (int i = 0; i < 2; i++) { ldsm4t(ug[i], ub + 128 + lane * 16 + 512 * i); ldsm4t(ug[2 + i], fresh(sb + SM_G) + lane * 16 + 512 * i); }
#pragma unroll
        for (int x = 0; x < 8; x++) ug[x >> 2][x & 3] = gmix(ug[2 + (x >> 2)][x & 3], x ? acc[x][0] + acc[x - 1][2] : acc[0][0], x ? acc[x][1] + acc[x - 1][3] : acc[0][1], ug[x >> 2][x & 3]);
        if (far) for (int i = 0; i < 2; i++) st_async128(mapa(yd, 1) + 512 * i, ug[i][0], ug[i][1], ug[i][2], ug[i][3], mapa(fb + FB_FAR, 1));
        else for (int i = 0; i < 2; i++) sts128(yd + 512 * i, ug[i][0], ug[i][1], ug[i][2], ug[i][3]);
        __syncwarp();
        if (warp == TW) TSTAMP(18 + (seq != 0));
    } while (seq);
    if (warp >= 12) TSTAMP(12 + warp);
    return key;
}
__device__ __forceinline__ void mini_out(const Params& p, const CUtensorMap* maps, uint32_t sb, int warp, int lane, int f, unsigned epoch, uint32_t key) {
    const int g = lane >> 2, t = lane & 3, mi = lane >> 3, r8 = lane & 7;
    const uint32_t fb = sb + SF_MISC;
    const bool ism = f >= NW;
    const int ch0 = mini_ch0(f);
    const int k = ism ? warp >> 3 : 0;
    uint32_t first = 1;
    if (lane == 0) asm volatile("atom.shared.exch.b32 %0, [%1], 1;" : "=r"(first) : "r"(fb + FS_BM + 64 + 4 * k) : "memory");
    if (!__all_sync(0xffffffffu, first)) {
        if (elect()) prefetch_map(maps + 6);
        const int row = key_row(wait_sel(p, (ch0 + 16 * k) >> 5, r8, key_tag(epoch), key));
        if (row < 512) asm volatile("red.shared.or.b32 [%0], %1;" :: "r"(fb + FS_BM + (row >> 5) * 4), "r"(1u << (row & 31)) : "memory");
        if (k) mbar_wait_cluster(fb + FB_FAR);
    }
    const int m = warp & 7, dr = 64 * (g >> 1) + 16 * (t >> 1) + 8 * (g & 1);
    const uint32_t y = SM_Y + ((r8 >> 1) & 1) * 8512 + (2 * mi + (r8 & 1)) * 1056 + (2 * m + (r8 >> 2)) * 16;
    const uint32_t so = (g >> 1) * 128 + (t >> 1) * 64 + (g & 1) * 32 + (t & 1) * 16;
    bar_sync(BAR_M - k, ism ? 256 : NTHR);
#pragma unroll 1
    for (int h = ism ? 0 : warp >> 3;; h++) {
        const int r0 = 256 * h + 32 * (m & 1) + (m >> 1), row = r0 + dr;
        const uint32_t bm = lds32(fresh(fb) + FS_BM + (row >> 5) * 4) >> (row & 31), ab = fresh(sb - 49152 * k + 512 * h), stg = ab + SM_UT + 2048 * m + 512 * h;
        uint32_t x[2][4];
        ldsm4t(x[0], ab + y); ldsm4t(x[1], ab + y + 256);
        if (warp == 0 && x[0][0] != 0x12345) TSTAMP(28);
        if (__any_sync(0xffffffffu, bm & 0x11u)) {
#pragma unroll
            for (int i = 0; i < 2; i++) store_or_add(p.out + (size_t)(row + 4 * i) * DM + ch0 + 16 * k + 8 * (t & 1), x[i], bm & (1u << (4 * i)));
        } else {
#pragma unroll
            for (int i = 0; i < 2; i++) sts128(stg + so + 512 * i, x[i][0], x[i][1], x[i][2], x[i][3]);
            asm volatile("fence.proxy.async.shared::cta;" ::: "memory");
            __syncwarp();
            if (elect()) store_rows(maps + 6, stg, ch0 + 16 * k, r0);
        }
        if (h >= ism) break;
    }
    if (elect()) { asm volatile("cp.async.bulk.commit_group;" ::: "memory"); asm volatile("cp.async.bulk.wait_group.read 0;" ::: "memory"); }
    if (warp == 8) TSTAMP(11);
    if (warp == 0) { TSTAMP(15); TFLUSH(); }
}

constexpr int SMEM_BYTES = 232448;
static_assert(SF_MISC + 1152 <= 232192, "layout");

struct Maps { CUtensorMap m[7]; };

__global__ void __cluster_dims__(2, 1, 1) __launch_bounds__(NTHR, 1)
fused_kernel(const Params p, const __grid_constant__ Maps maps) {
    extern __shared__ __align__(1024) uint8_t smem_raw[];
    uint32_t q[8];
    {
        const int b = role(blockIdx.x), x = threadIdx.x, rc = 5 * b + (b & ~3) + 4 + (x >> 6);
        const int cv = (unsigned)b < NW ? 0 : -1, ca = (b < 0 ? 8 * b + DM : 48 * b - 2300) + ((x >> 5) & 3), cb = 2 * rc - (rc & 3) + 4;
        const uint32_t ch = (ca & cv) | (cb & ~cv), o = NST * ch + 2 * ((x & 31) + ((x >> (cv & 2)) & 32));
        const bool c = x < (cv ? 256 : 320);
        q[6] = ldg16_if(c, p.logdt + ch);
        q[2] = ldg32_if(c, p.Bre + o); q[3] = ldg32_if(c, p.Bim + o); q[4] = ldg32_if(c, p.Cre + o); q[5] = ldg32_if(c, p.Cim + o); q[0] = ldg32_if(c, p.Are + o); q[1] = ldg32_if(c, p.Aim + o);
        q[7] = ldg16_if(c, p.Dskip + ch);
    }
    const unsigned epoch = ld_rlx32(&p.s->epoch[blockIdx.x * 16 + (threadIdx.x >> 5)]);
    const uint32_t sb = __shfl_sync(0xffffffffu, smem_u32(smem_raw), 0);
    const int warp = __shfl_sync(0xffffffffu, threadIdx.x >> 5, 0), bid = __shfl_sync(0xffffffffu, blockIdx.x, 0);
    const int lane = __shfl_sync(0xffffffffu, threadIdx.x & 31, threadIdx.x);
    const bool conv = bid < NCONV;
    const int f = role(bid);
    uint32_t w[12];
    uint64_t v[6];
    const bool four = (unsigned)f >= NW;
    if (warp < (four ? 8 : 10)) {
        const int half = four ? warp >> 2 : warp & 1, pr = four ? warp & 3 : warp >> 1;
        const int rc = 5 * f + (f & ~3) + 4 + pr;
        const uint32_t stage = sb + (conv ? SC_KG : SF_KG) + warp * KG_STAGE;
        uint4* const kp = p.s->kp + (four ? (conv ? 8 * bid : 48 * f - 2300) + pr : 2 * rc - (rc & 3) + 4) * 96 + lane;
        kgen(q, sb, half, stage, stage + (four ? 4 : 1) * KG_STAGE, 1 + pr, lane, w, [&] {
            sts128z_if(conv && lane < 20, sb + SC_KT + warp * KT_BYTES + lane * 16 + (lane < 4 ? 0 : lane < 14 ? 2048 : 2288));
            stg128z_if(!conv, kp + 64 * half); stg128z_if(!half && !conv, kp + 32);
            stg128z_if((unsigned)f < NW && warp < 6, (uint4*)(p.s->h + ((lane >> 4) * 288 + 6 * f + warp) * 32) + (lane & 15));
            if (!conv) bar_sync(0, NTHR);
            if ((unsigned)f >= NX) asm volatile("barrier.cluster.arrive.relaxed.aligned;" ::: "memory");
        });
        if (!half) publish_k(kp, w, epoch, v);
        else for (int i = 0; i < 6; i++) v[i] = 0;
        if (conv) { conv_main(p, sb, warp, lane, bid, epoch, w); return; }
        {
            if (!half && lane == 0) mbar_arrive(sb + SF_MISC + FB_KDONE);
            if (warp == 0) TSTAMP(22);
            if (warp == 2) TSTAMP(23);
        }
    } else if (conv) {
        conv_aux(p, maps.m, sb, warp - 8, lane, bid, epoch);
        return;
    } else {
        ffn_front(p, maps.m, sb, warp, lane, f, epoch);
        for (int i = 0; i < 6; i++) v[i] = 0;
    }
    converged();
    next_epoch(p, epoch);
    if (warp >= 12 && f < NX) return;
    mini_out(p, maps.m, sb, warp, lane, f, epoch, mini_conv(p, sb, warp, __shfl_sync(0xffffffffu, lane, lane), f, epoch, v));
}

typedef CUresult (*EncodeFn)(CUtensorMap*, CUtensorMapDataType, cuuint32_t, void*, const cuuint64_t*, const cuuint64_t*, const cuuint32_t*, const cuuint32_t*,
                             CUtensorMapInterleave, CUtensorMapSwizzle, CUtensorMapL2promotion, CUtensorMapFloatOOBfill);

void make_map(EncodeFn fn, CUtensorMap* m, const void* base, int rank, const cuuint64_t* dims, const cuuint64_t* strides, const cuuint32_t* box, CUtensorMapSwizzle sw) {
    const cuuint32_t es[5] = {1, 1, 1, 1, 1};
    fn(m, CU_TENSOR_MAP_DATA_TYPE_BFLOAT16, rank, (void*)base, dims, strides, box, es, CU_TENSOR_MAP_INTERLEAVE_NONE, sw,
       CU_TENSOR_MAP_L2_PROMOTION_NONE, CU_TENSOR_MAP_FLOAT_OOB_FILL_NONE);
}

}

extern "C" void kernel_launch(void* const* d_in, const int* in_sizes, int n_in, void* d_out, int out_size) {
    (void)in_sizes; (void)n_in; (void)out_size;
    static EncodeFn fn = nullptr;
    static void* scratch = nullptr;
    if (!fn) {
        void* ptr = nullptr; cudaDriverEntryPointQueryResult qr;
        cudaGetDriverEntryPoint("cuTensorMapEncodeTiled", &ptr, cudaEnableDefault, &qr);
        fn = (EncodeFn)ptr;
        cudaGetSymbolAddress(&scratch, g_scratch);
        cudaFuncSetAttribute(fused_kernel, cudaFuncAttributeMaxDynamicSharedMemorySize, SMEM_BYTES);
    }
    typedef const __nv_bfloat16* bp;
    Params p;
    p.u = (bp)d_in[0]; p.Are = (bp)d_in[1]; p.Aim = (bp)d_in[2]; p.Bre = (bp)d_in[3]; p.Bim = (bp)d_in[4]; p.Cre = (bp)d_in[5]; p.Cim = (bp)d_in[6];
    p.logdt = (bp)d_in[7]; p.Dskip = (bp)d_in[8]; p.wr = (bp)d_in[10]; p.gatew = (bp)d_in[14];
    p.out = (__nv_bfloat16*)d_out; p.s = (Scratch*)scratch; p.zero = 0;
    Maps maps;
    {
        const cuuint64_t dims[4] = {DM, 4, 16, 32}, strides[3] = {16 * DM * 2, DM * 2, 64 * DM * 2};
        const cuuint32_t box[4] = {16, 4, 16, 2};
        make_map(fn, &maps.m[0], d_in[0], 4, dims, strides, box, CU_TENSOR_MAP_SWIZZLE_32B);
        const cuuint32_t box2[4] = {16, 4, 16, 8};
        make_map(fn, &maps.m[5], d_in[0], 4, dims, strides, box2, CU_TENSOR_MAP_SWIZZLE_32B);
    }
    for (int i = 0; i < 2; i++) {
        const cuuint64_t dims[3] = {32, DM, FF / 32}, strides[2] = {FF * 2, 64};
        const cuuint32_t box[3] = {32, 64, 3};
        make_map(fn, &maps.m[1 + i], d_in[11 + i], 3, dims, strides, box, CU_TENSOR_MAP_SWIZZLE_64B);
    }
    {
        const cuuint64_t dims[2] = {DM, FF}, strides[1] = {DM * 2};
        const cuuint32_t box[2] = {32, 192};
        make_map(fn, &maps.m[3], d_in[13], 2, dims, strides, box, CU_TENSOR_MAP_SWIZZLE_64B);
    }
    {
        const cuuint64_t dims[5] = {DM, 2, 4, 4, L_SEQ}, strides[4] = {16 * DM * 2, 64 * DM * 2, 4 * DM * 2, DM * 2};
        const cuuint32_t box[5] = {16, 2, 4, 4, 1};
        make_map(fn, &maps.m[4], d_out, 5, dims, strides, box, CU_TENSOR_MAP_SWIZZLE_NONE);
    }
    {
        const cuuint64_t dims[5] = {DM, 4, 4, 2, L_SEQ}, strides[4] = {8 * DM * 2, 64 * DM * 2, 4 * DM * 2, DM * 2};
        const cuuint32_t box[5] = {16, 4, 4, 2, 1};
        make_map(fn, &maps.m[6], d_out, 5, dims, strides, box, CU_TENSOR_MAP_SWIZZLE_NONE);
    }
    fused_kernel<<<NCTA, NTHR, SMEM_BYTES>>>(p, maps);
}
```

```cpp
#include <cuda_runtime.h>
#include <cuda_bf16.h>
#include <cuda_fp16.h>
#include <cuda.h>
#include <stdint.h>

#define RESUME 300
#define MDELAY 2000
#define KPOLL 650
#define DPA 7
#define DPB 9
#define RDELAY 900
#define WDELAY 1700
#define WGAP 290
#define NPRE 8
#define DGAP 290
namespace {

constexpr int DM = 576, NST = 128, FF = 4608, L_SEQ = 2048;
constexpr int NCONV = 72, NX = 36, NW = 48, NCTA = 132, NTHR = 512;

struct __align__(128) Scratch {
    unsigned epoch[NCTA * 16];
    uint4 keys[16 * 128];
    uint32_t sel[18 * 64];
    uint16_t gate[L_SEQ];
    uint2 h[2 * 288 * 32];
    uint4 kp[DM * 96];
};
__device__ Scratch g_scratch;
#define TFLUSH()
#define TSTAMP(i)
#define TW 12

struct Params {
    const __nv_bfloat16 *Are, *Aim, *Bre, *Bim, *Cre, *Cim, *logdt, *Dskip, *u, *wr, *gatew;
    __nv_bfloat16* out;
    Scratch* s;
    uint32_t zero;
};

__device__ __forceinline__ void give_up() { asm volatile("trap; exit;"); __builtin_unreachable(); }
__device__ __forceinline__ void converged() { __syncwarp(); asm volatile("{ .reg .b32 t; mov.b32 t, 0; movmatrix.sync.aligned.m8n8.trans.b16 t, t; }" ::: "memory"); }
__device__ __forceinline__ bool elect() { uint32_t r; asm volatile("{ .reg .pred p; elect.sync _|p, 0xffffffff; selp.u32 %0, 1, 0, p; }" : "=r"(r)); return r; }
__device__ __forceinline__ uint32_t smem_u32(const void* p) { return (uint32_t)__cvta_generic_to_shared(p); }
__device__ __forceinline__ uint32_t pack_bf16(float lo, float hi) { uint32_t r; asm("cvt.rn.bf16x2.f32 %0, %1, %2;" : "=r"(r) : "f"(hi), "f"(lo)); return r; }
__device__ __forceinline__ uint32_t pack_f16(float lo, float hi) { uint32_t r; asm("cvt.rn.f16x2.f32 %0, %1, %2;" : "=r"(r) : "f"(hi), "f"(lo)); return r; }
__device__ __forceinline__ float bf_lo(uint32_t w) { return __uint_as_float(w << 16); }
__device__ __forceinline__ float bf_hi(uint32_t w) { return __uint_as_float(w & 0xffff0000u); }
__device__ __forceinline__ float rbf(float x) { return bf_lo(pack_bf16(x, 0.f)); }
__device__ __forceinline__ uint32_t badd2(uint32_t a, uint32_t b) { uint32_t r; asm("add.rn.bf16x2 %0, %1, %2;" : "=r"(r) : "r"(a), "r"(b)); return r; }
__device__ __forceinline__ uint32_t bsub2(uint32_t a, uint32_t b) { uint32_t r; asm("sub.rn.bf16x2 %0, %1, %2;" : "=r"(r) : "r"(a), "r"(b)); return r; }
__device__ __forceinline__ uint32_t gmix(uint32_t ng, float ny0, float ny1, uint32_t u) {
    uint32_t r; asm("{ .reg .b32 t; fma.rn.bf16x2 t, %1, %3, %3; fma.rn.bf16x2 %0, %1, %2, t; }" : "=r"(r) : "r"(ng), "r"(pack_bf16(ny0, ny1)), "r"(u)); return r;
}
__device__ __forceinline__ void mma_bf(float (&c)[4], uint32_t a0, uint32_t a1, uint32_t a2, uint32_t a3, uint32_t b0, uint32_t b1) {
    asm("mma.sync.aligned.m16n8k16.row.col.f32.bf16.bf16.f32 {%0,%1,%2,%3}, {%4,%5,%6,%7}, {%8,%9}, {%0,%1,%2,%3};"
        : "+f"(c[0]), "+f"(c[1]), "+f"(c[2]), "+f"(c[3]) : "r"(a0), "r"(a1), "r"(a2), "r"(a3), "r"(b0), "r"(b1));
}
__device__ __forceinline__ void mma_bf8(float (&c)[4], uint32_t a0, uint32_t a1, uint32_t b0) {
    asm("mma.sync.aligned.m16n8k8.row.col.f32.bf16.bf16.f32 {%0,%1,%2,%3}, {%4,%5}, {%6}, {%0,%1,%2,%3};"
        : "+f"(c[0]), "+f"(c[1]), "+f"(c[2]), "+f"(c[3]) : "r"(a0), "r"(a1), "r"(b0));
}
__device__ __forceinline__ void mma_h(float (&c)[4], uint32_t a0, uint32_t a1, uint32_t a2, uint32_t a3, uint32_t b0, uint32_t b1) {
    asm("mma.sync.aligned.m16n8k16.row.col.f32.f16.f16.f32 {%0,%1,%2,%3}, {%4,%5,%6,%7}, {%8,%9}, {%0,%1,%2,%3};"
        : "+f"(c[0]), "+f"(c[1]), "+f"(c[2]), "+f"(c[3]) : "r"(a0), "r"(a1), "r"(a2), "r"(a3), "r"(b0), "r"(b1));
}
__device__ __forceinline__ uint32_t fresh(uint32_t a) { asm volatile("" : "+r"(a) :: "memory"); return a; }
__device__ __forceinline__ uint32_t lds32(uint32_t a) { uint32_t v; asm("ld.shared.u32 %0, [%1];" : "=r"(v) : "r"(a)); return v; }
__device__ __forceinline__ uint2 lds64(uint32_t a) { uint2 v; asm("ld.shared.v2.u32 {%0,%1}, [%2];" : "=r"(v.x), "=r"(v.y) : "r"(a)); return v; }
__device__ __forceinline__ uint4 lds128(uint32_t a) { uint4 v; asm("ld.shared.v4.u32 {%0,%1,%2,%3}, [%4];" : "=r"(v.x), "=r"(v.y), "=r"(v.z), "=r"(v.w) : "r"(a)); return v; }
__device__ __forceinline__ void ldsm4(uint32_t (&r)[4], uint32_t a) {
    asm("ldmatrix.sync.aligned.m8n8.x4.shared.b16 {%0,%1,%2,%3}, [%4];" : "=r"(r[0]), "=r"(r[1]), "=r"(r[2]), "=r"(r[3]) : "r"(a));
}
__device__ __forceinline__ void ldsm4t(uint32_t (&r)[4], uint32_t a) {
    asm("ldmatrix.sync.aligned.m8n8.x4.trans.shared.b16 {%0,%1,%2,%3}, [%4];" : "=r"(r[0]), "=r"(r[1]), "=r"(r[2]), "=r"(r[3]) : "r"(a));
}
__device__ __forceinline__ void sts16(uint32_t a, uint32_t v) { asm volatile("st.shared.u16 [%0], %1;" :: "r"(a), "h"((unsigned short)v) : "memory"); }
__device__ __forceinline__ void sts32(uint32_t a, uint32_t v) { asm volatile("st.shared.u32 [%0], %1;" :: "r"(a), "r"(v) : "memory"); }
__device__ __forceinline__ void sts64(uint32_t a, uint32_t x, uint32_t y) { asm volatile("st.shared.v2.u32 [%0], {%1,%2};" :: "r"(a), "r"(x), "r"(y) : "memory"); }
__device__ __forceinline__ void sts128(uint32_t a, uint32_t x, uint32_t y, uint32_t z, uint32_t w) {
    asm volatile("st.shared.v4.u32 [%0], {%1,%2,%3,%4};" :: "r"(a), "r"(x), "r"(y), "r"(z), "r"(w) : "memory");
}
__device__ __forceinline__ void st_async128(uint32_t a, uint32_t x, uint32_t y, uint32_t z, uint32_t w, uint32_t bar) {
    asm volatile("st.async.weak.shared::cluster.mbarrier::complete_tx::bytes.v4.b32 [%0], {%1,%2,%3,%4}, [%5];" :: "r"(a), "r"(x), "r"(y), "r"(z), "r"(w), "r"(bar) : "memory");
}
__device__ __forceinline__ void mbar_init(uint32_t b, uint32_t cnt) { asm volatile("mbarrier.init.shared::cta.b64 [%0], %1;" :: "r"(b), "r"(cnt) : "memory"); }
__device__ __forceinline__ void mbar_fence() { asm volatile("fence.mbarrier_init.release.cluster;" ::: "memory"); }
__device__ __forceinline__ void mbar_expect(uint32_t b, uint32_t bytes) { asm volatile("mbarrier.arrive.expect_tx.shared::cta.b64 _, [%0], %1;" :: "r"(b), "r"(bytes) : "memory"); }
__device__ __forceinline__ void mbar_arrive(uint32_t b) { asm volatile("mbarrier.arrive.shared::cta.b64 _, [%0];" :: "r"(b) : "memory"); }
__device__ __forceinline__ void mbar_wait(uint32_t b, uint32_t parity = 0) {
    asm volatile("{ .reg .pred p; .reg .u32 n; mov.u32 n, 0;\n"
                 "LW: mbarrier.try_wait.parity.shared::cta.b64 p, [%0], %1; @p bra LD; add.u32 n, n, 1; setp.lt.u32 p, n, 65536; @p bra LW; trap;\n"
                 "LD: }" :: "r"(b), "r"(parity) : "memory");
}
__device__ __forceinline__ void mbar_wait_cluster(uint32_t b) {
    asm volatile("{ .reg .pred p; .reg .u32 n; mov.u32 n, 0;\n"
                 "LW: mbarrier.try_wait.parity.acquire.cluster.shared::cta.b64 p, [%0], 0; @p bra LD; add.u32 n, n, 1; setp.lt.u32 p, n, 65536; @p bra LW; trap;\n"
                 "LD: }" :: "r"(b) : "memory");
}
__device__ __forceinline__ void tma2d(uint32_t dst, const CUtensorMap* m, int c0, int c1, uint32_t bar) {
    asm volatile("cp.async.bulk.tensor.2d.shared::cluster.global.mbarrier::complete_tx::bytes [%0], [%1, {%3, %4}], [%2];"
                 :: "r"(dst), "l"(m), "r"(bar), "r"(c0), "r"(c1) : "memory");
}
__device__ __forceinline__ void tma3d(uint32_t dst, const CUtensorMap* m, int c0, int c1, int c2, uint32_t bar) {
    asm volatile("cp.async.bulk.tensor.3d.shared::cluster.global.mbarrier::complete_tx::bytes [%0], [%1, {%3, %4, %5}], [%2];"
                 :: "r"(dst), "l"(m), "r"(bar), "r"(c0), "r"(c1), "r"(c2) : "memory");
}
__device__ __forceinline__ void tma4d(uint32_t dst, const CUtensorMap* m, int c0, int c1, int c2, int c3, uint32_t bar) {
    asm volatile("cp.async.bulk.tensor.4d.shared::cluster.global.mbarrier::complete_tx::bytes [%0], [%1, {%3, %4, %5, %6}], [%2];"
                 :: "r"(dst), "l"(m), "r"(bar), "r"(c0), "r"(c1), "r"(c2), "r"(c3) : "memory");
}
__device__ __forceinline__ void bulk_g2s(uint32_t dst, const void* src, uint32_t bytes, uint32_t bar) {
    asm volatile("cp.async.bulk.shared::cluster.global.mbarrier::complete_tx::bytes [%0], [%1], %2, [%3];"
                 :: "r"(dst), "l"(src), "r"(bytes), "r"(bar) : "memory");
}
__device__ __forceinline__ uint32_t mapa(uint32_t a, uint32_t rank) { uint32_t r; asm("mapa.shared::cluster.u32 %0, %1, %2;" : "=r"(r) : "r"(a), "r"(rank)); return r; }
__device__ __forceinline__ void prefetch_map(const CUtensorMap* m) { asm volatile("prefetch.tensormap [%0];" :: "l"(m) : "memory"); }
__device__ __forceinline__ void bar_sync(int id, int n) { asm volatile("bar.sync %0, %1;" :: "r"(id), "r"(n) : "memory"); }
__device__ __forceinline__ void bar_arrive(int id, int n) { asm volatile("bar.arrive %0, %1;" :: "r"(id), "r"(n) : "memory"); }
__device__ __forceinline__ uint32_t ldg16_if(bool c, const void* p) { uint32_t v; asm volatile("{ .reg .pred p; setp.ne.u32 p, %2, 0; @p ld.global.nc.u16 %0, [%1]; }" : "=r"(v) : "l"(p), "r"((uint32_t)c)); return v; }
__device__ __forceinline__ uint32_t ldg32_if(bool c, const void* p) { uint32_t v; asm volatile("{ .reg .pred p; setp.ne.u32 p, %2, 0; @p ld.global.nc.u32 %0, [%1]; }" : "=r"(v) : "l"(p), "r"((uint32_t)c)); return v; }
__device__ __forceinline__ uint32_t ld_rlx32(const void* p) { uint32_t v; asm volatile("ld.relaxed.gpu.global.u32 %0, [%1];" : "=r"(v) : "l"(p) : "memory"); return v; }
__device__ __forceinline__ uint4 ld_rlx128(const void* p) {
    uint4 v; asm volatile("ld.relaxed.gpu.global.v4.u32 {%0,%1,%2,%3}, [%4];" : "=r"(v.x), "=r"(v.y), "=r"(v.z), "=r"(v.w) : "l"(p) : "memory"); return v;
}
__device__ __forceinline__ void st_rlx32(void* p, uint32_t v) { asm volatile("st.relaxed.gpu.global.u32 [%0], %1;" :: "l"(p), "r"(v) : "memory"); }
__device__ __forceinline__ void stg128(void* p, uint32_t x, uint32_t y, uint32_t z, uint32_t w) {
    asm volatile("st.global.v4.u32 [%0], {%1,%2,%3,%4};" :: "l"(p), "r"(x), "r"(y), "r"(z), "r"(w) : "memory");
}
__device__ __forceinline__ void next_epoch(const Params& p, unsigned e) { if ((threadIdx.x & 31) == 0) p.s->epoch[blockIdx.x * 16 + (threadIdx.x >> 5)] = e + 1; }
__device__ __forceinline__ void sts128z_if(bool c, uint32_t a) { asm volatile("{ .reg .pred p; setp.ne.u32 p, %1, 0; @p st.shared.v4.u32 [%0], {%2,%2,%2,%2}; }" :: "r"(a), "r"((uint32_t)c), "r"(0) : "memory"); }
__device__ __forceinline__ void stg128z_if(bool c, void* a) { asm volatile("{ .reg .pred p; setp.ne.u32 p, %1, 0; @p st.global.v4.u32 [%0], {%2,%2,%2,%2}; }" :: "l"(a), "r"((uint32_t)c), "r"(0) : "memory"); }
__device__ __forceinline__ unsigned clock32() { unsigned c; asm volatile("mov.u32 %0, %clock;" : "=r"(c) :: "memory"); return c; }
__device__ __forceinline__ void until(unsigned t0, int c) { while ((int)(clock32() - t0) < c) { } }
__device__ __forceinline__ float sigmoidf_(float x) { return __fdividef(1.0f, 1.0f + __expf(-x)); }
__device__ __forceinline__ uint32_t key_tag(unsigned epoch) { return ((epoch & 15u) | 16u) << 11; }
__device__ __forceinline__ int key_row(uint32_t key) { return 2047 - (int)(key & 2047u); }
__device__ __forceinline__ uint32_t wait_sel(const Params& p, int s32, int r8, uint32_t tag, uint32_t k = 0) {
#pragma unroll 1
    for (int it = 0; !__all_sync(0xffffffffu, (k & 0xf800u) == tag); it++) {
        k = ld_rlx32(&p.s->sel[s32 * 64 + r8]);
        if (it > (1 << 20)) give_up();
    }
    return k;
}

struct cplx { float re, im; };
__device__ __forceinline__ cplx csq(cplx a) { cplx r; r.re = a.re * a.re - a.im * a.im; r.im = (a.re * a.im) * 2.f; return r; }
__device__ __forceinline__ cplx cexpk(float ar, float ai, float k) {
    float mag, s, c;
    asm("ex2.approx.ftz.f32 %0, %1;" : "=f"(mag) : "f"(ar * (k * 1.4426950408889634f)));
    const float r = ai * k;
    asm("sin.approx.ftz.f32 %0, %1;" : "=f"(s) : "f"(r));
    asm("cos.approx.ftz.f32 %0, %1;" : "=f"(c) : "f"(r));
    cplx o; o.re = mag * c; o.im = mag * s; return o;
}
struct h2c { uint32_t re, im; };
__device__ __forceinline__ h2c cmul_cd(h2c v, __half2 c, __half2 d) {
    const __half2 r = *(const __half2*)&v.re, i = *(const __half2*)&v.im;
    const __half2 x = __hfma2(__hneg2(i), d, __hmul2(r, c)), y = __hfma2(i, c, __hmul2(r, d));
    h2c o; o.re = *(const uint32_t*)&x; o.im = *(const uint32_t*)&y; return o;
}
__device__ __forceinline__ h2c cmul_s(h2c v, uint32_t s) { const __half2 h = *(const __half2*)&s; return cmul_cd(v, __low2half2(h), __high2half2(h)); }
__device__ __forceinline__ h2c cmul_sc(h2c v, uint32_t s) {
    const __half2 h = *(const __half2*)&s, c = __low2half2(h), d = __high2half2(h), r = *(const __half2*)&v.re, i = *(const __half2*)&v.im;
    const __half2 x = __hfma2(i, d, __hmul2(r, c)), y = __hfma2(__hneg2(r), d, __hmul2(i, c));
    h2c o; o.re = *(const uint32_t*)&x; o.im = *(const uint32_t*)&y; return o;
}
__device__ __forceinline__ h2c cmul_vc(h2c v, uint32_t s) {
    const __half2 h = *(const __half2*)&s, c = __low2half2(h), d = __high2half2(h), r = *(const __half2*)&v.re, i = *(const __half2*)&v.im;
    const __half2 x = __hfma2(i, d, __hmul2(r, c)), y = __hfma2(__hneg2(i), c, __hmul2(r, d));
    h2c o; o.re = *(const uint32_t*)&x; o.im = *(const uint32_t*)&y; return o;
}

constexpr int UT_HALF = 2560, UT_STRIDE = 4736, GT_HALF = 2240;
__device__ __forceinline__ uint32_t swz(uint32_t x, int c) { return x ^ (((x >> 2) & 64) ^ (64 * (c & 1) + 8 * (c & 6))); }
__device__ __forceinline__ int col(int n) { return (n >> 1) + 4 * (n & 1); }
constexpr int KT_T = 542, KT_C = 552, KT_D = 645, KT_BYTES = 720 * 4;
constexpr int VC_OFF = 80, VE_BASE = 1616;
constexpr int V_STRIDE = (1616 + 1024) * 4 + 80;
constexpr int KG_STAGE = 5248;
constexpr int Y_CS = 2080, Y_RS = 8 * Y_CS + 64;

constexpr int SC_RT = 0;
constexpr int SC_UT = 33408;
constexpr int SC_KG = SC_UT + 8 * UT_STRIDE;
constexpr int SC_KT = SC_KG + 8 * KG_STAGE;
constexpr int SC_GT = SC_KT + 8 * KT_BYTES;
constexpr int SC_V = SC_GT + 4448;
constexpr int SC_MISC = SC_V + 8 * V_STRIDE;
static_assert(V_STRIDE % 128 == 16 && 2 * Y_RS <= SC_UT && SC_UT % 128 == 0 && SC_KG % 128 == 0, "layout");
static_assert(SC_MISC % 16 == 0 && SC_MISC + 512 <= 232192, "layout");

__device__ __forceinline__ void window_task(uint32_t s0, uint32_t s1, uint32_t d0, uint32_t d1, int k) {
    float S[51], s = 0.f;
    uint32_t w[28];
#pragma unroll
    for (int i = 0; i < 7; i++) {
        const uint4 v = lds128(((i < 3 ? s0 : s1) ^ 8 * ((i + 1) & 2)) + ((i & 1) ? 0 : UT_HALF));
        w[4 * i] = v.x; w[4 * i + 1] = v.y; w[4 * i + 2] = v.z; w[4 * i + 3] = v.w;
    }
    auto sums = [&](int lo, int hi) {
#pragma unroll
        for (int i = lo; i < hi; i++) { const float x = (i & 1) ? bf_hi(w[i >> 1]) : bf_lo(w[i >> 1]); s = i > 3 ? s + x : x; S[i] = s; }
    };
    auto put = [&](int off, int b, int o0, int o1, int o2) {
        auto v = [&](int i) { i += 16 * b; return pack_bf16(S[o0 + i] - S[o1 + i], S[o1 + i] - S[o2 + i]); };
#pragma unroll
        for (int i = 0; i < 8; i += 2) sts128((i & 4 ? d1 : d0) + 4 * off + 64 * b + 8 * (i & 2), v(i), v(i + 8), v(i + 1), v(i + 9));
    };
    S[2] = 0.f;
    sums(3, 26); put(VC_OFF - 16, 0, 10, 5, 2);
    if (k == 12) return;
    sums(26, 42); put(VC_OFF - 16, 1, 10, 5, 2);
    if (k < 8) { put(VE_BASE, 0, 19, 12, 3); sums(42, 51); put(VE_BASE, 1, 19, 12, 3); }
}

template <class F>
__device__ __forceinline__ void kgen(const uint32_t (&q)[8], uint32_t sb, int half, uint32_t stage, uint32_t pstage, int barid, int lane, uint32_t (&w)[12], F shadow) {
    const int t = lane & 3, mi = lane >> 3, r8 = lane & 7;
    {
        const uint32_t pAr = q[0], pAi = q[1], pBr = q[2], pBi = q[3], pCr = q[4], pCi = q[5], pDt = q[6], pD = q[7];
        const uint32_t wb = fresh(stage + lane * 16), za = fresh(stage + 5120 + ((lane >> 1) & 3) * 16 + mi * 4 + (lane & 1) * 2), zr = fresh(stage + 5120 + t * 16);
        const uint32_t oB = fresh(stage + 2048 + mi * 512 + r8 * 16), oC = fresh(stage + 4096 + (mi & 1) * 512 + (mi >> 1) * 128 + r8 * 16);
        float acc[6][4];
#pragma unroll
        for (int a = 0; a < 6; a++) { acc[a][0] = acc[a][1] = acc[a][2] = acc[a][3] = 0.f; asm volatile("" : "+f"(acc[a][0]), "+f"(acc[a][1]), "+f"(acc[a][2]), "+f"(acc[a][3])); }
        shadow();
        sts32(zr, clock32());
        const float dt = rbf(__expf(bf_lo(pDt)));
        float ar = dt * bf_lo(pAr), ai = dt * bf_lo(pAi), ar1 = dt * bf_hi(pAr), ai1 = dt * bf_hi(pAi);
        float wr, wi, wr1, wi1;
        { const float br = dt * bf_lo(pBr), bi = dt * bf_lo(pBi), cr = bf_lo(pCr), ci = bf_lo(pCi); wr = cr * br - ci * bi; wi = cr * bi + ci * br; }
        { const float br = dt * bf_hi(pBr), bi = dt * bf_hi(pBi), cr = bf_hi(pCr), ci = bf_hi(pCi); wr1 = cr * br - ci * bi; wi1 = cr * bi + ci * br; }
        const uint32_t ex = max(__reduce_max_sync(0xffffffffu, __float_as_uint(fmaxf(fmaxf(fabsf(wr), fabsf(wi)), fmaxf(fabsf(wr1), fabsf(wi1))))) >> 23, 14u);
        const float scl = __uint_as_float((267u - ex) << 23);
        uint32_t W = pack_f16(wr * scl, wi * -scl);
        const uint32_t W1 = pack_f16(wr1 * scl, wi1 * -scl);
        if (threadIdx.x < 32) TSTAMP(20);

#pragma unroll 1
        for (int r = 0; r < 2; r++) {
            const cplx z1 = cexpk(ar, ai, 1.f), z64 = cexpk(ar, ai, 64.f);
            const cplx z2 = csq(z1), z4 = csq(z2), z8 = csq(z4), z16 = csq(z8), z32 = csq(z16);
            const cplx z128 = csq(z64), z256 = csq(z128), z512 = csq(z256);
            auto put = [&](int grp, h2c a, h2c b, h2c c, h2c d) { sts128(wb + grp * 1024, a.re, b.re, c.re, d.re); sts128(wb + grp * 1024 + 512, a.im, b.im, c.im, d.im); };
            {
                const uint32_t s4 = pack_f16(z4.re, z4.im), s256 = pack_f16(z256.re, z256.im), s512 = pack_f16(z512.re, z512.im);
                auto mix = [](h2c a, h2c b, uint32_t sel) { return h2c{__byte_perm(a.re, b.re, sel), __byte_perm(a.im, b.im, sel)}; };
                const h2c c10 = cmul_vc(h2c{pack_f16(z1.re, 1.f), pack_f16(z1.im, 0.f)}, W), c32 = cmul_sc(c10, pack_f16(z2.re, z2.im)), c54 = cmul_sc(c10, s4);
                put(2, c10, c32, c54, cmul_sc(c32, s4));
                const h2c d20 = cmul_sc(mix(c32, c10, 0x7632), s256), e04 = cmul_sc(mix(c10, c54, 0x7632), s512), f04 = cmul_sc(e04, s256);
                put(3, d20, cmul_sc(d20, s4), e04, f04);
                const h2c ef = mix(e04, f04, 0x5410), gh = cmul_sc(ef, s512), g8 = cmul_sc(gh, pack_f16(z8.re, z8.im));
                put(4, g8, cmul_sc(g8, s512), gh, ef);
            }
            {
                const uint32_t s32 = pack_f16(z32.re, z32.im), s64 = pack_f16(z64.re, z64.im), s128 = pack_f16(z128.re, z128.im);
                const h2c p0 = {pack_f16(1.f, z8.re), pack_f16(0.f, z8.im)}, p1 = cmul_s(p0, pack_f16(z16.re, z16.im)), p2 = cmul_s(p0, s32), p3 = cmul_s(p1, s32);
                put(0, p0, p1, p2, p3);
                sts16(za - 4096, s64); sts16(za - 4032, s64 >> 16);
                sts16(za, s128); sts16(za + 64, s128 >> 16);
            }
            __syncwarp();
            {
                const uint32_t aB = fresh(oB), aC = fresh(oC), aZ = fresh(zr);
                const uint4 zc = lds128(aZ), zd = lds128(aZ + 64);
                const uint32_t zcs[4] = {zc.x, zc.y, zc.z, zc.w}, zds[4] = {zd.x, zd.y, zd.z, zd.w};
                const uint4 yc = lds128(aZ - 4096), yd = lds128(aZ - 4032);
                const uint32_t ycs[4] = {yc.x, yc.y, yc.z, yc.w}, yds[4] = {yd.x, yd.y, yd.z, yd.w};
                uint32_t c[4];
#pragma unroll
                for (int k = 0; k < 4; k++) {
                    uint32_t a[4], b[4];
                    for (int e = 0; e < 2; e++) asm("ldmatrix.sync.aligned.m8n8.x1.trans.shared.b16 {%0}, [%1];" : "=r"(a[2 * e]) : "r"(aB - 2048 + 128 * k + 512 * e));
                    const h2c a1 = cmul_cd(h2c{a[0], a[2]}, *(const __half2*)&ycs[k], *(const __half2*)&yds[k]);
                    a[1] = a1.re; a[3] = a1.im;
                    ldsm4t(b, aB + 128 * k);
                    if (!(k & 1)) ldsm4t(c, aC + 128 * k);
                    const h2c x = cmul_cd(h2c{a[0], a[2]}, *(const __half2*)&zcs[k], *(const __half2*)&zds[k]), y = cmul_cd(h2c{a[1], a[3]}, *(const __half2*)&zcs[k], *(const __half2*)&zds[k]);
                    mma_h(acc[0], a[0], a[1], a[2], a[3], b[0], b[1]);
                    mma_h(acc[1], a[0], a[1], a[2], a[3], b[2], b[3]);
                    mma_h(acc[2], a[0], a[1], a[2], a[3], c[2 * (k & 1)], c[2 * (k & 1) + 1]);
                    mma_h(acc[3], x.re, y.re, x.im, y.im, b[0], b[1]);
                    mma_h(acc[4], x.re, y.re, x.im, y.im, b[2], b[3]);
                    mma_h(acc[5], x.re, y.re, x.im, y.im, c[2 * (k & 1)], c[2 * (k & 1) + 1]);
                }
                asm volatile("" :: "f"(acc[0][0]), "f"(acc[1][0]), "f"(acc[2][0]), "f"(acc[3][0]), "f"(acc[4][0]), "f"(acc[5][0]) : "memory");
            }
            __syncwarp();
            ar = ar1; ai = ai1; W = W1;
        }
        if (threadIdx.x < 32) TSTAMP(21);
        const float i0 = __uint_as_float((ex + 243u) << 23);
        if (half) {
#pragma unroll
            for (int a = 0; a < 6; a++) { acc[a][0] *= i0; acc[a][1] *= i0; acc[a][2] *= i0; acc[a][3] *= i0; }
            if (lane == 0) acc[0][1] -= bf_lo(pD);
#pragma unroll
            for (int a = 0; a < 6; a++) sts128(wb + a * 512, __float_as_uint(acc[a][0]), __float_as_uint(acc[a][1]), __float_as_uint(acc[a][2]), __float_as_uint(acc[a][3]));
            bar_arrive(barid, 64);
        } else {
            bar_sync(barid, 64);
            const uint32_t src = fresh(pstage);
#pragma unroll
            for (int a = 0; a < 6; a++) {
                const uint4 y = lds128(src + lane * 16 + a * 512);
                auto sum = [&](uint32_t x, float c) { return fmaf(c, i0, __uint_as_float(x)); };
                w[4 * (a % 3) + 2 * (a / 3)] = pack_bf16(sum(y.x, acc[a][0]), sum(y.y, acc[a][1]));
                w[4 * (a % 3) + 2 * (a / 3) + 1] = pack_bf16(sum(y.z, acc[a][2]), sum(y.w, acc[a][3]));
            }
            const uint32_t x0 = __shfl_up_sync(0xffffffffu, w[10], 2), x1 = __shfl_up_sync(0xffffffffu, w[11], 2);
            w[10] = w[8];
            if (t >= 2) { w[8] = x0; w[9] = x1; }
        }
    }
}

enum { BC_AUX = 0, BC_U = 5  , BC_Y = 13   };

__device__ __forceinline__ void fetch_gates(const Params& p, int i, int lane, unsigned epoch, uint32_t dst) {
    const uint32_t par = (epoch & 1) ? 0x80008000u : 0u;
    uint4 v;
#pragma unroll 1
    for (int it = 0;; it++) {
        v = ld_rlx128(p.s->gate + 256 * i + 8 * lane);
        v.x ^= par; v.y ^= par; v.z ^= par; v.w ^= par;
        if (__all_sync(0xffffffffu, (v.x & v.y & v.z & v.w & 0x80008000u) == 0x80008000u)) break;
        if (it > (1 << 20)) give_up();
    }
    sts128(dst, v.x, v.y, v.z, v.w);
}
__device__ __forceinline__ void store_rows(const CUtensorMap* m, uint32_t src, int col, int row) {
    asm volatile("cp.async.bulk.tensor.5d.global.shared::cta.bulk_group [%0, {%2, %3, %3, %3, %4}], [%1];" :: "l"(m), "r"(src), "r"(col), "r"(0), "r"(row) : "memory");
}

__device__ __forceinline__ void store_or_add(void* o, const uint32_t (&y)[4], uint32_t add) {
    asm volatile("{ .reg .pred p; setp.ne.u32 p, %5, 0; @!p st.global.v4.u32 [%0], {%1,%2,%3,%4}; @p red.relaxed.gpu.global.add.noftz.v4.bf16x2 [%0], {%1,%2,%3,%4}; }"
                 :: "l"(o), "r"(y[0]), "r"(y[1]), "r"(y[2]), "r"(y[3]), "r"(add) : "memory");
}

__device__ __forceinline__ void conv_aux(const Params& p, const CUtensorMap* mU, uint32_t sb, int aw, int lane, int bid, unsigned epoch) {
    const int g = lane >> 2, t = lane & 3, mi = lane >> 3, r8 = lane & 7;
    const int rank = bid & 1, slab = bid >> 1;
    const uint32_t bar_y = sb + SC_MISC, bar_u = bar_y  , bar_v = bar_y + 8, bar_box = bar_y + 64 + 8 * aw, s_bm = bar_y + 128;
    if (elect()) {
        mbar_init(bar_box, 1); mbar_fence();
        mbar_expect(bar_box, 4096);
        tma4d(sb + SC_RT + 4096 * aw, mU, 16 * slab, 0, 0, 16 * rank + 2 * aw, bar_box);
        mbar_init(bar_y + 8 * aw, aw == 1 ? 8 : 1);
        if (aw == 1) mbar_init(bar_y + 384, 1);
        mbar_fence();
        if (aw != 1) mbar_expect(bar_y + 8 * aw, aw ? 4096 : 16384);
    }
    __syncwarp();
    asm volatile("barrier.cluster.arrive.relaxed.aligned;" ::: "memory");
    asm volatile("setmaxnreg.dec.sync.aligned.u32 88;");
    sts128(sb + (lane < 16 ? SC_UT + aw * UT_STRIDE + mi * (UT_HALF - 128) : SC_V - 256 + aw * V_STRIDE) + lane * 16, 0, 0, 0, 0);
    if (lane < 16) sts128(s_bm + lane * 16, 0, 0, 0, 0);
    {
        const uint32_t dst = sb + SC_UT + g * UT_STRIDE + swz((8 + 64 * rank + 8 * aw + t) * 16, g);
        const uint32_t rdst = mapa(dst, rank ^ 1), rbar = mapa(bar_u, rank ^ 1);
        asm volatile("barrier.cluster.wait.acquire.aligned;" ::: "memory");
        mbar_wait(bar_box);
        if (aw == 0) TSTAMP(1);
        const uint32_t src = fresh(sb + SC_RT) + aw * 4096 + (8 * mi + 4 * (r8 & 1) + (r8 >> 1)) * 32 + ((rank ^ (r8 & 1)) << 4);
        uint32_t x[8][4];
#pragma unroll
        for (int i = 0; i < 4; i++) { ldsm4t(x[i], src + 1024 * i); ldsm4t(x[4 + i], (src ^ 16) + 1024 * i); }
        asm volatile("" :: "r"(x[0][0]), "r"(x[1][0]), "r"(x[2][0]), "r"(x[3][0]) : "memory");
#pragma unroll
        for (int i = 0; i < 4; i++) st_async128((rdst ^ 32 * (i & 2)) + (i & 1) * UT_HALF, x[4 + i][0], x[4 + i][1], x[4 + i][2], x[4 + i][3], rbar);
#pragma unroll
        for (int i = 0; i < 4; i++) sts128((dst ^ 32 * (i & 2)) + (i & 1) * UT_HALF, x[i][0], x[i][1], x[i][2], x[i][3]);
    }
    bar_sync(BC_AUX, 256);
    mbar_wait_cluster(bar_u);
    if (aw == 0) TSTAMP(2);
    if (aw == 6 && elect()) mbar_arrive(bar_y + 384);
    if (aw < 4) bar_sync(BC_U + aw, 64);
    if (aw == 0) TSTAMP(3);
    {
        const uint32_t ws = fresh(sb + SC_UT) + r8 * UT_STRIDE, wd = sb + SC_V + r8 * V_STRIDE;
#pragma unroll 1
        for (int k = aw; k < 13; k += 8) {
            const int a = 8 * k + (k < 12 ? g & 6 : 0);
            const uint32_t d = wd + 64 * a, sw = 16 * (a & 2);
            window_task(ws + swz(16 * a + 96, r8), ws + swz(16 * a + 128, r8), d + sw, d + (sw ^ 32), k);
            if ((k & 12) == 4) bar_arrive(BC_U + k - 4, 64);
        }
    }
    if (aw == 0) TSTAMP(9);
    {
        if (aw >= 2) fetch_gates(p, aw, lane, epoch, sb + SC_GT + (lane & 1) * GT_HALF + (8 + 16 * aw + (lane >> 1)) * 16);
        __syncwarp();
        if (elect()) { mbar_arrive(bar_v); prefetch_map(mU + 4); p.s->epoch[fresh(bid) * 16 + aw + 8] = epoch + 1; }
        if (aw == 0) TSTAMP(4);
        if (aw == 7) {
            const int row = key_row(wait_sel(p, slab >> 1, r8, key_tag(epoch)));
            if (lane < 8) asm volatile("red.shared.or.b32 [%0], %1;" :: "r"(s_bm + (row >> 5) * 4), "r"(1u << (row & 31)) : "memory");
            TSTAMP(10);
        }
        bar_sync(BC_AUX, 256);
        const uint32_t src = sb + SC_RT + ((r8 >> 1) & 1) * Y_RS + (2 * mi + (r8 & 1)) * Y_CS + (2 * aw + (r8 >> 2)) * 16;
        const int rb = 64 * (aw & 4) + 32 * (aw & 1) + ((aw >> 1) & 1) + 2 * rank, row0 = rb + 128 * (g >> 2) + 16 * (t >> 1) + 64 * (g & 1) + 8 * ((g >> 1) & 1);
        __nv_bfloat16* outp = p.out + (size_t)row0 * DM + 16 * slab + 8 * (t & 1);
        const uint32_t stg = sb + SC_KG + 4096 * aw, so = (g & 2) * 256 + (g >> 2) * 128 + r8 * 16;
#pragma unroll 1
        for (int s = 1; s < 4; s++) {
            const uint32_t bm = lds32(fresh(s_bm) + (16 * s + (row0 >> 5)) * 4) >> (row0 & 31);
            const bool routed = __any_sync(0xffffffffu, bm & 0x11u);
            if ((aw & 3) == s) mbar_wait_cluster(bar_y + 16 * s + 2 * (aw & 4));
            bar_sync(BC_Y + (aw >> 2), 128);
            const uint32_t sf = fresh(src) + 512 * s;
            uint32_t y[2][4];
            ldsm4t(y[0], sf); ldsm4t(y[1], sf + 256);
            if (routed) {
#pragma unroll
                for (int k = 0; k < 2; k++) store_or_add(outp + (size_t)(512 * s + 4 * k) * DM, y[k], bm & (1u << (4 * k)));
            } else {
                sts128(stg + so + 1024 * s, y[0][0], y[0][1], y[0][2], y[0][3]); sts128(stg + so + 1024 * s + 256, y[1][0], y[1][1], y[1][2], y[1][3]);
                asm volatile("fence.proxy.async.shared::cta;" ::: "memory");
                __syncwarp();
                if (elect()) store_rows(mU + 4, stg + 1024 * s, 16 * slab, 512 * s + rb);
            }
            if (aw == 4) TSTAMP(16 + s);
            if (aw == 0) TSTAMP(16);
        }
        if (elect()) { asm volatile("cp.async.bulk.commit_group;" ::: "memory"); asm volatile("cp.async.bulk.wait_group.read 0;" ::: "memory"); }
        if (aw == 4) TFLUSH();
    }
}

__device__ __forceinline__ uint32_t k_tag(unsigned epoch) { return epoch << 16 | 0x80000000u; }
__device__ __forceinline__ void publish_k(uint4* kp, const uint32_t (&w)[12], unsigned epoch, uint64_t (&v)[6]) {
#pragma unroll
    for (int i = 0; i < 3; i++) {
        v[2 * i] = w[3 * i] | (uint64_t)w[3 * i + 1] << 32; v[2 * i + 1] = w[3 * i + 2] | (uint64_t)__byte_perm(w[9 + (i >> 1)], k_tag(epoch), i == 1 ? 0x7632 : 0x7610) << 32;
        asm volatile("st.relaxed.gpu.global.v2.u64 [%0], {%1,%2};" :: "l"(kp + 32 * i), "l"(v[2 * i]), "l"(v[2 * i + 1]));
    }
}
template <bool FULL>
__device__ __forceinline__ void k_tables(uint32_t kt, int lane, const uint32_t (&w)[12]) {
    const int g = lane >> 2, t = lane & 3, mi = lane >> 3, r8 = lane & 7;
    uint32_t x3 = w[7], re[4], rx[4];
#pragma unroll
    for (int i = 0; i < 4; i++) {
        re[i] = __shfl_sync(0xffffffffu, w[i], lane + 31);
        rx[i] = __shfl_sync(0xffffffffu, w[4 + i], lane + (i == 0 && lane == 29 ? 5 : 1 + 2 * t));
    }
    if (FULL) {
        asm volatile("stmatrix.sync.aligned.m8n8.x2.trans.shared.b16 [%0], {%1,%2};" :: "r"(kt + (KT_D + 7) * 4 + 64 * t + 16 * (mi & 1) + 8 * (r8 & 4)), "r"(w[8]), "r"(w[9]) : "memory");
        if (lane == 2) {
            sts32(kt + (KT_C + 78) * 4, w[10] & 0xffffu);
            sts128(kt + (KT_T + 2) * 4, 0, w[10] & 0xffffu, __byte_perm(w[10], 0, 0x1010), w[10] << 16);
        }
        if (lane == 29) x3 = bsub2(x3, rx[0] & 0xffffu);
    }
#pragma unroll
    for (int i = 0; i < 4; i++) {
        sts64(kt + (16 + 64 * i) * 4 + 8 * lane, __byte_perm(w[i], lane ? re[i] : i ? re[i - 1] : 0, 0x5432), w[i]);
        const uint32_t x = i < 3 ? w[4 + i] : x3, aa = __byte_perm(x, 0, 0x3232);
        if (t < 2) sts128(kt + (272 + 64 * i + 8 * g + 4 * t) * 4, i == 0 && lane == 0 ? __byte_perm(x, re[3], 0x5432) : aa, aa, x,
                          __byte_perm(lane != 29 ? rx[i] : i < 3 ? rx[(i + 1) & 3] : FULL ? 0 : rx[0] << 16, x, 0x5432));
        else if (FULL) sts32(kt + (KT_C - 50 + 8 * i + 32 * t + g) * 4, x);
    }
}

__device__ __forceinline__ void conv_main(const Params& p, uint32_t sb, int warp, int lane0, int bid, unsigned epoch, uint32_t (&w)[12]) {
    asm volatile("setmaxnreg.inc.sync.aligned.u32 168;");
    const int lane = __shfl_sync(0xffffffffu, lane0, lane0);
    const int g = lane >> 2, t = lane & 3, mi = lane >> 3, r8 = lane & 7;
    const int rank = bid & 1;
    const uint32_t bar_y = sb + SC_MISC, bar_v = bar_y + 8;
    next_epoch(p, epoch);
    asm volatile("barrier.cluster.wait.acquire.aligned;" ::: "memory");
    if (warp >= 4) {
        mbar_wait(bar_y + 384);
        if (KPOLL) until(clock32(), KPOLL);
        const uint4* src = p.s->kp + (8 * bid + warp) * 96 + lane0;
#pragma unroll 1
        for (int it = 0;; it++) {
            uint32_t bad = 0, e[3];
#pragma unroll
            for (int i = 0; i < 3; i++) { const uint4 v = ld_rlx128(src + 32 * i); w[3 * i] = v.x; w[3 * i + 1] = v.y; w[3 * i + 2] = v.z; e[i] = v.w; bad |= v.w ^ k_tag(epoch); }
            w[9] = __byte_perm(e[0], e[1], 0x5410); w[10] = e[2];
            const bool ok = __all_sync(0xffffffffu, bad < 65536);
            if (ok) break;
            if (it > (1 << 20)) give_up();
        }
    }
    if ((warp & 3) == 0) TSTAMP(5 + (warp >> 2));
    k_tables<true>(sb + SC_KT + warp * KT_BYTES, lane0, w);
    mbar_wait(bar_y + 384);
    __syncwarp();
    if ((warp & 3) == 0) TSTAMP(7 + (warp >> 2));
    {
        const uint32_t ut = fresh(sb + SC_UT) + warp * UT_STRIDE, kt = fresh(sb + SC_KT) + warp * KT_BYTES;
        auto dup = [&](uint32_t v) { return v ^ p.zero; };
        auto frag = [&](uint32_t (&a)[4], uint32_t x) { a[0] = lds32(x); a[1] = lds32(x + 32); a[2] = lds32(x - 32); a[3] = dup(a[0]); };
        const uint32_t kb = kt + (16 + g - 2 * t) * 4;
        float acc[16][4];
        {
            float y[12][4], M[6][4];
#pragma unroll
            for (int i = 0; i < 12; i++) { y[i][0] = y[i][1] = y[i][2] = y[i][3] = 0.f; M[i >> 1][0] = M[i >> 1][1] = M[i >> 1][2] = M[i >> 1][3] = 0.f; }
            uint32_t U[10][4], a1[4], ad[4], R = (mi & 1) * UT_HALF + (8 + (r8 >> 1) + 48 * (r8 & 1)) * 16 + 64 * (mi >> 1);
            auto places = [&] { ad[0] = swz(R, warp); ad[1] = swz(R + 128, warp); ad[2] = ad[0] ^ 64; ad[3] = ad[1] ^ 64; };
            auto ldu = [&](int k) { ldsm4(U[k], ut + ad[k & 3] + 256 * (k >> 1)); };
            places();
            frag(a1, kb + 2048);
#pragma unroll
            for (int k = 0; k < 7; k++) ldu(k);
#pragma unroll
            for (int i = 0; i < 12; i++) mma_bf(y[i], a1[0], a1[1], a1[2], a1[3], U[i >> 1][2 * (i & 1)], U[i >> 1][2 * (i & 1) + 1]);
            frag(a1, kb + 1792);
            __syncwarp();
#pragma unroll 1
            for (uint32_t ko = 0; ko != 256;) {
                ko = fresh(ko);
                const uint32_t kp = kb + ko;
                ko += 64;
                uint32_t se[10][2], so[10][2], ue[10][2];
                auto sums = [&](int k) {
#pragma unroll
                    for (int e = 0; e < 2; e++) { ue[k][e] = U[k][e]; se[k][e] = badd2(U[k][e], U[k - 1][2 + e]); so[k][e] = badd2(U[k][e], U[k][2 + e]); }
                };
#pragma unroll
                for (int k = 1; k < 6; k++) sums(k);
#pragma unroll
                for (int m = 3; m >= 0; m--) {
                    uint32_t a0[4];
                    frag(a0, kp + 512 * m);
                    sums(9 - m);
                    if (m) ldu(10 - m); else { R -= 16; places(); }
#pragma unroll
                    for (int i = 0; i < 6; i++) mma_bf(y[2 * i], a1[0], a1[1], a1[2], a1[3], se[i - m + 4][0], se[i - m + 4][1]);
#pragma unroll
                    for (int e = 0; e < 4; e++) a1[e] = bsub2(a0[e], a1[e]);
#pragma unroll
                    for (int i = 0; i < 6; i++) { mma_bf(M[i], a1[0], a1[1], a1[2], a1[3], ue[i - m + 4][0], ue[i - m + 4][1]); if (!m) ldu(i); }
                    frag(a1, m ? kp + 512 * m - 256 : kp + 1792 + 64);
                    if (!m) ldu(6);
#pragma unroll
                    for (int i = 0; i < 6; i++) mma_bf(y[2 * i + 1], a0[0], a0[1], a0[2], a0[3], so[i - m + 4][0], so[i - m + 4][1]);
                }
            }
#pragma unroll
            for (int i = 0; i < 6; i++)
#pragma unroll
                for (int c = 0; c < 4; c++) { acc[4 + i + 6 * (c & 1)][c & 2] = y[2 * i][c] + M[i][c]; acc[4 + i + 6 * (c & 1)][c | 1] = y[2 * i + 1][c] - M[i][c]; }
        }
        const uint32_t lo = (8 + col(r8)) * 16 + (mi >> 1) * 128, ua = fresh(ut) + (mi & 1) * UT_HALF, u1[2] = {ua + swz(lo, warp), ua + (swz(lo, warp) ^ 64)};
        {
            uint32_t e[4];
            frag(e, kb + (KT_T - 16) * 4);
            const uint32_t f0 = dup(e[1]), f1 = lds32(kb + KT_T * 4), uo = fresh(ut) + UT_HALF + swz((7 + 8 * mi + col(r8)) * 16, warp);
#pragma unroll
            for (int i = 0; i < 4; i++) {
                uint32_t b[4];
                if (i < 2) {
                    ldsm4(b, uo + 512 * i);
#pragma unroll
                    for (int k = 0; k < 4; k++) mma_bf8(acc[8 + 4 * i + k], f0, f1, b[k]);
                }
                ldsm4(b, u1[i & 1] + 256 * i);
                mma_bf(acc[2 * i + 8], e[0], e[1], e[2], e[3], b[0], b[1]); mma_bf(acc[2 * i + 9], e[0], e[1], e[2], e[3], b[2], b[3]);
            }
        }
        if ((warp & 3) == 0) TSTAMP(11 + (warp >> 2));
        mbar_wait(bar_v);
        const uint32_t vt = fresh(sb + SC_V) + warp * V_STRIDE;
        const uint32_t g1 = fresh(sb + SC_GT) + (mi & 1) * GT_HALF + lo;
        const uint32_t ydst = mapa(sb + SC_RT + rank * Y_RS + warp * Y_CS + (lane & 23) * 16, mi & 1), ybr = mapa(bar_y, mi & 1);
        uint32_t ug[2][2][4];
        auto ld_ug = [&](int i) { ldsm4t(ug[i & 1][0], u1[i & 1] + 256 * i); ldsm4t(ug[i & 1][1], g1 + 256 * i); };
        auto ship = [&](int i) {
            const uint32_t (&u)[4] = ug[i & 1][0], (&gg)[4] = ug[i & 1][1];
            const uint32_t y0 = gmix(gg[0], acc[2 * i][0], acc[2 * i][1], u[0]), y1 = gmix(gg[1], acc[2 * i][2], acc[2 * i][3], u[1]);
            const uint32_t y2 = gmix(gg[2], acc[2 * i + 1][0], acc[2 * i + 1][1], u[2]), y3 = gmix(gg[3], acc[2 * i + 1][2], acc[2 * i + 1][3], u[3]);
            st_async128(ydst + 512 * (i >> 1) + 128 * (i & 1), y0, y1, y2, y3, ybr + 8 * i);
        };
        const uint32_t VD = vt + (VC_OFF - 400 - 16 * t) * 4 + (8 * g ^ 16 * (-t & 2)), VD2 = vt + (VC_OFF - 415 - 16 * t) * 4 + (8 * g ^ 16 * (~t & 2));
        uint2 bd[10];
        uint32_t x[2][4][4];
        auto ld4 = [&](uint32_t (&v)[4], int dl) { const uint2 w = lds64(VD + 256 * dl); v[0] = w.x; v[1] = w.y; v[2] = lds32(VD2 + 256 * dl); v[3] = dup(w.x); };
        auto mm4 = [&](const uint32_t (&v)[4], int dl) {
#pragma unroll
            for (int s = dl & 1; s < 10; s += 2) if ((dl + s) / 2 >= 4 && (dl + s) / 2 < 16) mma_bf(acc[(dl + s) / 2], v[0], v[1], v[2], v[3], bd[s].x, bd[s].y);
        };
        const uint32_t KE = kt + (KT_D + col(g) + t) * 4, VE = vt + (VE_BASE - 912 - 16 * t) * 4 + (8 * g ^ 16 * (~t & 2));
        uint32_t b0[8], b1[8];
        auto ld8 = [&](uint32_t (&v)[4], int dl) { const uint2 w = lds64(VE + 512 * dl), z = lds64(VE + 512 * dl - 256); v[0] = w.x; v[1] = w.y; v[2] = z.x; v[3] = z.y; };
        auto mm8 = [&](const uint32_t (&v)[4], int dl, int lo, int hi) {
#pragma unroll
            for (int s = 0; s < 8; s++) if (dl + s >= lo && dl + s < hi) mma_bf(acc[dl + s], v[0], v[1], v[2], v[3], b0[s], b1[s]);
        };
        ld4(x[0][0], 6);
#pragma unroll
        for (int s = 0; s < 10; s++) bd[s] = lds64(kt + (KT_C + 2 * col(g) + 2 * t + 8 * s) * 4);
        mm4(x[0][0], 6);
        uint32_t e[8][4];
#pragma unroll
        for (int k = 1; k < 6; k++) {
#pragma unroll
            for (int j = 0; j < 4; j++) ld4(x[k & 1][j], 4 * k + 3 + j);
            ld_ug(k + 1);
            if (k == 3) {
#pragma unroll
                for (int s = 0; s < 8; s++) { b0[s] = lds32(KE + 32 * s); b1[s] = lds32(KE + 32 * s + 16); }
            }
            if (k > 1) ship(k);
#pragma unroll
            for (int j = 0; j < 4; j++) {
                mm4(x[k & 1][j], 4 * k + 3 + j);
                if (k == 3) { ld8(e[j], 8 + j); mm8(e[j], 8 + j, 8, 14); }
                if (k == 5 && j < 2) { ld8(e[4 + j], 12 + j); mm8(e[4 + j], 12 + j, 12, 14); }
            }
        }
        ld_ug(7);
        {
            float (&q0)[4] = acc[0], (&q1)[4] = acc[1];
#pragma unroll
            for (int c = 0; c < 4; c++) q0[c] = q1[c] = 0.f;
            auto m8 = [&](float (&c)[4], int T, int j) { mma_bf(c, e[j][0], e[j][1], e[j][2], e[j][3], b0[T - 8 - j], b1[T - 8 - j]); };
            auto m4 = [&](float (&c)[4], int T, int j) { mma_bf(c, x[0][j][0], x[0][j][1], x[0][j][2], x[0][j][3], bd[2 * T - 27 - j].x, bd[2 * T - 27 - j].y); };
            ship(6);
            ld8(e[6], 14); ld8(e[7], 15);
#pragma unroll
            for (int j = 0; j < 4; j++) ld4(x[0][j], 27 + j);
            m8(q1, 15, 0); m8(q0, 14, 0); m8(q1, 15, 1);
            m8(acc[15], 15, 6); m4(q1, 15, 0); m8(acc[14], 14, 6); m4(q0, 14, 0);
            m8(acc[15], 15, 4); m8(q1, 15, 2); m4(acc[14], 14, 1); m8(q0, 14, 1);
            m4(acc[15], 15, 1); m4(q1, 15, 2); m8(acc[14], 14, 4); m8(q0, 14, 2);
            m8(acc[15], 15, 5); m8(q1, 15, 3); m8(acc[14], 14, 5); m8(q0, 14, 3);
            m4(acc[15], 15, 3); m8(q1, 15, 7);
#pragma unroll
            for (int c = 0; c < 4; c++) { acc[14][c] += q0[c]; acc[15][c] += q1[c]; }
            ship(7);
        }
        if ((warp & 3) == 0) TSTAMP(14 + (warp >> 2)); else TSTAMP(21 + warp);
    }
}

constexpr int SF_WD = 73728;
constexpr int SF_RED = 49152;
constexpr int MU_STRIDE = 1168  , SM_RAW = 98304, SM_UT = SM_RAW + 16384, SM_G = SM_UT + 21504, SM_Y = 196608, SM_FT = SM_Y + 17024, SM_KT = 138880, SM_KW = SM_G - 49152;
constexpr int SF_XS = 221184;
constexpr int SF_MISC = SF_XS + 8 * 1168;
constexpr int SF_KG = SF_MISC - 10 * KG_STAGE;
constexpr int SF_WR = SF_KG - 2304;
constexpr int FB_X = 64, FB_KDONE = 72, FB_KEYS = 80, FB_FREE = 88  , FB_W = 104, FB_D = FB_W + 72, FB_MU = FB_D + 96, FB_FAR = FB_MU - 16, FB_MG = FB_MU + 8, FB_MT = FB_MU + 16  , FS_PART = 512, FS_TOK = 896, FS_BM = 1024;
enum { BAR_R = 7, BAR_GU = 8, BAR_RED = 9, BAR_R2 = 10, BAR_G = 12  , BAR_M = 15 };
static_assert(SF_KG % 128 == 0 && NPRE <= 8 && SM_KT + 4 * 2112 <= 147456 && SM_G + MU_STRIDE <= SF_WR - 4 * 9216 && SM_KW + 6 * 2112 >= SM_RAW && SM_KW + 12 * 2112 <= SM_UT, "layout");

__device__ __forceinline__ constexpr int box_no(int i) { return (0x987610ba5432ull >> (4 * i)) & 15; }
__device__ __forceinline__ int role(int b) { b -= NCONV; return b < NX ? b : 18 + (b >> 1) + 12 * (b & 1); }
__device__ __forceinline__ int mini_ch0(int f) { return 48 * f - (f < NW ? 1696 : 2304); }

__device__ __forceinline__ void ffn_front(const Params& p, const CUtensorMap* maps, uint32_t sb, int warp, int lane, int f, unsigned epoch) {
    const unsigned t0 = clock32();
    const int g = lane >> 2, t = lane & 3, mi = lane >> 3, r8 = lane & 7;
    const bool isx = f < NX;
    const int nrw = f < 52 ? 4 : 6, r0 = f < 52 ? 32 * f : 48 * f - 832;
    const int rw = warp < 12 ? 13 - warp : warp ^ (warp < 14 ? 10 : 15);
    const uint32_t bar_row = sb + SF_MISC  , bar_x = bar_row + FB_X;
    const uint32_t s_part = bar_row + FS_PART  , s_tok = bar_row + FS_TOK  ;
    const uint32_t rows = sb + SF_WR - 9216 * (rw + 1) - (rw & 4) * ((SF_WR - 6 * 9216) / 4);
    {
#pragma unroll 1
        for (int i = warp < 10 ? 30 : warp - 10; i < 30; i += 6) if (elect()) mbar_init(bar_x + 8 * i, i == 1 ? 4 + (f < NW) : i < 27 ? 1 : i == 27 ? 2 : 8);
        const uint32_t bytes = rw < 6 ? 9216 : 1152, dst = rw < 6 ? rows : sb + SF_WR + (rw & 1) * 1152;
        const __nv_bfloat16* src = rw < 6 ? p.u + (size_t)(r0 + 8 * rw) * DM : (rw & 1) ? p.gatew : p.wr;
        if (elect()) { mbar_init(bar_row + 8 * rw, 1); mbar_fence(); mbar_expect(bar_row + 8 * rw, bytes); }
        if (warp == 13) { sts32(s_part + 64 + lane * 4, 0); sts32(bar_row + FS_BM + lane * 4, 0); }
        bar_sync(0, NTHR);
        if (!isx) asm volatile("barrier.cluster.arrive.relaxed.aligned;" ::: "memory");
        if (rw < nrw) until(t0, RDELAY);
        if (rw < nrw || rw >= 6) { if (elect()) bulk_g2s(dst, src, bytes, bar_row + 8 * rw); }
    }
    uint4* const kdst = p.s->keys + (lane >> 1) * 128 + 2 * f + (lane & 1);
    if (warp == 15) TSTAMP(1);

    if (warp == 12) {
        if (lane < 22) mbar_expect(bar_row + FB_W + 8 * lane, lane < 9 ? 24576 : isx ? 12288 : lane < 20 ? 2048 : 16384);
        if (elect()) { prefetch_map(maps + 1); prefetch_map(maps + 2); prefetch_map(maps + (isx ? 3 : 5)); }
        unsigned tb = t0 + WDELAY;
        auto pieces = [&](int n, int end, uint32_t dst) {
#pragma unroll 1
            for (; n < end; n++, dst += 12288) {
                until(tb, 0); tb += WGAP;
                if (elect()) tma3d(dst, maps + 1 + (n & 1), 0, 64 * (n >> 1), 3 * f, bar_row + FB_W + 8 * (n >> 1));
            }
        };
        if (!isx) {
#pragma unroll 1
            for (int k = 0; k <= (f >= NW); k++) { until(t0, MDELAY); if (elect()) tma4d(sb + SM_RAW - 49152 * k, maps + 5, mini_ch0(f) + 16 * k, 0, 0, 0, bar_row + FB_MU - 8 * k); }
            if (f >= NW) return;
        }
#pragma unroll 1
        for (int i = 0; i < 4; i++) {
            if (i == 1) { mbar_wait(bar_row + FB_KEYS); mbar_wait(bar_row + FB_KDONE); tb = clock32() + RESUME; }
            if (i == 3) mbar_wait(bar_row + FB_FREE);
            const int n = ((0x0c080000 + NPRE * 256) >> (8 * i)) & 255;
            pieces(n, ((0x120c0800 + NPRE) >> (8 * i)) & 255, sb + 12288 * (((0x000c0000 + NPRE * 256) >> (8 * i)) & 255));
        }
        TSTAMP(12);
        if (isx) {
#pragma unroll 1
            for (int i = 0; i < 12; i++) {
                const int n = box_no(i);
                if (i == 6) mbar_wait(bar_row + FB_FREE + 8);
                until(tb, 0); tb += DGAP;
                if (elect()) tma2d(sb + SF_WD + n * 12288, maps + 3, 32 * (f >> 1), 2304 * (f & 1) + 192 * n, bar_row + FB_D + 8 * n);
            }
            TSTAMP(13);
        }
    } else if (warp == 13) {
        const uint32_t tag = key_tag(epoch), par = (epoch & 1) ? 0u : 0x8000u;
        stg128(kdst, 0, 0, 0, 0);
        if (lane < 8 && isx && !(f & 1)) st_rlx32(&p.s->sel[32 * f + lane], 0);
        bar_sync(BAR_R, 32 * (nrw + 1));
        TSTAMP(3);
        {
            const uint32_t sg = fresh(s_part) + 192 + lane * 4;
            const uint32_t gb = pack_bf16(sigmoidf_(rbf(__uint_as_float(lds32(sg)))), sigmoidf_(rbf(__uint_as_float(lds32(sg + 128))))) | par | (par << 16);
            asm volatile("st.relaxed.gpu.global.u16 [%0], %1;" :: "l"(p.s->gate + r0 + lane), "h"((unsigned short)gb) : "memory");
            if (nrw > 4 && lane < 16) asm volatile("st.relaxed.gpu.global.u16 [%0], %1;" :: "l"(p.s->gate + r0 + 32 + lane), "h"((unsigned short)(gb >> 16)) : "memory");
        }
        bar_sync(BAR_R2, 32 * (nrw + 1));
        {
            const uint4 v = lds128(fresh(s_tok) + (lane & 1) * 16);
            asm volatile("st.relaxed.gpu.global.v4.u32 [%0], {%1,%2,%3,%4};" :: "l"(kdst), "r"(v.x | tag), "r"(v.y | tag), "r"(v.z | tag), "r"(v.w | tag) : "memory");
        }
        TSTAMP(4);
        if (lane == 0) { mbar_arrive(bar_row + FB_KEYS); mbar_expect(bar_x, 8 * 1152); }
        if (f >= NW) return;
        mbar_wait(bar_row + FB_KDONE);
        uint32_t k[16];
        const uint4* src = p.s->keys + (f & 15) * 128 + lane;
#pragma unroll 1
        for (int it = 0;; it++) {
            uint32_t bad = 0;
#pragma unroll
            for (int i = 0; i < 4; i++) {
                const uint4 x = ld_rlx128(src + (i < 3 || lane < 24 ? 32 * i : 64));
                k[i] = x.x; k[4 + i] = x.y; k[8 + i] = x.z; k[12 + i] = x.w;
                bad |= x.x ^ tag;
            }
            const bool ok = __all_sync(0xffffffffu, (bad & 0xf800u) == 0);
            if (ok) break;
            if (it > (1 << 20)) give_up();
        }
        TSTAMP(5);
        uint32_t key = 0, m = __reduce_max_sync(0xffffffffu, max(max(k[0], k[1]), max(k[2], k[3])));
#pragma unroll 2
        for (int r = 0; r < 8; r++) {
            bool pop[4];
#pragma unroll
            for (int i = 0; i < 4; i++) { pop[i] = k[i] == m; k[i] = pop[i] ? k[4 + i] : k[i]; }
            const uint32_t mn = __reduce_max_sync(0xffffffffu, max(max(k[0], k[1]), max(k[2], k[3])));
            if (elect()) bulk_g2s(sb + SF_XS + r * 1168, p.u + (size_t)key_row(m) * DM, 1152, bar_x);
#pragma unroll
            for (int i = 0; i < 4; i++) { k[4 + i] = pop[i] ? k[8 + i] : k[4 + i]; k[8 + i] = pop[i] ? k[12 + i] : k[8 + i]; k[12 + i] = pop[i] ? 0 : k[12 + i]; }
            if (r8 == r) key = m;
            m = mn;
        }
        const int row = key_row(key);
        sts32(s_tok + r8 * 8, row);
        TSTAMP(6);
        if (isx) {
            if (!(f & 1)) {
                __nv_bfloat16* o = p.out + (size_t)row * DM + 16 * f + 8 * mi;
                asm volatile("st.relaxed.gpu.global.v4.u32 [%0], {%1,%1,%1,%1};" :: "l"(o), "r"(0) : "memory");
                if (__any_sync(0xffffffffu, ld_rlx32(o) != 0)) give_up();
                if (lane < 8) st_rlx32(&p.s->sel[32 * f + lane], key);
            } else wait_sel(p, f >> 1, r8, tag);
            uint32_t gb;
#pragma unroll 1
            for (int it = 0;; it++) {
                asm volatile("ld.relaxed.gpu.global.u16 %0, [%1];" : "=r"(gb) : "l"(p.s->gate + row) : "memory");
                gb ^= par;
                if (!(gb & 0x8000u)) break;
                if (it > (1 << 20)) give_up();
            }
            const uint32_t rb = key ^ 0x80000000u, rv = (rb ^ (((int)rb >> 31) & 0x7fff0000u)) & 0xffff0000u;
            sts32(s_tok + r8 * 8 + 4, __float_as_uint(rbf(1.0f - bf_lo(gb)) * rbf(sigmoidf_(__uint_as_float(rv)))));
            __syncwarp();
            TSTAMP(7);
            bar_arrive(BAR_RED, 416);
        }
    } else {
        if (rw < nrw) {
            float c[3][4];
#pragma unroll
            for (int i = 0; i < 3; i++) { c[i][0] = c[i][1] = c[i][2] = c[i][3] = 0.f; }
            mbar_wait(bar_row + 48); mbar_wait(bar_row + 56);
            const uint32_t b = fresh(sb + SF_WR) + (g & 1) * 1152 + (g >> 2) * 64 + t * 16 + (g & 2) * 2;
            uint32_t w[18][2];
#pragma unroll
            for (int kb = 0; kb < 18; kb++) { const uint32_t o = ((kb & 1) ? b ^ 64 : b) + 128 * (kb >> 1); w[kb][0] = lds32(o); w[kb][1] = lds32(o + 8); }
            mbar_wait(bar_row + 8 * rw);
            if (warp == 15) TSTAMP(2);
            const uint32_t a = fresh(rows) + g * 1152 + (g & 1) * 64 + t * 16;
#pragma unroll
            for (int kb = 0; kb < 18; kb++) {
                const uint4 x = lds128(((kb & 1) ? a ^ 64 : a) + 128 * (kb >> 1));
                mma_bf(c[kb % 3], x.x, x.y, x.z, x.w, w[kb][0], w[kb][1]);
            }
            const float sr = c[0][0] + c[1][0] + c[2][0] + __shfl_down_sync(0xffffffffu, c[0][2] + c[1][2] + c[2][2], 1);
            const float sg = c[0][1] + c[1][1] + c[2][1] + __shfl_down_sync(0xffffffffu, c[0][3] + c[1][3] + c[2][3], 1);
            const uint32_t rb = pack_bf16(0.f, sr);
            if (t == 2 * (g & 1)) {
                sts32(s_part + (8 * rw + g) * 4, (rb ^ (((int)rb >> 31) & 0x7fff0000u) ^ 0x80000000u) | (uint32_t)(2047 - r0 - 8 * rw - g));
                sts32(s_part + 192 + (8 * rw + g) * 4, __float_as_uint(sg));
            }
            __syncwarp();
            bar_sync(BAR_R, 32 * (nrw + 1));
            const uint32_t sk = fresh(s_part), kk = lds32(sk + (8 * rw + r8) * 4);
            int n = 0;
#pragma unroll
            for (int i = 0; i < 3; i++) { const uint4 v = lds128(sk + mi * 48 + 16 * i); n += (v.x > kk) + (v.y > kk) + (v.z > kk) + (v.w > kk); }
            n += __shfl_xor_sync(0xffffffffu, n, 8); n += __shfl_xor_sync(0xffffffffu, n, 16);
            if (n < 8) sts32(s_tok + 4 * n, kk);
            __syncwarp();
            bar_arrive(BAR_R2, 32 * (nrw + 1));
        }
    }
}

__device__ __forceinline__ void ffn_work(const Params& p, uint32_t sb, int warp, int lane, int f, unsigned epoch) {
    const int g = lane >> 2, t = lane & 3, mi = lane >> 3, r8 = lane & 7;
    const bool isx = f < NX;
    const uint32_t bar_x = sb + SF_MISC + FB_X, bar_free = sb + SF_MISC + FB_FREE, bar_w = sb + SF_MISC + FB_W, bar_d = sb + SF_MISC + FB_D, s_tok = sb + SF_MISC + FS_TOK;
    uint32_t fr[24][4];
    auto pin = [&] {
#pragma unroll
        for (int i = 0; i < 24; i += 8) asm volatile("" :: "r"(fr[i][0]), "r"(fr[i + 1][0]), "r"(fr[i + 2][0]), "r"(fr[i + 3][0]), "r"(fr[i + 4][0]), "r"(fr[i + 5][0]), "r"(fr[i + 6][0]), "r"(fr[i + 7][0]) : "memory");
    };
    {
        const int j = (unsigned)(warp - 4) < 6, w = warp - (j ? 4 : warp < 4 ? 0 : 6);
        float ag[2][4], au[2][4];
#pragma unroll
        for (int i = 0; i < 2; i++) { ag[i][0] = ag[i][1] = ag[i][2] = ag[i][3] = 0.f; au[i][0] = au[i][1] = au[i][2] = au[i][3] = 0.f; }
        const uint32_t wb = sb + (w >> 1) * 4096 + (r8 + 8 * (mi >> 1)) * 64 + (((2 * (w & 1) + (mi & 1)) ^ (r8 >> 1)) << 4);
        const uint32_t xb = sb + SF_XS + r8 * 1168 + mi * 16;
        auto load = [&](int i, int n, int place) {
            mbar_wait(bar_w + 8 * n);
            const uint32_t wk = fresh(wb) + place * 24576;
#pragma unroll
            for (int s = 0; s < 4; s++) { ldsm4t(fr[8 * i + s], wk + 1024 * s); ldsm4t(fr[8 * i + 4 + s], wk + 1024 * s + 12288); }
        };
        auto mul = [&](int i, uint32_t xk) {
            uint32_t x[2][4];
            ldsm4(x[0], xk); ldsm4(x[1], xk + 64);
#pragma unroll
            for (int s = 0; s < 4; s++) {
                const uint32_t (&a)[4] = fr[8 * i + s], (&b)[4] = fr[8 * i + 4 + s];
                mma_bf(ag[s & 1], a[0], a[1], a[2], a[3], x[s >> 1][2 * (s & 1)], x[s >> 1][2 * (s & 1) + 1]);
                mma_bf(au[s & 1], b[0], b[1], b[2], b[3], x[s >> 1][2 * (s & 1)], x[s >> 1][2 * (s & 1) + 1]);
            }
        };
#pragma unroll
        for (int i = 0; i < 3; i++) load(i, 3 * j + i, (i ? 5 : 3) * j + i);
        pin();
        bar_sync(BAR_G + j, 192);
        if (w == 0 && lane == 0) mbar_arrive(bar_free + 8 * j);
        mbar_wait(bar_x);
        if (warp == 0) TSTAMP(8);
        {
            const uint32_t xk = fresh(xb) + 384 * j;
#pragma unroll
            for (int i = 0; i < 3; i++) { mul(i, (i ? fresh(xk) : xk) + 128 * i); if (i == 0) { asm volatile("" :: "f"(ag[0][0]), "f"(ag[1][0]), "f"(au[0][0]), "f"(au[1][0])); sts32(s_tok + 64, clock32()); } }
        }
#pragma unroll 1
        for (int n = 6 + j; n < 9; n += 2) { load(0, n, n - 6); mul(0, fresh(xb) + 128 * n); }
#pragma unroll
        for (int c = 0; c < 4; c++) { ag[0][c] += ag[1][c]; au[0][c] += au[1][c]; }
        if (j) {
            sts128(wb + 24576, __float_as_uint(ag[0][0]), __float_as_uint(ag[0][1]), __float_as_uint(ag[0][2]), __float_as_uint(ag[0][3]));
            sts128(wb + 25600, __float_as_uint(au[0][0]), __float_as_uint(au[0][1]), __float_as_uint(au[0][2]), __float_as_uint(au[0][3]));
        }
        bar_sync(BAR_GU, 384);
        if (!j) {
            const uint32_t sf = fresh(wb);
            const uint4 g1 = lds128(sf + 24576), u1 = lds128(sf + 25600);
            const uint32_t gs[4] = {g1.x, g1.y, g1.z, g1.w}, us[4] = {u1.x, u1.y, u1.z, u1.w};
            if (warp == 0) TSTAMP(9);
            float h[4];
#pragma unroll
            for (int c = 0; c < 4; c++) {
                const float gv = rbf(ag[0][c] + __uint_as_float(gs[c]));
                h[c] = rbf(gv * sigmoidf_(gv)) * rbf(au[0][c] + __uint_as_float(us[c]));
            }
            uint32_t h0, h1;
            asm("movmatrix.sync.aligned.m8n8.trans.b16 %0, %1;" : "=r"(h0) : "r"(pack_bf16(h[0], h[1])));
            asm("movmatrix.sync.aligned.m8n8.trans.b16 %0, %1;" : "=r"(h1) : "r"(pack_bf16(h[2], h[3])));
            if (h0 == 0) h0 = 0x8000u;
            asm volatile("{ .reg .b64 v; mov.b64 v, {%1, %2}; st.relaxed.gpu.global.b64 [%0], v; }" :: "l"(p.s->h + ((epoch & 1) * 288 + 6 * f + w) * 32 + lane), "r"(h0), "r"(h1) : "memory");
        }
        if (isx) {
            if (warp == 0) TSTAMP(10);
            const uint2* hsrc = p.s->h + ((epoch & 1) * 288 + 144 * (f & 1) + warp) * 32 + lane;
            const uint32_t wd = sb + SF_WD + warp * 1024 + (r8 + 8 * (mi >> 1)) * 64 + (((mi & 1) ^ (r8 >> 1)) << 4), we = wd ^ 32;
            uint2 hb[12];
            auto ldh = [&](int i) { asm volatile("ld.relaxed.gpu.global.v2.u32 {%0, %1}, [%2];" : "=r"(hb[i].x), "=r"(hb[i].y) : "l"(hsrc + 384 * box_no(i)) : "memory"); };
            auto ldw = [&](int i) { mbar_wait(bar_d + 8 * box_no(i)); ldsm4t(fr[2 * i], fresh(wd) + 12288 * box_no(i)); ldsm4t(fr[2 * i + 1], fresh(we) + 12288 * box_no(i)); };
#pragma unroll
            for (int i = 0; i < DPA; i++) ldw(i);
#pragma unroll
            for (int i = 0; i < 12; i++) ldh(i);
#pragma unroll
            for (int i = DPA; i < DPB; i++) ldw(i);
#pragma unroll
            for (int i = 0; i < DPB; i++) asm volatile("" :: "r"(fr[2 * i][0]), "r"(fr[2 * i + 1][0]) : "memory");
#pragma unroll 1
            for (int it = 0;; it++) {
                bool again = false;
#pragma unroll
                for (int s = 0; s < 12; s += 2) if (__any_sync(0xffffffffu, min(hb[s].x, hb[s + 1].x) == 0)) { ldh(s); ldh(s + 1); again = true; }
                if (!again) break;
                if (it > (1 << 16)) give_up();
            }
            if (warp == 0) TSTAMP(11);
            float ad[2][2][4];
#pragma unroll
            for (int i = 0; i < 4; i++) { ad[i >> 1][i & 1][0] = ad[i >> 1][i & 1][1] = ad[i >> 1][i & 1][2] = ad[i >> 1][i & 1][3] = 0.f; }
#pragma unroll
            for (int i = 0; i < 12; i++) {
                if (i >= DPB) ldw(i);
                if (i == 11 && warp == 9) TSTAMP(14);
#pragma unroll
                for (int c = 0; c < 2; c++) mma_bf(ad[c][i & 1], fr[2 * i + c][0], fr[2 * i + c][1], fr[2 * i + c][2], fr[2 * i + c][3], hb[i].x, hb[i].y);
                if (i >= DPB - 1) asm volatile("" :: "f"(ad[0][i & 1][0]), "f"(ad[1][i & 1][0]) : "memory");
            }
            const uint32_t rd = sb + SF_RED + warp * 1152 + (72 * t + g) * 4;
#pragma unroll
            for (int i = 0; i < 8; i++) sts32(rd + (i >> 2) * 64 + (i & 1) * 144 + ((i >> 1) & 1) * 32, __float_as_uint(ad[i >> 2][0][i & 3] + ad[i >> 2][1][i & 3]));
            bar_sync(BAR_RED, 416);
            if (warp < 4) {
                const int tid = 32 * warp + lane;
                const uint32_t rs = fresh(sb + SF_RED) + (tid >> 4) * 144 + (tid & 15) * 8;
                const uint2 tk = lds64(fresh(s_tok) + (tid >> 4) * 8);
                float x = 0.f, y = 0.f;
#pragma unroll
                for (int w = 0; w < 12; w++) { const uint2 v = lds64(rs + w * 1152); x += __uint_as_float(v.x); y += __uint_as_float(v.y); }
                asm volatile("red.relaxed.gpu.global.add.noftz.bf16x2 [%0], %1;" :: "l"(p.out + (size_t)tk.x * DM + 32 * (f >> 1) + 2 * (tid & 15)),
                             "r"(pack_bf16(x * __uint_as_float(tk.y), y * __uint_as_float(tk.y))) : "memory");
            }
            if (warp == 0) { TSTAMP(15); TFLUSH(); }
            asm volatile("exit;"); __builtin_unreachable();
        }
    }
}

__device__ __forceinline__ void fetch_k(const uint4* src, uint64_t (&v)[6], uint32_t a, uint32_t b) {
    asm volatile("{ .reg .pred p; setp.eq.u32 p, %7, %8; @p ld.relaxed.gpu.global.v2.u64 {%0,%1}, [%6]; @p ld.relaxed.gpu.global.v2.u64 {%2,%3}, [%6 + 512]; @p ld.relaxed.gpu.global.v2.u64 {%4,%5}, [%6 + 1024]; }"
                 : "+l"(v[0]), "+l"(v[1]), "+l"(v[2]), "+l"(v[3]), "+l"(v[4]), "+l"(v[5]) : "l"(src), "r"(a), "r"(b));
}
__device__ __forceinline__ uint32_t mini_conv(const Params& p, uint32_t sb, int warp, int lane, int f, unsigned epoch, uint64_t (&v)[6]) {
    const int g = lane >> 2, t = lane & 3, mi = lane >> 3, r8 = lane & 7;
    const uint32_t fb = sb + SF_MISC, kt = sb + (warp >= 12 ? SM_KT - 12 * 2112 : f < NW ? SM_KW + 2 * 2112 : SM_KW) + warp * 2112;
    const bool ism = f >= NW;
    const uint32_t* const sel = &p.s->sel[((mini_ch0(f) + (ism ? 2 * (warp & 8) : 0)) >> 5) * 64 + r8];
    uint32_t seq = 128, key;
    const uint4* src = p.s->kp + lane;
    auto hi = [&](int i) { return (uint32_t)(v[i] >> 32); };
    if (f >= (warp < 4 ? NW : NX)) {
    {
        const uint32_t c = 68 + (warp & 3) + 2 * (warp & 12), y = ((uint32_t)((warp < 8 ? 0xe066806400000000ull : 0x5a6e00680080e26cull) >> ((8 * warp) & 48)) & 0xffff) + (warp < 14 ? 0 : 0x6a0000);
        seq = !ism ? y + (warp & 1) * ((y >> 6) & 0x10101) : warp < 14 ? 0x101 * c - 0x400 : c;
        src += (48 * (f - (ism ? NW : NX)) + (seq & 63)) * 96;
    }
    if (seq & 64) {
        if (seq & 4) {
            const int q = (seq & 3) + ((seq >> 1) & 4);
            const uint32_t ab = sb - 3072 * (seq & 16), d = ab + SM_UT + g * MU_STRIDE + (4 + 4 * q + t) * 32;
            asm volatile("st.shared.v2.u32 [%0], {%1,%1};" :: "r"(ab + SM_UT + (2 * q + (mi >> 1)) * MU_STRIDE + (lane & 15) * 8), "r"(0) : "memory");
            mbar_wait(fb + FB_MU - (seq & 16) / 2);
            if (warp == 15) TSTAMP(16);
            const uint32_t a = fresh(ab + SM_RAW) + q * 2048 + (8 * mi + 4 * (r8 & 1) + (r8 >> 1)) * 32 + ((r8 & 1) << 4);
            uint32_t x[4][4];
#pragma unroll
            for (int i = 0; i < 4; i++) ldsm4t(x[i], (i & 2 ? a ^ 16 : a) + 1024 * (i & 1));
#pragma unroll
            for (int i = 0; i < 4; i++) sts128(d + (i & 1) * 16 + (i & 2) * 4 * MU_STRIDE, x[i][0], x[i][1], x[i][2], x[i][3]);
            __syncwarp();
            if (lane == 0) mbar_arrive(fb + FB_MT + (seq & 16) / 2);
        }
        mbar_wait(fb + FB_KDONE);
        fetch_k(src, v, warp < 4, 0);
        if ((warp | 2) == 7) { fetch_gates(p, (warp >> 1) & 1, lane, epoch, sb + SM_G + 256 * (warp & 2) + 16 * lane); __syncwarp(); if (lane == 0) mbar_arrive(fb + FB_MG); }
        if (warp >= 8) {
            mbar_wait(fb + FB_KEYS); mbar_wait(fb + FB_MT);
            if (ism) {
                asm volatile("barrier.cluster.wait.aligned; fence.release.sync_restrict::shared::cta.cluster;" ::: "memory");
                if (lane == 0) asm volatile("mbarrier.arrive.relaxed.cluster.shared::cluster.b64 _, [%0];" :: "r"(mapa(fb + FB_MT + 8, 0)) : "memory");
            }
        }
        if (warp == TW) TSTAMP(17);
    }
    }
    const uint32_t lo = (8 + r8 - (mi & 1)) * 16 + (mi >> 1) * 128;
#pragma unroll 1
    do {
        const int c = seq & 63;
        const bool far = !ism && (seq & 16);
        const uint32_t ab = sb - 3072 * (c & 16);
        uint32_t ut = ab + SM_UT + (c & 15) * MU_STRIDE;
        if (seq & 64) {
        if (far) {
            mbar_wait_cluster(fb + FB_MT + 8);
            const uint32_t ru = mapa(ut, 1) + lane * 16;
            ut = sb + SM_FT + (c & 3) * 1536;
            uint4 x[3];
#pragma unroll
            for (int i = 0; i < 3; i++) asm volatile("ld.shared::cluster.v4.u32 {%0,%1,%2,%3}, [%4];" : "=r"(x[i].x), "=r"(x[i].y), "=r"(x[i].z), "=r"(x[i].w) : "r"(ru + 512 * i) : "memory");
#pragma unroll
            for (int i = 0; i < 3; i++) sts128(ut + lane * 16 + 512 * i, x[i].x, x[i].y, x[i].z, x[i].w);
        } else mbar_wait(fb + FB_MT + (seq & 16) / 2);
#pragma unroll 1
        for (int it = 0; !__all_sync(0xffffffffu, ((hi(1) ^ k_tag(epoch)) | (hi(3) ^ k_tag(epoch)) | (hi(5) ^ k_tag(epoch)) | ((uint32_t)v[5] & p.zero)) < 65536); it++) {
            fetch_k(src, v, 0, 0);
            if (it > (1 << 20)) give_up();
        }
        sts128(kt + t * 16, 0, 0, 0, 0);
        if (warp == TW) TSTAMP(seq >> 8 ? 7 : 10);
        const uint32_t w[12] = {(uint32_t)v[0], hi(0), (uint32_t)v[1], (uint32_t)v[2], hi(2), (uint32_t)v[3], (uint32_t)v[4], hi(4), 0, 0, 0, 0};
        k_tables<false>(fresh(kt), fresh(lane), w);
        }
        __syncwarp();
        if (seq & 128) ffn_work(p, sb, warp, fresh(lane), f, epoch);
        if (!(seq & 64)) return 0;
        const uint32_t kb = fresh(kt) + (16 + g - 2 * t) * 4, ub = fresh(ut);
        const uint32_t yd = ab + SM_Y + (c & 15) * 1056 + (c & 8) * 8 + lane * 16;
        if (warp == TW && !(seq >> 8)) TSTAMP(13);
        seq >>= 8;
        src += ((int)(seq & 63) - c) * 96;
#pragma unroll
        for (int i = 0; i < 6; i++) v[i] = 0;
        key = 0;
        float acc[8][4];
#pragma unroll
        for (int i = 0; i < 8; i++) { acc[i][0] = acc[i][1] = acc[i][2] = acc[i][3] = 0.f; }
        uint32_t a[4][4], b[2][4][4];
        auto lda = [&](int j, int s) { const uint32_t x = kb + 64 * s + 512 * j; a[j][0] = lds32(x); a[j][1] = lds32(x + 256); a[j][2] = lds32(x + 32); a[j][3] = lds32(x + 288); };
        auto ldb = [&](int i, int s) { ldsm4(b[s & 1][i], ub + lo + 256 * i - 32 * s); };
#pragma unroll
        for (int j = 0; j < 4; j++) { ldb(j, 0); lda(j, 0); }
#pragma unroll
        for (int s = 0; s < 4; s++) {
            if (s == 2) {
                const uint32_t e = seq | (__float_as_uint(acc[0][0]) & p.zero);
                fetch_k(src, v, e & 64, 64);
                asm volatile("{ .reg .pred p; setp.eq.u32 p, %2, 0; @p ld.relaxed.gpu.global.u32 %0, [%1]; }" : "+r"(key) : "l"(sel), "r"(e));
            }
#pragma unroll
            for (int i = 0; i < 4; i++) {
                const int j = (i >> 1) + 2 * (i & 1);
                if (s < 3) ldb(i, s + 1);
#pragma unroll
                for (int mu = 0; mu < 8; mu++) if (mu + 2 * j < 8) mma_bf(acc[mu + 2 * j], a[j][0], a[j][1], a[j][2], a[j][3], b[s & 1][mu >> 1][2 * (mu & 1)], b[s & 1][mu >> 1][2 * (mu & 1) + 1]);
                if (s < 3) lda(j, s + 1);
            }
        }
        if (warp == TW && !seq) TSTAMP(14);
        mbar_wait(fb + FB_MG);
        uint32_t ug[4][4];
#pragma unroll
        for (int i = 0; i < 2; i++) { ldsm4t(ug[i], ub + 128 + lane * 16 + 512 * i); ldsm4t(ug[2 + i], fresh(sb + SM_G) + lane * 16 + 512 * i); }
#pragma unroll
        for (int x = 0; x < 8; x++) ug[x >> 2][x & 3] = gmix(ug[2 + (x >> 2)][x & 3], x ? acc[x][0] + acc[x - 1][2] : acc[0][0], x ? acc[x][1] + acc[x - 1][3] : acc[0][1], ug[x >> 2][x & 3]);
        if (far) for (int i = 0; i < 2; i++) st_async128(mapa(yd, 1) + 512 * i, ug[i][0], ug[i][1], ug[i][2], ug[i][3], mapa(fb + FB_FAR, 1));
        else for (int i = 0; i < 2; i++) sts128(yd + 512 * i, ug[i][0], ug[i][1], ug[i][2], ug[i][3]);
        __syncwarp();
        if (warp == TW) TSTAMP(18 + (seq != 0));
    } while (seq);
    if (warp >= 12) TSTAMP(12 + warp);
    return key;
}
__device__ __forceinline__ void mini_out(const Params& p, const CUtensorMap* maps, uint32_t sb, int warp, int lane, int f, unsigned epoch, uint32_t key) {
    const int g = lane >> 2, t = lane & 3, mi = lane >> 3, r8 = lane & 7;
    const uint32_t fb = sb + SF_MISC;
    const bool ism = f >= NW;
    const int ch0 = mini_ch0(f);
    const int k = ism ? warp >> 3 : 0;
    uint32_t first = 1;
    if (lane == 0) asm volatile("atom.shared.exch.b32 %0, [%1], 1;" : "=r"(first) : "r"(fb + FS_BM + 64 + 4 * k) : "memory");
    if (!__all_sync(0xffffffffu, first)) {
        if (elect()) prefetch_map(maps + 6);
        const int row = key_row(wait_sel(p, (ch0 + 16 * k) >> 5, r8, key_tag(epoch), key));
        if (row < 512) asm volatile("red.shared.or.b32 [%0], %1;" :: "r"(fb + FS_BM + (row >> 5) * 4), "r"(1u << (row & 31)) : "memory");
        if (k) mbar_wait_cluster(fb + FB_FAR);
    }
    const int m = warp & 7, dr = 64 * (g >> 1) + 16 * (t >> 1) + 8 * (g & 1);
    const uint32_t y = SM_Y + ((r8 >> 1) & 1) * 8512 + (2 * mi + (r8 & 1)) * 1056 + (2 * m + (r8 >> 2)) * 16;
    const uint32_t so = (g >> 1) * 128 + (t >> 1) * 64 + (g & 1) * 32 + (t & 1) * 16;
    bar_sync(BAR_M - k, ism ? 256 : NTHR);
#pragma unroll 1
    for (int h = ism ? 0 : warp >> 3;; h++) {
        const int r0 = 256 * h + 32 * (m & 1) + (m >> 1), row = r0 + dr;
        const uint32_t bm = lds32(fresh(fb) + FS_BM + (row >> 5) * 4) >> (row & 31), ab = fresh(sb - 49152 * k + 512 * h), stg = ab + SM_UT + 2048 * m + 512 * h;
        uint32_t x[2][4];
        ldsm4t(x[0], ab + y); ldsm4t(x[1], ab + y + 256);
        if (warp == 0 && x[0][0] != 0x12345) TSTAMP(28);
        if (__any_sync(0xffffffffu, bm & 0x11u)) {
#pragma unroll
            for (int i = 0; i < 2; i++) store_or_add(p.out + (size_t)(row + 4 * i) * DM + ch0 + 16 * k + 8 * (t & 1), x[i], bm & (1u << (4 * i)));
        } else {
#pragma unroll
            for (int i = 0; i < 2; i++) sts128(stg + so + 512 * i, x[i][0], x[i][1], x[i][2], x[i][3]);
            asm volatile("fence.proxy.async.shared::cta;" ::: "memory");
            __syncwarp();
            if (elect()) store_rows(maps + 6, stg, ch0 + 16 * k, r0);
        }
        if (h >= ism) break;
    }
    if (elect()) { asm volatile("cp.async.bulk.commit_group;" ::: "memory"); asm volatile("cp.async.bulk.wait_group.read 0;" ::: "memory"); }
    if (warp == 8) TSTAMP(11);
    if (warp == 0) { TSTAMP(15); TFLUSH(); }
}

constexpr int SMEM_BYTES = 232448;
static_assert(SF_MISC + 1152 <= 232192, "layout");

struct Maps { CUtensorMap m[7]; };

__global__ void __cluster_dims__(2, 1, 1) __launch_bounds__(NTHR, 1)
fused_kernel(const Params p, const __grid_constant__ Maps maps) {
    extern __shared__ __align__(1024) uint8_t smem_raw[];
    uint32_t q[8];
    {
        const int b = role(blockIdx.x), x = threadIdx.x, rc = 5 * b + (b & ~3) + 4 + (x >> 6);
        const int cv = (unsigned)b < NW ? 0 : -1, ca = (b < 0 ? 8 * b + DM : 48 * b - 2300) + ((x >> 5) & 3), cb = 2 * rc - (rc & 3) + 4;
        const uint32_t ch = (ca & cv) | (cb & ~cv), o = NST * ch + 2 * ((x & 31) + ((x >> (cv & 2)) & 32));
        const bool c = x < (cv ? 256 : 320);
        q[6] = ldg16_if(c, p.logdt + ch);
        q[2] = ldg32_if(c, p.Bre + o); q[3] = ldg32_if(c, p.Bim + o); q[4] = ldg32_if(c, p.Cre + o); q[5] = ldg32_if(c, p.Cim + o); q[0] = ldg32_if(c, p.Are + o); q[1] = ldg32_if(c, p.Aim + o);
        q[7] = ldg16_if(c, p.Dskip + ch);
    }
    const unsigned epoch = ld_rlx32(&p.s->epoch[blockIdx.x * 16 + (threadIdx.x >> 5)]);
    const uint32_t sb = __shfl_sync(0xffffffffu, smem_u32(smem_raw), 0);
    const int warp = __shfl_sync(0xffffffffu, threadIdx.x >> 5, 0), bid = __shfl_sync(0xffffffffu, blockIdx.x, 0);
    const int lane = __shfl_sync(0xffffffffu, threadIdx.x & 31, threadIdx.x);
    const bool conv = bid < NCONV;
    const int f = role(bid);
    uint32_t w[12];
    uint64_t v[6];
    const bool four = (unsigned)f >= NW;
    if (warp < (four ? 8 : 10)) {
        const int half = four ? warp >> 2 : warp & 1, pr = four ? warp & 3 : warp >> 1;
        const int rc = 5 * f + (f & ~3) + 4 + pr;
        const uint32_t stage = sb + (conv ? SC_KG : SF_KG) + warp * KG_STAGE;
        uint4* const kp = p.s->kp + (four ? (conv ? 8 * bid : 48 * f - 2300) + pr : 2 * rc - (rc & 3) + 4) * 96 + lane;
        kgen(q, sb, half, stage, stage + (four ? 4 : 1) * KG_STAGE, 1 + pr, lane, w, [&] {
            sts128z_if(conv && lane < 20, sb + SC_KT + warp * KT_BYTES + lane * 16 + (lane < 4 ? 0 : lane < 14 ? 2048 : 2288));
            stg128z_if(!conv, kp + 64 * half); stg128z_if(!half && !conv, kp + 32);
            stg128z_if((unsigned)f < NW && warp < 6, (uint4*)(p.s->h + ((lane >> 4) * 288 + 6 * f + warp) * 32) + (lane & 15));
            if (!conv) bar_sync(0, NTHR);
            if ((unsigned)f >= NX) asm volatile("barrier.cluster.arrive.relaxed.aligned;" ::: "memory");
        });
        if (!half) publish_k(kp, w, epoch, v);
        else for (int i = 0; i < 6; i++) v[i] = 0;
        if (conv) { conv_main(p, sb, warp, lane, bid, epoch, w); return; }
        {
            if (!half && lane == 0) mbar_arrive(sb + SF_MISC + FB_KDONE);
            if (warp == 0) TSTAMP(22);
            if (warp == 2) TSTAMP(23);
        }
    } else if (conv) {
        conv_aux(p, maps.m, sb, warp - 8, lane, bid, epoch);
        return;
    } else {
        ffn_front(p, maps.m, sb, warp, lane, f, epoch);
        for (int i = 0; i < 6; i++) v[i] = 0;
    }
    converged();
    next_epoch(p, epoch);
    if (warp >= 12 && f < NX) return;
    mini_out(p, maps.m, sb, warp, lane, f, epoch, mini_conv(p, sb, warp, __shfl_sync(0xffffffffu, lane, lane), f, epoch, v));
}

typedef CUresult (*EncodeFn)(CUtensorMap*, CUtensorMapDataType, cuuint32_t, void*, const cuuint64_t*, const cuuint64_t*, const cuuint32_t*, const cuuint32_t*,
                             CUtensorMapInterleave, CUtensorMapSwizzle, CUtensorMapL2promotion, CUtensorMapFloatOOBfill);

void make_map(EncodeFn fn, CUtensorMap* m, const void* base, int rank, const cuuint64_t* dims, const cuuint64_t* strides, const cuuint32_t* box, CUtensorMapSwizzle sw) {
    const cuuint32_t es[5] = {1, 1, 1, 1, 1};
    fn(m, CU_TENSOR_MAP_DATA_TYPE_BFLOAT16, rank, (void*)base, dims, strides, box, es, CU_TENSOR_MAP_INTERLEAVE_NONE, sw,
       CU_TENSOR_MAP_L2_PROMOTION_NONE, CU_TENSOR_MAP_FLOAT_OOB_FILL_NONE);
}

}

extern "C" void kernel_launch(void* const* d_in, const int* in_sizes, int n_in, void* d_out, int out_size) {
    (void)in_sizes; (void)n_in; (void)out_size;
    static EncodeFn fn = nullptr;
    static void* scratch = nullptr;
    if (!fn) {
        void* ptr = nullptr; cudaDriverEntryPointQueryResult qr;
        cudaGetDriverEntryPoint("cuTensorMapEncodeTiled", &ptr, cudaEnableDefault, &qr);
        fn = (EncodeFn)ptr;
        cudaGetSymbolAddress(&scratch, g_scratch);
        cudaFuncSetAttribute(fused_kernel, cudaFuncAttributeMaxDynamicSharedMemorySize, SMEM_BYTES);
    }
    typedef const __nv_bfloat16* bp;
    Params p;
    p.u = (bp)d_in[0]; p.Are = (bp)d_in[1]; p.Aim = (bp)d_in[2]; p.Bre = (bp)d_in[3]; p.Bim = (bp)d_in[4]; p.Cre = (bp)d_in[5]; p.Cim = (bp)d_in[6];
    p.logdt = (bp)d_in[7]; p.Dskip = (bp)d_in[8]; p.wr = (bp)d_in[10]; p.gatew = (bp)d_in[14];
    p.out = (__nv_bfloat16*)d_out; p.s = (Scratch*)scratch; p.zero = 0;
    Maps maps;
    {
        const cuuint64_t dims[4] = {DM, 4, 16, 32}, strides[3] = {16 * DM * 2, DM * 2, 64 * DM * 2};
        const cuuint32_t box[4] = {16, 4, 16, 2};
        make_map(fn, &maps.m[0], d_in[0], 4, dims, strides, box, CU_TENSOR_MAP_SWIZZLE_32B);
        const cuuint32_t box2[4] = {16, 4, 16, 8};
        make_map(fn, &maps.m[5], d_in[0], 4, dims, strides, box2, CU_TENSOR_MAP_SWIZZLE_32B);
    }
    for (int i = 0; i < 2; i++) {
        const cuuint64_t dims[3] = {32, DM, FF / 32}, strides[2] = {FF * 2, 64};
        const cuuint32_t box[3] = {32, 64, 3};
        make_map(fn, &maps.m[1 + i], d_in[11 + i], 3, dims, strides, box, CU_TENSOR_MAP_SWIZZLE_64B);
    }
    {
        const cuuint64_t dims[2] = {DM, FF}, strides[1] = {DM * 2};
        const cuuint32_t box[2] = {32, 192};
        make_map(fn, &maps.m[3], d_in[13], 2, dims, strides, box, CU_TENSOR_MAP_SWIZZLE_64B);
    }
    {
        const cuuint64_t dims[5] = {DM, 2, 4, 4, L_SEQ}, strides[4] = {16 * DM * 2, 64 * DM * 2, 4 * DM * 2, DM * 2};
        const cuuint32_t box[5] = {16, 2, 4, 4, 1};
        make_map(fn, &maps.m[4], d_out, 5, dims, strides, box, CU_TENSOR_MAP_SWIZZLE_NONE);
    }
    {
        const cuuint64_t dims[5] = {DM, 4, 4, 2, L_SEQ}, strides[4] = {8 * DM * 2, 64 * DM * 2, 4 * DM * 2, DM * 2};
        const cuuint32_t box[5] = {16, 4, 4, 2, 1};
        make_map(fn, &maps.m[6], d_out, 5, dims, strides, box, CU_TENSOR_MAP_SWIZZLE_NONE);
    }
    fused_kernel<<<NCTA, NTHR, SMEM_BYTES>>>(p, maps);
}
```

```cpp
#include <cuda_runtime.h>
#include <cuda_bf16.h>
#include <cuda_fp16.h>
#include <cuda.h>
#include <stdint.h>

#define RESUME 300
#define MDELAY 2000
#define KPOLL 650
#define DPA 7
#define DPB 9
#define RDELAY 900
#define WDELAY 1700
#define WGAP 290
#define NPRE 8
#define DGAP 290
namespace {

constexpr int DM = 576, NST = 128, FF = 4608, L_SEQ = 2048;
constexpr int NCONV = 72, NX = 36, NW = 48, NCTA = 132, NTHR = 512;

struct __align__(128) Scratch {
    unsigned epoch[NCTA * 16];
    uint4 keys[16 * 128];
    uint32_t sel[18 * 64];
    uint16_t gate[L_SEQ];
    uint2 h[2 * 288 * 32];
    uint4 kp[DM * 96];
};
__device__ Scratch g_scratch;
#define TFLUSH()
#define TSTAMP(i)
#define TW 12

struct Params {
    const __nv_bfloat16 *Are, *Aim, *Bre, *Bim, *Cre, *Cim, *logdt, *Dskip, *u, *wr, *gatew;
    __nv_bfloat16* out;
    Scratch* s;
    uint32_t zero;
};

__device__ __forceinline__ void give_up() { asm volatile("trap; exit;"); __builtin_unreachable(); }
__device__ __forceinline__ void converged() { __syncwarp(); asm volatile("{ .reg .b32 t; mov.b32 t, 0; movmatrix.sync.aligned.m8n8.trans.b16 t, t; }" ::: "memory"); }
__device__ __forceinline__ bool elect() { uint32_t r; asm volatile("{ .reg .pred p; elect.sync _|p, 0xffffffff; selp.u32 %0, 1, 0, p; }" : "=r"(r)); return r; }
__device__ __forceinline__ uint32_t smem_u32(const void* p) { return (uint32_t)__cvta_generic_to_shared(p); }
__device__ __forceinline__ uint32_t pack_bf16(float lo, float hi) { uint32_t r; asm("cvt.rn.bf16x2.f32 %0, %1, %2;" : "=r"(r) : "f"(hi), "f"(lo)); return r; }
__device__ __forceinline__ uint32_t pack_f16(float lo, float hi) { uint32_t r; asm("cvt.rn.f16x2.f32 %0, %1, %2;" : "=r"(r) : "f"(hi), "f"(lo)); return r; }
__device__ __forceinline__ float bf_lo(uint32_t w) { return __uint_as_float(w << 16); }
__device__ __forceinline__ float bf_hi(uint32_t w) { return __uint_as_float(w & 0xffff0000u); }
__device__ __forceinline__ float rbf(float x) { return bf_lo(pack_bf16(x, 0.f)); }
__device__ __forceinline__ uint32_t badd2(uint32_t a, uint32_t b) { uint32_t r; asm("add.rn.bf16x2 %0, %1, %2;" : "=r"(r) : "r"(a), "r"(b)); return r; }
__device__ __forceinline__ uint32_t bsub2(uint32_t a, uint32_t b) { uint32_t r; asm("sub.rn.bf16x2 %0, %1, %2;" : "=r"(r) : "r"(a), "r"(b)); return r; }
__device__ __forceinline__ uint32_t gmix(uint32_t ng, float ny0, float ny1, uint32_t u) {
    uint32_t r; asm("{ .reg .b32 t; fma.rn.bf16x2 t, %1, %3, %3; fma.rn.bf16x2 %0, %1, %2, t; }" : "=r"(r) : "r"(ng), "r"(pack_bf16(ny0, ny1)), "r"(u)); return r;
}
__device__ __forceinline__ void mma_bf(float (&c)[4], uint32_t a0, uint32_t a1, uint32_t a2, uint32_t a3, uint32_t b0, uint32_t b1) {
    asm("mma.sync.aligned.m16n8k16.row.col.f32.bf16.bf16.f32 {%0,%1,%2,%3}, {%4,%5,%6,%7}, {%8,%9}, {%0,%1,%2,%3};"
        : "+f"(c[0]), "+f"(c[1]), "+f"(c[2]), "+f"(c[3]) : "r"(a0), "r"(a1), "r"(a2), "r"(a3), "r"(b0), "r"(b1));
}
__device__ __forceinline__ void mma_bf8(float (&c)[4], uint32_t a0, uint32_t a1, uint32_t b0) {
    asm("mma.sync.aligned.m16n8k8.row.col.f32.bf16.bf16.f32 {%0,%1,%2,%3}, {%4,%5}, {%6}, {%0,%1,%2,%3};"
        : "+f"(c[0]), "+f"(c[1]), "+f"(c[2]), "+f"(c[3]) : "r"(a0), "r"(a1), "r"(b0));
}
__device__ __forceinline__ void mma_h(float (&c)[4], uint32_t a0, uint32_t a1, uint32_t a2, uint32_t a3, uint32_t b0, uint32_t b1) {
    asm("mma.sync.aligned.m16n8k16.row.col.f32.f16.f16.f32 {%0,%1,%2,%3}, {%4,%5,%6,%7}, {%8,%9}, {%0,%1,%2,%3};"
        : "+f"(c[0]), "+f"(c[1]), "+f"(c[2]), "+f"(c[3]) : "r"(a0), "r"(a1), "r"(a2), "r"(a3), "r"(b0), "r"(b1));
}
__device__ __forceinline__ uint32_t fresh(uint32_t a) { asm volatile("" : "+r"(a) :: "memory"); return a; }
__device__ __forceinline__ uint32_t lds32(uint32_t a) { uint32_t v; asm("ld.shared.u32 %0, [%1];" : "=r"(v) : "r"(a)); return v; }
__device__ __forceinline__ uint2 lds64(uint32_t a) { uint2 v; asm("ld.shared.v2.u32 {%0,%1}, [%2];" : "=r"(v.x), "=r"(v.y) : "r"(a)); return v; }
__device__ __forceinline__ uint4 lds128(uint32_t a) { uint4 v; asm("ld.shared.v4.u32 {%0,%1,%2,%3}, [%4];" : "=r"(v.x), "=r"(v.y), "=r"(v.z), "=r"(v.w) : "r"(a)); return v; }
__device__ __forceinline__ void ldsm4(uint32_t (&r)[4], uint32_t a) {
    asm("ldmatrix.sync.aligned.m8n8.x4.shared.b16 {%0,%1,%2,%3}, [%4];" : "=r"(r[0]), "=r"(r[1]), "=r"(r[2]), "=r"(r[3]) : "r"(a));
}
__device__ __forceinline__ void ldsm4t(uint32_t (&r)[4], uint32_t a) {
    asm("ldmatrix.sync.aligned.m8n8.x4.trans.shared.b16 {%0,%1,%2,%3}, [%4];" : "=r"(r[0]), "=r"(r[1]), "=r"(r[2]), "=r"(r[3]) : "r"(a));
}
__device__ __forceinline__ void sts16(uint32_t a, uint32_t v) { asm volatile("st.shared.u16 [%0], %1;" :: "r"(a), "h"((unsigned short)v) : "memory"); }
__device__ __forceinline__ void sts32(uint32_t a, uint32_t v) { asm volatile("st.shared.u32 [%0], %1;" :: "r"(a), "r"(v) : "memory"); }
__device__ __forceinline__ void sts64(uint32_t a, uint32_t x, uint32_t y) { asm volatile("st.shared.v2.u32 [%0], {%1,%2};" :: "r"(a), "r"(x), "r"(y) : "memory"); }
__device__ __forceinline__ void sts128(uint32_t a, uint32_t x, uint32_t y, uint32_t z, uint32_t w) {
    asm volatile("st.shared.v4.u32 [%0], {%1,%2,%3,%4};" :: "r"(a), "r"(x), "r"(y), "r"(z), "r"(w) : "memory");
}
__device__ __forceinline__ void st_async128(uint32_t a, uint32_t x, uint32_t y, uint32_t z, uint32_t w, uint32_t bar) {
    asm volatile("st.async.weak.shared::cluster.mbarrier::complete_tx::bytes.v4.b32 [%0], {%1,%2,%3,%4}, [%5];" :: "r"(a), "r"(x), "r"(y), "r"(z), "r"(w), "r"(bar) : "memory");
}
__device__ __forceinline__ void mbar_init(uint32_t b, uint32_t cnt) { asm volatile("mbarrier.init.shared::cta.b64 [%0], %1;" :: "r"(b), "r"(cnt) : "memory"); }
__device__ __forceinline__ void mbar_fence() { asm volatile("fence.mbarrier_init.release.cluster;" ::: "memory"); }
__device__ __forceinline__ void mbar_expect(uint32_t b, uint32_t bytes) { asm volatile("mbarrier.arrive.expect_tx.shared::cta.b64 _, [%0], %1;" :: "r"(b), "r"(bytes) : "memory"); }
__device__ __forceinline__ void mbar_arrive(uint32_t b) { asm volatile("mbarrier.arrive.shared::cta.b64 _, [%0];" :: "r"(b) : "memory"); }
__device__ __forceinline__ void mbar_wait(uint32_t b, uint32_t parity = 0) {
    asm volatile("{ .reg .pred p; .reg .u32 n; mov.u32 n, 0;\n"
                 "LW: mbarrier.try_wait.parity.shared::cta.b64 p, [%0], %1; @p bra LD; add.u32 n, n, 1; setp.lt.u32 p, n, 65536; @p bra LW; trap;\n"
                 "LD: }" :: "r"(b), "r"(parity) : "memory");
}
__device__ __forceinline__ void mbar_wait_cluster(uint32_t b) {
    asm volatile("{ .reg .pred p; .reg .u32 n; mov.u32 n, 0;\n"
                 "LW: mbarrier.try_wait.parity.acquire.cluster.shared::cta.b64 p, [%0], 0; @p bra LD; add.u32 n, n, 1; setp.lt.u32 p, n, 65536; @p bra LW; trap;\n"
                 "LD: }" :: "r"(b) : "memory");
}
__device__ __forceinline__ void tma2d(uint32_t dst, const CUtensorMap* m, int c0, int c1, uint32_t bar) {
    asm volatile("cp.async.bulk.tensor.2d.shared::cluster.global.mbarrier::complete_tx::bytes [%0], [%1, {%3, %4}], [%2];"
                 :: "r"(dst), "l"(m), "r"(bar), "r"(c0), "r"(c1) : "memory");
}
__device__ __forceinline__ void tma3d(uint32_t dst, const CUtensorMap* m, int c0, int c1, int c2, uint32_t bar) {
    asm volatile("cp.async.bulk.tensor.3d.shared::cluster.global.mbarrier::complete_tx::bytes [%0], [%1, {%3, %4, %5}], [%2];"
                 :: "r"(dst), "l"(m), "r"(bar), "r"(c0), "r"(c1), "r"(c2) : "memory");
}
__device__ __forceinline__ void tma4d(uint32_t dst, const CUtensorMap* m, int c0, int c1, int c2, int c3, uint32_t bar) {
    asm volatile("cp.async.bulk.tensor.4d.shared::cluster.global.mbarrier::complete_tx::bytes [%0], [%1, {%3, %4, %5, %6}], [%2];"
                 :: "r"(dst), "l"(m), "r"(bar), "r"(c0), "r"(c1), "r"(c2), "r"(c3) : "memory");
}
__device__ __forceinline__ void bulk_g2s(uint32_t dst, const void* src, uint32_t bytes, uint32_t bar) {
    asm volatile("cp.async.bulk.shared::cluster.global.mbarrier::complete_tx::bytes [%0], [%1], %2, [%3];"
                 :: "r"(dst), "l"(src), "r"(bytes), "r"(bar) : "memory");
}
__device__ __forceinline__ uint32_t mapa(uint32_t a, uint32_t rank) { uint32_t r; asm("mapa.shared::cluster.u32 %0, %1, %2;" : "=r"(r) : "r"(a), "r"(rank)); return r; }
__device__ __forceinline__ void prefetch_map(const CUtensorMap* m) { asm volatile("prefetch.tensormap [%0];" :: "l"(m) : "memory"); }
__device__ __forceinline__ void bar_sync(int id, int n) { asm volatile("bar.sync %0, %1;" :: "r"(id), "r"(n) : "memory"); }
__device__ __forceinline__ void bar_arrive(int id, int n) { asm volatile("bar.arrive %0, %1;" :: "r"(id), "r"(n) : "memory"); }
__device__ __forceinline__ uint32_t ldg16_if(bool c, const void* p) { uint32_t v; asm volatile("{ .reg .pred p; setp.ne.u32 p, %2, 0; @p ld.global.nc.u16 %0, [%1]; }" : "=r"(v) : "l"(p), "r"((uint32_t)c)); return v; }
__device__ __forceinline__ uint32_t ldg32_if(bool c, const void* p) { uint32_t v; asm volatile("{ .reg .pred p; setp.ne.u32 p, %2, 0; @p ld.global.nc.u32 %0, [%1]; }" : "=r"(v) : "l"(p), "r"((uint32_t)c)); return v; }
__device__ __forceinline__ uint32_t ld_rlx32(const void* p) { uint32_t v; asm volatile("ld.relaxed.gpu.global.u32 %0, [%1];" : "=r"(v) : "l"(p) : "memory"); return v; }
__device__ __forceinline__ uint4 ld_rlx128(const void* p) {
    uint4 v; asm volatile("ld.relaxed.gpu.global.v4.u32 {%0,%1,%2,%3}, [%4];" : "=r"(v.x), "=r"(v.y), "=r"(v.z), "=r"(v.w) : "l"(p) : "memory"); return v;
}
__device__ __forceinline__ void st_rlx32(void* p, uint32_t v) { asm volatile("st.relaxed.gpu.global.u32 [%0], %1;" :: "l"(p), "r"(v) : "memory"); }
__device__ __forceinline__ void stg128(void* p, uint32_t x, uint32_t y, uint32_t z, uint32_t w) {
    asm volatile("st.global.v4.u32 [%0], {%1,%2,%3,%4};" :: "l"(p), "r"(x), "r"(y), "r"(z), "r"(w) : "memory");
}
__device__ __forceinline__ void next_epoch(const Params& p, unsigned e) { if ((threadIdx.x & 31) == 0) p.s->epoch[blockIdx.x * 16 + (threadIdx.x >> 5)] = e + 1; }
__device__ __forceinline__ void sts128z_if(bool c, uint32_t a) { asm volatile("{ .reg .pred p; setp.ne.u32 p, %1, 0; @p st.shared.v4.u32 [%0], {%2,%2,%2,%2}; }" :: "r"(a), "r"((uint32_t)c), "r"(0) : "memory"); }
__device__ __forceinline__ void stg128z_if(bool c, void* a) { asm volatile("{ .reg .pred p; setp.ne.u32 p, %1, 0; @p st.global.v4.u32 [%0], {%2,%2,%2,%2}; }" :: "l"(a), "r"((uint32_t)c), "r"(0) : "memory"); }
__device__ __forceinline__ unsigned clock32() { unsigned c; asm volatile("mov.u32 %0, %clock;" : "=r"(c) :: "memory"); return c; }
__device__ __forceinline__ void until(unsigned t0, int c) { while ((int)(clock32() - t0) < c) { } }
__device__ __forceinline__ float sigmoidf_(float x) { return __fdividef(1.0f, 1.0f + __expf(-x)); }
__device__ __forceinline__ uint32_t key_tag(unsigned epoch) { return ((epoch & 15u) | 16u) << 11; }
__device__ __forceinline__ int key_row(uint32_t key) { return 2047 - (int)(key & 2047u); }
__device__ __forceinline__ uint32_t wait_sel(const Params& p, int s32, int r8, uint32_t tag, uint32_t k = 0) {
#pragma unroll 1
    for (int it = 0; !__all_sync(0xffffffffu, (k & 0xf800u) == tag); it++) {
        k = ld_rlx32(&p.s->sel[s32 * 64 + r8]);
        if (it > (1 << 20)) give_up();
    }
    return k;
}

struct cplx { float re, im; };
__device__ __forceinline__ cplx csq(cplx a) { cplx r; r.re = a.re * a.re - a.im * a.im; r.im = (a.re * a.im) * 2.f; return r; }
__device__ __forceinline__ cplx cexpk(float ar, float ai, float k) {
    float mag, s, c;
    asm("ex2.approx.ftz.f32 %0, %1;" : "=f"(mag) : "f"(ar * (k * 1.4426950408889634f)));
    const float r = ai * k;
    asm("sin.approx.ftz.f32 %0, %1;" : "=f"(s) : "f"(r));
    asm("cos.approx.ftz.f32 %0, %1;" : "=f"(c) : "f"(r));
    cplx o; o.re = mag * c; o.im = mag * s; return o;
}
struct h2c { uint32_t re, im; };
__device__ __forceinline__ h2c cmul_cd(h2c v, __half2 c, __half2 d) {
    const __half2 r = *(const __half2*)&v.re, i = *(const __half2*)&v.im;
    const __half2 x = __hfma2(__hneg2(i), d, __hmul2(r, c)), y = __hfma2(i, c, __hmul2(r, d));
    h2c o; o.re = *(const uint32_t*)&x; o.im = *(const uint32_t*)&y; return o;
}
__device__ __forceinline__ h2c cmul_s(h2c v, uint32_t s) { const __half2 h = *(const __half2*)&s; return cmul_cd(v, __low2half2(h), __high2half2(h)); }
__device__ __forceinline__ h2c cmul_sc(h2c v, uint32_t s) {
    const __half2 h = *(const __half2*)&s, c = __low2half2(h), d = __high2half2(h), r = *(const __half2*)&v.re, i = *(const __half2*)&v.im;
    const __half2 x = __hfma2(i, d, __hmul2(r, c)), y = __hfma2(__hneg2(r), d, __hmul2(i, c));
    h2c o; o.re = *(const uint32_t*)&x; o.im = *(const uint32_t*)&y; return o;
}
__device__ __forceinline__ h2c cmul_vc(h2c v, uint32_t s) {
    const __half2 h = *(const __half2*)&s, c = __low2half2(h), d = __high2half2(h), r = *(const __half2*)&v.re, i = *(const __half2*)&v.im;
    const __half2 x = __hfma2(i, d, __hmul2(r, c)), y = __hfma2(__hneg2(i), c, __hmul2(r, d));
    h2c o; o.re = *(const uint32_t*)&x; o.im = *(const uint32_t*)&y; return o;
}

constexpr int UT_HALF = 2560, UT_STRIDE = 4736, GT_HALF = 2240;
__device__ __forceinline__ uint32_t swz(uint32_t x, int c) { return x ^ (((x >> 2) & 64) ^ (64 * (c & 1) + 8 * (c & 6))); }
__device__ __forceinline__ int col(int n) { return (n >> 1) + 4 * (n & 1); }
constexpr int KT_T = 542, KT_C = 552, KT_D = 645, KT_BYTES = 720 * 4;
constexpr int VC_OFF = 80, VE_BASE = 1616;
constexpr int V_STRIDE = (1616 + 1024) * 4 + 80;
constexpr int KG_STAGE = 5248;
constexpr int Y_CS = 2080, Y_RS = 8 * Y_CS + 64;

constexpr int SC_RT = 0;
constexpr int SC_UT = 33408;
constexpr int SC_KG = SC_UT + 8 * UT_STRIDE;
constexpr int SC_KT = SC_KG + 8 * KG_STAGE;
constexpr int SC_GT = SC_KT + 8 * KT_BYTES;
constexpr int SC_V = SC_GT + 4448;
constexpr int SC_MISC = SC_V + 8 * V_STRIDE;
static_assert(V_STRIDE % 128 == 16 && 2 * Y_RS <= SC_UT && SC_UT % 128 == 0 && SC_KG % 128 == 0, "layout");
static_assert(SC_MISC % 16 == 0 && SC_MISC + 512 <= 232192, "layout");

__device__ __forceinline__ void window_task(uint32_t s0, uint32_t s1, uint32_t d0, uint32_t d1, int k) {
    float S[51], s = 0.f;
    uint32_t w[28];
#pragma unroll
    for (int i = 0; i < 7; i++) {
        const uint4 v = lds128(((i < 3 ? s0 : s1) ^ 8 * ((i + 1) & 2)) + ((i & 1) ? 0 : UT_HALF));
        w[4 * i] = v.x; w[4 * i + 1] = v.y; w[4 * i + 2] = v.z; w[4 * i + 3] = v.w;
    }
    auto sums = [&](int lo, int hi) {
#pragma unroll
        for (int i = lo; i < hi; i++) { const float x = (i & 1) ? bf_hi(w[i >> 1]) : bf_lo(w[i >> 1]); s = i > 3 ? s + x : x; S[i] = s; }
    };
    auto put = [&](int off, int b, int o0, int o1, int o2) {
        auto v = [&](int i) { i += 16 * b; return pack_bf16(S[o0 + i] - S[o1 + i], S[o1 + i] - S[o2 + i]); };
#pragma unroll
        for (int i = 0; i < 8; i += 2) sts128((i & 4 ? d1 : d0) + 4 * off + 64 * b + 8 * (i & 2), v(i), v(i + 8), v(i + 1), v(i + 9));
    };
    S[2] = 0.f;
    sums(3, 26); put(VC_OFF - 16, 0, 10, 5, 2);
    if (k == 12) return;
    sums(26, 42); put(VC_OFF - 16, 1, 10, 5, 2);
    if (k < 8) { put(VE_BASE, 0, 19, 12, 3); sums(42, 51); put(VE_BASE, 1, 19, 12, 3); }
}

template <class F, class G>
__device__ __forceinline__ void kgen(const uint32_t (&q)[8], uint32_t sb, int half, uint32_t stage, uint32_t pstage, int barid, int lane, uint32_t (&w)[12], F shadow, G clear) {
    const int t = lane & 3, mi = lane >> 3, r8 = lane & 7;
    {
        const uint32_t pAr = q[0], pAi = q[1], pBr = q[2], pBi = q[3], pCr = q[4], pCi = q[5], pDt = q[6], pD = q[7];
        const uint32_t wb = fresh(stage + lane * 16), za = fresh(stage + 5120 + ((lane >> 1) & 3) * 16 + mi * 4 + (lane & 1) * 2), zr = fresh(stage + 5120 + t * 16);
        const uint32_t oB = fresh(stage + 2048 + mi * 512 + r8 * 16), oC = fresh(stage + 4096 + (mi & 1) * 512 + (mi >> 1) * 128 + r8 * 16);
        float acc[6][4];
#pragma unroll
        for (int a = 0; a < 6; a++) { acc[a][0] = acc[a][1] = acc[a][2] = acc[a][3] = 0.f; asm volatile("" : "+f"(acc[a][0]), "+f"(acc[a][1]), "+f"(acc[a][2]), "+f"(acc[a][3])); }
        shadow();
        sts32(zr, clock32());
        const float dt = rbf(__expf(bf_lo(pDt)));
        float ar = dt * bf_lo(pAr), ai = dt * bf_lo(pAi), ar1 = dt * bf_hi(pAr), ai1 = dt * bf_hi(pAi);
        float wr, wi, wr1, wi1;
        { const float br = dt * bf_lo(pBr), bi = dt * bf_lo(pBi), cr = bf_lo(pCr), ci = bf_lo(pCi); wr = cr * br - ci * bi; wi = cr * bi + ci * br; }
        { const float br = dt * bf_hi(pBr), bi = dt * bf_hi(pBi), cr = bf_hi(pCr), ci = bf_hi(pCi); wr1 = cr * br - ci * bi; wi1 = cr * bi + ci * br; }
        const uint32_t ex = max(__reduce_max_sync(0xffffffffu, __float_as_uint(fmaxf(fmaxf(fabsf(wr), fabsf(wi)), fmaxf(fabsf(wr1), fabsf(wi1))))) >> 23, 14u);
        const float scl = __uint_as_float((267u - ex) << 23);
        uint32_t W = pack_f16(wr * scl, wi * -scl);
        const uint32_t W1 = pack_f16(wr1 * scl, wi1 * -scl);
        if (threadIdx.x < 32) TSTAMP(20);
        clear();

#pragma unroll 1
        for (int r = 0; r < 2; r++) {
            const cplx z1 = cexpk(ar, ai, 1.f), z64 = cexpk(ar, ai, 64.f);
            const cplx z2 = csq(z1), z4 = csq(z2), z8 = csq(z4), z16 = csq(z8), z32 = csq(z16);
            const cplx z128 = csq(z64), z256 = csq(z128), z512 = csq(z256);
            auto put = [&](int grp, h2c a, h2c b, h2c c, h2c d) { sts128(wb + grp * 1024, a.re, b.re, c.re, d.re); sts128(wb + grp * 1024 + 512, a.im, b.im, c.im, d.im); };
            {
                const uint32_t s4 = pack_f16(z4.re, z4.im), s256 = pack_f16(z256.re, z256.im), s512 = pack_f16(z512.re, z512.im);
                auto mix = [](h2c a, h2c b, uint32_t sel) { return h2c{__byte_perm(a.re, b.re, sel), __byte_perm(a.im, b.im, sel)}; };
                const h2c c10 = cmul_vc(h2c{pack_f16(z1.re, 1.f), pack_f16(z1.im, 0.f)}, W), c32 = cmul_sc(c10, pack_f16(z2.re, z2.im)), c54 = cmul_sc(c10, s4);
                put(2, c10, c32, c54, cmul_sc(c32, s4));
                const h2c d20 = cmul_sc(mix(c32, c10, 0x7632), s256), e04 = cmul_sc(mix(c10, c54, 0x7632), s512), f04 = cmul_sc(e04, s256);
                put(3, d20, cmul_sc(d20, s4), e04, f04);
                const h2c ef = mix(e04, f04, 0x5410), gh = cmul_sc(ef, s512), g8 = cmul_sc(gh, pack_f16(z8.re, z8.im));
                put(4, g8, cmul_sc(g8, s512), gh, ef);
            }
            {
                const uint32_t s32 = pack_f16(z32.re, z32.im), s64 = pack_f16(z64.re, z64.im), s128 = pack_f16(z128.re, z128.im);
                const h2c p0 = {pack_f16(1.f, z8.re), pack_f16(0.f, z8.im)}, p1 = cmul_s(p0, pack_f16(z16.re, z16.im)), p2 = cmul_s(p0, s32), p3 = cmul_s(p1, s32);
                put(0, p0, p1, p2, p3);
                sts16(za - 4096, s64); sts16(za - 4032, s64 >> 16);
                sts16(za, s128); sts16(za + 64, s128 >> 16);
            }
            __syncwarp();
            {
                const uint32_t aB = fresh(oB), aC = fresh(oC), aZ = fresh(zr);
                const uint4 zc = lds128(aZ), zd = lds128(aZ + 64);
                const uint32_t zcs[4] = {zc.x, zc.y, zc.z, zc.w}, zds[4] = {zd.x, zd.y, zd.z, zd.w};
                const uint4 yc = lds128(aZ - 4096), yd = lds128(aZ - 4032);
                const uint32_t ycs[4] = {yc.x, yc.y, yc.z, yc.w}, yds[4] = {yd.x, yd.y, yd.z, yd.w};
                uint32_t c[4];
#pragma unroll
                for (int k = 0; k < 4; k++) {
                    uint32_t a[4], b[4];
                    for (int e = 0; e < 2; e++) asm("ldmatrix.sync.aligned.m8n8.x1.trans.shared.b16 {%0}, [%1];" : "=r"(a[2 * e]) : "r"(aB - 2048 + 128 * k + 512 * e));
                    const h2c a1 = cmul_cd(h2c{a[0], a[2]}, *(const __half2*)&ycs[k], *(const __half2*)&yds[k]);
                    a[1] = a1.re; a[3] = a1.im;
                    ldsm4t(b, aB + 128 * k);
                    if (!(k & 1)) ldsm4t(c, aC + 128 * k);
                    const h2c x = cmul_cd(h2c{a[0], a[2]}, *(const __half2*)&zcs[k], *(const __half2*)&zds[k]), y = cmul_cd(h2c{a[1], a[3]}, *(const __half2*)&zcs[k], *(const __half2*)&zds[k]);
                    mma_h(acc[0], a[0], a[1], a[2], a[3], b[0], b[1]);
                    mma_h(acc[1], a[0], a[1], a[2], a[3], b[2], b[3]);
                    mma_h(acc[2], a[0], a[1], a[2], a[3], c[2 * (k & 1)], c[2 * (k & 1) + 1]);
                    mma_h(acc[3], x.re, y.re, x.im, y.im, b[0], b[1]);
                    mma_h(acc[4], x.re, y.re, x.im, y.im, b[2], b[3]);
                    mma_h(acc[5], x.re, y.re, x.im, y.im, c[2 * (k & 1)], c[2 * (k & 1) + 1]);
                }
                asm volatile("" :: "f"(acc[0][0]), "f"(acc[1][0]), "f"(acc[2][0]), "f"(acc[3][0]), "f"(acc[4][0]), "f"(acc[5][0]) : "memory");
            }
            __syncwarp();
            ar = ar1; ai = ai1; W = W1;
        }
        if (threadIdx.x < 32) TSTAMP(21);
        const float i0 = __uint_as_float((ex + 243u) << 23);
        if (half) {
#pragma unroll
            for (int a = 0; a < 6; a++) { acc[a][0] *= i0; acc[a][1] *= i0; acc[a][2] *= i0; acc[a][3] *= i0; }
            if (lane == 0) acc[0][1] -= bf_lo(pD);
#pragma unroll
            for (int a = 0; a < 6; a++) sts128(wb + a * 512, __float_as_uint(acc[a][0]), __float_as_uint(acc[a][1]), __float_as_uint(acc[a][2]), __float_as_uint(acc[a][3]));
            bar_arrive(barid, 64);
        } else {
            bar_sync(barid, 64);
            const uint32_t src = fresh(pstage);
#pragma unroll
            for (int a = 0; a < 6; a++) {
                const uint4 y = lds128(src + lane * 16 + a * 512);
                auto sum = [&](uint32_t x, float c) { return fmaf(c, i0, __uint_as_float(x)); };
                w[4 * (a % 3) + 2 * (a / 3)] = pack_bf16(sum(y.x, acc[a][0]), sum(y.y, acc[a][1]));
                w[4 * (a % 3) + 2 * (a / 3) + 1] = pack_bf16(sum(y.z, acc[a][2]), sum(y.w, acc[a][3]));
            }
            const uint32_t x0 = __shfl_up_sync(0xffffffffu, w[10], 2), x1 = __shfl_up_sync(0xffffffffu, w[11], 2);
            w[10] = w[8];
            if (t >= 2) { w[8] = x0; w[9] = x1; }
        }
    }
}

enum { BC_AUX = 0, BC_U = 5  , BC_Y = 13   };

__device__ __forceinline__ void fetch_gates(const Params& p, int i, int lane, unsigned epoch, uint32_t dst) {
    const uint32_t par = (epoch & 1) ? 0x80008000u : 0u;
    uint4 v;
#pragma unroll 1
    for (int it = 0;; it++) {
        v = ld_rlx128(p.s->gate + 256 * i + 8 * lane);
        v.x ^= par; v.y ^= par; v.z ^= par; v.w ^= par;
        if (__all_sync(0xffffffffu, (v.x & v.y & v.z & v.w & 0x80008000u) == 0x80008000u)) break;
        if (it > (1 << 20)) give_up();
    }
    sts128(dst, v.x, v.y, v.z, v.w);
}
__device__ __forceinline__ void store_rows(const CUtensorMap* m, uint32_t src, int col, int row) {
    asm volatile("cp.async.bulk.tensor.5d.global.shared::cta.bulk_group [%0, {%2, %3, %3, %3, %4}], [%1];" :: "l"(m), "r"(src), "r"(col), "r"(0), "r"(row) : "memory");
}

__device__ __forceinline__ void store_or_add(void* o, const uint32_t (&y)[4], uint32_t add) {
    asm volatile("{ .reg .pred p; setp.ne.u32 p, %5, 0; @!p st.global.v4.u32 [%0], {%1,%2,%3,%4}; @p red.relaxed.gpu.global.add.noftz.v4.bf16x2 [%0], {%1,%2,%3,%4}; }"
                 :: "l"(o), "r"(y[0]), "r"(y[1]), "r"(y[2]), "r"(y[3]), "r"(add) : "memory");
}

__device__ __forceinline__ void conv_aux(const Params& p, const CUtensorMap* mU, uint32_t sb, int aw, int lane, int bid, unsigned epoch) {
    const int g = lane >> 2, t = lane & 3, mi = lane >> 3, r8 = lane & 7;
    const int rank = bid & 1, slab = bid >> 1;
    const uint32_t bar_y = sb + SC_MISC, bar_u = bar_y  , bar_v = bar_y + 8, bar_box = bar_y + 64 + 8 * aw, s_bm = bar_y + 128;
    if (elect()) {
        mbar_init(bar_box, 1); mbar_fence();
        mbar_expect(bar_box, 4096);
        tma4d(sb + SC_RT + 4096 * aw, mU, 16 * slab, 0, 0, 16 * rank + 2 * aw, bar_box);
        mbar_init(bar_y + 8 * aw, aw == 1 ? 8 : 1);
        if (aw == 1) mbar_init(bar_y + 384, 1);
        mbar_fence();
        if (aw != 1) mbar_expect(bar_y + 8 * aw, aw ? 4096 : 16384);
    }
    __syncwarp();
    asm volatile("barrier.cluster.arrive.relaxed.aligned;" ::: "memory");
    asm volatile("setmaxnreg.dec.sync.aligned.u32 88;");
    sts128(sb + (lane < 16 ? SC_UT + aw * UT_STRIDE + mi * (UT_HALF - 128) : SC_V - 256 + aw * V_STRIDE) + lane * 16, 0, 0, 0, 0);
    if (lane < 16) sts128(s_bm + lane * 16, 0, 0, 0, 0);
    {
        const uint32_t dst = sb + SC_UT + g * UT_STRIDE + swz((8 + 64 * rank + 8 * aw + t) * 16, g);
        const uint32_t rdst = mapa(dst, rank ^ 1), rbar = mapa(bar_u, rank ^ 1);
        asm volatile("barrier.cluster.wait.acquire.aligned;" ::: "memory");
        mbar_wait(bar_box);
        if (aw == 0) TSTAMP(1);
        const uint32_t src = fresh(sb + SC_RT) + aw * 4096 + (8 * mi + 4 * (r8 & 1) + (r8 >> 1)) * 32 + ((rank ^ (r8 & 1)) << 4);
        uint32_t x[8][4];
#pragma unroll
        for (int i = 0; i < 4; i++) { ldsm4t(x[i], src + 1024 * i); ldsm4t(x[4 + i], (src ^ 16) + 1024 * i); }
        asm volatile("" :: "r"(x[0][0]), "r"(x[1][0]), "r"(x[2][0]), "r"(x[3][0]) : "memory");
#pragma unroll
        for (int i = 0; i < 4; i++) st_async128((rdst ^ 32 * (i & 2)) + (i & 1) * UT_HALF, x[4 + i][0], x[4 + i][1], x[4 + i][2], x[4 + i][3], rbar);
#pragma unroll
        for (int i = 0; i < 4; i++) sts128((dst ^ 32 * (i & 2)) + (i & 1) * UT_HALF, x[i][0], x[i][1], x[i][2], x[i][3]);
    }
    bar_sync(BC_AUX, 256);
    mbar_wait_cluster(bar_u);
    if (aw == 0) TSTAMP(2);
    if (aw == 6 && elect()) mbar_arrive(bar_y + 384);
    if (aw < 4) bar_sync(BC_U + aw, 64);
    if (aw == 0) TSTAMP(3);
    {
        const uint32_t ws = fresh(sb + SC_UT) + r8 * UT_STRIDE, wd = sb + SC_V + r8 * V_STRIDE;
#pragma unroll 1
        for (int k = aw; k < 13; k += 8) {
            const int a = 8 * k + (k < 12 ? g & 6 : 0);
            const uint32_t d = wd + 64 * a, sw = 16 * (a & 2);
            window_task(ws + swz(16 * a + 96, r8), ws + swz(16 * a + 128, r8), d + sw, d + (sw ^ 32), k);
            if ((k & 12) == 4) bar_arrive(BC_U + k - 4, 64);
        }
    }
    if (aw == 0) TSTAMP(9);
    {
        if (aw >= 2) fetch_gates(p, aw, lane, epoch, sb + SC_GT + (lane & 1) * GT_HALF + (8 + 16 * aw + (lane >> 1)) * 16);
        __syncwarp();
        if (elect()) { mbar_arrive(bar_v); prefetch_map(mU + 4); p.s->epoch[fresh(bid) * 16 + aw + 8] = epoch + 1; }
        if (aw == 0) TSTAMP(4);
        if (aw == 7) {
            const int row = key_row(wait_sel(p, slab >> 1, r8, key_tag(epoch)));
            if (lane < 8) asm volatile("red.shared.or.b32 [%0], %1;" :: "r"(s_bm + (row >> 5) * 4), "r"(1u << (row & 31)) : "memory");
            TSTAMP(10);
        }
        bar_sync(BC_AUX, 256);
        const uint32_t src = sb + SC_RT + ((r8 >> 1) & 1) * Y_RS + (2 * mi + (r8 & 1)) * Y_CS + (2 * aw + (r8 >> 2)) * 16;
        const int rb = 64 * (aw & 4) + 32 * (aw & 1) + ((aw >> 1) & 1) + 2 * rank, row0 = rb + 128 * (g >> 2) + 16 * (t >> 1) + 64 * (g & 1) + 8 * ((g >> 1) & 1);
        __nv_bfloat16* outp = p.out + (size_t)row0 * DM + 16 * slab + 8 * (t & 1);
        const uint32_t stg = sb + SC_KG + 4096 * aw, so = (g & 2) * 256 + (g >> 2) * 128 + r8 * 16;
#pragma unroll 1
        for (int s = 1; s < 4; s++) {
            const uint32_t bm = lds32(fresh(s_bm) + (16 * s + (row0 >> 5)) * 4) >> (row0 & 31);
            const bool routed = __any_sync(0xffffffffu, bm & 0x11u);
            if ((aw & 3) == s) mbar_wait_cluster(bar_y + 16 * s + 2 * (aw & 4));
            bar_sync(BC_Y + (aw >> 2), 128);
            const uint32_t sf = fresh(src) + 512 * s;
            uint32_t y[2][4];
            ldsm4t(y[0], sf); ldsm4t(y[1], sf + 256);
            if (routed) {
#pragma unroll
                for (int k = 0; k < 2; k++) store_or_add(outp + (size_t)(512 * s + 4 * k) * DM, y[k], bm & (1u << (4 * k)));
            } else {
                sts128(stg + so + 1024 * s, y[0][0], y[0][1], y[0][2], y[0][3]); sts128(stg + so + 1024 * s + 256, y[1][0], y[1][1], y[1][2], y[1][3]);
                asm volatile("fence.proxy.async.shared::cta;" ::: "memory");
                __syncwarp();
                if (elect()) store_rows(mU + 4, stg + 1024 * s, 16 * slab, 512 * s + rb);
            }
            if (aw == 4) TSTAMP(16 + s);
            if (aw == 0) TSTAMP(16);
        }
        if (elect()) { asm volatile("cp.async.bulk.commit_group;" ::: "memory"); asm volatile("cp.async.bulk.wait_group.read 0;" ::: "memory"); }
        if (aw == 4) TFLUSH();
    }
}

__device__ __forceinline__ uint32_t k_tag(unsigned epoch) { return epoch & 1 ? 0x10000u : 1u; }
__device__ __forceinline__ void publish_k(uint4* kp, int lane, bool all, const uint32_t (&w)[12], unsigned epoch, uint64_t (&v)[4]) {
    auto tag = [&](uint32_t x) { return (x & 0xfffefffeu) | k_tag(epoch); };
#pragma unroll
    for (int i = 0; i < 2; i++) {
        v[2 * i] = w[4 * i] | (uint64_t)w[4 * i + 1] << 32; v[2 * i + 1] = w[4 * i + 2] | (uint64_t)tag(w[4 * i + 3]) << 32;
        asm volatile("st.relaxed.gpu.global.v2.u64 [%0], {%1,%2};" :: "l"(kp + 32 * i), "l"(v[2 * i]), "l"(v[2 * i + 1]));
    }
    asm volatile("{ .reg .pred p, q; setp.ne.u32 p, %6, 0; setp.lt.and.s32 q, %5, 4, p;\n"
                 "@p st.relaxed.gpu.global.v2.u32 [%0 + 1024], {%1,%2}; @q st.relaxed.gpu.global.v2.u32 [%0 + 1280], {%3,%4}; }"
                 :: "l"((uint2*)kp - lane), "r"(w[8]), "r"(tag(w[9])), "r"(w[10]), "r"(k_tag(epoch)), "r"(lane), "r"((uint32_t)all));
}
template <bool FULL>
__device__ __forceinline__ void k_tables(uint32_t kt, int lane, const uint32_t (&w)[12]) {
    const int g = lane >> 2, t = lane & 3, mi = lane >> 3, r8 = lane & 7;
    uint32_t x3 = w[7], re[4], rx[4];
#pragma unroll
    for (int i = 0; i < 4; i++) {
        re[i] = __shfl_sync(0xffffffffu, w[i], lane + 31);
        rx[i] = __shfl_sync(0xffffffffu, w[4 + i], lane + (i == 0 && lane == 29 ? 5 : 1 + 2 * t));
    }
    if (FULL) {
        asm volatile("stmatrix.sync.aligned.m8n8.x2.trans.shared.b16 [%0], {%1,%2};" :: "r"(kt + (KT_D + 7) * 4 + 64 * t + 16 * (mi & 1) + 8 * (r8 & 4)), "r"(w[8]), "r"(w[9]) : "memory");
        if (lane == 2) {
            sts32(kt + (KT_C + 78) * 4, w[10] & 0xffffu);
            sts128(kt + (KT_T + 2) * 4, 0, w[10] & 0xffffu, __byte_perm(w[10], 0, 0x1010), w[10] << 16);
        }
        if (lane == 29) x3 = bsub2(x3, rx[0] & 0xffffu);
    }
#pragma unroll
    for (int i = 0; i < 4; i++) {
        sts64(kt + (16 + 64 * i) * 4 + 8 * lane, __byte_perm(w[i], lane ? re[i] : i ? re[i - 1] : 0, 0x5432), w[i]);
        const uint32_t x = i < 3 ? w[4 + i] : x3, aa = __byte_perm(x, 0, 0x3232);
        if (t < 2) sts128(kt + (272 + 64 * i + 8 * g + 4 * t) * 4, i == 0 && lane == 0 ? __byte_perm(x, re[3], 0x5432) : aa, aa, x,
                          __byte_perm(lane != 29 ? rx[i] : i < 3 ? rx[(i + 1) & 3] : FULL ? 0 : rx[0] << 16, x, 0x5432));
        else if (FULL) sts32(kt + (KT_C - 50 + 8 * i + 32 * t + g) * 4, x);
    }
}

__device__ __forceinline__ void conv_main(const Params& p, uint32_t sb, int warp, int lane0, int bid, unsigned epoch, uint32_t (&w)[12]) {
    asm volatile("setmaxnreg.inc.sync.aligned.u32 168;");
    const int lane = __shfl_sync(0xffffffffu, lane0, lane0);
    const int g = lane >> 2, t = lane & 3, mi = lane >> 3, r8 = lane & 7;
    const int rank = bid & 1;
    const uint32_t bar_y = sb + SC_MISC, bar_v = bar_y + 8;
    next_epoch(p, epoch);
    asm volatile("barrier.cluster.wait.acquire.aligned;" ::: "memory");
    if (warp >= 4) {
        mbar_wait(bar_y + 384);
        if (KPOLL) until(clock32(), KPOLL);
        const uint4* src = p.s->kp + (8 * bid + warp) * 96 + lane0;
#pragma unroll 1
        for (int it = 0;; it++) {
#pragma unroll
            for (int i = 0; i < 2; i++) { const uint4 v = ld_rlx128(src + 32 * i); w[4 * i] = v.x; w[4 * i + 1] = v.y; w[4 * i + 2] = v.z; w[4 * i + 3] = v.w; }
            asm volatile("ld.relaxed.gpu.global.v2.u32 {%0,%1}, [%2 + 1024];" : "=r"(w[8]), "=r"(w[9]) : "l"((const uint2*)src - lane0) : "memory");
            asm volatile("ld.relaxed.gpu.global.v2.u32 {%0,%1}, [%2 + 1296];" : "=r"(w[10]), "=r"(w[11]) : "l"(src - lane0) : "memory");
            const bool ok = __all_sync(0xffffffffu, w[3] & w[7] & w[9] & w[11] & k_tag(epoch));
            if (ok) break;
            if (it > (1 << 20)) give_up();
        }
    }
    if ((warp & 3) == 0) TSTAMP(5 + (warp >> 2));
    k_tables<true>(sb + SC_KT + warp * KT_BYTES, lane0, w);
    mbar_wait(bar_y + 384);
    __syncwarp();
    if ((warp & 3) == 0) TSTAMP(7 + (warp >> 2));
    {
        const uint32_t ut = fresh(sb + SC_UT) + warp * UT_STRIDE, kt = fresh(sb + SC_KT) + warp * KT_BYTES;
        auto dup = [&](uint32_t v) { return v ^ p.zero; };
        auto frag = [&](uint32_t (&a)[4], uint32_t x) { a[0] = lds32(x); a[1] = lds32(x + 32); a[2] = lds32(x - 32); a[3] = dup(a[0]); };
        const uint32_t kb = kt + (16 + g - 2 * t) * 4;
        float acc[16][4];
        {
            float y[12][4], M[6][4];
#pragma unroll
            for (int i = 0; i < 12; i++) { y[i][0] = y[i][1] = y[i][2] = y[i][3] = 0.f; M[i >> 1][0] = M[i >> 1][1] = M[i >> 1][2] = M[i >> 1][3] = 0.f; }
            uint32_t U[10][4], a1[4], ad[4], R = (mi & 1) * UT_HALF + (8 + (r8 >> 1) + 48 * (r8 & 1)) * 16 + 64 * (mi >> 1);
            auto places = [&] { ad[0] = swz(R, warp); ad[1] = swz(R + 128, warp); ad[2] = ad[0] ^ 64; ad[3] = ad[1] ^ 64; };
            auto ldu = [&](int k) { ldsm4(U[k], ut + ad[k & 3] + 256 * (k >> 1)); };
            places();
            frag(a1, kb + 2048);
#pragma unroll
            for (int k = 0; k < 7; k++) ldu(k);
#pragma unroll
            for (int i = 0; i < 12; i++) mma_bf(y[i], a1[0], a1[1], a1[2], a1[3], U[i >> 1][2 * (i & 1)], U[i >> 1][2 * (i & 1) + 1]);
            frag(a1, kb + 1792);
            __syncwarp();
#pragma unroll 1
            for (uint32_t ko = 0; ko != 256;) {
                ko = fresh(ko);
                const uint32_t kp = kb + ko;
                ko += 64;
                uint32_t se[10][2], so[10][2], ue[10][2];
                auto sums = [&](int k) {
#pragma unroll
                    for (int e = 0; e < 2; e++) { ue[k][e] = U[k][e]; se[k][e] = badd2(U[k][e], U[k - 1][2 + e]); so[k][e] = badd2(U[k][e], U[k][2 + e]); }
                };
#pragma unroll
                for (int k = 1; k < 6; k++) sums(k);
#pragma unroll
                for (int m = 3; m >= 0; m--) {
                    uint32_t a0[4];
                    frag(a0, kp + 512 * m);
                    sums(9 - m);
                    if (m) ldu(10 - m); else { R -= 16; places(); }
#pragma unroll
                    for (int i = 0; i < 6; i++) mma_bf(y[2 * i], a1[0], a1[1], a1[2], a1[3], se[i - m + 4][0], se[i - m + 4][1]);
#pragma unroll
                    for (int e = 0; e < 4; e++) a1[e] = bsub2(a0[e], a1[e]);
#pragma unroll
                    for (int i = 0; i < 6; i++) { mma_bf(M[i], a1[0], a1[1], a1[2], a1[3], ue[i - m + 4][0], ue[i - m + 4][1]); if (!m) ldu(i); }
                    frag(a1, m ? kp + 512 * m - 256 : kp + 1792 + 64);
                    if (!m) ldu(6);
#pragma unroll
                    for (int i = 0; i < 6; i++) mma_bf(y[2 * i + 1], a0[0], a0[1], a0[2], a0[3], so[i - m + 4][0], so[i - m + 4][1]);
                }
            }
#pragma unroll
            for (int i = 0; i < 6; i++)
#pragma unroll
                for (int c = 0; c < 4; c++) { acc[4 + i + 6 * (c & 1)][c & 2] = y[2 * i][c] + M[i][c]; acc[4 + i + 6 * (c & 1)][c | 1] = y[2 * i + 1][c] - M[i][c]; }
        }
        const uint32_t lo = (8 + col(r8)) * 16 + (mi >> 1) * 128, ua = fresh(ut) + (mi & 1) * UT_HALF, u1[2] = {ua + swz(lo, warp), ua + (swz(lo, warp) ^ 64)};
        {
            uint32_t e[4];
            frag(e, kb + (KT_T - 16) * 4);
            const uint32_t f0 = dup(e[1]), f1 = lds32(kb + KT_T * 4), uo = fresh(ut) + UT_HALF + swz((7 + 8 * mi + col(r8)) * 16, warp);
#pragma unroll
            for (int i = 0; i < 4; i++) {
                uint32_t b[4];
                if (i < 2) {
                    ldsm4(b, uo + 512 * i);
#pragma unroll
                    for (int k = 0; k < 4; k++) mma_bf8(acc[8 + 4 * i + k], f0, f1, b[k]);
                }
                ldsm4(b, u1[i & 1] + 256 * i);
                mma_bf(acc[2 * i + 8], e[0], e[1], e[2], e[3], b[0], b[1]); mma_bf(acc[2 * i + 9], e[0], e[1], e[2], e[3], b[2], b[3]);
            }
        }
        if ((warp & 3) == 0) TSTAMP(11 + (warp >> 2));
        mbar_wait(bar_v);
        const uint32_t vt = fresh(sb + SC_V) + warp * V_STRIDE;
        const uint32_t g1 = fresh(sb + SC_GT) + (mi & 1) * GT_HALF + lo;
        const uint32_t ydst = mapa(sb + SC_RT + rank * Y_RS + warp * Y_CS + (lane & 23) * 16, mi & 1), ybr = mapa(bar_y, mi & 1);
        uint32_t ug[2][2][4];
        auto ld_ug = [&](int i) { ldsm4t(ug[i & 1][0], u1[i & 1] + 256 * i); ldsm4t(ug[i & 1][1], g1 + 256 * i); };
        auto ship = [&](int i) {
            const uint32_t (&u)[4] = ug[i & 1][0], (&gg)[4] = ug[i & 1][1];
            const uint32_t y0 = gmix(gg[0], acc[2 * i][0], acc[2 * i][1], u[0]), y1 = gmix(gg[1], acc[2 * i][2], acc[2 * i][3], u[1]);
            const uint32_t y2 = gmix(gg[2], acc[2 * i + 1][0], acc[2 * i + 1][1], u[2]), y3 = gmix(gg[3], acc[2 * i + 1][2], acc[2 * i + 1][3], u[3]);
            st_async128(ydst + 512 * (i >> 1) + 128 * (i & 1), y0, y1, y2, y3, ybr + 8 * i);
        };
        const uint32_t VD = vt + (VC_OFF - 400 - 16 * t) * 4 + (8 * g ^ 16 * (-t & 2)), VD2 = vt + (VC_OFF - 415 - 16 * t) * 4 + (8 * g ^ 16 * (~t & 2));
        uint2 bd[10];
        uint32_t x[2][4][4];
        auto ld4 = [&](uint32_t (&v)[4], int dl) { const uint2 w = lds64(VD + 256 * dl); v[0] = w.x; v[1] = w.y; v[2] = lds32(VD2 + 256 * dl); v[3] = dup(w.x); };
        auto mm4 = [&](const uint32_t (&v)[4], int dl) {
#pragma unroll
            for (int s = dl & 1; s < 10; s += 2) if ((dl + s) / 2 >= 4 && (dl + s) / 2 < 16) mma_bf(acc[(dl + s) / 2], v[0], v[1], v[2], v[3], bd[s].x, bd[s].y);
        };
        const uint32_t KE = kt + (KT_D + col(g) + t) * 4, VE = vt + (VE_BASE - 912 - 16 * t) * 4 + (8 * g ^ 16 * (~t & 2));
        uint32_t b0[8], b1[8];
        auto ld8 = [&](uint32_t (&v)[4], int dl) { const uint2 w = lds64(VE + 512 * dl), z = lds64(VE + 512 * dl - 256); v[0] = w.x; v[1] = w.y; v[2] = z.x; v[3] = z.y; };
        auto mm8 = [&](const uint32_t (&v)[4], int dl, int lo, int hi) {
#pragma unroll
            for (int s = 0; s < 8; s++) if (dl + s >= lo && dl + s < hi) mma_bf(acc[dl + s], v[0], v[1], v[2], v[3], b0[s], b1[s]);
        };
        ld4(x[0][0], 6);
#pragma unroll
        for (int s = 0; s < 10; s++) bd[s] = lds64(kt + (KT_C + 2 * col(g) + 2 * t + 8 * s) * 4);
        mm4(x[0][0], 6);
        uint32_t e[8][4];
#pragma unroll
        for (int k = 1; k < 6; k++) {
#pragma unroll
            for (int j = 0; j < 4; j++) ld4(x[k & 1][j], 4 * k + 3 + j);
            ld_ug(k + 1);
            if (k == 3) {
#pragma unroll
                for (int s = 0; s < 8; s++) { b0[s] = lds32(KE + 32 * s); b1[s] = lds32(KE + 32 * s + 16); }
            }
            if (k > 1) ship(k);
#pragma unroll
            for (int j = 0; j < 4; j++) {
                mm4(x[k & 1][j], 4 * k + 3 + j);
                if (k == 3) { ld8(e[j], 8 + j); mm8(e[j], 8 + j, 8, 14); }
                if (k == 5 && j < 2) { ld8(e[4 + j], 12 + j); mm8(e[4 + j], 12 + j, 12, 14); }
            }
        }
        ld_ug(7);
        {
            float (&q0)[4] = acc[0], (&q1)[4] = acc[1];
#pragma unroll
            for (int c = 0; c < 4; c++) q0[c] = q1[c] = 0.f;
            auto m8 = [&](float (&c)[4], int T, int j) { mma_bf(c, e[j][0], e[j][1], e[j][2], e[j][3], b0[T - 8 - j], b1[T - 8 - j]); };
            auto m4 = [&](float (&c)[4], int T, int j) { mma_bf(c, x[0][j][0], x[0][j][1], x[0][j][2], x[0][j][3], bd[2 * T - 27 - j].x, bd[2 * T - 27 - j].y); };
            ship(6);
            ld8(e[6], 14); ld8(e[7], 15);
#pragma unroll
            for (int j = 0; j < 4; j++) ld4(x[0][j], 27 + j);
            m8(q1, 15, 0); m8(q0, 14, 0); m8(q1, 15, 1);
            m8(acc[15], 15, 6); m4(q1, 15, 0); m8(acc[14], 14, 6); m4(q0, 14, 0);
            m8(acc[15], 15, 4); m8(q1, 15, 2); m4(acc[14], 14, 1); m8(q0, 14, 1);
            m4(acc[15], 15, 1); m4(q1, 15, 2); m8(acc[14], 14, 4); m8(q0, 14, 2);
            m8(acc[15], 15, 5); m8(q1, 15, 3); m8(acc[14], 14, 5); m8(q0, 14, 3);
            m4(acc[15], 15, 3); m8(q1, 15, 7);
#pragma unroll
            for (int c = 0; c < 4; c++) { acc[14][c] += q0[c]; acc[15][c] += q1[c]; }
            ship(7);
        }
        if ((warp & 3) == 0) TSTAMP(14 + (warp >> 2)); else TSTAMP(21 + warp);
    }
}

constexpr int SF_WD = 73728;
constexpr int SF_RED = 49152;
constexpr int MU_STRIDE = 1168  , SM_RAW = 98304, SM_UT = SM_RAW + 16384, SM_G = SM_UT + 21504, SM_Y = 196608, SM_FT = SM_Y + 17024, SM_KT = 138880, SM_KW = SM_G - 49152;
constexpr int SF_XS = 221184;
constexpr int SF_MISC = SF_XS + 8 * 1168;
constexpr int SF_KG = SF_MISC - 10 * KG_STAGE;
constexpr int SF_WR = SF_KG - 2304;
constexpr int FB_X = 64, FB_KDONE = 72, FB_KEYS = 80, FB_FREE = 88  , FB_W = 104, FB_D = FB_W + 72, FB_MU = FB_D + 96, FB_FAR = FB_MU - 16, FB_MG = FB_MU + 8, FB_MT = FB_MU + 16  , FS_PART = 512, FS_TOK = 896, FS_BM = 1024;
enum { BAR_R = 7, BAR_GU = 8, BAR_RED = 9, BAR_R2 = 10, BAR_G = 12  , BAR_M = 15 };
static_assert(SF_KG % 128 == 0 && NPRE <= 8 && SM_KT + 4 * 2112 <= 147456 && SM_G + MU_STRIDE <= SF_WR - 4 * 9216 && SM_KW + 6 * 2112 >= SM_RAW && SM_KW + 12 * 2112 <= SM_UT, "layout");

__device__ __forceinline__ constexpr int box_no(int i) { return (0x987610ba5432ull >> (4 * i)) & 15; }
__device__ __forceinline__ int role(int b) { b -= NCONV; return b < NX ? b : 18 + (b >> 1) + 12 * (b & 1); }
__device__ __forceinline__ int mini_ch0(int f) { return 48 * f - (f < NW ? 1696 : 2304); }

__device__ __forceinline__ void ffn_front(const Params& p, const CUtensorMap* maps, uint32_t sb, int warp, int lane, int f, unsigned epoch) {
    const unsigned t0 = clock32();
    const int g = lane >> 2, t = lane & 3, mi = lane >> 3, r8 = lane & 7;
    const bool isx = f < NX;
    const int nrw = f < 52 ? 4 : 6, r0 = f < 52 ? 32 * f : 48 * f - 832;
    const int rw = warp < 12 ? 13 - warp : warp ^ (warp < 14 ? 10 : 15);
    const uint32_t bar_row = sb + SF_MISC  , bar_x = bar_row + FB_X;
    const uint32_t s_part = bar_row + FS_PART  , s_tok = bar_row + FS_TOK  ;
    const uint32_t rows = sb + SF_WR - 9216 * (rw + 1) - (rw & 4) * ((SF_WR - 6 * 9216) / 4);
    {
#pragma unroll 1
        for (int i = warp < 10 ? 30 : warp - 10; i < 30; i += 6) if (elect()) mbar_init(bar_x + 8 * i, i == 1 ? 4 + (f < NW) : i < 27 ? 1 : i == 27 ? 2 : 8);
        const uint32_t bytes = rw < 6 ? 9216 : 1152, dst = rw < 6 ? rows : sb + SF_WR + (rw & 1) * 1152;
        const __nv_bfloat16* src = rw < 6 ? p.u + (size_t)(r0 + 8 * rw) * DM : (rw & 1) ? p.gatew : p.wr;
        if (elect()) { mbar_init(bar_row + 8 * rw, 1); mbar_fence(); mbar_expect(bar_row + 8 * rw, bytes); }
        if (warp == 13) { sts32(s_part + 64 + lane * 4, 0); sts32(bar_row + FS_BM + lane * 4, 0); }
        bar_sync(0, NTHR);
        if (!isx) asm volatile("barrier.cluster.arrive.relaxed.aligned;" ::: "memory");
        if (rw < nrw) until(t0, RDELAY);
        if (rw < nrw || rw >= 6) { if (elect()) bulk_g2s(dst, src, bytes, bar_row + 8 * rw); }
    }
    uint4* const kdst = p.s->keys + (lane >> 1) * 128 + 2 * f + (lane & 1);
    if (warp == 15) TSTAMP(1);

    if (warp == 12) {
        if (lane < 22) mbar_expect(bar_row + FB_W + 8 * lane, lane < 9 ? 24576 : isx ? 12288 : lane < 20 ? 2048 : 16384);
        if (elect()) { prefetch_map(maps + 1); prefetch_map(maps + 2); prefetch_map(maps + (isx ? 3 : 5)); }
        unsigned tb = t0 + WDELAY;
        auto pieces = [&](int n, int end, uint32_t dst) {
#pragma unroll 1
            for (; n < end; n++, dst += 12288) {
                until(tb, 0); tb += WGAP;
                if (elect()) tma3d(dst, maps + 1 + (n & 1), 0, 64 * (n >> 1), 3 * f, bar_row + FB_W + 8 * (n >> 1));
            }
        };
        if (!isx) {
#pragma unroll 1
            for (int k = 0; k <= (f >= NW); k++) { until(t0, MDELAY); if (elect()) tma4d(sb + SM_RAW - 49152 * k, maps + 5, mini_ch0(f) + 16 * k, 0, 0, 0, bar_row + FB_MU - 8 * k); }
            if (f >= NW) return;
        }
#pragma unroll 1
        for (int i = 0; i < 4; i++) {
            if (i == 1) { mbar_wait(bar_row + FB_KEYS); mbar_wait(bar_row + FB_KDONE); tb = clock32() + RESUME; }
            if (i == 3) mbar_wait(bar_row + FB_FREE);
            const int n = ((0x0c080000 + NPRE * 256) >> (8 * i)) & 255;
            pieces(n, ((0x120c0800 + NPRE) >> (8 * i)) & 255, sb + 12288 * (((0x000c0000 + NPRE * 256) >> (8 * i)) & 255));
        }
        TSTAMP(12);
        if (isx) {
#pragma unroll 1
            for (int i = 0; i < 12; i++) {
                const int n = box_no(i);
                if (i == 6) mbar_wait(bar_row + FB_FREE + 8);
                until(tb, 0); tb += DGAP;
                if (elect()) tma2d(sb + SF_WD + n * 12288, maps + 3, 32 * (f >> 1), 2304 * (f & 1) + 192 * n, bar_row + FB_D + 8 * n);
            }
            TSTAMP(13);
        }
    } else if (warp == 13) {
        const uint32_t tag = key_tag(epoch), par = (epoch & 1) ? 0u : 0x8000u;
        stg128(kdst, 0, 0, 0, 0);
        if (lane < 8 && isx && !(f & 1)) st_rlx32(&p.s->sel[32 * f + lane], 0);
        bar_sync(BAR_R, 32 * (nrw + 1));
        TSTAMP(3);
        {
            const uint32_t sg = fresh(s_part) + 192 + lane * 4;
            const uint32_t gb = pack_bf16(sigmoidf_(rbf(__uint_as_float(lds32(sg)))), sigmoidf_(rbf(__uint_as_float(lds32(sg + 128))))) | par | (par << 16);
            asm volatile("st.relaxed.gpu.global.u16 [%0], %1;" :: "l"(p.s->gate + r0 + lane), "h"((unsigned short)gb) : "memory");
            if (nrw > 4 && lane < 16) asm volatile("st.relaxed.gpu.global.u16 [%0], %1;" :: "l"(p.s->gate + r0 + 32 + lane), "h"((unsigned short)(gb >> 16)) : "memory");
        }
        bar_sync(BAR_R2, 32 * (nrw + 1));
        {
            const uint4 v = lds128(fresh(s_tok) + (lane & 1) * 16);
            asm volatile("st.relaxed.gpu.global.v4.u32 [%0], {%1,%2,%3,%4};" :: "l"(kdst), "r"(v.x | tag), "r"(v.y | tag), "r"(v.z | tag), "r"(v.w | tag) : "memory");
        }
        TSTAMP(4);
        if (lane == 0) { mbar_arrive(bar_row + FB_KEYS); mbar_expect(bar_x, 8 * 1152); }
        if (f >= NW) return;
        mbar_wait(bar_row + FB_KDONE);
        uint32_t k[16];
        const uint4* src = p.s->keys + (f & 15) * 128 + lane;
#pragma unroll 1
        for (int it = 0;; it++) {
            uint32_t bad = 0;
#pragma unroll
            for (int i = 0; i < 4; i++) {
                const uint4 x = ld_rlx128(src + (i < 3 || lane < 24 ? 32 * i : 64));
                k[i] = x.x; k[4 + i] = x.y; k[8 + i] = x.z; k[12 + i] = x.w;
                bad |= x.x ^ tag;
            }
            const bool ok = __all_sync(0xffffffffu, (bad & 0xf800u) == 0);
            if (ok) break;
            if (it > (1 << 20)) give_up();
        }
        TSTAMP(5);
        uint32_t key = 0, m = __reduce_max_sync(0xffffffffu, max(max(k[0], k[1]), max(k[2], k[3])));
#pragma unroll 2
        for (int r = 0; r < 8; r++) {
            bool pop[4];
#pragma unroll
            for (int i = 0; i < 4; i++) { pop[i] = k[i] == m; k[i] = pop[i] ? k[4 + i] : k[i]; }
            const uint32_t mn = __reduce_max_sync(0xffffffffu, max(max(k[0], k[1]), max(k[2], k[3])));
            if (elect()) bulk_g2s(sb + SF_XS + r * 1168, p.u + (size_t)key_row(m) * DM, 1152, bar_x);
#pragma unroll
            for (int i = 0; i < 4; i++) { k[4 + i] = pop[i] ? k[8 + i] : k[4 + i]; k[8 + i] = pop[i] ? k[12 + i] : k[8 + i]; k[12 + i] = pop[i] ? 0 : k[12 + i]; }
            if (r8 == r) key = m;
            m = mn;
        }
        const int row = key_row(key);
        sts32(s_tok + r8 * 8, row);
        TSTAMP(6);
        if (isx) {
            if (!(f & 1)) {
                __nv_bfloat16* o = p.out + (size_t)row * DM + 16 * f + 8 * mi;
                asm volatile("st.relaxed.gpu.global.v4.u32 [%0], {%1,%1,%1,%1};" :: "l"(o), "r"(0) : "memory");
                if (__any_sync(0xffffffffu, ld_rlx32(o) != 0)) give_up();
                if (lane < 8) st_rlx32(&p.s->sel[32 * f + lane], key);
            } else wait_sel(p, f >> 1, r8, tag);
            uint32_t gb;
#pragma unroll 1
            for (int it = 0;; it++) {
                asm volatile("ld.relaxed.gpu.global.u16 %0, [%1];" : "=r"(gb) : "l"(p.s->gate + row) : "memory");
                gb ^= par;
                if (!(gb & 0x8000u)) break;
                if (it > (1 << 20)) give_up();
            }
            const uint32_t rb = key ^ 0x80000000u, rv = (rb ^ (((int)rb >> 31) & 0x7fff0000u)) & 0xffff0000u;
            sts32(s_tok + r8 * 8 + 4, __float_as_uint(rbf(1.0f - bf_lo(gb)) * rbf(sigmoidf_(__uint_as_float(rv)))));
            __syncwarp();
            TSTAMP(7);
            bar_arrive(BAR_RED, 416);
        }
    } else {
        if (rw < nrw) {
            float c[3][4];
#pragma unroll
            for (int i = 0; i < 3; i++) { c[i][0] = c[i][1] = c[i][2] = c[i][3] = 0.f; }
            mbar_wait(bar_row + 48); mbar_wait(bar_row + 56);
            const uint32_t b = fresh(sb + SF_WR) + (g & 1) * 1152 + (g >> 2) * 64 + t * 16 + (g & 2) * 2;
            uint32_t w[18][2];
#pragma unroll
            for (int kb = 0; kb < 18; kb++) { const uint32_t o = ((kb & 1) ? b ^ 64 : b) + 128 * (kb >> 1); w[kb][0] = lds32(o); w[kb][1] = lds32(o + 8); }
            mbar_wait(bar_row + 8 * rw);
            if (warp == 15) TSTAMP(2);
            const uint32_t a = fresh(rows) + g * 1152 + (g & 1) * 64 + t * 16;
#pragma unroll
            for (int kb = 0; kb < 18; kb++) {
                const uint4 x = lds128(((kb & 1) ? a ^ 64 : a) + 128 * (kb >> 1));
                mma_bf(c[kb % 3], x.x, x.y, x.z, x.w, w[kb][0], w[kb][1]);
            }
            const float sr = c[0][0] + c[1][0] + c[2][0] + __shfl_down_sync(0xffffffffu, c[0][2] + c[1][2] + c[2][2], 1);
            const float sg = c[0][1] + c[1][1] + c[2][1] + __shfl_down_sync(0xffffffffu, c[0][3] + c[1][3] + c[2][3], 1);
            const uint32_t rb = pack_bf16(0.f, sr);
            if (t == 2 * (g & 1)) {
                sts32(s_part + (8 * rw + g) * 4, (rb ^ (((int)rb >> 31) & 0x7fff0000u) ^ 0x80000000u) | (uint32_t)(2047 - r0 - 8 * rw - g));
                sts32(s_part + 192 + (8 * rw + g) * 4, __float_as_uint(sg));
            }
            __syncwarp();
            bar_sync(BAR_R, 32 * (nrw + 1));
            const uint32_t sk = fresh(s_part), kk = lds32(sk + (8 * rw + r8) * 4);
            int n = 0;
#pragma unroll
            for (int i = 0; i < 3; i++) { const uint4 v = lds128(sk + mi * 48 + 16 * i); n += (v.x > kk) + (v.y > kk) + (v.z > kk) + (v.w > kk); }
            n += __shfl_xor_sync(0xffffffffu, n, 8); n += __shfl_xor_sync(0xffffffffu, n, 16);
            if (n < 8) sts32(s_tok + 4 * n, kk);
            __syncwarp();
            bar_arrive(BAR_R2, 32 * (nrw + 1));
        }
    }
}

__device__ __forceinline__ void ffn_work(const Params& p, uint32_t sb, int warp, int lane, int f, unsigned epoch) {
    const int g = lane >> 2, t = lane & 3, mi = lane >> 3, r8 = lane & 7;
    const bool isx = f < NX;
    const uint32_t bar_x = sb + SF_MISC + FB_X, bar_free = sb + SF_MISC + FB_FREE, bar_w = sb + SF_MISC + FB_W, bar_d = sb + SF_MISC + FB_D, s_tok = sb + SF_MISC + FS_TOK;
    uint32_t fr[24][4];
    auto pin = [&] {
#pragma unroll
        for (int i = 0; i < 24; i += 8) asm volatile("" :: "r"(fr[i][0]), "r"(fr[i + 1][0]), "r"(fr[i + 2][0]), "r"(fr[i + 3][0]), "r"(fr[i + 4][0]), "r"(fr[i + 5][0]), "r"(fr[i + 6][0]), "r"(fr[i + 7][0]) : "memory");
    };
    {
        const int j = (unsigned)(warp - 4) < 6, w = warp - (j ? 4 : warp < 4 ? 0 : 6);
        float ag[2][4], au[2][4];
#pragma unroll
        for (int i = 0; i < 2; i++) { ag[i][0] = ag[i][1] = ag[i][2] = ag[i][3] = 0.f; au[i][0] = au[i][1] = au[i][2] = au[i][3] = 0.f; }
        const uint32_t wb = sb + (w >> 1) * 4096 + (r8 + 8 * (mi >> 1)) * 64 + (((2 * (w & 1) + (mi & 1)) ^ (r8 >> 1)) << 4);
        const uint32_t xb = sb + SF_XS + r8 * 1168 + mi * 16;
        auto load = [&](int i, int n, int place) {
            mbar_wait(bar_w + 8 * n);
            const uint32_t wk = fresh(wb) + place * 24576;
#pragma unroll
            for (int s = 0; s < 4; s++) { ldsm4t(fr[8 * i + s], wk + 1024 * s); ldsm4t(fr[8 * i + 4 + s], wk + 1024 * s + 12288); }
        };
        auto mul = [&](int i, uint32_t xk) {
            uint32_t x[2][4];
            ldsm4(x[0], xk); ldsm4(x[1], xk + 64);
#pragma unroll
            for (int s = 0; s < 4; s++) {
                const uint32_t (&a)[4] = fr[8 * i + s], (&b)[4] = fr[8 * i + 4 + s];
                mma_bf(ag[s & 1], a[0], a[1], a[2], a[3], x[s >> 1][2 * (s & 1)], x[s >> 1][2 * (s & 1) + 1]);
                mma_bf(au[s & 1], b[0], b[1], b[2], b[3], x[s >> 1][2 * (s & 1)], x[s >> 1][2 * (s & 1) + 1]);
            }
        };
#pragma unroll
        for (int i = 0; i < 3; i++) load(i, 3 * j + i, (i ? 5 : 3) * j + i);
        pin();
        bar_sync(BAR_G + j, 192);
        if (w == 0 && lane == 0) mbar_arrive(bar_free + 8 * j);
        mbar_wait(bar_x);
        if (warp == 0) TSTAMP(8);
        {
            const uint32_t xk = fresh(xb) + 384 * j;
#pragma unroll
            for (int i = 0; i < 3; i++) { mul(i, (i ? fresh(xk) : xk) + 128 * i); if (i == 0) { asm volatile("" :: "f"(ag[0][0]), "f"(ag[1][0]), "f"(au[0][0]), "f"(au[1][0])); sts32(s_tok + 64, clock32()); } }
        }
#pragma unroll 1
        for (int n = 6 + j; n < 9; n += 2) { load(0, n, n - 6); mul(0, fresh(xb) + 128 * n); }
#pragma unroll
        for (int c = 0; c < 4; c++) { ag[0][c] += ag[1][c]; au[0][c] += au[1][c]; }
        if (j) {
            sts128(wb + 24576, __float_as_uint(ag[0][0]), __float_as_uint(ag[0][1]), __float_as_uint(ag[0][2]), __float_as_uint(ag[0][3]));
            sts128(wb + 25600, __float_as_uint(au[0][0]), __float_as_uint(au[0][1]), __float_as_uint(au[0][2]), __float_as_uint(au[0][3]));
        }
        bar_sync(BAR_GU, 384);
        if (!j) {
            const uint32_t sf = fresh(wb);
            const uint4 g1 = lds128(sf + 24576), u1 = lds128(sf + 25600);
            const uint32_t gs[4] = {g1.x, g1.y, g1.z, g1.w}, us[4] = {u1.x, u1.y, u1.z, u1.w};
            if (warp == 0) TSTAMP(9);
            float h[4];
#pragma unroll
            for (int c = 0; c < 4; c++) {
                const float gv = rbf(ag[0][c] + __uint_as_float(gs[c]));
                h[c] = rbf(gv * sigmoidf_(gv)) * rbf(au[0][c] + __uint_as_float(us[c]));
            }
            uint32_t h0, h1;
            asm("movmatrix.sync.aligned.m8n8.trans.b16 %0, %1;" : "=r"(h0) : "r"(pack_bf16(h[0], h[1])));
            asm("movmatrix.sync.aligned.m8n8.trans.b16 %0, %1;" : "=r"(h1) : "r"(pack_bf16(h[2], h[3])));
            if (h0 == 0) h0 = 0x8000u;
            asm volatile("{ .reg .b64 v; mov.b64 v, {%1, %2}; st.relaxed.gpu.global.b64 [%0], v; }" :: "l"(p.s->h + ((epoch & 1) * 288 + 6 * f + w) * 32 + lane), "r"(h0), "r"(h1) : "memory");
        }
        if (isx) {
            if (warp == 0) TSTAMP(10);
            const uint2* hsrc = p.s->h + ((epoch & 1) * 288 + 144 * (f & 1) + warp) * 32 + lane;
            const uint32_t wd = sb + SF_WD + warp * 1024 + (r8 + 8 * (mi >> 1)) * 64 + (((mi & 1) ^ (r8 >> 1)) << 4), we = wd ^ 32;
            uint2 hb[12];
            auto ldh = [&](int i) { asm volatile("ld.relaxed.gpu.global.v2.u32 {%0, %1}, [%2];" : "=r"(hb[i].x), "=r"(hb[i].y) : "l"(hsrc + 384 * box_no(i)) : "memory"); };
            auto ldw = [&](int i) { mbar_wait(bar_d + 8 * box_no(i)); ldsm4t(fr[2 * i], fresh(wd) + 12288 * box_no(i)); ldsm4t(fr[2 * i + 1], fresh(we) + 12288 * box_no(i)); };
#pragma unroll
            for (int i = 0; i < DPA; i++) ldw(i);
#pragma unroll
            for (int i = 0; i < 12; i++) ldh(i);
#pragma unroll
            for (int i = DPA; i < DPB; i++) ldw(i);
#pragma unroll
            for (int i = 0; i < DPB; i++) asm volatile("" :: "r"(fr[2 * i][0]), "r"(fr[2 * i + 1][0]) : "memory");
#pragma unroll 1
            for (int it = 0;; it++) {
                bool again = false;
#pragma unroll
                for (int s = 0; s < 12; s += 2) if (__any_sync(0xffffffffu, min(hb[s].x, hb[s + 1].x) == 0)) { ldh(s); ldh(s + 1); again = true; }
                if (!again) break;
                if (it > (1 << 16)) give_up();
            }
            if (warp == 0) TSTAMP(11);
            float ad[2][2][4];
#pragma unroll
            for (int i = 0; i < 4; i++) { ad[i >> 1][i & 1][0] = ad[i >> 1][i & 1][1] = ad[i >> 1][i & 1][2] = ad[i >> 1][i & 1][3] = 0.f; }
#pragma unroll
            for (int i = 0; i < 12; i++) {
                if (i >= DPB) ldw(i);
                if (i == 11 && warp == 9) TSTAMP(14);
#pragma unroll
                for (int c = 0; c < 2; c++) mma_bf(ad[c][i & 1], fr[2 * i + c][0], fr[2 * i + c][1], fr[2 * i + c][2], fr[2 * i + c][3], hb[i].x, hb[i].y);
                if (i >= DPB - 1) asm volatile("" :: "f"(ad[0][i & 1][0]), "f"(ad[1][i & 1][0]) : "memory");
            }
            const uint32_t rd = sb + SF_RED + warp * 1152 + (72 * t + g) * 4;
#pragma unroll
            for (int i = 0; i < 8; i++) sts32(rd + (i >> 2) * 64 + (i & 1) * 144 + ((i >> 1) & 1) * 32, __float_as_uint(ad[i >> 2][0][i & 3] + ad[i >> 2][1][i & 3]));
            bar_sync(BAR_RED, 416);
            if (warp < 4) {
                const int tid = 32 * warp + lane;
                const uint32_t rs = fresh(sb + SF_RED) + (tid >> 4) * 144 + (tid & 15) * 8;
                const uint2 tk = lds64(fresh(s_tok) + (tid >> 4) * 8);
                float x = 0.f, y = 0.f;
#pragma unroll
                for (int w = 0; w < 12; w++) { const uint2 v = lds64(rs + w * 1152); x += __uint_as_float(v.x); y += __uint_as_float(v.y); }
                asm volatile("red.relaxed.gpu.global.add.noftz.bf16x2 [%0], %1;" :: "l"(p.out + (size_t)tk.x * DM + 32 * (f >> 1) + 2 * (tid & 15)),
                             "r"(pack_bf16(x * __uint_as_float(tk.y), y * __uint_as_float(tk.y))) : "memory");
            }
            if (warp == 0) { TSTAMP(15); TFLUSH(); }
            asm volatile("exit;"); __builtin_unreachable();
        }
    }
}

__device__ __forceinline__ void fetch_k(const uint4* src, uint64_t (&v)[4], uint32_t a, uint32_t b) {
    asm volatile("{ .reg .pred p; setp.eq.u32 p, %5, %6; @p ld.relaxed.gpu.global.v2.u64 {%0,%1}, [%4]; @p ld.relaxed.gpu.global.v2.u64 {%2,%3}, [%4 + 512]; }"
                 : "+l"(v[0]), "+l"(v[1]), "+l"(v[2]), "+l"(v[3]) : "l"(src), "r"(a), "r"(b));
}
__device__ __forceinline__ uint32_t mini_conv(const Params& p, uint32_t sb, int warp, int lane, int f, unsigned epoch, uint64_t (&v)[4]) {
    const int g = lane >> 2, t = lane & 3, mi = lane >> 3, r8 = lane & 7;
    const uint32_t fb = sb + SF_MISC, kt = sb + (warp >= 12 ? SM_KT - 12 * 2112 : f < NW ? SM_KW + 2 * 2112 : SM_KW) + warp * 2112;
    const bool ism = f >= NW;
    const uint32_t* const sel = &p.s->sel[((mini_ch0(f) + (ism ? 2 * (warp & 8) : 0)) >> 5) * 64 + r8];
    uint32_t seq = 128, key;
    const uint4* src = p.s->kp + lane;
    auto hi = [&](int i) { return (uint32_t)(v[i] >> 32); };
    if (f >= (warp < 4 ? NW : NX)) {
    {
        const uint32_t c = 68 + (warp & 3) + 2 * (warp & 12), y = ((uint32_t)((warp < 8 ? 0xe066806400000000ull : 0x5a6e00680080e26cull) >> ((8 * warp) & 48)) & 0xffff) + (warp < 14 ? 0 : 0x6a0000);
        seq = !ism ? y + (warp & 1) * ((y >> 6) & 0x10101) : warp < 14 ? 0x101 * c - 0x400 : c;
        src += (48 * (f - (ism ? NW : NX)) + (seq & 63)) * 96;
    }
    if (seq & 64) {
        if (seq & 4) {
            const int q = (seq & 3) + ((seq >> 1) & 4);
            const uint32_t ab = sb - 3072 * (seq & 16), d = ab + SM_UT + g * MU_STRIDE + (4 + 4 * q + t) * 32;
            asm volatile("st.shared.v2.u32 [%0], {%1,%1};" :: "r"(ab + SM_UT + (2 * q + (mi >> 1)) * MU_STRIDE + (lane & 15) * 8), "r"(0) : "memory");
            mbar_wait(fb + FB_MU - (seq & 16) / 2);
            if (warp == 15) TSTAMP(16);
            const uint32_t a = fresh(ab + SM_RAW) + q * 2048 + (8 * mi + 4 * (r8 & 1) + (r8 >> 1)) * 32 + ((r8 & 1) << 4);
            uint32_t x[4][4];
#pragma unroll
            for (int i = 0; i < 4; i++) ldsm4t(x[i], (i & 2 ? a ^ 16 : a) + 1024 * (i & 1));
#pragma unroll
            for (int i = 0; i < 4; i++) sts128(d + (i & 1) * 16 + (i & 2) * 4 * MU_STRIDE, x[i][0], x[i][1], x[i][2], x[i][3]);
            __syncwarp();
            if (lane == 0) mbar_arrive(fb + FB_MT + (seq & 16) / 2);
        }
        mbar_wait(fb + FB_KDONE);
        fetch_k(src, v, warp < 4, 0);
        if ((warp | 2) == 7) { fetch_gates(p, (warp >> 1) & 1, lane, epoch, sb + SM_G + 256 * (warp & 2) + 16 * lane); __syncwarp(); if (lane == 0) mbar_arrive(fb + FB_MG); }
        if (warp >= 8) {
            mbar_wait(fb + FB_KEYS); mbar_wait(fb + FB_MT);
            if (ism) {
                asm volatile("barrier.cluster.wait.aligned; fence.release.sync_restrict::shared::cta.cluster;" ::: "memory");
                if (lane == 0) asm volatile("mbarrier.arrive.relaxed.cluster.shared::cluster.b64 _, [%0];" :: "r"(mapa(fb + FB_MT + 8, 0)) : "memory");
            }
        }
        if (warp == TW) TSTAMP(17);
    }
    }
    const uint32_t lo = (8 + r8 - (mi & 1)) * 16 + (mi >> 1) * 128;
#pragma unroll 1
    do {
        const int c = seq & 63;
        const bool far = !ism && (seq & 16);
        const uint32_t ab = sb - 3072 * (c & 16);
        uint32_t ut = ab + SM_UT + (c & 15) * MU_STRIDE;
        if (seq & 64) {
        if (far) {
            mbar_wait_cluster(fb + FB_MT + 8);
            const uint32_t ru = mapa(ut, 1) + lane * 16;
            ut = sb + SM_FT + (c & 3) * 1536;
            uint4 x[3];
#pragma unroll
            for (int i = 0; i < 3; i++) asm volatile("ld.shared::cluster.v4.u32 {%0,%1,%2,%3}, [%4];" : "=r"(x[i].x), "=r"(x[i].y), "=r"(x[i].z), "=r"(x[i].w) : "r"(ru + 512 * i) : "memory");
#pragma unroll
            for (int i = 0; i < 3; i++) sts128(ut + lane * 16 + 512 * i, x[i].x, x[i].y, x[i].z, x[i].w);
        } else mbar_wait(fb + FB_MT + (seq & 16) / 2);
#pragma unroll 1
        for (int it = 0; !__all_sync(0xffffffffu, hi(1) & hi(3) & k_tag(epoch)); it++) {
            fetch_k(src, v, 0, 0);
            if (it > (1 << 20)) give_up();
        }
        sts128(kt + t * 16, 0, 0, 0, 0);
        if (warp == TW) TSTAMP(seq >> 8 ? 7 : 10);
        const uint32_t w[12] = {(uint32_t)v[0], hi(0), (uint32_t)v[1], hi(1), (uint32_t)v[2], hi(2), (uint32_t)v[3], hi(3), 0, 0, 0, 0};
        k_tables<false>(fresh(kt), fresh(lane), w);
        }
        __syncwarp();
        if (seq & 128) ffn_work(p, sb, warp, fresh(lane), f, epoch);
        if (!(seq & 64)) return 0;
        const uint32_t kb = fresh(kt) + (16 + g - 2 * t) * 4, ub = fresh(ut);
        const uint32_t yd = ab + SM_Y + (c & 15) * 1056 + (c & 8) * 8 + lane * 16;
        if (warp == TW && !(seq >> 8)) TSTAMP(13);
        seq >>= 8;
        src += ((int)(seq & 63) - c) * 96;
#pragma unroll
        for (int i = 0; i < 4; i++) v[i] = 0;
        key = 0;
        float acc[8][4];
#pragma unroll
        for (int i = 0; i < 8; i++) { acc[i][0] = acc[i][1] = acc[i][2] = acc[i][3] = 0.f; }
        uint32_t a[4][4], b[2][4][4];
        auto lda = [&](int j, int s) { const uint32_t x = kb + 64 * s + 512 * j; a[j][0] = lds32(x); a[j][1] = lds32(x + 256); a[j][2] = lds32(x + 32); a[j][3] = lds32(x + 288); };
        auto ldb = [&](int i, int s) { ldsm4(b[s & 1][i], ub + lo + 256 * i - 32 * s); };
#pragma unroll
        for (int j = 0; j < 4; j++) { ldb(j, 0); lda(j, 0); }
#pragma unroll
        for (int s = 0; s < 4; s++) {
            if (s == 2) {
                const uint32_t e = seq | (__float_as_uint(acc[0][0]) & p.zero);
                fetch_k(src, v, e & 64, 64);
                asm volatile("{ .reg .pred p; setp.eq.u32 p, %2, 0; @p ld.relaxed.gpu.global.u32 %0, [%1]; }" : "+r"(key) : "l"(sel), "r"(e));
            }
#pragma unroll
            for (int i = 0; i < 4; i++) {
                const int j = (i >> 1) + 2 * (i & 1);
                if (s < 3) ldb(i, s + 1);
#pragma unroll
                for (int mu = 0; mu < 8; mu++) if (mu + 2 * j < 8) mma_bf(acc[mu + 2 * j], a[j][0], a[j][1], a[j][2], a[j][3], b[s & 1][mu >> 1][2 * (mu & 1)], b[s & 1][mu >> 1][2 * (mu & 1) + 1]);
                if (s < 3) lda(j, s + 1);
            }
        }
        if (warp == TW && !seq) TSTAMP(14);
        mbar_wait(fb + FB_MG);
        uint32_t ug[4][4];
#pragma unroll
        for (int i = 0; i < 2; i++) { ldsm4t(ug[i], ub + 128 + lane * 16 + 512 * i); ldsm4t(ug[2 + i], fresh(sb + SM_G) + lane * 16 + 512 * i); }
#pragma unroll
        for (int x = 0; x < 8; x++) ug[x >> 2][x & 3] = gmix(ug[2 + (x >> 2)][x & 3], x ? acc[x][0] + acc[x - 1][2] : acc[0][0], x ? acc[x][1] + acc[x - 1][3] : acc[0][1], ug[x >> 2][x & 3]);
        if (far) for (int i = 0; i < 2; i++) st_async128(mapa(yd, 1) + 512 * i, ug[i][0], ug[i][1], ug[i][2], ug[i][3], mapa(fb + FB_FAR, 1));
        else for (int i = 0; i < 2; i++) sts128(yd + 512 * i, ug[i][0], ug[i][1], ug[i][2], ug[i][3]);
        __syncwarp();
        if (warp == TW) TSTAMP(18 + (seq != 0));
    } while (seq);
    if (warp >= 12) TSTAMP(12 + warp);
    return key;
}
__device__ __forceinline__ void mini_out(const Params& p, const CUtensorMap* maps, uint32_t sb, int warp, int lane, int f, unsigned epoch, uint32_t key) {
    const int g = lane >> 2, t = lane & 3, mi = lane >> 3, r8 = lane & 7;
    const uint32_t fb = sb + SF_MISC;
    const bool ism = f >= NW;
    const int ch0 = mini_ch0(f);
    const int k = ism ? warp >> 3 : 0;
    uint32_t first = 1;
    if (lane == 0) asm volatile("atom.shared.exch.b32 %0, [%1], 1;" : "=r"(first) : "r"(fb + FS_BM + 64 + 4 * k) : "memory");
    if (!__all_sync(0xffffffffu, first)) {
        if (elect()) prefetch_map(maps + 6);
        const int row = key_row(wait_sel(p, (ch0 + 16 * k) >> 5, r8, key_tag(epoch), key));
        if (row < 512) asm volatile("red.shared.or.b32 [%0], %1;" :: "r"(fb + FS_BM + (row >> 5) * 4), "r"(1u << (row & 31)) : "memory");
        if (k) mbar_wait_cluster(fb + FB_FAR);
    }
    const int m = warp & 7, dr = 64 * (g >> 1) + 16 * (t >> 1) + 8 * (g & 1);
    const uint32_t y = SM_Y + ((r8 >> 1) & 1) * 8512 + (2 * mi + (r8 & 1)) * 1056 + (2 * m + (r8 >> 2)) * 16;
    const uint32_t so = (g >> 1) * 128 + (t >> 1) * 64 + (g & 1) * 32 + (t & 1) * 16;
    bar_sync(BAR_M - k, ism ? 256 : NTHR);
#pragma unroll 1
    for (int h = ism ? 0 : warp >> 3;; h++) {
        const int r0 = 256 * h + 32 * (m & 1) + (m >> 1), row = r0 + dr;
        const uint32_t bm = lds32(fresh(fb) + FS_BM + (row >> 5) * 4) >> (row & 31), ab = fresh(sb - 49152 * k + 512 * h), stg = ab + SM_UT + 2048 * m + 512 * h;
        uint32_t x[2][4];
        ldsm4t(x[0], ab + y); ldsm4t(x[1], ab + y + 256);
        if (warp == 0 && x[0][0] != 0x12345) TSTAMP(28);
        if (__any_sync(0xffffffffu, bm & 0x11u)) {
#pragma unroll
            for (int i = 0; i < 2; i++) store_or_add(p.out + (size_t)(row + 4 * i) * DM + ch0 + 16 * k + 8 * (t & 1), x[i], bm & (1u << (4 * i)));
        } else {
#pragma unroll
            for (int i = 0; i < 2; i++) sts128(stg + so + 512 * i, x[i][0], x[i][1], x[i][2], x[i][3]);
            asm volatile("fence.proxy.async.shared::cta;" ::: "memory");
            __syncwarp();
            if (elect()) store_rows(maps + 6, stg, ch0 + 16 * k, r0);
        }
        if (h >= ism) break;
    }
    if (elect()) { asm volatile("cp.async.bulk.commit_group;" ::: "memory"); asm volatile("cp.async.bulk.wait_group.read 0;" ::: "memory"); }
    if (warp == 8) TSTAMP(11);
    if (warp == 0) { TSTAMP(15); TFLUSH(); }
}

constexpr int SMEM_BYTES = 232448;
static_assert(SF_MISC + 1152 <= 232192, "layout");

struct Maps { CUtensorMap m[7]; };

__global__ void __cluster_dims__(2, 1, 1) __launch_bounds__(NTHR, 1)
fused_kernel(const Params p, const __grid_constant__ Maps maps) {
    extern __shared__ __align__(1024) uint8_t smem_raw[];
    uint32_t q[8];
    {
        const int b = role(blockIdx.x), x = threadIdx.x, rc = 5 * b + (b & ~3) + 4 + (x >> 6);
        const int cv = (unsigned)b < NW ? 0 : -1, ca = (b < 0 ? 8 * b + DM : 48 * b - 2300) + ((x >> 5) & 3), cb = 2 * rc - (rc & 3) + 4;
        const uint32_t ch = (ca & cv) | (cb & ~cv), o = NST * ch + 2 * ((x & 31) + ((x >> (cv & 2)) & 32));
        const bool c = x < (cv ? 256 : 320);
        q[6] = ldg16_if(c, p.logdt + ch);
        q[2] = ldg32_if(c, p.Bre + o); q[3] = ldg32_if(c, p.Bim + o); q[4] = ldg32_if(c, p.Cre + o); q[5] = ldg32_if(c, p.Cim + o); q[0] = ldg32_if(c, p.Are + o); q[1] = ldg32_if(c, p.Aim + o);
        q[7] = ldg16_if(c, p.Dskip + ch);
    }
    const unsigned epoch = ld_rlx32(&p.s->epoch[blockIdx.x * 16 + (threadIdx.x >> 5)]);
    const uint32_t sb = __shfl_sync(0xffffffffu, smem_u32(smem_raw), 0);
    const int warp = __shfl_sync(0xffffffffu, threadIdx.x >> 5, 0), bid = __shfl_sync(0xffffffffu, blockIdx.x, 0);
    const int lane = __shfl_sync(0xffffffffu, threadIdx.x & 31, threadIdx.x);
    const bool conv = bid < NCONV;
    const int f = role(bid);
    uint32_t w[12];
    uint64_t v[4];
    const bool four = (unsigned)f >= NW;
    if (warp < (four ? 8 : 10)) {
        const int half = four ? warp >> 2 : warp & 1, pr = four ? warp & 3 : warp >> 1;
        const int rc = 5 * f + (f & ~3) + 4 + pr;
        const uint32_t stage = sb + (conv ? SC_KG : SF_KG) + warp * KG_STAGE;
        uint4* const kp = p.s->kp + (four ? (conv ? 8 * bid : 48 * f - 2300) + pr : 2 * rc - (rc & 3) + 4) * 96 + lane;
        kgen(q, sb, half, stage, stage + (four ? 4 : 1) * KG_STAGE, 1 + pr, lane, w, [&] {
            sts128z_if(conv && lane < 20, sb + SC_KT + warp * KT_BYTES + lane * 16 + (lane < 4 ? 0 : lane < 14 ? 2048 : 2288));
            stg128z_if((unsigned)f < NW && warp < 6, (uint4*)(p.s->h + ((lane >> 4) * 288 + 6 * f + warp) * 32) + (lane & 15));
            if (!conv) bar_sync(0, NTHR);
            if ((unsigned)f >= NX) asm volatile("barrier.cluster.arrive.relaxed.aligned;" ::: "memory");
        }, [&] {
            asm volatile("{ .reg .pred p, q; setp.ne.u32 p, %2, 0; setp.ne.and.u32 q, %3, 0, p; @p st.global.v4.u32 [%0], {%1,%1,%1,%1}; @q st.global.v4.u32 [%0 + 512], {%1,%1,%1,%1}; }"
                         :: "l"(kp + 32 * half), "r"(0), "r"((uint32_t)!conv), "r"((uint32_t)(half && lane < 18)) : "memory");
        });
        if (!half) publish_k(kp, lane, !conv, w, epoch, v);
        else for (int i = 0; i < 4; i++) v[i] = 0;
        if (conv) { conv_main(p, sb, warp, lane, bid, epoch, w); return; }
        {
            if (!half && lane == 0) mbar_arrive(sb + SF_MISC + FB_KDONE);
            if (warp == 0) TSTAMP(22);
            if (warp == 2) TSTAMP(23);
        }
    } else if (conv) {
        conv_aux(p, maps.m, sb, warp - 8, lane, bid, epoch);
        return;
    } else {
        ffn_front(p, maps.m, sb, warp, lane, f, epoch);
        for (int i = 0; i < 4; i++) v[i] = 0;
    }
    converged();
    next_epoch(p, epoch);
    if (warp >= 12 && f < NX) return;
    mini_out(p, maps.m, sb, warp, lane, f, epoch, mini_conv(p, sb, warp, __shfl_sync(0xffffffffu, lane, lane), f, epoch, v));
}

typedef CUresult (*EncodeFn)(CUtensorMap*, CUtensorMapDataType, cuuint32_t, void*, const cuuint64_t*, const cuuint64_t*, const cuuint32_t*, const cuuint32_t*,
                             CUtensorMapInterleave, CUtensorMapSwizzle, CUtensorMapL2promotion, CUtensorMapFloatOOBfill);

void make_map(EncodeFn fn, CUtensorMap* m, const void* base, int rank, const cuuint64_t* dims, const cuuint64_t* strides, const cuuint32_t* box, CUtensorMapSwizzle sw) {
    const cuuint32_t es[5] = {1, 1, 1, 1, 1};
    fn(m, CU_TENSOR_MAP_DATA_TYPE_BFLOAT16, rank, (void*)base, dims, strides, box, es, CU_TENSOR_MAP_INTERLEAVE_NONE, sw,
       CU_TENSOR_MAP_L2_PROMOTION_NONE, CU_TENSOR_MAP_FLOAT_OOB_FILL_NONE);
}

}

extern "C" void kernel_launch(void* const* d_in, const int* in_sizes, int n_in, void* d_out, int out_size) {
    (void)in_sizes; (void)n_in; (void)out_size;
    static EncodeFn fn = nullptr;
    static void* scratch = nullptr;
    if (!fn) {
        void* ptr = nullptr; cudaDriverEntryPointQueryResult qr;
        cudaGetDriverEntryPoint("cuTensorMapEncodeTiled", &ptr, cudaEnableDefault, &qr);
        fn = (EncodeFn)ptr;
        cudaGetSymbolAddress(&scratch, g_scratch);
        cudaFuncSetAttribute(fused_kernel, cudaFuncAttributeMaxDynamicSharedMemorySize, SMEM_BYTES);
    }
    typedef const __nv_bfloat16* bp;
    Params p;
    p.u = (bp)d_in[0]; p.Are = (bp)d_in[1]; p.Aim = (bp)d_in[2]; p.Bre = (bp)d_in[3]; p.Bim = (bp)d_in[4]; p.Cre = (bp)d_in[5]; p.Cim = (bp)d_in[6];
    p.logdt = (bp)d_in[7]; p.Dskip = (bp)d_in[8]; p.wr = (bp)d_in[10]; p.gatew = (bp)d_in[14];
    p.out = (__nv_bfloat16*)d_out; p.s = (Scratch*)scratch; p.zero = 0;
    Maps maps;
    {
        const cuuint64_t dims[4] = {DM, 4, 16, 32}, strides[3] = {16 * DM * 2, DM * 2, 64 * DM * 2};
        const cuuint32_t box[4] = {16, 4, 16, 2};
        make_map(fn, &maps.m[0], d_in[0], 4, dims, strides, box, CU_TENSOR_MAP_SWIZZLE_32B);
        const cuuint32_t box2[4] = {16, 4, 16, 8};
        make_map(fn, &maps.m[5], d_in[0], 4, dims, strides, box2, CU_TENSOR_MAP_SWIZZLE_32B);
    }
    for (int i = 0; i < 2; i++) {
        const cuuint64_t dims[3] = {32, DM, FF / 32}, strides[2] = {FF * 2, 64};
        const cuuint32_t box[3] = {32, 64, 3};
        make_map(fn, &maps.m[1 + i], d_in[11 + i], 3, dims, strides, box, CU_TENSOR_MAP_SWIZZLE_64B);
    }
    {
        const cuuint64_t dims[2] = {DM, FF}, strides[1] = {DM * 2};
        const cuuint32_t box[2] = {32, 192};
        make_map(fn, &maps.m[3], d_in[13], 2, dims, strides, box, CU_TENSOR_MAP_SWIZZLE_64B);
    }
    {
        const cuuint64_t dims[5] = {DM, 2, 4, 4, L_SEQ}, strides[4] = {16 * DM * 2, 64 * DM * 2, 4 * DM * 2, DM * 2};
        const cuuint32_t box[5] = {16, 2, 4, 4, 1};
        make_map(fn, &maps.m[4], d_out, 5, dims, strides, box, CU_TENSOR_MAP_SWIZZLE_NONE);
    }
    {
        const cuuint64_t dims[5] = {DM, 4, 4, 2, L_SEQ}, strides[4] = {8 * DM * 2, 64 * DM * 2, 4 * DM * 2, DM * 2};
        const cuuint32_t box[5] = {16, 4, 4, 2, 1};
        make_map(fn, &maps.m[6], d_out, 5, dims, strides, box, CU_TENSOR_MAP_SWIZZLE_NONE);
    }
    fused_kernel<<<NCTA, NTHR, SMEM_BYTES>>>(p, maps);
}
```

```cpp
#include <cuda_runtime.h>
#include <cuda_bf16.h>
#include <cuda_fp16.h>
#include <cuda.h>
#include <stdint.h>

#define RESUME 400
#define MDELAY 2000
#define KPOLL 650
#define DPA 7
#define DPB 9
#define RDELAY 900
#define WDELAY 1700
#define WGAP 290
#define NPRE 8
#define DGAP 280
namespace {

constexpr int DM = 576, NST = 128, FF = 4608, L_SEQ = 2048;
constexpr int NCONV = 72, NX = 36, NW = 48, NCTA = 132, NTHR = 512;

struct __align__(128) Scratch {
    unsigned epoch[NCTA * 16];
    uint4 keys[16 * 128];
    uint32_t sel[18 * 64];
    uint16_t gate[L_SEQ];
    uint2 h[288 * 32];
    uint4 kp[DM * 96];
};
__device__ Scratch g_scratch;
#define TFLUSH()
#define TSTAMP(i)
#define TW 12

struct Params {
    const __nv_bfloat16 *Are, *Aim, *Bre, *Bim, *Cre, *Cim, *logdt, *Dskip, *u, *wr, *gatew;
    __nv_bfloat16* out;
    Scratch* s;
    uint32_t zero;
};

__device__ __forceinline__ void give_up() { asm volatile("trap; exit;"); __builtin_unreachable(); }
__device__ __forceinline__ void converged() { __syncwarp(); asm volatile("{ .reg .b32 t; mov.b32 t, 0; movmatrix.sync.aligned.m8n8.trans.b16 t, t; }" ::: "memory"); }
__device__ __forceinline__ bool elect() { uint32_t r; asm volatile("{ .reg .pred p; elect.sync _|p, 0xffffffff; selp.u32 %0, 1, 0, p; }" : "=r"(r)); return r; }
__device__ __forceinline__ uint32_t smem_u32(const void* p) { return (uint32_t)__cvta_generic_to_shared(p); }
__device__ __forceinline__ uint32_t pack_bf16(float lo, float hi) { uint32_t r; asm("cvt.rn.bf16x2.f32 %0, %1, %2;" : "=r"(r) : "f"(hi), "f"(lo)); return r; }
__device__ __forceinline__ uint32_t pack_f16(float lo, float hi) { uint32_t r; asm("cvt.rn.f16x2.f32 %0, %1, %2;" : "=r"(r) : "f"(hi), "f"(lo)); return r; }
__device__ __forceinline__ float bf_lo(uint32_t w) { return __uint_as_float(w << 16); }
__device__ __forceinline__ float bf_hi(uint32_t w) { return __uint_as_float(w & 0xffff0000u); }
__device__ __forceinline__ float rbf(float x) { return bf_lo(pack_bf16(x, 0.f)); }
__device__ __forceinline__ uint32_t badd2(uint32_t a, uint32_t b) { uint32_t r; asm("add.rn.bf16x2 %0, %1, %2;" : "=r"(r) : "r"(a), "r"(b)); return r; }
__device__ __forceinline__ uint32_t bsub2(uint32_t a, uint32_t b) { uint32_t r; asm("sub.rn.bf16x2 %0, %1, %2;" : "=r"(r) : "r"(a), "r"(b)); return r; }
__device__ __forceinline__ uint32_t gmix(uint32_t ng, float ny0, float ny1, uint32_t u) {
    uint32_t r; asm("{ .reg .b32 t; fma.rn.bf16x2 t, %1, %3, %3; fma.rn.bf16x2 %0, %1, %2, t; }" : "=r"(r) : "r"(ng), "r"(pack_bf16(ny0, ny1)), "r"(u)); return r;
}
__device__ __forceinline__ void mma_bf(float (&c)[4], uint32_t a0, uint32_t a1, uint32_t a2, uint32_t a3, uint32_t b0, uint32_t b1) {
    asm("mma.sync.aligned.m16n8k16.row.col.f32.bf16.bf16.f32 {%0,%1,%2,%3}, {%4,%5,%6,%7}, {%8,%9}, {%0,%1,%2,%3};"
        : "+f"(c[0]), "+f"(c[1]), "+f"(c[2]), "+f"(c[3]) : "r"(a0), "r"(a1), "r"(a2), "r"(a3), "r"(b0), "r"(b1));
}
__device__ __forceinline__ void mma_bf8(float (&c)[4], uint32_t a0, uint32_t a1, uint32_t b0) {
    asm("mma.sync.aligned.m16n8k8.row.col.f32.bf16.bf16.f32 {%0,%1,%2,%3}, {%4,%5}, {%6}, {%0,%1,%2,%3};"
        : "+f"(c[0]), "+f"(c[1]), "+f"(c[2]), "+f"(c[3]) : "r"(a0), "r"(a1), "r"(b0));
}
__device__ __forceinline__ void mma_h(float (&c)[4], uint32_t a0, uint32_t a1, uint32_t a2, uint32_t a3, uint32_t b0, uint32_t b1) {
    asm("mma.sync.aligned.m16n8k16.row.col.f32.f16.f16.f32 {%0,%1,%2,%3}, {%4,%5,%6,%7}, {%8,%9}, {%0,%1,%2,%3};"
        : "+f"(c[0]), "+f"(c[1]), "+f"(c[2]), "+f"(c[3]) : "r"(a0), "r"(a1), "r"(a2), "r"(a3), "r"(b0), "r"(b1));
}
__device__ __forceinline__ uint32_t fresh(uint32_t a) { asm volatile("" : "+r"(a) :: "memory"); return a; }
__device__ __forceinline__ uint32_t lds32(uint32_t a) { uint32_t v; asm("ld.shared.u32 %0, [%1];" : "=r"(v) : "r"(a)); return v; }
__device__ __forceinline__ uint2 lds64(uint32_t a) { uint2 v; asm("ld.shared.v2.u32 {%0,%1}, [%2];" : "=r"(v.x), "=r"(v.y) : "r"(a)); return v; }
__device__ __forceinline__ uint4 lds128(uint32_t a) { uint4 v; asm("ld.shared.v4.u32 {%0,%1,%2,%3}, [%4];" : "=r"(v.x), "=r"(v.y), "=r"(v.z), "=r"(v.w) : "r"(a)); return v; }
__device__ __forceinline__ void ldsm4(uint32_t (&r)[4], uint32_t a) {
    asm("ldmatrix.sync.aligned.m8n8.x4.shared.b16 {%0,%1,%2,%3}, [%4];" : "=r"(r[0]), "=r"(r[1]), "=r"(r[2]), "=r"(r[3]) : "r"(a));
}
__device__ __forceinline__ void ldsm4t(uint32_t (&r)[4], uint32_t a) {
    asm("ldmatrix.sync.aligned.m8n8.x4.trans.shared.b16 {%0,%1,%2,%3}, [%4];" : "=r"(r[0]), "=r"(r[1]), "=r"(r[2]), "=r"(r[3]) : "r"(a));
}
__device__ __forceinline__ void sts16(uint32_t a, uint32_t v) { asm volatile("st.shared.u16 [%0], %1;" :: "r"(a), "h"((unsigned short)v) : "memory"); }
__device__ __forceinline__ void sts32(uint32_t a, uint32_t v) { asm volatile("st.shared.u32 [%0], %1;" :: "r"(a), "r"(v) : "memory"); }
__device__ __forceinline__ void sts64(uint32_t a, uint32_t x, uint32_t y) { asm volatile("st.shared.v2.u32 [%0], {%1,%2};" :: "r"(a), "r"(x), "r"(y) : "memory"); }
__device__ __forceinline__ void sts128(uint32_t a, uint32_t x, uint32_t y, uint32_t z, uint32_t w) {
    asm volatile("st.shared.v4.u32 [%0], {%1,%2,%3,%4};" :: "r"(a), "r"(x), "r"(y), "r"(z), "r"(w) : "memory");
}
__device__ __forceinline__ void st_async128(uint32_t a, uint32_t x, uint32_t y, uint32_t z, uint32_t w, uint32_t bar) {
    asm volatile("st.async.weak.shared::cluster.mbarrier::complete_tx::bytes.v4.b32 [%0], {%1,%2,%3,%4}, [%5];" :: "r"(a), "r"(x), "r"(y), "r"(z), "r"(w), "r"(bar) : "memory");
}
__device__ __forceinline__ void mbar_init(uint32_t b, uint32_t cnt) { asm volatile("mbarrier.init.shared::cta.b64 [%0], %1;" :: "r"(b), "r"(cnt) : "memory"); }
__device__ __forceinline__ void mbar_fence() { asm volatile("fence.mbarrier_init.release.cluster;" ::: "memory"); }
__device__ __forceinline__ void mbar_expect(uint32_t b, uint32_t bytes) { asm volatile("mbarrier.arrive.expect_tx.shared::cta.b64 _, [%0], %1;" :: "r"(b), "r"(bytes) : "memory"); }
__device__ __forceinline__ void mbar_arrive(uint32_t b) { asm volatile("mbarrier.arrive.shared::cta.b64 _, [%0];" :: "r"(b) : "memory"); }
__device__ __forceinline__ void mbar_wait(uint32_t b, uint32_t parity = 0) {
    asm volatile("{ .reg .pred p; .reg .u32 n; mov.u32 n, 0;\n"
                 "LW: mbarrier.try_wait.parity.shared::cta.b64 p, [%0], %1; @p bra LD; add.u32 n, n, 1; setp.lt.u32 p, n, 65536; @p bra LW; trap;\n"
                 "LD: }" :: "r"(b), "r"(parity) : "memory");
}
__device__ __forceinline__ void mbar_wait_cluster(uint32_t b) {
    asm volatile("{ .reg .pred p; .reg .u32 n; mov.u32 n, 0;\n"
                 "LW: mbarrier.try_wait.parity.acquire.cluster.shared::cta.b64 p, [%0], 0; @p bra LD; add.u32 n, n, 1; setp.lt.u32 p, n, 65536; @p bra LW; trap;\n"
                 "LD: }" :: "r"(b) : "memory");
}
__device__ __forceinline__ void tma2d(uint32_t dst, const CUtensorMap* m, int c0, int c1, uint32_t bar) {
    asm volatile("cp.async.bulk.tensor.2d.shared::cluster.global.mbarrier::complete_tx::bytes [%0], [%1, {%3, %4}], [%2];"
                 :: "r"(dst), "l"(m), "r"(bar), "r"(c0), "r"(c1) : "memory");
}
__device__ __forceinline__ void tma3d(uint32_t dst, const CUtensorMap* m, int c0, int c1, int c2, uint32_t bar) {
    asm volatile("cp.async.bulk.tensor.3d.shared::cluster.global.mbarrier::complete_tx::bytes [%0], [%1, {%3, %4, %5}], [%2];"
                 :: "r"(dst), "l"(m), "r"(bar), "r"(c0), "r"(c1), "r"(c2) : "memory");
}
__device__ __forceinline__ void tma4d(uint32_t dst, const CUtensorMap* m, int c0, int c1, int c2, int c3, uint32_t bar) {
    asm volatile("cp.async.bulk.tensor.4d.shared::cluster.global.mbarrier::complete_tx::bytes [%0], [%1, {%3, %4, %5, %6}], [%2];"
                 :: "r"(dst), "l"(m), "r"(bar), "r"(c0), "r"(c1), "r"(c2), "r"(c3) : "memory");
}
__device__ __forceinline__ void bulk_g2s(uint32_t dst, const void* src, uint32_t bytes, uint32_t bar) {
    asm volatile("cp.async.bulk.shared::cluster.global.mbarrier::complete_tx::bytes [%0], [%1], %2, [%3];"
                 :: "r"(dst), "l"(src), "r"(bytes), "r"(bar) : "memory");
}
__device__ __forceinline__ uint32_t mapa(uint32_t a, uint32_t rank) { uint32_t r; asm("mapa.shared::cluster.u32 %0, %1, %2;" : "=r"(r) : "r"(a), "r"(rank)); return r; }
__device__ __forceinline__ void prefetch_map(const CUtensorMap* m) { asm volatile("prefetch.tensormap [%0];" :: "l"(m) : "memory"); }
__device__ __forceinline__ void bar_sync(int id, int n) { asm volatile("bar.sync %0, %1;" :: "r"(id), "r"(n) : "memory"); }
__device__ __forceinline__ void bar_arrive(int id, int n) { asm volatile("bar.arrive %0, %1;" :: "r"(id), "r"(n) : "memory"); }
__device__ __forceinline__ uint32_t ldg16_if(bool c, const void* p) { uint32_t v; asm volatile("{ .reg .pred p; setp.ne.u32 p, %2, 0; @p ld.global.nc.u16 %0, [%1]; }" : "=r"(v) : "l"(p), "r"((uint32_t)c)); return v; }
__device__ __forceinline__ uint32_t ldg32_if(bool c, const void* p) { uint32_t v; asm volatile("{ .reg .pred p; setp.ne.u32 p, %2, 0; @p ld.global.nc.u32 %0, [%1]; }" : "=r"(v) : "l"(p), "r"((uint32_t)c)); return v; }
__device__ __forceinline__ uint32_t ld_rlx32(const void* p) { uint32_t v; asm volatile("ld.relaxed.gpu.global.u32 %0, [%1];" : "=r"(v) : "l"(p) : "memory"); return v; }
__device__ __forceinline__ uint4 ld_rlx128(const void* p) {
    uint4 v; asm volatile("ld.relaxed.gpu.global.v4.u32 {%0,%1,%2,%3}, [%4];" : "=r"(v.x), "=r"(v.y), "=r"(v.z), "=r"(v.w) : "l"(p) : "memory"); return v;
}
__device__ __forceinline__ void st_rlx32(void* p, uint32_t v) { asm volatile("st.relaxed.gpu.global.u32 [%0], %1;" :: "l"(p), "r"(v) : "memory"); }
__device__ __forceinline__ void stg128(void* p, uint32_t x, uint32_t y, uint32_t z, uint32_t w) {
    asm volatile("st.global.v4.u32 [%0], {%1,%2,%3,%4};" :: "l"(p), "r"(x), "r"(y), "r"(z), "r"(w) : "memory");
}
__device__ __forceinline__ void next_epoch(const Params& p, unsigned e) { if ((threadIdx.x & 31) == 0) p.s->epoch[blockIdx.x * 16 + (threadIdx.x >> 5)] = e + 1; }
__device__ __forceinline__ void sts128z_if(bool c, uint32_t a) { asm volatile("{ .reg .pred p; setp.ne.u32 p, %1, 0; @p st.shared.v4.u32 [%0], {%2,%2,%2,%2}; }" :: "r"(a), "r"((uint32_t)c), "r"(0) : "memory"); }
__device__ __forceinline__ void stg128z_if(bool c, void* a) { asm volatile("{ .reg .pred p; setp.ne.u32 p, %1, 0; @p st.global.v4.u32 [%0], {%2,%2,%2,%2}; }" :: "l"(a), "r"((uint32_t)c), "r"(0) : "memory"); }
__device__ __forceinline__ unsigned clock32() { unsigned c; asm volatile("mov.u32 %0, %clock;" : "=r"(c) :: "memory"); return c; }
__device__ __forceinline__ void until(unsigned t0, int c) { while ((int)(clock32() - t0) < c) { } }
__device__ __forceinline__ float sigmoidf_(float x) { return __fdividef(1.0f, 1.0f + __expf(-x)); }
__device__ __forceinline__ uint32_t key_tag(unsigned epoch) { return ((epoch & 15u) | 16u) << 11; }
__device__ __forceinline__ int key_row(uint32_t key) { return 2047 - (int)(key & 2047u); }
__device__ __forceinline__ uint32_t wait_sel(const Params& p, int s32, int r8, uint32_t tag, uint32_t k = 0) {
#pragma unroll 1
    for (int it = 0; !__all_sync(0xffffffffu, (k & 0xf800u) == tag); it++) {
        k = ld_rlx32(&p.s->sel[s32 * 64 + r8]);
        if (it > (1 << 20)) give_up();
    }
    return k;
}

struct cplx { float re, im; };
__device__ __forceinline__ cplx csq(cplx a) { cplx r; r.re = a.re * a.re - a.im * a.im; r.im = (a.re * a.im) * 2.f; return r; }
__device__ __forceinline__ cplx cexpk(float ar, float ai, float k) {
    float mag, s, c;
    asm("ex2.approx.ftz.f32 %0, %1;" : "=f"(mag) : "f"(ar * (k * 1.4426950408889634f)));
    const float r = ai * k;
    asm("sin.approx.ftz.f32 %0, %1;" : "=f"(s) : "f"(r));
    asm("cos.approx.ftz.f32 %0, %1;" : "=f"(c) : "f"(r));
    cplx o; o.re = mag * c; o.im = mag * s; return o;
}
struct h2c { uint32_t re, im; };
__device__ __forceinline__ h2c cmul_cd(h2c v, __half2 c, __half2 d) {
    const __half2 r = *(const __half2*)&v.re, i = *(const __half2*)&v.im;
    const __half2 x = __hfma2(__hneg2(i), d, __hmul2(r, c)), y = __hfma2(i, c, __hmul2(r, d));
    h2c o; o.re = *(const uint32_t*)&x; o.im = *(const uint32_t*)&y; return o;
}
__device__ __forceinline__ h2c cmul_s(h2c v, uint32_t s) { const __half2 h = *(const __half2*)&s; return cmul_cd(v, __low2half2(h), __high2half2(h)); }
__device__ __forceinline__ h2c cmul_sc(h2c v, uint32_t s) {
    const __half2 h = *(const __half2*)&s, c = __low2half2(h), d = __high2half2(h), r = *(const __half2*)&v.re, i = *(const __half2*)&v.im;
    const __half2 x = __hfma2(i, d, __hmul2(r, c)), y = __hfma2(__hneg2(r), d, __hmul2(i, c));
    h2c o; o.re = *(const uint32_t*)&x; o.im = *(const uint32_t*)&y; return o;
}
__device__ __forceinline__ h2c cmul_vc(h2c v, uint32_t s) {
    const __half2 h = *(const __half2*)&s, c = __low2half2(h), d = __high2half2(h), r = *(const __half2*)&v.re, i = *(const __half2*)&v.im;
    const __half2 x = __hfma2(i, d, __hmul2(r, c)), y = __hfma2(__hneg2(i), c, __hmul2(r, d));
    h2c o; o.re = *(const uint32_t*)&x; o.im = *(const uint32_t*)&y; return o;
}

constexpr int UT_HALF = 2560, UT_STRIDE = 4736, GT_HALF = 2240;
__device__ __forceinline__ uint32_t swz(uint32_t x, int c) { return x ^ (((x >> 2) & 64) ^ (64 * (c & 1) + 8 * (c & 6))); }
__device__ __forceinline__ int col(int n) { return (n >> 1) + 4 * (n & 1); }
constexpr int KT_T = 542, KT_C = 552, KT_D = 645, KT_BYTES = 720 * 4;
constexpr int VC_OFF = 80, VE_BASE = 1616;
constexpr int V_STRIDE = (1616 + 1024) * 4 + 80;
constexpr int KG_STAGE = 5248;
constexpr int Y_CS = 2080, Y_RS = 8 * Y_CS + 64;

constexpr int SC_RT = 0;
constexpr int SC_UT = 33408;
constexpr int SC_KG = SC_UT + 8 * UT_STRIDE;
constexpr int SC_KT = SC_KG + 8 * KG_STAGE;
constexpr int SC_GT = SC_KT + 8 * KT_BYTES;
constexpr int SC_V = SC_GT + 4448;
constexpr int SC_MISC = SC_V + 8 * V_STRIDE;
static_assert(V_STRIDE % 128 == 16 && 2 * Y_RS <= SC_UT && SC_UT % 128 == 0 && SC_KG % 128 == 0, "layout");
static_assert(SC_MISC % 16 == 0 && SC_MISC + 512 <= 232192, "layout");

__device__ __forceinline__ void window_task(uint32_t s0, uint32_t s1, uint32_t d0, uint32_t d1, int k) {
    float S[51], s = 0.f;
    uint32_t w[28];
#pragma unroll
    for (int i = 0; i < 7; i++) {
        const uint4 v = lds128(((i < 3 ? s0 : s1) ^ 8 * ((i + 1) & 2)) + ((i & 1) ? 0 : UT_HALF));
        w[4 * i] = v.x; w[4 * i + 1] = v.y; w[4 * i + 2] = v.z; w[4 * i + 3] = v.w;
    }
    auto sums = [&](int lo, int hi) {
#pragma unroll
        for (int i = lo; i < hi; i++) { const float x = (i & 1) ? bf_hi(w[i >> 1]) : bf_lo(w[i >> 1]); s = i > 3 ? s + x : x; S[i] = s; }
    };
    auto put = [&](int off, int b, int o0, int o1, int o2) {
        auto v = [&](int i) { i += 16 * b; return pack_bf16(S[o0 + i] - S[o1 + i], S[o1 + i] - S[o2 + i]); };
#pragma unroll
        for (int i = 0; i < 8; i += 2) sts128((i & 4 ? d1 : d0) + 4 * off + 64 * b + 8 * (i & 2), v(i), v(i + 8), v(i + 1), v(i + 9));
    };
    S[2] = 0.f;
    sums(3, 26); put(VC_OFF - 16, 0, 10, 5, 2);
    if (k == 12) return;
    sums(26, 42); put(VC_OFF - 16, 1, 10, 5, 2);
    if (k < 8) { put(VE_BASE, 0, 19, 12, 3); sums(42, 51); put(VE_BASE, 1, 19, 12, 3); }
}

template <class F, class G>
__device__ __forceinline__ void kgen(const uint32_t (&q)[8], uint32_t sb, int half, uint32_t stage, uint32_t pstage, int barid, int lane, uint32_t (&w)[12], F shadow, G clear) {
    const int t = lane & 3, mi = lane >> 3, r8 = lane & 7;
    {
        const uint32_t pAr = q[0], pAi = q[1], pBr = q[2], pBi = q[3], pCr = q[4], pCi = q[5], pDt = q[6], pD = q[7];
        const uint32_t wb = fresh(stage + lane * 16), za = fresh(stage + 5120 + ((lane >> 1) & 3) * 16 + mi * 4 + (lane & 1) * 2), zr = fresh(stage + 5120 + t * 16);
        const uint32_t oB = fresh(stage + 2048 + mi * 512 + r8 * 16), oC = fresh(stage + 4096 + (mi & 1) * 512 + (mi >> 1) * 128 + r8 * 16);
        float acc[6][4];
#pragma unroll
        for (int a = 0; a < 6; a++) { acc[a][0] = acc[a][1] = acc[a][2] = acc[a][3] = 0.f; asm volatile("" : "+f"(acc[a][0]), "+f"(acc[a][1]), "+f"(acc[a][2]), "+f"(acc[a][3])); }
        shadow();
        sts32(zr, clock32());
        const float dt = rbf(__expf(bf_lo(pDt)));
        float ar = dt * bf_lo(pAr), ai = dt * bf_lo(pAi), ar1 = dt * bf_hi(pAr), ai1 = dt * bf_hi(pAi);
        float wr, wi, wr1, wi1;
        { const float br = dt * bf_lo(pBr), bi = dt * bf_lo(pBi), cr = bf_lo(pCr), ci = bf_lo(pCi); wr = cr * br - ci * bi; wi = cr * bi + ci * br; }
        { const float br = dt * bf_hi(pBr), bi = dt * bf_hi(pBi), cr = bf_hi(pCr), ci = bf_hi(pCi); wr1 = cr * br - ci * bi; wi1 = cr * bi + ci * br; }
        const uint32_t ex = max(__reduce_max_sync(0xffffffffu, __float_as_uint(fmaxf(fmaxf(fabsf(wr), fabsf(wi)), fmaxf(fabsf(wr1), fabsf(wi1))))) >> 23, 14u);
        const float scl = __uint_as_float((267u - ex) << 23);
        uint32_t W = pack_f16(wr * scl, wi * -scl);
        const uint32_t W1 = pack_f16(wr1 * scl, wi1 * -scl);
        if (threadIdx.x < 32) TSTAMP(20);
        clear();

#pragma unroll 1
        for (int r = 0; r < 2; r++) {
            const cplx z1 = cexpk(ar, ai, 1.f), z64 = cexpk(ar, ai, 64.f);
            const cplx z2 = csq(z1), z4 = csq(z2), z8 = csq(z4), z16 = csq(z8), z32 = csq(z16);
            const cplx z128 = csq(z64), z256 = csq(z128), z512 = csq(z256);
            auto put = [&](int grp, h2c a, h2c b, h2c c, h2c d) { sts128(wb + grp * 1024, a.re, b.re, c.re, d.re); sts128(wb + grp * 1024 + 512, a.im, b.im, c.im, d.im); };
            {
                const uint32_t s4 = pack_f16(z4.re, z4.im), s256 = pack_f16(z256.re, z256.im), s512 = pack_f16(z512.re, z512.im);
                auto mix = [](h2c a, h2c b, uint32_t sel) { return h2c{__byte_perm(a.re, b.re, sel), __byte_perm(a.im, b.im, sel)}; };
                const h2c c10 = cmul_vc(h2c{pack_f16(z1.re, 1.f), pack_f16(z1.im, 0.f)}, W), c32 = cmul_sc(c10, pack_f16(z2.re, z2.im)), c54 = cmul_sc(c10, s4);
                put(2, c10, c32, c54, cmul_sc(c32, s4));
                const h2c d20 = cmul_sc(mix(c32, c10, 0x7632), s256), e04 = cmul_sc(mix(c10, c54, 0x7632), s512), f04 = cmul_sc(e04, s256);
                put(3, d20, cmul_sc(d20, s4), e04, f04);
                const h2c ef = mix(e04, f04, 0x5410), gh = cmul_sc(ef, s512), g8 = cmul_sc(gh, pack_f16(z8.re, z8.im));
                put(4, g8, cmul_sc(g8, s512), gh, ef);
            }
            {
                const uint32_t s32 = pack_f16(z32.re, z32.im), s64 = pack_f16(z64.re, z64.im), s128 = pack_f16(z128.re, z128.im);
                const h2c p0 = {pack_f16(1.f, z8.re), pack_f16(0.f, z8.im)}, p1 = cmul_s(p0, pack_f16(z16.re, z16.im)), p2 = cmul_s(p0, s32), p3 = cmul_s(p1, s32);
                put(0, p0, p1, p2, p3);
                sts16(za - 4096, s64); sts16(za - 4032, s64 >> 16);
                sts16(za, s128); sts16(za + 64, s128 >> 16);
            }
            __syncwarp();
            {
                const uint32_t aB = fresh(oB), aC = fresh(oC), aZ = fresh(zr);
                const uint4 zc = lds128(aZ), zd = lds128(aZ + 64);
                const uint32_t zcs[4] = {zc.x, zc.y, zc.z, zc.w}, zds[4] = {zd.x, zd.y, zd.z, zd.w};
                const uint4 yc = lds128(aZ - 4096), yd = lds128(aZ - 4032);
                const uint32_t ycs[4] = {yc.x, yc.y, yc.z, yc.w}, yds[4] = {yd.x, yd.y, yd.z, yd.w};
                uint32_t c[4];
#pragma unroll
                for (int k = 0; k < 4; k++) {
                    uint32_t a[4], b[4];
                    for (int e = 0; e < 2; e++) asm("ldmatrix.sync.aligned.m8n8.x1.trans.shared.b16 {%0}, [%1];" : "=r"(a[2 * e]) : "r"(aB - 2048 + 128 * k + 512 * e));
                    const h2c a1 = cmul_cd(h2c{a[0], a[2]}, *(const __half2*)&ycs[k], *(const __half2*)&yds[k]);
                    a[1] = a1.re; a[3] = a1.im;
                    ldsm4t(b, aB + 128 * k);
                    if (!(k & 1)) ldsm4t(c, aC + 128 * k);
                    const h2c x = cmul_cd(h2c{a[0], a[2]}, *(const __half2*)&zcs[k], *(const __half2*)&zds[k]), y = cmul_cd(h2c{a[1], a[3]}, *(const __half2*)&zcs[k], *(const __half2*)&zds[k]);
                    mma_h(acc[0], a[0], a[1], a[2], a[3], b[0], b[1]);
                    mma_h(acc[1], a[0], a[1], a[2], a[3], b[2], b[3]);
                    mma_h(acc[2], a[0], a[1], a[2], a[3], c[2 * (k & 1)], c[2 * (k & 1) + 1]);
                    mma_h(acc[3], x.re, y.re, x.im, y.im, b[0], b[1]);
                    mma_h(acc[4], x.re, y.re, x.im, y.im, b[2], b[3]);
                    mma_h(acc[5], x.re, y.re, x.im, y.im, c[2 * (k & 1)], c[2 * (k & 1) + 1]);
                }
                asm volatile("" :: "f"(acc[0][0]), "f"(acc[1][0]), "f"(acc[2][0]), "f"(acc[3][0]), "f"(acc[4][0]), "f"(acc[5][0]) : "memory");
            }
            __syncwarp();
            ar = ar1; ai = ai1; W = W1;
        }
        if (threadIdx.x < 32) TSTAMP(21);
        const float i0 = __uint_as_float((ex + 243u) << 23);
        if (half) {
#pragma unroll
            for (int a = 0; a < 6; a++) { acc[a][0] *= i0; acc[a][1] *= i0; acc[a][2] *= i0; acc[a][3] *= i0; }
            if (lane == 0) acc[0][1] -= bf_lo(pD);
#pragma unroll
            for (int a = 0; a < 6; a++) sts128(wb + a * 512, __float_as_uint(acc[a][0]), __float_as_uint(acc[a][1]), __float_as_uint(acc[a][2]), __float_as_uint(acc[a][3]));
            bar_arrive(barid, 64);
        } else {
            bar_sync(barid, 64);
            const uint32_t src = fresh(pstage);
#pragma unroll
            for (int a = 0; a < 6; a++) {
                const uint4 y = lds128(src + lane * 16 + a * 512);
                auto sum = [&](uint32_t x, float c) { return fmaf(c, i0, __uint_as_float(x)); };
                w[4 * (a % 3) + 2 * (a / 3)] = pack_bf16(sum(y.x, acc[a][0]), sum(y.y, acc[a][1]));
                w[4 * (a % 3) + 2 * (a / 3) + 1] = pack_bf16(sum(y.z, acc[a][2]), sum(y.w, acc[a][3]));
            }
            const uint32_t x0 = __shfl_up_sync(0xffffffffu, w[10], 2), x1 = __shfl_up_sync(0xffffffffu, w[11], 2);
            w[10] = w[8];
            if (t >= 2) { w[8] = x0; w[9] = x1; }
        }
    }
}

enum { BC_AUX = 0, BC_U = 5  , BC_Y = 13   };

__device__ __forceinline__ void fetch_gates(const Params& p, int i, int lane, unsigned epoch, uint32_t dst) {
    const uint32_t par = (epoch & 1) ? 0x80008000u : 0u;
    uint4 v;
#pragma unroll 1
    for (int it = 0;; it++) {
        v = ld_rlx128(p.s->gate + 256 * i + 8 * lane);
        v.x ^= par; v.y ^= par; v.z ^= par; v.w ^= par;
        if (__all_sync(0xffffffffu, (v.x & v.y & v.z & v.w & 0x80008000u) == 0x80008000u)) break;
        if (it > (1 << 20)) give_up();
    }
    sts128(dst, v.x, v.y, v.z, v.w);
}
__device__ __forceinline__ void store_rows(const CUtensorMap* m, uint32_t src, int col, int row) {
    asm volatile("cp.async.bulk.tensor.5d.global.shared::cta.bulk_group [%0, {%2, %3, %3, %3, %4}], [%1];" :: "l"(m), "r"(src), "r"(col), "r"(0), "r"(row) : "memory");
}

__device__ __forceinline__ void store_or_add(void* o, const uint32_t (&y)[4], uint32_t add) {
    asm volatile("{ .reg .pred p; setp.ne.u32 p, %5, 0; @!p st.global.v4.u32 [%0], {%1,%2,%3,%4}; @p red.relaxed.gpu.global.add.noftz.v4.bf16x2 [%0], {%1,%2,%3,%4}; }"
                 :: "l"(o), "r"(y[0]), "r"(y[1]), "r"(y[2]), "r"(y[3]), "r"(add) : "memory");
}

__device__ __forceinline__ void conv_aux(const Params& p, const CUtensorMap* mU, uint32_t sb, int aw, int lane, int bid, unsigned epoch) {
    const int g = lane >> 2, t = lane & 3, mi = lane >> 3, r8 = lane & 7;
    const int rank = bid & 1, slab = bid >> 1;
    const uint32_t bar_y = sb + SC_MISC, bar_u = bar_y  , bar_v = bar_y + 8, bar_box = bar_y + 64 + 8 * aw, s_bm = bar_y + 128;
    if (elect()) {
        mbar_init(bar_box, 1); mbar_fence();
        mbar_expect(bar_box, 4096);
        tma4d(sb + SC_RT + 4096 * aw, mU, 16 * slab, 0, 0, 16 * rank + 2 * aw, bar_box);
        mbar_init(bar_y + 8 * aw, aw == 1 ? 8 : 1);
        if (aw == 1) mbar_init(bar_y + 384, 1);
        mbar_fence();
        if (aw != 1) mbar_expect(bar_y + 8 * aw, aw ? 4096 : 16384);
    }
    __syncwarp();
    asm volatile("barrier.cluster.arrive.relaxed.aligned;" ::: "memory");
    asm volatile("setmaxnreg.dec.sync.aligned.u32 88;");
    sts128(sb + (lane < 16 ? SC_UT + aw * UT_STRIDE + mi * (UT_HALF - 128) : SC_V - 256 + aw * V_STRIDE) + lane * 16, 0, 0, 0, 0);
    if (lane < 16) sts128(s_bm + lane * 16, 0, 0, 0, 0);
    {
        const uint32_t dst = sb + SC_UT + g * UT_STRIDE + swz((8 + 64 * rank + 8 * aw + t) * 16, g);
        const uint32_t rdst = mapa(dst, rank ^ 1), rbar = mapa(bar_u, rank ^ 1);
        asm volatile("barrier.cluster.wait.acquire.aligned;" ::: "memory");
        mbar_wait(bar_box);
        if (aw == 0) TSTAMP(1);
        const uint32_t src = fresh(sb + SC_RT) + aw * 4096 + (8 * mi + 4 * (r8 & 1) + (r8 >> 1)) * 32 + ((rank ^ (r8 & 1)) << 4);
        uint32_t x[8][4];
#pragma unroll
        for (int i = 0; i < 4; i++) { ldsm4t(x[i], src + 1024 * i); ldsm4t(x[4 + i], (src ^ 16) + 1024 * i); }
        asm volatile("" :: "r"(x[0][0]), "r"(x[1][0]), "r"(x[2][0]), "r"(x[3][0]) : "memory");
#pragma unroll
        for (int i = 0; i < 4; i++) st_async128((rdst ^ 32 * (i & 2)) + (i & 1) * UT_HALF, x[4 + i][0], x[4 + i][1], x[4 + i][2], x[4 + i][3], rbar);
#pragma unroll
        for (int i = 0; i < 4; i++) sts128((dst ^ 32 * (i & 2)) + (i & 1) * UT_HALF, x[i][0], x[i][1], x[i][2], x[i][3]);
    }
    bar_sync(BC_AUX, 256);
    mbar_wait_cluster(bar_u);
    if (aw == 0) TSTAMP(2);
    if (aw == 6 && elect()) mbar_arrive(bar_y + 384);
    if (aw < 4) bar_sync(BC_U + aw, 64);
    if (aw == 0) TSTAMP(3);
    {
        const uint32_t ws = fresh(sb + SC_UT) + r8 * UT_STRIDE, wd = sb + SC_V + r8 * V_STRIDE;
#pragma unroll 1
        for (int k = aw; k < 13; k += 8) {
            const int a = 8 * k + (k < 12 ? g & 6 : 0);
            const uint32_t d = wd + 64 * a, sw = 16 * (a & 2);
            window_task(ws + swz(16 * a + 96, r8), ws + swz(16 * a + 128, r8), d + sw, d + (sw ^ 32), k);
            if ((k & 12) == 4) bar_arrive(BC_U + k - 4, 64);
        }
    }
    if (aw == 0) TSTAMP(9);
    {
        if (aw >= 2) fetch_gates(p, aw, lane, epoch, sb + SC_GT + (lane & 1) * GT_HALF + (8 + 16 * aw + (lane >> 1)) * 16);
        __syncwarp();
        if (elect()) { mbar_arrive(bar_v); prefetch_map(mU + 4); p.s->epoch[fresh(bid) * 16 + aw + 8] = epoch + 1; }
        if (aw == 0) TSTAMP(4);
        if (aw == 7) {
            const int row = key_row(wait_sel(p, slab >> 1, r8, key_tag(epoch)));
            if (lane < 8) asm volatile("red.shared.or.b32 [%0], %1;" :: "r"(s_bm + (row >> 5) * 4), "r"(1u << (row & 31)) : "memory");
            TSTAMP(10);
        }
        bar_sync(BC_AUX, 256);
        const uint32_t src = sb + SC_RT + ((r8 >> 1) & 1) * Y_RS + (2 * mi + (r8 & 1)) * Y_CS + (2 * aw + (r8 >> 2)) * 16;
        const int rb = 64 * (aw & 4) + 32 * (aw & 1) + ((aw >> 1) & 1) + 2 * rank, row0 = rb + 128 * (g >> 2) + 16 * (t >> 1) + 64 * (g & 1) + 8 * ((g >> 1) & 1);
        __nv_bfloat16* outp = p.out + (size_t)row0 * DM + 16 * slab + 8 * (t & 1);
        const uint32_t stg = sb + SC_KG + 4096 * aw, so = (g & 2) * 256 + (g >> 2) * 128 + r8 * 16;
#pragma unroll 1
        for (int s = 1; s < 4; s++) {
            const uint32_t bm = lds32(fresh(s_bm) + (16 * s + (row0 >> 5)) * 4) >> (row0 & 31);
            const bool routed = __any_sync(0xffffffffu, bm & 0x11u);
            if ((aw & 3) == s) mbar_wait_cluster(bar_y + 16 * s + 2 * (aw & 4));
            bar_sync(BC_Y + (aw >> 2), 128);
            const uint32_t sf = fresh(src) + 512 * s;
            uint32_t y[2][4];
            ldsm4t(y[0], sf); ldsm4t(y[1], sf + 256);
            if (routed) {
#pragma unroll
                for (int k = 0; k < 2; k++) store_or_add(outp + (size_t)(512 * s + 4 * k) * DM, y[k], bm & (1u << (4 * k)));
            } else {
                sts128(stg + so + 1024 * s, y[0][0], y[0][1], y[0][2], y[0][3]); sts128(stg + so + 1024 * s + 256, y[1][0], y[1][1], y[1][2], y[1][3]);
                asm volatile("fence.proxy.async.shared::cta;" ::: "memory");
                __syncwarp();
                if (elect()) store_rows(mU + 4, stg + 1024 * s, 16 * slab, 512 * s + rb);
            }
            if (aw == 4) TSTAMP(16 + s);
            if (aw == 0) TSTAMP(16);
        }
        if (elect()) { asm volatile("cp.async.bulk.commit_group;" ::: "memory"); asm volatile("cp.async.bulk.wait_group.read 0;" ::: "memory"); }
        if (aw == 4) TFLUSH();
    }
}

__device__ __forceinline__ uint32_t k_tag(unsigned epoch) { return epoch & 1 ? 0x10000u : 1u; }
__device__ __forceinline__ void publish_k(uint4* kp, int lane, bool all, const uint32_t (&w)[12], unsigned epoch, uint64_t (&v)[4]) {
    auto tag = [&](uint32_t x) { return (x & 0xfffefffeu) | k_tag(epoch); };
#pragma unroll
    for (int i = 0; i < 2; i++) {
        v[2 * i] = w[4 * i] | (uint64_t)w[4 * i + 1] << 32; v[2 * i + 1] = w[4 * i + 2] | (uint64_t)tag(w[4 * i + 3]) << 32;
        asm volatile("st.relaxed.gpu.global.v2.u64 [%0], {%1,%2};" :: "l"(kp + 32 * i), "l"(v[2 * i]), "l"(v[2 * i + 1]));
    }
    asm volatile("{ .reg .pred p, q; setp.ne.u32 p, %6, 0; setp.lt.and.s32 q, %5, 4, p;\n"
                 "@p st.relaxed.gpu.global.v2.u32 [%0 + 1024], {%1,%2}; @q st.relaxed.gpu.global.v2.u32 [%0 + 1280], {%3,%4}; }"
                 :: "l"((uint2*)kp - lane), "r"(w[8]), "r"(tag(w[9])), "r"(w[10]), "r"(k_tag(epoch)), "r"(lane), "r"((uint32_t)all));
}
template <bool FULL>
__device__ __forceinline__ void k_tables(uint32_t kt, int lane, const uint32_t (&w)[12]) {
    const int g = lane >> 2, t = lane & 3, mi = lane >> 3, r8 = lane & 7;
    uint32_t x3 = w[7], re[4], rx[4];
#pragma unroll
    for (int i = 0; i < 4; i++) {
        re[i] = __shfl_sync(0xffffffffu, w[i], lane + 31);
        rx[i] = __shfl_sync(0xffffffffu, w[4 + i], lane + (i == 0 && lane == 29 ? 5 : 1 + 2 * t));
    }
    if (FULL) {
        asm volatile("stmatrix.sync.aligned.m8n8.x2.trans.shared.b16 [%0], {%1,%2};" :: "r"(kt + (KT_D + 7) * 4 + 64 * t + 16 * (mi & 1) + 8 * (r8 & 4)), "r"(w[8]), "r"(w[9]) : "memory");
        if (lane == 2) {
            sts32(kt + (KT_C + 78) * 4, w[10] & 0xffffu);
            sts128(kt + (KT_T + 2) * 4, 0, w[10] & 0xffffu, __byte_perm(w[10], 0, 0x1010), w[10] << 16);
        }
        if (lane == 29) x3 = bsub2(x3, rx[0] & 0xffffu);
    }
#pragma unroll
    for (int i = 0; i < 4; i++) {
        sts64(kt + (16 + 64 * i) * 4 + 8 * lane, __byte_perm(w[i], lane ? re[i] : i ? re[i - 1] : 0, 0x5432), w[i]);
        const uint32_t x = i < 3 ? w[4 + i] : x3, aa = __byte_perm(x, 0, 0x3232);
        if (t < 2) sts128(kt + (272 + 64 * i + 8 * g + 4 * t) * 4, i == 0 && lane == 0 ? __byte_perm(x, re[3], 0x5432) : aa, aa, x,
                          __byte_perm(lane != 29 ? rx[i] : i < 3 ? rx[(i + 1) & 3] : FULL ? 0 : rx[0] << 16, x, 0x5432));
        else if (FULL) sts32(kt + (KT_C - 50 + 8 * i + 32 * t + g) * 4, x);
    }
}

__device__ __forceinline__ void conv_main(const Params& p, uint32_t sb, int warp, int lane0, int bid, unsigned epoch, uint32_t (&w)[12]) {
    asm volatile("setmaxnreg.inc.sync.aligned.u32 168;");
    const int lane = __shfl_sync(0xffffffffu, lane0, lane0);
    const int g = lane >> 2, t = lane & 3, mi = lane >> 3, r8 = lane & 7;
    const int rank = bid & 1;
    const uint32_t bar_y = sb + SC_MISC, bar_v = bar_y + 8;
    next_epoch(p, epoch);
    asm volatile("barrier.cluster.wait.acquire.aligned;" ::: "memory");
    if (warp >= 4) {
        mbar_wait(bar_y + 384);
        if (KPOLL) until(clock32(), KPOLL);
        const uint4* src = p.s->kp + (8 * bid + warp) * 96 + lane0;
#pragma unroll 1
        for (int it = 0;; it++) {
#pragma unroll
            for (int i = 0; i < 2; i++) { const uint4 v = ld_rlx128(src + 32 * i); w[4 * i] = v.x; w[4 * i + 1] = v.y; w[4 * i + 2] = v.z; w[4 * i + 3] = v.w; }
            asm volatile("ld.relaxed.gpu.global.v2.u32 {%0,%1}, [%2 + 1024];" : "=r"(w[8]), "=r"(w[9]) : "l"((const uint2*)src - lane0) : "memory");
            asm volatile("ld.relaxed.gpu.global.v2.u32 {%0,%1}, [%2 + 1296];" : "=r"(w[10]), "=r"(w[11]) : "l"(src - lane0) : "memory");
            const bool ok = __all_sync(0xffffffffu, w[3] & w[7] & w[9] & w[11] & k_tag(epoch));
            if (ok) break;
            if (it > (1 << 20)) give_up();
        }
    }
    if ((warp & 3) == 0) TSTAMP(5 + (warp >> 2));
    k_tables<true>(sb + SC_KT + warp * KT_BYTES, lane0, w);
    mbar_wait(bar_y + 384);
    __syncwarp();
    if ((warp & 3) == 0) TSTAMP(7 + (warp >> 2));
    {
        const uint32_t ut = fresh(sb + SC_UT) + warp * UT_STRIDE, kt = fresh(sb + SC_KT) + warp * KT_BYTES;
        auto dup = [&](uint32_t v) { return v ^ p.zero; };
        auto frag = [&](uint32_t (&a)[4], uint32_t x) { a[0] = lds32(x); a[1] = lds32(x + 32); a[2] = lds32(x - 32); a[3] = dup(a[0]); };
        const uint32_t kb = kt + (16 + g - 2 * t) * 4;
        float acc[16][4];
        {
            float y[12][4], M[6][4];
#pragma unroll
            for (int i = 0; i < 12; i++) { y[i][0] = y[i][1] = y[i][2] = y[i][3] = 0.f; M[i >> 1][0] = M[i >> 1][1] = M[i >> 1][2] = M[i >> 1][3] = 0.f; }
            uint32_t U[10][4], a1[4], ad[4], R = (mi & 1) * UT_HALF + (8 + (r8 >> 1) + 48 * (r8 & 1)) * 16 + 64 * (mi >> 1);
            auto places = [&] { ad[0] = swz(R, warp); ad[1] = swz(R + 128, warp); ad[2] = ad[0] ^ 64; ad[3] = ad[1] ^ 64; };
            auto ldu = [&](int k) { ldsm4(U[k], ut + ad[k & 3] + 256 * (k >> 1)); };
            places();
            frag(a1, kb + 2048);
#pragma unroll
            for (int k = 0; k < 7; k++) ldu(k);
#pragma unroll
            for (int i = 0; i < 12; i++) mma_bf(y[i], a1[0], a1[1], a1[2], a1[3], U[i >> 1][2 * (i & 1)], U[i >> 1][2 * (i & 1) + 1]);
            frag(a1, kb + 1792);
            __syncwarp();
#pragma unroll 1
            for (uint32_t ko = 0; ko != 256;) {
                ko = fresh(ko);
                const uint32_t kp = kb + ko;
                ko += 64;
                uint32_t se[10][2], so[10][2], ue[10][2];
                auto sums = [&](int k) {
#pragma unroll
                    for (int e = 0; e < 2; e++) { ue[k][e] = U[k][e]; se[k][e] = badd2(U[k][e], U[k - 1][2 + e]); so[k][e] = badd2(U[k][e], U[k][2 + e]); }
                };
#pragma unroll
                for (int k = 1; k < 6; k++) sums(k);
#pragma unroll
                for (int m = 3; m >= 0; m--) {
                    uint32_t a0[4];
                    frag(a0, kp + 512 * m);
                    sums(9 - m);
                    if (m) ldu(10 - m); else { R -= 16; places(); }
#pragma unroll
                    for (int i = 0; i < 6; i++) mma_bf(y[2 * i], a1[0], a1[1], a1[2], a1[3], se[i - m + 4][0], se[i - m + 4][1]);
#pragma unroll
                    for (int e = 0; e < 4; e++) a1[e] = bsub2(a0[e], a1[e]);
#pragma unroll
                    for (int i = 0; i < 6; i++) { mma_bf(M[i], a1[0], a1[1], a1[2], a1[3], ue[i - m + 4][0], ue[i - m + 4][1]); if (!m) ldu(i); }
                    frag(a1, m ? kp + 512 * m - 256 : kp + 1792 + 64);
                    if (!m) ldu(6);
#pragma unroll
                    for (int i = 0; i < 6; i++) mma_bf(y[2 * i + 1], a0[0], a0[1], a0[2], a0[3], so[i - m + 4][0], so[i - m + 4][1]);
                }
            }
#pragma unroll
            for (int i = 0; i < 6; i++)
#pragma unroll
                for (int c = 0; c < 4; c++) { acc[4 + i + 6 * (c & 1)][c & 2] = y[2 * i][c] + M[i][c]; acc[4 + i + 6 * (c & 1)][c | 1] = y[2 * i + 1][c] - M[i][c]; }
        }
        const uint32_t lo = (8 + col(r8)) * 16 + (mi >> 1) * 128, ua = fresh(ut) + (mi & 1) * UT_HALF, u1[2] = {ua + swz(lo, warp), ua + (swz(lo, warp) ^ 64)};
        {
            uint32_t e[4];
            frag(e, kb + (KT_T - 16) * 4);
            const uint32_t f0 = dup(e[1]), f1 = lds32(kb + KT_T * 4), uo = fresh(ut) + UT_HALF + swz((7 + 8 * mi + col(r8)) * 16, warp);
#pragma unroll
            for (int i = 0; i < 4; i++) {
                uint32_t b[4];
                if (i < 2) {
                    ldsm4(b, uo + 512 * i);
#pragma unroll
                    for (int k = 0; k < 4; k++) mma_bf8(acc[8 + 4 * i + k], f0, f1, b[k]);
                }
                ldsm4(b, u1[i & 1] + 256 * i);
                mma_bf(acc[2 * i + 8], e[0], e[1], e[2], e[3], b[0], b[1]); mma_bf(acc[2 * i + 9], e[0], e[1], e[2], e[3], b[2], b[3]);
            }
        }
        if ((warp & 3) == 0) TSTAMP(11 + (warp >> 2));
        mbar_wait(bar_v);
        const uint32_t vt = fresh(sb + SC_V) + warp * V_STRIDE;
        const uint32_t g1 = fresh(sb + SC_GT) + (mi & 1) * GT_HALF + lo;
        const uint32_t ydst = mapa(sb + SC_RT + rank * Y_RS + warp * Y_CS + (lane & 23) * 16, mi & 1), ybr = mapa(bar_y, mi & 1);
        uint32_t ug[2][2][4];
        auto ld_ug = [&](int i) { ldsm4t(ug[i & 1][0], u1[i & 1] + 256 * i); ldsm4t(ug[i & 1][1], g1 + 256 * i); };
        auto ship = [&](int i) {
            const uint32_t (&u)[4] = ug[i & 1][0], (&gg)[4] = ug[i & 1][1];
            const uint32_t y0 = gmix(gg[0], acc[2 * i][0], acc[2 * i][1], u[0]), y1 = gmix(gg[1], acc[2 * i][2], acc[2 * i][3], u[1]);
            const uint32_t y2 = gmix(gg[2], acc[2 * i + 1][0], acc[2 * i + 1][1], u[2]), y3 = gmix(gg[3], acc[2 * i + 1][2], acc[2 * i + 1][3], u[3]);
            st_async128(ydst + 512 * (i >> 1) + 128 * (i & 1), y0, y1, y2, y3, ybr + 8 * i);
        };
        const uint32_t VD = vt + (VC_OFF - 400 - 16 * t) * 4 + (8 * g ^ 16 * (-t & 2)), VD2 = vt + (VC_OFF - 415 - 16 * t) * 4 + (8 * g ^ 16 * (~t & 2));
        uint2 bd[10];
        uint32_t x[2][4][4];
        auto ld4 = [&](uint32_t (&v)[4], int dl) { const uint2 w = lds64(VD + 256 * dl); v[0] = w.x; v[1] = w.y; v[2] = lds32(VD2 + 256 * dl); v[3] = dup(w.x); };
        auto mm4 = [&](const uint32_t (&v)[4], int dl) {
#pragma unroll
            for (int s = dl & 1; s < 10; s += 2) if ((dl + s) / 2 >= 4 && (dl + s) / 2 < 16) mma_bf(acc[(dl + s) / 2], v[0], v[1], v[2], v[3], bd[s].x, bd[s].y);
        };
        const uint32_t KE = kt + (KT_D + col(g) + t) * 4, VE = vt + (VE_BASE - 912 - 16 * t) * 4 + (8 * g ^ 16 * (~t & 2));
        uint32_t b0[8], b1[8];
        auto ld8 = [&](uint32_t (&v)[4], int dl) { const uint2 w = lds64(VE + 512 * dl), z = lds64(VE + 512 * dl - 256); v[0] = w.x; v[1] = w.y; v[2] = z.x; v[3] = z.y; };
        auto mm8 = [&](const uint32_t (&v)[4], int dl, int lo, int hi) {
#pragma unroll
            for (int s = 0; s < 8; s++) if (dl + s >= lo && dl + s < hi) mma_bf(acc[dl + s], v[0], v[1], v[2], v[3], b0[s], b1[s]);
        };
        ld4(x[0][0], 6);
#pragma unroll
        for (int s = 0; s < 10; s++) bd[s] = lds64(kt + (KT_C + 2 * col(g) + 2 * t + 8 * s) * 4);
        mm4(x[0][0], 6);
        uint32_t e[8][4];
#pragma unroll
        for (int k = 1; k < 6; k++) {
#pragma unroll
            for (int j = 0; j < 4; j++) ld4(x[k & 1][j], 4 * k + 3 + j);
            ld_ug(k + 1);
            if (k == 2) {
#pragma unroll
                for (int s = 0; s < 8; s++) { b0[s] = lds32(KE + 32 * s); b1[s] = lds32(KE + 32 * s + 16); }
            }
            if (k > 1) ship(k);
#pragma unroll
            for (int j = 0; j < 4; j++) {
                mm4(x[k & 1][j], 4 * k + 3 + j);
                if (k == 2) { ld8(e[j], 8 + j); mm8(e[j], 8 + j, 8, 12); }
                if (k == 4) mm8(e[j], 8 + j, 12, 14);
                if (k == 5 && j < 2) { ld8(e[4 + j], 12 + j); mm8(e[4 + j], 12 + j, 12, 14); }
            }
        }
        ld_ug(7);
        {
            float (&q0)[4] = acc[0], (&q1)[4] = acc[1];
#pragma unroll
            for (int c = 0; c < 4; c++) q0[c] = q1[c] = 0.f;
            auto m8 = [&](float (&c)[4], int T, int j) { mma_bf(c, e[j][0], e[j][1], e[j][2], e[j][3], b0[T - 8 - j], b1[T - 8 - j]); };
            auto m4 = [&](float (&c)[4], int T, int j) { mma_bf(c, x[0][j][0], x[0][j][1], x[0][j][2], x[0][j][3], bd[2 * T - 27 - j].x, bd[2 * T - 27 - j].y); };
            ship(6);
            ld8(e[6], 14); ld8(e[7], 15);
#pragma unroll
            for (int j = 0; j < 4; j++) ld4(x[0][j], 27 + j);
            m8(q1, 15, 0); m8(q0, 14, 0); m8(q1, 15, 1);
            m8(acc[15], 15, 6); m4(q1, 15, 0); m8(acc[14], 14, 6); m4(q0, 14, 0);
            m8(acc[15], 15, 4); m8(q1, 15, 2); m4(acc[14], 14, 1); m8(q0, 14, 1);
            m4(acc[15], 15, 1); m4(q1, 15, 2); m8(acc[14], 14, 4); m8(q0, 14, 2);
            m8(acc[15], 15, 5); m8(q1, 15, 3); m8(acc[14], 14, 5); m8(q0, 14, 3);
            m4(acc[15], 15, 3); m8(q1, 15, 7);
#pragma unroll
            for (int c = 0; c < 4; c++) { acc[14][c] += q0[c]; acc[15][c] += q1[c]; }
            ship(7);
        }
        if ((warp & 3) == 0) TSTAMP(14 + (warp >> 2)); else TSTAMP(21 + warp);
    }
}

constexpr int SF_WD = 73728;
constexpr int SF_RED = 49152;
constexpr int MU_STRIDE = 1168  , SM_RAW = 98304, SM_UT = SM_RAW + 16384, SM_G = SM_UT + 21504, SM_Y = 196608, SM_FT = SM_Y + 17024, SM_KT = 138880, SM_KW = SM_G - 49152;
constexpr int SF_XS = 221184;
constexpr int SF_MISC = SF_XS + 8 * 1168;
constexpr int SF_KG = SF_MISC - 10 * KG_STAGE;
constexpr int SF_WR = SF_KG - 2304;
constexpr int FB_X = 64, FB_KDONE = 72, FB_KEYS = 80, FB_FREE = 88  , FB_W = 104, FB_D = FB_W + 72, FB_MU = FB_D + 96, FB_FAR = FB_MU - 16, FB_MG = FB_MU + 8, FB_MT = FB_MU + 16  , FS_PART = 512, FS_TOK = 896, FS_BM = 1024;
enum { BAR_R = 7, BAR_GU = 8, BAR_RED = 9, BAR_R2 = 10, BAR_G = 12  , BAR_M = 15 };
static_assert(SF_KG % 128 == 0 && NPRE <= 8 && SM_KT + 4 * 2112 <= 147456 && SM_G + MU_STRIDE <= SF_WR - 4 * 9216 && SM_KW + 6 * 2112 >= SM_RAW && SM_KW + 12 * 2112 <= SM_UT, "layout");

__device__ __forceinline__ constexpr int box_no(int i) { return (0x987610ba5432ull >> (4 * i)) & 15; }
__device__ __forceinline__ int role(int b) { b -= NCONV; return b < NX ? b : 18 + (b >> 1) + 12 * (b & 1); }
__device__ __forceinline__ int mini_ch0(int f) { return 48 * f - (f < NW ? 1696 : 2304); }

__device__ __forceinline__ void ffn_front(const Params& p, const CUtensorMap* maps, uint32_t sb, int warp, int lane, int f, unsigned epoch) {
    const unsigned t0 = clock32();
    const int g = lane >> 2, t = lane & 3, mi = lane >> 3, r8 = lane & 7;
    const bool isx = f < NX;
    const int nrw = f < 52 ? 4 : 6, r0 = f < 52 ? 32 * f : 48 * f - 832;
    const int rw = warp < 12 ? 13 - warp : warp ^ (warp < 14 ? 10 : 15);
    const uint32_t bar_row = sb + SF_MISC  , bar_x = bar_row + FB_X;
    const uint32_t s_part = bar_row + FS_PART  , s_tok = bar_row + FS_TOK  ;
    const uint32_t rows = sb + SF_WR - 9216 * (rw + 1) - (rw & 4) * ((SF_WR - 6 * 9216) / 4);
    {
#pragma unroll 1
        for (int i = warp < 10 ? 30 : warp - 10; i < 30; i += 6) if (elect()) mbar_init(bar_x + 8 * i, i == 1 ? 4 + (f < NW) : i < 27 ? 1 : i == 27 ? 2 : 8);
        const uint32_t bytes = rw < 6 ? 9216 : 1152, dst = rw < 6 ? rows : sb + SF_WR + (rw & 1) * 1152;
        const __nv_bfloat16* src = rw < 6 ? p.u + (size_t)(r0 + 8 * rw) * DM : (rw & 1) ? p.gatew : p.wr;
        if (elect()) { mbar_init(bar_row + 8 * rw, 1); mbar_fence(); mbar_expect(bar_row + 8 * rw, bytes); }
        if (warp == 13) { sts32(s_part + 64 + lane * 4, 0); sts32(bar_row + FS_BM + lane * 4, 0); }
        bar_sync(0, NTHR);
        if (!isx) asm volatile("barrier.cluster.arrive.relaxed.aligned;" ::: "memory");
        if (rw < nrw) until(t0, RDELAY);
        if (rw < nrw || rw >= 6) { if (elect()) bulk_g2s(dst, src, bytes, bar_row + 8 * rw); }
    }
    uint4* const kdst = p.s->keys + (lane >> 1) * 128 + 2 * f + (lane & 1);
    if (warp == 15) TSTAMP(1);

    if (warp == 12) {
        if (lane < 22) mbar_expect(bar_row + FB_W + 8 * lane, lane < 9 ? 24576 : isx ? 12288 : lane < 20 ? 2048 : 16384);
        if (elect()) { prefetch_map(maps + 1); prefetch_map(maps + 2); prefetch_map(maps + (isx ? 3 : 5)); }
        unsigned tb = t0 + WDELAY;
        auto pieces = [&](int n, int end, uint32_t dst) {
#pragma unroll 1
            for (; n < end; n++, dst += 12288) {
                until(tb, 0); tb += WGAP;
                if (elect()) tma3d(dst, maps + 1 + (n & 1), 0, 64 * (n >> 1), 3 * f, bar_row + FB_W + 8 * (n >> 1));
            }
        };
        if (!isx) {
#pragma unroll 1
            for (int k = 0; k <= (f >= NW); k++) { until(t0, MDELAY); if (elect()) tma4d(sb + SM_RAW - 49152 * k, maps + 5, mini_ch0(f) + 16 * k, 0, 0, 0, bar_row + FB_MU - 8 * k); }
            if (f >= NW) return;
        }
#pragma unroll 1
        for (int i = 0; i < 4; i++) {
            if (i == 1) { mbar_wait(bar_row + FB_KEYS); mbar_wait(bar_row + FB_KDONE); tb = clock32() + RESUME; }
            if (i == 3) mbar_wait(bar_row + FB_FREE);
            const int n = ((0x0c080000 + NPRE * 256) >> (8 * i)) & 255;
            pieces(n, ((0x120c0800 + NPRE) >> (8 * i)) & 255, sb + 12288 * (((0x000c0000 + NPRE * 256) >> (8 * i)) & 255));
        }
        TSTAMP(12);
        if (isx) {
#pragma unroll 1
            for (int i = 0; i < 12; i++) {
                const int n = box_no(i);
                if (i == 6) mbar_wait(bar_row + FB_FREE + 8);
                until(tb, 0); tb += DGAP;
                if (elect()) tma2d(sb + SF_WD + n * 12288, maps + 3, 32 * (f >> 1), 2304 * (f & 1) + 192 * n, bar_row + FB_D + 8 * n);
            }
            TSTAMP(13);
        }
    } else if (warp == 13) {
        const uint32_t tag = key_tag(epoch), par = (epoch & 1) ? 0u : 0x8000u;
        stg128(kdst, 0, 0, 0, 0);
        if (lane < 8 && isx && !(f & 1)) st_rlx32(&p.s->sel[32 * f + lane], 0);
        bar_sync(BAR_R, 32 * (nrw + 1));
        TSTAMP(3);
        {
            const uint32_t sg = fresh(s_part) + 192 + lane * 4;
            const uint32_t gb = pack_bf16(sigmoidf_(rbf(__uint_as_float(lds32(sg)))), sigmoidf_(rbf(__uint_as_float(lds32(sg + 128))))) | par | (par << 16);
            asm volatile("st.relaxed.gpu.global.u16 [%0], %1;" :: "l"(p.s->gate + r0 + lane), "h"((unsigned short)gb) : "memory");
            if (nrw > 4 && lane < 16) asm volatile("st.relaxed.gpu.global.u16 [%0], %1;" :: "l"(p.s->gate + r0 + 32 + lane), "h"((unsigned short)(gb >> 16)) : "memory");
        }
        bar_sync(BAR_R2, 32 * (nrw + 1));
        {
            const uint4 v = lds128(fresh(s_tok) + (lane & 1) * 16);
            asm volatile("st.relaxed.gpu.global.v4.u32 [%0], {%1,%2,%3,%4};" :: "l"(kdst), "r"(v.x | tag), "r"(v.y | tag), "r"(v.z | tag), "r"(v.w | tag) : "memory");
        }
        TSTAMP(4);
        if (lane == 0) { mbar_arrive(bar_row + FB_KEYS); mbar_expect(bar_x, 8 * 1152); }
        if (f >= NW) return;
        mbar_wait(bar_row + FB_KDONE);
        uint32_t k[16];
        const uint4* src = p.s->keys + (f & 15) * 128 + lane;
#pragma unroll 1
        for (int it = 0;; it++) {
            uint32_t bad = 0;
#pragma unroll
            for (int i = 0; i < 4; i++) {
                const uint4 x = ld_rlx128(src + (i < 3 || lane < 24 ? 32 * i : 64));
                k[i] = x.x; k[4 + i] = x.y; k[8 + i] = x.z; k[12 + i] = x.w;
                bad |= x.x ^ tag;
            }
            const bool ok = __all_sync(0xffffffffu, (bad & 0xf800u) == 0);
            if (ok) break;
            if (it > (1 << 20)) give_up();
        }
        TSTAMP(5);
        uint32_t key = 0, m = __reduce_max_sync(0xffffffffu, max(max(k[0], k[1]), max(k[2], k[3])));
#pragma unroll 2
        for (int r = 0; r < 8; r++) {
            bool pop[4];
#pragma unroll
            for (int i = 0; i < 4; i++) { pop[i] = k[i] == m; k[i] = pop[i] ? k[4 + i] : k[i]; }
            const uint32_t mn = __reduce_max_sync(0xffffffffu, max(max(k[0], k[1]), max(k[2], k[3])));
            if (elect()) bulk_g2s(sb + SF_XS + r * 1168, p.u + (size_t)key_row(m) * DM, 1152, bar_x);
#pragma unroll
            for (int i = 0; i < 4; i++) { k[4 + i] = pop[i] ? k[8 + i] : k[4 + i]; k[8 + i] = pop[i] ? k[12 + i] : k[8 + i]; k[12 + i] = pop[i] ? 0 : k[12 + i]; }
            if (r8 == r) key = m;
            m = mn;
        }
        const int row = key_row(key);
        sts32(s_tok + r8 * 8, row);
        TSTAMP(6);
        if (isx) {
            if (!(f & 1)) {
                __nv_bfloat16* o = p.out + (size_t)row * DM + 16 * f + 8 * mi;
                asm volatile("st.relaxed.gpu.global.v4.u32 [%0], {%1,%1,%1,%1};" :: "l"(o), "r"(0) : "memory");
                if (__any_sync(0xffffffffu, ld_rlx32(o) != 0)) give_up();
                if (lane < 8) st_rlx32(&p.s->sel[32 * f + lane], key);
            } else wait_sel(p, f >> 1, r8, tag);
            uint32_t gb;
#pragma unroll 1
            for (int it = 0;; it++) {
                asm volatile("ld.relaxed.gpu.global.u16 %0, [%1];" : "=r"(gb) : "l"(p.s->gate + row) : "memory");
                gb ^= par;
                if (!(gb & 0x8000u)) break;
                if (it > (1 << 20)) give_up();
            }
            const uint32_t rb = key ^ 0x80000000u, rv = (rb ^ (((int)rb >> 31) & 0x7fff0000u)) & 0xffff0000u;
            sts32(s_tok + r8 * 8 + 4, __float_as_uint(rbf(1.0f - bf_lo(gb)) * rbf(sigmoidf_(__uint_as_float(rv)))));
            __syncwarp();
            TSTAMP(7);
            bar_arrive(BAR_RED, 416);
        }
    } else {
        if (rw < nrw) {
            float c[3][4];
#pragma unroll
            for (int i = 0; i < 3; i++) { c[i][0] = c[i][1] = c[i][2] = c[i][3] = 0.f; }
            mbar_wait(bar_row + 48); mbar_wait(bar_row + 56);
            const uint32_t b = fresh(sb + SF_WR) + (g & 1) * 1152 + (g >> 2) * 64 + t * 16 + (g & 2) * 2;
            uint32_t w[18][2];
#pragma unroll
            for (int kb = 0; kb < 18; kb++) { const uint32_t o = ((kb & 1) ? b ^ 64 : b) + 128 * (kb >> 1); w[kb][0] = lds32(o); w[kb][1] = lds32(o + 8); }
            mbar_wait(bar_row + 8 * rw);
            if (warp == 15) TSTAMP(2);
            const uint32_t a = fresh(rows) + g * 1152 + (g & 1) * 64 + t * 16;
#pragma unroll
            for (int kb = 0; kb < 18; kb++) {
                const uint4 x = lds128(((kb & 1) ? a ^ 64 : a) + 128 * (kb >> 1));
                mma_bf(c[kb % 3], x.x, x.y, x.z, x.w, w[kb][0], w[kb][1]);
            }
            const float sr = c[0][0] + c[1][0] + c[2][0] + __shfl_down_sync(0xffffffffu, c[0][2] + c[1][2] + c[2][2], 1);
            const float sg = c[0][1] + c[1][1] + c[2][1] + __shfl_down_sync(0xffffffffu, c[0][3] + c[1][3] + c[2][3], 1);
            const uint32_t rb = pack_bf16(0.f, sr);
            if (t == 2 * (g & 1)) {
                sts32(s_part + (8 * rw + g) * 4, (rb ^ (((int)rb >> 31) & 0x7fff0000u) ^ 0x80000000u) | (uint32_t)(2047 - r0 - 8 * rw - g));
                sts32(s_part + 192 + (8 * rw + g) * 4, __float_as_uint(sg));
            }
            __syncwarp();
            bar_sync(BAR_R, 32 * (nrw + 1));
            const uint32_t sk = fresh(s_part), kk = lds32(sk + (8 * rw + r8) * 4);
            int n = 0;
#pragma unroll
            for (int i = 0; i < 3; i++) { const uint4 v = lds128(sk + mi * 48 + 16 * i); n += (v.x > kk) + (v.y > kk) + (v.z > kk) + (v.w > kk); }
            n += __shfl_xor_sync(0xffffffffu, n, 8); n += __shfl_xor_sync(0xffffffffu, n, 16);
            if (n < 8) sts32(s_tok + 4 * n, kk);
            __syncwarp();
            bar_arrive(BAR_R2, 32 * (nrw + 1));
        }
    }
}

__device__ __forceinline__ void ffn_work(const Params& p, uint32_t sb, int warp, int lane, int f, unsigned epoch) {
    const int g = lane >> 2, t = lane & 3, mi = lane >> 3, r8 = lane & 7;
    const bool isx = f < NX;
    const uint32_t bar_x = sb + SF_MISC + FB_X, bar_free = sb + SF_MISC + FB_FREE, bar_w = sb + SF_MISC + FB_W, bar_d = sb + SF_MISC + FB_D, s_tok = sb + SF_MISC + FS_TOK;
    uint32_t fr[24][4];
    auto pin = [&] {
#pragma unroll
        for (int i = 0; i < 24; i += 8) asm volatile("" :: "r"(fr[i][0]), "r"(fr[i + 1][0]), "r"(fr[i + 2][0]), "r"(fr[i + 3][0]), "r"(fr[i + 4][0]), "r"(fr[i + 5][0]), "r"(fr[i + 6][0]), "r"(fr[i + 7][0]) : "memory");
    };
    {
        const int j = (unsigned)(warp - 4) < 6, w = warp - (j ? 4 : warp < 4 ? 0 : 6);
        float ag[2][4], au[2][4];
#pragma unroll
        for (int i = 0; i < 2; i++) { ag[i][0] = ag[i][1] = ag[i][2] = ag[i][3] = 0.f; au[i][0] = au[i][1] = au[i][2] = au[i][3] = 0.f; }
        const uint32_t wb = sb + (w >> 1) * 4096 + (r8 + 8 * (mi >> 1)) * 64 + (((2 * (w & 1) + (mi & 1)) ^ (r8 >> 1)) << 4);
        const uint32_t xb = sb + SF_XS + r8 * 1168 + mi * 16;
        auto load = [&](int i, int n, int place) {
            mbar_wait(bar_w + 8 * n);
            const uint32_t wk = fresh(wb) + place * 24576;
#pragma unroll
            for (int s = 0; s < 4; s++) { ldsm4t(fr[8 * i + s], wk + 1024 * s); ldsm4t(fr[8 * i + 4 + s], wk + 1024 * s + 12288); }
        };
        auto mul = [&](int i, uint32_t xk) {
            uint32_t x[2][4];
            ldsm4(x[0], xk); ldsm4(x[1], xk + 64);
#pragma unroll
            for (int s = 0; s < 4; s++) {
                const uint32_t (&a)[4] = fr[8 * i + s], (&b)[4] = fr[8 * i + 4 + s];
                mma_bf(ag[s & 1], a[0], a[1], a[2], a[3], x[s >> 1][2 * (s & 1)], x[s >> 1][2 * (s & 1) + 1]);
                mma_bf(au[s & 1], b[0], b[1], b[2], b[3], x[s >> 1][2 * (s & 1)], x[s >> 1][2 * (s & 1) + 1]);
            }
        };
#pragma unroll
        for (int i = 0; i < 3; i++) load(i, 3 * j + i, (i ? 5 : 3) * j + i);
        pin();
        bar_sync(BAR_G + j, 192);
        if (w == 0 && lane == 0) mbar_arrive(bar_free + 8 * j);
        mbar_wait(bar_x);
        stg128z_if(!j && lane < 16, (uint4*)p.s->h + (6 * f + w) * 16 + lane);
        if (warp == 0) TSTAMP(8);
        {
            const uint32_t xk = fresh(xb) + 384 * j;
#pragma unroll
            for (int i = 0; i < 3; i++) { mul(i, (i ? fresh(xk) : xk) + 128 * i); if (i == 0) { asm volatile("" :: "f"(ag[0][0]), "f"(ag[1][0]), "f"(au[0][0]), "f"(au[1][0])); sts32(s_tok + 64, clock32()); } }
        }
#pragma unroll 1
        for (int n = 6 + j; n < 9; n += 2) { load(0, n, n - 6); mul(0, fresh(xb) + 128 * n); }
#pragma unroll
        for (int c = 0; c < 4; c++) { ag[0][c] += ag[1][c]; au[0][c] += au[1][c]; }
        if (j) {
            sts128(wb + 24576, __float_as_uint(ag[0][0]), __float_as_uint(ag[0][1]), __float_as_uint(ag[0][2]), __float_as_uint(ag[0][3]));
            sts128(wb + 25600, __float_as_uint(au[0][0]), __float_as_uint(au[0][1]), __float_as_uint(au[0][2]), __float_as_uint(au[0][3]));
        }
        bar_sync(BAR_GU, 384);
        if (!j) {
            const uint32_t sf = fresh(wb);
            const uint4 g1 = lds128(sf + 24576), u1 = lds128(sf + 25600);
            const uint32_t gs[4] = {g1.x, g1.y, g1.z, g1.w}, us[4] = {u1.x, u1.y, u1.z, u1.w};
            if (warp == 0) TSTAMP(9);
            float h[4];
#pragma unroll
            for (int c = 0; c < 4; c++) {
                const float gv = rbf(ag[0][c] + __uint_as_float(gs[c]));
                h[c] = rbf(gv * sigmoidf_(gv)) * rbf(au[0][c] + __uint_as_float(us[c]));
            }
            uint32_t h0, h1;
            asm("movmatrix.sync.aligned.m8n8.trans.b16 %0, %1;" : "=r"(h0) : "r"(pack_bf16(h[0], h[1])));
            asm("movmatrix.sync.aligned.m8n8.trans.b16 %0, %1;" : "=r"(h1) : "r"(pack_bf16(h[2], h[3])));
            h0 = (h0 & 0xfffefffeu) | k_tag(epoch);
            asm volatile("{ .reg .b64 v; mov.b64 v, {%1, %2}; st.relaxed.gpu.global.b64 [%0], v; }" :: "l"(p.s->h + (6 * f + w) * 32 + lane), "r"(h0), "r"(h1) : "memory");
        }
        if (isx) {
            if (warp == 0) TSTAMP(10);
            const uint2* hsrc = p.s->h + (144 * (f & 1) + warp) * 32 + lane;
            const uint32_t wd = sb + SF_WD + warp * 1024 + (r8 + 8 * (mi >> 1)) * 64 + (((mi & 1) ^ (r8 >> 1)) << 4), we = wd ^ 32;
            uint2 hb[12];
            auto ldh = [&](int i) { asm volatile("ld.relaxed.gpu.global.v2.u32 {%0, %1}, [%2];" : "=r"(hb[i].x), "=r"(hb[i].y) : "l"(hsrc + 384 * box_no(i)) : "memory"); };
            auto ldw = [&](int i) { mbar_wait(bar_d + 8 * box_no(i)); ldsm4t(fr[2 * i], fresh(wd) + 12288 * box_no(i)); ldsm4t(fr[2 * i + 1], fresh(we) + 12288 * box_no(i)); };
#pragma unroll
            for (int i = 0; i < DPA; i++) ldw(i);
#pragma unroll
            for (int i = 0; i < 12; i++) ldh(i);
#pragma unroll
            for (int i = DPA; i < DPB; i++) ldw(i);
#pragma unroll
            for (int i = 0; i < DPB; i++) asm volatile("" :: "r"(fr[2 * i][0]), "r"(fr[2 * i + 1][0]) : "memory");
#pragma unroll 1
            for (int it = 0;; it++) {
                bool again = false;
#pragma unroll
                for (int s = 0; s < 12; s += 2) if (!__all_sync(0xffffffffu, hb[s].x & hb[s + 1].x & k_tag(epoch))) { ldh(s); ldh(s + 1); again = true; }
                if (!again) break;
                if (it > (1 << 16)) give_up();
            }
            if (warp == 0) TSTAMP(11);
            float ad[2][2][4];
#pragma unroll
            for (int i = 0; i < 4; i++) { ad[i >> 1][i & 1][0] = ad[i >> 1][i & 1][1] = ad[i >> 1][i & 1][2] = ad[i >> 1][i & 1][3] = 0.f; }
#pragma unroll
            for (int i = 0; i < 12; i++) {
                if (i >= DPB) ldw(i);
                if (i == 11 && warp == 9) TSTAMP(14);
#pragma unroll
                for (int c = 0; c < 2; c++) mma_bf(ad[c][i & 1], fr[2 * i + c][0], fr[2 * i + c][1], fr[2 * i + c][2], fr[2 * i + c][3], hb[i].x, hb[i].y);
                if (i >= DPB - 1) asm volatile("" :: "f"(ad[0][i & 1][0]), "f"(ad[1][i & 1][0]) : "memory");
            }
            const uint32_t rd = sb + SF_RED + warp * 1152 + (72 * t + g) * 4;
#pragma unroll
            for (int i = 0; i < 8; i++) sts32(rd + (i >> 2) * 64 + (i & 1) * 144 + ((i >> 1) & 1) * 32, __float_as_uint(ad[i >> 2][0][i & 3] + ad[i >> 2][1][i & 3]));
            bar_sync(BAR_RED, 416);
            if (warp < 4) {
                const int tid = 32 * warp + lane;
                const uint32_t rs = fresh(sb + SF_RED) + (tid >> 4) * 144 + (tid & 15) * 8;
                const uint2 tk = lds64(fresh(s_tok) + (tid >> 4) * 8);
                float x = 0.f, y = 0.f;
#pragma unroll
                for (int w = 0; w < 12; w++) { const uint2 v = lds64(rs + w * 1152); x += __uint_as_float(v.x); y += __uint_as_float(v.y); }
                asm volatile("red.relaxed.gpu.global.add.noftz.bf16x2 [%0], %1;" :: "l"(p.out + (size_t)tk.x * DM + 32 * (f >> 1) + 2 * (tid & 15)),
                             "r"(pack_bf16(x * __uint_as_float(tk.y), y * __uint_as_float(tk.y))) : "memory");
            }
            if (warp == 0) { TSTAMP(15); TFLUSH(); }
            asm volatile("exit;"); __builtin_unreachable();
        }
    }
}

__device__ __forceinline__ void fetch_k(const uint4* src, uint64_t (&v)[4], uint32_t a, uint32_t b) {
    asm volatile("{ .reg .pred p; setp.eq.u32 p, %5, %6; @p ld.relaxed.gpu.global.v2.u64 {%0,%1}, [%4]; @p ld.relaxed.gpu.global.v2.u64 {%2,%3}, [%4 + 512]; }"
                 : "+l"(v[0]), "+l"(v[1]), "+l"(v[2]), "+l"(v[3]) : "l"(src), "r"(a), "r"(b));
}
__device__ __forceinline__ uint32_t mini_conv(const Params& p, uint32_t sb, int warp, int lane, int f, unsigned epoch, uint64_t (&v)[4]) {
    const int g = lane >> 2, t = lane & 3, mi = lane >> 3, r8 = lane & 7;
    const uint32_t fb = sb + SF_MISC, kt = sb + (warp >= 12 ? SM_KT - 12 * 2112 : f < NW ? SM_KW + 2 * 2112 : SM_KW) + warp * 2112;
    const bool ism = f >= NW;
    const uint32_t* const sel = &p.s->sel[((mini_ch0(f) + (ism ? 2 * (warp & 8) : 0)) >> 5) * 64 + r8];
    uint32_t seq = 128, key;
    const uint4* src = p.s->kp + lane;
    auto hi = [&](int i) { return (uint32_t)(v[i] >> 32); };
    if (f >= (warp < 4 ? NW : NX)) {
    {
        const uint32_t c = 68 + (warp & 3) + 2 * (warp & 12), y = ((uint32_t)((warp < 8 ? 0xe066806400000000ull : 0x5a6e00680080e26cull) >> ((8 * warp) & 48)) & 0xffff) + (warp < 14 ? 0 : 0x6a0000);
        seq = !ism ? y + (warp & 1) * ((y >> 6) & 0x10101) : warp < 14 ? 0x101 * c - 0x400 : c;
        src += (48 * (f - (ism ? NW : NX)) + (seq & 63)) * 96;
    }
    if (seq & 64) {
        if (seq & 4) {
            const int q = (seq & 3) + ((seq >> 1) & 4);
            const uint32_t ab = sb - 3072 * (seq & 16), d = ab + SM_UT + g * MU_STRIDE + (4 + 4 * q + t) * 32;
            asm volatile("st.shared.v2.u32 [%0], {%1,%1};" :: "r"(ab + SM_UT + (2 * q + (mi >> 1)) * MU_STRIDE + (lane & 15) * 8), "r"(0) : "memory");
            mbar_wait(fb + FB_MU - (seq & 16) / 2);
            if (warp == 15) TSTAMP(16);
            const uint32_t a = fresh(ab + SM_RAW) + q * 2048 + (8 * mi + 4 * (r8 & 1) + (r8 >> 1)) * 32 + ((r8 & 1) << 4);
            uint32_t x[4][4];
#pragma unroll
            for (int i = 0; i < 4; i++) ldsm4t(x[i], (i & 2 ? a ^ 16 : a) + 1024 * (i & 1));
#pragma unroll
            for (int i = 0; i < 4; i++) sts128(d + (i & 1) * 16 + (i & 2) * 4 * MU_STRIDE, x[i][0], x[i][1], x[i][2], x[i][3]);
            __syncwarp();
            if (lane == 0) mbar_arrive(fb + FB_MT + (seq & 16) / 2);
        }
        mbar_wait(fb + FB_KDONE);
        fetch_k(src, v, warp < 4, 0);
        if ((warp | 2) == 7) { fetch_gates(p, (warp >> 1) & 1, lane, epoch, sb + SM_G + 256 * (warp & 2) + 16 * lane); __syncwarp(); if (lane == 0) mbar_arrive(fb + FB_MG); }
        if (warp >= 8) {
            mbar_wait(fb + FB_KEYS); mbar_wait(fb + FB_MT);
            if (ism) {
                asm volatile("barrier.cluster.wait.aligned; fence.release.sync_restrict::shared::cta.cluster;" ::: "memory");
                if (lane == 0) asm volatile("mbarrier.arrive.relaxed.cluster.shared::cluster.b64 _, [%0];" :: "r"(mapa(fb + FB_MT + 8, 0)) : "memory");
            }
        }
        if (warp == TW) TSTAMP(17);
    }
    }
    const uint32_t lo = (8 + r8 - (mi & 1)) * 16 + (mi >> 1) * 128;
#pragma unroll 1
    do {
        const int c = seq & 63;
        const bool far = !ism && (seq & 16);
        const uint32_t ab = sb - 3072 * (c & 16);
        uint32_t ut = ab + SM_UT + (c & 15) * MU_STRIDE;
        if (seq & 64) {
        if (far) {
            mbar_wait_cluster(fb + FB_MT + 8);
            const uint32_t ru = mapa(ut, 1) + lane * 16;
            ut = sb + SM_FT + (c & 3) * 1536;
            uint4 x[3];
#pragma unroll
            for (int i = 0; i < 3; i++) asm volatile("ld.shared::cluster.v4.u32 {%0,%1,%2,%3}, [%4];" : "=r"(x[i].x), "=r"(x[i].y), "=r"(x[i].z), "=r"(x[i].w) : "r"(ru + 512 * i) : "memory");
#pragma unroll
            for (int i = 0; i < 3; i++) sts128(ut + lane * 16 + 512 * i, x[i].x, x[i].y, x[i].z, x[i].w);
        } else mbar_wait(fb + FB_MT + (seq & 16) / 2);
#pragma unroll 1
        for (int it = 0; !__all_sync(0xffffffffu, hi(1) & hi(3) & k_tag(epoch)); it++) {
            fetch_k(src, v, 0, 0);
            if (it > (1 << 20)) give_up();
        }
        sts128(kt + t * 16, 0, 0, 0, 0);
        if (warp == TW) TSTAMP(seq >> 8 ? 7 : 10);
        const uint32_t w[12] = {(uint32_t)v[0], hi(0), (uint32_t)v[1], hi(1), (uint32_t)v[2], hi(2), (uint32_t)v[3], hi(3), 0, 0, 0, 0};
        k_tables<false>(fresh(kt), fresh(lane), w);
        }
        __syncwarp();
        if (seq & 128) ffn_work(p, sb, warp, fresh(lane), f, epoch);
        if (!(seq & 64)) return 0;
        const uint32_t kb = fresh(kt) + (16 + g - 2 * t) * 4, ub = fresh(ut);
        const uint32_t yd = ab + SM_Y + (c & 15) * 1056 + (c & 8) * 8 + lane * 16;
        if (warp == TW && !(seq >> 8)) TSTAMP(13);
        seq >>= 8;
        src += ((int)(seq & 63) - c) * 96;
#pragma unroll
        for (int i = 0; i < 4; i++) v[i] = 0;
        key = 0;
        float acc[8][4];
#pragma unroll
        for (int i = 0; i < 8; i++) { acc[i][0] = acc[i][1] = acc[i][2] = acc[i][3] = 0.f; }
        uint32_t a[4][4], b[2][4][4];
        auto lda = [&](int j, int s) { const uint32_t x = kb + 64 * s + 512 * j; a[j][0] = lds32(x); a[j][1] = lds32(x + 256); a[j][2] = lds32(x + 32); a[j][3] = lds32(x + 288); };
        auto ldb = [&](int i, int s) { ldsm4(b[s & 1][i], ub + lo + 256 * i - 32 * s); };
#pragma unroll
        for (int j = 0; j < 4; j++) { ldb(j, 0); lda(j, 0); }
#pragma unroll
        for (int s = 0; s < 4; s++) {
            if (s == 2) {
                const uint32_t e = seq | (__float_as_uint(acc[0][0]) & p.zero);
                fetch_k(src, v, e & 64, 64);
                asm volatile("{ .reg .pred p; setp.eq.u32 p, %2, 0; @p ld.relaxed.gpu.global.u32 %0, [%1]; }" : "+r"(key) : "l"(sel), "r"(e));
            }
#pragma unroll
            for (int i = 0; i < 4; i++) {
                const int j = (i >> 1) + 2 * (i & 1);
                if (s < 3) ldb(i, s + 1);
#pragma unroll
                for (int mu = 0; mu < 8; mu++) if (mu + 2 * j < 8) mma_bf(acc[mu + 2 * j], a[j][0], a[j][1], a[j][2], a[j][3], b[s & 1][mu >> 1][2 * (mu & 1)], b[s & 1][mu >> 1][2 * (mu & 1) + 1]);
                if (s < 3) lda(j, s + 1);
            }
        }
        if (warp == TW && !seq) TSTAMP(14);
        mbar_wait(fb + FB_MG);
        uint32_t ug[4][4];
#pragma unroll
        for (int i = 0; i < 2; i++) { ldsm4t(ug[i], ub + 128 + lane * 16 + 512 * i); ldsm4t(ug[2 + i], fresh(sb + SM_G) + lane * 16 + 512 * i); }
#pragma unroll
        for (int x = 0; x < 8; x++) ug[x >> 2][x & 3] = gmix(ug[2 + (x >> 2)][x & 3], x ? acc[x][0] + acc[x - 1][2] : acc[0][0], x ? acc[x][1] + acc[x - 1][3] : acc[0][1], ug[x >> 2][x & 3]);
        if (far) for (int i = 0; i < 2; i++) st_async128(mapa(yd, 1) + 512 * i, ug[i][0], ug[i][1], ug[i][2], ug[i][3], mapa(fb + FB_FAR, 1));
        else for (int i = 0; i < 2; i++) sts128(yd + 512 * i, ug[i][0], ug[i][1], ug[i][2], ug[i][3]);
        __syncwarp();
        if (warp == TW) TSTAMP(18 + (seq != 0));
    } while (seq);
    if (warp >= 12) TSTAMP(12 + warp);
    return key;
}
__device__ __forceinline__ void mini_out(const Params& p, const CUtensorMap* maps, uint32_t sb, int warp, int lane, int f, unsigned epoch, uint32_t key) {
    const int g = lane >> 2, t = lane & 3, mi = lane >> 3, r8 = lane & 7;
    const uint32_t fb = sb + SF_MISC;
    const bool ism = f >= NW;
    const int ch0 = mini_ch0(f);
    const int k = ism ? warp >> 3 : 0;
    uint32_t first = 1;
    if (lane == 0) asm volatile("atom.shared.exch.b32 %0, [%1], 1;" : "=r"(first) : "r"(fb + FS_BM + 64 + 4 * k) : "memory");
    if (!__all_sync(0xffffffffu, first)) {
        if (elect()) prefetch_map(maps + 6);
        const int row = key_row(wait_sel(p, (ch0 + 16 * k) >> 5, r8, key_tag(epoch), key));
        if (row < 512) asm volatile("red.shared.or.b32 [%0], %1;" :: "r"(fb + FS_BM + (row >> 5) * 4), "r"(1u << (row & 31)) : "memory");
        if (k) mbar_wait_cluster(fb + FB_FAR);
    }
    const int m = warp & 7, dr = 64 * (g >> 1) + 16 * (t >> 1) + 8 * (g & 1);
    const uint32_t y = SM_Y + ((r8 >> 1) & 1) * 8512 + (2 * mi + (r8 & 1)) * 1056 + (2 * m + (r8 >> 2)) * 16;
    const uint32_t so = (g >> 1) * 128 + (t >> 1) * 64 + (g & 1) * 32 + (t & 1) * 16;
    bar_sync(BAR_M - k, ism ? 256 : NTHR);
#pragma unroll 1
    for (int h = ism ? 0 : warp >> 3;; h++) {
        const int r0 = 256 * h + 32 * (m & 1) + (m >> 1), row = r0 + dr;
        const uint32_t bm = lds32(fresh(fb) + FS_BM + (row >> 5) * 4) >> (row & 31), ab = fresh(sb - 49152 * k + 512 * h), stg = ab + SM_UT + 2048 * m + 512 * h;
        uint32_t x[2][4];
        ldsm4t(x[0], ab + y); ldsm4t(x[1], ab + y + 256);
        if (warp == 0 && x[0][0] != 0x12345) TSTAMP(28);
        if (__any_sync(0xffffffffu, bm & 0x11u)) {
#pragma unroll
            for (int i = 0; i < 2; i++) store_or_add(p.out + (size_t)(row + 4 * i) * DM + ch0 + 16 * k + 8 * (t & 1), x[i], bm & (1u << (4 * i)));
        } else {
#pragma unroll
            for (int i = 0; i < 2; i++) sts128(stg + so + 512 * i, x[i][0], x[i][1], x[i][2], x[i][3]);
            asm volatile("fence.proxy.async.shared::cta;" ::: "memory");
            __syncwarp();
            if (elect()) store_rows(maps + 6, stg, ch0 + 16 * k, r0);
        }
        if (h >= ism) break;
    }
    if (elect()) { asm volatile("cp.async.bulk.commit_group;" ::: "memory"); asm volatile("cp.async.bulk.wait_group.read 0;" ::: "memory"); }
    if (warp == 8) TSTAMP(11);
    if (warp == 0) { TSTAMP(15); TFLUSH(); }
}

constexpr int SMEM_BYTES = 232448;
static_assert(SF_MISC + 1152 <= 232192, "layout");

struct Maps { CUtensorMap m[7]; };

__global__ void __cluster_dims__(2, 1, 1) __launch_bounds__(NTHR, 1)
fused_kernel(const Params p, const __grid_constant__ Maps maps) {
    extern __shared__ __align__(1024) uint8_t smem_raw[];
    uint32_t q[8];
    {
        const int b = role(blockIdx.x), x = threadIdx.x, rc = 5 * b + (b & ~3) + 4 + (x >> 6);
        const int cv = (unsigned)b < NW ? 0 : -1, ca = (b < 0 ? 8 * b + DM : 48 * b - 2300) + ((x >> 5) & 3), cb = 2 * rc - (rc & 3) + 4;
        const uint32_t ch = (ca & cv) | (cb & ~cv), o = NST * ch + 2 * ((x & 31) + ((x >> (cv & 2)) & 32));
        const bool c = x < (cv ? 256 : 320);
        q[6] = ldg16_if(c, p.logdt + ch);
        q[2] = ldg32_if(c, p.Bre + o); q[3] = ldg32_if(c, p.Bim + o); q[4] = ldg32_if(c, p.Cre + o); q[5] = ldg32_if(c, p.Cim + o); q[0] = ldg32_if(c, p.Are + o); q[1] = ldg32_if(c, p.Aim + o);
        q[7] = ldg16_if(c, p.Dskip + ch);
    }
    const unsigned epoch = ld_rlx32(&p.s->epoch[blockIdx.x * 16 + (threadIdx.x >> 5)]);
    const uint32_t sb = __shfl_sync(0xffffffffu, smem_u32(smem_raw), 0);
    const int warp = __shfl_sync(0xffffffffu, threadIdx.x >> 5, 0), bid = __shfl_sync(0xffffffffu, blockIdx.x, 0);
    const int lane = __shfl_sync(0xffffffffu, threadIdx.x & 31, threadIdx.x);
    const bool conv = bid < NCONV;
    const int f = role(bid);
    uint32_t w[12];
    uint64_t v[4];
    const bool four = (unsigned)f >= NW;
    if (warp < (four ? 8 : 10)) {
        const int half = four ? warp >> 2 : warp & 1, pr = four ? warp & 3 : warp >> 1;
        const int rc = 5 * f + (f & ~3) + 4 + pr;
        const uint32_t stage = sb + (conv ? SC_KG : SF_KG) + warp * KG_STAGE;
        uint4* const kp = p.s->kp + (four ? (conv ? 8 * bid : 48 * f - 2300) + pr : 2 * rc - (rc & 3) + 4) * 96 + lane;
        kgen(q, sb, half, stage, stage + (four ? 4 : 1) * KG_STAGE, 1 + pr, lane, w, [&] {
            sts128z_if(conv && lane < 20, sb + SC_KT + warp * KT_BYTES + lane * 16 + (lane < 4 ? 0 : lane < 14 ? 2048 : 2288));
            if (!conv) bar_sync(0, NTHR);
            if ((unsigned)f >= NX) asm volatile("barrier.cluster.arrive.relaxed.aligned;" ::: "memory");
        }, [&] {
            asm volatile("{ .reg .pred p, q; setp.ne.u32 p, %2, 0; setp.ne.and.u32 q, %3, 0, p; @p st.global.v4.u32 [%0], {%1,%1,%1,%1}; @q st.global.v4.u32 [%0 + 512], {%1,%1,%1,%1}; }"
                         :: "l"(kp + 32 * half), "r"(0), "r"((uint32_t)!conv), "r"((uint32_t)(half && lane < 18)) : "memory");
        });
        if (!half) publish_k(kp, lane, !conv, w, epoch, v);
        else for (int i = 0; i < 4; i++) v[i] = 0;
        if (conv) { conv_main(p, sb, warp, lane, bid, epoch, w); return; }
        {
            if (!half && lane == 0) mbar_arrive(sb + SF_MISC + FB_KDONE);
            if (warp == 0) TSTAMP(22);
            if (warp == 2) TSTAMP(23);
        }
    } else if (conv) {
        conv_aux(p, maps.m, sb, warp - 8, lane, bid, epoch);
        return;
    } else {
        ffn_front(p, maps.m, sb, warp, lane, f, epoch);
        for (int i = 0; i < 4; i++) v[i] = 0;
    }
    converged();
    next_epoch(p, epoch);
    if (warp >= 12 && f < NX) return;
    mini_out(p, maps.m, sb, warp, lane, f, epoch, mini_conv(p, sb, warp, __shfl_sync(0xffffffffu, lane, lane), f, epoch, v));
}

typedef CUresult (*EncodeFn)(CUtensorMap*, CUtensorMapDataType, cuuint32_t, void*, const cuuint64_t*, const cuuint64_t*, const cuuint32_t*, const cuuint32_t*,
                             CUtensorMapInterleave, CUtensorMapSwizzle, CUtensorMapL2promotion, CUtensorMapFloatOOBfill);

void make_map(EncodeFn fn, CUtensorMap* m, const void* base, int rank, const cuuint64_t* dims, const cuuint64_t* strides, const cuuint32_t* box, CUtensorMapSwizzle sw) {
    const cuuint32_t es[5] = {1, 1, 1, 1, 1};
    fn(m, CU_TENSOR_MAP_DATA_TYPE_BFLOAT16, rank, (void*)base, dims, strides, box, es, CU_TENSOR_MAP_INTERLEAVE_NONE, sw,
       CU_TENSOR_MAP_L2_PROMOTION_NONE, CU_TENSOR_MAP_FLOAT_OOB_FILL_NONE);
}

}

extern "C" void kernel_launch(void* const* d_in, const int* in_sizes, int n_in, void* d_out, int out_size) {
    (void)in_sizes; (void)n_in; (void)out_size;
    static EncodeFn fn = nullptr;
    static void* scratch = nullptr;
    if (!fn) {
        void* ptr = nullptr; cudaDriverEntryPointQueryResult qr;
        cudaGetDriverEntryPoint("cuTensorMapEncodeTiled", &ptr, cudaEnableDefault, &qr);
        fn = (EncodeFn)ptr;
        cudaGetSymbolAddress(&scratch, g_scratch);
        cudaFuncSetAttribute(fused_kernel, cudaFuncAttributeMaxDynamicSharedMemorySize, SMEM_BYTES);
    }
    typedef const __nv_bfloat16* bp;
    Params p;
    p.u = (bp)d_in[0]; p.Are = (bp)d_in[1]; p.Aim = (bp)d_in[2]; p.Bre = (bp)d_in[3]; p.Bim = (bp)d_in[4]; p.Cre = (bp)d_in[5]; p.Cim = (bp)d_in[6];
    p.logdt = (bp)d_in[7]; p.Dskip = (bp)d_in[8]; p.wr = (bp)d_in[10]; p.gatew = (bp)d_in[14];
    p.out = (__nv_bfloat16*)d_out; p.s = (Scratch*)scratch; p.zero = 0;
    Maps maps;
    {
        const cuuint64_t dims[4] = {DM, 4, 16, 32}, strides[3] = {16 * DM * 2, DM * 2, 64 * DM * 2};
        const cuuint32_t box[4] = {16, 4, 16, 2};
        make_map(fn, &maps.m[0], d_in[0], 4, dims, strides, box, CU_TENSOR_MAP_SWIZZLE_32B);
        const cuuint32_t box2[4] = {16, 4, 16, 8};
        make_map(fn, &maps.m[5], d_in[0], 4, dims, strides, box2, CU_TENSOR_MAP_SWIZZLE_32B);
    }
    for (int i = 0; i < 2; i++) {
        const cuuint64_t dims[3] = {32, DM, FF / 32}, strides[2] = {FF * 2, 64};
        const cuuint32_t box[3] = {32, 64, 3};
        make_map(fn, &maps.m[1 + i], d_in[11 + i], 3, dims, strides, box, CU_TENSOR_MAP_SWIZZLE_64B);
    }
    {
        const cuuint64_t dims[2] = {DM, FF}, strides[1] = {DM * 2};
        const cuuint32_t box[2] = {32, 192};
        make_map(fn, &maps.m[3], d_in[13], 2, dims, strides, box, CU_TENSOR_MAP_SWIZZLE_64B);
    }
    {
        const cuuint64_t dims[5] = {DM, 2, 4, 4, L_SEQ}, strides[4] = {16 * DM * 2, 64 * DM * 2, 4 * DM * 2, DM * 2};
        const cuuint32_t box[5] = {16, 2, 4, 4, 1};
        make_map(fn, &maps.m[4], d_out, 5, dims, strides, box, CU_TENSOR_MAP_SWIZZLE_NONE);
    }
    {
        const cuuint64_t dims[5] = {DM, 4, 4, 2, L_SEQ}, strides[4] = {8 * DM * 2, 64 * DM * 2, 4 * DM * 2, DM * 2};
        const cuuint32_t box[5] = {16, 4, 4, 2, 1};
        make_map(fn, &maps.m[6], d_out, 5, dims, strides, box, CU_TENSOR_MAP_SWIZZLE_NONE);
    }
    fused_kernel<<<NCTA, NTHR, SMEM_BYTES>>>(p, maps);
}
```

```cpp
#include <cuda_runtime.h>
#include <cuda_bf16.h>
#include <cuda_fp16.h>
#include <cuda.h>
#include <stdint.h>

#define RESUME 400
#define MDELAY 2000
#define KPOLL 650
#define DPA 7
#define DPB 9
#define RDELAY 900
#define WDELAY 1700
#define WGAP 290
#define NPRE 8
#define DGAP 280
namespace {

constexpr int DM = 576, NST = 128, FF = 4608, L_SEQ = 2048;
constexpr int NCONV = 72, NX = 36, NW = 48, NCTA = 132, NTHR = 512;

struct __align__(128) Scratch {
    unsigned epoch[NCTA * 16];
    uint4 keys[16 * 128];
    uint32_t sel[18 * 64];
    uint16_t gate[L_SEQ];
    uint2 h[288 * 32];
    uint4 kp[DM * 96];
};
__device__ Scratch g_scratch;
#define TFLUSH()
#define TSTAMP(i)
#define TW 12

struct Params {
    const __nv_bfloat16 *Are, *Aim, *Bre, *Bim, *Cre, *Cim, *logdt, *Dskip, *u, *wr, *gatew;
    __nv_bfloat16* out;
    Scratch* s;
    uint32_t zero;
};

__device__ __forceinline__ void give_up() { asm volatile("trap; exit;"); __builtin_unreachable(); }
__device__ __forceinline__ void converged() { __syncwarp(); asm volatile("{ .reg .b32 t; mov.b32 t, 0; movmatrix.sync.aligned.m8n8.trans.b16 t, t; }" ::: "memory"); }
__device__ __forceinline__ bool elect() { uint32_t r; asm volatile("{ .reg .pred p; elect.sync _|p, 0xffffffff; selp.u32 %0, 1, 0, p; }" : "=r"(r)); return r; }
__device__ __forceinline__ uint32_t smem_u32(const void* p) { return (uint32_t)__cvta_generic_to_shared(p); }
__device__ __forceinline__ uint32_t pack_bf16(float lo, float hi) { uint32_t r; asm("cvt.rn.bf16x2.f32 %0, %1, %2;" : "=r"(r) : "f"(hi), "f"(lo)); return r; }
__device__ __forceinline__ uint32_t pack_f16(float lo, float hi) { uint32_t r; asm("cvt.rn.f16x2.f32 %0, %1, %2;" : "=r"(r) : "f"(hi), "f"(lo)); return r; }
__device__ __forceinline__ float bf_lo(uint32_t w) { return __uint_as_float(w << 16); }
__device__ __forceinline__ float bf_hi(uint32_t w) { return __uint_as_float(w & 0xffff0000u); }
__device__ __forceinline__ float rbf(float x) { return bf_lo(pack_bf16(x, 0.f)); }
__device__ __forceinline__ uint32_t badd2(uint32_t a, uint32_t b) { uint32_t r; asm("add.rn.bf16x2 %0, %1, %2;" : "=r"(r) : "r"(a), "r"(b)); return r; }
__device__ __forceinline__ uint32_t bsub2(uint32_t a, uint32_t b) { uint32_t r; asm("sub.rn.bf16x2 %0, %1, %2;" : "=r"(r) : "r"(a), "r"(b)); return r; }
__device__ __forceinline__ uint32_t gmix(uint32_t ng, float ny0, float ny1, uint32_t u) {
    uint32_t r; asm("{ .reg .b32 t; fma.rn.bf16x2 t, %1, %3, %3; fma.rn.bf16x2 %0, %1, %2, t; }" : "=r"(r) : "r"(ng), "r"(pack_bf16(ny0, ny1)), "r"(u)); return r;
}
__device__ __forceinline__ void mma_bf(float (&c)[4], uint32_t a0, uint32_t a1, uint32_t a2, uint32_t a3, uint32_t b0, uint32_t b1) {
    asm("mma.sync.aligned.m16n8k16.row.col.f32.bf16.bf16.f32 {%0,%1,%2,%3}, {%4,%5,%6,%7}, {%8,%9}, {%0,%1,%2,%3};"
        : "+f"(c[0]), "+f"(c[1]), "+f"(c[2]), "+f"(c[3]) : "r"(a0), "r"(a1), "r"(a2), "r"(a3), "r"(b0), "r"(b1));
}
__device__ __forceinline__ void mma_bf8(float (&c)[4], uint32_t a0, uint32_t a1, uint32_t b0) {
    asm("mma.sync.aligned.m16n8k8.row.col.f32.bf16.bf16.f32 {%0,%1,%2,%3}, {%4,%5}, {%6}, {%0,%1,%2,%3};"
        : "+f"(c[0]), "+f"(c[1]), "+f"(c[2]), "+f"(c[3]) : "r"(a0), "r"(a1), "r"(b0));
}
__device__ __forceinline__ void mma_h(float (&c)[4], uint32_t a0, uint32_t a1, uint32_t a2, uint32_t a3, uint32_t b0, uint32_t b1) {
    asm("mma.sync.aligned.m16n8k16.row.col.f32.f16.f16.f32 {%0,%1,%2,%3}, {%4,%5,%6,%7}, {%8,%9}, {%0,%1,%2,%3};"
        : "+f"(c[0]), "+f"(c[1]), "+f"(c[2]), "+f"(c[3]) : "r"(a0), "r"(a1), "r"(a2), "r"(a3), "r"(b0), "r"(b1));
}
__device__ __forceinline__ uint32_t fresh(uint32_t a) { asm volatile("" : "+r"(a) :: "memory"); return a; }
__device__ __forceinline__ uint32_t lds32(uint32_t a) { uint32_t v; asm("ld.shared.u32 %0, [%1];" : "=r"(v) : "r"(a)); return v; }
__device__ __forceinline__ uint2 lds64(uint32_t a) { uint2 v; asm("ld.shared.v2.u32 {%0,%1}, [%2];" : "=r"(v.x), "=r"(v.y) : "r"(a)); return v; }
__device__ __forceinline__ uint4 lds128(uint32_t a) { uint4 v; asm("ld.shared.v4.u32 {%0,%1,%2,%3}, [%4];" : "=r"(v.x), "=r"(v.y), "=r"(v.z), "=r"(v.w) : "r"(a)); return v; }
__device__ __forceinline__ void ldsm4(uint32_t (&r)[4], uint32_t a) {
    asm("ldmatrix.sync.aligned.m8n8.x4.shared.b16 {%0,%1,%2,%3}, [%4];" : "=r"(r[0]), "=r"(r[1]), "=r"(r[2]), "=r"(r[3]) : "r"(a));
}
__device__ __forceinline__ void ldsm4t(uint32_t (&r)[4], uint32_t a) {
    asm("ldmatrix.sync.aligned.m8n8.x4.trans.shared.b16 {%0,%1,%2,%3}, [%4];" : "=r"(r[0]), "=r"(r[1]), "=r"(r[2]), "=r"(r[3]) : "r"(a));
}
__device__ __forceinline__ void sts16(uint32_t a, uint32_t v) { asm volatile("st.shared.u16 [%0], %1;" :: "r"(a), "h"((unsigned short)v) : "memory"); }
__device__ __forceinline__ void sts32(uint32_t a, uint32_t v) { asm volatile("st.shared.u32 [%0], %1;" :: "r"(a), "r"(v) : "memory"); }
__device__ __forceinline__ void sts64(uint32_t a, uint32_t x, uint32_t y) { asm volatile("st.shared.v2.u32 [%0], {%1,%2};" :: "r"(a), "r"(x), "r"(y) : "memory"); }
__device__ __forceinline__ void sts128(uint32_t a, uint32_t x, uint32_t y, uint32_t z, uint32_t w) {
    asm volatile("st.shared.v4.u32 [%0], {%1,%2,%3,%4};" :: "r"(a), "r"(x), "r"(y), "r"(z), "r"(w) : "memory");
}
__device__ __forceinline__ void st_async128(uint32_t a, uint32_t x, uint32_t y, uint32_t z, uint32_t w, uint32_t bar) {
    asm volatile("st.async.weak.shared::cluster.mbarrier::complete_tx::bytes.v4.b32 [%0], {%1,%2,%3,%4}, [%5];" :: "r"(a), "r"(x), "r"(y), "r"(z), "r"(w), "r"(bar) : "memory");
}
__device__ __forceinline__ void mbar_init(uint32_t b, uint32_t cnt) { asm volatile("mbarrier.init.shared::cta.b64 [%0], %1;" :: "r"(b), "r"(cnt) : "memory"); }
__device__ __forceinline__ void mbar_fence() { asm volatile("fence.mbarrier_init.release.cluster;" ::: "memory"); }
__device__ __forceinline__ void mbar_expect(uint32_t b, uint32_t bytes) { asm volatile("mbarrier.arrive.expect_tx.shared::cta.b64 _, [%0], %1;" :: "r"(b), "r"(bytes) : "memory"); }
__device__ __forceinline__ void mbar_arrive(uint32_t b) { asm volatile("mbarrier.arrive.shared::cta.b64 _, [%0];" :: "r"(b) : "memory"); }
__device__ __forceinline__ void mbar_wait(uint32_t b, uint32_t parity = 0) {
    asm volatile("{ .reg .pred p; .reg .u32 n; mov.u32 n, 0;\n"
                 "LW: mbarrier.try_wait.parity.shared::cta.b64 p, [%0], %1; @p bra LD; add.u32 n, n, 1; setp.lt.u32 p, n, 65536; @p bra LW; trap;\n"
                 "LD: }" :: "r"(b), "r"(parity) : "memory");
}
__device__ __forceinline__ void mbar_wait_cluster(uint32_t b) {
    asm volatile("{ .reg .pred p; .reg .u32 n; mov.u32 n, 0;\n"
                 "LW: mbarrier.try_wait.parity.acquire.cluster.shared::cta.b64 p, [%0], 0; @p bra LD; add.u32 n, n, 1; setp.lt.u32 p, n, 65536; @p bra LW; trap;\n"
                 "LD: }" :: "r"(b) : "memory");
}
__device__ __forceinline__ void tma2d(uint32_t dst, const CUtensorMap* m, int c0, int c1, uint32_t bar) {
    asm volatile("cp.async.bulk.tensor.2d.shared::cluster.global.mbarrier::complete_tx::bytes [%0], [%1, {%3, %4}], [%2];"
                 :: "r"(dst), "l"(m), "r"(bar), "r"(c0), "r"(c1) : "memory");
}
__device__ __forceinline__ void tma3d(uint32_t dst, const CUtensorMap* m, int c0, int c1, int c2, uint32_t bar) {
    asm volatile("cp.async.bulk.tensor.3d.shared::cluster.global.mbarrier::complete_tx::bytes [%0], [%1, {%3, %4, %5}], [%2];"
                 :: "r"(dst), "l"(m), "r"(bar), "r"(c0), "r"(c1), "r"(c2) : "memory");
}
__device__ __forceinline__ void tma4d(uint32_t dst, const CUtensorMap* m, int c0, int c1, int c2, int c3, uint32_t bar) {
    asm volatile("cp.async.bulk.tensor.4d.shared::cluster.global.mbarrier::complete_tx::bytes [%0], [%1, {%3, %4, %5, %6}], [%2];"
                 :: "r"(dst), "l"(m), "r"(bar), "r"(c0), "r"(c1), "r"(c2), "r"(c3) : "memory");
}
__device__ __forceinline__ void bulk_g2s(uint32_t dst, const void* src, uint32_t bytes, uint32_t bar) {
    asm volatile("cp.async.bulk.shared::cluster.global.mbarrier::complete_tx::bytes [%0], [%1], %2, [%3];"
                 :: "r"(dst), "l"(src), "r"(bytes), "r"(bar) : "memory");
}
__device__ __forceinline__ uint32_t mapa(uint32_t a, uint32_t rank) { uint32_t r; asm("mapa.shared::cluster.u32 %0, %1, %2;" : "=r"(r) : "r"(a), "r"(rank)); return r; }
__device__ __forceinline__ void prefetch_map(const CUtensorMap* m) { asm volatile("prefetch.tensormap [%0];" :: "l"(m) : "memory"); }
__device__ __forceinline__ void bar_sync(int id, int n) { asm volatile("bar.sync %0, %1;" :: "r"(id), "r"(n) : "memory"); }
__device__ __forceinline__ void bar_arrive(int id, int n) { asm volatile("bar.arrive %0, %1;" :: "r"(id), "r"(n) : "memory"); }
__device__ __forceinline__ uint32_t ldg16_if(bool c, const void* p) { uint32_t v; asm volatile("{ .reg .pred p; setp.ne.u32 p, %2, 0; @p ld.global.nc.u16 %0, [%1]; }" : "=r"(v) : "l"(p), "r"((uint32_t)c)); return v; }
__device__ __forceinline__ uint32_t ldg32_if(bool c, const void* p) { uint32_t v; asm volatile("{ .reg .pred p; setp.ne.u32 p, %2, 0; @p ld.global.nc.u32 %0, [%1]; }" : "=r"(v) : "l"(p), "r"((uint32_t)c)); return v; }
__device__ __forceinline__ uint32_t ld_rlx32(const void* p) { uint32_t v; asm volatile("ld.relaxed.gpu.global.u32 %0, [%1];" : "=r"(v) : "l"(p) : "memory"); return v; }
__device__ __forceinline__ uint4 ld_rlx128(const void* p) {
    uint4 v; asm volatile("ld.relaxed.gpu.global.v4.u32 {%0,%1,%2,%3}, [%4];" : "=r"(v.x), "=r"(v.y), "=r"(v.z), "=r"(v.w) : "l"(p) : "memory"); return v;
}
__device__ __forceinline__ void st_rlx32(void* p, uint32_t v) { asm volatile("st.relaxed.gpu.global.u32 [%0], %1;" :: "l"(p), "r"(v) : "memory"); }
__device__ __forceinline__ void stg128(void* p, uint32_t x, uint32_t y, uint32_t z, uint32_t w) {
    asm volatile("st.global.v4.u32 [%0], {%1,%2,%3,%4};" :: "l"(p), "r"(x), "r"(y), "r"(z), "r"(w) : "memory");
}
__device__ __forceinline__ void next_epoch(const Params& p, unsigned e) { if ((threadIdx.x & 31) == 0) p.s->epoch[blockIdx.x * 16 + (threadIdx.x >> 5)] = e + 1; }
__device__ __forceinline__ void sts128z_if(bool c, uint32_t a) { asm volatile("{ .reg .pred p; setp.ne.u32 p, %1, 0; @p st.shared.v4.u32 [%0], {%2,%2,%2,%2}; }" :: "r"(a), "r"((uint32_t)c), "r"(0) : "memory"); }
__device__ __forceinline__ void stg128z_if(bool c, void* a) { asm volatile("{ .reg .pred p; setp.ne.u32 p, %1, 0; @p st.global.v4.u32 [%0], {%2,%2,%2,%2}; }" :: "l"(a), "r"((uint32_t)c), "r"(0) : "memory"); }
__device__ __forceinline__ unsigned clock32() { unsigned c; asm volatile("mov.u32 %0, %clock;" : "=r"(c) :: "memory"); return c; }
__device__ __forceinline__ void until(unsigned t0, int c) { while ((int)(clock32() - t0) < c) { } }
__device__ __forceinline__ float sigmoidf_(float x) { return __fdividef(1.0f, 1.0f + __expf(-x)); }
__device__ __forceinline__ uint32_t key_tag(unsigned epoch) { return ((epoch & 15u) | 16u) << 11; }
__device__ __forceinline__ int key_row(uint32_t key) { return 2047 - (int)(key & 2047u); }
__device__ __forceinline__ uint32_t wait_sel(const Params& p, int s32, int r8, uint32_t tag, uint32_t k = 0) {
#pragma unroll 1
    for (int it = 0; !__all_sync(0xffffffffu, (k & 0xf800u) == tag); it++) {
        k = ld_rlx32(&p.s->sel[s32 * 64 + r8]);
        if (it > (1 << 20)) give_up();
    }
    return k;
}

struct cplx { float re, im; };
__device__ __forceinline__ cplx csq(cplx a) { cplx r; r.re = a.re * a.re - a.im * a.im; r.im = (a.re * a.im) * 2.f; return r; }
__device__ __forceinline__ cplx cexpk(float ar, float ai, float k) {
    float mag, s, c;
    asm("ex2.approx.ftz.f32 %0, %1;" : "=f"(mag) : "f"(ar * (k * 1.4426950408889634f)));
    const float r = ai * k;
    asm("sin.approx.ftz.f32 %0, %1;" : "=f"(s) : "f"(r));
    asm("cos.approx.ftz.f32 %0, %1;" : "=f"(c) : "f"(r));
    cplx o; o.re = mag * c; o.im = mag * s; return o;
}
struct h2c { uint32_t re, im; };
__device__ __forceinline__ h2c cmul_cd(h2c v, __half2 c, __half2 d) {
    const __half2 r = *(const __half2*)&v.re, i = *(const __half2*)&v.im;
    const __half2 x = __hfma2(__hneg2(i), d, __hmul2(r, c)), y = __hfma2(i, c, __hmul2(r, d));
    h2c o; o.re = *(const uint32_t*)&x; o.im = *(const uint32_t*)&y; return o;
}
__device__ __forceinline__ h2c cmul_s(h2c v, uint32_t s) { const __half2 h = *(const __half2*)&s; return cmul_cd(v, __low2half2(h), __high2half2(h)); }
__device__ __forceinline__ h2c cmul_sc(h2c v, uint32_t s) {
    const __half2 h = *(const __half2*)&s, c = __low2half2(h), d = __high2half2(h), r = *(const __half2*)&v.re, i = *(const __half2*)&v.im;
    const __half2 x = __hfma2(i, d, __hmul2(r, c)), y = __hfma2(__hneg2(r), d, __hmul2(i, c));
    h2c o; o.re = *(const uint32_t*)&x; o.im = *(const uint32_t*)&y; return o;
}
__device__ __forceinline__ h2c cmul_vc(h2c v, uint32_t s) {
    const __half2 h = *(const __half2*)&s, c = __low2half2(h), d = __high2half2(h), r = *(const __half2*)&v.re, i = *(const __half2*)&v.im;
    const __half2 x = __hfma2(i, d, __hmul2(r, c)), y = __hfma2(__hneg2(i), c, __hmul2(r, d));
    h2c o; o.re = *(const uint32_t*)&x; o.im = *(const uint32_t*)&y; return o;
}

constexpr int UT_HALF = 2560, UT_STRIDE = 4736, GT_HALF = 2240;
__device__ __forceinline__ uint32_t swz(uint32_t x, int c) { return x ^ (((x >> 2) & 64) ^ (64 * (c & 1) + 8 * (c & 6))); }
__device__ __forceinline__ int col(int n) { return (n >> 1) + 4 * (n & 1); }
constexpr int KT_T = 542, KT_C = 552, KT_D = 645, KT_BYTES = 720 * 4;
constexpr int VC_OFF = 80, VE_BASE = 1616;
constexpr int V_STRIDE = (1616 + 1024) * 4 + 80;
constexpr int KG_STAGE = 5248;
constexpr int Y_CS = 2080, Y_RS = 8 * Y_CS + 64;

constexpr int SC_RT = 0;
constexpr int SC_UT = 33408;
constexpr int SC_KG = SC_UT + 8 * UT_STRIDE;
constexpr int SC_KT = SC_KG + 8 * KG_STAGE;
constexpr int SC_GT = SC_KT + 8 * KT_BYTES;
constexpr int SC_V = SC_GT + 4448;
constexpr int SC_MISC = SC_V + 8 * V_STRIDE;
static_assert(V_STRIDE % 128 == 16 && 2 * Y_RS <= SC_UT && SC_UT % 128 == 0 && SC_KG % 128 == 0, "layout");
static_assert(SC_MISC % 16 == 0 && SC_MISC + 512 <= 232192, "layout");

__device__ __forceinline__ void window_task(uint32_t s0, uint32_t s1, uint32_t d0, uint32_t d1, int k) {
    float S[51], s = 0.f;
    uint32_t w[28];
#pragma unroll
    for (int i = 0; i < 7; i++) {
        const uint4 v = lds128(((i < 3 ? s0 : s1) ^ 8 * ((i + 1) & 2)) + ((i & 1) ? 0 : UT_HALF));
        w[4 * i] = v.x; w[4 * i + 1] = v.y; w[4 * i + 2] = v.z; w[4 * i + 3] = v.w;
    }
    auto sums = [&](int lo, int hi) {
#pragma unroll
        for (int i = lo; i < hi; i++) { const float x = (i & 1) ? bf_hi(w[i >> 1]) : bf_lo(w[i >> 1]); s = i > 3 ? s + x : x; S[i] = s; }
    };
    auto put = [&](int off, int b, int o0, int o1, int o2) {
        auto v = [&](int i) { i += 16 * b; return pack_bf16(S[o0 + i] - S[o1 + i], S[o1 + i] - S[o2 + i]); };
#pragma unroll
        for (int i = 0; i < 8; i += 2) sts128((i & 4 ? d1 : d0) + 4 * off + 64 * b + 8 * (i & 2), v(i), v(i + 8), v(i + 1), v(i + 9));
    };
    S[2] = 0.f;
    sums(3, 26); put(VC_OFF - 16, 0, 10, 5, 2);
    if (k == 12) return;
    sums(26, 42); put(VC_OFF - 16, 1, 10, 5, 2);
    if (k < 8) { put(VE_BASE, 0, 19, 12, 3); sums(42, 51); put(VE_BASE, 1, 19, 12, 3); }
}

template <class F, class G>
__device__ __forceinline__ void kgen(const uint32_t (&q)[8], uint32_t sb, int half, uint32_t stage, uint32_t pstage, int barid, int lane, uint32_t (&w)[12], F shadow, G clear) {
    const int t = lane & 3, mi = lane >> 3, r8 = lane & 7;
    {
        const uint32_t pAr = q[0], pAi = q[1], pBr = q[2], pBi = q[3], pCr = q[4], pCi = q[5], pDt = q[6], pD = q[7];
        const uint32_t wb = fresh(stage + lane * 16), za = fresh(stage + 5120 + ((lane >> 1) & 3) * 16 + mi * 4 + (lane & 1) * 2), zr = fresh(stage + 5120 + t * 16);
        const uint32_t oB = fresh(stage + 2048 + mi * 512 + r8 * 16), oC = fresh(stage + 4096 + (mi & 1) * 512 + (mi >> 1) * 128 + r8 * 16);
        float acc[6][4];
#pragma unroll
        for (int a = 0; a < 6; a++) { acc[a][0] = acc[a][1] = acc[a][2] = acc[a][3] = 0.f; asm volatile("" : "+f"(acc[a][0]), "+f"(acc[a][1]), "+f"(acc[a][2]), "+f"(acc[a][3])); }
        shadow();
        sts32(zr, clock32());
        const float dt = rbf(__expf(bf_lo(pDt)));
        float ar = dt * bf_lo(pAr), ai = dt * bf_lo(pAi), ar1 = dt * bf_hi(pAr), ai1 = dt * bf_hi(pAi);
        float wr, wi, wr1, wi1;
        { const float br = dt * bf_lo(pBr), bi = dt * bf_lo(pBi), cr = bf_lo(pCr), ci = bf_lo(pCi); wr = cr * br - ci * bi; wi = cr * bi + ci * br; }
        { const float br = dt * bf_hi(pBr), bi = dt * bf_hi(pBi), cr = bf_hi(pCr), ci = bf_hi(pCi); wr1 = cr * br - ci * bi; wi1 = cr * bi + ci * br; }
        const uint32_t ex = max(__reduce_max_sync(0xffffffffu, __float_as_uint(fmaxf(fmaxf(fabsf(wr), fabsf(wi)), fmaxf(fabsf(wr1), fabsf(wi1))))) >> 23, 14u);
        const float scl = __uint_as_float((267u - ex) << 23);
        uint32_t W = pack_f16(wr * scl, wi * -scl);
        const uint32_t W1 = pack_f16(wr1 * scl, wi1 * -scl);
        if (threadIdx.x < 32) TSTAMP(20);
        clear();

#pragma unroll 1
        for (int r = 0; r < 2; r++) {
            const cplx z1 = cexpk(ar, ai, 1.f), z64 = cexpk(ar, ai, 64.f);
            const cplx z2 = csq(z1), z4 = csq(z2), z8 = csq(z4), z16 = csq(z8), z32 = csq(z16);
            const cplx z128 = csq(z64), z256 = csq(z128), z512 = csq(z256);
            auto put = [&](int grp, h2c a, h2c b, h2c c, h2c d) { sts128(wb + grp * 1024, a.re, b.re, c.re, d.re); sts128(wb + grp * 1024 + 512, a.im, b.im, c.im, d.im); };
            {
                const uint32_t s4 = pack_f16(z4.re, z4.im), s256 = pack_f16(z256.re, z256.im), s512 = pack_f16(z512.re, z512.im);
                auto mix = [](h2c a, h2c b, uint32_t sel) { return h2c{__byte_perm(a.re, b.re, sel), __byte_perm(a.im, b.im, sel)}; };
                const h2c c10 = cmul_vc(h2c{pack_f16(z1.re, 1.f), pack_f16(z1.im, 0.f)}, W), c32 = cmul_sc(c10, pack_f16(z2.re, z2.im)), c54 = cmul_sc(c10, s4);
                put(2, c10, c32, c54, cmul_sc(c32, s4));
                const h2c d20 = cmul_sc(mix(c32, c10, 0x7632), s256), e04 = cmul_sc(mix(c10, c54, 0x7632), s512), f04 = cmul_sc(e04, s256);
                put(3, d20, cmul_sc(d20, s4), e04, f04);
                const h2c ef = mix(e04, f04, 0x5410), gh = cmul_sc(ef, s512), g8 = cmul_sc(gh, pack_f16(z8.re, z8.im));
                put(4, g8, cmul_sc(g8, s512), gh, ef);
            }
            {
                const uint32_t s32 = pack_f16(z32.re, z32.im), s64 = pack_f16(z64.re, z64.im), s128 = pack_f16(z128.re, z128.im);
                const h2c p0 = {pack_f16(1.f, z8.re), pack_f16(0.f, z8.im)}, p1 = cmul_s(p0, pack_f16(z16.re, z16.im)), p2 = cmul_s(p0, s32), p3 = cmul_s(p1, s32);
                put(0, p0, p1, p2, p3);
                sts16(za - 4096, s64); sts16(za - 4032, s64 >> 16);
                sts16(za, s128); sts16(za + 64, s128 >> 16);
            }
            __syncwarp();
            {
                const uint32_t aB = fresh(oB), aC = fresh(oC), aZ = fresh(zr);
                const uint4 zc = lds128(aZ), zd = lds128(aZ + 64);
                const uint32_t zcs[4] = {zc.x, zc.y, zc.z, zc.w}, zds[4] = {zd.x, zd.y, zd.z, zd.w};
                const uint4 yc = lds128(aZ - 4096), yd = lds128(aZ - 4032);
                const uint32_t ycs[4] = {yc.x, yc.y, yc.z, yc.w}, yds[4] = {yd.x, yd.y, yd.z, yd.w};
                uint32_t c[4];
#pragma unroll
                for (int k = 0; k < 4; k++) {
                    uint32_t a[4], b[4];
                    for (int e = 0; e < 2; e++) asm("ldmatrix.sync.aligned.m8n8.x1.trans.shared.b16 {%0}, [%1];" : "=r"(a[2 * e]) : "r"(aB - 2048 + 128 * k + 512 * e));
                    const h2c a1 = cmul_cd(h2c{a[0], a[2]}, *(const __half2*)&ycs[k], *(const __half2*)&yds[k]);
                    a[1] = a1.re; a[3] = a1.im;
                    ldsm4t(b, aB + 128 * k);
                    if (!(k & 1)) ldsm4t(c, aC + 128 * k);
                    const h2c x = cmul_cd(h2c{a[0], a[2]}, *(const __half2*)&zcs[k], *(const __half2*)&zds[k]), y = cmul_cd(h2c{a[1], a[3]}, *(const __half2*)&zcs[k], *(const __half2*)&zds[k]);
                    mma_h(acc[0], a[0], a[1], a[2], a[3], b[0], b[1]);
                    mma_h(acc[1], a[0], a[1], a[2], a[3], b[2], b[3]);
                    mma_h(acc[2], a[0], a[1], a[2], a[3], c[2 * (k & 1)], c[2 * (k & 1) + 1]);
                    mma_h(acc[3], x.re, y.re, x.im, y.im, b[0], b[1]);
                    mma_h(acc[4], x.re, y.re, x.im, y.im, b[2], b[3]);
                    mma_h(acc[5], x.re, y.re, x.im, y.im, c[2 * (k & 1)], c[2 * (k & 1) + 1]);
                }
                asm volatile("" :: "f"(acc[0][0]), "f"(acc[1][0]), "f"(acc[2][0]), "f"(acc[3][0]), "f"(acc[4][0]), "f"(acc[5][0]) : "memory");
            }
            __syncwarp();
            ar = ar1; ai = ai1; W = W1;
        }
        if (threadIdx.x < 32) TSTAMP(21);
        const float i0 = __uint_as_float((ex + 243u) << 23);
        if (half) {
#pragma unroll
            for (int a = 0; a < 6; a++) { acc[a][0] *= i0; acc[a][1] *= i0; acc[a][2] *= i0; acc[a][3] *= i0; }
            if (lane == 0) acc[0][1] -= bf_lo(pD);
#pragma unroll
            for (int a = 0; a < 6; a++) sts128(wb + a * 512, __float_as_uint(acc[a][0]), __float_as_uint(acc[a][1]), __float_as_uint(acc[a][2]), __float_as_uint(acc[a][3]));
            bar_arrive(barid, 64);
        } else {
            bar_sync(barid, 64);
            const uint32_t src = fresh(pstage);
#pragma unroll
            for (int a = 0; a < 6; a++) {
                const uint4 y = lds128(src + lane * 16 + a * 512);
                auto sum = [&](uint32_t x, float c) { return fmaf(c, i0, __uint_as_float(x)); };
                w[4 * (a % 3) + 2 * (a / 3)] = pack_bf16(sum(y.x, acc[a][0]), sum(y.y, acc[a][1]));
                w[4 * (a % 3) + 2 * (a / 3) + 1] = pack_bf16(sum(y.z, acc[a][2]), sum(y.w, acc[a][3]));
            }
            const uint32_t x0 = __shfl_up_sync(0xffffffffu, w[10], 2), x1 = __shfl_up_sync(0xffffffffu, w[11], 2);
            w[10] = w[8];
            if (t >= 2) { w[8] = x0; w[9] = x1; }
        }
    }
}

enum { BC_AUX = 0, BC_U = 5  , BC_Y = 13   };

__device__ __forceinline__ void fetch_gates(const Params& p, int i, int lane, unsigned epoch, uint32_t dst) {
    const uint32_t par = (epoch & 1) ? 0x80008000u : 0u;
    uint4 v;
#pragma unroll 1
    for (int it = 0;; it++) {
        v = ld_rlx128(p.s->gate + 256 * i + 8 * lane);
        v.x ^= par; v.y ^= par; v.z ^= par; v.w ^= par;
        if (__all_sync(0xffffffffu, (v.x & v.y & v.z & v.w & 0x80008000u) == 0x80008000u)) break;
        if (it > (1 << 20)) give_up();
    }
    sts128(dst, v.x, v.y, v.z, v.w);
}
__device__ __forceinline__ void store_rows(const CUtensorMap* m, uint32_t src, int col, int row) {
    asm volatile("cp.async.bulk.tensor.5d.global.shared::cta.bulk_group [%0, {%2, %3, %3, %3, %4}], [%1];" :: "l"(m), "r"(src), "r"(col), "r"(0), "r"(row) : "memory");
}

__device__ __forceinline__ void store_or_add(void* o, const uint32_t (&y)[4], uint32_t add) {
    asm volatile("{ .reg .pred p; setp.ne.u32 p, %5, 0; @!p st.global.v4.u32 [%0], {%1,%2,%3,%4}; @p red.relaxed.gpu.global.add.noftz.v4.bf16x2 [%0], {%1,%2,%3,%4}; }"
                 :: "l"(o), "r"(y[0]), "r"(y[1]), "r"(y[2]), "r"(y[3]), "r"(add) : "memory");
}

__device__ __forceinline__ void conv_aux(const Params& p, const CUtensorMap* mU, uint32_t sb, int aw, int lane, int bid, unsigned epoch) {
    const int g = lane >> 2, t = lane & 3, mi = lane >> 3, r8 = lane & 7;
    const int rank = bid & 1, slab = bid >> 1;
    const uint32_t bar_y = sb + SC_MISC, bar_u = bar_y  , bar_v = bar_y + 8, bar_box = bar_y + 64 + 8 * aw, s_bm = bar_y + 128;
    if (elect()) {
        mbar_init(bar_box, 1); mbar_fence();
        mbar_expect(bar_box, 4096);
        tma4d(sb + SC_RT + 4096 * aw, mU, 16 * slab, 0, 0, 16 * rank + 2 * aw, bar_box);
        mbar_init(bar_y + 8 * aw, aw == 1 ? 8 : 1);
        if (aw == 1) mbar_init(bar_y + 384, 1);
        mbar_fence();
        if (aw != 1) mbar_expect(bar_y + 8 * aw, aw ? 4096 : 16384);
    }
    __syncwarp();
    asm volatile("barrier.cluster.arrive.relaxed.aligned;" ::: "memory");
    asm volatile("setmaxnreg.dec.sync.aligned.u32 88;");
    sts128(sb + (lane < 16 ? SC_UT + aw * UT_STRIDE + mi * (UT_HALF - 128) : SC_V - 256 + aw * V_STRIDE) + lane * 16, 0, 0, 0, 0);
    if (lane < 16) sts128(s_bm + lane * 16, 0, 0, 0, 0);
    {
        const uint32_t dst = sb + SC_UT + g * UT_STRIDE + swz((8 + 64 * rank + 8 * aw + t) * 16, g);
        const uint32_t rdst = mapa(dst, rank ^ 1), rbar = mapa(bar_u, rank ^ 1);
        asm volatile("barrier.cluster.wait.acquire.aligned;" ::: "memory");
        mbar_wait(bar_box);
        if (aw == 0) TSTAMP(1);
        const uint32_t src = fresh(sb + SC_RT) + aw * 4096 + (8 * mi + 4 * (r8 & 1) + (r8 >> 1)) * 32 + ((rank ^ (r8 & 1)) << 4);
        uint32_t x[8][4];
#pragma unroll
        for (int i = 0; i < 4; i++) { ldsm4t(x[i], src + 1024 * i); ldsm4t(x[4 + i], (src ^ 16) + 1024 * i); }
        asm volatile("" :: "r"(x[0][0]), "r"(x[1][0]), "r"(x[2][0]), "r"(x[3][0]) : "memory");
#pragma unroll
        for (int i = 0; i < 4; i++) st_async128((rdst ^ 32 * (i & 2)) + (i & 1) * UT_HALF, x[4 + i][0], x[4 + i][1], x[4 + i][2], x[4 + i][3], rbar);
#pragma unroll
        for (int i = 0; i < 4; i++) sts128((dst ^ 32 * (i & 2)) + (i & 1) * UT_HALF, x[i][0], x[i][1], x[i][2], x[i][3]);
    }
    bar_sync(BC_AUX, 256);
    mbar_wait_cluster(bar_u);
    if (aw == 0) TSTAMP(2);
    if (aw == 6 && elect()) mbar_arrive(bar_y + 384);
    if (aw < 4) bar_sync(BC_U + aw, 64);
    if (aw == 0) TSTAMP(3);
    {
        const uint32_t ws = fresh(sb + SC_UT) + r8 * UT_STRIDE, wd = sb + SC_V + r8 * V_STRIDE;
#pragma unroll 1
        for (int k = aw; k < 13; k += 8) {
            const int a = 8 * k + (k < 12 ? g & 6 : 0);
            const uint32_t d = wd + 64 * a, sw = 16 * (a & 2);
            window_task(ws + swz(16 * a + 96, r8), ws + swz(16 * a + 128, r8), d + sw, d + (sw ^ 32), k);
            if ((k & 12) == 4) bar_arrive(BC_U + k - 4, 64);
        }
    }
    if (aw == 0) TSTAMP(9);
    {
        if (aw >= 2) fetch_gates(p, aw, lane, epoch, sb + SC_GT + (lane & 1) * GT_HALF + (8 + 16 * aw + (lane >> 1)) * 16);
        __syncwarp();
        if (elect()) { mbar_arrive(bar_v); prefetch_map(mU + 4); p.s->epoch[fresh(bid) * 16 + aw + 8] = epoch + 1; }
        if (aw == 0) TSTAMP(4);
        if (aw == 7) {
            const int row = key_row(wait_sel(p, slab >> 1, r8, key_tag(epoch)));
            if (lane < 8) asm volatile("red.shared.or.b32 [%0], %1;" :: "r"(s_bm + (row >> 5) * 4), "r"(1u << (row & 31)) : "memory");
            TSTAMP(10);
        }
        bar_sync(BC_AUX, 256);
        const uint32_t src = sb + SC_RT + ((r8 >> 1) & 1) * Y_RS + (2 * mi + (r8 & 1)) * Y_CS + (2 * aw + (r8 >> 2)) * 16;
        const int rb = 64 * (aw & 4) + 32 * (aw & 1) + ((aw >> 1) & 1) + 2 * rank, row0 = rb + 128 * (g >> 2) + 16 * (t >> 1) + 64 * (g & 1) + 8 * ((g >> 1) & 1);
        __nv_bfloat16* outp = p.out + (size_t)row0 * DM + 16 * slab + 8 * (t & 1);
        const uint32_t stg = sb + SC_KG + 4096 * aw, so = (g & 2) * 256 + (g >> 2) * 128 + r8 * 16;
#pragma unroll 1
        for (int s = 1; s < 4; s++) {
            const uint32_t bm = lds32(fresh(s_bm) + (16 * s + (row0 >> 5)) * 4) >> (row0 & 31);
            const bool routed = __any_sync(0xffffffffu, bm & 0x11u);
            if ((aw & 3) == s) mbar_wait_cluster(bar_y + 16 * s + 2 * (aw & 4));
            bar_sync(BC_Y + (aw >> 2), 128);
            const uint32_t sf = fresh(src) + 512 * s;
            uint32_t y[2][4];
            ldsm4t(y[0], sf); ldsm4t(y[1], sf + 256);
            if (routed) {
#pragma unroll
                for (int k = 0; k < 2; k++) store_or_add(outp + (size_t)(512 * s + 4 * k) * DM, y[k], bm & (1u << (4 * k)));
            } else {
                sts128(stg + so + 1024 * s, y[0][0], y[0][1], y[0][2], y[0][3]); sts128(stg + so + 1024 * s + 256, y[1][0], y[1][1], y[1][2], y[1][3]);
                asm volatile("fence.proxy.async.shared::cta;" ::: "memory");
                __syncwarp();
                if (elect()) store_rows(mU + 4, stg + 1024 * s, 16 * slab, 512 * s + rb);
            }
            if (aw == 4) TSTAMP(16 + s);
            if (aw == 0) TSTAMP(16);
        }
        if (elect()) { asm volatile("cp.async.bulk.commit_group;" ::: "memory"); asm volatile("cp.async.bulk.wait_group.read 0;" ::: "memory"); }
        if (aw == 4) TFLUSH();
    }
}

__device__ __forceinline__ uint32_t k_tag(unsigned epoch) { return epoch & 1 ? 0x10000u : 1u; }
__device__ __forceinline__ void publish_k(uint4* kp, int lane, bool all, const uint32_t (&w)[12], unsigned epoch, uint64_t (&v)[4]) {
    auto tag = [&](uint32_t x) { return (x & 0xfffefffeu) | k_tag(epoch); };
#pragma unroll
    for (int i = 0; i < 2; i++) {
        v[2 * i] = w[4 * i] | (uint64_t)w[4 * i + 1] << 32; v[2 * i + 1] = w[4 * i + 2] | (uint64_t)tag(w[4 * i + 3]) << 32;
        asm volatile("st.relaxed.gpu.global.v2.u64 [%0], {%1,%2};" :: "l"(kp + 32 * i), "l"(v[2 * i]), "l"(v[2 * i + 1]));
    }
    asm volatile("{ .reg .pred p, q; setp.ne.u32 p, %6, 0; setp.lt.and.s32 q, %5, 4, p;\n"
                 "@p st.relaxed.gpu.global.v2.u32 [%0 + 1024], {%1,%2}; @q st.relaxed.gpu.global.v2.u32 [%0 + 1280], {%3,%4}; }"
                 :: "l"((uint2*)kp - lane), "r"(w[8]), "r"(tag(w[9])), "r"(w[10]), "r"(k_tag(epoch)), "r"(lane), "r"((uint32_t)all));
}
template <bool FULL>
__device__ __forceinline__ void k_tables(uint32_t kt, int lane, const uint32_t (&w)[12]) {
    const int g = lane >> 2, t = lane & 3, mi = lane >> 3, r8 = lane & 7;
    uint32_t x3 = w[7], re[4], rx[4];
#pragma unroll
    for (int i = 0; i < 4; i++) {
        re[i] = __shfl_sync(0xffffffffu, w[i], lane + 31);
        rx[i] = __shfl_sync(0xffffffffu, w[4 + i], lane + (i == 0 && lane == 29 ? 5 : 1 + 2 * t));
    }
    if (FULL) {
        asm volatile("stmatrix.sync.aligned.m8n8.x2.trans.shared.b16 [%0], {%1,%2};" :: "r"(kt + (KT_D + 7) * 4 + 64 * t + 16 * (mi & 1) + 8 * (r8 & 4)), "r"(w[8]), "r"(w[9]) : "memory");
        if (lane == 2) {
            sts32(kt + (KT_C + 78) * 4, w[10] & 0xffffu);
            sts128(kt + (KT_T + 2) * 4, 0, w[10] & 0xffffu, __byte_perm(w[10], 0, 0x1010), w[10] << 16);
        }
        if (lane == 29) x3 = bsub2(x3, rx[0] & 0xffffu);
    }
#pragma unroll
    for (int i = 0; i < 4; i++) {
        sts64(kt + (16 + 64 * i) * 4 + 8 * lane, __byte_perm(w[i], lane ? re[i] : i ? re[i - 1] : 0, 0x5432), w[i]);
        const uint32_t x = i < 3 ? w[4 + i] : x3, aa = __byte_perm(x, 0, 0x3232);
        if (t < 2) sts128(kt + (272 + 64 * i + 8 * g + 4 * t) * 4, i == 0 && lane == 0 ? __byte_perm(x, re[3], 0x5432) : aa, aa, x,
                          __byte_perm(lane != 29 ? rx[i] : i < 3 ? rx[(i + 1) & 3] : FULL ? 0 : rx[0] << 16, x, 0x5432));
        else if (FULL) sts32(kt + (KT_C - 50 + 8 * i + 32 * t + g) * 4, x);
    }
}

__device__ __forceinline__ void conv_main(const Params& p, uint32_t sb, int warp, int lane0, int bid, unsigned epoch, uint32_t (&w)[12]) {
    asm volatile("setmaxnreg.inc.sync.aligned.u32 168;");
    const int lane = __shfl_sync(0xffffffffu, lane0, lane0);
    const int g = lane >> 2, t = lane & 3, mi = lane >> 3, r8 = lane & 7;
    const int rank = bid & 1;
    const uint32_t bar_y = sb + SC_MISC, bar_v = bar_y + 8;
    next_epoch(p, epoch);
    asm volatile("barrier.cluster.wait.acquire.aligned;" ::: "memory");
    if (warp >= 4) {
        mbar_wait(bar_y + 384);
        if (KPOLL) until(clock32(), KPOLL);
        const uint4* src = p.s->kp + (8 * bid + warp) * 96 + lane0;
#pragma unroll 1
        for (int it = 0;; it++) {
#pragma unroll
            for (int i = 0; i < 2; i++) { const uint4 v = ld_rlx128(src + 32 * i); w[4 * i] = v.x; w[4 * i + 1] = v.y; w[4 * i + 2] = v.z; w[4 * i + 3] = v.w; }
            asm volatile("ld.relaxed.gpu.global.v2.u32 {%0,%1}, [%2 + 1024];" : "=r"(w[8]), "=r"(w[9]) : "l"((const uint2*)src - lane0) : "memory");
            asm volatile("ld.relaxed.gpu.global.v2.u32 {%0,%1}, [%2 + 1296];" : "=r"(w[10]), "=r"(w[11]) : "l"(src - lane0) : "memory");
            const bool ok = __all_sync(0xffffffffu, w[3] & w[7] & w[9] & w[11] & k_tag(epoch));
            if (ok) break;
            if (it > (1 << 20)) give_up();
        }
    }
    if ((warp & 3) == 0) TSTAMP(5 + (warp >> 2));
    k_tables<true>(sb + SC_KT + warp * KT_BYTES, lane0, w);
    mbar_wait(bar_y + 384);
    __syncwarp();
    if ((warp & 3) == 0) TSTAMP(7 + (warp >> 2));
    {
        const uint32_t ut = fresh(sb + SC_UT) + warp * UT_STRIDE, kt = fresh(sb + SC_KT) + warp * KT_BYTES;
        auto dup = [&](uint32_t v) { return v ^ p.zero; };
        auto frag = [&](uint32_t (&a)[4], uint32_t x) { a[0] = lds32(x); a[1] = lds32(x + 32); a[2] = lds32(x - 32); a[3] = dup(a[0]); };
        const uint32_t kb = kt + (16 + g - 2 * t) * 4;
        float acc[16][4];
        const uint32_t lo = (8 + col(r8)) * 16 + (mi >> 1) * 128;
        uint32_t u1[2];
        {
            float y[12][4], M[6][4];
#pragma unroll
            for (int i = 0; i < 12; i++) { y[i][0] = y[i][1] = y[i][2] = y[i][3] = 0.f; M[i >> 1][0] = M[i >> 1][1] = M[i >> 1][2] = M[i >> 1][3] = 0.f; }
            uint32_t U[10][4], a1[4], ad[4], R = (mi & 1) * UT_HALF + (8 + (r8 >> 1) + 48 * (r8 & 1)) * 16 + 64 * (mi >> 1);
            R = R * 0x10001u + 0x800000u;
            const uint32_t cx = swz(0, warp) * 0x10001u;
            auto places = [&](uint32_t r) { r ^= ((r >> 2) & 0x400040u) ^ cx; ad[0] = r & 0xffffu; ad[1] = r >> 16; ad[2] = ad[0] ^ 64; ad[3] = ad[1] ^ 64; };
            const uint32_t Rn = fresh((mi & 1) * UT_HALF + lo + ((UT_HALF + (7 + 8 * mi + col(r8)) * 16) << 16));
            auto ldu = [&](int k) { ldsm4(U[k], ut + ad[k & 3] + 256 * (k >> 1)); };
            places(R);
            frag(a1, kb + 2048);
#pragma unroll
            for (int k = 0; k < 7; k++) ldu(k);
#pragma unroll
            for (int i = 0; i < 12; i++) mma_bf(y[i], a1[0], a1[1], a1[2], a1[3], U[i >> 1][2 * (i & 1)], U[i >> 1][2 * (i & 1) + 1]);
            frag(a1, kb + 1792);
            __syncwarp();
#pragma unroll 1
            for (uint32_t ko = 0; ko != 256;) {
                ko = fresh(ko);
                const uint32_t kp = kb + ko;
                ko += 64;
                uint32_t se[10][2], so[10][2], ue[10][2];
                auto sums = [&](int k) {
#pragma unroll
                    for (int e = 0; e < 2; e++) { ue[k][e] = U[k][e]; se[k][e] = badd2(U[k][e], U[k - 1][2 + e]); so[k][e] = badd2(U[k][e], U[k][2 + e]); }
                };
#pragma unroll
                for (int k = 1; k < 6; k++) sums(k);
#pragma unroll
                for (int m = 3; m >= 0; m--) {
                    uint32_t a0[4];
                    frag(a0, kp + 512 * m);
                    sums(9 - m);
                    if (m) ldu(10 - m); else { R = ko == 256 ? Rn : R - 0x100010u; places(R); }
#pragma unroll
                    for (int i = 0; i < 6; i++) mma_bf(y[2 * i], a1[0], a1[1], a1[2], a1[3], se[i - m + 4][0], se[i - m + 4][1]);
#pragma unroll
                    for (int e = 0; e < 4; e++) a1[e] = bsub2(a0[e], a1[e]);
#pragma unroll
                    for (int i = 0; i < 6; i++) { mma_bf(M[i], a1[0], a1[1], a1[2], a1[3], ue[i - m + 4][0], ue[i - m + 4][1]); if (!m) ldu(i); }
                    frag(a1, m ? kp + 512 * m - 256 : kp + 1792 + 64);
                    if (!m) ldu(6);
#pragma unroll
                    for (int i = 0; i < 6; i++) mma_bf(y[2 * i + 1], a0[0], a0[1], a0[2], a0[3], so[i - m + 4][0], so[i - m + 4][1]);
                }
            }
#pragma unroll
            for (int i = 0; i < 6; i++)
#pragma unroll
                for (int c = 0; c < 4; c++) { acc[4 + i + 6 * (c & 1)][c & 2] = y[2 * i][c] + M[i][c]; acc[4 + i + 6 * (c & 1)][c | 1] = y[2 * i + 1][c] - M[i][c]; }
            frag(a1, kb + (KT_T - 16) * 4);
            const uint32_t f0 = dup(a1[1]), f1 = lds32(kb + KT_T * 4);
#pragma unroll
            for (int i = 0; i < 8; i++) mma_bf8(acc[8 + i], f0, f1, U[1 + (i & 4)][i & 3]);
#pragma unroll
            for (int i = 0; i < 8; i++) mma_bf(acc[8 + i], a1[0], a1[1], a1[2], a1[3], U[i & 6][2 * (i & 1)], U[i & 6][2 * (i & 1) + 1]);
            u1[0] = ut + ad[0]; u1[1] = ut + ad[2];
        }
        if ((warp & 3) == 0) TSTAMP(11 + (warp >> 2));
        mbar_wait(bar_v);
        const uint32_t vt = fresh(sb + SC_V) + warp * V_STRIDE;
        const uint32_t g1 = fresh(sb + SC_GT) + (mi & 1) * GT_HALF + lo;
        const uint32_t ydst = mapa(sb + SC_RT + rank * Y_RS + warp * Y_CS + (lane & 23) * 16, mi & 1), ybr = mapa(bar_y, mi & 1);
        uint32_t ug[2][2][4];
        auto ld_ug = [&](int i) { ldsm4t(ug[i & 1][0], u1[i & 1] + 256 * i); ldsm4t(ug[i & 1][1], g1 + 256 * i); };
        auto ship = [&](int i) {
            const uint32_t (&u)[4] = ug[i & 1][0], (&gg)[4] = ug[i & 1][1];
            const uint32_t y0 = gmix(gg[0], acc[2 * i][0], acc[2 * i][1], u[0]), y1 = gmix(gg[1], acc[2 * i][2], acc[2 * i][3], u[1]);
            const uint32_t y2 = gmix(gg[2], acc[2 * i + 1][0], acc[2 * i + 1][1], u[2]), y3 = gmix(gg[3], acc[2 * i + 1][2], acc[2 * i + 1][3], u[3]);
            st_async128(ydst + 512 * (i >> 1) + 128 * (i & 1), y0, y1, y2, y3, ybr + 8 * i);
        };
        const uint32_t VD = vt + (VC_OFF - 400 - 16 * t) * 4 + (8 * g ^ 16 * (-t & 2)), VD2 = vt + (VC_OFF - 415 - 16 * t) * 4 + (8 * g ^ 16 * (~t & 2));
        uint2 bd[10];
        uint32_t x[2][4][4];
        auto ld4 = [&](uint32_t (&v)[4], int dl) { const uint2 w = lds64(VD + 256 * dl); v[0] = w.x; v[1] = w.y; v[2] = lds32(VD2 + 256 * dl); v[3] = dup(w.x); };
        auto mm4 = [&](const uint32_t (&v)[4], int dl) {
#pragma unroll
            for (int s = dl & 1; s < 10; s += 2) if ((dl + s) / 2 >= 4 && (dl + s) / 2 < 16) mma_bf(acc[(dl + s) / 2], v[0], v[1], v[2], v[3], bd[s].x, bd[s].y);
        };
        const uint32_t KE = kt + (KT_D + col(g) + t) * 4, VE = vt + (VE_BASE - 912 - 16 * t) * 4 + (8 * g ^ 16 * (~t & 2));
        uint32_t b0[8], b1[8];
        auto ld8 = [&](uint32_t (&v)[4], int dl) { const uint2 w = lds64(VE + 512 * dl), z = lds64(VE + 512 * dl - 256); v[0] = w.x; v[1] = w.y; v[2] = z.x; v[3] = z.y; };
        auto mm8 = [&](const uint32_t (&v)[4], int dl, int lo, int hi) {
#pragma unroll
            for (int s = 0; s < 8; s++) if (dl + s >= lo && dl + s < hi) mma_bf(acc[dl + s], v[0], v[1], v[2], v[3], b0[s], b1[s]);
        };
        ld4(x[0][0], 6);
#pragma unroll
        for (int s = 0; s < 10; s++) bd[s] = lds64(kt + (KT_C + 2 * col(g) + 2 * t + 8 * s) * 4);
        mm4(x[0][0], 6);
        uint32_t e[8][4];
#pragma unroll
        for (int k = 1; k < 6; k++) {
#pragma unroll
            for (int j = 0; j < 4; j++) ld4(x[k & 1][j], 4 * k + 3 + j);
            ld_ug(k + 1);
            if (k == 2) {
#pragma unroll
                for (int s = 0; s < 8; s++) { b0[s] = lds32(KE + 32 * s); b1[s] = lds32(KE + 32 * s + 16); }
            }
            if (k > 1) ship(k);
#pragma unroll
            for (int j = 0; j < 4; j++) {
                mm4(x[k & 1][j], 4 * k + 3 + j);
                if (k == 2) { ld8(e[j], 8 + j); mm8(e[j], 8 + j, 8, 12); }
                if (k == 4) mm8(e[j], 8 + j, 12, 14);
                if (k == 5 && j < 2) { ld8(e[4 + j], 12 + j); mm8(e[4 + j], 12 + j, 12, 14); }
            }
        }
        ld_ug(7);
        {
            float (&q0)[4] = acc[0], (&q1)[4] = acc[1];
#pragma unroll
            for (int c = 0; c < 4; c++) q0[c] = q1[c] = 0.f;
            auto m8 = [&](float (&c)[4], int T, int j) { mma_bf(c, e[j][0], e[j][1], e[j][2], e[j][3], b0[T - 8 - j], b1[T - 8 - j]); };
            auto m4 = [&](float (&c)[4], int T, int j) { mma_bf(c, x[0][j][0], x[0][j][1], x[0][j][2], x[0][j][3], bd[2 * T - 27 - j].x, bd[2 * T - 27 - j].y); };
            ship(6);
            ld8(e[6], 14); ld8(e[7], 15);
#pragma unroll
            for (int j = 0; j < 4; j++) ld4(x[0][j], 27 + j);
            m8(q1, 15, 0); m8(q0, 14, 0); m8(q1, 15, 1);
            m8(acc[15], 15, 6); m4(q1, 15, 0); m8(acc[14], 14, 6); m4(q0, 14, 0);
            m8(acc[15], 15, 4); m8(q1, 15, 2); m4(acc[14], 14, 1); m8(q0, 14, 1);
            m4(acc[15], 15, 1); m4(q1, 15, 2); m8(acc[14], 14, 4); m8(q0, 14, 2);
            m8(acc[15], 15, 5); m8(q1, 15, 3); m8(acc[14], 14, 5); m8(q0, 14, 3);
            m4(acc[15], 15, 3); m8(q1, 15, 7);
#pragma unroll
            for (int c = 0; c < 4; c++) { acc[14][c] += q0[c]; acc[15][c] += q1[c]; }
            ship(7);
        }
        if ((warp & 3) == 0) TSTAMP(14 + (warp >> 2)); else TSTAMP(21 + warp);
    }
}

constexpr int SF_WD = 73728;
constexpr int SF_RED = 49152;
constexpr int MU_STRIDE = 1168  , SM_RAW = 98304, SM_UT = SM_RAW + 16384, SM_G = SM_UT + 21504, SM_Y = 196608, SM_FT = SM_Y + 17024, SM_KT = 138880, SM_KW = SM_G - 49152;
constexpr int SF_XS = 221184;
constexpr int SF_MISC = SF_XS + 8 * 1168;
constexpr int SF_KG = SF_MISC - 10 * KG_STAGE;
constexpr int SF_WR = SF_KG - 2304;
constexpr int FB_X = 64, FB_KDONE = 72, FB_KEYS = 80, FB_FREE = 88  , FB_W = 104, FB_D = FB_W + 72, FB_MU = FB_D + 96, FB_FAR = FB_MU - 16, FB_MG = FB_MU + 8, FB_MT = FB_MU + 16  , FS_PART = 512, FS_TOK = 896, FS_BM = 1024;
enum { BAR_R = 7, BAR_GU = 8, BAR_RED = 9, BAR_R2 = 10, BAR_G = 12  , BAR_M = 15 };
static_assert(SF_KG % 128 == 0 && NPRE <= 8 && SM_KT + 4 * 2112 <= 147456 && SM_G + MU_STRIDE <= SF_WR - 4 * 9216 && SM_KW + 6 * 2112 >= SM_RAW && SM_KW + 12 * 2112 <= SM_UT, "layout");

__device__ __forceinline__ constexpr int box_no(int i) { return (0x987610ba5432ull >> (4 * i)) & 15; }
__device__ __forceinline__ int role(int b) { b -= NCONV; return b < NX ? b : 18 + (b >> 1) + 12 * (b & 1); }
__device__ __forceinline__ int mini_ch0(int f) { return 48 * f - (f < NW ? 1696 : 2304); }

__device__ __forceinline__ void ffn_front(const Params& p, const CUtensorMap* maps, uint32_t sb, int warp, int lane, int f, unsigned epoch) {
    const unsigned t0 = clock32();
    const int g = lane >> 2, t = lane & 3, mi = lane >> 3, r8 = lane & 7;
    const bool isx = f < NX;
    const int nrw = f < 52 ? 4 : 6, r0 = f < 52 ? 32 * f : 48 * f - 832;
    const int rw = warp < 12 ? 13 - warp : warp ^ (warp < 14 ? 10 : 15);
    const uint32_t bar_row = sb + SF_MISC  , bar_x = bar_row + FB_X;
    const uint32_t s_part = bar_row + FS_PART  , s_tok = bar_row + FS_TOK  ;
    const uint32_t rows = sb + SF_WR - 9216 * (rw + 1) - (rw & 4) * ((SF_WR - 6 * 9216) / 4);
    {
#pragma unroll 1
        for (int i = warp < 10 ? 30 : warp - 10; i < 30; i += 6) if (elect()) mbar_init(bar_x + 8 * i, i == 1 ? 4 + (f < NW) : i < 27 ? 1 : i == 27 ? 2 : 8);
        const uint32_t bytes = rw < 6 ? 9216 : 1152, dst = rw < 6 ? rows : sb + SF_WR + (rw & 1) * 1152;
        const __nv_bfloat16* src = rw < 6 ? p.u + (size_t)(r0 + 8 * rw) * DM : (rw & 1) ? p.gatew : p.wr;
        if (elect()) { mbar_init(bar_row + 8 * rw, 1); mbar_fence(); mbar_expect(bar_row + 8 * rw, bytes); }
        if (warp == 13) { sts32(s_part + 64 + lane * 4, 0); sts32(bar_row + FS_BM + lane * 4, 0); }
        bar_sync(0, NTHR);
        if (!isx) asm volatile("barrier.cluster.arrive.relaxed.aligned;" ::: "memory");
        if (rw < nrw) until(t0, RDELAY);
        if (rw < nrw || rw >= 6) { if (elect()) bulk_g2s(dst, src, bytes, bar_row + 8 * rw); }
    }
    uint4* const kdst = p.s->keys + (lane >> 1) * 128 + 2 * f + (lane & 1);
    if (warp == 15) TSTAMP(1);

    if (warp == 12) {
        if (lane < 22) mbar_expect(bar_row + FB_W + 8 * lane, lane < 9 ? 24576 : isx ? 12288 : lane < 20 ? 2048 : 16384);
        if (elect()) { prefetch_map(maps + 1); prefetch_map(maps + 2); prefetch_map(maps + (isx ? 3 : 5)); }
        unsigned tb = t0 + WDELAY;
        auto pieces = [&](int n, int end, uint32_t dst) {
#pragma unroll 1
            for (; n < end; n++, dst += 12288) {
                until(tb, 0); tb += WGAP;
                if (elect()) tma3d(dst, maps + 1 + (n & 1), 0, 64 * (n >> 1), 3 * f, bar_row + FB_W + 8 * (n >> 1));
            }
        };
        if (!isx) {
#pragma unroll 1
            for (int k = 0; k <= (f >= NW); k++) { until(t0, MDELAY); if (elect()) tma4d(sb + SM_RAW - 49152 * k, maps + 5, mini_ch0(f) + 16 * k, 0, 0, 0, bar_row + FB_MU - 8 * k); }
            if (f >= NW) return;
        }
#pragma unroll 1
        for (int i = 0; i < 4; i++) {
            if (i == 1) { mbar_wait(bar_row + FB_KEYS); mbar_wait(bar_row + FB_KDONE); tb = clock32() + RESUME; }
            if (i == 3) mbar_wait(bar_row + FB_FREE);
            const int n = ((0x0c080000 + NPRE * 256) >> (8 * i)) & 255;
            pieces(n, ((0x120c0800 + NPRE) >> (8 * i)) & 255, sb + 12288 * (((0x000c0000 + NPRE * 256) >> (8 * i)) & 255));
        }
        TSTAMP(12);
        if (isx) {
#pragma unroll 1
            for (int i = 0; i < 12; i++) {
                const int n = box_no(i);
                if (i == 6) mbar_wait(bar_row + FB_FREE + 8);
                until(tb, 0); tb += DGAP;
                if (elect()) tma2d(sb + SF_WD + n * 12288, maps + 3, 32 * (f >> 1), 2304 * (f & 1) + 192 * n, bar_row + FB_D + 8 * n);
            }
            TSTAMP(13);
        }
    } else if (warp == 13) {
        const uint32_t tag = key_tag(epoch), par = (epoch & 1) ? 0u : 0x8000u;
        stg128(kdst, 0, 0, 0, 0);
        if (lane < 8 && isx && !(f & 1)) st_rlx32(&p.s->sel[32 * f + lane], 0);
        bar_sync(BAR_R, 32 * (nrw + 1));
        TSTAMP(3);
        {
            const uint32_t sg = fresh(s_part) + 192 + lane * 4;
            const uint32_t gb = pack_bf16(sigmoidf_(rbf(__uint_as_float(lds32(sg)))), sigmoidf_(rbf(__uint_as_float(lds32(sg + 128))))) | par | (par << 16);
            asm volatile("st.relaxed.gpu.global.u16 [%0], %1;" :: "l"(p.s->gate + r0 + lane), "h"((unsigned short)gb) : "memory");
            if (nrw > 4 && lane < 16) asm volatile("st.relaxed.gpu.global.u16 [%0], %1;" :: "l"(p.s->gate + r0 + 32 + lane), "h"((unsigned short)(gb >> 16)) : "memory");
        }
        bar_sync(BAR_R2, 32 * (nrw + 1));
        {
            const uint4 v = lds128(fresh(s_tok) + (lane & 1) * 16);
            asm volatile("st.relaxed.gpu.global.v4.u32 [%0], {%1,%2,%3,%4};" :: "l"(kdst), "r"(v.x | tag), "r"(v.y | tag), "r"(v.z | tag), "r"(v.w | tag) : "memory");
        }
        TSTAMP(4);
        if (lane == 0) { mbar_arrive(bar_row + FB_KEYS); mbar_expect(bar_x, 8 * 1152); }
        if (f >= NW) return;
        mbar_wait(bar_row + FB_KDONE);
        uint32_t k[16];
        const uint4* src = p.s->keys + (f & 15) * 128 + lane;
#pragma unroll 1
        for (int it = 0;; it++) {
            uint32_t bad = 0;
#pragma unroll
            for (int i = 0; i < 4; i++) {
                const uint4 x = ld_rlx128(src + (i < 3 || lane < 24 ? 32 * i : 64));
                k[i] = x.x; k[4 + i] = x.y; k[8 + i] = x.z; k[12 + i] = x.w;
                bad |= x.x ^ tag;
            }
            const bool ok = __all_sync(0xffffffffu, (bad & 0xf800u) == 0);
            if (ok) break;
            if (it > (1 << 20)) give_up();
        }
        TSTAMP(5);
        uint32_t key = 0, m = __reduce_max_sync(0xffffffffu, max(max(k[0], k[1]), max(k[2], k[3])));
#pragma unroll 2
        for (int r = 0; r < 8; r++) {
            bool pop[4];
#pragma unroll
            for (int i = 0; i < 4; i++) { pop[i] = k[i] == m; k[i] = pop[i] ? k[4 + i] : k[i]; }
            const uint32_t mn = __reduce_max_sync(0xffffffffu, max(max(k[0], k[1]), max(k[2], k[3])));
            if (elect()) bulk_g2s(sb + SF_XS + r * 1168, p.u + (size_t)key_row(m) * DM, 1152, bar_x);
#pragma unroll
            for (int i = 0; i < 4; i++) { k[4 + i] = pop[i] ? k[8 + i] : k[4 + i]; k[8 + i] = pop[i] ? k[12 + i] : k[8 + i]; k[12 + i] = pop[i] ? 0 : k[12 + i]; }
            if (r8 == r) key = m;
            m = mn;
        }
        const int row = key_row(key);
        sts32(s_tok + r8 * 8, row);
        TSTAMP(6);
        if (isx) {
            if (!(f & 1)) {
                __nv_bfloat16* o = p.out + (size_t)row * DM + 16 * f + 8 * mi;
                asm volatile("st.relaxed.gpu.global.v4.u32 [%0], {%1,%1,%1,%1};" :: "l"(o), "r"(0) : "memory");
                if (__any_sync(0xffffffffu, ld_rlx32(o) != 0)) give_up();
                if (lane < 8) st_rlx32(&p.s->sel[32 * f + lane], key);
            } else wait_sel(p, f >> 1, r8, tag);
            uint32_t gb;
#pragma unroll 1
            for (int it = 0;; it++) {
                asm volatile("ld.relaxed.gpu.global.u16 %0, [%1];" : "=r"(gb) : "l"(p.s->gate + row) : "memory");
                gb ^= par;
                if (!(gb & 0x8000u)) break;
                if (it > (1 << 20)) give_up();
            }
            const uint32_t rb = key ^ 0x80000000u, rv = (rb ^ (((int)rb >> 31) & 0x7fff0000u)) & 0xffff0000u;
            sts32(s_tok + r8 * 8 + 4, __float_as_uint(rbf(1.0f - bf_lo(gb)) * rbf(sigmoidf_(__uint_as_float(rv)))));
            __syncwarp();
            TSTAMP(7);
            bar_arrive(BAR_RED, 416);
        }
    } else {
        if (rw < nrw) {
            float c[3][4];
#pragma unroll
            for (int i = 0; i < 3; i++) { c[i][0] = c[i][1] = c[i][2] = c[i][3] = 0.f; }
            mbar_wait(bar_row + 48); mbar_wait(bar_row + 56);
            const uint32_t b = fresh(sb + SF_WR) + (g & 1) * 1152 + (g >> 2) * 64 + t * 16 + (g & 2) * 2;
            uint32_t w[18][2];
#pragma unroll
            for (int kb = 0; kb < 18; kb++) { const uint32_t o = ((kb & 1) ? b ^ 64 : b) + 128 * (kb >> 1); w[kb][0] = lds32(o); w[kb][1] = lds32(o + 8); }
            mbar_wait(bar_row + 8 * rw);
            if (warp == 15) TSTAMP(2);
            const uint32_t a = fresh(rows) + g * 1152 + (g & 1) * 64 + t * 16;
#pragma unroll
            for (int kb = 0; kb < 18; kb++) {
                const uint4 x = lds128(((kb & 1) ? a ^ 64 : a) + 128 * (kb >> 1));
                mma_bf(c[kb % 3], x.x, x.y, x.z, x.w, w[kb][0], w[kb][1]);
            }
            const float sr = c[0][0] + c[1][0] + c[2][0] + __shfl_down_sync(0xffffffffu, c[0][2] + c[1][2] + c[2][2], 1);
            const float sg = c[0][1] + c[1][1] + c[2][1] + __shfl_down_sync(0xffffffffu, c[0][3] + c[1][3] + c[2][3], 1);
            const uint32_t rb = pack_bf16(0.f, sr);
            if (t == 2 * (g & 1)) {
                sts32(s_part + (8 * rw + g) * 4, (rb ^ (((int)rb >> 31) & 0x7fff0000u) ^ 0x80000000u) | (uint32_t)(2047 - r0 - 8 * rw - g));
                sts32(s_part + 192 + (8 * rw + g) * 4, __float_as_uint(sg));
            }
            __syncwarp();
            bar_sync(BAR_R, 32 * (nrw + 1));
            const uint32_t sk = fresh(s_part), kk = lds32(sk + (8 * rw + r8) * 4);
            int n = 0;
#pragma unroll
            for (int i = 0; i < 3; i++) { const uint4 v = lds128(sk + mi * 48 + 16 * i); n += (v.x > kk) + (v.y > kk) + (v.z > kk) + (v.w > kk); }
            n += __shfl_xor_sync(0xffffffffu, n, 8); n += __shfl_xor_sync(0xffffffffu, n, 16);
            if (n < 8) sts32(s_tok + 4 * n, kk);
            __syncwarp();
            bar_arrive(BAR_R2, 32 * (nrw + 1));
        }
    }
}

__device__ __forceinline__ void ffn_work(const Params& p, uint32_t sb, int warp, int lane, int f, unsigned epoch) {
    const int g = lane >> 2, t = lane & 3, mi = lane >> 3, r8 = lane & 7;
    const bool isx = f < NX;
    const uint32_t bar_x = sb + SF_MISC + FB_X, bar_free = sb + SF_MISC + FB_FREE, bar_w = sb + SF_MISC + FB_W, bar_d = sb + SF_MISC + FB_D, s_tok = sb + SF_MISC + FS_TOK;
    uint32_t fr[24][4];
    auto pin = [&] {
#pragma unroll
        for (int i = 0; i < 24; i += 8) asm volatile("" :: "r"(fr[i][0]), "r"(fr[i + 1][0]), "r"(fr[i + 2][0]), "r"(fr[i + 3][0]), "r"(fr[i + 4][0]), "r"(fr[i + 5][0]), "r"(fr[i + 6][0]), "r"(fr[i + 7][0]) : "memory");
    };
    {
        const int j = (unsigned)(warp - 4) < 6, w = warp - (j ? 4 : warp < 4 ? 0 : 6);
        float ag[2][4], au[2][4];
#pragma unroll
        for (int i = 0; i < 2; i++) { ag[i][0] = ag[i][1] = ag[i][2] = ag[i][3] = 0.f; au[i][0] = au[i][1] = au[i][2] = au[i][3] = 0.f; }
        const uint32_t wb = sb + (w >> 1) * 4096 + (r8 + 8 * (mi >> 1)) * 64 + (((2 * (w & 1) + (mi & 1)) ^ (r8 >> 1)) << 4);
        const uint32_t xb = sb + SF_XS + r8 * 1168 + mi * 16;
        auto load = [&](int i, int n, int place) {
            mbar_wait(bar_w + 8 * n);
            const uint32_t wk = fresh(wb) + place * 24576;
#pragma unroll
            for (int s = 0; s < 4; s++) { ldsm4t(fr[8 * i + s], wk + 1024 * s); ldsm4t(fr[8 * i + 4 + s], wk + 1024 * s + 12288); }
        };
        auto mul = [&](int i, uint32_t xk) {
            uint32_t x[2][4];
            ldsm4(x[0], xk); ldsm4(x[1], xk + 64);
#pragma unroll
            for (int s = 0; s < 4; s++) {
                const uint32_t (&a)[4] = fr[8 * i + s], (&b)[4] = fr[8 * i + 4 + s];
                mma_bf(ag[s & 1], a[0], a[1], a[2], a[3], x[s >> 1][2 * (s & 1)], x[s >> 1][2 * (s & 1) + 1]);
                mma_bf(au[s & 1], b[0], b[1], b[2], b[3], x[s >> 1][2 * (s & 1)], x[s >> 1][2 * (s & 1) + 1]);
            }
        };
#pragma unroll
        for (int i = 0; i < 3; i++) load(i, 3 * j + i, (i ? 5 : 3) * j + i);
        pin();
        bar_sync(BAR_G + j, 192);
        if (w == 0 && lane == 0) mbar_arrive(bar_free + 8 * j);
        mbar_wait(bar_x);
        stg128z_if(!j && lane < 16, (uint4*)p.s->h + (6 * f + w) * 16 + lane);
        if (warp == 0) TSTAMP(8);
        {
            const uint32_t xk = fresh(xb) + 384 * j;
#pragma unroll
            for (int i = 0; i < 3; i++) { mul(i, (i ? fresh(xk) : xk) + 128 * i); if (i == 0) { asm volatile("" :: "f"(ag[0][0]), "f"(ag[1][0]), "f"(au[0][0]), "f"(au[1][0])); sts32(s_tok + 64, clock32()); } }
        }
#pragma unroll 1
        for (int n = 6 + j; n < 9; n += 2) { load(0, n, n - 6); mul(0, fresh(xb) + 128 * n); }
#pragma unroll
        for (int c = 0; c < 4; c++) { ag[0][c] += ag[1][c]; au[0][c] += au[1][c]; }
        if (j) {
            sts128(wb + 24576, __float_as_uint(ag[0][0]), __float_as_uint(ag[0][1]), __float_as_uint(ag[0][2]), __float_as_uint(ag[0][3]));
            sts128(wb + 25600, __float_as_uint(au[0][0]), __float_as_uint(au[0][1]), __float_as_uint(au[0][2]), __float_as_uint(au[0][3]));
        }
        bar_sync(BAR_GU, 384);
        if (!j) {
            const uint32_t sf = fresh(wb);
            const uint4 g1 = lds128(sf + 24576), u1 = lds128(sf + 25600);
            const uint32_t gs[4] = {g1.x, g1.y, g1.z, g1.w}, us[4] = {u1.x, u1.y, u1.z, u1.w};
            if (warp == 0) TSTAMP(9);
            float h[4];
#pragma unroll
            for (int c = 0; c < 4; c++) {
                const float gv = rbf(ag[0][c] + __uint_as_float(gs[c]));
                h[c] = rbf(gv * sigmoidf_(gv)) * rbf(au[0][c] + __uint_as_float(us[c]));
            }
            uint32_t h0, h1;
            asm("movmatrix.sync.aligned.m8n8.trans.b16 %0, %1;" : "=r"(h0) : "r"(pack_bf16(h[0], h[1])));
            asm("movmatrix.sync.aligned.m8n8.trans.b16 %0, %1;" : "=r"(h1) : "r"(pack_bf16(h[2], h[3])));
            h0 = (h0 & 0xfffefffeu) | k_tag(epoch);
            asm volatile("{ .reg .b64 v; mov.b64 v, {%1, %2}; st.relaxed.gpu.global.b64 [%0], v; }" :: "l"(p.s->h + (6 * f + w) * 32 + lane), "r"(h0), "r"(h1) : "memory");
        }
        if (isx) {
            if (warp == 0) TSTAMP(10);
            const uint2* hsrc = p.s->h + (144 * (f & 1) + warp) * 32 + lane;
            const uint32_t wd = sb + SF_WD + warp * 1024 + (r8 + 8 * (mi >> 1)) * 64 + (((mi & 1) ^ (r8 >> 1)) << 4), we = wd ^ 32;
            uint2 hb[12];
            auto ldh = [&](int i) { asm volatile("ld.relaxed.gpu.global.v2.u32 {%0, %1}, [%2];" : "=r"(hb[i].x), "=r"(hb[i].y) : "l"(hsrc + 384 * box_no(i)) : "memory"); };
            auto ldw = [&](int i) { mbar_wait(bar_d + 8 * box_no(i)); ldsm4t(fr[2 * i], fresh(wd) + 12288 * box_no(i)); ldsm4t(fr[2 * i + 1], fresh(we) + 12288 * box_no(i)); };
#pragma unroll
            for (int i = 0; i < DPA; i++) ldw(i);
#pragma unroll
            for (int i = 0; i < 12; i++) ldh(i);
#pragma unroll
            for (int i = DPA; i < DPB; i++) ldw(i);
#pragma unroll
            for (int i = 0; i < DPB; i++) asm volatile("" :: "r"(fr[2 * i][0]), "r"(fr[2 * i + 1][0]) : "memory");
#pragma unroll 1
            for (int it = 0;; it++) {
                bool again = false;
#pragma unroll
                for (int s = 0; s < 12; s += 2) if (!__all_sync(0xffffffffu, hb[s].x & hb[s + 1].x & k_tag(epoch))) { ldh(s); ldh(s + 1); again = true; }
                if (!again) break;
                if (it > (1 << 16)) give_up();
            }
            if (warp == 0) TSTAMP(11);
            float ad[2][2][4];
#pragma unroll
            for (int i = 0; i < 4; i++) { ad[i >> 1][i & 1][0] = ad[i >> 1][i & 1][1] = ad[i >> 1][i & 1][2] = ad[i >> 1][i & 1][3] = 0.f; }
#pragma unroll
            for (int i = 0; i < 12; i++) {
                if (i >= DPB) ldw(i);
                if (i == 11 && warp == 9) TSTAMP(14);
#pragma unroll
                for (int c = 0; c < 2; c++) mma_bf(ad[c][i & 1], fr[2 * i + c][0], fr[2 * i + c][1], fr[2 * i + c][2], fr[2 * i + c][3], hb[i].x, hb[i].y);
                if (i >= DPB - 1) asm volatile("" :: "f"(ad[0][i & 1][0]), "f"(ad[1][i & 1][0]) : "memory");
            }
            const uint32_t rd = sb + SF_RED + warp * 1152 + (72 * t + g) * 4;
#pragma unroll
            for (int i = 0; i < 8; i++) sts32(rd + (i >> 2) * 64 + (i & 1) * 144 + ((i >> 1) & 1) * 32, __float_as_uint(ad[i >> 2][0][i & 3] + ad[i >> 2][1][i & 3]));
            bar_sync(BAR_RED, 416);
            if (warp < 4) {
                const int tid = 32 * warp + lane;
                const uint32_t rs = fresh(sb + SF_RED) + (tid >> 4) * 144 + (tid & 15) * 8;
                const uint2 tk = lds64(fresh(s_tok) + (tid >> 4) * 8);
                float x = 0.f, y = 0.f;
#pragma unroll
                for (int w = 0; w < 12; w++) { const uint2 v = lds64(rs + w * 1152); x += __uint_as_float(v.x); y += __uint_as_float(v.y); }
                asm volatile("red.relaxed.gpu.global.add.noftz.bf16x2 [%0], %1;" :: "l"(p.out + (size_t)tk.x * DM + 32 * (f >> 1) + 2 * (tid & 15)),
                             "r"(pack_bf16(x * __uint_as_float(tk.y), y * __uint_as_float(tk.y))) : "memory");
            }
            if (warp == 0) { TSTAMP(15); TFLUSH(); }
            asm volatile("exit;"); __builtin_unreachable();
        }
    }
}

__device__ __forceinline__ void fetch_k(const uint4* src, uint64_t (&v)[4], uint32_t a, uint32_t b) {
    asm volatile("{ .reg .pred p; setp.eq.u32 p, %5, %6; @p ld.relaxed.gpu.global.v2.u64 {%0,%1}, [%4]; @p ld.relaxed.gpu.global.v2.u64 {%2,%3}, [%4 + 512]; }"
                 : "+l"(v[0]), "+l"(v[1]), "+l"(v[2]), "+l"(v[3]) : "l"(src), "r"(a), "r"(b));
}
__device__ __forceinline__ uint32_t mini_conv(const Params& p, uint32_t sb, int warp, int lane, int f, unsigned epoch, uint64_t (&v)[4]) {
    const int g = lane >> 2, t = lane & 3, mi = lane >> 3, r8 = lane & 7;
    const uint32_t fb = sb + SF_MISC, kt = sb + (warp >= 12 ? SM_KT - 12 * 2112 : f < NW ? SM_KW + 2 * 2112 : SM_KW) + warp * 2112;
    const bool ism = f >= NW;
    const uint32_t* const sel = &p.s->sel[((mini_ch0(f) + (ism ? 2 * (warp & 8) : 0)) >> 5) * 64 + r8];
    uint32_t seq = 128, key;
    const uint4* src = p.s->kp + lane;
    auto hi = [&](int i) { return (uint32_t)(v[i] >> 32); };
    if (f >= (warp < 4 ? NW : NX)) {
    {
        const uint32_t c = 68 + (warp & 3) + 2 * (warp & 12), y = ((uint32_t)((warp < 8 ? 0xe066806400000000ull : 0x5a6e00680080e26cull) >> ((8 * warp) & 48)) & 0xffff) + (warp < 14 ? 0 : 0x6a0000);
        seq = !ism ? y + (warp & 1) * ((y >> 6) & 0x10101) : warp < 14 ? 0x101 * c - 0x400 : c;
        src += (48 * (f - (ism ? NW : NX)) + (seq & 63)) * 96;
    }
    if (seq & 64) {
        if (seq & 4) {
            const int q = (seq & 3) + ((seq >> 1) & 4);
            const uint32_t ab = sb - 3072 * (seq & 16), d = ab + SM_UT + g * MU_STRIDE + (4 + 4 * q + t) * 32;
            asm volatile("st.shared.v2.u32 [%0], {%1,%1};" :: "r"(ab + SM_UT + (2 * q + (mi >> 1)) * MU_STRIDE + (lane & 15) * 8), "r"(0) : "memory");
            mbar_wait(fb + FB_MU - (seq & 16) / 2);
            if (warp == 15) TSTAMP(16);
            const uint32_t a = fresh(ab + SM_RAW) + q * 2048 + (8 * mi + 4 * (r8 & 1) + (r8 >> 1)) * 32 + ((r8 & 1) << 4);
            uint32_t x[4][4];
#pragma unroll
            for (int i = 0; i < 4; i++) ldsm4t(x[i], (i & 2 ? a ^ 16 : a) + 1024 * (i & 1));
#pragma unroll
            for (int i = 0; i < 4; i++) sts128(d + (i & 1) * 16 + (i & 2) * 4 * MU_STRIDE, x[i][0], x[i][1], x[i][2], x[i][3]);
            __syncwarp();
            if (lane == 0) mbar_arrive(fb + FB_MT + (seq & 16) / 2);
        }
        mbar_wait(fb + FB_KDONE);
        fetch_k(src, v, warp < 4, 0);
        if ((warp | 2) == 7) { fetch_gates(p, (warp >> 1) & 1, lane, epoch, sb + SM_G + 256 * (warp & 2) + 16 * lane); __syncwarp(); if (lane == 0) mbar_arrive(fb + FB_MG); }
        if (warp >= 8) {
            mbar_wait(fb + FB_KEYS); mbar_wait(fb + FB_MT);
            if (ism) {
                asm volatile("barrier.cluster.wait.aligned; fence.release.sync_restrict::shared::cta.cluster;" ::: "memory");
                if (lane == 0) asm volatile("mbarrier.arrive.relaxed.cluster.shared::cluster.b64 _, [%0];" :: "r"(mapa(fb + FB_MT + 8, 0)) : "memory");
            }
        }
        if (warp == TW) TSTAMP(17);
    }
    }
    const uint32_t lo = (8 + r8 - (mi & 1)) * 16 + (mi >> 1) * 128;
#pragma unroll 1
    do {
        const int c = seq & 63;
        const bool far = !ism && (seq & 16);
        const uint32_t ab = sb - 3072 * (c & 16);
        uint32_t ut = ab + SM_UT + (c & 15) * MU_STRIDE;
        if (seq & 64) {
        if (far) {
            mbar_wait_cluster(fb + FB_MT + 8);
            const uint32_t ru = mapa(ut, 1) + lane * 16;
            ut = sb + SM_FT + (c & 3) * 1536;
            uint4 x[3];
#pragma unroll
            for (int i = 0; i < 3; i++) asm volatile("ld.shared::cluster.v4.u32 {%0,%1,%2,%3}, [%4];" : "=r"(x[i].x), "=r"(x[i].y), "=r"(x[i].z), "=r"(x[i].w) : "r"(ru + 512 * i) : "memory");
#pragma unroll
            for (int i = 0; i < 3; i++) sts128(ut + lane * 16 + 512 * i, x[i].x, x[i].y, x[i].z, x[i].w);
        } else mbar_wait(fb + FB_MT + (seq & 16) / 2);
#pragma unroll 1
        for (int it = 0; !__all_sync(0xffffffffu, hi(1) & hi(3) & k_tag(epoch)); it++) {
            fetch_k(src, v, 0, 0);
            if (it > (1 << 20)) give_up();
        }
        sts128(kt + t * 16, 0, 0, 0, 0);
        if (warp == TW) TSTAMP(seq >> 8 ? 7 : 10);
        const uint32_t w[12] = {(uint32_t)v[0], hi(0), (uint32_t)v[1], hi(1), (uint32_t)v[2], hi(2), (uint32_t)v[3], hi(3), 0, 0, 0, 0};
        k_tables<false>(fresh(kt), fresh(lane), w);
        }
        __syncwarp();
        if (seq & 128) ffn_work(p, sb, warp, fresh(lane), f, epoch);
        if (!(seq & 64)) return 0;
        const uint32_t kb = fresh(kt) + (16 + g - 2 * t) * 4, ub = fresh(ut);
        const uint32_t yd = ab + SM_Y + (c & 15) * 1056 + (c & 8) * 8 + lane * 16;
        if (warp == TW && !(seq >> 8)) TSTAMP(13);
        seq >>= 8;
        src += ((int)(seq & 63) - c) * 96;
#pragma unroll
        for (int i = 0; i < 4; i++) v[i] = 0;
        key = 0;
        float acc[8][4];
#pragma unroll
        for (int i = 0; i < 8; i++) { acc[i][0] = acc[i][1] = acc[i][2] = acc[i][3] = 0.f; }
        uint32_t a[4][4], b[2][4][4];
        auto lda = [&](int j, int s) { const uint32_t x = kb + 64 * s + 512 * j; a[j][0] = lds32(x); a[j][1] = lds32(x + 256); a[j][2] = lds32(x + 32); a[j][3] = lds32(x + 288); };
        auto ldb = [&](int i, int s) { ldsm4(b[s & 1][i], ub + lo + 256 * i - 32 * s); };
#pragma unroll
        for (int j = 0; j < 4; j++) { ldb(j, 0); lda(j, 0); }
#pragma unroll
        for (int s = 0; s < 4; s++) {
            if (s == 2) {
                const uint32_t e = seq | (__float_as_uint(acc[0][0]) & p.zero);
                fetch_k(src, v, e & 64, 64);
                asm volatile("{ .reg .pred p; setp.eq.u32 p, %2, 0; @p ld.relaxed.gpu.global.u32 %0, [%1]; }" : "+r"(key) : "l"(sel), "r"(e));
            }
#pragma unroll
            for (int i = 0; i < 4; i++) {
                const int j = (i >> 1) + 2 * (i & 1);
                if (s < 3) ldb(i, s + 1);
#pragma unroll
                for (int mu = 0; mu < 8; mu++) if (mu + 2 * j < 8) mma_bf(acc[mu + 2 * j], a[j][0], a[j][1], a[j][2], a[j][3], b[s & 1][mu >> 1][2 * (mu & 1)], b[s & 1][mu >> 1][2 * (mu & 1) + 1]);
                if (s < 3) lda(j, s + 1);
            }
        }
        if (warp == TW && !seq) TSTAMP(14);
        mbar_wait(fb + FB_MG);
        uint32_t ug[4][4];
#pragma unroll
        for (int i = 0; i < 2; i++) { ldsm4t(ug[i], ub + 128 + lane * 16 + 512 * i); ldsm4t(ug[2 + i], fresh(sb + SM_G) + lane * 16 + 512 * i); }
#pragma unroll
        for (int x = 0; x < 8; x++) ug[x >> 2][x & 3] = gmix(ug[2 + (x >> 2)][x & 3], x ? acc[x][0] + acc[x - 1][2] : acc[0][0], x ? acc[x][1] + acc[x - 1][3] : acc[0][1], ug[x >> 2][x & 3]);
        if (far) for (int i = 0; i < 2; i++) st_async128(mapa(yd, 1) + 512 * i, ug[i][0], ug[i][1], ug[i][2], ug[i][3], mapa(fb + FB_FAR, 1));
        else for (int i = 0; i < 2; i++) sts128(yd + 512 * i, ug[i][0], ug[i][1], ug[i][2], ug[i][3]);
        __syncwarp();
        if (warp == TW) TSTAMP(18 + (seq != 0));
    } while (seq);
    if (warp >= 12) TSTAMP(12 + warp);
    return key;
}
__device__ __forceinline__ void mini_out(const Params& p, const CUtensorMap* maps, uint32_t sb, int warp, int lane, int f, unsigned epoch, uint32_t key) {
    const int g = lane >> 2, t = lane & 3, mi = lane >> 3, r8 = lane & 7;
    const uint32_t fb = sb + SF_MISC;
    const bool ism = f >= NW;
    const int ch0 = mini_ch0(f);
    const int k = ism ? warp >> 3 : 0;
    uint32_t first = 1;
    if (lane == 0) asm volatile("atom.shared.exch.b32 %0, [%1], 1;" : "=r"(first) : "r"(fb + FS_BM + 64 + 4 * k) : "memory");
    if (!__all_sync(0xffffffffu, first)) {
        if (elect()) prefetch_map(maps + 6);
        const int row = key_row(wait_sel(p, (ch0 + 16 * k) >> 5, r8, key_tag(epoch), key));
        if (row < 512) asm volatile("red.shared.or.b32 [%0], %1;" :: "r"(fb + FS_BM + (row >> 5) * 4), "r"(1u << (row & 31)) : "memory");
        if (k) mbar_wait_cluster(fb + FB_FAR);
    }
    const int m = warp & 7, dr = 64 * (g >> 1) + 16 * (t >> 1) + 8 * (g & 1);
    const uint32_t y = SM_Y + ((r8 >> 1) & 1) * 8512 + (2 * mi + (r8 & 1)) * 1056 + (2 * m + (r8 >> 2)) * 16;
    const uint32_t so = (g >> 1) * 128 + (t >> 1) * 64 + (g & 1) * 32 + (t & 1) * 16;
    bar_sync(BAR_M - k, ism ? 256 : NTHR);
#pragma unroll 1
    for (int h = ism ? 0 : warp >> 3;; h++) {
        const int r0 = 256 * h + 32 * (m & 1) + (m >> 1), row = r0 + dr;
        const uint32_t bm = lds32(fresh(fb) + FS_BM + (row >> 5) * 4) >> (row & 31), ab = fresh(sb - 49152 * k + 512 * h), stg = ab + SM_UT + 2048 * m + 512 * h;
        uint32_t x[2][4];
        ldsm4t(x[0], ab + y); ldsm4t(x[1], ab + y + 256);
        if (warp == 0 && x[0][0] != 0x12345) TSTAMP(28);
        if (__any_sync(0xffffffffu, bm & 0x11u)) {
#pragma unroll
            for (int i = 0; i < 2; i++) store_or_add(p.out + (size_t)(row + 4 * i) * DM + ch0 + 16 * k + 8 * (t & 1), x[i], bm & (1u << (4 * i)));
        } else {
#pragma unroll
            for (int i = 0; i < 2; i++) sts128(stg + so + 512 * i, x[i][0], x[i][1], x[i][2], x[i][3]);
            asm volatile("fence.proxy.async.shared::cta;" ::: "memory");
            __syncwarp();
            if (elect()) store_rows(maps + 6, stg, ch0 + 16 * k, r0);
        }
        if (h >= ism) break;
    }
    if (elect()) { asm volatile("cp.async.bulk.commit_group;" ::: "memory"); asm volatile("cp.async.bulk.wait_group.read 0;" ::: "memory"); }
    if (warp == 8) TSTAMP(11);
    if (warp == 0) { TSTAMP(15); TFLUSH(); }
}

constexpr int SMEM_BYTES = 232448;
static_assert(SF_MISC + 1152 <= 232192, "layout");

struct Maps { CUtensorMap m[7]; };

__global__ void __cluster_dims__(2, 1, 1) __launch_bounds__(NTHR, 1)
fused_kernel(const Params p, const __grid_constant__ Maps maps) {
    extern __shared__ __align__(1024) uint8_t smem_raw[];
    uint32_t q[8];
    {
        const int b = role(blockIdx.x), x = threadIdx.x, rc = 5 * b + (b & ~3) + 4 + (x >> 6);
        const int cv = (unsigned)b < NW ? 0 : -1, ca = (b < 0 ? 8 * b + DM : 48 * b - 2300) + ((x >> 5) & 3), cb = 2 * rc - (rc & 3) + 4;
        const uint32_t ch = (ca & cv) | (cb & ~cv), o = NST * ch + 2 * ((x & 31) + ((x >> (cv & 2)) & 32));
        const bool c = x < (cv ? 256 : 320);
        q[6] = ldg16_if(c, p.logdt + ch);
        q[2] = ldg32_if(c, p.Bre + o); q[3] = ldg32_if(c, p.Bim + o); q[4] = ldg32_if(c, p.Cre + o); q[5] = ldg32_if(c, p.Cim + o); q[0] = ldg32_if(c, p.Are + o); q[1] = ldg32_if(c, p.Aim + o);
        q[7] = ldg16_if(c, p.Dskip + ch);
    }
    const unsigned epoch = ld_rlx32(&p.s->epoch[blockIdx.x * 16 + (threadIdx.x >> 5)]);
    const uint32_t sb = __shfl_sync(0xffffffffu, smem_u32(smem_raw), 0);
    const int warp = __shfl_sync(0xffffffffu, threadIdx.x >> 5, 0), bid = __shfl_sync(0xffffffffu, blockIdx.x, 0);
    const int lane = __shfl_sync(0xffffffffu, threadIdx.x & 31, threadIdx.x);
    const bool conv = bid < NCONV;
    const int f = role(bid);
    uint32_t w[12];
    uint64_t v[4];
    const bool four = (unsigned)f >= NW;
    if (warp < (four ? 8 : 10)) {
        const int half = four ? warp >> 2 : warp & 1, pr = four ? warp & 3 : warp >> 1;
        const int rc = 5 * f + (f & ~3) + 4 + pr;
        const uint32_t stage = sb + (conv ? SC_KG : SF_KG) + warp * KG_STAGE;
        uint4* const kp = p.s->kp + (four ? (conv ? 8 * bid : 48 * f - 2300) + pr : 2 * rc - (rc & 3) + 4) * 96 + lane;
        kgen(q, sb, half, stage, stage + (four ? 4 : 1) * KG_STAGE, 1 + pr, lane, w, [&] {
            sts128z_if(conv && lane < 20, sb + SC_KT + warp * KT_BYTES + lane * 16 + (lane < 4 ? 0 : lane < 14 ? 2048 : 2288));
            if (!conv) bar_sync(0, NTHR);
            if ((unsigned)f >= NX) asm volatile("barrier.cluster.arrive.relaxed.aligned;" ::: "memory");
        }, [&] {
            asm volatile("{ .reg .pred p, q; setp.ne.u32 p, %2, 0; setp.ne.and.u32 q, %3, 0, p; @p st.global.v4.u32 [%0], {%1,%1,%1,%1}; @q st.global.v4.u32 [%0 + 512], {%1,%1,%1,%1}; }"
                         :: "l"(kp + 32 * half), "r"(0), "r"((uint32_t)!conv), "r"((uint32_t)(half && lane < 18)) : "memory");
        });
        if (!half) publish_k(kp, lane, !conv, w, epoch, v);
        else for (int i = 0; i < 4; i++) v[i] = 0;
        if (conv) { conv_main(p, sb, warp, lane, bid, epoch, w); return; }
        {
            if (!half && lane == 0) mbar_arrive(sb + SF_MISC + FB_KDONE);
            if (warp == 0) TSTAMP(22);
            if (warp == 2) TSTAMP(23);
        }
    } else if (conv) {
        conv_aux(p, maps.m, sb, warp - 8, lane, bid, epoch);
        return;
    } else {
        ffn_front(p, maps.m, sb, warp, lane, f, epoch);
        for (int i = 0; i < 4; i++) v[i] = 0;
    }
    converged();
    next_epoch(p, epoch);
    if (warp >= 12 && f < NX) return;
    mini_out(p, maps.m, sb, warp, lane, f, epoch, mini_conv(p, sb, warp, __shfl_sync(0xffffffffu, lane, lane), f, epoch, v));
}

typedef CUresult (*EncodeFn)(CUtensorMap*, CUtensorMapDataType, cuuint32_t, void*, const cuuint64_t*, const cuuint64_t*, const cuuint32_t*, const cuuint32_t*,
                             CUtensorMapInterleave, CUtensorMapSwizzle, CUtensorMapL2promotion, CUtensorMapFloatOOBfill);

void make_map(EncodeFn fn, CUtensorMap* m, const void* base, int rank, const cuuint64_t* dims, const cuuint64_t* strides, const cuuint32_t* box, CUtensorMapSwizzle sw) {
    const cuuint32_t es[5] = {1, 1, 1, 1, 1};
    fn(m, CU_TENSOR_MAP_DATA_TYPE_BFLOAT16, rank, (void*)base, dims, strides, box, es, CU_TENSOR_MAP_INTERLEAVE_NONE, sw,
       CU_TENSOR_MAP_L2_PROMOTION_NONE, CU_TENSOR_MAP_FLOAT_OOB_FILL_NONE);
}

}

extern "C" void kernel_launch(void* const* d_in, const int* in_sizes, int n_in, void* d_out, int out_size) {
    (void)in_sizes; (void)n_in; (void)out_size;
    static EncodeFn fn = nullptr;
    static void* scratch = nullptr;
    if (!fn) {
        void* ptr = nullptr; cudaDriverEntryPointQueryResult qr;
        cudaGetDriverEntryPoint("cuTensorMapEncodeTiled", &ptr, cudaEnableDefault, &qr);
        fn = (EncodeFn)ptr;
        cudaGetSymbolAddress(&scratch, g_scratch);
        cudaFuncSetAttribute(fused_kernel, cudaFuncAttributeMaxDynamicSharedMemorySize, SMEM_BYTES);
    }
    typedef const __nv_bfloat16* bp;
    Params p;
    p.u = (bp)d_in[0]; p.Are = (bp)d_in[1]; p.Aim = (bp)d_in[2]; p.Bre = (bp)d_in[3]; p.Bim = (bp)d_in[4]; p.Cre = (bp)d_in[5]; p.Cim = (bp)d_in[6];
    p.logdt = (bp)d_in[7]; p.Dskip = (bp)d_in[8]; p.wr = (bp)d_in[10]; p.gatew = (bp)d_in[14];
    p.out = (__nv_bfloat16*)d_out; p.s = (Scratch*)scratch; p.zero = 0;
    Maps maps;
    {
        const cuuint64_t dims[4] = {DM, 4, 16, 32}, strides[3] = {16 * DM * 2, DM * 2, 64 * DM * 2};
        const cuuint32_t box[4] = {16, 4, 16, 2};
        make_map(fn, &maps.m[0], d_in[0], 4, dims, strides, box, CU_TENSOR_MAP_SWIZZLE_32B);
        const cuuint32_t box2[4] = {16, 4, 16, 8};
        make_map(fn, &maps.m[5], d_in[0], 4, dims, strides, box2, CU_TENSOR_MAP_SWIZZLE_32B);
    }
    for (int i = 0; i < 2; i++) {
        const cuuint64_t dims[3] = {32, DM, FF / 32}, strides[2] = {FF * 2, 64};
        const cuuint32_t box[3] = {32, 64, 3};
        make_map(fn, &maps.m[1 + i], d_in[11 + i], 3, dims, strides, box, CU_TENSOR_MAP_SWIZZLE_64B);
    }
    {
        const cuuint64_t dims[2] = {DM, FF}, strides[1] = {DM * 2};
        const cuuint32_t box[2] = {32, 192};
        make_map(fn, &maps.m[3], d_in[13], 2, dims, strides, box, CU_TENSOR_MAP_SWIZZLE_64B);
    }
    {
        const cuuint64_t dims[5] = {DM, 2, 4, 4, L_SEQ}, strides[4] = {16 * DM * 2, 64 * DM * 2, 4 * DM * 2, DM * 2};
        const cuuint32_t box[5] = {16, 2, 4, 4, 1};
        make_map(fn, &maps.m[4], d_out, 5, dims, strides, box, CU_TENSOR_MAP_SWIZZLE_NONE);
    }
    {
        const cuuint64_t dims[5] = {DM, 4, 4, 2, L_SEQ}, strides[4] = {8 * DM * 2, 64 * DM * 2, 4 * DM * 2, DM * 2};
        const cuuint32_t box[5] = {16, 4, 4, 2, 1};
        make_map(fn, &maps.m[6], d_out, 5, dims, strides, box, CU_TENSOR_MAP_SWIZZLE_NONE);
    }
    fused_kernel<<<NCTA, NTHR, SMEM_BYTES>>>(p, maps);
}
```
